```python
import torch

def _softmax(x, axis=-1):
    return torch.softmax(x, dim=axis)
def _gelu(x):
    return torch.nn.functional.gelu(x, approximate="tanh")
def _silu(x):
    return torch.nn.functional.silu(x)
def _sigmoid(x):
    return torch.sigmoid(x)
def _layernorm(x, axis=-1, eps=1e-5):
    m = x.mean(dim=axis, keepdim=True)
    v = x.var(dim=axis, keepdim=True, unbiased=False)
    return (x - m) / torch.sqrt(v + eps)
def _scatter_add(tgt, idx, src, axis=0):
    return tgt.clone().index_add_(axis, idx, src)
def _segment_sum(src, seg, n):
    out = torch.zeros((n,) + src.shape[1:], dtype=src.dtype)
    return out.index_add_(0, seg, src)
def _pad(x, pw):
    flat = tuple(v for pair in reversed(pw) for v in pair)
    return torch.nn.functional.pad(x, flat)

kernel_name = 'concat_heads__ssm_conv_h3__sliding_local_dilated__prompt'

def setup_inputs():

    _w = (lambda a: (lambda t: t.to(torch.bfloat16) if t.is_floating_point() else t)(torch.as_tensor(a)))
    def _A_setup():
        B, S, D = 1, 2048, 1024
        ks = 4
        return {
            "q": _w((lambda *s: torch.randn(*s, dtype=torch.bfloat16) * 0.05)(B, S, D)),
            "k": _w((lambda *s: torch.randn(*s, dtype=torch.bfloat16) * 1.6)(B, S, D)),
            "v": _w((lambda *s: torch.randn(*s, dtype=torch.bfloat16) * 0.8)(B, S, D)),
            "shift_k": _w((lambda *s: torch.randn(*s, dtype=torch.bfloat16) * 1.6)(D, ks) * 0.5),
            "ssm_k": _w((lambda *s: torch.randn(*s, dtype=torch.bfloat16) * 1.6)(D, S) * (1.0 / S ** 0.5)),
            "ssm_D": _w((lambda *s: torch.randn(*s, dtype=torch.bfloat16) * 0.8)(D)),
        }
    _A_in = _A_setup()

    def _B_setup():
        B, S, D = 1, 2048, 1024
        return {
            "x": _w((lambda *s: torch.randn(*s, dtype=torch.bfloat16) * 0.2)(B, S, D)),
            "wqkv": _w((lambda *s: torch.randn(*s, dtype=torch.bfloat16) * 0.2)(D, 3 * D)),
            "wo": _w((lambda *s: torch.randn(*s, dtype=torch.bfloat16) * 0.05)(D, D)),
        }
    _B_in = _B_setup()

    return {
        "A_q": _A_in["q"],
        "A_k": _A_in["k"],
        "A_v": _A_in["v"],
        "A_shift_k": _A_in["shift_k"],
        "A_ssm_k": _A_in["ssm_k"],
        "A_ssm_D": _A_in["ssm_D"],
        "B_x": _B_in["x"],
        "B_wqkv": _B_in["wqkv"],
        "B_wo": _B_in["wo"],
    }

def reference(A_q, A_k, A_v, A_shift_k, A_ssm_k, A_ssm_D, B_x, B_wqkv, B_wo):
    def _A_ref(q, k, v, shift_k, ssm_k, ssm_D):
        B, S, D = q.shape
        ks = shift_k.shape[-1]
        k_pad = _pad(k, ((0, 0), (ks - 1, 0), (0, 0)))
        k_shift = torch.zeros_like(k)
        for t in range(ks):
            k_shift = k_shift + k_pad[:, t:t + S, :] * shift_k[:, ks - 1 - t][None, None, :]
        kv = k_shift * v
        L = 2 * S
        kv_pad = _pad(kv, ((0, 0), (0, S), (0, 0)))
        kf_pad = _pad(ssm_k, ((0, 0), (0, S)))
        kv_f = (lambda x, axes=(-2,-1): torch.fft.rfft2(x.float(), dim=axes))(kv_pad[:, None, :, :], axes=(1, 2))
        kf_f = (lambda x, axes=(-2,-1): torch.fft.rfft2(x.float(), dim=axes))(kf_pad[:, None, :], axes=(1, 2))
        kf_f = (lambda x, *d: x.permute(*d))(kf_f, 1, 2, 0)
        y_f = kv_f * kf_f[None, :, :, :]
        y = (lambda x, s, axes=(-2,-1): torch.fft.irfft2(x, s=s, dim=axes).to(torch.bfloat16))(y_f, (1, L), axes=(1, 2))[:, 0, :S, :]
        y = y + kv * ssm_D[None, None, :]
        return q * y

    def _B_ref(x, wqkv, wo):
        B, S, D = x.shape
        H = 32; Dh = D // H
        W, dil = 8, 2
        qkv = (lambda x, *d: x.permute(*d))((x @ wqkv).reshape(B, S, 3, H, Dh), 2, 0, 3, 1, 4)
        q, k, v = qkv[0], qkv[1], qkv[2]
        scale = Dh ** -0.5
        pos = torch.arange(S)
        off = torch.arange(W) * dil
        idx = pos[:, None] - off[None, :]
        mask = idx >= 0
        idx_c = torch.where(mask, idx, 0).reshape(-1)
        kg = k[:, :, idx_c, :].reshape(B, H, S, W, Dh)
        vg = v[:, :, idx_c, :].reshape(B, H, S, W, Dh)
        logits = torch.einsum("bhsd,bhswd->bhsw", q, kg) * scale
        logits = torch.where(mask[None, None, :, :], logits, -1e9)
        attn = _softmax(logits, axis=-1)
        o = torch.einsum("bhsw,bhswd->bhsd", attn, vg)
        return (lambda x, *d: x.permute(*d))(o, 0, 2, 1, 3).reshape(B, S, D) @ wo

    a = _A_ref(A_q, A_k, A_v, A_shift_k, A_ssm_k, A_ssm_D)
    b = _B_ref(B_x, B_wqkv, B_wo)
    return torch.concatenate([a, b], axis=-1)
```

```cpp
#include <cuda_runtime.h>
#include <cuda.h>
#include <cuda_bf16.h>
#include <stdint.h>

namespace {

constexpr int SEQ = 2048;
constexpr int DM = 1024;
constexpr int NCTA = 132;
constexpr int NTHREADS = 384;

constexpr int STG1A = 32768;
constexpr int NS1A = 3;
constexpr int STG1B = 12288;
constexpr int NS1B = 5;
constexpr int OFF_1B = NS1A * STG1A;
constexpr int STG2 = 32768;
constexpr int NS2 = 5;
#define G2SEQ 0x0432104321043210ull
#define ILV 2
#define ENDG 5
constexpr unsigned long long G2_STAGE = G2SEQ;
__host__ __device__ constexpr int g2_stage(int kb) { return (int)(G2_STAGE >> (4 * kb)) & 7; }
constexpr unsigned g2_bits(bool reuse) {
  unsigned r = 0;
  for (int kb = 0; kb < 16; kb++) {
    int n = 0;
    for (int j = reuse ? kb + 1 : 0; j < (reuse ? 16 : kb); j++) n += g2_stage(j) == g2_stage(kb);
    r |= (unsigned)(reuse ? n > 0 : n & 1) << kb;
  }
  return r;
}
constexpr unsigned G2_PARITY = g2_bits(false);
constexpr unsigned G2_REUSE = g2_bits(true);
constexpr int STGH = 73728;
constexpr int OFF_KH = 1 * STG2;
constexpr int OFF_OP = 2 * STG2;
constexpr int OFF_TAB = NS2 * STG2 - 8192;
constexpr int OFF_X = NS2 * STG2;
constexpr int XT = 8192;
constexpr int OFF_BAR = OFF_X + 8 * XT;
constexpr int OFF_EX = OFF_BAR + 384;
constexpr int OFF_L0 = 230400;
constexpr int SMEM_BYTES = OFF_L0 + 2048;
static_assert(OFF_TAB >= OFF_1B + 2 * STG1B && OFF_1B + NS1B * STG1B <= OFF_X && OFF_X % 1024 == 0, "layout");
static_assert(3 * STGH <= OFF_BAR && OFF_EX + 64 <= OFF_L0 && SMEM_BYTES <= 232448, "smem");

constexpr int BAR_FULLA = 0;
constexpr int BAR_EMPTYA = 3;
constexpr int BAR_FULLB = 6;
constexpr int BAR_EMPTYB = 11;
constexpr int BAR_FULL2 = 16;
constexpr int BAR_EMPTY2 = 21;
constexpr int BAR_X = 26;
constexpr int BAR_LAND = 27;
constexpr int BAR_U = 29;
constexpr int BAR_Q = 30;
constexpr int BAR_STG = 31;
constexpr int BAR_Y = 32;
constexpr int BAR_HALO = 40;

constexpr int NB_G1DONE = 1;
constexpr int NB_OREADY = 4;
constexpr int NB_CONV = 5;
constexpr int NB_HELP3 = 11;
constexpr int NB_FIRST = 13;

#define REG_MATH 224
#define REG_HELP 56
constexpr int SPIN_LIMIT = 1 << 20;

__device__ __align__(1024) __nv_bfloat16 g_o[SEQ * DM];
__device__ uint32_t g_flag_o[128];
__device__ uint32_t g_flag_h[4];
__device__ uint4 g_halo[128 * 128];
__device__ __align__(128) const uint32_t g_tab[2048] = {
  0x3c003c00,0x3c003c00,0x3c003c00,0x3c003c00,0x3b643c00,0x361f39a8,0xb61f0000,0xbb64b9a8,0x39a83c00,0xb9a80000,0xb9a8bc00,0x39a80000,
  0x361f3c00,0xbb64b9a8,0x3b640000,0xb61f39a8,0x3c00,0xbc00,0x3c00,0xbc00,0xb61f3c00,0x3b64b9a8,0xbb640000,0x361f39a8,
  0xb9a83c00,0x39a80000,0x39a8bc00,0xb9a80000,0xbb643c00,0xb61f39a8,0x361f0000,0x3b64b9a8,0x0,0x0,0x0,0x0,
  0xb61f0000,0xbb64b9a8,0xbb64bc00,0xb61fb9a8,0xb9a80000,0xb9a8bc00,0x39a80000,0x39a83c00,0xbb640000,0x361fb9a8,0x361f3c00,0xbb64b9a8,
  0xbc000000,0x3c000000,0xbc000000,0x3c000000,0xbb640000,0x361f39a8,0x361fbc00,0xbb6439a8,0xb9a80000,0xb9a83c00,0x39a80000,0x39a8bc00,
  0xb61f0000,0xbb6439a8,0xbb643c00,0xb61f39a8,0x0,0x0,0x0,0x0,0x361f0000,0x3b6439a8,0x3b643c00,0x361f39a8,
  0x39a80000,0x39a83c00,0xb9a80000,0xb9a8bc00,0x3b640000,0xb61f39a8,0xb61fbc00,0x3b6439a8,0x3c000000,0xbc000000,0x3c000000,0xbc000000,
  0x3b640000,0xb61fb9a8,0xb61f3c00,0x3b64b9a8,0x39a80000,0x39a8bc00,0xb9a80000,0xb9a83c00,0x361f0000,0x3b64b9a8,0x3b64bc00,0x361fb9a8,
  0x3c003c00,0x3c003c00,0x3c003c00,0x3c003c00,0x3b643c00,0x361f39a8,0xb61f0000,0xbb64b9a8,0x39a83c00,0xb9a80000,0xb9a8bc00,0x39a80000,
  0x361f3c00,0xbb64b9a8,0x3b640000,0xb61f39a8,0x3c00,0xbc00,0x3c00,0xbc00,0xb61f3c00,0x3b64b9a8,0xbb640000,0x361f39a8,
  0xb9a83c00,0x39a80000,0x39a8bc00,0xb9a80000,0xbb643c00,0xb61f39a8,0x361f0000,0x3b64b9a8,0xbc003c00,0xbc003c00,0xbc003c00,0xbc003c00,
  0xbb643c00,0xb61f39a8,0x361f0000,0x3b64b9a8,0xb9a83c00,0x39a80000,0x39a8bc00,0xb9a80000,0xb61f3c00,0x3b64b9a8,0xbb640000,0x361f39a8,
  0x3c00,0xbc00,0x3c00,0xbc00,0x361f3c00,0xbb64b9a8,0x3b640000,0xb61f39a8,0x39a83c00,0xb9a80000,0xb9a8bc00,0x39a80000,
  0x3b643c00,0x361f39a8,0xb61f0000,0xbb64b9a8,0x0,0x0,0x0,0x0,0x361f0000,0x3b64b9a8,0x3b64bc00,0x361fb9a8,
  0x39a80000,0x39a8bc00,0xb9a80000,0xb9a83c00,0x3b640000,0xb61fb9a8,0xb61f3c00,0x3b64b9a8,0x3c000000,0xbc000000,0x3c000000,0xbc000000,
  0x3b640000,0xb61f39a8,0xb61fbc00,0x3b6439a8,0x39a80000,0x39a83c00,0xb9a80000,0xb9a8bc00,0x361f0000,0x3b6439a8,0x3b643c00,0x361f39a8,
  0x0,0x0,0x0,0x0,0xb61f0000,0xbb6439a8,0xbb643c00,0xb61f39a8,0xb9a80000,0xb9a83c00,0x39a80000,0x39a8bc00,
  0xbb640000,0x361f39a8,0x361fbc00,0xbb6439a8,0xbc000000,0x3c000000,0xbc000000,0x3c000000,0xbb640000,0x361fb9a8,0x361f3c00,0xbb64b9a8,
  0xb9a80000,0xb9a8bc00,0x39a80000,0x39a83c00,0xb61f0000,0xbb64b9a8,0xbb64bc00,0xb61fb9a8,0xbc003c00,0xbc003c00,0xbc003c00,0xbc003c00,
  0xbb643c00,0xb61f39a8,0x361f0000,0x3b64b9a8,0xb9a83c00,0x39a80000,0x39a8bc00,0xb9a80000,0xb61f3c00,0x3b64b9a8,0xbb640000,0x361f39a8,
  0x3c00,0xbc00,0x3c00,0xbc00,0x361f3c00,0xbb64b9a8,0x3b640000,0xb61f39a8,0x39a83c00,0xb9a80000,0xb9a8bc00,0x39a80000,
  0x3b643c00,0x361f39a8,0xb61f0000,0xbb64b9a8,0x3c003c00,0x3c003c00,0x3c003c00,0x3c003c00,0xbb64bc00,0xb61fb9a8,0x361f0000,0x3b6439a8,
  0x39a83c00,0xb9a80000,0xb9a8bc00,0x39a80000,0xb61fbc00,0x3b6439a8,0xbb640000,0x361fb9a8,0x3c00,0xbc00,0x3c00,0xbc00,
  0x361fbc00,0xbb6439a8,0x3b640000,0xb61fb9a8,0xb9a83c00,0x39a80000,0x39a8bc00,0xb9a80000,0x3b64bc00,0x361fb9a8,0xb61f0000,0xbb6439a8,
  0x0,0x0,0x0,0x0,0x361f0000,0x3b6439a8,0x3b643c00,0x361f39a8,0xb9a80000,0xb9a8bc00,0x39a80000,0x39a83c00,
  0x3b640000,0xb61f39a8,0xb61fbc00,0x3b6439a8,0xbc000000,0x3c000000,0xbc000000,0x3c000000,0x3b640000,0xb61fb9a8,0xb61f3c00,0x3b64b9a8,
  0xb9a80000,0xb9a83c00,0x39a80000,0x39a8bc00,0x361f0000,0x3b64b9a8,0x3b64bc00,0x361fb9a8,0x0,0x0,0x0,0x0,
  0xb61f0000,0xbb64b9a8,0xbb64bc00,0xb61fb9a8,0x39a80000,0x39a83c00,0xb9a80000,0xb9a8bc00,0xbb640000,0x361fb9a8,0x361f3c00,0xbb64b9a8,
  0x3c000000,0xbc000000,0x3c000000,0xbc000000,0xbb640000,0x361f39a8,0x361fbc00,0xbb6439a8,0x39a80000,0x39a8bc00,0xb9a80000,0xb9a83c00,
  0xb61f0000,0xbb6439a8,0xbb643c00,0xb61f39a8,0x3c003c00,0x3c003c00,0x3c003c00,0x3c003c00,0xbb64bc00,0xb61fb9a8,0x361f0000,0x3b6439a8,
  0x39a83c00,0xb9a80000,0xb9a8bc00,0x39a80000,0xb61fbc00,0x3b6439a8,0xbb640000,0x361fb9a8,0x3c00,0xbc00,0x3c00,0xbc00,
  0x361fbc00,0xbb6439a8,0x3b640000,0xb61fb9a8,0xb9a83c00,0x39a80000,0x39a8bc00,0xb9a80000,0x3b64bc00,0x361fb9a8,0xb61f0000,0xbb6439a8,
  0xbc003c00,0xbc003c00,0xbc003c00,0xbc003c00,0x3b64bc00,0x361fb9a8,0xb61f0000,0xbb6439a8,0xb9a83c00,0x39a80000,0x39a8bc00,0xb9a80000,
  0x361fbc00,0xbb6439a8,0x3b640000,0xb61fb9a8,0x3c00,0xbc00,0x3c00,0xbc00,0xb61fbc00,0x3b6439a8,0xbb640000,0x361fb9a8,
  0x39a83c00,0xb9a80000,0xb9a8bc00,0x39a80000,0xbb64bc00,0xb61fb9a8,0x361f0000,0x3b6439a8,0x0,0x0,0x0,0x0,
  0xb61f0000,0xbb6439a8,0xbb643c00,0xb61f39a8,0x39a80000,0x39a8bc00,0xb9a80000,0xb9a83c00,0xbb640000,0x361f39a8,0x361fbc00,0xbb6439a8,
  0x3c000000,0xbc000000,0x3c000000,0xbc000000,0xbb640000,0x361fb9a8,0x361f3c00,0xbb64b9a8,0x39a80000,0x39a83c00,0xb9a80000,0xb9a8bc00,
  0xb61f0000,0xbb64b9a8,0xbb64bc00,0xb61fb9a8,0x0,0x0,0x0,0x0,0x361f0000,0x3b64b9a8,0x3b64bc00,0x361fb9a8,
  0xb9a80000,0xb9a83c00,0x39a80000,0x39a8bc00,0x3b640000,0xb61fb9a8,0xb61f3c00,0x3b64b9a8,0xbc000000,0x3c000000,0xbc000000,0x3c000000,
  0x3b640000,0xb61f39a8,0xb61fbc00,0x3b6439a8,0xb9a80000,0xb9a8bc00,0x39a80000,0x39a83c00,0x361f0000,0x3b6439a8,0x3b643c00,0x361f39a8,
  0xbc003c00,0xbc003c00,0xbc003c00,0xbc003c00,0x3b64bc00,0x361fb9a8,0xb61f0000,0xbb6439a8,0xb9a83c00,0x39a80000,0x39a8bc00,0xb9a80000,
  0x361fbc00,0xbb6439a8,0x3b640000,0xb61fb9a8,0x3c00,0xbc00,0x3c00,0xbc00,0xb61fbc00,0x3b6439a8,0xbb640000,0x361fb9a8,
  0x39a83c00,0xb9a80000,0xb9a8bc00,0x39a80000,0xbb64bc00,0xb61fb9a8,0x361f0000,0x3b6439a8,0x3bfe3c00,0x3bea3bf6,0x3bc33bd9,0x3b883ba8,
  0x3bc33c00,0x39ed3b0e,0x35643872,0xb0b22e46,0x3b3b3c00,0x33c63913,0xb8c4b23e,0xbbfebb0e,0x3a6d3c00,0xb56434a5,0xbbfebaa7,0xb3c6ba2f,
  0x395f3c00,0xba6dae46,0xb81dbbd9,0x3b3b34a5,0x381d3c00,0xbbfeb78b,0x36d7b872,0x38c43bf6,0x35643c00,0xbaddba2f,0x3bea323e,0xb95f378b,
  0x30b23c00,0xb6d7bba8,0x395f3aa7,0xbaddb913,0x2a480000,0x30b22e46,0x33c6323e,0x356434a5,0x33c60000,0x395f378b,0x3b883aa7,0x3bea3bf6,
  0x36d70000,0x3bc33a2f,0x3a6d3bd9,0x2a48378b,0x38c40000,0x3b883ba8,0xaa483872,0xbbc3b913,0x39ed0000,0x38c43bf6,0xbaddb23e,0xb6d7bba8,
  0x3add0000,0x2a483b0e,0xbb3bbaa7,0x3a6dae46,0x3b880000,0xb81d3913,0xb0b2bbd9,0x39ed3b0e,0x3bea0000,0xbb3b34a5,0x39edb872,0xb81d3a2f,
  0x3b3b3b64,0x3add3b0e,0x3a6d3aa7,0x39ed3a2f,0xb8c4b61f,0xbb3bba2f,0xbbfebbd9,0xbaddbba8,0xb95fbb64,0x30b2b4a5,0x3add3872,0x3b883bf6,
  0x3add361f,0x39ed3bf6,0xb6d7323e,0xbbeabb0e,0x35643b64,0xbbc3b78b,0xb0b2baa7,0x3bfe3913,0xbbeab61f,0x3564b913,0x395f3bd9,0xbbc3b4a5,
  0x2a48bb64,0x38c43ba8,0xbbc3b872,0x3b3bae46,0x3bc3361f,0xbbfeae46,0x3b88b23e,0xba6d378b,0x36d7361f,0x381d378b,0x38c43872,0x395f3913,
  0x3a6d3b64,0x36d73913,0xaa48323e,0xb81db4a5,0xb9edb61f,0xbbeabba8,0xb81dbaa7,0x3564ae46,0xb81dbb64,0x395f2e46,0x3b3b3bd9,0xb0b2378b,
  0x3b88361f,0x33c63b0e,0xbbeab872,0xaa48ba2f,0x30b23b64,0xbb88ba2f,0x39edb23e,0x33c63ba8,0xbbfeb61f,0x3a6db4a5,0xb3c63aa7,0xb6d7bbf6,
  0x33c6bb64,0x2a483bf6,0xb564bbd9,0x38c43b0e,0x395f39a8,0x38c43913,0x381d3872,0x36d7378b,0xb81db9a8,0xaa48b4a5,0x36d7323e,0x3a6d3913,
  0x356439a8,0xb81dae46,0xbbeabaa7,0xb9edbba8,0xb0b2b9a8,0x3b3b378b,0x395f3bd9,0xb81d2e46,0xaa4839a8,0xbbeaba2f,0x33c6b872,0x3b883b0e,
  0x33c6b9a8,0x39ed3ba8,0xbb88b23e,0x30b2ba2f,0xb6d739a8,0xb3c6bbf6,0x3a6d3aa7,0xbbfeb4a5,0x38c4b9a8,0xb5643b0e,0x2a48bbd9,0x33c63bf6,
  0x39ed39a8,0x3a6d3a2f,0x3add3aa7,0x3b3b3b0e,0xbaddb9a8,0xbbfebba8,0xbb3bbbd9,0xb8c4ba2f,0x3b8839a8,0x3add3bf6,0x30b23872,0xb95fb4a5,
  0xbbeab9a8,0xb6d7bb0e,0x39ed323e,0x3add3bf6,0x3bfe39a8,0xb0b23913,0xbbc3baa7,0x3564b78b,0xbbc3b9a8,0x395fb4a5,0x35643bd9,0xbbeab913,
  0x3b3b39a8,0xbbc3ae46,0x38c4b872,0x2a483ba8,0xba6db9a8,0x3b88378b,0xbbfeb23e,0x3bc3ae46,0x3564361f,0x33c634a5,0x30b2323e,0x2a482e46,
  0x3bea3b64,0x3b883bf6,0x395f3aa7,0x33c6378b,0x2a48b61f,0x3a6d378b,0x3bc33bd9,0x36d73a2f,0xbbc3bb64,0xaa48b913,0x3b883872,0x38c43ba8,
  0xb6d7361f,0xbaddbba8,0x38c4b23e,0x39ed3bf6,0x3a6d3b64,0xbb3bae46,0x2a48baa7,0x3add3b0e,0x39edb61f,0xb0b23b0e,0xb81dbbd9,0x3b883913,
  0xb81dbb64,0x39ed3a2f,0xbb3bb872,0x3bea34a5,0x3b883b64,0x3bc33ba8,0x3bea3bd9,0x3bfe3bf6,0xb0b2b61f,0x35642e46,0x39ed3872,0x3bc33b0e,
  0xbbfebb64,0xb8c4bb0e,0x33c6b23e,0x3b3b3913,0xb3c6361f,0xbbfeba2f,0xb564baa7,0x3a6d34a5,0x3b3b3b64,0xb81d34a5,0xba6dbbd9,0x395fae46,
  0x38c4b61f,0x36d73bf6,0xbbfeb872,0x381db78b,0xb95fbb64,0x3bea378b,0xbadd323e,0x3564ba2f,0xbadd361f,0x395fb913,0xb6d73aa7,0x30b2bba8,
  0xaa483c00,0x30b2bbf6,0xb3c63bd9,0x3564bba8,0xb3c63c00,0x395fbb0e,0xbb883872,0x3beaae46,0xb6d73c00,0x3bc3b913,0xba6db23e,0x2a483b0e,
  0xb8c43c00,0x3b88b4a5,0x2a48baa7,0xbbc33a2f,0xb9ed3c00,0x38c42e46,0x3addbbd9,0xb6d7b4a5,0xbadd3c00,0x2a48378b,0x3b3bb872,0x3a6dbbf6,
  0xbb883c00,0xb81d3a2f,0x30b2323e,0x39edb78b,0xbbea3c00,0xbb3b3ba8,0xb9ed3aa7,0xb81d3913,0x3bfe0000,0xbbeaae46,0x3bc3323e,0xbb88b4a5,
  0x3bc30000,0xb9edb78b,0x35643aa7,0x30b2bbf6,0x3b3b0000,0xb3c6ba2f,0xb8c43bd9,0x3bfeb78b,0x3a6d0000,0x3564bba8,0xbbfe3872,0x33c63913,
  0x395f0000,0x3a6dbbf6,0xb81db23e,0xbb3b3ba8,0x381d0000,0x3bfebb0e,0x36d7baa7,0xb8c42e46,0x35640000,0x3addb913,0x3beabbd9,0x395fbb0e,
  0x30b20000,0x36d7b4a5,0x395fb872,0x3addba2f,0xb6d73b64,0x381dbb0e,0xb8c43aa7,0x395fba2f,0xba6db61f,0x36d73a2f,0x2a48bbd9,0xb81d3ba8,
  0x39edbb64,0xbbea34a5,0x381d3872,0x3564bbf6,0x381d361f,0x395fbbf6,0xbb3b323e,0xb0b23b0e,0xbb883b64,0x33c6378b,0x3beabaa7,0xaa48b913,
  0xb0b2b61f,0xbb883913,0xb9ed3bd9,0x33c634a5,0x3bfebb64,0x3a6dbba8,0x33c6b872,0xb6d72e46,0xb3c6361f,0x2a482e46,0x3564b23e,0x38c4b78b,
  0x3b3b361f,0xbaddb78b,0x3a6d3872,0xb9edb913,0xb8c43b64,0x3b3bb913,0xbbfe323e,0x3add34a5,0xb95fb61f,0xb0b23ba8,0x3addbaa7,0xbb882e46,
  0x3addbb64,0xb9edae46,0xb6d73bd9,0x3beab78b,0x3564361f,0x3bc3bb0e,0xb0b2b872,0xbbfe3a2f,0xbbea3b64,0xb5643a2f,0x395fb23e,0x3bc3bba8,
  0x2a48b61f,0xb8c434a5,0xbbc33aa7,0xbb3b3bf6,0x3bc3bb64,0x3bfebbf6,0x3b88bbd9,0x3a6dbb0e,0xb9ed39a8,0x3a6db913,0xbadd3872,0x3b3bb78b,
  0x3addb9a8,0xbbfe34a5,0x3b3b323e,0xb8c4b913,0xbb8839a8,0x3add2e46,0xb0b2baa7,0xb95f3ba8,0x3beab9a8,0xb6d7b78b,0xb9ed3bd9,0x3addae46,
  0xbbfe39a8,0xb0b23a2f,0x3bc3b872,0x3564bb0e,0x3bc3b9a8,0x395fbba8,0xb564b23e,0xbbea3a2f,0xbb3b39a8,0xbbc33bf6,0xb8c43aa7,0x2a4834a5,
  0x3a6db9a8,0x3b88bb0e,0x3bfebbd9,0x3bc3bbf6,0x395f39a8,0xb8c4ba2f,0x381d3aa7,0xb6d7bb0e,0xb81db9a8,0x2a483ba8,0x36d7bbd9,0xba6d3a2f,
  0x356439a8,0x381dbbf6,0xbbea3872,0x39ed34a5,0xb0b2b9a8,0xbb3b3b0e,0x395f323e,0x381dbbf6,0xaa4839a8,0x3beab913,0x33c6baa7,0xbb88378b,
  0x33c6b9a8,0xb9ed34a5,0xbb883bd9,0xb0b23913,0xb6d739a8,0x33c62e46,0x3a6db872,0x3bfebba8,0x38c4b9a8,0x3564b78b,0x2a48b23e,0xb3c62e46,
  0xbb88361f,0x3bc3b4a5,0xbbea323e,0x3bfeae46,0x30b23b64,0x3564bbf6,0xb9ed3aa7,0x3bc3b78b,0x3bfeb61f,0xb8c4b78b,0xb3c63bd9,0x3b3bba2f,
  0x33c6bb64,0xbbfe3913,0x35643872,0x3a6dbba8,0xbb3b361f,0xb81d3ba8,0x3a6db23e,0x395fbbf6,0xb8c43b64,0x36d72e46,0x3bfebaa7,0x381dbb0e,
  0x395fb61f,0x3beabb0e,0x3addbbd9,0x3564b913,0x3addbb64,0x395fba2f,0x36d7b872,0x30b2b4a5,0x35643b64,0xb3c6bba8,0x30b23bd9,0xaa48bbf6,
  0x3beab61f,0xbb88ae46,0x395f3872,0xb3c6bb0e,0x2a48bb64,0xba6d3b0e,0x3bc3b23e,0xb6d7b913,0xbbc3361f,0x2a483a2f,0x3b88baa7,0xb8c4b4a5,
  0xb6d73b64,0x3addb4a5,0x38c4bbd9,0xb9ed2e46,0x3a6db61f,0x3b3bbbf6,0x2a48b872,0xbadd378b,0x39edbb64,0x30b2b78b,0xb81d323e,0xbb883a2f,
  0xb81d361f,0xb9ed3913,0xbb3b3aa7,0xbbea3ba8,0xbbfe3c00,0xbbea3bf6,0xbbc33bd9,0xbb883ba8,0xbbc33c00,0xb9ed3b0e,0xb5643872,0x30b22e46,
  0xbb3b3c00,0xb3c63913,0x38c4b23e,0x3bfebb0e,0xba6d3c00,0x356434a5,0x3bfebaa7,0x33c6ba2f,0xb95f3c00,0x3a6dae46,0x381dbbd9,0xbb3b34a5,
  0xb81d3c00,0x3bfeb78b,0xb6d7b872,0xb8c43bf6,0xb5643c00,0x3addba2f,0xbbea323e,0x395f378b,0xb0b23c00,0x36d7bba8,0xb95f3aa7,0x3addb913,
  0xaa480000,0xb0b22e46,0xb3c6323e,0xb56434a5,0xb3c60000,0xb95f378b,0xbb883aa7,0xbbea3bf6,0xb6d70000,0xbbc33a2f,0xba6d3bd9,0xaa48378b,
  0xb8c40000,0xbb883ba8,0x2a483872,0x3bc3b913,0xb9ed0000,0xb8c43bf6,0x3addb23e,0x36d7bba8,0xbadd0000,0xaa483b0e,0x3b3bbaa7,0xba6dae46,
  0xbb880000,0x381d3913,0x30b2bbd9,0xb9ed3b0e,0xbbea0000,0x3b3b34a5,0xb9edb872,0x381d3a2f,0xbb3b3b64,0xbadd3b0e,0xba6d3aa7,0xb9ed3a2f,
  0x38c4b61f,0x3b3bba2f,0x3bfebbd9,0x3addbba8,0x395fbb64,0xb0b2b4a5,0xbadd3872,0xbb883bf6,0xbadd361f,0xb9ed3bf6,0x36d7323e,0x3beabb0e,
  0xb5643b64,0x3bc3b78b,0x30b2baa7,0xbbfe3913,0x3beab61f,0xb564b913,0xb95f3bd9,0x3bc3b4a5,0xaa48bb64,0xb8c43ba8,0x3bc3b872,0xbb3bae46,
  0xbbc3361f,0x3bfeae46,0xbb88b23e,0x3a6d378b,0xb6d7361f,0xb81d378b,0xb8c43872,0xb95f3913,0xba6d3b64,0xb6d73913,0x2a48323e,0x381db4a5,
  0x39edb61f,0x3beabba8,0x381dbaa7,0xb564ae46,0x381dbb64,0xb95f2e46,0xbb3b3bd9,0x30b2378b,0xbb88361f,0xb3c63b0e,0x3beab872,0x2a48ba2f,
  0xb0b23b64,0x3b88ba2f,0xb9edb23e,0xb3c63ba8,0x3bfeb61f,0xba6db4a5,0x33c63aa7,0x36d7bbf6,0xb3c6bb64,0xaa483bf6,0x3564bbd9,0xb8c43b0e,
  0xb95f39a8,0xb8c43913,0xb81d3872,0xb6d7378b,0x381db9a8,0x2a48b4a5,0xb6d7323e,0xba6d3913,0xb56439a8,0x381dae46,0x3beabaa7,0x39edbba8,
  0x30b2b9a8,0xbb3b378b,0xb95f3bd9,0x381d2e46,0x2a4839a8,0x3beaba2f,0xb3c6b872,0xbb883b0e,0xb3c6b9a8,0xb9ed3ba8,0x3b88b23e,0xb0b2ba2f,
  0x36d739a8,0x33c6bbf6,0xba6d3aa7,0x3bfeb4a5,0xb8c4b9a8,0x35643b0e,0xaa48bbd9,0xb3c63bf6,0xb9ed39a8,0xba6d3a2f,0xbadd3aa7,0xbb3b3b0e,
  0x3addb9a8,0x3bfebba8,0x3b3bbbd9,0x38c4ba2f,0xbb8839a8,0xbadd3bf6,0xb0b23872,0x395fb4a5,0x3beab9a8,0x36d7bb0e,0xb9ed323e,0xbadd3bf6,
  0xbbfe39a8,0x30b23913,0x3bc3baa7,0xb564b78b,0x3bc3b9a8,0xb95fb4a5,0xb5643bd9,0x3beab913,0xbb3b39a8,0x3bc3ae46,0xb8c4b872,0xaa483ba8,
  0x3a6db9a8,0xbb88378b,0x3bfeb23e,0xbbc3ae46,0xb564361f,0xb3c634a5,0xb0b2323e,0xaa482e46,0xbbea3b64,0xbb883bf6,0xb95f3aa7,0xb3c6378b,
  0xaa48b61f,0xba6d378b,0xbbc33bd9,0xb6d73a2f,0x3bc3bb64,0x2a48b913,0xbb883872,0xb8c43ba8,0x36d7361f,0x3addbba8,0xb8c4b23e,0xb9ed3bf6,
  0xba6d3b64,0x3b3bae46,0xaa48baa7,0xbadd3b0e,0xb9edb61f,0x30b23b0e,0x381dbbd9,0xbb883913,0x381dbb64,0xb9ed3a2f,0x3b3bb872,0xbbea34a5,
  0xbb883b64,0xbbc33ba8,0xbbea3bd9,0xbbfe3bf6,0x30b2b61f,0xb5642e46,0xb9ed3872,0xbbc33b0e,0x3bfebb64,0x38c4bb0e,0xb3c6b23e,0xbb3b3913,
  0x33c6361f,0x3bfeba2f,0x3564baa7,0xba6d34a5,0xbb3b3b64,0x381d34a5,0x3a6dbbd9,0xb95fae46,0xb8c4b61f,0xb6d73bf6,0x3bfeb872,0xb81db78b,
  0x395fbb64,0xbbea378b,0x3add323e,0xb564ba2f,0x3add361f,0xb95fb913,0x36d73aa7,0xb0b2bba8,0x2a483c00,0xb0b2bbf6,0x33c63bd9,0xb564bba8,
  0x33c63c00,0xb95fbb0e,0x3b883872,0xbbeaae46,0x36d73c00,0xbbc3b913,0x3a6db23e,0xaa483b0e,0x38c43c00,0xbb88b4a5,0xaa48baa7,0x3bc33a2f,
  0x39ed3c00,0xb8c42e46,0xbaddbbd9,0x36d7b4a5,0x3add3c00,0xaa48378b,0xbb3bb872,0xba6dbbf6,0x3b883c00,0x381d3a2f,0xb0b2323e,0xb9edb78b,
  0x3bea3c00,0x3b3b3ba8,0x39ed3aa7,0x381d3913,0xbbfe0000,0x3beaae46,0xbbc3323e,0x3b88b4a5,0xbbc30000,0x39edb78b,0xb5643aa7,0xb0b2bbf6,
  0xbb3b0000,0x33c6ba2f,0x38c43bd9,0xbbfeb78b,0xba6d0000,0xb564bba8,0x3bfe3872,0xb3c63913,0xb95f0000,0xba6dbbf6,0x381db23e,0x3b3b3ba8,
  0xb81d0000,0xbbfebb0e,0xb6d7baa7,0x38c42e46,0xb5640000,0xbaddb913,0xbbeabbd9,0xb95fbb0e,0xb0b20000,0xb6d7b4a5,0xb95fb872,0xbaddba2f,
  0x36d73b64,0xb81dbb0e,0x38c43aa7,0xb95fba2f,0x3a6db61f,0xb6d73a2f,0xaa48bbd9,0x381d3ba8,0xb9edbb64,0x3bea34a5,0xb81d3872,0xb564bbf6,
  0xb81d361f,0xb95fbbf6,0x3b3b323e,0x30b23b0e,0x3b883b64,0xb3c6378b,0xbbeabaa7,0x2a48b913,0x30b2b61f,0x3b883913,0x39ed3bd9,0xb3c634a5,
  0xbbfebb64,0xba6dbba8,0xb3c6b872,0x36d72e46,0x33c6361f,0xaa482e46,0xb564b23e,0xb8c4b78b,0xbb3b361f,0x3addb78b,0xba6d3872,0x39edb913,
  0x38c43b64,0xbb3bb913,0x3bfe323e,0xbadd34a5,0x395fb61f,0x30b23ba8,0xbaddbaa7,0x3b882e46,0xbaddbb64,0x39edae46,0x36d73bd9,0xbbeab78b,
  0xb564361f,0xbbc3bb0e,0x30b2b872,0x3bfe3a2f,0x3bea3b64,0x35643a2f,0xb95fb23e,0xbbc3bba8,0xaa48b61f,0x38c434a5,0x3bc33aa7,0x3b3b3bf6,
  0xbbc3bb64,0xbbfebbf6,0xbb88bbd9,0xba6dbb0e,0x39ed39a8,0xba6db913,0x3add3872,0xbb3bb78b,0xbaddb9a8,0x3bfe34a5,0xbb3b323e,0x38c4b913,
  0x3b8839a8,0xbadd2e46,0x30b2baa7,0x395f3ba8,0xbbeab9a8,0x36d7b78b,0x39ed3bd9,0xbaddae46,0x3bfe39a8,0x30b23a2f,0xbbc3b872,0xb564bb0e,
  0xbbc3b9a8,0xb95fbba8,0x3564b23e,0x3bea3a2f,0x3b3b39a8,0x3bc33bf6,0x38c43aa7,0xaa4834a5,0xba6db9a8,0xbb88bb0e,0xbbfebbd9,0xbbc3bbf6,
  0xb95f39a8,0x38c4ba2f,0xb81d3aa7,0x36d7bb0e,0x381db9a8,0xaa483ba8,0xb6d7bbd9,0x3a6d3a2f,0xb56439a8,0xb81dbbf6,0x3bea3872,0xb9ed34a5,
  0x30b2b9a8,0x3b3b3b0e,0xb95f323e,0xb81dbbf6,0x2a4839a8,0xbbeab913,0xb3c6baa7,0x3b88378b,0xb3c6b9a8,0x39ed34a5,0x3b883bd9,0x30b23913,
  0x36d739a8,0xb3c62e46,0xba6db872,0xbbfebba8,0xb8c4b9a8,0xb564b78b,0xaa48b23e,0x33c62e46,0x3b88361f,0xbbc3b4a5,0x3bea323e,0xbbfeae46,
  0xb0b23b64,0xb564bbf6,0x39ed3aa7,0xbbc3b78b,0xbbfeb61f,0x38c4b78b,0x33c63bd9,0xbb3bba2f,0xb3c6bb64,0x3bfe3913,0xb5643872,0xba6dbba8,
  0x3b3b361f,0x381d3ba8,0xba6db23e,0xb95fbbf6,0x38c43b64,0xb6d72e46,0xbbfebaa7,0xb81dbb0e,0xb95fb61f,0xbbeabb0e,0xbaddbbd9,0xb564b913,
  0xbaddbb64,0xb95fba2f,0xb6d7b872,0xb0b2b4a5,0xb5643b64,0x33c6bba8,0xb0b23bd9,0x2a48bbf6,0xbbeab61f,0x3b88ae46,0xb95f3872,0x33c6bb0e,
  0xaa48bb64,0x3a6d3b0e,0xbbc3b23e,0x36d7b913,0x3bc3361f,0xaa483a2f,0xbb88baa7,0x38c4b4a5,0x36d73b64,0xbaddb4a5,0xb8c4bbd9,0x39ed2e46,
  0xba6db61f,0xbb3bbbf6,0xaa48b872,0x3add378b,0xb9edbb64,0xb0b2b78b,0x381d323e,0x3b883a2f,0x381d361f,0x39ed3913,0x3b3b3aa7,0x3bea3ba8,
  0x30003000,0x2fff2fff,0xe480000,0x1b111a48,0x30003000,0x2fff2fff,0x14b61248,0x1c521bda,0x30003000,0x2ffe2fff,0x17db1648,0x1d1b1cb6,
  0x30003000,0x2ffe2ffe,0x197f18b6,0x1de31d7f,0x30003000,0x2fed2ff1,0x17db0000,0x246723d6,0x2ffe2fff,0x2fe32fe8,0x1de31bda,0x256024e4,
  0x2ffa2ffc,0x2fd72fdd,0x20e71fd9,0x265725db,0x2ff42ff7,0x2fca2fd1,0x22dc21e2,0x274c26d2,0x2fff3000,0x2fc12fce,0x1b110000,0x27df2703,
  0x2ff92ffd,0x2fa22fb2,0x214c1f11,0x28c9285d,0x2fed2ff4,0x2f7d2f91,0x2467230e,0x299f2934,0x2fda2fe4,0x2f532f69,0x26262547,0x2a702a08,
  0x2ffe3000,0x2f7d2f99,0x1d1b0000,0x299f2905,0x2ff12ff9,0x2f3e2f5f,0x23a4211a,0x2acc2a37,0x2fd72fe6,0x2ef32f1a,0x26572515,0x2bee2b5e,
  0x2fb12fc6,0x2e9c2ec9,0x28692796,0x2c812c3d,0x2ffd3000,0x2f222f50,0x1eac0000,0x2b3d2a7c,0x2fe72ff5,0x2eb82ef0,0x24fd22aa,0x2c582bf9,
  0x2fbb2fd4,0x2e3b2e7c,0x282026a1,0x2d052cb0,0x2f792f9d,0x2dad2df6,0x29b628ed,0x2da42d56,0x2ffc3000,0x2eb12ef6,0x201f0000,0x2c622be3,
  0x2fda2fef,0x2e132e65,0x2626241d,0x2d352cce,0x2f972fbc,0x2d5b2dba,0x29112814,0x2df22d96,0x2f332f69,0x2c8c2cf6,0x2af92a08,0x2e952e47,
  0x2ffa3000,0x2e2b2e8a,0x20e70000,0x2d182c9b,0x2fca2fe8,0x2d512dc3,0x274c24e4,0x2dfa2d8d,0x2f6b2fa0,0x2c582cd8,0x29fd28d5,0x2eb82e5e,
  0x2ee02f2b,0x2a872ba1,0x2c172b1b,0x2f4e2f08,0x2ff83000,0x2d922e0f,0x21b00000,0x2dbe2d3a,0x2fb72fe0,0x2c772d09,0x283825aa,0x2ea32e37,
  0x2f392f80,0x2a702bb7,0x2ae32993,0x2f532f02,0x2e7f2ee3,0x277d291d,0x2cab2c12,0x2fc72f95,0x2ff63000,0x2ce72d84,0x22780000,0x2e522dcb,
  0x2fa22fd6,0x2b102c3d,0x28c9266f,0x2f2e2ec9,0x2eff2f5a,0x28082993,0x2bc22a4e,0x2fbe2f80,0x2e132e92,0x1eac24e4,0x2d352c91,0x2ffd2fe8,
  0x2ff33000,0x2c2d2cec,0x23400000,0x2ed32e4f,0x2f8a2fcb,0x29112ac1,0x29582734,0x2f972f41,0x2ebf2f30,0x221426a1,0x2c4d2b05,0x2ff72fd4,
  0x2d9b2e37,0xa43698b6,0x2db52d09,0x2fee3000,0x2ff03000,0x2acc2c48,0x24040000,0x2f3e2ec2,0x2f702fc0,0x25f428ed,0x29e527f7,0x2fdc2f9d,
  0x2e782f02,0xa01f1fd9,0x2cb52bb7,0x2ffc2ffc,0x2d182dd4,0xa8f9a60d,0x2e2b2d7b,0x2f9b2fdb,0x2fed3000,0x29292b32,0x24670000,0x2f932f25,
  0x2f532fb2,0x1eac260d,0x2a70285d,0x2ffd2fdb,0x2e2b2ed0,0xa71ba17e,0x2d182c32,0x2fcd2ff8,0x2c8c2d69,0xabaca9ab,0x2e952de5,0x2f052f7b,
  0x2fe93000,0x26ea29c2,0x24cb0000,0x2fd02f77,0x2f332fa4,0xa14c2051,0x2af928bd,0x2ff92ffb,0x2dd82e99,0xa9fda765,0x2d762c87,0x2f6b2fc9,
  0x2bee2cf6,0xad0eac12,0x2ef32e47,0x2e332ee3,0x2fe53000,0x22dc2844,0x252e0000,0x2ff42fb6,0x2f112f95,0xa6ea9f11,0x2b80291d,0x2fd02ffd,
  0x2d802e5e,0xac22a9f1,0x2dd02cd8,0x2ed92f6e,0x2ab52c7c,0xae1bad30,0x2f432ea0,0x2d2b2e17,0x2fe13000,0x8e482579,0x25910000,0x30002fe2,
  0x2eed2f84,0xa987a5aa,0x2c02297c,0x2f822fe0,0x2d222e1f,0xad2bac07,0x2e232d27,0x2e1b2ee9,0x29702bf9,0xaef3ae27,0x2f862ef0,0x2bee2d1d,
  0x2fdc3000,0xa34020b5,0x25f40000,0x2ff32ffa,0x2ec62f72,0xab80a8bd,0x2c4229da,0x2f112fa4,0x2cbf2ddc,0xae13ad00,0x2e712d72,0x2d352e3f,
  0x28202aee,0xaf8faef0,0x2fbb2f36,0x29402bf9,0x2fd73000,0xa71b9a48,0x26570000,0x2fcd2fff,0x2e9c2f5f,0xacabaa93,0x2c812a37,0x2e7f2f4b,
  0x2c582d96,0xaed3addc,0x2eb82dba,0x2c2d2d72,0x259129da,0xafe9af84,0x2fe12f72,0x24cb297c,0x2fd23000,0xa940a3d6,0x26b90000,0x2f8f2ff1,
  0x2e712f4b,0xad80ac28,0x2cbf2a93,0x2dd02ed6,0x2bd82d4d,0xaf67ae99,0x2ef92dfe,0x2a142c87,0x21b028bd,0xafffafe0,0x2ff82fa4,0x9c5225aa,
  0x2fcd3000,0xaae3a703,0x271b0000,0x2f392fce,0x2e432f36,0xae3bacf6,0x2cfb2aee,0x2d052e47,0x2af92d00,0xafcaaf30,0x2f332e3f,0x274c2b05,
  0xe482734,0xafd0b000,0x30002fcb,0xa6ea1248,0x2fc73000,0xac38a905,0x277d0000,0x2ecc2f99,0x2e132f20,0xaed9adb1,0x2d352b48,0x2c222d9f,
  0x2a142cb0,0xaffbafa0,0x2f672e7c,0x208328d5,0xa14c24e4,0xaf5dafe4,0x2ff92fe8,0xaa42a547,0x2fc13000,0xacf1aa7c,0x27df0000,0x2e4b2f50,
  0x2de12f08,0xaf58ae56,0x2d6d2ba1,0x2a592ce2,0x29292c5d,0xaff8afe6,0x2f932eb5,0xa1b02515,0xa560211a,0xaeaaaf8c,0x2fe32ff9,0xac6da94c,
  0x2fbb3000,0xad9babe3,0x28200000,0x2db52ef6,0x2dad2ef0,0xafb4aee3,0x2da42bf9,0x28512c12,0x28382c07,0xafc1b000,0x2fb72ee9,0xa7df1648,
  0xa8081248,0xadbeaefc,0x2fbe3000,0xad92abcd,0x2fb43000,0xae33ac9b,0x28510000,0x2d0e2e8a,0x2d762ed6,0xafedaf55,0x2dd82c28,0x24672a65,
  0x26882b5e,0xaf58afed,0x2fd52f1a,0xaa59a44e,0xa958a051,0xaca0ae37,0x2f8a2ffb,0xae87ad09,0x2fad3000,0xaeb8ad3a,0x28810000,0x2c582e0f,
  0x2d3e2ebc,0xb000afab,0x2e0b2c52,0xe48288d,0x24992aaa,0xaebfafaf,0x2feb2f46,0xac4da875,0xaa9ea480,0xaab5ad43,0x2f492fec,0xaf43ae07,
  0x2fa63000,0xaf28adcb,0x28b10000,0x2b262d84,0x2d052ea0,0xafeeafe4,0x2e3b2c7c,0xa4362547,0x214c29f1,0xadfaaf46,0x2ff92f6e,0xad51aaaa,
  0xabd8a6d2,0xa7dfac28,0x2ef92fd1,0xafc1aed6,0x2f9e3000,0xaf82ae4f,0x28e10000,0x29872cec,0x2cc92e83,0xafb7affe,0x2e692ca6,0xa8381d7f,
  0x197f2934,0xad0eaeb5,0x30002f91,0xae33ac5d,0xac81a88d,0xa01fa9da,0x2e9c2fab,0xaffcaf72,0x2f973000,0xafc4aec2,0x29110000,0x27ae2c48,
  0x2c8c2e65,0xaf5daff9,0x2e952cce,0xaa42a11a,0x9d1b2875,0xac02adfe,0x2ffe2faf,0xaeedad4d,0xad0ea9ab,0x23a4a66f,0x2e332f7b,0xaff1afd6,
  0x2f8f3000,0xafeeaf25,0x29400000,0x24362b32,0x2c4d2e47,0xaee0afd6,0x2ebf2cf6,0xac17a66f,0xa2782765,0xa9b6ad27,0x2ff62fc9,0xaf79ae1f,
  0xad92aac1,0x28c99bda,0x2dbe2f41,0xafa2afff,0x2f863000,0xb000af77,0x29700000,0x197f29c2,0x2c0d2e27,0xae43af95,0x2ee62d1d,0xacfba91d,
  0xa52e25db,0xa688ac32,0x2fe52fdd,0xafd5aed0,0xae0babcd,0x2b802480,0x2d3e2efc,0xaf11afec,0x2f7d3000,0xaff8afb6,0x299f0000,0xa1b02844,
  0x2b962e07,0xad89af36,0x2f0b2d43,0xadc7aaee,0xa71b244e,0x9de3aa4e,0x2fcd2fed,0xaffeaf5a,0xae78ac67,0x2cfb28ed,0x2cb52eae,0xae43af9d,
  0x2f743000,0xafd7afe2,0x29ce0000,0xa6572579,0x2b102de5,0xacb5aebc,0x2f2e2d69,0xae78ac52,0xa881217e,0x2340a814,0x2fad2ff8,0xaff3afbc,
  0xaed9ace2,0x2e0b2b75,0x2c222e56,0xad3eaf14,0x2f6b3000,0xaf9eaffa,0x29fd0000,0xa8e120b5,0x2a872dc3,0xab96ae27,0x2f4e2d8d,0xaf0bad1d,
  0xa9701cb6,0x2851a30e,0x2f862fff,0xafb4aff4,0xaf2ead56,0x2ee62ce2,0x2b102df6,0xac0dae56,
};

#define PROF(slot) do {} while (0)
#define PROFA(slot, dep) do {} while (0)
#define PROF3(slot) do {} while (0)
#define PROF2(slot) do {} while (0)

__device__ __forceinline__ uint32_t smem_u32(const void* p) { return (uint32_t)__cvta_generic_to_shared(p); }

__device__ __forceinline__ void mbar_init(uint32_t a, uint32_t c) {
  asm volatile("mbarrier.init.shared::cta.b64 [%0], %1;\n" ::"r"(a), "r"(c) : "memory");
}
__device__ __forceinline__ void mbar_expect_tx(uint32_t a, uint32_t bytes) {
  asm volatile("mbarrier.arrive.expect_tx.shared::cta.b64 _, [%0], %1;\n" ::"r"(a), "r"(bytes) : "memory");
}
__device__ __forceinline__ void mbar_arrive_cluster(uint32_t cluster_addr) {
  asm volatile("mbarrier.arrive.shared::cluster.b64 _, [%0];\n" ::"r"(cluster_addr) : "memory");
}
__device__ __forceinline__ void mbar_arrive_cluster_n(uint32_t cluster_addr, uint32_t n) {
  asm volatile("mbarrier.arrive.shared::cluster.b64 _, [%0], %1;\n" ::"r"(cluster_addr), "r"(n) : "memory");
}
__device__ __forceinline__ bool mbar_try(uint32_t a, uint32_t parity) {
  uint32_t ok;
  asm volatile("{\n.reg .pred p;\nmbarrier.try_wait.parity.shared::cta.b64 p, [%1], %2;\nselp.u32 %0, 1, 0, p;\n}\n"
               : "=r"(ok) : "r"(a), "r"(parity) : "memory");
  return ok;
}
__device__ __forceinline__ void mbar_wait(uint32_t a, uint32_t parity) {
  if (mbar_try(a, parity)) return;
#pragma unroll 1
  for (int n = 0; n < SPIN_LIMIT; n++)
    if (mbar_try(a, parity)) break;
}
__device__ __forceinline__ bool elect_one() {
  uint32_t p;
  asm volatile("{\n.reg .pred P;\nelect.sync _|P, 0xffffffff;\nselp.u32 %0, 1, 0, P;\n}\n" : "=r"(p));
  return p;
}
__device__ __forceinline__ uint32_t mapa(uint32_t a, uint32_t rank) {
  uint32_t r;
  asm volatile("mapa.shared::cluster.u32 %0, %1, %2;\n" : "=r"(r) : "r"(a), "r"(rank));
  return r;
}
__device__ __forceinline__ void nb_sync(int id, int n) { asm volatile("bar.sync %0, %1;\n" ::"r"(id), "r"(n) : "memory"); }
__device__ __forceinline__ void nb_arrive(int id, int n) { asm volatile("bar.arrive %0, %1;\n" ::"r"(id), "r"(n) : "memory"); }
__device__ __forceinline__ void cluster_sync_all() {
  asm volatile("barrier.cluster.arrive.relaxed.aligned;\nbarrier.cluster.wait.aligned;\n" ::: "memory");
}
__device__ __forceinline__ void fence_async_smem() { asm volatile("fence.proxy.async.shared::cta;\n" ::: "memory"); }
__device__ __forceinline__ void fence_async_all() { asm volatile("fence.proxy.async.global;\n" ::: "memory"); }

__device__ __forceinline__ void tma_load_3d(uint32_t dst, const CUtensorMap* tm, uint32_t bar, int c0, int c1, int c2) {
  asm volatile(
      "cp.async.bulk.tensor.3d.shared::cluster.global.mbarrier::complete_tx::bytes [%0], [%1, {%3, %4, %5}], [%2];\n"
      ::"r"(dst), "l"(tm), "r"(bar), "r"(c0), "r"(c1), "r"(c2) : "memory");
}
__device__ __forceinline__ void tma_load_4d(uint32_t dst, const CUtensorMap* tm, uint32_t bar, int c0, int c1, int c2, int c3) {
  asm volatile(
      "cp.async.bulk.tensor.4d.shared::cluster.global.mbarrier::complete_tx::bytes [%0], [%1, {%3, %4, %5, %6}], [%2];\n"
      ::"r"(dst), "l"(tm), "r"(bar), "r"(c0), "r"(c1), "r"(c2), "r"(c3) : "memory");
}
__device__ __forceinline__ void tma_load_3d_mc(uint32_t dst, const CUtensorMap* tm, uint32_t bar, int c0, int c1, int c2) {
  asm volatile(
      "cp.async.bulk.tensor.3d.shared::cluster.global.mbarrier::complete_tx::bytes.multicast::cluster [%0], [%1, {%3, %4, %5}], [%2], %6;\n"
      ::"r"(dst), "l"(tm), "r"(bar), "r"(c0), "r"(c1), "r"(c2), "h"((uint16_t)3) : "memory");
}
__device__ __forceinline__ void tma_load_2d(uint32_t dst, const CUtensorMap* tm, uint32_t bar, int c0, int c1) {
  asm volatile(
      "cp.async.bulk.tensor.2d.shared::cluster.global.mbarrier::complete_tx::bytes [%0], [%1, {%3, %4}], [%2];\n"
      ::"r"(dst), "l"(tm), "r"(bar), "r"(c0), "r"(c1) : "memory");
}
__device__ __forceinline__ void bulk_load(uint32_t dst, const void* src, uint32_t bytes, uint32_t bar) {
  asm volatile("cp.async.bulk.shared::cluster.global.mbarrier::complete_tx::bytes [%0], [%1], %2, [%3];\n"
               ::"r"(dst), "l"(src), "r"(bytes), "r"(bar) : "memory");
}
__device__ __forceinline__ void tma_store_2d(const CUtensorMap* tm, uint32_t src, int c0, int c1) {
  asm volatile("cp.async.bulk.tensor.2d.global.shared::cta.bulk_group [%0, {%2, %3}], [%1];\n"
               ::"l"(tm), "r"(src), "r"(c0), "r"(c1) : "memory");
}
__device__ __forceinline__ void tma_store_3d(const CUtensorMap* tm, uint32_t src, int c0, int c1, int c2) {
  asm volatile("cp.async.bulk.tensor.3d.global.shared::cta.bulk_group [%0, {%2, %3, %4}], [%1];\n"
               ::"l"(tm), "r"(src), "r"(c0), "r"(c1), "r"(c2) : "memory");
}
__device__ __forceinline__ void bulk_commit() { asm volatile("cp.async.bulk.commit_group;\n" ::: "memory"); }
__device__ __forceinline__ void bulk_wait0() { asm volatile("cp.async.bulk.wait_group 0;\n" ::: "memory"); }
__device__ __forceinline__ void prefetch_tmap(const CUtensorMap* tm) {
  asm volatile("prefetch.tensormap [%0];\n" ::"l"(tm) : "memory");
}

__device__ __forceinline__ void wg_fence() { asm volatile("wgmma.fence.sync.aligned;\n" ::: "memory"); }
__device__ __forceinline__ void wg_commit() { asm volatile("wgmma.commit_group.sync.aligned;\n" ::: "memory"); }
template <int N> __device__ __forceinline__ void wg_wait() {
  asm volatile("wgmma.wait_group.sync.aligned %0;\n" ::"n"(N) : "memory");
}
__device__ __forceinline__ uint64_t mkdesc(uint32_t addr, uint32_t lbo, uint32_t sbo, uint32_t swz) {
  return (uint64_t)((addr & 0x3FFFF) >> 4) | ((uint64_t)(lbo >> 4) << 16) | ((uint64_t)(sbo >> 4) << 32) |
         ((uint64_t)swz << 62);
}

#define R4(d, o) "+f"(d[o + 0]), "+f"(d[o + 1]), "+f"(d[o + 2]), "+f"(d[o + 3])
#define R8(d, o) R4(d, o), R4(d, o + 4)
#define R16(d, o) R8(d, o), R8(d, o + 8)
#define R32(d, o) R16(d, o), R16(d, o + 16)
#define R64(d, o) R32(d, o), R32(d, o + 32)

__device__ __forceinline__ void wgmma_n192(float (&d)[96], uint64_t da, uint64_t db, uint32_t acc) {
  asm volatile(
      "{\n.reg .pred p;\nsetp.ne.u32 p, %98, 0;\n"
      "wgmma.mma_async.sync.aligned.m64n192k16.f32.bf16.bf16 "
      "{%0,%1,%2,%3,%4,%5,%6,%7,%8,%9,%10,%11,%12,%13,%14,%15,%16,%17,%18,%19,%20,%21,%22,%23,%24,%25,%26,%27,%28,%29,%30,%31,"
      "%32,%33,%34,%35,%36,%37,%38,%39,%40,%41,%42,%43,%44,%45,%46,%47,%48,%49,%50,%51,%52,%53,%54,%55,%56,%57,%58,%59,%60,%61,%62,%63,"
      "%64,%65,%66,%67,%68,%69,%70,%71,%72,%73,%74,%75,%76,%77,%78,%79,%80,%81,%82,%83,%84,%85,%86,%87,%88,%89,%90,%91,%92,%93,%94,%95}, "
      "%96, %97, p, 1, 1, 0, 1;\n}\n"
      : R64(d, 0), R32(d, 64)
      : "l"(da), "l"(db), "r"(acc));
}
__device__ __forceinline__ void wgmma_n128(float (&d)[64], uint64_t da, uint64_t db, uint32_t acc) {
  asm volatile(
      "{\n.reg .pred p;\nsetp.ne.u32 p, %66, 0;\n"
      "wgmma.mma_async.sync.aligned.m64n128k16.f32.bf16.bf16 "
      "{%0,%1,%2,%3,%4,%5,%6,%7,%8,%9,%10,%11,%12,%13,%14,%15,%16,%17,%18,%19,%20,%21,%22,%23,%24,%25,%26,%27,%28,%29,%30,%31,"
      "%32,%33,%34,%35,%36,%37,%38,%39,%40,%41,%42,%43,%44,%45,%46,%47,%48,%49,%50,%51,%52,%53,%54,%55,%56,%57,%58,%59,%60,%61,%62,%63}, "
      "%64, %65, p, 1, 1, 0, 1;\n}\n"
      : R64(d, 0)
      : "l"(da), "l"(db), "r"(acc));
}
template <int N> __device__ __forceinline__ void fence_regs(float (&d)[N]) {
#pragma unroll
  for (int i = 0; i < N; i++) asm volatile("" : "+f"(d[i])::"memory");
}

__device__ __forceinline__ void mma16816(float (&d)[4], uint32_t a0, uint32_t a1, uint32_t a2, uint32_t a3, uint32_t b0,
                                         uint32_t b1) {
  asm("mma.sync.aligned.m16n8k16.row.col.f32.bf16.bf16.f32 {%0,%1,%2,%3}, {%4,%5,%6,%7}, {%8,%9}, {%0,%1,%2,%3};\n"
      : "+f"(d[0]), "+f"(d[1]), "+f"(d[2]), "+f"(d[3])
      : "r"(a0), "r"(a1), "r"(a2), "r"(a3), "r"(b0), "r"(b1));
}
__device__ __forceinline__ void mma16816_z(float (&d)[4], uint32_t a0, uint32_t a1, uint32_t a2, uint32_t a3, uint32_t b0,
                                           uint32_t b1) {
  asm("mma.sync.aligned.m16n8k16.row.col.f32.bf16.bf16.f32 {%0,%1,%2,%3}, {%4,%5,%6,%7}, {%8,%9}, {%10,%10,%10,%10};\n"
      : "=f"(d[0]), "=f"(d[1]), "=f"(d[2]), "=f"(d[3])
      : "r"(a0), "r"(a1), "r"(a2), "r"(a3), "r"(b0), "r"(b1), "f"(0.f));
}
__device__ __forceinline__ void ldsm4t(uint32_t (&r)[4], uint32_t a) {
  asm volatile("ldmatrix.sync.aligned.m8n8.x4.trans.shared.b16 {%0,%1,%2,%3}, [%4];\n"
               : "=r"(r[0]), "=r"(r[1]), "=r"(r[2]), "=r"(r[3]) : "r"(a) : "memory");
}
__device__ __forceinline__ void ldsm2t(uint32_t& r0, uint32_t& r1, uint32_t a) {
  asm volatile("ldmatrix.sync.aligned.m8n8.x2.trans.shared.b16 {%0,%1}, [%2];\n" : "=r"(r0), "=r"(r1) : "r"(a) : "memory");
}
__device__ __forceinline__ void st_async128(uint32_t a, uint32_t bar, uint32_t x, uint32_t y, uint32_t z, uint32_t w) {
  asm volatile("st.async.weak.shared::cluster.mbarrier::complete_tx::bytes.v4.b32 [%0], {%2,%3,%4,%5}, [%1];\n"
               ::"r"(a), "r"(bar), "r"(x), "r"(y), "r"(z), "r"(w) : "memory");
}
__device__ __forceinline__ void mbar_arrive(uint32_t a) {
  asm volatile("mbarrier.arrive.shared::cta.b64 _, [%0];\n" ::"r"(a) : "memory");
}
__device__ __forceinline__ void stsm4(uint32_t a, uint32_t r0, uint32_t r1, uint32_t r2, uint32_t r3) {
  asm volatile("stmatrix.sync.aligned.m8n8.x4.shared.b16 [%0], {%1,%2,%3,%4};\n"
               ::"r"(a), "r"(r0), "r"(r1), "r"(r2), "r"(r3) : "memory");
}
__device__ __forceinline__ void stsm4t(uint32_t a, uint32_t r0, uint32_t r1, uint32_t r2, uint32_t r3) {
  asm volatile("stmatrix.sync.aligned.m8n8.x4.trans.shared.b16 [%0], {%1,%2,%3,%4};\n"
               ::"r"(a), "r"(r0), "r"(r1), "r"(r2), "r"(r3) : "memory");
}
__device__ __forceinline__ uint2 lds64(uint32_t a) {
  uint2 v;
  asm volatile("ld.shared.v2.u32 {%0,%1}, [%2];\n" : "=r"(v.x), "=r"(v.y) : "r"(a));
  return v;
}
__device__ __forceinline__ uint4 lds128(uint32_t a) {
  uint4 v;
  asm volatile("ld.shared.v4.u32 {%0,%1,%2,%3}, [%4];\n" : "=r"(v.x), "=r"(v.y), "=r"(v.z), "=r"(v.w) : "r"(a) : "memory");
  return v;
}
__device__ __forceinline__ void sts128(uint32_t a, uint32_t x, uint32_t y, uint32_t z, uint32_t w) {
  asm volatile("st.shared.v4.u32 [%0], {%1,%2,%3,%4};\n" ::"r"(a), "r"(x), "r"(y), "r"(z), "r"(w) : "memory");
}
__device__ __forceinline__ void sts64(uint32_t a, uint32_t x, uint32_t y) {
  asm volatile("st.shared.v2.u32 [%0], {%1,%2};\n" ::"r"(a), "r"(x), "r"(y) : "memory");
}
__device__ __forceinline__ uint32_t pack_bf16(float lo, float hi) {
  uint32_t r;
  asm("cvt.rn.bf16x2.f32 %0, %1, %2;\n" : "=r"(r) : "f"(hi), "f"(lo));
  return r;
}
__device__ __forceinline__ uint32_t bmul2(uint32_t a, uint32_t b) {
  uint32_t r;
  asm("mul.rn.bf16x2 %0, %1, %2;\n" : "=r"(r) : "r"(a), "r"(b));
  return r;
}
__device__ __forceinline__ uint32_t bmax2(uint32_t a, uint32_t b) {
  uint32_t r;
  asm("max.bf16x2 %0, %1, %2;\n" : "=r"(r) : "r"(a), "r"(b));
  return r;
}
__device__ __forceinline__ uint32_t bfma2(uint32_t a, uint32_t b, uint32_t c) {
  uint32_t r;
  asm("fma.rn.bf16x2 %0, %1, %2, %3;\n" : "=r"(r) : "r"(a), "r"(b), "r"(c));
  return r;
}
__device__ __forceinline__ uint32_t badd2(uint32_t a, uint32_t b) {
  uint32_t r;
  asm("add.rn.bf16x2 %0, %1, %2;\n" : "=r"(r) : "r"(a), "r"(b));
  return r;
}
__device__ __forceinline__ void prefetch_l2(const void* p) { asm volatile("prefetch.global.L2 [%0];\n" ::"l"(p)); }
__device__ __forceinline__ void cp_async16n(uint32_t dst, const void* src) {
  asm volatile("cp.async.cg.shared.global [%0], [%1], 16;\n" ::"r"(dst), "l"(src) : "memory");
}
__device__ __forceinline__ void cp_async16(uint32_t dst, const void* src, uint32_t srcbytes) {
  asm volatile("cp.async.cg.shared.global.L2::256B [%0], [%1], 16, %2;\n" ::"r"(dst), "l"(src), "r"(srcbytes) : "memory");
}
__device__ __forceinline__ uint32_t ld_acquire(const uint32_t* p) {
  uint32_t v;
  asm volatile("ld.acquire.gpu.global.u32 %0, [%1];\n" : "=r"(v) : "l"(p) : "memory");
  return v;
}
__device__ __forceinline__ uint32_t ld_relaxed(const uint32_t* p) {
  uint32_t v;
  asm volatile("ld.relaxed.gpu.global.u32 %0, [%1];\n" : "=r"(v) : "l"(p) : "memory");
  return v;
}
__device__ __forceinline__ void st_release(uint32_t* p, uint32_t v) {
  asm volatile("st.release.gpu.global.u32 [%0], %1;\n" ::"l"(p), "r"(v) : "memory");
}
__device__ __forceinline__ void wait_flag(const uint32_t* p, uint32_t want) {
  int n = 0;
  while (ld_relaxed(p) != want && ++n < SPIN_LIMIT) __nanosleep(40);
  (void)ld_acquire(p);
}

struct Params {
  const __nv_bfloat16* x;
  const __nv_bfloat16* w;
  const __nv_bfloat16* q;
  const __nv_bfloat16* k;
  const __nv_bfloat16* v;
  const __nv_bfloat16* shift_k;
  const __nv_bfloat16* ssm_k;
  const __nv_bfloat16* ssm_D;
  const __nv_bfloat16* wo;
  __nv_bfloat16* out;
  uint32_t zero;
};

__device__ __forceinline__ uint32_t lds32(uint32_t a) {
  uint32_t v;
  asm volatile("ld.shared.u32 %0, [%1];\n" : "=r"(v) : "r"(a));
  return v;
}
__device__ __forceinline__ float bf_lo(uint32_t v) {
  uint32_t r;
  asm("prmt.b32 %0, %1, 0, 0x1044;\n" : "=r"(r) : "r"(v));
  return __uint_as_float(r);
}
__device__ __forceinline__ float bf_hi(uint32_t v) { return __uint_as_float(v & 0xffff0000u); }
__device__ __forceinline__ float ex2(float x) {
  float r;
  asm("ex2.approx.ftz.f32 %0, %1;\n" : "=f"(r) : "f"(x));
  return r;
}
__device__ __forceinline__ float rcp(float x) {
  float r;
  asm("rcp.approx.ftz.f32 %0, %1;\n" : "=f"(r) : "f"(x));
  return r;
}

#define Q4(c, d, o) c(d[o + 0]), c(d[o + 1]), c(d[o + 2]), c(d[o + 3])
#define Q8(c, d, o) Q4(c, d, o), Q4(c, d, o + 4)
#define Q16(c, d, o) Q8(c, d, o), Q8(c, d, o + 8)
#define Q32(c, d) Q16(c, d, 0), Q16(c, d, 16)
#define L8 "{%0,%1,%2,%3,%4,%5,%6,%7}"
#define L16 "{%0,%1,%2,%3,%4,%5,%6,%7,%8,%9,%10,%11,%12,%13,%14,%15}"
#define L32 "{%0,%1,%2,%3,%4,%5,%6,%7,%8,%9,%10,%11,%12,%13,%14,%15,%16,%17,%18,%19,%20,%21,%22,%23,%24,%25,%26,%27,%28,%29,%30,%31}"
__device__ __forceinline__ void fft_rows(uint32_t (&d)[32], const uint32_t (&a)[2][4], uint64_t db) {
  asm volatile("wgmma.mma_async.sync.aligned.m64n128k16.f16.f16.f16 " L32 ", {%32,%33,%34,%35}, %36, 0, 1, 1, 1;\n"
               : Q32("=r", d) : "r"(a[0][0]), "r"(a[0][1]), "r"(a[0][2]), "r"(a[0][3]), "l"(db));
  asm volatile("wgmma.mma_async.sync.aligned.m64n128k16.f16.f16.f16 " L32 ", {%32,%33,%34,%35}, %36, 1, 1, 1, 1;\n"
               : Q32("+r", d) : "r"(a[1][0]), "r"(a[1][1]), "r"(a[1][2]), "r"(a[1][3]), "l"(db + 128));
}
__device__ __forceinline__ void fft_cols(uint32_t (&d)[8], const uint32_t (&a)[2][4], uint64_t db) {
  asm volatile("wgmma.mma_async.sync.aligned.m64n32k16.f16.f16.f16 " L8 ", {%8,%9,%10,%11}, %12, 0, 1, 1, 0;\n"
               : Q8("=r", d, 0) : "r"(a[0][0]), "r"(a[0][1]), "r"(a[0][2]), "r"(a[0][3]), "l"(db));
  asm volatile("wgmma.mma_async.sync.aligned.m64n32k16.f16.f16.f16 " L8 ", {%8,%9,%10,%11}, %12, 1, 1, 1, 0;\n"
               : Q8("+r", d, 0) : "r"(a[1][0]), "r"(a[1][1]), "r"(a[1][2]), "r"(a[1][3]), "l"(db + 64));
}
__device__ __forceinline__ void fft_back(float (&d)[16], uint64_t da, uint64_t db) {
  asm volatile("wgmma.mma_async.sync.aligned.m64n32k16.f32.f16.f16 " L16 ", %16, %17, 0, 1, 1, 1, 1;\n"
               : Q16("=f", d, 0) : "l"(da), "l"(db));
#pragma unroll
  for (int i = 1; i < 4; i++)
    asm volatile("wgmma.mma_async.sync.aligned.m64n32k16.f32.f16.f16 " L16 ", %16, %17, 1, 1, 1, 1, 1;\n"
                 : Q16("+f", d, 0) : "l"(da + 32 * i), "l"(db + 64 * i));
}
__device__ __forceinline__ uint32_t hmul2(uint32_t a, uint32_t b) {
  uint32_t r;
  asm("mul.rn.f16x2 %0, %1, %2;\n" : "=r"(r) : "r"(a), "r"(b));
  return r;
}
__device__ __forceinline__ uint32_t hadd2(uint32_t a, uint32_t b) {
  uint32_t r;
  asm("add.rn.f16x2 %0, %1, %2;\n" : "=r"(r) : "r"(a), "r"(b));
  return r;
}
__device__ __forceinline__ uint32_t hneg2(uint32_t a) {
  uint32_t r;
  asm("neg.f16x2 %0, %1;\n" : "=r"(r) : "r"(a));
  return r;
}
__device__ __forceinline__ uint32_t hfma2(uint32_t a, uint32_t b, uint32_t c) {
  uint32_t r;
  asm("fma.rn.f16x2 %0, %1, %2, %3;\n" : "=r"(r) : "r"(a), "r"(b), "r"(c));
  return r;
}
__device__ __forceinline__ uint32_t pack_f16(float lo, float hi) {
  uint32_t r;
  asm("cvt.rn.f16x2.f32 %0, %1, %2;\n" : "=r"(r) : "f"(hi), "f"(lo));
  return r;
}
__device__ __forceinline__ uint32_t bmaxabs2(uint32_t a, uint32_t b) {
  uint32_t r;
  asm("max.xorsign.abs.bf16x2 %0, %1, %2;\n" : "=r"(r) : "r"(a), "r"(b));
  return r;
}
struct C2 { uint32_t r, i; };
__device__ __forceinline__ C2 cmul(C2 a, C2 b) {
  return C2{hfma2(a.r, b.r, hneg2(hmul2(a.i, b.i))), hfma2(a.r, b.i, hmul2(a.i, b.r))};
}
__device__ __forceinline__ C2 cfma(C2 a, C2 b, C2 c) {
  return C2{hfma2(a.r, b.r, hfma2(hneg2(a.i), b.i, c.r)), hfma2(a.r, b.i, hfma2(a.i, b.r, c.i))};
}
__device__ __forceinline__ C2 cget(const uint32_t (&e)[8], int j, int b) { return C2{e[4 * j + b], e[4 * j + 2 + b]}; }
template <int N> __device__ __forceinline__ void fence_regs(uint32_t (&d)[N]) {
#pragma unroll
  for (int i = 0; i < N; i++) asm volatile("" : "+r"(d[i])::"memory");
}
__device__ __forceinline__ void ldsm4(uint32_t (&r)[4], uint32_t a) {
  asm volatile("ldmatrix.sync.aligned.m8n8.x4.shared.b16 {%0,%1,%2,%3}, [%4];\n"
               : "=r"(r[0]), "=r"(r[1]), "=r"(r[2]), "=r"(r[3]) : "r"(a) : "memory");
}

__device__ __forceinline__ uint32_t movm(uint32_t a) {
  uint32_t r;
  asm volatile("movmatrix.sync.aligned.m8n8.trans.b16 %0, %1;\n" : "=r"(r) : "r"(a));
  return r;
}
template <int C0, int H, bool T> __device__ __forceinline__ void attn_pack(const float (&acc)[96], uint32_t (&d)[8]) {
#pragma unroll
  for (int c = 0; c < 8; c++) {
    asm volatile("cvt.rn.bf16x2.f32 %0, %1, %2;\n" : "=r"(d[c]) : "f"(acc[4 * (C0 + c) + 2 * H + 1]), "f"(acc[4 * (C0 + c) + 2 * H]));
    if (T) d[c] = movm(d[c]);
  }
}
__device__ __forceinline__ void attn_qk(float (&s)[4], const uint32_t (&qlo)[8], const uint32_t (&qhi)[8],
                                        const uint32_t (&k)[8], int c) {
  mma16816_z(s, qlo[c], qhi[c], qlo[c + 1], qhi[c + 1], k[c], k[c + 1]);
  mma16816(s, qlo[c + 2], qhi[c + 2], qlo[c + 3], qhi[c + 3], k[c + 2], k[c + 3]);
}
template <int N> __device__ __forceinline__ void quad_softmax(float (&x)[N][2], uint32_t (&pp)[N]) {
  const float c2 = 1.4426950408889634f;
  uint32_t q[N], mx[N / 2];
#pragma unroll
  for (int n = 0; n < N; n++) {
    const uint32_t r = pack_bf16(x[n][0], x[n][1]);
    q[n] = bfma2(r, 0x3e353e35u, bmul2(r, 0x379e379eu));
    x[n][0] = bf_lo(q[n]);
    x[n][1] = bf_hi(q[n]);
  }
#pragma unroll
  for (int n = 0; n < N / 2; n++)
    mx[n] = bmax2(__byte_perm(q[2 * n], q[2 * n + 1], 0x5410), __byte_perm(q[2 * n], q[2 * n + 1], 0x7632));
#pragma unroll
  for (int o = 1; o <= 2; o++) {
#pragma unroll
    for (int n = 0; n < N / 2; n++) mx[n] = bmax2(mx[n], __shfl_xor_sync(0xffffffffu, mx[n], o));
  }
  float m[N], t[N];
#pragma unroll
  for (int n = 0; n < N / 2; n++) {
    m[2 * n] = bf_lo(mx[n]);
    m[2 * n + 1] = bf_hi(mx[n]);
  }
#pragma unroll
  for (int n = 0; n < N; n++) {
    const float nm = -m[n] * c2;
    x[n][0] = ex2(fmaf(x[n][0], c2, nm));
    x[n][1] = ex2(fmaf(x[n][1], c2, nm));
  }
#pragma unroll
  for (int n = 0; n < N; n += 2) {
    float u0, u1;
    asm("mma.sync.aligned.m16n8k8.row.col.f32.tf32.tf32.f32 {%0,%1,%2,%3}, {%4,%5,%6,%7}, {%8,%8}, {%9,%9,%9,%9};\n"
        : "=f"(t[n]), "=f"(u0), "=f"(t[n + 1]), "=f"(u1)
        : "r"(__float_as_uint(x[n][0])), "r"(__float_as_uint(x[n + 1][0])), "r"(__float_as_uint(x[n][1])),
          "r"(__float_as_uint(x[n + 1][1])), "r"(0x3f800000u), "f"(0.f));
  }
#pragma unroll
  for (int n = 0; n < N; n++) {
    const float inv = rcp(t[n]);
    pp[n] = pack_bf16(x[n][0] * inv, x[n][1] * inv);
  }
}
__device__ __forceinline__ void attn_pv(uint32_t dst, const uint32_t (&vp)[8], const uint32_t (&vo)[8], int c, uint32_t pp,
                                        uint32_t maskLE) {
  const uint32_t b0 = pp & ~maskLE, b1 = pp & maskLE;
  float oa[4], ob[4];
  mma16816_z(oa, vp[c], vp[c + 1], vo[c], vo[c + 1], b0, b1);
  mma16816_z(ob, vp[c + 2], vp[c + 3], vo[c + 2], vo[c + 3], b0, b1);
  stsm4t(dst, pack_bf16(oa[0], oa[1]), pack_bf16(oa[2], oa[3]), pack_bf16(ob[0], ob[1]), pack_bf16(ob[2], ob[3]));
}

template <int MODE>
__global__ void __cluster_dims__(2, 1, 1) __launch_bounds__(NTHREADS, 1)
fused_kernel(const Params p, const __grid_constant__ CUtensorMap tmX, const __grid_constant__ CUtensorMap tmW,
             const __grid_constant__ CUtensorMap tmWo,
             const __grid_constant__ CUtensorMap tmQ, const __grid_constant__ CUtensorMap tmOa,
             const __grid_constant__ CUtensorMap tmOb,
             const __grid_constant__ CUtensorMap tmXh, const __grid_constant__ CUtensorMap tmWh) {
  extern __shared__ __align__(1024) uint8_t smem[];
  if (threadIdx.x < 32) {
    const uint32_t i = (blockIdx.x & 127) * 16 + (threadIdx.x & 15);
    prefetch_l2(threadIdx.x & 16 ? (const char*)p.w + i * 128 : (const char*)p.x + i * 2048);
  }
  const uint32_t sb = smem_u32(smem);
  const uint32_t bars = sb + OFF_BAR;
  const int tid = threadIdx.x, lane = tid & 31, warp = __shfl_sync(0xffffffffu, tid >> 5, 0);
  const int rank = blockIdx.x & 1;
  const bool halo_cta = blockIdx.x < 4;
  if (halo_cta && MODE != 0) return;
  int grp, mem;
  {
    const int t = (blockIdx.x >> 1) - 4, u = t - 32;
    const int q7 = (u * 37) >> 8;
    const bool lo = (unsigned)t < 32u, mid = (unsigned)u < 28u;
    grp = lo ? (t & 7) : (mid ? 1 + u - 7 * q7 : 0);
    mem = lo ? (t >> 3) : (mid ? 4 + q7 : (t < 0 ? t + 6 : t - 54));
  }
  const int rg = (grp >> 2) * 4 + (mem >> 1), hp = (grp & 3) * 4 + (mem & 1) * 2 + rank;
  const int rb2 = (grp >> 2) * 8 + mem, cb2 = (grp & 3) * 2 + rank;
  const int chb = grp * 16 + mem * 2 + rank;
  const int cta = rg * 16 + hp;
  const int g2wg = 0;
  const int par = rg >> 2, gidx = rg & 3;

  if (tid < 256 && !halo_cta && MODE != 2) {
    const int r = tid >> 3, c = tid & 7;
    const uint32_t so = r * 128 + ((c ^ (r & 7)) << 4);
    const __nv_bfloat16* wg0 = p.w + (size_t)r * (3 * DM) + hp * 64 + c * 8;
    const __nv_bfloat16* xg0 = p.x + (size_t)(2 * (gidx * 256 + r) + par) * DM + c * 8;
#pragma unroll
    for (int j = 0; j < 3; j++) cp_async16n(sb + OFF_1B + j * 4096 + so, wg0 + j * DM);
#pragma unroll
    for (int i = 0; i < 8; i++) cp_async16n(sb + i * 4096 + so, xg0 + (size_t)i * 64 * DM);
    asm volatile("cp.async.commit_group;\n" ::: "memory");
  }
  auto halo_issue = [&](int kb, int s) {
    const uint32_t fb = bars + 8 * (BAR_FULLB + s), st = sb + s * STGH;
    mbar_expect_tx(fb, STGH - 2048);
    tma_load_3d(st + 8192, &tmWh, fb, 0, kb * 64, 16 + blockIdx.x * 4);
    tma_load_3d(st + 8192 + 32768, &tmWh, fb, 0, kb * 64, 32 + blockIdx.x * 4);
    tma_load_4d(st, &tmXh, fb, kb * 64, 248, 0, 0);
  };
  if (tid == 256) {
    prefetch_tmap(halo_cta ? &tmXh : &tmX);
#pragma unroll
    for (int i = 0; i < NS1B; i++) mbar_init(bars + 8 * (BAR_FULLB + i), 1);
#pragma unroll
    for (int i = 0; i < NS1A; i++) mbar_init(bars + 8 * (BAR_FULLA + i), 1);
    asm volatile("fence.mbarrier_init.release.cluster;\n" ::: "memory");
    if (!halo_cta && MODE != 2) {
      mbar_expect_tx(bars + 8 * (BAR_FULLB + 1), STG1B);
      tma_load_3d(sb + OFF_1B + 1 * STG1B, &tmW, bars + 8 * (BAR_FULLB + 1), hp * 64, 32, 0);
      mbar_expect_tx(bars + 8 * (BAR_FULLB + 2), STG1B);
      tma_load_3d(sb + OFF_1B + 2 * STG1B, &tmW, bars + 8 * (BAR_FULLB + 2), hp * 64, 64, 0);
    } else if (halo_cta) {
      halo_issue(0, 0);
    }
  } else if (tid == 288) {
#pragma unroll
    for (int i = 0; i < NS1A; i++) mbar_init(bars + 8 * (BAR_EMPTYA + i), 4);
#pragma unroll
    for (int i = 0; i < NS1B; i++) mbar_init(bars + 8 * (BAR_EMPTYB + i), 2);
    mbar_init(bars + 8 * BAR_X, 4);
    mbar_init(bars + 8 * BAR_LAND, 17);
    mbar_init(bars + 8 * BAR_U, 1);
    mbar_init(bars + 8 * BAR_Q, 1);
    mbar_init(bars + 8 * BAR_STG, 8);
    mbar_init(bars + 8 * BAR_HALO, 1);
    asm volatile("fence.mbarrier_init.release.cluster;\n" ::: "memory");
  } else if (tid == 320) {
#pragma unroll
    for (int i = 0; i < NS2; i++) {
      mbar_init(bars + 8 * (BAR_FULL2 + i), 1);
      mbar_init(bars + 8 * (BAR_EMPTY2 + i), 2);
    }
    asm volatile("fence.mbarrier_init.release.cluster;\n" ::: "memory");
  } else if (tid == 352) {
#pragma unroll
    for (int i = 0; i < 8; i++) mbar_init(bars + 8 * (BAR_Y + i), 4);
    asm volatile("fence.mbarrier_init.release.cluster;\n" ::: "memory");
  }
  if (warp == 8) PROF2(23);
  cluster_sync_all();
  if (warp == 8) PROF2(24);

  if (warp >= 8) {
    const int hw = warp - 8;
    const int lr = lane & 7, lm = lane >> 3;
    auto g1_issue_a = [&](int j, int s) {
      const uint32_t fb = bars + 8 * (BAR_FULLA + s);
      mbar_expect_tx(fb, STG1A);
      tma_load_3d_mc(sb + s * STG1A + rank * 16384, &tmX, fb, j * 64, par, gidx * 256 + rank * 128);
    };
    auto g1_issue_b = [&](int kb, int s) {
      const uint32_t fb = bars + 8 * (BAR_FULLB + s);
      mbar_expect_tx(fb, STG1B);
      tma_load_3d(sb + OFF_1B + s * STG1B, &tmW, fb, hp * 64, kb * 32, 0);
    };
    asm volatile("setmaxnreg.dec.sync.aligned.u32 %0;\n" :: "n"(REG_HELP));

    if (halo_cta) {
      if (hw == 0) {
        int s = 1, ph = 1;
#pragma unroll 1
        for (int kb = 1; kb < 16; kb++) {
          mbar_wait(bars + 8 * (BAR_EMPTYB + s), ph);
          if (elect_one()) halo_issue(kb, s);
          if (++s == 3) { s = 0; ph ^= 1; }
        }
      }
      __syncwarp();
    } else if (hw == 0) {
      if (MODE == 2) {
        if (lane < NS2) mbar_arrive_cluster_n(mapa(bars, rank) + 8 * (BAR_EMPTY2 + lane), 2);
      } else {
      uint32_t epoch = 0;
      if (lane == 0) {
        mbar_expect_tx(bars + 8 * BAR_U, 32768);
        mbar_expect_tx(bars + 8 * BAR_LAND, 16384);
        mbar_expect_tx(bars + 8 * BAR_Q, 32768);
      }
      {
        int sa = 1, pha = 1, sbb = 2, phb = 1;
#pragma unroll 1
        for (int kb = 2; kb < 32; kb++) {
          if (!(kb & 1)) {
            mbar_wait(bars + 8 * (BAR_EMPTYA + sa), pha);
            if (elect_one()) g1_issue_a(kb >> 1, sa);
            if (++sa == NS1A) { sa = 0; pha ^= 1; }
          }
          mbar_wait(bars + 8 * (BAR_EMPTYB + sbb), phb);
          if (kb > 2 && elect_one()) g1_issue_b(kb, sbb);
          __syncwarp();
          if (kb == 4) epoch = ld_relaxed(g_flag_o + cta);
          if (kb == 4) PROF2(27);
          if (kb == 1) PROF2(38);
          if (kb == 2) PROF2(39);
          if (++sbb == NS1B) { sbb = 0; phb ^= 1; }
        }
      }
      epoch++;
      if (lane == 0) {
        prefetch_tmap(&tmWo);
        prefetch_tmap(&tmQ);
        prefetch_tmap(&tmOa);
        prefetch_tmap(&tmOb);
        if (gidx != 0) wait_flag(g_flag_h + (hp >> 2), epoch);
      }
      __syncwarp();
      {
        uint4 hk0 = make_uint4(0, 0, 0, 0), hk1 = hk0, hv0 = hk0, hv1 = hk0;
        if (gidx != 0) {
          const uint4* src = g_halo + cta * 128 + lane;
          hk0 = __ldcg(src); hk1 = __ldcg(src + 32); hv0 = __ldcg(src + 64); hv1 = __ldcg(src + 96);
        }
        if (gidx != 0) PROF(18);
        sts128(sb + OFF_L0 + lane * 16, hk0.x, hk0.y, hk0.z, hk0.w);
        sts128(sb + OFF_L0 + 512 + lane * 16, hk1.x, hk1.y, hk1.z, hk1.w);
        sts64(sb + OFF_L0 + 1024 + lane * 8, movm(hv0.x), movm(hv0.y));
        sts64(sb + OFF_L0 + 1280 + lane * 8, movm(hv0.z), movm(hv0.w));
        sts64(sb + OFF_L0 + 1536 + lane * 8, movm(hv1.x), movm(hv1.y));
        sts64(sb + OFF_L0 + 1792 + lane * 8, movm(hv1.z), movm(hv1.w));
        __syncwarp();
        if (lane == 0) mbar_arrive(bars + 8 * BAR_HALO);
      }
      const uint32_t rb = mapa(bars, lane & 1);
      nb_sync(NB_OREADY, 288);
      if (lane < 2) {
        mbar_arrive_cluster(rb + 8 * (BAR_EMPTY2 + 0));
        mbar_arrive_cluster(rb + 8 * (BAR_EMPTY2 + 1));
        mbar_arrive_cluster(rb + 8 * (BAR_EMPTY2 + 3));
      }
      if (lane == 0) {
        asm volatile("cp.async.bulk.global.shared::cta.bulk_group [%0], [%1], %2;\n" ::"l"(g_o + (size_t)cta * 16384),
                     "r"(sb + OFF_OP), "r"(32768) : "memory");
        bulk_commit();
        bulk_wait0();
        st_release(g_flag_o + cta, epoch);
      }
      __syncwarp();
      PROF2(17);
      if (lane < 2) mbar_arrive_cluster(rb + 8 * (BAR_EMPTY2 + 2));
      if (lane < 16 && MODE == 0) wait_flag(g_flag_o + (rb2 >> 1) * 16 + lane, epoch);
      }
      __syncwarp();
      PROF(21);
      if (MODE != 1) {
        fence_async_all();
        const __nv_bfloat16* osrc = g_o + (size_t)(rb2 >> 1) * 16 * 16384 + ((rb2 & 1) * 2 + rank) * 4096;
#pragma unroll 1
        for (int kb = 0; kb < 16; kb++) {
          const int s = (int)(G2_STAGE >> (4 * kb)) & 7;
          const uint32_t fb = bars + 8 * (BAR_FULL2 + s);
          const uint32_t st = sb + s * STG2;
          mbar_wait(bars + 8 * (BAR_EMPTY2 + s), (G2_PARITY >> kb) & 1);
          if (elect_one()) {
            mbar_expect_tx(fb, STG2);
            asm volatile(
                "cp.async.bulk.shared::cluster.global.mbarrier::complete_tx::bytes.multicast::cluster [%0], [%1], %2, [%3], %4;\n"
                ::"r"(st + rank * 8192), "l"(osrc), "r"(8192), "r"(fb), "h"((uint16_t)3) : "memory");
            tma_load_3d(st + 16384, &tmWo, fb, 0, kb * 64, cb2 * 2);
          }
          osrc += 16384;
        }
      }
      __syncwarp();
    } else if (MODE != 2) {
      {
        const int g = lane >> 2, t = lane & 3;
        uint32_t w[2][4];
#pragma unroll
        for (int h = 0; h < 2; h++) {
          const uint2 x = __ldg(reinterpret_cast<const uint2*>(p.shift_k + ((chb & ~1) * 8 + h * 8 + g) * 4));
          w[h][0] = __byte_perm(x.x, x.x, 0x1010);
          w[h][1] = __byte_perm(x.x, x.x, 0x3232);
          w[h][2] = __byte_perm(x.y, x.y, 0x1010);
          w[h][3] = __byte_perm(x.y, x.y, 0x3232);
        }
        auto swz = [](int r) { return (((r & 29) | ((r ^ (r >> 2)) & 2)) << 5) | (r & 16); };
        const uint32_t kring = sb + OFF_X + 4096 + (hw - 1) * 2 * XT, vring = kring + XT;
        const int s0 = rank * 32 + (hw - 1) * 11, s1 = hw == 3 ? rank * 32 + 32 : s0 + 11;
        const size_t goff = (size_t)(lane >> 1) * DM + (chb & ~1) * 8 + (lane & 1) * 8;
        const __nv_bfloat16* kg = p.k + goff;
        const __nv_bfloat16* vg = p.v + goff;
        const uint32_t d0 = swz(lane >> 1) ^ ((lane & 1) << 4), d1 = swz(16 + (lane >> 1)) ^ ((lane & 1) << 4);
        auto issue = [&](int st) {
          const uint32_t so = (st & 3) << 10;
          cp_async16(kring + so + d0, kg + (size_t)st * 32 * DM, 16);
          cp_async16(kring + so + d1, kg + (size_t)(st * 32 + 16) * DM, 16);
          cp_async16(vring + so + d0, vg + (size_t)st * 32 * DM, 16);
          cp_async16(vring + so + d1, vg + (size_t)(st * 32 + 16) * DM, 16);
        };
        const int xa = 8 * (lr >> 1) + 2 * lm + (lr & 1), xb = 8 * (lr >> 1) - 4 + 2 * (lm & 1) + (lr & 1);
        const uint32_t la = swz(xa), lb = swz(xb & 31);
        const int backb = xb < 0 ? 1 : 0;
        const uint32_t ud[2] = {mapa(sb + OFF_X + g * XT + t * 16, 0), mapa(sb + OFF_X + g * XT + t * 16, 1)};
        const uint32_t ub[2] = {mapa(bars + 8 * BAR_U, 0), mapa(bars + 8 * BAR_U, 1)};
        if (lane == 0) mbar_wait(bars + 8 * (BAR_FULLB + NS1B - 1), 0);
        __syncwarp();
        if (lane >= 24) cp_async16(kring + (((s0 - 1) & 3) << 10) + d1, s0 > 0 ? kg + (size_t)(s0 * 32 - 16) * DM : kg, s0 > 0 ? 16 : 0);
        issue(s0);
        asm volatile("cp.async.commit_group;\n" ::: "memory");
        issue(s0 + 1);
        asm volatile("cp.async.commit_group;\n" ::: "memory");
#pragma unroll 1
        for (int st = s0; st < s1; st++) {
          if (st + 2 < s1) issue(st + 2);
          if (hw == 1 && st - s0 < 8) prefetch_l2(p.ssm_k + (size_t)(chb * 8 + st - s0) * SEQ + lane * 64);
          asm volatile("cp.async.commit_group;\n" ::: "memory");
          asm volatile("cp.async.wait_group 2;\n" ::: "memory");
          __syncwarp();
#pragma unroll
          for (int h = 0; h < 2; h++) {
            uint32_t e[6], vv[4], e4[4];
            ldsm4t(e4, kring + ((st & 3) << 10) + (la ^ (h << 4)));
            ldsm2t(e[0], e[1], kring + (((st - backb) & 3) << 10) + (lb ^ (h << 4)));
            ldsm4t(vv, vring + ((st & 3) << 10) + (la ^ (h << 4)));
            e[2] = e4[0]; e[3] = e4[1]; e[4] = e4[2]; e[5] = e4[3];
            uint32_t o[5];
#pragma unroll
            for (int i = 0; i < 5; i++) o[i] = __byte_perm(e[i], e[i + 1], 0x5432);
#pragma unroll
            for (int i = 0; i < 4; i++) {
              uint32_t a = bmul2(o[i], w[h][3]);
              a = bfma2(e[i + 1], w[h][2], a);
              a = bfma2(o[i + 1], w[h][1], a);
              a = bfma2(e[i + 2], w[h][0], a);
              vv[i] = bmul2(a, vv[i]);
            }
            st_async128(ud[h] + (st ^ (g & 1)) * 64, ub[h], vv[0], vv[1], vv[2], vv[3]);
          }
          __syncwarp();
        }
        PROF(16);
      }
      nb_sync(NB_HELP3, 96);
      {
        const int ck = 16 * (lane >> 4) + 2 * lr + (((lane >> 3) ^ (lane >> 2)) & 1);
        const uint32_t xo = (ck >> 1) * 128, xs = ((ck & 1) ^ lr) << 4;
#pragma unroll 1
        for (int job = hw - 1; job < 16; job += 3) {
          const int c = job & 7;
          uint4 a[8];
          float dv = 0.f;
          if (job < 8) {
            const uint4* src = reinterpret_cast<const uint4*>(p.ssm_k + (size_t)(chb * 8 + c) * SEQ) + ck;
#pragma unroll
            for (int i = 0; i < 8; i++) a[i] = __ldcg(src + 32 * i);
            if (lane == 0) dv = __bfloat162float(p.ssm_D[chb * 8 + c]);
            prefetch_l2(p.q + (size_t)chb * 16384 + c * 2048 + lane * 64);
            if (lane < 16) prefetch_l2(p.wo + (size_t)chb * 8192 + c * 1024 + lane * 64);
          } else {
            mbar_wait(bars + 8 * BAR_U, 0);
#pragma unroll
            for (int i = 0; i < 8; i++) a[i] = lds128(sb + OFF_X + c * XT + i * 512 + ((ck ^ ((c & 1) << 2)) << 4));
          }
          uint32_t m = pack_bf16(bf_lo(a[0].x) + dv, 0.f);
#pragma unroll
          for (int i = 0; i < 8; i++) m = bmaxabs2(bmaxabs2(m, bmaxabs2(a[i].x, a[i].y)), bmaxabs2(a[i].z, a[i].w));
          m = __reduce_max_sync(0xffffffffu, max(m & 0x7fffu, (m >> 16) & 0x7fffu));
          const uint32_t f = max(252 - (int)(m >> 7), 1), mul = f * 0x00800080u;
          if (lane == 0) asm volatile("st.shared.u32 [%0], %1;\n" ::"r"(sb + OFF_EX + job * 4), "r"(f) : "memory");
          auto cv = [&](uint32_t x) {
            x = bmul2(x, mul);
            return pack_f16(bf_lo(x), bf_hi(x));
          };
          const uint32_t x0 = bmul2(a[0].x, mul);
          const uint32_t dst = sb + OFF_X + c * XT + (job < 8 ? 4096 : 0) + xo;
#pragma unroll
          for (int i = 0; i < 8; i++)
            sts128(dst + (i & 1) * 2048 + (xs ^ ((i >> 1) << 5)),
                   i ? cv(a[i].x) : pack_f16(fmaf(dv, __uint_as_float(f << 23), bf_lo(x0)), bf_hi(x0)), cv(a[i].y), cv(a[i].z),
                   cv(a[i].w));
        }
        fence_async_smem();
        __syncwarp();
        if (lane == 0) mbar_arrive(bars + 8 * BAR_X);
        PROF(19);
      }
      if (hw == 3) {
        nb_sync(NB_G1DONE, 288);
        if (elect_one()) {
          mbar_expect_tx(bars + 8 * BAR_X, 8192);
          bulk_load(sb + OFF_TAB, g_tab, 8192, bars + 8 * BAR_X);
        }
      } else {
        const uint32_t peer = mapa(sb, rank ^ 1);
#pragma unroll 1
        for (int ch = hw * 4 - 4; ch < hw * 4; ch++) {
          const uint32_t o = OFF_X + ch * XT + (rank ^ 1) * 4096;
          uint4 a[4];
          mbar_wait(bars + 8 * (BAR_Y + ch), 0);
#pragma unroll
          for (int i = 0; i < 4; i++) a[i] = lds128(sb + o + (i >> 1) * 2048 + (i & 1) * 512 + lane * 16);
#pragma unroll
          for (int i = 0; i < 4; i++)
            st_async128(peer + o + 1024 + (i >> 1) * 2048 + (i & 1) * 512 + lane * 16, peer + OFF_BAR + 8 * BAR_LAND, a[i].x,
                        a[i].y, a[i].z, a[i].w);
          fence_async_smem();
          __syncwarp();
          if (elect_one()) tma_load_2d(sb + o, &tmQ, bars + 8 * BAR_Q, (chb & ~1) * 8, rank * 1024 + ch * 128);
        }
      }
      nb_sync(NB_HELP3, 96);
      PROF(32);
      {
        const int c8 = (4 * (lr >> 1) + 2 * (lm & 1) + (lr & 1)) & 7;
        const uint32_t ya = sb + OFF_X + c8 * XT + rank * 4096 + ((lr >> 2) == rank ? 0 : 1024);
        const uint32_t yx = ((lm >> 1) ^ c8 ^ ((lr >> 2) << 1)) << 4;
        const uint32_t qa = sb + OFF_X + (rank ^ 1) * 4096;
        mbar_wait(bars + 8 * BAR_LAND, 0);
        if (hw == 3 && lane < 2) mbar_arrive_cluster(mapa(bars, lane) + 8 * (BAR_EMPTY2 + 4));
        mbar_wait(bars + 8 * BAR_Q, 0);
        PROF2(33);
#pragma unroll 1
        for (int j = hw - 1; j < 16; j += 3) {
          uint32_t y[4][4];
          uint2 q[8];
          const uint32_t qj = qa + (j >> 1) * XT + (j & 1) * 2048;
#pragma unroll
          for (int i = 0; i < 4; i++) ldsm4t(y[i], ya + (j >> 3) * 2048 + (j & 7) * 128 + (yx ^ ((j & 1) << 4) ^ (i << 5)));
#pragma unroll
          for (int i = 0; i < 8; i++) q[i] = lds64(qj + i * 256 + lane * 8);
#pragma unroll
          for (int i = 0; i < 8; i++) {
            const uint2 o = make_uint2(bmul2(q[i].x, y[i >> 1][2 * (i & 1)]), bmul2(q[i].y, y[i >> 1][2 * (i & 1) + 1]));
            sts64(qj + i * 256 + lane * 8, o.x, o.y);
          }
          fence_async_smem();
          __syncwarp();
          if (elect_one()) {
            tma_store_2d(&tmOa, qj, (chb & ~1) * 8, rank * 1024 + j * 64);
            bulk_commit();
          }
        }
        bulk_wait0();
      }
      PROF(22);
    }
    cluster_sync_all();
  } else {
    asm volatile("setmaxnreg.inc.sync.aligned.u32 %0;\n" :: "n"(REG_MATH));
    if (warp == 0) PROF2(26);
    const int wg = warp >> 2;
    const int wtid = tid & 127;
    const bool signaller = (wtid == 0) || (wtid == 32);
    const uint32_t rbars = mapa(bars, wtid >> 5 & 1);

    if (halo_cta) {
      const uint32_t epoch = ld_relaxed(g_flag_h + blockIdx.x) + 1;
      float acc0[64], acc1[64];
      int s = 0, ph = 0;
#pragma unroll 1
      for (int kb = 0; kb < 16; kb++) {
        mbar_wait(bars + 8 * (BAR_FULLB + s), ph);
        const uint32_t st = sb + s * STGH;
        const uint64_t da = mkdesc(st, 16, 1024, 1);
        const uint64_t db = mkdesc(st + 8192 + wg * 32768, 8192, 1024, 1);
        wg_fence();
#pragma unroll
        for (int kk = 0; kk < 4; kk++) {
          wgmma_n128(acc0, da + 2 * kk, db + 128 * kk, kb + kk);
          wgmma_n128(acc1, da + 2 * kk, db + 1024 + 128 * kk, kb + kk);
        }
        wg_commit();
        wg_wait<0>();
        if (kb == 15) PROF(37);
        if (wtid == 0) mbar_arrive(bars + 8 * (BAR_EMPTYB + s));
        if (++s == 3) { s = 0; ph ^= 1; }
      }
      fence_regs(acc0);
      fence_regs(acc1);
      if ((warp & 3) != 3) {
#pragma unroll
        for (int hh = 0; hh < 2; hh++) {
          uint4* dst = g_halo + ((hh * 4 + (warp & 3) + 1) * 16 + blockIdx.x * 4) * 128 + wg * 64 + lane;
#pragma unroll
          for (int j = 0; j < 4; j++) {
            const int o = 16 * j + 2 * hh;
            dst[(j >> 1) * 128 + (j & 1) * 32] =
                make_uint4(pack_bf16(acc0[o], acc0[o + 1]), pack_bf16(acc0[o + 4], acc0[o + 5]),
                           pack_bf16(acc0[o + 8], acc0[o + 9]), pack_bf16(acc0[o + 12], acc0[o + 13]));
            dst[(2 + (j >> 1)) * 128 + (j & 1) * 32] =
                make_uint4(pack_bf16(acc1[o], acc1[o + 1]), pack_bf16(acc1[o + 4], acc1[o + 5]),
                           pack_bf16(acc1[o + 8], acc1[o + 9]), pack_bf16(acc1[o + 12], acc1[o + 13]));
          }
        }
      }
      nb_sync(NB_G1DONE, 256);
      if (tid == 0) st_release(g_flag_h + blockIdx.x, epoch);
      PROF(36);
      cluster_sync_all();
      return;
    }

    if (MODE != 2) {
    {
      float acc0[96], acc1[96];
      int sa = 0, pha = 0, sbb = 0, phb = 0;
      asm volatile("cp.async.wait_group 0;\n" ::: "memory");
      fence_async_smem();
      nb_sync(NB_FIRST, 256);
      if (tid == 0) {
        mbar_arrive(bars + 8 * BAR_FULLA);
        mbar_arrive(bars + 8 * BAR_FULLB);
      }
      PROF(0 + wg);
#pragma unroll 1
      for (int kb = 0; kb < 30; kb++) {
        if (!(kb & 1)) mbar_wait(bars + 8 * (BAR_FULLA + sa), pha);
        mbar_wait(bars + 8 * (BAR_FULLB + sbb), phb);
        if (kb == 0) PROF2(0 + wg);
        if (kb == 4 && wg == 0) PROF2(28);
        if (kb == 8 && wg == 0) PROF2(29);
        if (kb == 16 && wg == 0) PROF2(30);
        const uint64_t da = mkdesc(sb + sa * STG1A + wg * 16384 + (kb & 1) * 64, 16, 2048, 1);
        const uint64_t db = mkdesc(sb + OFF_1B + sbb * STG1B, 4096, 1024, 1);
        wg_fence();
        wgmma_n192(acc0, da + 64, db, kb);
        wgmma_n192(acc1, da, db, kb);
        wgmma_n192(acc0, da + 66, db + 128, 1);
        wgmma_n192(acc1, da + 2, db + 128, 1);
        wg_commit();
        wg_wait<1>();
        if (kb > 0) {
          if (wtid == 64) mbar_arrive(bars + 8 * (BAR_EMPTYB + (sbb == 0 ? NS1B - 1 : sbb - 1)));
          if (!(kb & 1) && signaller) mbar_arrive_cluster(rbars + 8 * (BAR_EMPTYA + (sa == 0 ? NS1A - 1 : sa - 1)));
        }
        if (++sbb == NS1B) { sbb = 0; phb ^= 1; }
        if ((kb & 1) && ++sa == NS1A) { sa = 0; pha ^= 1; }
      }
      const int lr = lane & 7, lm = lane >> 3;
      const bool le0 = 2 * (lane & 3) <= (lane >> 2), le1 = 2 * (lane & 3) + 1 <= (lane >> 2);
      const uint32_t maskLE = (le0 ? 0x0000FFFFu : 0u) | (le1 ? 0xFFFF0000u : 0u);
      uint32_t q[4][8], k[5][8], vt[5][8];
      {
        static_assert(15 % NS1A == 0 && 30 % NS1B == 0, "slots of the last k blocks");
        mbar_wait(bars + 8 * BAR_FULLA, 1);
        mbar_wait(bars + 8 * BAR_FULLB, 0);
        mbar_wait(bars + 8 * (BAR_FULLB + 1), 0);
        const uint64_t da = mkdesc(sb + wg * 16384, 16, 2048, 1);
        const uint64_t db = mkdesc(sb + OFF_1B, 4096, 1024, 1);
        wg_fence();
#pragma unroll
        for (int i = 0; i < 4; i++) wgmma_n192(acc0, da + 64 + 2 * i, db + (i >> 1) * (STG1B >> 4) + (i & 1) * 128, 1);
        wg_commit();
        wg_wait<1>();
        nb_arrive(NB_G1DONE, 288);
#pragma unroll
        for (int i = 0; i < 2; i++) wgmma_n192(acc1, da + 2 * i, db + (i >> 1) * (STG1B >> 4) + (i & 1) * 128, 1);
        wg_commit();
        wg_wait<1>();
        fence_regs(acc0);
        PROFA(45, 0);
        attn_pack<8, 1, false>(acc0, k[4]);
        attn_pack<16, 1, true>(acc0, vt[4]);
        const uint32_t kh = sb + OFF_KH + warp * 4096 + lane * 16;
        sts128(kh, k[4][0], k[4][1], k[4][2], k[4][3]);
        sts128(kh + 512, k[4][4], k[4][5], k[4][6], k[4][7]);
#pragma unroll
        for (int i = 0; i < 4; i++) sts64(kh - lane * 8 + 1024 + 256 * i, vt[4][2 * i], vt[4][2 * i + 1]);
#pragma unroll
        for (int i = 2; i < 4; i++) wgmma_n192(acc1, da + 2 * i, db + (i >> 1) * (STG1B >> 4) + (i & 1) * 128, 1);
        wg_commit();
        attn_pack<0, 0, false>(acc0, q[1]);
        attn_pack<0, 1, false>(acc0, q[3]);
        attn_pack<8, 0, false>(acc0, k[2]);
        attn_pack<16, 0, true>(acc0, vt[2]);
        uint32_t z = p.zero;
#pragma unroll
        for (int i = 0; i < 8; i++) z &= q[1][i] & q[3][i];
#pragma unroll
        for (int i = 0; i < 8; i += 2) z &= k[2][i] & k[2][i + 1];
        __syncwarp();
        if (lane == 0) mbar_arrive(bars + 8 * BAR_STG + z);
        wg_wait<0>();
        fence_regs(acc1);
      }
      PROF(2 + wg);
      mbar_wait(bars + 8 * (warp == 0 ? BAR_HALO : BAR_STG), 0);
      {
        const uint32_t kh = sb + (warp == 0 ? OFF_L0 : OFF_KH + (warp - 1) * 4096) + lane * 16;
#pragma unroll
        for (int i = 0; i < 2; i++) {
          const uint4 t = lds128(kh + 512 * i);
          k[0][4 * i] = t.x; k[0][4 * i + 1] = t.y; k[0][4 * i + 2] = t.z; k[0][4 * i + 3] = t.w;
        }
#pragma unroll
        for (int i = 0; i < 4; i++) {
          const uint2 t = lds64(kh - lane * 8 + 1024 + 256 * i);
          vt[0][2 * i] = t.x; vt[0][2 * i + 1] = t.y;
        }
      }
      attn_pack<0, 0, false>(acc1, q[0]);
      attn_pack<0, 1, false>(acc1, q[2]);
      attn_pack<8, 0, false>(acc1, k[1]);
      attn_pack<8, 1, false>(acc1, k[3]);
      {
        float x[8][2];
        uint32_t pp[8];
        const bool first = warp == 0 && gidx == 0;
#pragma unroll
        for (int hd = 0; hd < 2; hd++) {
#pragma unroll
          for (int j = 0; j < 4; j += 2) {
            float s0[4], s1[4], s2[4];
            attn_qk(s2, q[j], q[j + 1], k[j + 2], 4 * hd);
            attn_qk(s1, q[j], q[j + 1], k[j + 1], 4 * hd);
            attn_qk(s0, q[j], q[j + 1], k[j], 4 * hd);
            if (j == 0 && first) s0[0] = s0[1] = -1e9f / 0.17677669529663687f;
            x[2 * j + hd][0] = le0 ? s1[0] : s0[0];
            x[2 * j + hd][1] = le1 ? s1[1] : s0[1];
            x[2 * j + 2 + hd][0] = le0 ? s2[2] : s1[2];
            x[2 * j + 2 + hd][1] = le1 ? s2[3] : s1[3];
          }
        }
        PROFA(40, __float_as_uint(x[1][0] + x[7][1]));
        attn_pack<16, 0, true>(acc1, vt[1]);
        attn_pack<16, 1, true>(acc1, vt[3]);
        quad_softmax<8>(x, pp);
        PROFA(41, pp[1] + pp[7]);
        const uint32_t obase = sb + OFF_OP + (warp * 32 + lr) * 128;
#pragma unroll
        for (int n = 0; n < 8; n++) {
          attn_pv(obase + (n >> 1) * 1024 + (((4 * (n & 1) + lm) ^ lr) << 4), vt[n >> 1], vt[(n >> 1) + 1], 4 * (n & 1), pp[n],
                  maskLE);
        }
      }
      PROFA(42, 0);
    }

    {
      fence_async_smem();
      nb_arrive(NB_OREADY, 288);
      const int w = warp & 3;
      const int lr = lane & 7, lm = lane >> 3;
      mbar_wait(bars + 8 * BAR_X, 0);
      PROF(34 + wg);
      uint32_t a1[2][4], sc[4];
      ldsm4(a1[0], sb + OFF_TAB + 2048 + w * 1024 + lane * 16);
      ldsm4(a1[1], sb + OFF_TAB + 2560 + w * 1024 + lane * 16);
      C2 t[2];
      {
        const uint4 x = lds128(sb + OFF_TAB + 6144 + wtid * 16);
        t[0] = C2{x.x, x.z};
        t[1] = C2{x.y, x.w};
        const uint4 fh = lds128(sb + OFF_EX + wg * 16), fu = lds128(sb + OFF_EX + 32 + wg * 16);
        auto pw2 = [](uint32_t a, uint32_t b) { return min(max(381 - (int)a - (int)b, 1), 254) * 0x00800080u; };
        sc[0] = pw2(fh.x, fu.x); sc[1] = pw2(fh.y, fu.y); sc[2] = pw2(fh.z, fu.z); sc[3] = pw2(fh.w, fu.w);
      }
      const uint32_t xb = sb + OFF_X + wg * 4 * XT;
      const uint64_t dc2 = mkdesc(sb + OFF_TAB, 128, 256, 0), dc4 = mkdesc(sb + OFF_TAB + 2048, 128, 256, 0);
      const uint64_t dx = mkdesc(xb, 4096, 1024, 1), dz = mkdesc(xb, 2048, 256, 3);
      const uint32_t zs = xb + (w * 16 + (lm & 1) * 8 + lr) * 32 + (((lm >> 1) ^ (lr >> 2)) << 4);
      const uint32_t ys = xb + w * 2048 + (lm >> 1) * 256;
      const uint32_t yx = (lr * 32 + (((lm & 1) ^ (lr >> 2)) << 4)) ^ (wg << 6) ^ (rank << 5);
      const bool own = (w >> 1) == rank;
      const uint32_t ybar = mapa(bars, own ? rank ^ 1 : rank) + 8 * (BAR_Y + wg * 4);
      uint32_t d[2][32], pa[2][4][2][4], e[2][4][8], ya[2][2][2][4], v[2][2][8];
      float o[2][16];
      auto rows = [&](int c) {
        fft_rows(d[c & 1], a1, dx + (XT >> 4) * c);
        wg_commit();
      };
      auto cols = [&](int c) {
        const int s = c & 1;
        fence_regs(d[s]);
#pragma unroll
        for (int i = 0; i < 16; i++) {
          const C2 z = cmul(C2{d[s][2 * i], d[s][2 * i + 1]}, t[i & 1]);
          pa[s][i >> 2][i & 1][(i >> 1) & 1] = z.r;
          pa[s][i >> 2][i & 1][2 + ((i >> 1) & 1)] = z.i;
        }
        wg_fence();
#pragma unroll
        for (int i = 0; i < 4; i++) fft_cols(e[s][i], pa[s][i], dc2);
        wg_commit();
      };
      auto prod = [&](int c) {
        const int s = c & 1;
#pragma unroll
        for (int i = 0; i < 4; i++) fence_regs(e[s][i]);
#pragma unroll
        for (int j = 0; j < 2; j++) {
          const C2 u0 = cget(e[s][0], j, 0), u1 = cget(e[s][0], j, 1), u2 = cget(e[s][1], j, 0), u3 = cget(e[s][1], j, 1);
          const C2 h0 = cget(e[s][2], j, 0), h1 = cget(e[s][2], j, 1), h2 = cget(e[s][3], j, 0), h3 = cget(e[s][3], j, 1);
          const C2 s0 = cmul(h0, u0), s1 = cfma(h0, u1, cmul(h1, u0)), s2 = cfma(h0, u2, cfma(h2, u0, cmul(h1, u1)));
          const C2 y3 = cfma(h0, u3, cfma(h1, u2, cfma(h2, u1, cfma(h3, u0, C2{s2.i, hneg2(s2.r)}))));
          ya[s][0][j][0] = s0.i;
          ya[s][0][j][1] = hadd2(s1.i, hneg2(s0.r));
          ya[s][0][j][2] = s0.r;
          ya[s][0][j][3] = hadd2(s1.r, s0.i);
          ya[s][1][j][0] = hadd2(s2.i, hneg2(s1.r));
          ya[s][1][j][1] = y3.i;
          ya[s][1][j][2] = hadd2(s2.r, s1.i);
          ya[s][1][j][3] = y3.r;
        }
        wg_fence();
        fft_cols(v[s][0], ya[s][0], dc2);
        fft_cols(v[s][1], ya[s][1], dc2);
        wg_commit();
      };
      auto stage = [&](int c) {
        const int s = c & 1;
        fence_regs(v[s][0]);
        fence_regs(v[s][1]);
#pragma unroll
        for (int b = 0; b < 4; b++) {
          const C2 z0 = cmul(cget(v[s][b >> 1], 0, b & 1), t[0]), z1 = cmul(cget(v[s][b >> 1], 1, b & 1), t[1]);
          stsm4(zs + c * XT + b * 2048, z0.i, z0.r, z1.i, z1.r);
        }
      };
      auto back = [&](int c) {
        fft_back(o[c & 1], dz + (XT >> 4) * c, dc4);
        wg_commit();
      };
      auto out = [&](int c) {
        float (&r)[16] = o[c & 1];
        fence_regs(r);
#pragma unroll
        for (int i = 0; i < 16; i += 8)
          stsm4t(ys + c * XT + (yx ^ (c << 4)) + 64 * i, bmul2(pack_bf16(r[i], r[i + 1]), sc[c]),
                 bmul2(pack_bf16(r[i + 2], r[i + 3]), sc[c]), bmul2(pack_bf16(r[i + 4], r[i + 5]), sc[c]),
                 bmul2(pack_bf16(r[i + 6], r[i + 7]), sc[c]));
        __syncwarp();
        if (lane == 0) {
          mbar_arrive_cluster(ybar + 8 * c);
          if (own) mbar_arrive(bars + 8 * BAR_LAND);
        }
      };
      wg_fence();
      rows(0);
      rows(1);
      wg_wait<1>();
      cols(0);
      wg_wait<1>();
      cols(1);
      nb_sync(NB_CONV + wg, 128);
      wg_wait<1>();
      prod(0);
      rows(2);
      wg_wait<2>();
      prod(1);
      rows(3);
      wg_wait<3>();
      stage(0);
      wg_wait<1>();
      stage(1);
      fence_async_smem();
      cols(2);
      wg_wait<1>();
      nb_sync(NB_CONV + wg, 128);
      wg_fence();
      back(0);
      back(1);
      cols(3);
      wg_wait<3>();
      prod(2);
      wg_wait<2>();
      out(0);
      out(1);
      wg_wait<1>();
      prod(3);
      wg_wait<1>();
      stage(2);
      wg_wait<0>();
      stage(3);
      fence_async_smem();
      nb_sync(NB_CONV + wg, 128);
      wg_fence();
      back(2);
      back(3);
      wg_wait<1>();
      out(2);
      wg_wait<0>();
      out(3);
      PROF(6 + wg);
    }
    }

    if (MODE != 1 && wg == g2wg) {
      float acc0[64], acc1[64];
      int sprev = 0;
#pragma unroll 1
      for (int kb = 0; kb < 16 - ENDG; kb++) {
        const int s = (int)(G2_STAGE >> (4 * kb)) & 7;
        mbar_wait(bars + 8 * (BAR_FULL2 + s), (G2_PARITY >> kb) & 1);
        if (kb == 0) PROF(8);
        if ((warp & 3) == 0) PROF2(40 + kb);
        const uint32_t st = sb + s * STG2;
        const uint64_t da = mkdesc(st, 16, 1024, 1);
        const uint64_t db = mkdesc(st + 16384, 8192, 1024, 1);
        wg_fence();
        wgmma_n128(acc0, da, db, kb);
        wgmma_n128(acc1, da + 512, db, kb);
        wgmma_n128(acc0, da + 2, db + 128, 1);
        wgmma_n128(acc1, da + 514, db + 128, 1);
        wg_commit();
        wg_wait<1>();
        if (kb > 0 && ((G2_REUSE << 1 >> kb) & 1) && signaller) mbar_arrive_cluster(rbars + 8 * (BAR_EMPTY2 + sprev));
        wgmma_n128(acc0, da + 4, db + 256, 1);
        wgmma_n128(acc1, da + 516, db + 256, 1);
        wgmma_n128(acc0, da + 6, db + 384, 1);
        wgmma_n128(acc1, da + 518, db + 384, 1);
        wg_commit();
        wg_wait<1>();
        sprev = s;
      }
#pragma unroll
      for (int kb = 16 - ENDG; kb < 16; kb++) {
        mbar_wait(bars + 8 * (BAR_FULL2 + g2_stage(kb)), (G2_PARITY >> kb) & 1);
        if ((warp & 3) == 0) PROF2(40 + kb);
        const uint64_t da = mkdesc(sb + g2_stage(kb) * STG2, 16, 1024, 1);
        const uint64_t db = mkdesc(sb + g2_stage(kb) * STG2 + 16384, 8192, 1024, 1);
        wg_fence();
#pragma unroll
        for (int i = 0; i < 4; i++) wgmma_n128(acc0, da + 2 * i, db + 128 * i, 1);
        wg_commit();
        if (kb == 16 - ENDG && ((G2_REUSE >> (kb - 1)) & 1)) {
          wg_wait<1>();
          if (signaller) mbar_arrive_cluster(rbars + 8 * (BAR_EMPTY2 + sprev));
        }
      }
      static_assert((G2_REUSE >> (16 - ENDG)) == 0, "the last stages stay resident");
      auto second = [&](int i0, int i1) {
#pragma unroll
        for (int i = i0; i < i1; i++) {
          const uint32_t st = sb + g2_stage(16 - ENDG + (i >> 2)) * STG2;
          wgmma_n128(acc1, mkdesc(st + 8192, 16, 1024, 1) + 2 * (i & 3), mkdesc(st + 16384, 8192, 1024, 1) + 128 * (i & 3), 1);
        }
        wg_commit();
      };
      second(0, 4);
      const int lr = lane & 7, lm = lane >> 3;
      const uint32_t wb[2] = {sb + g2_stage(14) * STG2 + (warp & 3) * 2048, sb + g2_stage(15) * STG2 + (warp & 3) * 2048};
      const int orow = (rb2 & 7) * 128 + (warp & 3) * 16;
      auto stage_out = [&](const float (&acc)[64], uint32_t off, int j0, int j1) {
#pragma unroll
        for (int j = j0; j < j1; j += 2) {
          const uint32_t a = wb[j >> 3] + off + (lr + 8 * (lm & 1)) * 128 + ((((j & 7) + (lm >> 1)) ^ lr) << 4);
          stsm4(a, pack_bf16(acc[4 * j], acc[4 * j + 1]), pack_bf16(acc[4 * j + 2], acc[4 * j + 3]),
                pack_bf16(acc[4 * j + 4], acc[4 * j + 5]), pack_bf16(acc[4 * j + 6], acc[4 * j + 7]));
        }
      };
      auto store_tma = [&](uint32_t off, int row) {
        fence_async_smem();
        __syncwarp();
        if (elect_one()) {
          tma_store_3d(&tmOb, wb[0] + off, DM + cb2 * 128, rb2 >> 3, row);
          tma_store_3d(&tmOb, wb[1] + off, DM + cb2 * 128 + 64, rb2 >> 3, row);
          bulk_commit();
        }
      };
      wg_wait<1>();
      fence_regs(acc0);
      PROF(10);
#pragma unroll
      for (int c = 0; c < 4; c++) {
        stage_out(acc0, 0, 4 * c, 4 * c + 4);
        second(4 + ILV * c, 4 + ILV * (c + 1));
      }
      store_tma(0, orow);
      if (4 + 4 * ILV < 4 * ENDG) second(4 + 4 * ILV, 4 * ENDG);
      PROF(12);
      wg_wait<0>();
      fence_regs(acc1);
      PROF(11);
      stage_out(acc1, 8192, 0, 16);
      __syncwarp();
      {
        const int rr = lane >> 4, ck = lane & 7, hf = (lane >> 3) & 1;
        uint4* og = reinterpret_cast<uint4*>(p.out + (size_t)(2 * (orow + 64 + rr) + (rb2 >> 3)) * (2 * DM) + DM + cb2 * 128 + hf * 64 + ck * 8);
        uint4 v[8];
#pragma unroll
        for (int i = 0; i < 8; i++) v[i] = lds128((hf ? wb[1] : wb[0]) + 8192 + (2 * i + rr) * 128 + ((ck ^ ((2 * i + rr) & 7)) << 4));
#pragma unroll
        for (int i = 0; i < 8; i++) og[(size_t)i * 4 * (2 * DM / 8)] = v[i];
      }
      PROF(13);
      bulk_wait0();
    }
    cluster_sync_all();
  }
}

typedef CUresult (*EncodeFn)(CUtensorMap*, CUtensorMapDataType, cuuint32_t, void*, const cuuint64_t*, const cuuint64_t*,
                             const cuuint32_t*, const cuuint32_t*, CUtensorMapInterleave, CUtensorMapSwizzle,
                             CUtensorMapL2promotion, CUtensorMapFloatOOBfill);

void make_map(EncodeFn enc, CUtensorMap* tm, const void* base, int rank, const cuuint64_t* dims, const cuuint64_t* strides,
              const cuuint32_t* box, CUtensorMapSwizzle swz) {
  cuuint32_t es[4] = {1, 1, 1, 1};
  enc(tm, CU_TENSOR_MAP_DATA_TYPE_BFLOAT16, rank, const_cast<void*>(base), dims, strides, box, es,
      CU_TENSOR_MAP_INTERLEAVE_NONE, swz, CU_TENSOR_MAP_L2_PROMOTION_L2_256B, CU_TENSOR_MAP_FLOAT_OOB_FILL_NONE);
}

}

extern "C" void kernel_launch(void* const* d_in, const int* in_sizes, int n_in, void* d_out, int out_size) {
  static EncodeFn enc = nullptr;
  static bool coresident = true;
  if (!enc) {
    void* fn = nullptr;
    cudaDriverEntryPointQueryResult qr;
    cudaGetDriverEntryPoint("cuTensorMapEncodeTiled", &fn, cudaEnableDefault, &qr);
    enc = (EncodeFn)fn;
    cudaFuncSetAttribute(fused_kernel<0>, cudaFuncAttributeMaxDynamicSharedMemorySize, SMEM_BYTES);
    cudaFuncSetAttribute(fused_kernel<1>, cudaFuncAttributeMaxDynamicSharedMemorySize, SMEM_BYTES);
    cudaFuncSetAttribute(fused_kernel<2>, cudaFuncAttributeMaxDynamicSharedMemorySize, SMEM_BYTES);
    cudaLaunchConfig_t cfg = {};
    cfg.gridDim = dim3(NCTA);
    cfg.blockDim = dim3(NTHREADS);
    cfg.dynamicSmemBytes = SMEM_BYTES;
    cudaLaunchAttribute at;
    at.id = cudaLaunchAttributeClusterDimension;
    at.val.clusterDim.x = 2;
    at.val.clusterDim.y = 1;
    at.val.clusterDim.z = 1;
    cfg.attrs = &at;
    cfg.numAttrs = 1;
    int nclusters = 0;
    if (cudaOccupancyMaxActiveClusters(&nclusters, fused_kernel<0>, &cfg) == cudaSuccess) coresident = nclusters >= NCTA / 2;
    (void)cudaGetLastError();
  }
  CUtensorMap tmX, tmW, tmWo, tmQ, tmOa, tmOb, tmXh, tmWh;
  {
    cuuint64_t dims[3] = {1024, 2, 1024};
    cuuint64_t str[2] = {2048, 4096};
    cuuint32_t box[3] = {64, 1, 128};
    make_map(enc, &tmX, d_in[6], 3, dims, str, box, CU_TENSOR_MAP_SWIZZLE_128B);
  }
  {
    cuuint64_t dims[3] = {1024, 1024, 3};
    cuuint64_t str[2] = {6144, 2048};
    cuuint32_t box[3] = {64, 32, 3};
    make_map(enc, &tmW, d_in[7], 3, dims, str, box, CU_TENSOR_MAP_SWIZZLE_128B);
  }
  {
    cuuint64_t dims[3] = {64, 1024, 16};
    cuuint64_t str[2] = {2048, 128};
    cuuint32_t box[3] = {64, 64, 2};
    make_map(enc, &tmWo, d_in[8], 3, dims, str, box, CU_TENSOR_MAP_SWIZZLE_128B);
  }
  {
    cuuint64_t dims[2] = {1024, 2048};
    cuuint64_t str[1] = {2048};
    cuuint32_t box[2] = {16, 128};
    make_map(enc, &tmQ, d_in[0], 2, dims, str, box, CU_TENSOR_MAP_SWIZZLE_NONE);
  }
  {
    cuuint64_t dims[2] = {2048, 2048};
    cuuint64_t str[1] = {4096};
    cuuint32_t box[2] = {16, 64};
    make_map(enc, &tmOa, d_out, 2, dims, str, box, CU_TENSOR_MAP_SWIZZLE_NONE);
  }
  {
    cuuint64_t dims[3] = {2048, 2, 1024};
    cuuint64_t str[2] = {4096, 8192};
    cuuint32_t box[3] = {64, 1, 16};
    make_map(enc, &tmOb, d_out, 3, dims, str, box, CU_TENSOR_MAP_SWIZZLE_128B);
  }
  {
    cuuint64_t dims[4] = {1024, 256, 2, 4};
    cuuint64_t str[3] = {4096, 2048, 256 * 4096};
    cuuint32_t box[4] = {64, 8, 2, 3};
    make_map(enc, &tmXh, d_in[6], 4, dims, str, box, CU_TENSOR_MAP_SWIZZLE_128B);
  }
  {
    cuuint64_t dims[3] = {64, 1024, 48};
    cuuint64_t str[2] = {6144, 128};
    cuuint32_t box[3] = {64, 64, 4};
    make_map(enc, &tmWh, d_in[7], 3, dims, str, box, CU_TENSOR_MAP_SWIZZLE_128B);
  }
  Params p;
  p.q = (const __nv_bfloat16*)d_in[0];
  p.k = (const __nv_bfloat16*)d_in[1];
  p.v = (const __nv_bfloat16*)d_in[2];
  p.shift_k = (const __nv_bfloat16*)d_in[3];
  p.ssm_k = (const __nv_bfloat16*)d_in[4];
  p.ssm_D = (const __nv_bfloat16*)d_in[5];
  p.x = (const __nv_bfloat16*)d_in[6];
  p.w = (const __nv_bfloat16*)d_in[7];
  p.wo = (const __nv_bfloat16*)d_in[8];
  p.out = (__nv_bfloat16*)d_out;
  p.zero = 0;
  if (coresident) {
    fused_kernel<0><<<NCTA, NTHREADS, SMEM_BYTES>>>(p, tmX, tmW, tmWo, tmQ, tmOa, tmOb, tmXh, tmWh);
  } else {
    fused_kernel<0><<<4, NTHREADS, SMEM_BYTES>>>(p, tmX, tmW, tmWo, tmQ, tmOa, tmOb, tmXh, tmWh);
    fused_kernel<1><<<NCTA, NTHREADS, SMEM_BYTES>>>(p, tmX, tmW, tmWo, tmQ, tmOa, tmOb, tmXh, tmWh);
    fused_kernel<2><<<NCTA, NTHREADS, SMEM_BYTES>>>(p, tmX, tmW, tmWo, tmQ, tmOa, tmOb, tmXh, tmWh);
  }
}
```

```cpp
#include <cuda_runtime.h>
#include <cuda.h>
#include <cuda_bf16.h>
#include <stdint.h>

namespace {

constexpr int SEQ = 2048;
constexpr int DM = 1024;
constexpr int NCTA = 132;
constexpr int NTHREADS = 384;

constexpr int STG1A = 32768;
constexpr int NS1A = 3;
constexpr int STG1B = 12288;
constexpr int NS1B = 5;
constexpr int OFF_1B = NS1A * STG1A;
constexpr int STG2 = 32768;
constexpr int NS2 = 5;
#define ILV 2
#define ENDG 5
__device__ __forceinline__ uint32_t g2_a(int s, int hsel) { return (((0x95324 >> (4 * s)) & 15) ^ (s % 3 ? 0 : hsel)) << 14; }
__device__ __forceinline__ uint32_t g2_b(int s) { return (s < 2 ? s : s + 4) << 14; }
constexpr int STGH = 73728;
constexpr int OFF_KH = 1 * STG2;
constexpr int OFF_OP = 2 * STG2;
constexpr int OFF_TAB = NS2 * STG2 - 8192;
constexpr int OFF_X = NS2 * STG2;
constexpr int XT = 8192;
constexpr int OFF_BAR = OFF_X + 8 * XT;
constexpr int OFF_EX = OFF_BAR + 384;
constexpr int OFF_L0 = 230400;
constexpr int SMEM_BYTES = OFF_L0 + 2048;
static_assert(OFF_TAB >= OFF_1B + 2 * STG1B && OFF_1B + NS1B * STG1B <= OFF_X && OFF_X % 1024 == 0, "layout");
static_assert(3 * STGH <= OFF_BAR && OFF_EX + 64 <= OFF_L0 && SMEM_BYTES <= 232448, "smem");

constexpr int BAR_FULLA = 0;
constexpr int BAR_EMPTYA = 3;
constexpr int BAR_FULLB = 6;
constexpr int BAR_EMPTYB = 11;
constexpr int BAR_FULL2 = 16;
constexpr int BAR_EMPTY2 = 21;
constexpr int BAR_X = 26;
constexpr int BAR_LAND = 27;
constexpr int BAR_U = 29;
constexpr int BAR_Q = 30;
constexpr int BAR_STG = 31;
constexpr int BAR_Y = 32;
constexpr int BAR_HALO = 40;

constexpr int NB_G1DONE = 1;
constexpr int NB_OREADY = 4;
constexpr int NB_CONV = 5;
constexpr int NB_HELP3 = 11;
constexpr int NB_FIRST = 13;

#define REG_MATH 224
#define REG_HELP 56
constexpr int SPIN_LIMIT = 1 << 20;

__device__ __align__(1024) __nv_bfloat16 g_o[SEQ * DM];
__device__ uint32_t g_flag_o[128];
__device__ uint32_t g_flag_h[4];
__device__ uint4 g_halo[128 * 128];
__device__ __align__(128) const uint32_t g_tab[2048] = {
  0x3c003c00,0x3c003c00,0x3c003c00,0x3c003c00,0x3b643c00,0x361f39a8,0xb61f0000,0xbb64b9a8,0x39a83c00,0xb9a80000,0xb9a8bc00,0x39a80000,
  0x361f3c00,0xbb64b9a8,0x3b640000,0xb61f39a8,0x3c00,0xbc00,0x3c00,0xbc00,0xb61f3c00,0x3b64b9a8,0xbb640000,0x361f39a8,
  0xb9a83c00,0x39a80000,0x39a8bc00,0xb9a80000,0xbb643c00,0xb61f39a8,0x361f0000,0x3b64b9a8,0x0,0x0,0x0,0x0,
  0xb61f0000,0xbb64b9a8,0xbb64bc00,0xb61fb9a8,0xb9a80000,0xb9a8bc00,0x39a80000,0x39a83c00,0xbb640000,0x361fb9a8,0x361f3c00,0xbb64b9a8,
  0xbc000000,0x3c000000,0xbc000000,0x3c000000,0xbb640000,0x361f39a8,0x361fbc00,0xbb6439a8,0xb9a80000,0xb9a83c00,0x39a80000,0x39a8bc00,
  0xb61f0000,0xbb6439a8,0xbb643c00,0xb61f39a8,0x0,0x0,0x0,0x0,0x361f0000,0x3b6439a8,0x3b643c00,0x361f39a8,
  0x39a80000,0x39a83c00,0xb9a80000,0xb9a8bc00,0x3b640000,0xb61f39a8,0xb61fbc00,0x3b6439a8,0x3c000000,0xbc000000,0x3c000000,0xbc000000,
  0x3b640000,0xb61fb9a8,0xb61f3c00,0x3b64b9a8,0x39a80000,0x39a8bc00,0xb9a80000,0xb9a83c00,0x361f0000,0x3b64b9a8,0x3b64bc00,0x361fb9a8,
  0x3c003c00,0x3c003c00,0x3c003c00,0x3c003c00,0x3b643c00,0x361f39a8,0xb61f0000,0xbb64b9a8,0x39a83c00,0xb9a80000,0xb9a8bc00,0x39a80000,
  0x361f3c00,0xbb64b9a8,0x3b640000,0xb61f39a8,0x3c00,0xbc00,0x3c00,0xbc00,0xb61f3c00,0x3b64b9a8,0xbb640000,0x361f39a8,
  0xb9a83c00,0x39a80000,0x39a8bc00,0xb9a80000,0xbb643c00,0xb61f39a8,0x361f0000,0x3b64b9a8,0xbc003c00,0xbc003c00,0xbc003c00,0xbc003c00,
  0xbb643c00,0xb61f39a8,0x361f0000,0x3b64b9a8,0xb9a83c00,0x39a80000,0x39a8bc00,0xb9a80000,0xb61f3c00,0x3b64b9a8,0xbb640000,0x361f39a8,
  0x3c00,0xbc00,0x3c00,0xbc00,0x361f3c00,0xbb64b9a8,0x3b640000,0xb61f39a8,0x39a83c00,0xb9a80000,0xb9a8bc00,0x39a80000,
  0x3b643c00,0x361f39a8,0xb61f0000,0xbb64b9a8,0x0,0x0,0x0,0x0,0x361f0000,0x3b64b9a8,0x3b64bc00,0x361fb9a8,
  0x39a80000,0x39a8bc00,0xb9a80000,0xb9a83c00,0x3b640000,0xb61fb9a8,0xb61f3c00,0x3b64b9a8,0x3c000000,0xbc000000,0x3c000000,0xbc000000,
  0x3b640000,0xb61f39a8,0xb61fbc00,0x3b6439a8,0x39a80000,0x39a83c00,0xb9a80000,0xb9a8bc00,0x361f0000,0x3b6439a8,0x3b643c00,0x361f39a8,
  0x0,0x0,0x0,0x0,0xb61f0000,0xbb6439a8,0xbb643c00,0xb61f39a8,0xb9a80000,0xb9a83c00,0x39a80000,0x39a8bc00,
  0xbb640000,0x361f39a8,0x361fbc00,0xbb6439a8,0xbc000000,0x3c000000,0xbc000000,0x3c000000,0xbb640000,0x361fb9a8,0x361f3c00,0xbb64b9a8,
  0xb9a80000,0xb9a8bc00,0x39a80000,0x39a83c00,0xb61f0000,0xbb64b9a8,0xbb64bc00,0xb61fb9a8,0xbc003c00,0xbc003c00,0xbc003c00,0xbc003c00,
  0xbb643c00,0xb61f39a8,0x361f0000,0x3b64b9a8,0xb9a83c00,0x39a80000,0x39a8bc00,0xb9a80000,0xb61f3c00,0x3b64b9a8,0xbb640000,0x361f39a8,
  0x3c00,0xbc00,0x3c00,0xbc00,0x361f3c00,0xbb64b9a8,0x3b640000,0xb61f39a8,0x39a83c00,0xb9a80000,0xb9a8bc00,0x39a80000,
  0x3b643c00,0x361f39a8,0xb61f0000,0xbb64b9a8,0x3c003c00,0x3c003c00,0x3c003c00,0x3c003c00,0xbb64bc00,0xb61fb9a8,0x361f0000,0x3b6439a8,
  0x39a83c00,0xb9a80000,0xb9a8bc00,0x39a80000,0xb61fbc00,0x3b6439a8,0xbb640000,0x361fb9a8,0x3c00,0xbc00,0x3c00,0xbc00,
  0x361fbc00,0xbb6439a8,0x3b640000,0xb61fb9a8,0xb9a83c00,0x39a80000,0x39a8bc00,0xb9a80000,0x3b64bc00,0x361fb9a8,0xb61f0000,0xbb6439a8,
  0x0,0x0,0x0,0x0,0x361f0000,0x3b6439a8,0x3b643c00,0x361f39a8,0xb9a80000,0xb9a8bc00,0x39a80000,0x39a83c00,
  0x3b640000,0xb61f39a8,0xb61fbc00,0x3b6439a8,0xbc000000,0x3c000000,0xbc000000,0x3c000000,0x3b640000,0xb61fb9a8,0xb61f3c00,0x3b64b9a8,
  0xb9a80000,0xb9a83c00,0x39a80000,0x39a8bc00,0x361f0000,0x3b64b9a8,0x3b64bc00,0x361fb9a8,0x0,0x0,0x0,0x0,
  0xb61f0000,0xbb64b9a8,0xbb64bc00,0xb61fb9a8,0x39a80000,0x39a83c00,0xb9a80000,0xb9a8bc00,0xbb640000,0x361fb9a8,0x361f3c00,0xbb64b9a8,
  0x3c000000,0xbc000000,0x3c000000,0xbc000000,0xbb640000,0x361f39a8,0x361fbc00,0xbb6439a8,0x39a80000,0x39a8bc00,0xb9a80000,0xb9a83c00,
  0xb61f0000,0xbb6439a8,0xbb643c00,0xb61f39a8,0x3c003c00,0x3c003c00,0x3c003c00,0x3c003c00,0xbb64bc00,0xb61fb9a8,0x361f0000,0x3b6439a8,
  0x39a83c00,0xb9a80000,0xb9a8bc00,0x39a80000,0xb61fbc00,0x3b6439a8,0xbb640000,0x361fb9a8,0x3c00,0xbc00,0x3c00,0xbc00,
  0x361fbc00,0xbb6439a8,0x3b640000,0xb61fb9a8,0xb9a83c00,0x39a80000,0x39a8bc00,0xb9a80000,0x3b64bc00,0x361fb9a8,0xb61f0000,0xbb6439a8,
  0xbc003c00,0xbc003c00,0xbc003c00,0xbc003c00,0x3b64bc00,0x361fb9a8,0xb61f0000,0xbb6439a8,0xb9a83c00,0x39a80000,0x39a8bc00,0xb9a80000,
  0x361fbc00,0xbb6439a8,0x3b640000,0xb61fb9a8,0x3c00,0xbc00,0x3c00,0xbc00,0xb61fbc00,0x3b6439a8,0xbb640000,0x361fb9a8,
  0x39a83c00,0xb9a80000,0xb9a8bc00,0x39a80000,0xbb64bc00,0xb61fb9a8,0x361f0000,0x3b6439a8,0x0,0x0,0x0,0x0,
  0xb61f0000,0xbb6439a8,0xbb643c00,0xb61f39a8,0x39a80000,0x39a8bc00,0xb9a80000,0xb9a83c00,0xbb640000,0x361f39a8,0x361fbc00,0xbb6439a8,
  0x3c000000,0xbc000000,0x3c000000,0xbc000000,0xbb640000,0x361fb9a8,0x361f3c00,0xbb64b9a8,0x39a80000,0x39a83c00,0xb9a80000,0xb9a8bc00,
  0xb61f0000,0xbb64b9a8,0xbb64bc00,0xb61fb9a8,0x0,0x0,0x0,0x0,0x361f0000,0x3b64b9a8,0x3b64bc00,0x361fb9a8,
  0xb9a80000,0xb9a83c00,0x39a80000,0x39a8bc00,0x3b640000,0xb61fb9a8,0xb61f3c00,0x3b64b9a8,0xbc000000,0x3c000000,0xbc000000,0x3c000000,
  0x3b640000,0xb61f39a8,0xb61fbc00,0x3b6439a8,0xb9a80000,0xb9a8bc00,0x39a80000,0x39a83c00,0x361f0000,0x3b6439a8,0x3b643c00,0x361f39a8,
  0xbc003c00,0xbc003c00,0xbc003c00,0xbc003c00,0x3b64bc00,0x361fb9a8,0xb61f0000,0xbb6439a8,0xb9a83c00,0x39a80000,0x39a8bc00,0xb9a80000,
  0x361fbc00,0xbb6439a8,0x3b640000,0xb61fb9a8,0x3c00,0xbc00,0x3c00,0xbc00,0xb61fbc00,0x3b6439a8,0xbb640000,0x361fb9a8,
  0x39a83c00,0xb9a80000,0xb9a8bc00,0x39a80000,0xbb64bc00,0xb61fb9a8,0x361f0000,0x3b6439a8,0x3bfe3c00,0x3bea3bf6,0x3bc33bd9,0x3b883ba8,
  0x3bc33c00,0x39ed3b0e,0x35643872,0xb0b22e46,0x3b3b3c00,0x33c63913,0xb8c4b23e,0xbbfebb0e,0x3a6d3c00,0xb56434a5,0xbbfebaa7,0xb3c6ba2f,
  0x395f3c00,0xba6dae46,0xb81dbbd9,0x3b3b34a5,0x381d3c00,0xbbfeb78b,0x36d7b872,0x38c43bf6,0x35643c00,0xbaddba2f,0x3bea323e,0xb95f378b,
  0x30b23c00,0xb6d7bba8,0x395f3aa7,0xbaddb913,0x2a480000,0x30b22e46,0x33c6323e,0x356434a5,0x33c60000,0x395f378b,0x3b883aa7,0x3bea3bf6,
  0x36d70000,0x3bc33a2f,0x3a6d3bd9,0x2a48378b,0x38c40000,0x3b883ba8,0xaa483872,0xbbc3b913,0x39ed0000,0x38c43bf6,0xbaddb23e,0xb6d7bba8,
  0x3add0000,0x2a483b0e,0xbb3bbaa7,0x3a6dae46,0x3b880000,0xb81d3913,0xb0b2bbd9,0x39ed3b0e,0x3bea0000,0xbb3b34a5,0x39edb872,0xb81d3a2f,
  0x3b3b3b64,0x3add3b0e,0x3a6d3aa7,0x39ed3a2f,0xb8c4b61f,0xbb3bba2f,0xbbfebbd9,0xbaddbba8,0xb95fbb64,0x30b2b4a5,0x3add3872,0x3b883bf6,
  0x3add361f,0x39ed3bf6,0xb6d7323e,0xbbeabb0e,0x35643b64,0xbbc3b78b,0xb0b2baa7,0x3bfe3913,0xbbeab61f,0x3564b913,0x395f3bd9,0xbbc3b4a5,
  0x2a48bb64,0x38c43ba8,0xbbc3b872,0x3b3bae46,0x3bc3361f,0xbbfeae46,0x3b88b23e,0xba6d378b,0x36d7361f,0x381d378b,0x38c43872,0x395f3913,
  0x3a6d3b64,0x36d73913,0xaa48323e,0xb81db4a5,0xb9edb61f,0xbbeabba8,0xb81dbaa7,0x3564ae46,0xb81dbb64,0x395f2e46,0x3b3b3bd9,0xb0b2378b,
  0x3b88361f,0x33c63b0e,0xbbeab872,0xaa48ba2f,0x30b23b64,0xbb88ba2f,0x39edb23e,0x33c63ba8,0xbbfeb61f,0x3a6db4a5,0xb3c63aa7,0xb6d7bbf6,
  0x33c6bb64,0x2a483bf6,0xb564bbd9,0x38c43b0e,0x395f39a8,0x38c43913,0x381d3872,0x36d7378b,0xb81db9a8,0xaa48b4a5,0x36d7323e,0x3a6d3913,
  0x356439a8,0xb81dae46,0xbbeabaa7,0xb9edbba8,0xb0b2b9a8,0x3b3b378b,0x395f3bd9,0xb81d2e46,0xaa4839a8,0xbbeaba2f,0x33c6b872,0x3b883b0e,
  0x33c6b9a8,0x39ed3ba8,0xbb88b23e,0x30b2ba2f,0xb6d739a8,0xb3c6bbf6,0x3a6d3aa7,0xbbfeb4a5,0x38c4b9a8,0xb5643b0e,0x2a48bbd9,0x33c63bf6,
  0x39ed39a8,0x3a6d3a2f,0x3add3aa7,0x3b3b3b0e,0xbaddb9a8,0xbbfebba8,0xbb3bbbd9,0xb8c4ba2f,0x3b8839a8,0x3add3bf6,0x30b23872,0xb95fb4a5,
  0xbbeab9a8,0xb6d7bb0e,0x39ed323e,0x3add3bf6,0x3bfe39a8,0xb0b23913,0xbbc3baa7,0x3564b78b,0xbbc3b9a8,0x395fb4a5,0x35643bd9,0xbbeab913,
  0x3b3b39a8,0xbbc3ae46,0x38c4b872,0x2a483ba8,0xba6db9a8,0x3b88378b,0xbbfeb23e,0x3bc3ae46,0x3564361f,0x33c634a5,0x30b2323e,0x2a482e46,
  0x3bea3b64,0x3b883bf6,0x395f3aa7,0x33c6378b,0x2a48b61f,0x3a6d378b,0x3bc33bd9,0x36d73a2f,0xbbc3bb64,0xaa48b913,0x3b883872,0x38c43ba8,
  0xb6d7361f,0xbaddbba8,0x38c4b23e,0x39ed3bf6,0x3a6d3b64,0xbb3bae46,0x2a48baa7,0x3add3b0e,0x39edb61f,0xb0b23b0e,0xb81dbbd9,0x3b883913,
  0xb81dbb64,0x39ed3a2f,0xbb3bb872,0x3bea34a5,0x3b883b64,0x3bc33ba8,0x3bea3bd9,0x3bfe3bf6,0xb0b2b61f,0x35642e46,0x39ed3872,0x3bc33b0e,
  0xbbfebb64,0xb8c4bb0e,0x33c6b23e,0x3b3b3913,0xb3c6361f,0xbbfeba2f,0xb564baa7,0x3a6d34a5,0x3b3b3b64,0xb81d34a5,0xba6dbbd9,0x395fae46,
  0x38c4b61f,0x36d73bf6,0xbbfeb872,0x381db78b,0xb95fbb64,0x3bea378b,0xbadd323e,0x3564ba2f,0xbadd361f,0x395fb913,0xb6d73aa7,0x30b2bba8,
  0xaa483c00,0x30b2bbf6,0xb3c63bd9,0x3564bba8,0xb3c63c00,0x395fbb0e,0xbb883872,0x3beaae46,0xb6d73c00,0x3bc3b913,0xba6db23e,0x2a483b0e,
  0xb8c43c00,0x3b88b4a5,0x2a48baa7,0xbbc33a2f,0xb9ed3c00,0x38c42e46,0x3addbbd9,0xb6d7b4a5,0xbadd3c00,0x2a48378b,0x3b3bb872,0x3a6dbbf6,
  0xbb883c00,0xb81d3a2f,0x30b2323e,0x39edb78b,0xbbea3c00,0xbb3b3ba8,0xb9ed3aa7,0xb81d3913,0x3bfe0000,0xbbeaae46,0x3bc3323e,0xbb88b4a5,
  0x3bc30000,0xb9edb78b,0x35643aa7,0x30b2bbf6,0x3b3b0000,0xb3c6ba2f,0xb8c43bd9,0x3bfeb78b,0x3a6d0000,0x3564bba8,0xbbfe3872,0x33c63913,
  0x395f0000,0x3a6dbbf6,0xb81db23e,0xbb3b3ba8,0x381d0000,0x3bfebb0e,0x36d7baa7,0xb8c42e46,0x35640000,0x3addb913,0x3beabbd9,0x395fbb0e,
  0x30b20000,0x36d7b4a5,0x395fb872,0x3addba2f,0xb6d73b64,0x381dbb0e,0xb8c43aa7,0x395fba2f,0xba6db61f,0x36d73a2f,0x2a48bbd9,0xb81d3ba8,
  0x39edbb64,0xbbea34a5,0x381d3872,0x3564bbf6,0x381d361f,0x395fbbf6,0xbb3b323e,0xb0b23b0e,0xbb883b64,0x33c6378b,0x3beabaa7,0xaa48b913,
  0xb0b2b61f,0xbb883913,0xb9ed3bd9,0x33c634a5,0x3bfebb64,0x3a6dbba8,0x33c6b872,0xb6d72e46,0xb3c6361f,0x2a482e46,0x3564b23e,0x38c4b78b,
  0x3b3b361f,0xbaddb78b,0x3a6d3872,0xb9edb913,0xb8c43b64,0x3b3bb913,0xbbfe323e,0x3add34a5,0xb95fb61f,0xb0b23ba8,0x3addbaa7,0xbb882e46,
  0x3addbb64,0xb9edae46,0xb6d73bd9,0x3beab78b,0x3564361f,0x3bc3bb0e,0xb0b2b872,0xbbfe3a2f,0xbbea3b64,0xb5643a2f,0x395fb23e,0x3bc3bba8,
  0x2a48b61f,0xb8c434a5,0xbbc33aa7,0xbb3b3bf6,0x3bc3bb64,0x3bfebbf6,0x3b88bbd9,0x3a6dbb0e,0xb9ed39a8,0x3a6db913,0xbadd3872,0x3b3bb78b,
  0x3addb9a8,0xbbfe34a5,0x3b3b323e,0xb8c4b913,0xbb8839a8,0x3add2e46,0xb0b2baa7,0xb95f3ba8,0x3beab9a8,0xb6d7b78b,0xb9ed3bd9,0x3addae46,
  0xbbfe39a8,0xb0b23a2f,0x3bc3b872,0x3564bb0e,0x3bc3b9a8,0x395fbba8,0xb564b23e,0xbbea3a2f,0xbb3b39a8,0xbbc33bf6,0xb8c43aa7,0x2a4834a5,
  0x3a6db9a8,0x3b88bb0e,0x3bfebbd9,0x3bc3bbf6,0x395f39a8,0xb8c4ba2f,0x381d3aa7,0xb6d7bb0e,0xb81db9a8,0x2a483ba8,0x36d7bbd9,0xba6d3a2f,
  0x356439a8,0x381dbbf6,0xbbea3872,0x39ed34a5,0xb0b2b9a8,0xbb3b3b0e,0x395f323e,0x381dbbf6,0xaa4839a8,0x3beab913,0x33c6baa7,0xbb88378b,
  0x33c6b9a8,0xb9ed34a5,0xbb883bd9,0xb0b23913,0xb6d739a8,0x33c62e46,0x3a6db872,0x3bfebba8,0x38c4b9a8,0x3564b78b,0x2a48b23e,0xb3c62e46,
  0xbb88361f,0x3bc3b4a5,0xbbea323e,0x3bfeae46,0x30b23b64,0x3564bbf6,0xb9ed3aa7,0x3bc3b78b,0x3bfeb61f,0xb8c4b78b,0xb3c63bd9,0x3b3bba2f,
  0x33c6bb64,0xbbfe3913,0x35643872,0x3a6dbba8,0xbb3b361f,0xb81d3ba8,0x3a6db23e,0x395fbbf6,0xb8c43b64,0x36d72e46,0x3bfebaa7,0x381dbb0e,
  0x395fb61f,0x3beabb0e,0x3addbbd9,0x3564b913,0x3addbb64,0x395fba2f,0x36d7b872,0x30b2b4a5,0x35643b64,0xb3c6bba8,0x30b23bd9,0xaa48bbf6,
  0x3beab61f,0xbb88ae46,0x395f3872,0xb3c6bb0e,0x2a48bb64,0xba6d3b0e,0x3bc3b23e,0xb6d7b913,0xbbc3361f,0x2a483a2f,0x3b88baa7,0xb8c4b4a5,
  0xb6d73b64,0x3addb4a5,0x38c4bbd9,0xb9ed2e46,0x3a6db61f,0x3b3bbbf6,0x2a48b872,0xbadd378b,0x39edbb64,0x30b2b78b,0xb81d323e,0xbb883a2f,
  0xb81d361f,0xb9ed3913,0xbb3b3aa7,0xbbea3ba8,0xbbfe3c00,0xbbea3bf6,0xbbc33bd9,0xbb883ba8,0xbbc33c00,0xb9ed3b0e,0xb5643872,0x30b22e46,
  0xbb3b3c00,0xb3c63913,0x38c4b23e,0x3bfebb0e,0xba6d3c00,0x356434a5,0x3bfebaa7,0x33c6ba2f,0xb95f3c00,0x3a6dae46,0x381dbbd9,0xbb3b34a5,
  0xb81d3c00,0x3bfeb78b,0xb6d7b872,0xb8c43bf6,0xb5643c00,0x3addba2f,0xbbea323e,0x395f378b,0xb0b23c00,0x36d7bba8,0xb95f3aa7,0x3addb913,
  0xaa480000,0xb0b22e46,0xb3c6323e,0xb56434a5,0xb3c60000,0xb95f378b,0xbb883aa7,0xbbea3bf6,0xb6d70000,0xbbc33a2f,0xba6d3bd9,0xaa48378b,
  0xb8c40000,0xbb883ba8,0x2a483872,0x3bc3b913,0xb9ed0000,0xb8c43bf6,0x3addb23e,0x36d7bba8,0xbadd0000,0xaa483b0e,0x3b3bbaa7,0xba6dae46,
  0xbb880000,0x381d3913,0x30b2bbd9,0xb9ed3b0e,0xbbea0000,0x3b3b34a5,0xb9edb872,0x381d3a2f,0xbb3b3b64,0xbadd3b0e,0xba6d3aa7,0xb9ed3a2f,
  0x38c4b61f,0x3b3bba2f,0x3bfebbd9,0x3addbba8,0x395fbb64,0xb0b2b4a5,0xbadd3872,0xbb883bf6,0xbadd361f,0xb9ed3bf6,0x36d7323e,0x3beabb0e,
  0xb5643b64,0x3bc3b78b,0x30b2baa7,0xbbfe3913,0x3beab61f,0xb564b913,0xb95f3bd9,0x3bc3b4a5,0xaa48bb64,0xb8c43ba8,0x3bc3b872,0xbb3bae46,
  0xbbc3361f,0x3bfeae46,0xbb88b23e,0x3a6d378b,0xb6d7361f,0xb81d378b,0xb8c43872,0xb95f3913,0xba6d3b64,0xb6d73913,0x2a48323e,0x381db4a5,
  0x39edb61f,0x3beabba8,0x381dbaa7,0xb564ae46,0x381dbb64,0xb95f2e46,0xbb3b3bd9,0x30b2378b,0xbb88361f,0xb3c63b0e,0x3beab872,0x2a48ba2f,
  0xb0b23b64,0x3b88ba2f,0xb9edb23e,0xb3c63ba8,0x3bfeb61f,0xba6db4a5,0x33c63aa7,0x36d7bbf6,0xb3c6bb64,0xaa483bf6,0x3564bbd9,0xb8c43b0e,
  0xb95f39a8,0xb8c43913,0xb81d3872,0xb6d7378b,0x381db9a8,0x2a48b4a5,0xb6d7323e,0xba6d3913,0xb56439a8,0x381dae46,0x3beabaa7,0x39edbba8,
  0x30b2b9a8,0xbb3b378b,0xb95f3bd9,0x381d2e46,0x2a4839a8,0x3beaba2f,0xb3c6b872,0xbb883b0e,0xb3c6b9a8,0xb9ed3ba8,0x3b88b23e,0xb0b2ba2f,
  0x36d739a8,0x33c6bbf6,0xba6d3aa7,0x3bfeb4a5,0xb8c4b9a8,0x35643b0e,0xaa48bbd9,0xb3c63bf6,0xb9ed39a8,0xba6d3a2f,0xbadd3aa7,0xbb3b3b0e,
  0x3addb9a8,0x3bfebba8,0x3b3bbbd9,0x38c4ba2f,0xbb8839a8,0xbadd3bf6,0xb0b23872,0x395fb4a5,0x3beab9a8,0x36d7bb0e,0xb9ed323e,0xbadd3bf6,
  0xbbfe39a8,0x30b23913,0x3bc3baa7,0xb564b78b,0x3bc3b9a8,0xb95fb4a5,0xb5643bd9,0x3beab913,0xbb3b39a8,0x3bc3ae46,0xb8c4b872,0xaa483ba8,
  0x3a6db9a8,0xbb88378b,0x3bfeb23e,0xbbc3ae46,0xb564361f,0xb3c634a5,0xb0b2323e,0xaa482e46,0xbbea3b64,0xbb883bf6,0xb95f3aa7,0xb3c6378b,
  0xaa48b61f,0xba6d378b,0xbbc33bd9,0xb6d73a2f,0x3bc3bb64,0x2a48b913,0xbb883872,0xb8c43ba8,0x36d7361f,0x3addbba8,0xb8c4b23e,0xb9ed3bf6,
  0xba6d3b64,0x3b3bae46,0xaa48baa7,0xbadd3b0e,0xb9edb61f,0x30b23b0e,0x381dbbd9,0xbb883913,0x381dbb64,0xb9ed3a2f,0x3b3bb872,0xbbea34a5,
  0xbb883b64,0xbbc33ba8,0xbbea3bd9,0xbbfe3bf6,0x30b2b61f,0xb5642e46,0xb9ed3872,0xbbc33b0e,0x3bfebb64,0x38c4bb0e,0xb3c6b23e,0xbb3b3913,
  0x33c6361f,0x3bfeba2f,0x3564baa7,0xba6d34a5,0xbb3b3b64,0x381d34a5,0x3a6dbbd9,0xb95fae46,0xb8c4b61f,0xb6d73bf6,0x3bfeb872,0xb81db78b,
  0x395fbb64,0xbbea378b,0x3add323e,0xb564ba2f,0x3add361f,0xb95fb913,0x36d73aa7,0xb0b2bba8,0x2a483c00,0xb0b2bbf6,0x33c63bd9,0xb564bba8,
  0x33c63c00,0xb95fbb0e,0x3b883872,0xbbeaae46,0x36d73c00,0xbbc3b913,0x3a6db23e,0xaa483b0e,0x38c43c00,0xbb88b4a5,0xaa48baa7,0x3bc33a2f,
  0x39ed3c00,0xb8c42e46,0xbaddbbd9,0x36d7b4a5,0x3add3c00,0xaa48378b,0xbb3bb872,0xba6dbbf6,0x3b883c00,0x381d3a2f,0xb0b2323e,0xb9edb78b,
  0x3bea3c00,0x3b3b3ba8,0x39ed3aa7,0x381d3913,0xbbfe0000,0x3beaae46,0xbbc3323e,0x3b88b4a5,0xbbc30000,0x39edb78b,0xb5643aa7,0xb0b2bbf6,
  0xbb3b0000,0x33c6ba2f,0x38c43bd9,0xbbfeb78b,0xba6d0000,0xb564bba8,0x3bfe3872,0xb3c63913,0xb95f0000,0xba6dbbf6,0x381db23e,0x3b3b3ba8,
  0xb81d0000,0xbbfebb0e,0xb6d7baa7,0x38c42e46,0xb5640000,0xbaddb913,0xbbeabbd9,0xb95fbb0e,0xb0b20000,0xb6d7b4a5,0xb95fb872,0xbaddba2f,
  0x36d73b64,0xb81dbb0e,0x38c43aa7,0xb95fba2f,0x3a6db61f,0xb6d73a2f,0xaa48bbd9,0x381d3ba8,0xb9edbb64,0x3bea34a5,0xb81d3872,0xb564bbf6,
  0xb81d361f,0xb95fbbf6,0x3b3b323e,0x30b23b0e,0x3b883b64,0xb3c6378b,0xbbeabaa7,0x2a48b913,0x30b2b61f,0x3b883913,0x39ed3bd9,0xb3c634a5,
  0xbbfebb64,0xba6dbba8,0xb3c6b872,0x36d72e46,0x33c6361f,0xaa482e46,0xb564b23e,0xb8c4b78b,0xbb3b361f,0x3addb78b,0xba6d3872,0x39edb913,
  0x38c43b64,0xbb3bb913,0x3bfe323e,0xbadd34a5,0x395fb61f,0x30b23ba8,0xbaddbaa7,0x3b882e46,0xbaddbb64,0x39edae46,0x36d73bd9,0xbbeab78b,
  0xb564361f,0xbbc3bb0e,0x30b2b872,0x3bfe3a2f,0x3bea3b64,0x35643a2f,0xb95fb23e,0xbbc3bba8,0xaa48b61f,0x38c434a5,0x3bc33aa7,0x3b3b3bf6,
  0xbbc3bb64,0xbbfebbf6,0xbb88bbd9,0xba6dbb0e,0x39ed39a8,0xba6db913,0x3add3872,0xbb3bb78b,0xbaddb9a8,0x3bfe34a5,0xbb3b323e,0x38c4b913,
  0x3b8839a8,0xbadd2e46,0x30b2baa7,0x395f3ba8,0xbbeab9a8,0x36d7b78b,0x39ed3bd9,0xbaddae46,0x3bfe39a8,0x30b23a2f,0xbbc3b872,0xb564bb0e,
  0xbbc3b9a8,0xb95fbba8,0x3564b23e,0x3bea3a2f,0x3b3b39a8,0x3bc33bf6,0x38c43aa7,0xaa4834a5,0xba6db9a8,0xbb88bb0e,0xbbfebbd9,0xbbc3bbf6,
  0xb95f39a8,0x38c4ba2f,0xb81d3aa7,0x36d7bb0e,0x381db9a8,0xaa483ba8,0xb6d7bbd9,0x3a6d3a2f,0xb56439a8,0xb81dbbf6,0x3bea3872,0xb9ed34a5,
  0x30b2b9a8,0x3b3b3b0e,0xb95f323e,0xb81dbbf6,0x2a4839a8,0xbbeab913,0xb3c6baa7,0x3b88378b,0xb3c6b9a8,0x39ed34a5,0x3b883bd9,0x30b23913,
  0x36d739a8,0xb3c62e46,0xba6db872,0xbbfebba8,0xb8c4b9a8,0xb564b78b,0xaa48b23e,0x33c62e46,0x3b88361f,0xbbc3b4a5,0x3bea323e,0xbbfeae46,
  0xb0b23b64,0xb564bbf6,0x39ed3aa7,0xbbc3b78b,0xbbfeb61f,0x38c4b78b,0x33c63bd9,0xbb3bba2f,0xb3c6bb64,0x3bfe3913,0xb5643872,0xba6dbba8,
  0x3b3b361f,0x381d3ba8,0xba6db23e,0xb95fbbf6,0x38c43b64,0xb6d72e46,0xbbfebaa7,0xb81dbb0e,0xb95fb61f,0xbbeabb0e,0xbaddbbd9,0xb564b913,
  0xbaddbb64,0xb95fba2f,0xb6d7b872,0xb0b2b4a5,0xb5643b64,0x33c6bba8,0xb0b23bd9,0x2a48bbf6,0xbbeab61f,0x3b88ae46,0xb95f3872,0x33c6bb0e,
  0xaa48bb64,0x3a6d3b0e,0xbbc3b23e,0x36d7b913,0x3bc3361f,0xaa483a2f,0xbb88baa7,0x38c4b4a5,0x36d73b64,0xbaddb4a5,0xb8c4bbd9,0x39ed2e46,
  0xba6db61f,0xbb3bbbf6,0xaa48b872,0x3add378b,0xb9edbb64,0xb0b2b78b,0x381d323e,0x3b883a2f,0x381d361f,0x39ed3913,0x3b3b3aa7,0x3bea3ba8,
  0x30003000,0x2fff2fff,0xe480000,0x1b111a48,0x30003000,0x2fff2fff,0x14b61248,0x1c521bda,0x30003000,0x2ffe2fff,0x17db1648,0x1d1b1cb6,
  0x30003000,0x2ffe2ffe,0x197f18b6,0x1de31d7f,0x30003000,0x2fed2ff1,0x17db0000,0x246723d6,0x2ffe2fff,0x2fe32fe8,0x1de31bda,0x256024e4,
  0x2ffa2ffc,0x2fd72fdd,0x20e71fd9,0x265725db,0x2ff42ff7,0x2fca2fd1,0x22dc21e2,0x274c26d2,0x2fff3000,0x2fc12fce,0x1b110000,0x27df2703,
  0x2ff92ffd,0x2fa22fb2,0x214c1f11,0x28c9285d,0x2fed2ff4,0x2f7d2f91,0x2467230e,0x299f2934,0x2fda2fe4,0x2f532f69,0x26262547,0x2a702a08,
  0x2ffe3000,0x2f7d2f99,0x1d1b0000,0x299f2905,0x2ff12ff9,0x2f3e2f5f,0x23a4211a,0x2acc2a37,0x2fd72fe6,0x2ef32f1a,0x26572515,0x2bee2b5e,
  0x2fb12fc6,0x2e9c2ec9,0x28692796,0x2c812c3d,0x2ffd3000,0x2f222f50,0x1eac0000,0x2b3d2a7c,0x2fe72ff5,0x2eb82ef0,0x24fd22aa,0x2c582bf9,
  0x2fbb2fd4,0x2e3b2e7c,0x282026a1,0x2d052cb0,0x2f792f9d,0x2dad2df6,0x29b628ed,0x2da42d56,0x2ffc3000,0x2eb12ef6,0x201f0000,0x2c622be3,
  0x2fda2fef,0x2e132e65,0x2626241d,0x2d352cce,0x2f972fbc,0x2d5b2dba,0x29112814,0x2df22d96,0x2f332f69,0x2c8c2cf6,0x2af92a08,0x2e952e47,
  0x2ffa3000,0x2e2b2e8a,0x20e70000,0x2d182c9b,0x2fca2fe8,0x2d512dc3,0x274c24e4,0x2dfa2d8d,0x2f6b2fa0,0x2c582cd8,0x29fd28d5,0x2eb82e5e,
  0x2ee02f2b,0x2a872ba1,0x2c172b1b,0x2f4e2f08,0x2ff83000,0x2d922e0f,0x21b00000,0x2dbe2d3a,0x2fb72fe0,0x2c772d09,0x283825aa,0x2ea32e37,
  0x2f392f80,0x2a702bb7,0x2ae32993,0x2f532f02,0x2e7f2ee3,0x277d291d,0x2cab2c12,0x2fc72f95,0x2ff63000,0x2ce72d84,0x22780000,0x2e522dcb,
  0x2fa22fd6,0x2b102c3d,0x28c9266f,0x2f2e2ec9,0x2eff2f5a,0x28082993,0x2bc22a4e,0x2fbe2f80,0x2e132e92,0x1eac24e4,0x2d352c91,0x2ffd2fe8,
  0x2ff33000,0x2c2d2cec,0x23400000,0x2ed32e4f,0x2f8a2fcb,0x29112ac1,0x29582734,0x2f972f41,0x2ebf2f30,0x221426a1,0x2c4d2b05,0x2ff72fd4,
  0x2d9b2e37,0xa43698b6,0x2db52d09,0x2fee3000,0x2ff03000,0x2acc2c48,0x24040000,0x2f3e2ec2,0x2f702fc0,0x25f428ed,0x29e527f7,0x2fdc2f9d,
  0x2e782f02,0xa01f1fd9,0x2cb52bb7,0x2ffc2ffc,0x2d182dd4,0xa8f9a60d,0x2e2b2d7b,0x2f9b2fdb,0x2fed3000,0x29292b32,0x24670000,0x2f932f25,
  0x2f532fb2,0x1eac260d,0x2a70285d,0x2ffd2fdb,0x2e2b2ed0,0xa71ba17e,0x2d182c32,0x2fcd2ff8,0x2c8c2d69,0xabaca9ab,0x2e952de5,0x2f052f7b,
  0x2fe93000,0x26ea29c2,0x24cb0000,0x2fd02f77,0x2f332fa4,0xa14c2051,0x2af928bd,0x2ff92ffb,0x2dd82e99,0xa9fda765,0x2d762c87,0x2f6b2fc9,
  0x2bee2cf6,0xad0eac12,0x2ef32e47,0x2e332ee3,0x2fe53000,0x22dc2844,0x252e0000,0x2ff42fb6,0x2f112f95,0xa6ea9f11,0x2b80291d,0x2fd02ffd,
  0x2d802e5e,0xac22a9f1,0x2dd02cd8,0x2ed92f6e,0x2ab52c7c,0xae1bad30,0x2f432ea0,0x2d2b2e17,0x2fe13000,0x8e482579,0x25910000,0x30002fe2,
  0x2eed2f84,0xa987a5aa,0x2c02297c,0x2f822fe0,0x2d222e1f,0xad2bac07,0x2e232d27,0x2e1b2ee9,0x29702bf9,0xaef3ae27,0x2f862ef0,0x2bee2d1d,
  0x2fdc3000,0xa34020b5,0x25f40000,0x2ff32ffa,0x2ec62f72,0xab80a8bd,0x2c4229da,0x2f112fa4,0x2cbf2ddc,0xae13ad00,0x2e712d72,0x2d352e3f,
  0x28202aee,0xaf8faef0,0x2fbb2f36,0x29402bf9,0x2fd73000,0xa71b9a48,0x26570000,0x2fcd2fff,0x2e9c2f5f,0xacabaa93,0x2c812a37,0x2e7f2f4b,
  0x2c582d96,0xaed3addc,0x2eb82dba,0x2c2d2d72,0x259129da,0xafe9af84,0x2fe12f72,0x24cb297c,0x2fd23000,0xa940a3d6,0x26b90000,0x2f8f2ff1,
  0x2e712f4b,0xad80ac28,0x2cbf2a93,0x2dd02ed6,0x2bd82d4d,0xaf67ae99,0x2ef92dfe,0x2a142c87,0x21b028bd,0xafffafe0,0x2ff82fa4,0x9c5225aa,
  0x2fcd3000,0xaae3a703,0x271b0000,0x2f392fce,0x2e432f36,0xae3bacf6,0x2cfb2aee,0x2d052e47,0x2af92d00,0xafcaaf30,0x2f332e3f,0x274c2b05,
  0xe482734,0xafd0b000,0x30002fcb,0xa6ea1248,0x2fc73000,0xac38a905,0x277d0000,0x2ecc2f99,0x2e132f20,0xaed9adb1,0x2d352b48,0x2c222d9f,
  0x2a142cb0,0xaffbafa0,0x2f672e7c,0x208328d5,0xa14c24e4,0xaf5dafe4,0x2ff92fe8,0xaa42a547,0x2fc13000,0xacf1aa7c,0x27df0000,0x2e4b2f50,
  0x2de12f08,0xaf58ae56,0x2d6d2ba1,0x2a592ce2,0x29292c5d,0xaff8afe6,0x2f932eb5,0xa1b02515,0xa560211a,0xaeaaaf8c,0x2fe32ff9,0xac6da94c,
  0x2fbb3000,0xad9babe3,0x28200000,0x2db52ef6,0x2dad2ef0,0xafb4aee3,0x2da42bf9,0x28512c12,0x28382c07,0xafc1b000,0x2fb72ee9,0xa7df1648,
  0xa8081248,0xadbeaefc,0x2fbe3000,0xad92abcd,0x2fb43000,0xae33ac9b,0x28510000,0x2d0e2e8a,0x2d762ed6,0xafedaf55,0x2dd82c28,0x24672a65,
  0x26882b5e,0xaf58afed,0x2fd52f1a,0xaa59a44e,0xa958a051,0xaca0ae37,0x2f8a2ffb,0xae87ad09,0x2fad3000,0xaeb8ad3a,0x28810000,0x2c582e0f,
  0x2d3e2ebc,0xb000afab,0x2e0b2c52,0xe48288d,0x24992aaa,0xaebfafaf,0x2feb2f46,0xac4da875,0xaa9ea480,0xaab5ad43,0x2f492fec,0xaf43ae07,
  0x2fa63000,0xaf28adcb,0x28b10000,0x2b262d84,0x2d052ea0,0xafeeafe4,0x2e3b2c7c,0xa4362547,0x214c29f1,0xadfaaf46,0x2ff92f6e,0xad51aaaa,
  0xabd8a6d2,0xa7dfac28,0x2ef92fd1,0xafc1aed6,0x2f9e3000,0xaf82ae4f,0x28e10000,0x29872cec,0x2cc92e83,0xafb7affe,0x2e692ca6,0xa8381d7f,
  0x197f2934,0xad0eaeb5,0x30002f91,0xae33ac5d,0xac81a88d,0xa01fa9da,0x2e9c2fab,0xaffcaf72,0x2f973000,0xafc4aec2,0x29110000,0x27ae2c48,
  0x2c8c2e65,0xaf5daff9,0x2e952cce,0xaa42a11a,0x9d1b2875,0xac02adfe,0x2ffe2faf,0xaeedad4d,0xad0ea9ab,0x23a4a66f,0x2e332f7b,0xaff1afd6,
  0x2f8f3000,0xafeeaf25,0x29400000,0x24362b32,0x2c4d2e47,0xaee0afd6,0x2ebf2cf6,0xac17a66f,0xa2782765,0xa9b6ad27,0x2ff62fc9,0xaf79ae1f,
  0xad92aac1,0x28c99bda,0x2dbe2f41,0xafa2afff,0x2f863000,0xb000af77,0x29700000,0x197f29c2,0x2c0d2e27,0xae43af95,0x2ee62d1d,0xacfba91d,
  0xa52e25db,0xa688ac32,0x2fe52fdd,0xafd5aed0,0xae0babcd,0x2b802480,0x2d3e2efc,0xaf11afec,0x2f7d3000,0xaff8afb6,0x299f0000,0xa1b02844,
  0x2b962e07,0xad89af36,0x2f0b2d43,0xadc7aaee,0xa71b244e,0x9de3aa4e,0x2fcd2fed,0xaffeaf5a,0xae78ac67,0x2cfb28ed,0x2cb52eae,0xae43af9d,
  0x2f743000,0xafd7afe2,0x29ce0000,0xa6572579,0x2b102de5,0xacb5aebc,0x2f2e2d69,0xae78ac52,0xa881217e,0x2340a814,0x2fad2ff8,0xaff3afbc,
  0xaed9ace2,0x2e0b2b75,0x2c222e56,0xad3eaf14,0x2f6b3000,0xaf9eaffa,0x29fd0000,0xa8e120b5,0x2a872dc3,0xab96ae27,0x2f4e2d8d,0xaf0bad1d,
  0xa9701cb6,0x2851a30e,0x2f862fff,0xafb4aff4,0xaf2ead56,0x2ee62ce2,0x2b102df6,0xac0dae56,
};

#define PROF(slot) do {} while (0)
#define PROFA(slot, dep) do {} while (0)
#define PROF3(slot) do {} while (0)
#define PROF2(slot) do {} while (0)

__device__ __forceinline__ uint32_t smem_u32(const void* p) { return (uint32_t)__cvta_generic_to_shared(p); }

__device__ __forceinline__ void mbar_init(uint32_t a, uint32_t c) {
  asm volatile("mbarrier.init.shared::cta.b64 [%0], %1;\n" ::"r"(a), "r"(c) : "memory");
}
__device__ __forceinline__ void mbar_expect_tx(uint32_t a, uint32_t bytes) {
  asm volatile("mbarrier.arrive.expect_tx.shared::cta.b64 _, [%0], %1;\n" ::"r"(a), "r"(bytes) : "memory");
}
__device__ __forceinline__ void mbar_arrive_cluster(uint32_t cluster_addr) {
  asm volatile("mbarrier.arrive.shared::cluster.b64 _, [%0];\n" ::"r"(cluster_addr) : "memory");
}
__device__ __forceinline__ void mbar_arrive_cluster_n(uint32_t cluster_addr, uint32_t n) {
  asm volatile("mbarrier.arrive.shared::cluster.b64 _, [%0], %1;\n" ::"r"(cluster_addr), "r"(n) : "memory");
}
__device__ __forceinline__ bool mbar_try(uint32_t a, uint32_t parity) {
  uint32_t ok;
  asm volatile("{\n.reg .pred p;\nmbarrier.try_wait.parity.shared::cta.b64 p, [%1], %2;\nselp.u32 %0, 1, 0, p;\n}\n"
               : "=r"(ok) : "r"(a), "r"(parity) : "memory");
  return ok;
}
__device__ __forceinline__ void mbar_wait(uint32_t a, uint32_t parity) {
  if (mbar_try(a, parity)) return;
#pragma unroll 1
  for (int n = 0; n < SPIN_LIMIT; n++)
    if (mbar_try(a, parity)) break;
}
__device__ __forceinline__ bool elect_one() {
  uint32_t p;
  asm volatile("{\n.reg .pred P;\nelect.sync _|P, 0xffffffff;\nselp.u32 %0, 1, 0, P;\n}\n" : "=r"(p));
  return p;
}
__device__ __forceinline__ uint32_t mapa(uint32_t a, uint32_t rank) {
  uint32_t r;
  asm volatile("mapa.shared::cluster.u32 %0, %1, %2;\n" : "=r"(r) : "r"(a), "r"(rank));
  return r;
}
__device__ __forceinline__ void nb_sync(int id, int n) { asm volatile("bar.sync %0, %1;\n" ::"r"(id), "r"(n) : "memory"); }
__device__ __forceinline__ void nb_arrive(int id, int n) { asm volatile("bar.arrive %0, %1;\n" ::"r"(id), "r"(n) : "memory"); }
__device__ __forceinline__ void cluster_sync_all() {
  asm volatile("barrier.cluster.arrive.relaxed.aligned;\nbarrier.cluster.wait.aligned;\n" ::: "memory");
}
__device__ __forceinline__ void fence_async_smem() { asm volatile("fence.proxy.async.shared::cta;\n" ::: "memory"); }
__device__ __forceinline__ void fence_async_all() { asm volatile("fence.proxy.async.global;\n" ::: "memory"); }

__device__ __forceinline__ void tma_load_3d(uint32_t dst, const CUtensorMap* tm, uint32_t bar, int c0, int c1, int c2) {
  asm volatile(
      "cp.async.bulk.tensor.3d.shared::cluster.global.mbarrier::complete_tx::bytes [%0], [%1, {%3, %4, %5}], [%2];\n"
      ::"r"(dst), "l"(tm), "r"(bar), "r"(c0), "r"(c1), "r"(c2) : "memory");
}
__device__ __forceinline__ void tma_load_4d(uint32_t dst, const CUtensorMap* tm, uint32_t bar, int c0, int c1, int c2, int c3) {
  asm volatile(
      "cp.async.bulk.tensor.4d.shared::cluster.global.mbarrier::complete_tx::bytes [%0], [%1, {%3, %4, %5, %6}], [%2];\n"
      ::"r"(dst), "l"(tm), "r"(bar), "r"(c0), "r"(c1), "r"(c2), "r"(c3) : "memory");
}
__device__ __forceinline__ void tma_load_3d_mc(uint32_t dst, const CUtensorMap* tm, uint32_t bar, int c0, int c1, int c2) {
  asm volatile(
      "cp.async.bulk.tensor.3d.shared::cluster.global.mbarrier::complete_tx::bytes.multicast::cluster [%0], [%1, {%3, %4, %5}], [%2], %6;\n"
      ::"r"(dst), "l"(tm), "r"(bar), "r"(c0), "r"(c1), "r"(c2), "h"((uint16_t)3) : "memory");
}
__device__ __forceinline__ void tma_load_2d(uint32_t dst, const CUtensorMap* tm, uint32_t bar, int c0, int c1) {
  asm volatile(
      "cp.async.bulk.tensor.2d.shared::cluster.global.mbarrier::complete_tx::bytes [%0], [%1, {%3, %4}], [%2];\n"
      ::"r"(dst), "l"(tm), "r"(bar), "r"(c0), "r"(c1) : "memory");
}
__device__ __forceinline__ void bulk_load(uint32_t dst, const void* src, uint32_t bytes, uint32_t bar) {
  asm volatile("cp.async.bulk.shared::cluster.global.mbarrier::complete_tx::bytes [%0], [%1], %2, [%3];\n"
               ::"r"(dst), "l"(src), "r"(bytes), "r"(bar) : "memory");
}
__device__ __forceinline__ void tma_store_2d(const CUtensorMap* tm, uint32_t src, int c0, int c1) {
  asm volatile("cp.async.bulk.tensor.2d.global.shared::cta.bulk_group [%0, {%2, %3}], [%1];\n"
               ::"l"(tm), "r"(src), "r"(c0), "r"(c1) : "memory");
}
__device__ __forceinline__ void tma_store_3d(const CUtensorMap* tm, uint32_t src, int c0, int c1, int c2) {
  asm volatile("cp.async.bulk.tensor.3d.global.shared::cta.bulk_group [%0, {%2, %3, %4}], [%1];\n"
               ::"l"(tm), "r"(src), "r"(c0), "r"(c1), "r"(c2) : "memory");
}
__device__ __forceinline__ void bulk_commit() { asm volatile("cp.async.bulk.commit_group;\n" ::: "memory"); }
__device__ __forceinline__ void bulk_wait0() { asm volatile("cp.async.bulk.wait_group 0;\n" ::: "memory"); }
__device__ __forceinline__ void prefetch_tmap(const CUtensorMap* tm) {
  asm volatile("prefetch.tensormap [%0];\n" ::"l"(tm) : "memory");
}

__device__ __forceinline__ void wg_fence() { asm volatile("wgmma.fence.sync.aligned;\n" ::: "memory"); }
__device__ __forceinline__ void wg_commit() { asm volatile("wgmma.commit_group.sync.aligned;\n" ::: "memory"); }
template <int N> __device__ __forceinline__ void wg_wait() {
  asm volatile("wgmma.wait_group.sync.aligned %0;\n" ::"n"(N) : "memory");
}
__device__ __forceinline__ uint64_t mkdesc(uint32_t addr, uint32_t lbo, uint32_t sbo, uint32_t swz) {
  return (uint64_t)((addr & 0x3FFFF) >> 4) | ((uint64_t)(lbo >> 4) << 16) | ((uint64_t)(sbo >> 4) << 32) |
         ((uint64_t)swz << 62);
}

#define R4(d, o) "+f"(d[o + 0]), "+f"(d[o + 1]), "+f"(d[o + 2]), "+f"(d[o + 3])
#define R8(d, o) R4(d, o), R4(d, o + 4)
#define R16(d, o) R8(d, o), R8(d, o + 8)
#define R32(d, o) R16(d, o), R16(d, o + 16)
#define R64(d, o) R32(d, o), R32(d, o + 32)

__device__ __forceinline__ void wgmma_n192(float (&d)[96], uint64_t da, uint64_t db, uint32_t acc) {
  asm volatile(
      "{\n.reg .pred p;\nsetp.ne.u32 p, %98, 0;\n"
      "wgmma.mma_async.sync.aligned.m64n192k16.f32.bf16.bf16 "
      "{%0,%1,%2,%3,%4,%5,%6,%7,%8,%9,%10,%11,%12,%13,%14,%15,%16,%17,%18,%19,%20,%21,%22,%23,%24,%25,%26,%27,%28,%29,%30,%31,"
      "%32,%33,%34,%35,%36,%37,%38,%39,%40,%41,%42,%43,%44,%45,%46,%47,%48,%49,%50,%51,%52,%53,%54,%55,%56,%57,%58,%59,%60,%61,%62,%63,"
      "%64,%65,%66,%67,%68,%69,%70,%71,%72,%73,%74,%75,%76,%77,%78,%79,%80,%81,%82,%83,%84,%85,%86,%87,%88,%89,%90,%91,%92,%93,%94,%95}, "
      "%96, %97, p, 1, 1, 0, 1;\n}\n"
      : R64(d, 0), R32(d, 64)
      : "l"(da), "l"(db), "r"(acc));
}
__device__ __forceinline__ void wgmma_n128(float (&d)[64], uint64_t da, uint64_t db, uint32_t acc) {
  asm volatile(
      "{\n.reg .pred p;\nsetp.ne.u32 p, %66, 0;\n"
      "wgmma.mma_async.sync.aligned.m64n128k16.f32.bf16.bf16 "
      "{%0,%1,%2,%3,%4,%5,%6,%7,%8,%9,%10,%11,%12,%13,%14,%15,%16,%17,%18,%19,%20,%21,%22,%23,%24,%25,%26,%27,%28,%29,%30,%31,"
      "%32,%33,%34,%35,%36,%37,%38,%39,%40,%41,%42,%43,%44,%45,%46,%47,%48,%49,%50,%51,%52,%53,%54,%55,%56,%57,%58,%59,%60,%61,%62,%63}, "
      "%64, %65, p, 1, 1, 0, 1;\n}\n"
      : R64(d, 0)
      : "l"(da), "l"(db), "r"(acc));
}
template <int N> __device__ __forceinline__ void fence_regs(float (&d)[N]) {
#pragma unroll
  for (int i = 0; i < N; i++) asm volatile("" : "+f"(d[i])::"memory");
}

__device__ __forceinline__ void mma16816(float (&d)[4], uint32_t a0, uint32_t a1, uint32_t a2, uint32_t a3, uint32_t b0,
                                         uint32_t b1) {
  asm("mma.sync.aligned.m16n8k16.row.col.f32.bf16.bf16.f32 {%0,%1,%2,%3}, {%4,%5,%6,%7}, {%8,%9}, {%0,%1,%2,%3};\n"
      : "+f"(d[0]), "+f"(d[1]), "+f"(d[2]), "+f"(d[3])
      : "r"(a0), "r"(a1), "r"(a2), "r"(a3), "r"(b0), "r"(b1));
}
__device__ __forceinline__ void mma16816_z(float (&d)[4], uint32_t a0, uint32_t a1, uint32_t a2, uint32_t a3, uint32_t b0,
                                           uint32_t b1) {
  asm("mma.sync.aligned.m16n8k16.row.col.f32.bf16.bf16.f32 {%0,%1,%2,%3}, {%4,%5,%6,%7}, {%8,%9}, {%10,%10,%10,%10};\n"
      : "=f"(d[0]), "=f"(d[1]), "=f"(d[2]), "=f"(d[3])
      : "r"(a0), "r"(a1), "r"(a2), "r"(a3), "r"(b0), "r"(b1), "f"(0.f));
}
__device__ __forceinline__ void ldsm4t(uint32_t (&r)[4], uint32_t a) {
  asm volatile("ldmatrix.sync.aligned.m8n8.x4.trans.shared.b16 {%0,%1,%2,%3}, [%4];\n"
               : "=r"(r[0]), "=r"(r[1]), "=r"(r[2]), "=r"(r[3]) : "r"(a) : "memory");
}
__device__ __forceinline__ void ldsm2t(uint32_t& r0, uint32_t& r1, uint32_t a) {
  asm volatile("ldmatrix.sync.aligned.m8n8.x2.trans.shared.b16 {%0,%1}, [%2];\n" : "=r"(r0), "=r"(r1) : "r"(a) : "memory");
}
__device__ __forceinline__ void st_async128(uint32_t a, uint32_t bar, uint32_t x, uint32_t y, uint32_t z, uint32_t w) {
  asm volatile("st.async.weak.shared::cluster.mbarrier::complete_tx::bytes.v4.b32 [%0], {%2,%3,%4,%5}, [%1];\n"
               ::"r"(a), "r"(bar), "r"(x), "r"(y), "r"(z), "r"(w) : "memory");
}
__device__ __forceinline__ void mbar_arrive(uint32_t a) {
  asm volatile("mbarrier.arrive.shared::cta.b64 _, [%0];\n" ::"r"(a) : "memory");
}
__device__ __forceinline__ void stsm4(uint32_t a, uint32_t r0, uint32_t r1, uint32_t r2, uint32_t r3) {
  asm volatile("stmatrix.sync.aligned.m8n8.x4.shared.b16 [%0], {%1,%2,%3,%4};\n"
               ::"r"(a), "r"(r0), "r"(r1), "r"(r2), "r"(r3) : "memory");
}
__device__ __forceinline__ void stsm4t(uint32_t a, uint32_t r0, uint32_t r1, uint32_t r2, uint32_t r3) {
  asm volatile("stmatrix.sync.aligned.m8n8.x4.trans.shared.b16 [%0], {%1,%2,%3,%4};\n"
               ::"r"(a), "r"(r0), "r"(r1), "r"(r2), "r"(r3) : "memory");
}
__device__ __forceinline__ uint2 lds64(uint32_t a) {
  uint2 v;
  asm volatile("ld.shared.v2.u32 {%0,%1}, [%2];\n" : "=r"(v.x), "=r"(v.y) : "r"(a));
  return v;
}
__device__ __forceinline__ uint4 lds128(uint32_t a) {
  uint4 v;
  asm volatile("ld.shared.v4.u32 {%0,%1,%2,%3}, [%4];\n" : "=r"(v.x), "=r"(v.y), "=r"(v.z), "=r"(v.w) : "r"(a) : "memory");
  return v;
}
__device__ __forceinline__ void sts128(uint32_t a, uint32_t x, uint32_t y, uint32_t z, uint32_t w) {
  asm volatile("st.shared.v4.u32 [%0], {%1,%2,%3,%4};\n" ::"r"(a), "r"(x), "r"(y), "r"(z), "r"(w) : "memory");
}
__device__ __forceinline__ void sts64(uint32_t a, uint32_t x, uint32_t y) {
  asm volatile("st.shared.v2.u32 [%0], {%1,%2};\n" ::"r"(a), "r"(x), "r"(y) : "memory");
}
__device__ __forceinline__ uint32_t pack_bf16(float lo, float hi) {
  uint32_t r;
  asm("cvt.rn.bf16x2.f32 %0, %1, %2;\n" : "=r"(r) : "f"(hi), "f"(lo));
  return r;
}
__device__ __forceinline__ uint32_t bmul2(uint32_t a, uint32_t b) {
  uint32_t r;
  asm("mul.rn.bf16x2 %0, %1, %2;\n" : "=r"(r) : "r"(a), "r"(b));
  return r;
}
__device__ __forceinline__ uint32_t bmax2(uint32_t a, uint32_t b) {
  uint32_t r;
  asm("max.bf16x2 %0, %1, %2;\n" : "=r"(r) : "r"(a), "r"(b));
  return r;
}
__device__ __forceinline__ uint32_t bfma2(uint32_t a, uint32_t b, uint32_t c) {
  uint32_t r;
  asm("fma.rn.bf16x2 %0, %1, %2, %3;\n" : "=r"(r) : "r"(a), "r"(b), "r"(c));
  return r;
}
__device__ __forceinline__ uint32_t badd2(uint32_t a, uint32_t b) {
  uint32_t r;
  asm("add.rn.bf16x2 %0, %1, %2;\n" : "=r"(r) : "r"(a), "r"(b));
  return r;
}
__device__ __forceinline__ void prefetch_l2(const void* p) { asm volatile("prefetch.global.L2 [%0];\n" ::"l"(p)); }
__device__ __forceinline__ void cp_async16n(uint32_t dst, const void* src) {
  asm volatile("cp.async.cg.shared.global [%0], [%1], 16;\n" ::"r"(dst), "l"(src) : "memory");
}
__device__ __forceinline__ void cp_async16(uint32_t dst, const void* src, uint32_t srcbytes) {
  asm volatile("cp.async.cg.shared.global.L2::256B [%0], [%1], 16, %2;\n" ::"r"(dst), "l"(src), "r"(srcbytes) : "memory");
}
__device__ __forceinline__ uint32_t ld_acquire(const uint32_t* p) {
  uint32_t v;
  asm volatile("ld.acquire.gpu.global.u32 %0, [%1];\n" : "=r"(v) : "l"(p) : "memory");
  return v;
}
__device__ __forceinline__ uint32_t ld_relaxed(const uint32_t* p) {
  uint32_t v;
  asm volatile("ld.relaxed.gpu.global.u32 %0, [%1];\n" : "=r"(v) : "l"(p) : "memory");
  return v;
}
__device__ __forceinline__ void st_release(uint32_t* p, uint32_t v) {
  asm volatile("st.release.gpu.global.u32 [%0], %1;\n" ::"l"(p), "r"(v) : "memory");
}
__device__ __forceinline__ void wait_flag(const uint32_t* p, uint32_t want) {
  int n = 0;
  while (ld_relaxed(p) != want && ++n < SPIN_LIMIT) __nanosleep(40);
  (void)ld_acquire(p);
}

struct Params {
  const __nv_bfloat16* x;
  const __nv_bfloat16* w;
  const __nv_bfloat16* q;
  const __nv_bfloat16* k;
  const __nv_bfloat16* v;
  const __nv_bfloat16* shift_k;
  const __nv_bfloat16* ssm_k;
  const __nv_bfloat16* ssm_D;
  const __nv_bfloat16* wo;
  __nv_bfloat16* out;
  uint32_t zero;
};

__device__ __forceinline__ uint32_t lds32(uint32_t a) {
  uint32_t v;
  asm volatile("ld.shared.u32 %0, [%1];\n" : "=r"(v) : "r"(a));
  return v;
}
__device__ __forceinline__ float bf_lo(uint32_t v) {
  uint32_t r;
  asm("prmt.b32 %0, %1, 0, 0x1044;\n" : "=r"(r) : "r"(v));
  return __uint_as_float(r);
}
__device__ __forceinline__ float bf_hi(uint32_t v) { return __uint_as_float(v & 0xffff0000u); }
__device__ __forceinline__ float ex2(float x) {
  float r;
  asm("ex2.approx.ftz.f32 %0, %1;\n" : "=f"(r) : "f"(x));
  return r;
}
__device__ __forceinline__ float rcp(float x) {
  float r;
  asm("rcp.approx.ftz.f32 %0, %1;\n" : "=f"(r) : "f"(x));
  return r;
}

#define Q4(c, d, o) c(d[o + 0]), c(d[o + 1]), c(d[o + 2]), c(d[o + 3])
#define Q8(c, d, o) Q4(c, d, o), Q4(c, d, o + 4)
#define Q16(c, d, o) Q8(c, d, o), Q8(c, d, o + 8)
#define Q32(c, d) Q16(c, d, 0), Q16(c, d, 16)
#define L8 "{%0,%1,%2,%3,%4,%5,%6,%7}"
#define L16 "{%0,%1,%2,%3,%4,%5,%6,%7,%8,%9,%10,%11,%12,%13,%14,%15}"
#define L32 "{%0,%1,%2,%3,%4,%5,%6,%7,%8,%9,%10,%11,%12,%13,%14,%15,%16,%17,%18,%19,%20,%21,%22,%23,%24,%25,%26,%27,%28,%29,%30,%31}"
__device__ __forceinline__ void fft_rows(uint32_t (&d)[32], const uint32_t (&a)[2][4], uint64_t db) {
  asm volatile("wgmma.mma_async.sync.aligned.m64n128k16.f16.f16.f16 " L32 ", {%32,%33,%34,%35}, %36, 0, 1, 1, 1;\n"
               : Q32("=r", d) : "r"(a[0][0]), "r"(a[0][1]), "r"(a[0][2]), "r"(a[0][3]), "l"(db));
  asm volatile("wgmma.mma_async.sync.aligned.m64n128k16.f16.f16.f16 " L32 ", {%32,%33,%34,%35}, %36, 1, 1, 1, 1;\n"
               : Q32("+r", d) : "r"(a[1][0]), "r"(a[1][1]), "r"(a[1][2]), "r"(a[1][3]), "l"(db + 128));
}
__device__ __forceinline__ void fft_cols(uint32_t (&d)[8], const uint32_t (&a)[2][4], uint64_t db) {
  asm volatile("wgmma.mma_async.sync.aligned.m64n32k16.f16.f16.f16 " L8 ", {%8,%9,%10,%11}, %12, 0, 1, 1, 0;\n"
               : Q8("=r", d, 0) : "r"(a[0][0]), "r"(a[0][1]), "r"(a[0][2]), "r"(a[0][3]), "l"(db));
  asm volatile("wgmma.mma_async.sync.aligned.m64n32k16.f16.f16.f16 " L8 ", {%8,%9,%10,%11}, %12, 1, 1, 1, 0;\n"
               : Q8("+r", d, 0) : "r"(a[1][0]), "r"(a[1][1]), "r"(a[1][2]), "r"(a[1][3]), "l"(db + 64));
}
__device__ __forceinline__ void fft_back(float (&d)[16], uint64_t da, uint64_t db) {
  asm volatile("wgmma.mma_async.sync.aligned.m64n32k16.f32.f16.f16 " L16 ", %16, %17, 0, 1, 1, 1, 1;\n"
               : Q16("=f", d, 0) : "l"(da), "l"(db));
#pragma unroll
  for (int i = 1; i < 4; i++)
    asm volatile("wgmma.mma_async.sync.aligned.m64n32k16.f32.f16.f16 " L16 ", %16, %17, 1, 1, 1, 1, 1;\n"
                 : Q16("+f", d, 0) : "l"(da + 32 * i), "l"(db + 64 * i));
}
__device__ __forceinline__ uint32_t hmul2(uint32_t a, uint32_t b) {
  uint32_t r;
  asm("mul.rn.f16x2 %0, %1, %2;\n" : "=r"(r) : "r"(a), "r"(b));
  return r;
}
__device__ __forceinline__ uint32_t hadd2(uint32_t a, uint32_t b) {
  uint32_t r;
  asm("add.rn.f16x2 %0, %1, %2;\n" : "=r"(r) : "r"(a), "r"(b));
  return r;
}
__device__ __forceinline__ uint32_t hneg2(uint32_t a) {
  uint32_t r;
  asm("neg.f16x2 %0, %1;\n" : "=r"(r) : "r"(a));
  return r;
}
__device__ __forceinline__ uint32_t hfma2(uint32_t a, uint32_t b, uint32_t c) {
  uint32_t r;
  asm("fma.rn.f16x2 %0, %1, %2, %3;\n" : "=r"(r) : "r"(a), "r"(b), "r"(c));
  return r;
}
__device__ __forceinline__ uint32_t pack_f16(float lo, float hi) {
  uint32_t r;
  asm("cvt.rn.f16x2.f32 %0, %1, %2;\n" : "=r"(r) : "f"(hi), "f"(lo));
  return r;
}
__device__ __forceinline__ uint32_t bmaxabs2(uint32_t a, uint32_t b) {
  uint32_t r;
  asm("max.xorsign.abs.bf16x2 %0, %1, %2;\n" : "=r"(r) : "r"(a), "r"(b));
  return r;
}
struct C2 { uint32_t r, i; };
__device__ __forceinline__ C2 cmul(C2 a, C2 b) {
  return C2{hfma2(a.r, b.r, hneg2(hmul2(a.i, b.i))), hfma2(a.r, b.i, hmul2(a.i, b.r))};
}
__device__ __forceinline__ C2 cfma(C2 a, C2 b, C2 c) {
  return C2{hfma2(a.r, b.r, hfma2(hneg2(a.i), b.i, c.r)), hfma2(a.r, b.i, hfma2(a.i, b.r, c.i))};
}
__device__ __forceinline__ C2 cget(const uint32_t (&e)[8], int j, int b) { return C2{e[4 * j + b], e[4 * j + 2 + b]}; }
template <int N> __device__ __forceinline__ void fence_regs(uint32_t (&d)[N]) {
#pragma unroll
  for (int i = 0; i < N; i++) asm volatile("" : "+r"(d[i])::"memory");
}
__device__ __forceinline__ void ldsm4(uint32_t (&r)[4], uint32_t a) {
  asm volatile("ldmatrix.sync.aligned.m8n8.x4.shared.b16 {%0,%1,%2,%3}, [%4];\n"
               : "=r"(r[0]), "=r"(r[1]), "=r"(r[2]), "=r"(r[3]) : "r"(a) : "memory");
}

__device__ __forceinline__ uint32_t movm(uint32_t a) {
  uint32_t r;
  asm volatile("movmatrix.sync.aligned.m8n8.trans.b16 %0, %1;\n" : "=r"(r) : "r"(a));
  return r;
}
template <int C0, int H, bool T> __device__ __forceinline__ void attn_pack(const float (&acc)[96], uint32_t (&d)[8]) {
#pragma unroll
  for (int c = 0; c < 8; c++) {
    asm volatile("cvt.rn.bf16x2.f32 %0, %1, %2;\n" : "=r"(d[c]) : "f"(acc[4 * (C0 + c) + 2 * H + 1]), "f"(acc[4 * (C0 + c) + 2 * H]));
    if (T) d[c] = movm(d[c]);
  }
}
__device__ __forceinline__ void attn_qk(float (&s)[4], const uint32_t (&qlo)[8], const uint32_t (&qhi)[8],
                                        const uint32_t (&k)[8], int c) {
  mma16816_z(s, qlo[c], qhi[c], qlo[c + 1], qhi[c + 1], k[c], k[c + 1]);
  mma16816(s, qlo[c + 2], qhi[c + 2], qlo[c + 3], qhi[c + 3], k[c + 2], k[c + 3]);
}
template <int N> __device__ __forceinline__ void quad_softmax(float (&x)[N][2], uint32_t (&pp)[N]) {
  const float c2 = 1.4426950408889634f;
  uint32_t q[N], mx[N / 2];
#pragma unroll
  for (int n = 0; n < N; n++) {
    const uint32_t r = pack_bf16(x[n][0], x[n][1]);
    q[n] = bfma2(r, 0x3e353e35u, bmul2(r, 0x379e379eu));
    x[n][0] = bf_lo(q[n]);
    x[n][1] = bf_hi(q[n]);
  }
#pragma unroll
  for (int n = 0; n < N / 2; n++)
    mx[n] = bmax2(__byte_perm(q[2 * n], q[2 * n + 1], 0x5410), __byte_perm(q[2 * n], q[2 * n + 1], 0x7632));
#pragma unroll
  for (int o = 1; o <= 2; o++) {
#pragma unroll
    for (int n = 0; n < N / 2; n++) mx[n] = bmax2(mx[n], __shfl_xor_sync(0xffffffffu, mx[n], o));
  }
  float m[N], t[N];
#pragma unroll
  for (int n = 0; n < N / 2; n++) {
    m[2 * n] = bf_lo(mx[n]);
    m[2 * n + 1] = bf_hi(mx[n]);
  }
#pragma unroll
  for (int n = 0; n < N; n++) {
    const float nm = -m[n] * c2;
    x[n][0] = ex2(fmaf(x[n][0], c2, nm));
    x[n][1] = ex2(fmaf(x[n][1], c2, nm));
  }
#pragma unroll
  for (int n = 0; n < N; n += 2) {
    float u0, u1;
    asm("mma.sync.aligned.m16n8k8.row.col.f32.tf32.tf32.f32 {%0,%1,%2,%3}, {%4,%5,%6,%7}, {%8,%8}, {%9,%9,%9,%9};\n"
        : "=f"(t[n]), "=f"(u0), "=f"(t[n + 1]), "=f"(u1)
        : "r"(__float_as_uint(x[n][0])), "r"(__float_as_uint(x[n + 1][0])), "r"(__float_as_uint(x[n][1])),
          "r"(__float_as_uint(x[n + 1][1])), "r"(0x3f800000u), "f"(0.f));
  }
#pragma unroll
  for (int n = 0; n < N; n++) {
    const float inv = rcp(t[n]);
    pp[n] = pack_bf16(x[n][0] * inv, x[n][1] * inv);
  }
}
__device__ __forceinline__ void attn_pv(uint32_t dst, const uint32_t (&vp)[8], const uint32_t (&vo)[8], int c, uint32_t pp,
                                        uint32_t maskLE) {
  const uint32_t b0 = pp & ~maskLE, b1 = pp & maskLE;
  float oa[4], ob[4];
  mma16816_z(oa, vp[c], vp[c + 1], vo[c], vo[c + 1], b0, b1);
  mma16816_z(ob, vp[c + 2], vp[c + 3], vo[c + 2], vo[c + 3], b0, b1);
  stsm4t(dst, pack_bf16(oa[0], oa[1]), pack_bf16(oa[2], oa[3]), pack_bf16(ob[0], ob[1]), pack_bf16(ob[2], ob[3]));
}

template <int MODE>
__global__ void __cluster_dims__(2, 1, 1) __launch_bounds__(NTHREADS, 1)
fused_kernel(const Params p, const __grid_constant__ CUtensorMap tmX, const __grid_constant__ CUtensorMap tmW,
             const __grid_constant__ CUtensorMap tmWo,
             const __grid_constant__ CUtensorMap tmQ, const __grid_constant__ CUtensorMap tmOa,
             const __grid_constant__ CUtensorMap tmOb,
             const __grid_constant__ CUtensorMap tmXh, const __grid_constant__ CUtensorMap tmWh) {
  extern __shared__ __align__(1024) uint8_t smem[];
  if (threadIdx.x < 32) {
    const uint32_t i = (blockIdx.x & 127) * 16 + (threadIdx.x & 15);
    prefetch_l2(threadIdx.x & 16 ? (const char*)p.w + i * 128 : (const char*)p.x + i * 2048);
  }
  const uint32_t sb = smem_u32(smem);
  const uint32_t bars = sb + OFF_BAR;
  const int tid = threadIdx.x, lane = tid & 31, warp = __shfl_sync(0xffffffffu, tid >> 5, 0);
  const int rank = blockIdx.x & 1;
  const bool halo_cta = blockIdx.x < 4;
  if (halo_cta && MODE != 0) return;
  int grp, mem;
  {
    const int t = (blockIdx.x >> 1) - 4, u = t - 32;
    const int q7 = (u * 37) >> 8;
    const bool lo = (unsigned)t < 32u, mid = (unsigned)u < 28u;
    grp = lo ? (t & 7) : (mid ? 1 + u - 7 * q7 : 0);
    mem = lo ? (t >> 3) : (mid ? 4 + q7 : (t < 0 ? t + 6 : t - 54));
  }
  const int rg = (grp >> 2) * 4 + (mem >> 1), hp = (grp & 3) * 4 + (mem & 1) * 2 + rank;
  const int rb2 = (grp >> 2) * 8 + mem, cb2 = (grp & 3) * 2 + rank;
  const int chb = grp * 16 + mem * 2 + rank;
  const int cta = rg * 16 + hp;
  const int g2wg = 0, hsel = rb2 & 1;
  const int par = rg >> 2, gidx = rg & 3;

  if (tid < 256 && !halo_cta && MODE != 2) {
    const int r = tid >> 3, c = tid & 7;
    const uint32_t so = r * 128 + ((c ^ (r & 7)) << 4);
    const __nv_bfloat16* wg0 = p.w + (size_t)r * (3 * DM) + hp * 64 + c * 8;
    const __nv_bfloat16* xg0 = p.x + (size_t)(2 * (gidx * 256 + r) + par) * DM + c * 8;
#pragma unroll
    for (int j = 0; j < 3; j++) cp_async16n(sb + OFF_1B + j * 4096 + so, wg0 + j * DM);
#pragma unroll
    for (int i = 0; i < 8; i++) cp_async16n(sb + i * 4096 + so, xg0 + (size_t)i * 64 * DM);
    asm volatile("cp.async.commit_group;\n" ::: "memory");
  }
  auto halo_issue = [&](int kb, int s) {
    const uint32_t fb = bars + 8 * (BAR_FULLB + s), st = sb + s * STGH;
    mbar_expect_tx(fb, STGH - 2048);
    tma_load_3d(st + 8192, &tmWh, fb, 0, kb * 64, 16 + blockIdx.x * 4);
    tma_load_3d(st + 8192 + 32768, &tmWh, fb, 0, kb * 64, 32 + blockIdx.x * 4);
    tma_load_4d(st, &tmXh, fb, kb * 64, 248, 0, 0);
  };
  if (tid == 256) {
    prefetch_tmap(halo_cta ? &tmXh : &tmX);
#pragma unroll
    for (int i = 0; i < NS1B; i++) mbar_init(bars + 8 * (BAR_FULLB + i), 1);
#pragma unroll
    for (int i = 0; i < NS1A; i++) mbar_init(bars + 8 * (BAR_FULLA + i), 1);
    asm volatile("fence.mbarrier_init.release.cluster;\n" ::: "memory");
    if (!halo_cta && MODE != 2) {
      mbar_expect_tx(bars + 8 * (BAR_FULLB + 1), STG1B);
      tma_load_3d(sb + OFF_1B + 1 * STG1B, &tmW, bars + 8 * (BAR_FULLB + 1), hp * 64, 32, 0);
      mbar_expect_tx(bars + 8 * (BAR_FULLB + 2), STG1B);
      tma_load_3d(sb + OFF_1B + 2 * STG1B, &tmW, bars + 8 * (BAR_FULLB + 2), hp * 64, 64, 0);
    } else if (halo_cta) {
      halo_issue(0, 0);
    }
  } else if (tid == 288) {
#pragma unroll
    for (int i = 0; i < NS1A; i++) mbar_init(bars + 8 * (BAR_EMPTYA + i), 4);
#pragma unroll
    for (int i = 0; i < NS1B; i++) mbar_init(bars + 8 * (BAR_EMPTYB + i), 2);
    mbar_init(bars + 8 * BAR_X, 4);
    mbar_init(bars + 8 * BAR_LAND, 17);
    mbar_init(bars + 8 * BAR_U, 1);
    mbar_init(bars + 8 * BAR_Q, 1);
    mbar_init(bars + 8 * BAR_STG, 8);
    mbar_init(bars + 8 * BAR_HALO, 1);
    asm volatile("fence.mbarrier_init.release.cluster;\n" ::: "memory");
  } else if (tid == 320) {
#pragma unroll
    for (int i = 0; i < NS2; i++) {
      mbar_init(bars + 8 * (BAR_FULL2 + i), 1);
      mbar_init(bars + 8 * (BAR_EMPTY2 + i), 2);
    }
    asm volatile("fence.mbarrier_init.release.cluster;\n" ::: "memory");
  } else if (tid == 352) {
#pragma unroll
    for (int i = 0; i < 8; i++) mbar_init(bars + 8 * (BAR_Y + i), 4);
    asm volatile("fence.mbarrier_init.release.cluster;\n" ::: "memory");
  }
  if (warp == 8) PROF2(23);
  cluster_sync_all();
  if (warp == 8) PROF2(24);

  if (warp >= 8) {
    const int hw = warp - 8;
    const int lr = lane & 7, lm = lane >> 3;
    auto g1_issue_a = [&](int j, int s) {
      const uint32_t fb = bars + 8 * (BAR_FULLA + s);
      mbar_expect_tx(fb, STG1A);
      tma_load_3d_mc(sb + s * STG1A + rank * 16384, &tmX, fb, j * 64, par, gidx * 256 + rank * 128);
    };
    auto g1_issue_b = [&](int kb, int s) {
      const uint32_t fb = bars + 8 * (BAR_FULLB + s);
      mbar_expect_tx(fb, STG1B);
      tma_load_3d(sb + OFF_1B + s * STG1B, &tmW, fb, hp * 64, kb * 32, 0);
    };
    asm volatile("setmaxnreg.dec.sync.aligned.u32 %0;\n" :: "n"(REG_HELP));

    if (halo_cta) {
      if (hw == 0) {
        int s = 1, ph = 1;
#pragma unroll 1
        for (int kb = 1; kb < 16; kb++) {
          mbar_wait(bars + 8 * (BAR_EMPTYB + s), ph);
          if (elect_one()) halo_issue(kb, s);
          if (++s == 3) { s = 0; ph ^= 1; }
        }
      }
      __syncwarp();
    } else if (hw == 0) {
      auto g2_k = [&](int kb) { return kb < 2 ? hp ^ kb : kb < 4 ? (hp & 14) ^ kb : ((hp & 12) + kb) & 15; };
      auto g2_issue_b = [&](int kb, int s, uint32_t bytes) {
        mbar_expect_tx(bars + 8 * (BAR_FULL2 + s), bytes);
        tma_load_3d(sb + g2_b(s), &tmWo, bars + 8 * (BAR_FULL2 + s), 0, g2_k(kb) * 64, cb2 * 2);
      };
      uint32_t epoch = 0;
      if (MODE == 2) {
        if (lane < NS2) mbar_arrive_cluster_n(mapa(bars, rank) + 8 * (BAR_EMPTY2 + lane), 2);
      } else {
      if (lane == 0) {
        mbar_expect_tx(bars + 8 * BAR_U, 32768);
        mbar_expect_tx(bars + 8 * BAR_LAND, 16384);
        mbar_expect_tx(bars + 8 * BAR_Q, 32768);
      }
      {
        int sa = 1, pha = 1, sbb = 2, phb = 1;
#pragma unroll 1
        for (int kb = 2; kb < 32; kb++) {
          if (!(kb & 1)) {
            mbar_wait(bars + 8 * (BAR_EMPTYA + sa), pha);
            if (elect_one()) g1_issue_a(kb >> 1, sa);
            if (++sa == NS1A) { sa = 0; pha ^= 1; }
          }
          mbar_wait(bars + 8 * (BAR_EMPTYB + sbb), phb);
          if (kb > 2 && elect_one()) g1_issue_b(kb, sbb);
          __syncwarp();
          if (kb == 4) epoch = ld_relaxed(g_flag_o + cta);
          if (kb == 4) PROF2(27);
          if (kb == 1) PROF2(38);
          if (kb == 2) PROF2(39);
          if (++sbb == NS1B) { sbb = 0; phb ^= 1; }
        }
      }
      epoch++;
      if (lane == 0) {
        prefetch_tmap(&tmWo);
        prefetch_tmap(&tmQ);
        prefetch_tmap(&tmOa);
        prefetch_tmap(&tmOb);
        if (gidx != 0) wait_flag(g_flag_h + (hp >> 2), epoch);
      }
      __syncwarp();
      {
        uint4 hk0 = make_uint4(0, 0, 0, 0), hk1 = hk0, hv0 = hk0, hv1 = hk0;
        if (gidx != 0) {
          const uint4* src = g_halo + cta * 128 + lane;
          hk0 = __ldcg(src); hk1 = __ldcg(src + 32); hv0 = __ldcg(src + 64); hv1 = __ldcg(src + 96);
        }
        if (gidx != 0) PROF(18);
        sts128(sb + OFF_L0 + lane * 16, hk0.x, hk0.y, hk0.z, hk0.w);
        sts128(sb + OFF_L0 + 512 + lane * 16, hk1.x, hk1.y, hk1.z, hk1.w);
        sts64(sb + OFF_L0 + 1024 + lane * 8, movm(hv0.x), movm(hv0.y));
        sts64(sb + OFF_L0 + 1280 + lane * 8, movm(hv0.z), movm(hv0.w));
        sts64(sb + OFF_L0 + 1536 + lane * 8, movm(hv1.x), movm(hv1.y));
        sts64(sb + OFF_L0 + 1792 + lane * 8, movm(hv1.z), movm(hv1.w));
        __syncwarp();
        if (lane == 0) mbar_arrive(bars + 8 * BAR_HALO);
      }
      const uint32_t rb = mapa(bars, lane & 1);
      nb_sync(NB_OREADY, 288);
      if (lane == 0) {
        asm volatile("cp.async.bulk.global.shared::cta.bulk_group [%0], [%1], %2;\n" ::"l"(g_o + (size_t)cta * 16384),
                     "r"(sb + OFF_OP), "r"(32768) : "memory");
        bulk_commit();
      }
      if (lane < 2) {
#pragma unroll
        for (int i = 0; i < 3; i++) mbar_arrive_cluster(rb + 8 * (BAR_EMPTY2 + i));
      }
      if (lane == 0) {
        bulk_wait0();
        st_release(g_flag_o + cta, epoch);
      }
      __syncwarp();
      PROF2(17);
      if (lane < 2) mbar_arrive_cluster(rb + 8 * (BAR_EMPTY2 + 3));
      }
      if (MODE != 1) {
        const __nv_bfloat16* osrc = g_o + (size_t)(rb2 >> 1) * 16 * 16384 + hsel * 8192;
        mbar_wait(bars + 8 * (BAR_EMPTY2 + 1), 0);
        if (elect_one()) {
          if (MODE == 0) {
            asm volatile("cp.async.bulk.shared::cluster.shared::cta.mbarrier::complete_tx::bytes [%0], [%1], %2, [%3];\n"
                         ::"r"(mapa(sb + g2_a(1, hsel), rank ^ 1)), "r"(sb + g2_a(0, hsel)), "r"(16384),
                         "r"(mapa(bars + 8 * (BAR_FULL2 + 1), rank ^ 1)) : "memory");
          } else {
            bulk_load(sb + g2_a(0, hsel), osrc + hp * 16384, 16384, bars + 8 * BAR_FULL2);
            bulk_load(sb + g2_a(1, hsel), osrc + (hp ^ 1) * 16384, 16384, bars + 8 * (BAR_FULL2 + 1));
          }
          {
#pragma unroll 1
            for (int kb = 0; kb < NS2; kb++) g2_issue_b(kb, kb, kb || MODE ? STG2 : STG2 / 2);
          }
        }
        __syncwarp();
        uint32_t ready = MODE == 0 ? 0u : ~0u;
        int s = 2, ph = 0;
#pragma unroll 1
        for (int kb = 2; kb < 16; kb++) {
          const int k = g2_k(kb);
          if (!(ready >> k & 1)) {
            for (int n = 0; n < SPIN_LIMIT && !(ready >> k & 1); n++)
              ready = __ballot_sync(0xffffffffu, ld_acquire(g_flag_o + (rb2 >> 1) * 16 + (lane & 15)) == epoch);
            fence_async_all();
          }
          if (kb == 2) PROF(21);
          mbar_wait(bars + 8 * (BAR_EMPTY2 + s), ph);
          if (elect_one()) {
            asm volatile(
                "cp.async.bulk.shared::cluster.global.mbarrier::complete_tx::bytes.multicast::cluster [%0], [%1], %2, [%3], %4;\n"
                ::"r"(sb + g2_a(s, hsel) + rank * 8192), "l"(osrc + k * 16384 + rank * 4096), "r"(8192),
                "r"(bars + 8 * (BAR_FULL2 + s)), "h"((uint16_t)3) : "memory");
            if (kb >= NS2) g2_issue_b(kb, s, STG2);
          }
          __syncwarp();
          if (++s == NS2) { s = 0; ph ^= 1; }
        }
      }
      __syncwarp();
    } else if (MODE != 2) {
      {
        const int g = lane >> 2, t = lane & 3;
        uint32_t w[2][4];
#pragma unroll
        for (int h = 0; h < 2; h++) {
          const uint2 x = __ldg(reinterpret_cast<const uint2*>(p.shift_k + ((chb & ~1) * 8 + h * 8 + g) * 4));
          w[h][0] = __byte_perm(x.x, x.x, 0x1010);
          w[h][1] = __byte_perm(x.x, x.x, 0x3232);
          w[h][2] = __byte_perm(x.y, x.y, 0x1010);
          w[h][3] = __byte_perm(x.y, x.y, 0x3232);
        }
        auto swz = [](int r) { return (((r & 29) | ((r ^ (r >> 2)) & 2)) << 5) | (r & 16); };
        const uint32_t kring = sb + OFF_X + 4096 + (hw - 1) * 2 * XT, vring = kring + XT;
        const int s0 = rank * 32 + (hw - 1) * 11, s1 = hw == 3 ? rank * 32 + 32 : s0 + 11;
        const size_t goff = (size_t)(lane >> 1) * DM + (chb & ~1) * 8 + (lane & 1) * 8;
        const __nv_bfloat16* kg = p.k + goff;
        const __nv_bfloat16* vg = p.v + goff;
        const uint32_t d0 = swz(lane >> 1) ^ ((lane & 1) << 4), d1 = swz(16 + (lane >> 1)) ^ ((lane & 1) << 4);
        auto issue = [&](int st) {
          const uint32_t so = (st & 3) << 10;
          cp_async16(kring + so + d0, kg + (size_t)st * 32 * DM, 16);
          cp_async16(kring + so + d1, kg + (size_t)(st * 32 + 16) * DM, 16);
          cp_async16(vring + so + d0, vg + (size_t)st * 32 * DM, 16);
          cp_async16(vring + so + d1, vg + (size_t)(st * 32 + 16) * DM, 16);
        };
        const int xa = 8 * (lr >> 1) + 2 * lm + (lr & 1), xb = 8 * (lr >> 1) - 4 + 2 * (lm & 1) + (lr & 1);
        const uint32_t la = swz(xa), lb = swz(xb & 31);
        const int backb = xb < 0 ? 1 : 0;
        const uint32_t ud[2] = {mapa(sb + OFF_X + g * XT + t * 16, 0), mapa(sb + OFF_X + g * XT + t * 16, 1)};
        const uint32_t ub[2] = {mapa(bars + 8 * BAR_U, 0), mapa(bars + 8 * BAR_U, 1)};
        if (lane == 0) mbar_wait(bars + 8 * (BAR_FULLB + NS1B - 1), 0);
        __syncwarp();
        if (lane >= 24) cp_async16(kring + (((s0 - 1) & 3) << 10) + d1, s0 > 0 ? kg + (size_t)(s0 * 32 - 16) * DM : kg, s0 > 0 ? 16 : 0);
        issue(s0);
        asm volatile("cp.async.commit_group;\n" ::: "memory");
        issue(s0 + 1);
        asm volatile("cp.async.commit_group;\n" ::: "memory");
#pragma unroll 1
        for (int st = s0; st < s1; st++) {
          if (st + 2 < s1) issue(st + 2);
          if (hw == 1 && st - s0 < 8) prefetch_l2(p.ssm_k + (size_t)(chb * 8 + st - s0) * SEQ + lane * 64);
          asm volatile("cp.async.commit_group;\n" ::: "memory");
          asm volatile("cp.async.wait_group 2;\n" ::: "memory");
          __syncwarp();
#pragma unroll
          for (int h = 0; h < 2; h++) {
            uint32_t e[6], vv[4], e4[4];
            ldsm4t(e4, kring + ((st & 3) << 10) + (la ^ (h << 4)));
            ldsm2t(e[0], e[1], kring + (((st - backb) & 3) << 10) + (lb ^ (h << 4)));
            ldsm4t(vv, vring + ((st & 3) << 10) + (la ^ (h << 4)));
            e[2] = e4[0]; e[3] = e4[1]; e[4] = e4[2]; e[5] = e4[3];
            uint32_t o[5];
#pragma unroll
            for (int i = 0; i < 5; i++) o[i] = __byte_perm(e[i], e[i + 1], 0x5432);
#pragma unroll
            for (int i = 0; i < 4; i++) {
              uint32_t a = bmul2(o[i], w[h][3]);
              a = bfma2(e[i + 1], w[h][2], a);
              a = bfma2(o[i + 1], w[h][1], a);
              a = bfma2(e[i + 2], w[h][0], a);
              vv[i] = bmul2(a, vv[i]);
            }
            st_async128(ud[h] + (st ^ (g & 1)) * 64, ub[h], vv[0], vv[1], vv[2], vv[3]);
          }
          __syncwarp();
        }
        PROF(16);
      }
      nb_sync(NB_HELP3, 96);
      {
        const int ck = 16 * (lane >> 4) + 2 * lr + (((lane >> 3) ^ (lane >> 2)) & 1);
        const uint32_t xo = (ck >> 1) * 128, xs = ((ck & 1) ^ lr) << 4;
#pragma unroll 1
        for (int job = hw - 1; job < 16; job += 3) {
          const int c = job & 7;
          uint4 a[8];
          float dv = 0.f;
          if (job < 8) {
            const uint4* src = reinterpret_cast<const uint4*>(p.ssm_k + (size_t)(chb * 8 + c) * SEQ) + ck;
#pragma unroll
            for (int i = 0; i < 8; i++) a[i] = __ldcg(src + 32 * i);
            if (lane == 0) dv = __bfloat162float(p.ssm_D[chb * 8 + c]);
            prefetch_l2(p.q + (size_t)chb * 16384 + c * 2048 + lane * 64);
            if (lane < 16) prefetch_l2(p.wo + (size_t)chb * 8192 + c * 1024 + lane * 64);
          } else {
            mbar_wait(bars + 8 * BAR_U, 0);
#pragma unroll
            for (int i = 0; i < 8; i++) a[i] = lds128(sb + OFF_X + c * XT + i * 512 + ((ck ^ ((c & 1) << 2)) << 4));
          }
          uint32_t m = pack_bf16(bf_lo(a[0].x) + dv, 0.f);
#pragma unroll
          for (int i = 0; i < 8; i++) m = bmaxabs2(bmaxabs2(m, bmaxabs2(a[i].x, a[i].y)), bmaxabs2(a[i].z, a[i].w));
          m = __reduce_max_sync(0xffffffffu, max(m & 0x7fffu, (m >> 16) & 0x7fffu));
          const uint32_t f = max(252 - (int)(m >> 7), 1), mul = f * 0x00800080u;
          if (lane == 0) asm volatile("st.shared.u32 [%0], %1;\n" ::"r"(sb + OFF_EX + job * 4), "r"(f) : "memory");
          auto cv = [&](uint32_t x) {
            x = bmul2(x, mul);
            return pack_f16(bf_lo(x), bf_hi(x));
          };
          const uint32_t x0 = bmul2(a[0].x, mul);
          const uint32_t dst = sb + OFF_X + c * XT + (job < 8 ? 4096 : 0) + xo;
#pragma unroll
          for (int i = 0; i < 8; i++)
            sts128(dst + (i & 1) * 2048 + (xs ^ ((i >> 1) << 5)),
                   i ? cv(a[i].x) : pack_f16(fmaf(dv, __uint_as_float(f << 23), bf_lo(x0)), bf_hi(x0)), cv(a[i].y), cv(a[i].z),
                   cv(a[i].w));
        }
        fence_async_smem();
        __syncwarp();
        if (lane == 0) mbar_arrive(bars + 8 * BAR_X);
        PROF(19);
      }
      if (hw == 3) {
        nb_sync(NB_G1DONE, 288);
        if (elect_one()) {
          mbar_expect_tx(bars + 8 * BAR_X, 8192);
          bulk_load(sb + OFF_TAB, g_tab, 8192, bars + 8 * BAR_X);
        }
      } else {
        const uint32_t peer = mapa(sb, rank ^ 1);
#pragma unroll 1
        for (int ch = hw * 4 - 4; ch < hw * 4; ch++) {
          const uint32_t o = OFF_X + ch * XT + (rank ^ 1) * 4096;
          uint4 a[4];
          mbar_wait(bars + 8 * (BAR_Y + ch), 0);
#pragma unroll
          for (int i = 0; i < 4; i++) a[i] = lds128(sb + o + (i >> 1) * 2048 + (i & 1) * 512 + lane * 16);
#pragma unroll
          for (int i = 0; i < 4; i++)
            st_async128(peer + o + 1024 + (i >> 1) * 2048 + (i & 1) * 512 + lane * 16, peer + OFF_BAR + 8 * BAR_LAND, a[i].x,
                        a[i].y, a[i].z, a[i].w);
          fence_async_smem();
          __syncwarp();
          if (elect_one()) tma_load_2d(sb + o, &tmQ, bars + 8 * BAR_Q, (chb & ~1) * 8, rank * 1024 + ch * 128);
        }
      }
      nb_sync(NB_HELP3, 96);
      PROF(32);
      {
        const int c8 = (4 * (lr >> 1) + 2 * (lm & 1) + (lr & 1)) & 7;
        const uint32_t ya = sb + OFF_X + c8 * XT + rank * 4096 + ((lr >> 2) == rank ? 0 : 1024);
        const uint32_t yx = ((lm >> 1) ^ c8 ^ ((lr >> 2) << 1)) << 4;
        const uint32_t qa = sb + OFF_X + (rank ^ 1) * 4096;
        mbar_wait(bars + 8 * BAR_LAND, 0);
        if (hw == 3 && lane < 2) mbar_arrive_cluster(mapa(bars, lane) + 8 * (BAR_EMPTY2 + 4));
        mbar_wait(bars + 8 * BAR_Q, 0);
        PROF2(33);
#pragma unroll 1
        for (int j = hw - 1; j < 16; j += 3) {
          uint32_t y[4][4];
          uint2 q[8];
          const uint32_t qj = qa + (j >> 1) * XT + (j & 1) * 2048;
#pragma unroll
          for (int i = 0; i < 4; i++) ldsm4t(y[i], ya + (j >> 3) * 2048 + (j & 7) * 128 + (yx ^ ((j & 1) << 4) ^ (i << 5)));
#pragma unroll
          for (int i = 0; i < 8; i++) q[i] = lds64(qj + i * 256 + lane * 8);
#pragma unroll
          for (int i = 0; i < 8; i++) {
            const uint2 o = make_uint2(bmul2(q[i].x, y[i >> 1][2 * (i & 1)]), bmul2(q[i].y, y[i >> 1][2 * (i & 1) + 1]));
            sts64(qj + i * 256 + lane * 8, o.x, o.y);
          }
          fence_async_smem();
          __syncwarp();
          if (elect_one()) {
            tma_store_2d(&tmOa, qj, (chb & ~1) * 8, rank * 1024 + j * 64);
            bulk_commit();
          }
        }
        bulk_wait0();
      }
      PROF(22);
    }
    cluster_sync_all();
  } else {
    asm volatile("setmaxnreg.inc.sync.aligned.u32 %0;\n" :: "n"(REG_MATH));
    if (warp == 0) PROF2(26);
    const int wg = warp >> 2;
    const int wtid = tid & 127;
    const bool signaller = (wtid == 0) || (wtid == 32);
    const uint32_t rbars = mapa(bars, wtid >> 5 & 1);

    if (halo_cta) {
      const uint32_t epoch = ld_relaxed(g_flag_h + blockIdx.x) + 1;
      float acc0[64], acc1[64];
      int s = 0, ph = 0;
#pragma unroll 1
      for (int kb = 0; kb < 16; kb++) {
        mbar_wait(bars + 8 * (BAR_FULLB + s), ph);
        const uint32_t st = sb + s * STGH;
        const uint64_t da = mkdesc(st, 16, 1024, 1);
        const uint64_t db = mkdesc(st + 8192 + wg * 32768, 8192, 1024, 1);
        wg_fence();
#pragma unroll
        for (int kk = 0; kk < 4; kk++) {
          wgmma_n128(acc0, da + 2 * kk, db + 128 * kk, kb + kk);
          wgmma_n128(acc1, da + 2 * kk, db + 1024 + 128 * kk, kb + kk);
        }
        wg_commit();
        wg_wait<0>();
        if (kb == 15) PROF(37);
        if (wtid == 0) mbar_arrive(bars + 8 * (BAR_EMPTYB + s));
        if (++s == 3) { s = 0; ph ^= 1; }
      }
      fence_regs(acc0);
      fence_regs(acc1);
      if ((warp & 3) != 3) {
#pragma unroll
        for (int hh = 0; hh < 2; hh++) {
          uint4* dst = g_halo + ((hh * 4 + (warp & 3) + 1) * 16 + blockIdx.x * 4) * 128 + wg * 64 + lane;
#pragma unroll
          for (int j = 0; j < 4; j++) {
            const int o = 16 * j + 2 * hh;
            dst[(j >> 1) * 128 + (j & 1) * 32] =
                make_uint4(pack_bf16(acc0[o], acc0[o + 1]), pack_bf16(acc0[o + 4], acc0[o + 5]),
                           pack_bf16(acc0[o + 8], acc0[o + 9]), pack_bf16(acc0[o + 12], acc0[o + 13]));
            dst[(2 + (j >> 1)) * 128 + (j & 1) * 32] =
                make_uint4(pack_bf16(acc1[o], acc1[o + 1]), pack_bf16(acc1[o + 4], acc1[o + 5]),
                           pack_bf16(acc1[o + 8], acc1[o + 9]), pack_bf16(acc1[o + 12], acc1[o + 13]));
          }
        }
      }
      nb_sync(NB_G1DONE, 256);
      if (tid == 0) st_release(g_flag_h + blockIdx.x, epoch);
      PROF(36);
      cluster_sync_all();
      return;
    }

    if (MODE != 2) {
    {
      float acc0[96], acc1[96];
      int sa = 0, pha = 0, sbb = 0, phb = 0;
      asm volatile("cp.async.wait_group 0;\n" ::: "memory");
      fence_async_smem();
      nb_sync(NB_FIRST, 256);
      if (tid == 0) {
        mbar_arrive(bars + 8 * BAR_FULLA);
        mbar_arrive(bars + 8 * BAR_FULLB);
      }
      PROF(0 + wg);
#pragma unroll 1
      for (int kb = 0; kb < 30; kb++) {
        if (!(kb & 1)) mbar_wait(bars + 8 * (BAR_FULLA + sa), pha);
        mbar_wait(bars + 8 * (BAR_FULLB + sbb), phb);
        if (kb == 0) PROF2(0 + wg);
        if (kb == 4 && wg == 0) PROF2(28);
        if (kb == 8 && wg == 0) PROF2(29);
        if (kb == 16 && wg == 0) PROF2(30);
        const uint64_t da = mkdesc(sb + sa * STG1A + wg * 16384 + (kb & 1) * 64, 16, 2048, 1);
        const uint64_t db = mkdesc(sb + OFF_1B + sbb * STG1B, 4096, 1024, 1);
        wg_fence();
        wgmma_n192(acc0, da + 64, db, kb);
        wgmma_n192(acc1, da, db, kb);
        wgmma_n192(acc0, da + 66, db + 128, 1);
        wgmma_n192(acc1, da + 2, db + 128, 1);
        wg_commit();
        wg_wait<1>();
        if (kb > 0) {
          if (wtid == 64) mbar_arrive(bars + 8 * (BAR_EMPTYB + (sbb == 0 ? NS1B - 1 : sbb - 1)));
          if (!(kb & 1) && signaller) mbar_arrive_cluster(rbars + 8 * (BAR_EMPTYA + (sa == 0 ? NS1A - 1 : sa - 1)));
        }
        if (++sbb == NS1B) { sbb = 0; phb ^= 1; }
        if ((kb & 1) && ++sa == NS1A) { sa = 0; pha ^= 1; }
      }
      const int lr = lane & 7, lm = lane >> 3;
      const bool le0 = 2 * (lane & 3) <= (lane >> 2), le1 = 2 * (lane & 3) + 1 <= (lane >> 2);
      const uint32_t maskLE = (le0 ? 0x0000FFFFu : 0u) | (le1 ? 0xFFFF0000u : 0u);
      uint32_t q[4][8], k[5][8], vt[5][8];
      {
        static_assert(15 % NS1A == 0 && 30 % NS1B == 0, "slots of the last k blocks");
        mbar_wait(bars + 8 * BAR_FULLA, 1);
        mbar_wait(bars + 8 * BAR_FULLB, 0);
        mbar_wait(bars + 8 * (BAR_FULLB + 1), 0);
        const uint64_t da = mkdesc(sb + wg * 16384, 16, 2048, 1);
        const uint64_t db = mkdesc(sb + OFF_1B, 4096, 1024, 1);
        wg_fence();
#pragma unroll
        for (int i = 0; i < 4; i++) wgmma_n192(acc0, da + 64 + 2 * i, db + (i >> 1) * (STG1B >> 4) + (i & 1) * 128, 1);
        wg_commit();
        wg_wait<1>();
        nb_arrive(NB_G1DONE, 288);
#pragma unroll
        for (int i = 0; i < 2; i++) wgmma_n192(acc1, da + 2 * i, db + (i >> 1) * (STG1B >> 4) + (i & 1) * 128, 1);
        wg_commit();
        wg_wait<1>();
        fence_regs(acc0);
        PROFA(45, 0);
        attn_pack<8, 1, false>(acc0, k[4]);
        attn_pack<16, 1, true>(acc0, vt[4]);
        const uint32_t kh = sb + OFF_KH + warp * 4096 + lane * 16;
        sts128(kh, k[4][0], k[4][1], k[4][2], k[4][3]);
        sts128(kh + 512, k[4][4], k[4][5], k[4][6], k[4][7]);
#pragma unroll
        for (int i = 0; i < 4; i++) sts64(kh - lane * 8 + 1024 + 256 * i, vt[4][2 * i], vt[4][2 * i + 1]);
#pragma unroll
        for (int i = 2; i < 4; i++) wgmma_n192(acc1, da + 2 * i, db + (i >> 1) * (STG1B >> 4) + (i & 1) * 128, 1);
        wg_commit();
        attn_pack<0, 0, false>(acc0, q[1]);
        attn_pack<0, 1, false>(acc0, q[3]);
        attn_pack<8, 0, false>(acc0, k[2]);
        attn_pack<16, 0, true>(acc0, vt[2]);
        uint32_t z = p.zero;
#pragma unroll
        for (int i = 0; i < 8; i++) z &= q[1][i] & q[3][i];
#pragma unroll
        for (int i = 0; i < 8; i += 2) z &= k[2][i] & k[2][i + 1];
        __syncwarp();
        if (lane == 0) mbar_arrive(bars + 8 * BAR_STG + z);
        wg_wait<0>();
        fence_regs(acc1);
      }
      PROF(2 + wg);
      mbar_wait(bars + 8 * (warp == 0 ? BAR_HALO : BAR_STG), 0);
      {
        const uint32_t kh = sb + (warp == 0 ? OFF_L0 : OFF_KH + (warp - 1) * 4096) + lane * 16;
#pragma unroll
        for (int i = 0; i < 2; i++) {
          const uint4 t = lds128(kh + 512 * i);
          k[0][4 * i] = t.x; k[0][4 * i + 1] = t.y; k[0][4 * i + 2] = t.z; k[0][4 * i + 3] = t.w;
        }
#pragma unroll
        for (int i = 0; i < 4; i++) {
          const uint2 t = lds64(kh - lane * 8 + 1024 + 256 * i);
          vt[0][2 * i] = t.x; vt[0][2 * i + 1] = t.y;
        }
      }
      attn_pack<0, 0, false>(acc1, q[0]);
      attn_pack<0, 1, false>(acc1, q[2]);
      attn_pack<8, 0, false>(acc1, k[1]);
      attn_pack<8, 1, false>(acc1, k[3]);
      {
        float x[8][2];
        uint32_t pp[8];
        const bool first = warp == 0 && gidx == 0;
#pragma unroll
        for (int hd = 0; hd < 2; hd++) {
#pragma unroll
          for (int j = 0; j < 4; j += 2) {
            float s0[4], s1[4], s2[4];
            attn_qk(s2, q[j], q[j + 1], k[j + 2], 4 * hd);
            attn_qk(s1, q[j], q[j + 1], k[j + 1], 4 * hd);
            attn_qk(s0, q[j], q[j + 1], k[j], 4 * hd);
            if (j == 0 && first) s0[0] = s0[1] = -1e9f / 0.17677669529663687f;
            x[2 * j + hd][0] = le0 ? s1[0] : s0[0];
            x[2 * j + hd][1] = le1 ? s1[1] : s0[1];
            x[2 * j + 2 + hd][0] = le0 ? s2[2] : s1[2];
            x[2 * j + 2 + hd][1] = le1 ? s2[3] : s1[3];
          }
        }
        PROFA(40, __float_as_uint(x[1][0] + x[7][1]));
        attn_pack<16, 0, true>(acc1, vt[1]);
        attn_pack<16, 1, true>(acc1, vt[3]);
        quad_softmax<8>(x, pp);
        PROFA(41, pp[1] + pp[7]);
        const uint32_t obase = sb + OFF_OP + (warp * 32 + lr) * 128;
#pragma unroll
        for (int n = 0; n < 8; n++) {
          attn_pv(obase + (n >> 1) * 1024 + (((4 * (n & 1) + lm) ^ lr) << 4), vt[n >> 1], vt[(n >> 1) + 1], 4 * (n & 1), pp[n],
                  maskLE);
        }
      }
      PROFA(42, 0);
    }

    {
      fence_async_smem();
      nb_arrive(NB_OREADY, 288);
      const int w = warp & 3;
      const int lr = lane & 7, lm = lane >> 3;
      mbar_wait(bars + 8 * BAR_X, 0);
      PROF(34 + wg);
      uint32_t a1[2][4], sc[4];
      ldsm4(a1[0], sb + OFF_TAB + 2048 + w * 1024 + lane * 16);
      ldsm4(a1[1], sb + OFF_TAB + 2560 + w * 1024 + lane * 16);
      C2 t[2];
      {
        const uint4 x = lds128(sb + OFF_TAB + 6144 + wtid * 16);
        t[0] = C2{x.x, x.z};
        t[1] = C2{x.y, x.w};
        const uint4 fh = lds128(sb + OFF_EX + wg * 16), fu = lds128(sb + OFF_EX + 32 + wg * 16);
        auto pw2 = [](uint32_t a, uint32_t b) { return min(max(381 - (int)a - (int)b, 1), 254) * 0x00800080u; };
        sc[0] = pw2(fh.x, fu.x); sc[1] = pw2(fh.y, fu.y); sc[2] = pw2(fh.z, fu.z); sc[3] = pw2(fh.w, fu.w);
      }
      const uint32_t xb = sb + OFF_X + wg * 4 * XT;
      const uint64_t dc2 = mkdesc(sb + OFF_TAB, 128, 256, 0), dc4 = mkdesc(sb + OFF_TAB + 2048, 128, 256, 0);
      const uint64_t dx = mkdesc(xb, 4096, 1024, 1), dz = mkdesc(xb, 2048, 256, 3);
      const uint32_t zs = xb + (w * 16 + (lm & 1) * 8 + lr) * 32 + (((lm >> 1) ^ (lr >> 2)) << 4);
      const uint32_t ys = xb + w * 2048 + (lm >> 1) * 256;
      const uint32_t yx = (lr * 32 + (((lm & 1) ^ (lr >> 2)) << 4)) ^ (wg << 6) ^ (rank << 5);
      const bool own = (w >> 1) == rank;
      const uint32_t ybar = mapa(bars, own ? rank ^ 1 : rank) + 8 * (BAR_Y + wg * 4);
      uint32_t d[2][32], pa[2][4][2][4], e[2][4][8], ya[2][2][2][4], v[2][2][8];
      float o[2][16];
      auto rows = [&](int c) {
        fft_rows(d[c & 1], a1, dx + (XT >> 4) * c);
        wg_commit();
      };
      auto cols = [&](int c) {
        const int s = c & 1;
        fence_regs(d[s]);
#pragma unroll
        for (int i = 0; i < 16; i++) {
          const C2 z = cmul(C2{d[s][2 * i], d[s][2 * i + 1]}, t[i & 1]);
          pa[s][i >> 2][i & 1][(i >> 1) & 1] = z.r;
          pa[s][i >> 2][i & 1][2 + ((i >> 1) & 1)] = z.i;
        }
        wg_fence();
#pragma unroll
        for (int i = 0; i < 4; i++) fft_cols(e[s][i], pa[s][i], dc2);
        wg_commit();
      };
      auto prod = [&](int c) {
        const int s = c & 1;
#pragma unroll
        for (int i = 0; i < 4; i++) fence_regs(e[s][i]);
#pragma unroll
        for (int j = 0; j < 2; j++) {
          const C2 u0 = cget(e[s][0], j, 0), u1 = cget(e[s][0], j, 1), u2 = cget(e[s][1], j, 0), u3 = cget(e[s][1], j, 1);
          const C2 h0 = cget(e[s][2], j, 0), h1 = cget(e[s][2], j, 1), h2 = cget(e[s][3], j, 0), h3 = cget(e[s][3], j, 1);
          const C2 s0 = cmul(h0, u0), s1 = cfma(h0, u1, cmul(h1, u0)), s2 = cfma(h0, u2, cfma(h2, u0, cmul(h1, u1)));
          const C2 y3 = cfma(h0, u3, cfma(h1, u2, cfma(h2, u1, cfma(h3, u0, C2{s2.i, hneg2(s2.r)}))));
          ya[s][0][j][0] = s0.i;
          ya[s][0][j][1] = hadd2(s1.i, hneg2(s0.r));
          ya[s][0][j][2] = s0.r;
          ya[s][0][j][3] = hadd2(s1.r, s0.i);
          ya[s][1][j][0] = hadd2(s2.i, hneg2(s1.r));
          ya[s][1][j][1] = y3.i;
          ya[s][1][j][2] = hadd2(s2.r, s1.i);
          ya[s][1][j][3] = y3.r;
        }
        wg_fence();
        fft_cols(v[s][0], ya[s][0], dc2);
        fft_cols(v[s][1], ya[s][1], dc2);
        wg_commit();
      };
      auto stage = [&](int c) {
        const int s = c & 1;
        fence_regs(v[s][0]);
        fence_regs(v[s][1]);
#pragma unroll
        for (int b = 0; b < 4; b++) {
          const C2 z0 = cmul(cget(v[s][b >> 1], 0, b & 1), t[0]), z1 = cmul(cget(v[s][b >> 1], 1, b & 1), t[1]);
          stsm4(zs + c * XT + b * 2048, z0.i, z0.r, z1.i, z1.r);
        }
      };
      auto back = [&](int c) {
        fft_back(o[c & 1], dz + (XT >> 4) * c, dc4);
        wg_commit();
      };
      auto out = [&](int c) {
        float (&r)[16] = o[c & 1];
        fence_regs(r);
#pragma unroll
        for (int i = 0; i < 16; i += 8)
          stsm4t(ys + c * XT + (yx ^ (c << 4)) + 64 * i, bmul2(pack_bf16(r[i], r[i + 1]), sc[c]),
                 bmul2(pack_bf16(r[i + 2], r[i + 3]), sc[c]), bmul2(pack_bf16(r[i + 4], r[i + 5]), sc[c]),
                 bmul2(pack_bf16(r[i + 6], r[i + 7]), sc[c]));
        __syncwarp();
        if (lane == 0) {
          mbar_arrive_cluster(ybar + 8 * c);
          if (own) mbar_arrive(bars + 8 * BAR_LAND);
        }
      };
      wg_fence();
      rows(0);
      rows(1);
      wg_wait<1>();
      cols(0);
      wg_wait<1>();
      cols(1);
      nb_sync(NB_CONV + wg, 128);
      wg_wait<1>();
      prod(0);
      rows(2);
      wg_wait<2>();
      prod(1);
      rows(3);
      wg_wait<3>();
      stage(0);
      wg_wait<1>();
      stage(1);
      fence_async_smem();
      cols(2);
      wg_wait<1>();
      nb_sync(NB_CONV + wg, 128);
      wg_fence();
      back(0);
      back(1);
      cols(3);
      wg_wait<3>();
      prod(2);
      wg_wait<2>();
      out(0);
      out(1);
      wg_wait<1>();
      prod(3);
      wg_wait<1>();
      stage(2);
      wg_wait<0>();
      stage(3);
      fence_async_smem();
      nb_sync(NB_CONV + wg, 128);
      wg_fence();
      back(2);
      back(3);
      wg_wait<1>();
      out(2);
      wg_wait<0>();
      out(3);
      PROF(6 + wg);
    }
    }

    if (MODE != 1 && wg == g2wg) {
      float acc0[64], acc1[64];
      int s = 0, ph = 0, sprev = 0;
#pragma unroll 1
      for (int kb = 0; kb < 16 - ENDG; kb++) {
        mbar_wait(bars + 8 * (BAR_FULL2 + s), ph);
        if (kb == 0) PROF(8);
        if ((warp & 3) == 0) PROF2(40 + kb);
        const uint64_t da = mkdesc(sb + g2_a(s, hsel), 16, 1024, 1);
        const uint64_t db = mkdesc(sb + g2_b(s), 8192, 1024, 1);
        wg_fence();
        wgmma_n128(acc0, da, db, kb);
        wgmma_n128(acc1, da + 512, db, kb);
        wgmma_n128(acc0, da + 2, db + 128, 1);
        wgmma_n128(acc1, da + 514, db + 128, 1);
        wg_commit();
        wg_wait<1>();
        if (kb > 0 && kb + NS2 <= 16 && signaller) mbar_arrive_cluster(rbars + 8 * (BAR_EMPTY2 + sprev));
        wgmma_n128(acc0, da + 4, db + 256, 1);
        wgmma_n128(acc1, da + 516, db + 256, 1);
        wgmma_n128(acc0, da + 6, db + 384, 1);
        wgmma_n128(acc1, da + 518, db + 384, 1);
        wg_commit();
        wg_wait<1>();
        sprev = s;
        if (++s == NS2) { s = 0; ph ^= 1; }
      }
#pragma unroll
      for (int kb = 16 - ENDG; kb < 16; kb++) {
        mbar_wait(bars + 8 * (BAR_FULL2 + kb % NS2), (kb / NS2) & 1);
        if ((warp & 3) == 0) PROF2(40 + kb);
        const uint64_t da = mkdesc(sb + g2_a(kb % NS2, hsel), 16, 1024, 1);
        const uint64_t db = mkdesc(sb + g2_b(kb % NS2), 8192, 1024, 1);
        wg_fence();
#pragma unroll
        for (int i = 0; i < 4; i++) wgmma_n128(acc0, da + 2 * i, db + 128 * i, 1);
        wg_commit();
        if (kb == 16 - ENDG && kb + NS2 <= 16) {
          wg_wait<1>();
          if (signaller) mbar_arrive_cluster(rbars + 8 * (BAR_EMPTY2 + sprev));
        }
      }
      static_assert(ENDG <= NS2, "the last stages stay resident");
      auto second = [&](int i0, int i1) {
#pragma unroll
        for (int i = i0; i < i1; i++) {
          const int st = (16 - ENDG + (i >> 2)) % NS2;
          wgmma_n128(acc1, mkdesc(sb + g2_a(st, hsel) + 8192, 16, 1024, 1) + 2 * (i & 3),
                     mkdesc(sb + g2_b(st), 8192, 1024, 1) + 128 * (i & 3), 1);
        }
        wg_commit();
      };
      second(0, 4);
      const int lr = lane & 7, lm = lane >> 3;
      const uint32_t wb[2] = {sb + g2_a(1, 0) + (warp & 3) * 2048, sb + g2_a(2, 0) + (warp & 3) * 2048};
      const int orow = (rb2 & 7) * 128 + (warp & 3) * 16;
      auto stage_out = [&](const float (&acc)[64], uint32_t off, int j0, int j1) {
#pragma unroll
        for (int j = j0; j < j1; j += 2) {
          const uint32_t a = wb[j >> 3] + off + (lr + 8 * (lm & 1)) * 128 + ((((j & 7) + (lm >> 1)) ^ lr) << 4);
          stsm4(a, pack_bf16(acc[4 * j], acc[4 * j + 1]), pack_bf16(acc[4 * j + 2], acc[4 * j + 3]),
                pack_bf16(acc[4 * j + 4], acc[4 * j + 5]), pack_bf16(acc[4 * j + 6], acc[4 * j + 7]));
        }
      };
      auto store_tma = [&](uint32_t off, int row) {
        fence_async_smem();
        __syncwarp();
        if (elect_one()) {
          tma_store_3d(&tmOb, wb[0] + off, DM + cb2 * 128, rb2 >> 3, row);
          tma_store_3d(&tmOb, wb[1] + off, DM + cb2 * 128 + 64, rb2 >> 3, row);
          bulk_commit();
        }
      };
      wg_wait<1>();
      fence_regs(acc0);
      PROF(10);
#pragma unroll
      for (int c = 0; c < 4; c++) {
        stage_out(acc0, 0, 4 * c, 4 * c + 4);
        second(4 + ILV * c, 4 + ILV * (c + 1));
      }
      store_tma(0, orow);
      if (4 + 4 * ILV < 4 * ENDG) second(4 + 4 * ILV, 4 * ENDG);
      PROF(12);
      wg_wait<0>();
      fence_regs(acc1);
      PROF(11);
      stage_out(acc1, 8192, 0, 16);
      __syncwarp();
      {
        const int rr = lane >> 4, ck = lane & 7, hf = (lane >> 3) & 1;
        uint4* og = reinterpret_cast<uint4*>(p.out + (size_t)(2 * (orow + 64 + rr) + (rb2 >> 3)) * (2 * DM) + DM + cb2 * 128 + hf * 64 + ck * 8);
        uint4 v[8];
#pragma unroll
        for (int i = 0; i < 8; i++) v[i] = lds128((hf ? wb[1] : wb[0]) + 8192 + (2 * i + rr) * 128 + ((ck ^ ((2 * i + rr) & 7)) << 4));
#pragma unroll
        for (int i = 0; i < 8; i++) og[(size_t)i * 4 * (2 * DM / 8)] = v[i];
      }
      PROF(13);
      bulk_wait0();
    }
    cluster_sync_all();
  }
}

typedef CUresult (*EncodeFn)(CUtensorMap*, CUtensorMapDataType, cuuint32_t, void*, const cuuint64_t*, const cuuint64_t*,
                             const cuuint32_t*, const cuuint32_t*, CUtensorMapInterleave, CUtensorMapSwizzle,
                             CUtensorMapL2promotion, CUtensorMapFloatOOBfill);

void make_map(EncodeFn enc, CUtensorMap* tm, const void* base, int rank, const cuuint64_t* dims, const cuuint64_t* strides,
              const cuuint32_t* box, CUtensorMapSwizzle swz) {
  cuuint32_t es[4] = {1, 1, 1, 1};
  enc(tm, CU_TENSOR_MAP_DATA_TYPE_BFLOAT16, rank, const_cast<void*>(base), dims, strides, box, es,
      CU_TENSOR_MAP_INTERLEAVE_NONE, swz, CU_TENSOR_MAP_L2_PROMOTION_L2_256B, CU_TENSOR_MAP_FLOAT_OOB_FILL_NONE);
}

}

extern "C" void kernel_launch(void* const* d_in, const int* in_sizes, int n_in, void* d_out, int out_size) {
  static EncodeFn enc = nullptr;
  static bool coresident = true;
  if (!enc) {
    void* fn = nullptr;
    cudaDriverEntryPointQueryResult qr;
    cudaGetDriverEntryPoint("cuTensorMapEncodeTiled", &fn, cudaEnableDefault, &qr);
    enc = (EncodeFn)fn;
    cudaFuncSetAttribute(fused_kernel<0>, cudaFuncAttributeMaxDynamicSharedMemorySize, SMEM_BYTES);
    cudaFuncSetAttribute(fused_kernel<1>, cudaFuncAttributeMaxDynamicSharedMemorySize, SMEM_BYTES);
    cudaFuncSetAttribute(fused_kernel<2>, cudaFuncAttributeMaxDynamicSharedMemorySize, SMEM_BYTES);
    cudaLaunchConfig_t cfg = {};
    cfg.gridDim = dim3(NCTA);
    cfg.blockDim = dim3(NTHREADS);
    cfg.dynamicSmemBytes = SMEM_BYTES;
    cudaLaunchAttribute at;
    at.id = cudaLaunchAttributeClusterDimension;
    at.val.clusterDim.x = 2;
    at.val.clusterDim.y = 1;
    at.val.clusterDim.z = 1;
    cfg.attrs = &at;
    cfg.numAttrs = 1;
    int nclusters = 0;
    if (cudaOccupancyMaxActiveClusters(&nclusters, fused_kernel<0>, &cfg) == cudaSuccess) coresident = nclusters >= NCTA / 2;
    (void)cudaGetLastError();
  }
  CUtensorMap tmX, tmW, tmWo, tmQ, tmOa, tmOb, tmXh, tmWh;
  {
    cuuint64_t dims[3] = {1024, 2, 1024};
    cuuint64_t str[2] = {2048, 4096};
    cuuint32_t box[3] = {64, 1, 128};
    make_map(enc, &tmX, d_in[6], 3, dims, str, box, CU_TENSOR_MAP_SWIZZLE_128B);
  }
  {
    cuuint64_t dims[3] = {1024, 1024, 3};
    cuuint64_t str[2] = {6144, 2048};
    cuuint32_t box[3] = {64, 32, 3};
    make_map(enc, &tmW, d_in[7], 3, dims, str, box, CU_TENSOR_MAP_SWIZZLE_128B);
  }
  {
    cuuint64_t dims[3] = {64, 1024, 16};
    cuuint64_t str[2] = {2048, 128};
    cuuint32_t box[3] = {64, 64, 2};
    make_map(enc, &tmWo, d_in[8], 3, dims, str, box, CU_TENSOR_MAP_SWIZZLE_128B);
  }
  {
    cuuint64_t dims[2] = {1024, 2048};
    cuuint64_t str[1] = {2048};
    cuuint32_t box[2] = {16, 128};
    make_map(enc, &tmQ, d_in[0], 2, dims, str, box, CU_TENSOR_MAP_SWIZZLE_NONE);
  }
  {
    cuuint64_t dims[2] = {2048, 2048};
    cuuint64_t str[1] = {4096};
    cuuint32_t box[2] = {16, 64};
    make_map(enc, &tmOa, d_out, 2, dims, str, box, CU_TENSOR_MAP_SWIZZLE_NONE);
  }
  {
    cuuint64_t dims[3] = {2048, 2, 1024};
    cuuint64_t str[2] = {4096, 8192};
    cuuint32_t box[3] = {64, 1, 16};
    make_map(enc, &tmOb, d_out, 3, dims, str, box, CU_TENSOR_MAP_SWIZZLE_128B);
  }
  {
    cuuint64_t dims[4] = {1024, 256, 2, 4};
    cuuint64_t str[3] = {4096, 2048, 256 * 4096};
    cuuint32_t box[4] = {64, 8, 2, 3};
    make_map(enc, &tmXh, d_in[6], 4, dims, str, box, CU_TENSOR_MAP_SWIZZLE_128B);
  }
  {
    cuuint64_t dims[3] = {64, 1024, 48};
    cuuint64_t str[2] = {6144, 128};
    cuuint32_t box[3] = {64, 64, 4};
    make_map(enc, &tmWh, d_in[7], 3, dims, str, box, CU_TENSOR_MAP_SWIZZLE_128B);
  }
  Params p;
  p.q = (const __nv_bfloat16*)d_in[0];
  p.k = (const __nv_bfloat16*)d_in[1];
  p.v = (const __nv_bfloat16*)d_in[2];
  p.shift_k = (const __nv_bfloat16*)d_in[3];
  p.ssm_k = (const __nv_bfloat16*)d_in[4];
  p.ssm_D = (const __nv_bfloat16*)d_in[5];
  p.x = (const __nv_bfloat16*)d_in[6];
  p.w = (const __nv_bfloat16*)d_in[7];
  p.wo = (const __nv_bfloat16*)d_in[8];
  p.out = (__nv_bfloat16*)d_out;
  p.zero = 0;
  if (coresident) {
    fused_kernel<0><<<NCTA, NTHREADS, SMEM_BYTES>>>(p, tmX, tmW, tmWo, tmQ, tmOa, tmOb, tmXh, tmWh);
  } else {
    fused_kernel<0><<<4, NTHREADS, SMEM_BYTES>>>(p, tmX, tmW, tmWo, tmQ, tmOa, tmOb, tmXh, tmWh);
    fused_kernel<1><<<NCTA, NTHREADS, SMEM_BYTES>>>(p, tmX, tmW, tmWo, tmQ, tmOa, tmOb, tmXh, tmWh);
    fused_kernel<2><<<NCTA, NTHREADS, SMEM_BYTES>>>(p, tmX, tmW, tmWo, tmQ, tmOa, tmOb, tmXh, tmWh);
  }
}
```

```cpp
#include <cuda_runtime.h>
#include <cuda.h>
#include <cuda_bf16.h>
#include <stdint.h>

namespace {

constexpr int SEQ = 2048;
constexpr int DM = 1024;
constexpr int NCTA = 132;
constexpr int NTHREADS = 384;

constexpr int STG1A = 32768;
constexpr int NS1A = 3;
constexpr int STG1B = 12288;
constexpr int NS1B = 5;
constexpr int OFF_1B = NS1A * STG1A;
constexpr int STG2 = 32768;
constexpr int NS2 = 5;
#define ILV 2
#define PACE 100
#define PACE0 0
#define ENDG 5
__device__ __forceinline__ uint32_t g2_a(int s, int hsel) { return (((0x97524 >> (4 * s)) & 15) ^ (s & 5 ? 0 : hsel)) << 14; }
__device__ __forceinline__ uint32_t g2_b(int s) { return ((0x83610 >> (4 * s)) & 15) << 14; }
constexpr int STGH = 73728;
constexpr int OFF_KH = 1 * STG2;
constexpr int OFF_OP = 2 * STG2;
constexpr int OFF_TAB = NS2 * STG2 - 8192;
constexpr int OFF_X = NS2 * STG2;
constexpr int XT = 8192;
constexpr int OFF_BAR = OFF_X + 8 * XT;
constexpr int OFF_EX = OFF_BAR + 384;
constexpr int OFF_L0 = 230400;
constexpr int SMEM_BYTES = OFF_L0 + 2048;
static_assert(OFF_TAB >= OFF_1B + 2 * STG1B && OFF_1B + NS1B * STG1B <= OFF_X && OFF_X % 1024 == 0, "layout");
static_assert(3 * STGH <= OFF_BAR && OFF_EX + 64 <= OFF_L0 && SMEM_BYTES <= 232448, "smem");

constexpr int BAR_FULLA = 0;
constexpr int BAR_EMPTYA = 3;
constexpr int BAR_FULLB = 6;
constexpr int BAR_EMPTYB = 11;
constexpr int BAR_FULL2 = 16;
constexpr int BAR_EMPTY2 = 21;
constexpr int BAR_X = 26;
constexpr int BAR_LAND = 27;
constexpr int BAR_TAB = 28;
constexpr int BAR_U = 29;
constexpr int BAR_H = 30;
constexpr int BAR_STG = 31;
constexpr int BAR_Y = 32;
constexpr int BAR_HALO = 40;
constexpr int BAR_Q = 41;
constexpr int BAR_QFREE = 42;

constexpr int NB_G1DONE = 1;
constexpr int NB_OREADY = 4;
constexpr int NB_CONV = 5;
constexpr int NB_HELP3 = 11;
constexpr int NB_FIRST = 13;

#define REG_MATH 224
#define REG_HELP 56
constexpr int SPIN_LIMIT = 1 << 20;

__device__ __align__(1024) __nv_bfloat16 g_o[SEQ * DM];
__device__ uint32_t g_flag_o[128];
__device__ uint32_t g_flag_h[4];
__device__ uint4 g_halo[128 * 128];
__device__ __align__(128) const uint32_t g_tab[2048] = {
  0x2fd93000,0x2ea72f64,0x2c722da8,0x263e2a1f,0x2ea73000,0xa63e2a1f,0xafd9ada8,0xac72af64,0x2c723000,0xafd9aa1f,0x263eada8,0x2ea72f64,
  0x263e3000,0xac72af64,0x2ea72da8,0xafd9aa1f,0xa63e3000,0x2c72af64,0xaea72da8,0x2fd9aa1f,0xac723000,0x2fd9aa1f,0xa63eada8,0xaea72f64,
  0xaea73000,0x263e2a1f,0x2fd9ada8,0x2c72af64,0xafd93000,0xaea72f64,0xac722da8,0xa63e2a1f,0x263e0000,0x2c722a1f,0x2ea72da8,0x2fd92f64,
  0x2c720000,0x2fd92f64,0x263e2da8,0xaea7aa1f,0x2ea70000,0x263e2f64,0xafd9ada8,0x2c72aa1f,0x2fd90000,0xaea72a1f,0x2c72ada8,0xa63e2f64,
  0x2fd90000,0xaea7aa1f,0x2c722da8,0xa63eaf64,0x2ea70000,0x263eaf64,0xafd92da8,0x2c722a1f,0x2c720000,0x2fd9af64,0x263eada8,0xaea72a1f,
  0x263e0000,0x2c72aa1f,0x2ea7ada8,0x2fd9af64,0xafd93000,0xaea72f64,0xac722da8,0xa63e2a1f,0xaea73000,0x263e2a1f,0x2fd9ada8,0x2c72af64,
  0xac723000,0x2fd9aa1f,0xa63eada8,0xaea72f64,0xa63e3000,0x2c72af64,0xaea72da8,0x2fd9aa1f,0x263e3000,0xac72af64,0x2ea72da8,0xafd9aa1f,
  0x2c723000,0xafd9aa1f,0x263eada8,0x2ea72f64,0x2ea73000,0xa63e2a1f,0xafd9ada8,0xac72af64,0x2fd93000,0x2ea72f64,0x2c722da8,0x263e2a1f,
  0xa63e0000,0xac722a1f,0xaea72da8,0xafd92f64,0xac720000,0xafd92f64,0xa63e2da8,0x2ea7aa1f,0xaea70000,0xa63e2f64,0x2fd9ada8,0xac72aa1f,
  0xafd90000,0x2ea72a1f,0xac72ada8,0x263e2f64,0xafd90000,0x2ea7aa1f,0xac722da8,0x263eaf64,0xaea70000,0xa63eaf64,0x2fd92da8,0xac722a1f,
  0xac720000,0xafd9af64,0xa63eada8,0x2ea72a1f,0xa63e0000,0xac72aa1f,0xaea7ada8,0xafd9af64,0xa63e0000,0xac72aa1f,0xaea7ada8,0xafd9af64,
  0xac720000,0xafd9af64,0xa63eada8,0x2ea72a1f,0xaea70000,0xa63eaf64,0x2fd92da8,0xac722a1f,0xafd90000,0x2ea7aa1f,0xac722da8,0x263eaf64,
  0xafd90000,0x2ea72a1f,0xac72ada8,0x263e2f64,0xaea70000,0xa63e2f64,0x2fd9ada8,0xac72aa1f,0xac720000,0xafd92f64,0xa63e2da8,0x2ea7aa1f,
  0xa63e0000,0xac722a1f,0xaea72da8,0xafd92f64,0x2fd93000,0x2ea72f64,0x2c722da8,0x263e2a1f,0x2ea73000,0xa63e2a1f,0xafd9ada8,0xac72af64,
  0x2c723000,0xafd9aa1f,0x263eada8,0x2ea72f64,0x263e3000,0xac72af64,0x2ea72da8,0xafd9aa1f,0xa63e3000,0x2c72af64,0xaea72da8,0x2fd9aa1f,
  0xac723000,0x2fd9aa1f,0xa63eada8,0xaea72f64,0xaea73000,0x263e2a1f,0x2fd9ada8,0x2c72af64,0xafd93000,0xaea72f64,0xac722da8,0xa63e2a1f,
  0x263e0000,0x2c72aa1f,0x2ea7ada8,0x2fd9af64,0x2c720000,0x2fd9af64,0x263eada8,0xaea72a1f,0x2ea70000,0x263eaf64,0xafd92da8,0x2c722a1f,
  0x2fd90000,0xaea7aa1f,0x2c722da8,0xa63eaf64,0x2fd90000,0xaea72a1f,0x2c72ada8,0xa63e2f64,0x2ea70000,0x263e2f64,0xafd9ada8,0x2c72aa1f,
  0x2c720000,0x2fd92f64,0x263e2da8,0xaea7aa1f,0x263e0000,0x2c722a1f,0x2ea72da8,0x2fd92f64,0xafd93000,0xaea72f64,0xac722da8,0xa63e2a1f,
  0xaea73000,0x263e2a1f,0x2fd9ada8,0x2c72af64,0xac723000,0x2fd9aa1f,0xa63eada8,0xaea72f64,0xa63e3000,0x2c72af64,0xaea72da8,0x2fd9aa1f,
  0x263e3000,0xac72af64,0x2ea72da8,0xafd9aa1f,0x2c723000,0xafd9aa1f,0x263eada8,0x2ea72f64,0x2ea73000,0xa63e2a1f,0xafd9ada8,0xac72af64,
  0x2fd93000,0x2ea72f64,0x2c722da8,0x263e2a1f,0xa63e0000,0xac72aa1f,0xaea7ada8,0xafd9af64,0x2c720000,0x2fd92f64,0x263e2da8,0xaea7aa1f,
  0xaea70000,0xa63eaf64,0x2fd92da8,0xac722a1f,0x2fd90000,0xaea72a1f,0x2c72ada8,0xa63e2f64,0xafd90000,0x2ea72a1f,0xac72ada8,0x263e2f64,
  0x2ea70000,0x263eaf64,0xafd92da8,0x2c722a1f,0xac720000,0xafd92f64,0xa63e2da8,0x2ea7aa1f,0x263e0000,0x2c72aa1f,0x2ea7ada8,0x2fd9af64,
  0x2fd93000,0x2ea72f64,0x2c722da8,0x263e2a1f,0xaea7b000,0x263eaa1f,0x2fd92da8,0x2c722f64,0x2c723000,0xafd9aa1f,0x263eada8,0x2ea72f64,
  0xa63eb000,0x2c722f64,0xaea7ada8,0x2fd92a1f,0xa63e3000,0x2c72af64,0xaea72da8,0x2fd9aa1f,0x2c72b000,0xafd92a1f,0x263e2da8,0x2ea7af64,
  0xaea73000,0x263e2a1f,0x2fd9ada8,0x2c72af64,0x2fd9b000,0x2ea7af64,0x2c72ada8,0x263eaa1f,0x263e0000,0x2c72aa1f,0x2ea7ada8,0x2fd9af64,
  0xac720000,0xafd92f64,0xa63e2da8,0x2ea7aa1f,0x2ea70000,0x263eaf64,0xafd92da8,0x2c722a1f,0xafd90000,0x2ea72a1f,0xac72ada8,0x263e2f64,
  0x2fd90000,0xaea72a1f,0x2c72ada8,0xa63e2f64,0xaea70000,0xa63eaf64,0x2fd92da8,0xac722a1f,0x2c720000,0x2fd92f64,0x263e2da8,0xaea7aa1f,
  0xa63e0000,0xac72aa1f,0xaea7ada8,0xafd9af64,0xafd93000,0xaea72f64,0xac722da8,0xa63e2a1f,0x2ea7b000,0xa63eaa1f,0xafd92da8,0xac722f64,
  0xac723000,0x2fd9aa1f,0xa63eada8,0xaea72f64,0x263eb000,0xac722f64,0x2ea7ada8,0xafd92a1f,0x263e3000,0xac72af64,0x2ea72da8,0xafd9aa1f,
  0xac72b000,0x2fd92a1f,0xa63e2da8,0xaea7af64,0x2ea73000,0xa63e2a1f,0xafd9ada8,0xac72af64,0xafd9b000,0xaea7af64,0xac72ada8,0xa63eaa1f,
  0xafd9b000,0xaea7af64,0xac72ada8,0xa63eaa1f,0x2ea73000,0xa63e2a1f,0xafd9ada8,0xac72af64,0xac72b000,0x2fd92a1f,0xa63e2da8,0xaea7af64,
  0x263e3000,0xac72af64,0x2ea72da8,0xafd9aa1f,0x263eb000,0xac722f64,0x2ea7ada8,0xafd92a1f,0xac723000,0x2fd9aa1f,0xa63eada8,0xaea72f64,
  0x2ea7b000,0xa63eaa1f,0xafd92da8,0xac722f64,0xafd93000,0xaea72f64,0xac722da8,0xa63e2a1f,0xa63e0000,0xac72aa1f,0xaea7ada8,0xafd9af64,
  0x2c720000,0x2fd92f64,0x263e2da8,0xaea7aa1f,0xaea70000,0xa63eaf64,0x2fd92da8,0xac722a1f,0x2fd90000,0xaea72a1f,0x2c72ada8,0xa63e2f64,
  0xafd90000,0x2ea72a1f,0xac72ada8,0x263e2f64,0x2ea70000,0x263eaf64,0xafd92da8,0x2c722a1f,0xac720000,0xafd92f64,0xa63e2da8,0x2ea7aa1f,
  0x263e0000,0x2c72aa1f,0x2ea7ada8,0x2fd9af64,0x2fd9b000,0x2ea7af64,0x2c72ada8,0x263eaa1f,0xaea73000,0x263e2a1f,0x2fd9ada8,0x2c72af64,
  0x2c72b000,0xafd92a1f,0x263e2da8,0x2ea7af64,0xa63e3000,0x2c72af64,0xaea72da8,0x2fd9aa1f,0xa63eb000,0x2c722f64,0xaea7ada8,0x2fd92a1f,
  0x2c723000,0xafd9aa1f,0x263eada8,0x2ea72f64,0xaea7b000,0x263eaa1f,0x2fd92da8,0x2c722f64,0x2fd93000,0x2ea72f64,0x2c722da8,0x263e2a1f,
  0x263e0000,0x2c72aa1f,0x2ea7ada8,0x2fd9af64,0xac720000,0xafd92f64,0xa63e2da8,0x2ea7aa1f,0x2ea70000,0x263eaf64,0xafd92da8,0x2c722a1f,
  0xafd90000,0x2ea72a1f,0xac72ada8,0x263e2f64,0x2fd90000,0xaea72a1f,0x2c72ada8,0xa63e2f64,0xaea70000,0xa63eaf64,0x2fd92da8,0xac722a1f,
  0x2c720000,0x2fd92f64,0x263e2da8,0xaea7aa1f,0xa63e0000,0xac72aa1f,0xaea7ada8,0xafd9af64,0x316c2fbd,0x343e32f7,0x35bc34ff,0x372c3676,
  0x371532c6,0x3a81392e,0x3bef3b71,0x3b7c3bf2,0x397034cf,0x3bfc3b6c,0x38b23b04,0xb40e31e8,0x3ae13631,0x39e73bf5,0xb6e83219,0xbbe8bb13,
  0x3bc23785,0x30be3aa9,0xbbfdb911,0x2a16b9aa,0x3bfe3865,0xb80f37a6,0xb82abc00,0x3bfd376f,0x3b9238fd,0xbb7f2311,0x3805b929,0x31223bde,
  0x3a85398b,0xbb96b742,0x3bff319e,0xbbb82f8b,0xbbe2bbf1,0xbbb7bbcf,0xbb78bb9a,0xbb27bb52,0xbb2cbbd2,0xb8a8ba19,0xb029b5df,0x35a52f59,
  0xb9dfbba1,0x2ba7b5f7,0x3a7a37b2,0x3bbd3bdd,0xb815bb60,0x39662e91,0x3b373bda,0xb0d7377a,0xb3d3bb10,0x3be9386f,0x2a7a3a31,0xbbfeb9a6,
  0x294dbab0,0x3ae53b07,0xbad51fdb,0xab43bb16,0x352fba41,0x35993c00,0xbaebba1d,0x3be531cf,0x38a3b9c5,0xb5173b21,0x2776bbe0,0x34323bf2,
  0x384537dd,0x38ea3899,0x39823937,0x3a0d39c9,0x39463a93,0x3340374e,0xb426a452,0xb979b7c8,0xbb45b924,0xbb32bc00,0xb371b902,0x38d63294,
  0xb08db9a1,0x3b3f379b,0x39583bd7,0xb8252dfb,0x3bea3a2d,0xb3ba3874,0xbb89bb0d,0x36d2b625,0xb6bb387f,0xb8d1bbf5,0x3be73602,0xb546391f,
  0xba00bb01,0x3bff35eb,0xba5c34db,0x3359bab6,0x3ac7b66b,0xb9413933,0x368dbabd,0xb0103bb3,0xbac4baf7,0xba50ba8c,0xb9cdba11,0xb93cb986,
  0x3a04388e,0x3bcb3b1e,0x3bba3c00,0x39d63afe,0x36af3a21,0xb6ffa17f,0xbbc8ba3d,0xba60bbd4,0xbbebb9af,0xb6c6bb0a,0x39f43263,0x3ad83bf7,
  0x30a6b916,0x3bc33aa5,0xb55e3790,0xbb3dbb63,0x3b423a9e,0xba642ec3,0xb0f0bb6a,0x3b8e3a25,0xb94a37bd,0x2884bb6f,0x38db3b9f,0xbbc9b85a,
  0xb840bb54,0x3a093a15,0xbb4cb850,0x3bef3457,0x3a893a4d,0x3af43ac1,0x3b4f3b24,0x3b983b76,0xbb94baba,0xbbe4bbf9,0xba58bb57,0xb699b8f8,
  0x3bfe3b18,0x394f3b5c,0xb109347b,0xbae8b884,0xbbc0bb68,0xa9b1b90c,0x3b8b387a,0x38bc3ba5,0x3ade3ba7,0xb8c1324b,0xb9f0bbf6,0x39eb9648,
  0xb96bbbd6,0x3bbf3487,0xb38939b3,0xb9f8bba3,0x370a3bf3,0xbb47b994,0x3bbc2d65,0xb8ad3889,0xb153bc00,0x37213b9c,0xb97dba90,0x3af138f3,
  0xb89eb8ee,0xb7e8b84a,0xb682b737,0xb50bb5c8,0x35233855,0xb13b2d33,0xb8e0b65f,0xbb4aba45,0xa8e8b764,0x39fc3648,0x3be63bae,0x380a3a9b,
  0xb3eb360e,0xbbfeba35,0xb552baa2,0x3a7334b7,0x381ab4ab,0x3a6f3bd8,0xb95d2e5f,0xb962bc00,0xb9e3327c,0xb402bbac,0x3bc6399d,0xb95434c3,
  0x3b2faf27,0xb6a439bc,0xb41abbf9,0x3a7e3a97,0xbbe3251b,0x3b2ab4f3,0xb9d23894,0x37f3ba49,0x3bce3bb5,0x3bf03be1,0x3bff3bfa,0x3bfb3bff,
  0x2c38b1b6,0x383a34e7,0x3aee39c0,0x3bff3bb2,0xbb81bbf8,0xb53ab999,0x38302ef5,0x3bed3ab3,0xb8cc9cb6,0xbb85bbab,0x2adeb86a,0x3bc5391b,
  0x38c73bf6,0xbadbb232,0xb6ddbba9,0x3b87361a,0x3b833201,0xb0743a39,0xba76bb5e,0x3b352dc9,0xac06bbb0,0x39743b59,0xbbeeb759,0x3aceb2ad,
  0xbbccb5d4,0x3bfb2d00,0xbb7a32de,0x3a54b7d2,0xb30fb44b,0xafefb185,0xa6adacce,0x2c9c25e4,0xbbfcbbdf,0xbacbbb9e,0xb7feb990,0xa81fb463,
  0xb58d2d97,0xbb90b9b8,0xbad1bbf4,0xb05bb85f,0x3a673c00,0xb5763493,0xbbfdbaac,0xb3a2ba29,0x3a6b2e2d,0x38203bd9,0xbb3ab49f,0xb56abb65,
  0xb581bbdc,0x3bec3907,0xb8b7363c,0xb6f4bbf8,0xbbfcb46f,0x39dab654,0xb0423b1b,0xb835bbd3,0xb3283b73,0xac6abbfa,0x35b13bd0,0xb8e5bafb,
  0x38ee3a0d,0xb84aba89,0x37373af4,0xb5c8bb4f,0x35df3a81,0x2f59bbef,0xb88e3b7c,0x3b1eb946,0x2d973ae8,0x39b8bb81,0xbbf4353a,0x385f3830,
  0xb2633b3f,0x3bf7b958,0xb60eb825,0xba353bc0,0xb7853b87,0x3aa9b3d3,0x3911bbe9,0xb9aa2a7a,0xb99d3bbf,0x34c33389,0x3bdcb9f8,0x3907bb83,
  0xbb013be5,0xb5eb394a,0x34db2884,0x3ab6b8db,0xbbd03bfb,0xbafb3b7a,0xb98b3a54,0xb74238a3,0x3a4db93c,0xbac1389e,0x3b24b7e8,0xbb763682,
  0x3b71b8a8,0xbbf23029,0x3a9335a5,0xb74eba04,0x3bf8b80a,0xb999b58d,0xaef53b90,0x3ab3bad1,0x3bd7b6c6,0xadfbb9f4,0xbb683ad8,0x390c33eb,
  0x3b10b56a,0x386fbbc2,0xba3130be,0xb9a63bfd,0x39b3b402,0x3ba3bbc6,0x3201b954,0xba393581,0x37bdb122,0x3b6fba00,0x3b9fbbff,0x385aba5c,
  0x32deac6a,0x37d2b5b1,0x39c5b8e5,0x3b21ba85,0x344b3b98,0xb185bbce,0x2cce3bf0,0x25e4bbff,0xbc003340,0x3afe3426,0xb855b979,0x2d333b94,
  0x34cfbbed,0xbb6c39df,0x3b042ba7,0xb1e8ba7a,0x3aa2a9b1,0x34b7bb8b,0xbc0038bc,0x349338cc,0xba2d3bfe,0x387430a6,0x3b0dbbc3,0xb625b55e,
  0xb63cb074,0xbbf83a76,0xb8653b35,0x37a6294d,0x3bf3bbc9,0x3994bb2f,0x2d65b6a4,0xb889341a,0xb19e3517,0x2f8b2776,0x366bb432,0x3933b840,
  0x3bb5b50b,0xbbe1330f,0x3bfaafef,0xbbff26ad,0xa4523bcb,0x37c8bbba,0xbaba39d6,0x3bf9b523,0xbba1305b,0x35f73970,0x37b2bbfc,0xbbdd38b2,
  0x387abbfe,0xbba53552,0x9cb63a73,0x3babba67,0x39162a16,0x3aa5bbea,0xb790b3ba,0xbb633b89,0xbb5e3bec,0xadc938b7,0x3ab0b6f4,0x3b07bbfe,
  0xaf27b359,0xb9bc370a,0xbbf93b47,0xba973bbc,0x3be0bb96,0x3bf2bbff,0x3b54bbb8,0x3a15bac7,0xafbd3bfb,0x32f7bbe2,0xb4ff3bb7,0x3676bb78,
  0x365fbbe4,0xba453a58,0x3bdfb699,0xbb9eac38,0xb9243bbd,0x3c00b6af,0xb902b6ff,0xb2943bc8,0x3aacbb85,0xba29aade,0xb6313bc5,0x3bf5b815,
  0xbba73b3d,0x324b381a,0x3bf6ba6f,0x9648b95d,0x3c00bae5,0x376fbad5,0xb87f2b43,0xbbf53b42,0xbbb03a7e,0xbb593bfc,0xb75939da,0x32ad3042,
  0x3abdba09,0x3bb3bb4c,0x3c00bbef,0x3b9cbbe3,0x3bf12c9c,0xbbcfb16c,0x3b9a343e,0xbb52b5bc,0xbb57b13b,0x38f838e0,0xb1b6bb4a,0xb4e73bfc,
  0x3a21340e,0x217fbb45,0xba3d3b32,0x3bd4b371,0xb86ab576,0xb91b3bfd,0x3b60b3a2,0x2e91bae1,0x34ab36d2,0x3bd8bade,0xae5fb8c1,0xbc0039f0,
  0x9fdbb80f,0xbb16382a,0xba9e3bfd,0x2ec336bb,0xb46f38ad,0x3654ac06,0x3b1bb974,0x3bd3bbee,0x3850b941,0x3457b68d,0xa51bb010,0xb4f33153,
  0xb7dd3b27,0x3899bac4,0xb9373a50,0x39c9b9cd,0x3990383a,0xb463baee,0xb2c63bff,0x392ebb2c,0x3b18ba60,0xbb5c28e8,0x347b39fc,0x3884bbe6,
  0xb219b966,0xbb133b37,0x39a130d7,0x379bbbeb,0xbbf63962,0xb2323a6b,0x3ba9b820,0x361abb3a,0xb6023a64,0x391fb0f0,0x3bd6bb8e,0x3487b9e3,
  0x3a41b835,0x3c00bb92,0x3a1dbb7f,0x31cfb805,0x3a90bb2a,0x38f3b9d2,0x35d4b7f3,0x2d00b328,0x3af7372c,0xba8cb845,0x3a1138ea,0xb986b982,
  0x39c0bacb,0xbbb237fe,0x3bd2a81f,0xba19b715,0xb764b8d6,0xb6483bfe,0x3baeb94f,0xba9bb109,0xbbda39e7,0x377a36e8,0x39afbbe8,0xbb0a308d,
  0xae2d39eb,0x3bd9b8c7,0x349fbadb,0xbb6536dd,0x3b6ab8d1,0x3a25bbe7,0xb27cb546,0xbbac396b,0x38fdbace,0xa311b52f,0xb9293599,0xbbde3aeb,
  0xb8943721,0xba49397d,0xbb733af1,0xbbfa3bcc,0xbbfb3bff,0xbbe23bf1,0xbbb73bcf,0xbb783b9a,0xbb7c3bf2,0xb9463a93,0xb340374e,0x3426a452,
  0xba603bd4,0xa8e83764,0x39fcb648,0x3be6bbae,0xb8bc3ba5,0x38cc9cb6,0x3b85bbab,0xaadeb86a,0xb56a3b65,0x3bc2b785,0x30bebaa9,0xbbfd3911,
  0xab433b16,0x3b42ba9e,0xba64aec3,0xb0f03b6a,0x33593ab6,0x370abbf3,0xbb473994,0x3bbcad65,0x37f33a49,0xb328bb73,0xac6a3bfa,0x35b1bbd0,
  0xac9c25e4,0xb16c2fbd,0xb43e32f7,0xb5bc34ff,0xb5a52f59,0xba04388e,0xbbcb3b1e,0xbbba3c00,0xb8d63294,0xbbfe3b18,0xb94f3b5c,0x3109347b,
  0xba7334b7,0xba673c00,0x35763493,0x3bfdbaac,0xbb87361a,0xb3d33b10,0x3be9b86f,0x2a7aba31,0xbbfd376f,0x36bb387f,0x38d1bbf5,0xbbe73602,
  0xbbc9385a,0x3b2f2f27,0xb6a4b9bc,0xb41a3bf9,0xbaf138f3,0x3bccb5d4,0xbbfb2d00,0x3b7a32de,0xbb273b52,0xbac43af7,0xba503a8c,0xb9cd3a11,
  0x3979b7c8,0x3b94baba,0x3be4bbf9,0x3a58bb57,0x380aba9b,0xb58dad97,0xbb9039b8,0xbad13bf4,0xbbc5391b,0xb8153b60,0x3966ae91,0x3b37bbda,
  0x2a1639aa,0x3beaba2d,0xb3bab874,0xbb893b0d,0x3b8eba25,0xb9e3b27c,0xb4023bac,0x3bc6b99d,0xb8adb889,0xac063bb0,0x3974bb59,0xbbee3759,
  0xb8e53afb,0x3a85b98b,0xbb963742,0x3bffb19e,0xb72c3676,0xb84537dd,0xb8ea3899,0xb9823937,0xb9d63afe,0xb5233855,0x313b2d33,0x38e0b65f,
  0x3ae8b884,0x3b81bbf8,0x353ab999,0xb8302ef5,0x33a2ba29,0xbae13631,0xb9e73bf5,0x36e83219,0xbbfe39a6,0x30a63916,0x3bc3baa5,0xb55eb790,
  0x3546391f,0x396bbbd6,0xbbbf3487,0x338939b3,0x3a7eba97,0xbbfc346f,0x39da3654,0xb042bb1b,0xba54b7d2,0x38a339c5,0xb517bb21,0x27763be0,
  0xb93c3986,0xb89e38ee,0xb7e8384a,0xb6823737,0x3699b8f8,0xac38b1b6,0xb83a34e7,0xbaee39c0,0xb05b385f,0x3970b4cf,0x3bfcbb6c,0x38b2bb04,
  0xb0d7b77a,0xbbeb39af,0xb6c63b0a,0x39f4b263,0x36d23625,0x3adebba7,0xb8c1b24b,0xb9f03bf6,0xb954b4c3,0xb5813bdc,0x3becb907,0xb8b7b63c,
  0x3ace32ad,0xb52fba41,0xb5993c00,0x3aebba1d,0xbbb8af8b,0x3ac7366b,0xb941b933,0x368d3abd,0xba0d39c9,0xba893a4d,0xbaf43ac1,0xbb4f3b24,
  0x3b4aba45,0x3bfcbbdf,0x3acbbb9e,0x37feb990,0xbbed3ab3,0xb9df3ba1,0x2ba735f7,0x3a7ab7b2,0x3be8bb13,0x308db9a1,0xbb3f379b,0xb9583bd7,
  0xbb3d3b63,0x381a34ab,0x3a6fbbd8,0xb95dae5f,0x39f8bba3,0xbb833201,0x30743a39,0x3a76bb5e,0xb8353bd3,0x3b92b8fd,0xbb7fa311,0x38053929,
  0x3432bbf2,0xb8403b54,0x3a09ba15,0xbb4c3850,0xb50b35c8,0xb30f344b,0xafef3185,0xa6ad2cce,0xbbff3bb2,0xbb2c3bd2,0xb8a83a19,0xb02935df,
  0xb40eb1e8,0xbb453924,0xbb323c00,0xb3713902,0x3ad8bbf7,0xb3ebb60e,0xbbfe3a35,0xb5523aa2,0x39eb1648,0x38c7bbf6,0xbadb3232,0xb6dd3ba9,
  0xb6f43bf8,0x3bfeb865,0xb80fb7a6,0xb82a3c00,0xbbe531cf,0x394a37bd,0xa884bb6f,0xb8db3b9f,0xb010bbb3,0xb1533c00,0x3721bb9c,0xb97d3a90,
  0xbb983b76,0xbbce3bb5,0xbbf03be1,0xbbff3bfa,0x281fb463,0xb71532c6,0xba81392e,0xbbef3b71,0x3bbdbbdd,0x36afba21,0xb6ff217f,0xbbc83a3d,
  0x38252dfb,0x3bc0bb68,0x29b1b90c,0xbb8b387a,0xb9623c00,0x3a6bae2d,0x3820bbd9,0xbb3a349f,0xbb352dc9,0x294d3ab0,0x3ae5bb07,0xbad59fdb,
  0x3122bbde,0xba003b01,0x3bffb5eb,0xba5cb4db,0x3befb457,0xbbe3a51b,0x3b2a34f3,0xb9d2b894,0x39c939cd,0xba4db93c,0x3ac1389e,0xbb24b7e8,
  0x3b1e3946,0xbc00b340,0x3afeb426,0xb8553979,0x3bdd38b2,0xba21340e,0xa17fbb45,0x3a3d3b32,0x3bf53815,0xb2193966,0xbb13bb37,0x39a1b0d7,
  0x3b6536dd,0x37853b87,0xbaa9b3d3,0xb911bbe9,0x3a393581,0x3b5e3bec,0x2dc938b7,0xbab0b6f4,0x3889341a,0x3bb03a7e,0x3b593bfc,0x375939da,
  0x34f33153,0x38943721,0x3a49397d,0x3b733af1,0xb9863982,0x38eeba0d,0xb84a3a89,0x3737baf4,0xb74e3a04,0xa452bbcb,0x37c83bba,0xbabab9d6,
  0xb1e83a7a,0xb924bbbd,0x3c0036af,0xb90236ff,0x2e913ae1,0xbbdab9e7,0x377ab6e8,0x39af3be8,0x361a3b3a,0xbb10b56a,0xb86fbbc2,0x3a3130be,
  0x39073b83,0xb63c3074,0xbbf8ba76,0xb865bb35,0x3a973bbc,0x346f38ad,0xb654ac06,0xbb1bb974,0x3b9c3be3,0x3a903b2a,0x38f339d2,0x35d437f3,
  0x3b763682,0xbbb5b50b,0x3be1330f,0xbbfaafef,0x2d33bb94,0x365f3be4,0xba45ba58,0x3bdf3699,0xbbd4b371,0x3764b8d6,0x36483bfe,0xbbaeb94f,
  0x379b3beb,0xbbd7b6c6,0x2dfbb9f4,0x3b683ad8,0x39aa2a7a,0x3a2d3bfe,0xb87430a6,0xbb0dbbc3,0xbb07bbfe,0x1fdbb80f,0x3b16382a,0x3a9e3bfd,
  0xb2ad3042,0xba41b835,0xbc00bb92,0xba1dbb7f,0x3bfa3bcc,0x3bd03bfb,0x3afb3b7a,0x398b3a54,0xb5c83b4f,0x344bbb98,0xb1853bce,0x2ccebbf0,
  0x3bf93523,0xbb57313b,0x38f8b8e0,0xb1b63b4a,0xb294bbc8,0x3b183a60,0xbb5ca8e8,0x347bb9fc,0xbb0ab08d,0xb263bb3f,0x3bf73958,0xb60e3825,
  0x39a63bfd,0xb9162a16,0xbaa5bbea,0x3790b3ba,0x37a6a94d,0x3c003ae5,0x376f3ad5,0xb87fab43,0xbbd3bbee,0xb8fdbace,0x2311b52f,0x39293599,
  0x2d003328,0xb2deac6a,0xb7d2b5b1,0xb9c5b8e5,0x3bff26ad,0xbbf12c9c,0x3bcfb16c,0xbb9a343e,0xbb9e2c38,0x3990b83a,0xb4633aee,0xb2c6bbff,
  0x3a9bb109,0xad973ae8,0xb9b8bb81,0x3bf4353a,0xb90c33eb,0xb87abbfe,0x3ba53552,0x1cb63a73,0x3625b55e,0x3ba73b3d,0xb24b381a,0xbbf6ba6f,
  0xaec336bb,0xbb6ab8d1,0xba25bbe7,0x327cb546,0xb1cfb805,0x37bd3122,0x3b6f3a00,0x3b9f3bff,0x374238a3,0x319e3517,0xaf8b2776,0xb66bb432,
  0x25e43bff,0xafbdbbfb,0x32f73be2,0xb4ffbbb7,0xb4e7bbfc,0x39c03acb,0xbbb2b7fe,0x3bd2281f,0x38843be6,0xbbf8b80a,0x3999b58d,0x2ef53b90,
  0xba35bbc0,0x3aa229b1,0x34b73b8b,0xbc00b8bc,0x3b633b89,0xb4ab36d2,0xbbd8bade,0x2e5fb8c1,0xbbf5bb42,0xb602ba64,0x391f30f0,0x3bd63b8e,
  0x3bde3aeb,0x3b013be5,0x35eb394a,0xb4db2884,0xbb21ba85,0xbbe0bb96,0xbbf2bbff,0xbb54bbb8,0x3b52b5bc,0xbaf7372c,0x3a8cb845,0xba1138ea,
  0x392e3b2c,0xbb71b8a8,0x3bf23029,0xba9335a5,0xb85f3830,0xb4cfbbed,0x3b6c39df,0xbb042ba7,0xbbabba67,0x386ab576,0x391b3bfd,0xbb60b3a2,
  0x1648b95d,0x3bf63962,0x32323a6b,0xbba9b820,0x3bac396b,0x399d3bbf,0xb4c33389,0xbbdcb9f8,0x385a3a5c,0xaf273359,0xb9bcb70a,0xbbf9bb47,
  0xb933b840,0xbabdba09,0xbbb3bb4c,0xbc00bbef,0x36763b78,0xb7ddbb27,0x38993ac4,0xb937ba50,0xba193715,0x35dfba81,0x2f593bef,0xb88ebb7c,
  0xbab3bad1,0x3ba1305b,0xb5f73970,0xb7b2bbfc,0x3493b8cc,0x3aac3b85,0xba292ade,0xb631bbc5,0x3c0039f0,0x2e2d39eb,0xbbd9b8c7,0xb49fbadb,
  0x348739e3,0xb9b3b402,0xbba3bbc6,0xb201b954,0xbab6b8db,0xbbf3bbc9,0xb994bb2f,0xad65b6a4,0xba15bac7,0xb850b941,0xb457b68d,0x251bb010,
  0xb9cfbb16,0x30ac2a31,0x3b9c3bf1,0xb493ae2d,0xb76fb8b4,0x35a133e3,0x3a1d3afe,0xb902b76f,0xb3e3b5a1,0x38b4376f,0x376f3902,0xbafeba1d,
  0xaa31b0ac,0x3b1639cf,0x2e2d3493,0xbbf1bb9c,0xb956ba74,0x305f29cc,0x3b633bd2,0xb44badc9,0xb6e7b859,0x353f335e,0x39d23ab6,0xb8bcb6ff,
  0xb35eb53f,0x385936e7,0x36ff38bc,0xbab6b9d2,0xa9ccb05f,0x3a743956,0x2dc9344b,0xbbd2bb63,0xb8e3b9de,0x30122967,0x3b1e3ba1,0xb402ad65,
  0xb662b801,0x34de32da,0x39823a67,0xb874b68d,0xb2dab4de,0x38013662,0x368d3874,0xba67b982,0xa967b012,0x39de38e3,0x2d653402,0xbba1bb1e,
  0xb876b952,0x2f8c2902,0x3ace3b60,0xb371ad00,0xb5e1b758,0x347e3257,0x392e3a11,0xb82ab61a,0xb257b47e,0x375835e1,0x361a382a,0xba11b92e,
  0xa902af8c,0x39523876,0x2d003371,0xbb60bace,0xb80db8ce,0x2ef3289e,0x3a733b10,0xb2deac9c,0xb562b6b3,0x342031d5,0x38d639b3,0xb7bdb5a5,
  0xb1d5b420,0x36b33562,0x35a537bd,0xb9b3b8d6,0xa89eaef3,0x38ce380d,0x2c9c32de,0xbb10ba73,0xb750b851,0x2e5a2839,0x3a0d3ab0,0xb24bac38,
  0xb4e5b613,0x33863153,0x387a394f,0xb721b52f,0xb153b386,0x361334e5,0x352f3721,0xb94fb87a,0xa839ae5a,0x38513750,0x2c38324b,0xbab0ba0d,
  0xb68eb7b4,0x2dc227a9,0x399d3a41,0xb1b6aba7,0xb46ab577,0x32cd30d2,0x381a38e5,0xb682b4b7,0xb0d2b2cd,0x3577346a,0x34b73682,0xb8e5b81a,
  0xa7a9adc2,0x37b4368e,0x2ba731b6,0xba41b99d,0xb5d2b6d1,0x2d2a26e0,0x392439c5,0xb122aade,0xb3e3b4de,0x32163052,0x376f3874,0xb5dfb43e,
  0xb052b216,0x34de33e3,0x343e35df,0xb874b76f,0xa6e0ad2a,0x36d135d2,0x2ade3122,0xb9c5b924,0xb51cb5f6,0x2c932617,0x38a3393c,0xb08daa16,
  0xb2f4b448,0x31602fa5,0x36a437fe,0xb53ab389,0xafa5b160,0x344832f4,0x3389353a,0xb7feb6a4,0xa617ac93,0x35f6351c,0x2a16308d,0xb93cb8a3,
  0xb46ab523,0x2bf6254d,0x381a38a8,0xafefa94d,0xb209b36b,0x30ac2ea7,0x35d4370a,0xb493b294,0xaea7b0ac,0x336b3209,0x32943493,0xb70ab5d4,
  0xa54dabf6,0x3523346a,0x294d2fef,0xb8a8b81a,0xb378b456,0x2ac82484,0x3715380a,0xaec3a884,0xb120b24a,0x2ff22da9,0x34ff360e,0xb3d3b19e,
  0xada9aff2,0x324a3120,0x319e33d3,0xb60eb4ff,0xa484aac8,0x34563378,0x28842ec3,0xb80ab715,0xb223b31c,0x29992376,0x35eb36c6,0xad97a776,
  0xb039b12d,0x2e8d2cac,0x3426350b,0xb27cb0a6,0xacacae8d,0x312d3039,0x30a6327c,0xb50bb426,0xa376a999,0x331c3223,0x27762d97,0xb6c6b5eb,
  0xb0d2b194,0x286b21e4,0x34b7356a,0xac6aa5e4,0xaea7b012,0x2d2a2b5f,0x32943402,0xb122af59,0xab5fad2a,0x30122ea7,0x2f593122,0xb402b294,
  0xa1e4a86b,0x319430d2,0x25e42c6a,0xb56ab4b7,0xaf0cb012,0x267b2052,0x32f73402,0xaa7aa452,0xacdeadf5,0x2b912967,0x30d731e8,0xaf8bad65,
  0xa967ab91,0x2df52cde,0x2d652f8b,0xb1e8b0d7,0xa052a67b,0x30122f0c,0x24522a7a,0xb402b2f7,0xac79ad2a,0x24201d7f,0x30743122,0xa81fa17f,
  0xaa31ab91,0x28d026e0,0x2e2d2f8b,0xacceaade,0xa6e0a8d0,0x2b912a31,0x2ade2cce,0xaf8bae2d,0x9d7fa420,0x2d2a2c79,0x217f281f,0xb122b074,
  0xa7a9a86b,0x1f1218b6,0x2ba72c6a,0xa3119cb6,0xa54da67b,0x242021e4,0x294d2a7a,0xa81fa5e4,0xa1e4a420,0x267b254d,0x25e4281f,0xaa7aa94d,
  0x98b69f12,0x286b27a9,0x1cb62311,0xac6aaba7,0x211b21e4,0x98b69248,0xa51ba5e4,0x1cb61648,0x1f122052,0x9d7f9bdb,0xa311a452,0x217f1fdb,
  0x1bdb1d7f,0xa0529f12,0x9fdba17f,0x24522311,0x124818b6,0xa1e4a11b,0x96489cb6,0x25e4251b,0x2a632b5f,0xa1e49bdb,0xae5faf59,0x25e41fdb,
  0x286b2967,0xa6e0a4e9,0xac6aad65,0x2ade28e8,0x24e926e0,0xa967a86b,0xa8e8aade,0x2d652c6a,0x1bdb21e4,0xab5faa63,0x9fdba5e4,0x2f592e5f,
  0x2dc22ea7,0xa54d9f12,0xb1b6b294,0x294d2311,0x2bf62cde,0xaa31a86b,0xafefb0d7,0x2e2d2c6a,0x286b2a31,0xacdeabf6,0xac6aae2d,0x30d72fef,
  0x1f12254d,0xaea7adc2,0xa311a94d,0x329431b6,0x302c30d2,0xa7a9a11b,0xb41ab4b7,0x2ba7251b,0x2dc22f0c,0xac79aa63,0xb1b6b2f7,0x30742e5f,
  0x2a632c79,0xaf0cadc2,0xae5fb074,0x32f731b6,0x211b27a9,0xb0d2b02c,0xa51baba7,0x34b7341a,0x317a3257,0xa902a2ad,0xb552b61a,0x2d0026ad,
  0x2f8c309f,0xaddcac2e,0xb371b487,0x31cf3029,0x2c2e2ddc,0xb09faf8c,0xb029b1cf,0x34873371,0x22ad2902,0xb257b17a,0xa6adad00,0x361a3552,
  0x32cd33e3,0xaa31a420,0xb682b76f,0x2e2d281f,0x30ac31bb,0xaf3fad2a,0xb493b58d,0x33283122,0x2d2a2f3f,0xb1bbb0ac,0xb122b328,0x358d3493,
  0x24202a31,0xb3e3b2cd,0xa81fae2d,0x376f3682,0x341334bc,0xab5fa4e9,0xb7a6b85a,0x2f5928e8,0x319432da,0xb052ae28,0xb56ab68d,0x343e3219,
  0x2e283052,0xb2dab194,0xb219b43e,0x368d356a,0x24e92b5f,0xb4bcb413,0xa8e8af59,0x385a37a6,0x34c3358c,0xac47a5b2,0xb85fb8f3,0x304229b1,
  0x327e33fd,0xb106af26,0xb63cb785,0x34e7330f,0x2f263106,0xb3fdb27e,0xb30fb4e7,0x3785363c,0x25b22c47,0xb58cb4c3,0xa9b1b042,0x38f3385f,
  0x35773662,0xacdea67b,0xb8e5b982,0x30d72a7a,0x336b3493,0xb1bbb012,0xb70ab83a,0x358d3402,0x301231bb,0xb493b36b,0xb402b58d,0x383a370a,
  0x267b2cde,0xb662b577,0xaa7ab0d7,0x398238e5,0x36303741,0xad76a744,0xb962ba04,0x316c2b43,0x342e352a,0xb271b092,0xb7d2b8ad,0x3631347b,
  0x30923271,0xb52ab42e,0xb47bb631,0x38ad37d2,0x27442d76,0xb741b630,0xab43b16c,0x3a043962,0x36ee3815,0xae0ea807,0xb9d6ba7a,0x32012c06,
  0x34a735c4,0xb329b113,0xb84ab91b,0x36d234f3,0x31133329,0xb5c4b4a7,0xb4f3b6d2,0x391b384a,0x28072e0e,0xb815b6ee,0xac06b201,0x3a7a39d6,
  0x37b4388e,0xaea7a86b,0xba41bae1,0x32942c6a,0x35233662,0xb3e3b194,0xb8a8b982,0x376f356a,0x319433e3,0xb662b523,0xb56ab76f,0x398238a8,
  0x286b2ea7,0xb88eb7b4,0xac6ab294,0x3ae13a41,0x3841390f,0xaf3fa8d0,0xbaa2bb3a,0x33282cce,0x35a13705,0xb44fb216,0xb902b9e3,0x380535df,
  0x3216344f,0xb705b5a1,0xb5dfb805,0x39e33902,0x28d02f3f,0xb90fb841,0xacceb328,0x3b3a3aa2,0x38ac3997,0xafd8a935,0xbaf7bb83,0x33ba2d33,
  0x362137ac,0xb4aeb298,0xb958ba3d,0x38503654,0x329834ae,0xb7acb621,0xb654b850,0x3a3d3958,0x29352fd8,0xb997b8ac,0xad33b3ba,0x3b833af7,
  0x391c3a28,0xb039a999,0xbb42bbbc,0x34262d97,0x36a4382d,0xb50eb31c,0xb9aaba90,0x389936c6,0x331c350e,0xb82db6a4,0xb6c6b899,0x3a9039aa,
  0x29993039,0xba28b91c,0xad97b426,0x3bbc3b42,0x39923ac3,0xb085a9fe,0xbb81bbe3,0x346f2dfb,0x372a3886,0xb570b3a0,0xb9f8badb,0x38e03737,
  0x33a03570,0xb886b72a,0xb737b8e0,0x3adb39f8,0x29fe3085,0xbac3b992,0xadfbb46f,0x3be33b81,
};

#define PROF(slot) do {} while (0)
#define PROFA(slot, dep) do {} while (0)
#define PROF3(slot) do {} while (0)
#define PROF2(slot) do {} while (0)

__device__ __forceinline__ uint32_t smem_u32(const void* p) { return (uint32_t)__cvta_generic_to_shared(p); }

__device__ __forceinline__ void mbar_init(uint32_t a, uint32_t c) {
  asm volatile("mbarrier.init.shared::cta.b64 [%0], %1;\n" ::"r"(a), "r"(c) : "memory");
}
__device__ __forceinline__ void mbar_expect_tx(uint32_t a, uint32_t bytes) {
  asm volatile("mbarrier.arrive.expect_tx.shared::cta.b64 _, [%0], %1;\n" ::"r"(a), "r"(bytes) : "memory");
}
__device__ __forceinline__ void mbar_arrive_cluster(uint32_t cluster_addr) {
  asm volatile("mbarrier.arrive.shared::cluster.b64 _, [%0];\n" ::"r"(cluster_addr) : "memory");
}
__device__ __forceinline__ void mbar_arrive_cluster_n(uint32_t cluster_addr, uint32_t n) {
  asm volatile("mbarrier.arrive.shared::cluster.b64 _, [%0], %1;\n" ::"r"(cluster_addr), "r"(n) : "memory");
}
__device__ __forceinline__ bool mbar_try(uint32_t a, uint32_t parity) {
  uint32_t ok;
  asm volatile("{\n.reg .pred p;\nmbarrier.try_wait.parity.shared::cta.b64 p, [%1], %2;\nselp.u32 %0, 1, 0, p;\n}\n"
               : "=r"(ok) : "r"(a), "r"(parity) : "memory");
  return ok;
}
__device__ __forceinline__ void mbar_wait(uint32_t a, uint32_t parity) {
  if (mbar_try(a, parity)) return;
#pragma unroll 1
  for (int n = 0; n < SPIN_LIMIT; n++)
    if (mbar_try(a, parity)) break;
}
__device__ __forceinline__ bool elect_one() {
  uint32_t p;
  asm volatile("{\n.reg .pred P;\nelect.sync _|P, 0xffffffff;\nselp.u32 %0, 1, 0, P;\n}\n" : "=r"(p));
  return p;
}
__device__ __forceinline__ uint32_t mapa(uint32_t a, uint32_t rank) {
  uint32_t r;
  asm volatile("mapa.shared::cluster.u32 %0, %1, %2;\n" : "=r"(r) : "r"(a), "r"(rank));
  return r;
}
__device__ __forceinline__ void nb_sync(int id, int n) { asm volatile("bar.sync %0, %1;\n" ::"r"(id), "r"(n) : "memory"); }
__device__ __forceinline__ void nb_arrive(int id, int n) { asm volatile("bar.arrive %0, %1;\n" ::"r"(id), "r"(n) : "memory"); }
__device__ __forceinline__ void cluster_sync_all() {
  asm volatile("barrier.cluster.arrive.relaxed.aligned;\nbarrier.cluster.wait.aligned;\n" ::: "memory");
}
__device__ __forceinline__ void fence_async_smem() { asm volatile("fence.proxy.async.shared::cta;\n" ::: "memory"); }
__device__ __forceinline__ void fence_async_all() { asm volatile("fence.proxy.async.global;\n" ::: "memory"); }

__device__ __forceinline__ void tma_load_3d(uint32_t dst, const CUtensorMap* tm, uint32_t bar, int c0, int c1, int c2) {
  asm volatile(
      "cp.async.bulk.tensor.3d.shared::cluster.global.mbarrier::complete_tx::bytes [%0], [%1, {%3, %4, %5}], [%2];\n"
      ::"r"(dst), "l"(tm), "r"(bar), "r"(c0), "r"(c1), "r"(c2) : "memory");
}
__device__ __forceinline__ void tma_load_4d(uint32_t dst, const CUtensorMap* tm, uint32_t bar, int c0, int c1, int c2, int c3) {
  asm volatile(
      "cp.async.bulk.tensor.4d.shared::cluster.global.mbarrier::complete_tx::bytes [%0], [%1, {%3, %4, %5, %6}], [%2];\n"
      ::"r"(dst), "l"(tm), "r"(bar), "r"(c0), "r"(c1), "r"(c2), "r"(c3) : "memory");
}
__device__ __forceinline__ void tma_load_3d_mc(uint32_t dst, const CUtensorMap* tm, uint32_t bar, int c0, int c1, int c2) {
  asm volatile(
      "cp.async.bulk.tensor.3d.shared::cluster.global.mbarrier::complete_tx::bytes.multicast::cluster [%0], [%1, {%3, %4, %5}], [%2], %6;\n"
      ::"r"(dst), "l"(tm), "r"(bar), "r"(c0), "r"(c1), "r"(c2), "h"((uint16_t)3) : "memory");
}
__device__ __forceinline__ void bulk_load(uint32_t dst, const void* src, uint32_t bytes, uint32_t bar) {
  asm volatile("cp.async.bulk.shared::cluster.global.mbarrier::complete_tx::bytes [%0], [%1], %2, [%3];\n"
               ::"r"(dst), "l"(src), "r"(bytes), "r"(bar) : "memory");
}
__device__ __forceinline__ void tma_store_3d(const CUtensorMap* tm, uint32_t src, int c0, int c1, int c2) {
  asm volatile("cp.async.bulk.tensor.3d.global.shared::cta.bulk_group [%0, {%2, %3, %4}], [%1];\n"
               ::"l"(tm), "r"(src), "r"(c0), "r"(c1), "r"(c2) : "memory");
}
__device__ __forceinline__ void bulk_commit() { asm volatile("cp.async.bulk.commit_group;\n" ::: "memory"); }
__device__ __forceinline__ void bulk_wait0() { asm volatile("cp.async.bulk.wait_group 0;\n" ::: "memory"); }
__device__ __forceinline__ void prefetch_tmap(const CUtensorMap* tm) {
  asm volatile("prefetch.tensormap [%0];\n" ::"l"(tm) : "memory");
}

__device__ __forceinline__ void wg_fence() { asm volatile("wgmma.fence.sync.aligned;\n" ::: "memory"); }
__device__ __forceinline__ void wg_commit() { asm volatile("wgmma.commit_group.sync.aligned;\n" ::: "memory"); }
template <int N> __device__ __forceinline__ void wg_wait() {
  asm volatile("wgmma.wait_group.sync.aligned %0;\n" ::"n"(N) : "memory");
}
__device__ __forceinline__ uint64_t mkdesc(uint32_t addr, uint32_t lbo, uint32_t sbo, uint32_t swz) {
  return (uint64_t)((addr & 0x3FFFF) >> 4) | ((uint64_t)(lbo >> 4) << 16) | ((uint64_t)(sbo >> 4) << 32) |
         ((uint64_t)swz << 62);
}

#define R4(d, o) "+f"(d[o + 0]), "+f"(d[o + 1]), "+f"(d[o + 2]), "+f"(d[o + 3])
#define R8(d, o) R4(d, o), R4(d, o + 4)
#define R16(d, o) R8(d, o), R8(d, o + 8)
#define R32(d, o) R16(d, o), R16(d, o + 16)
#define R64(d, o) R32(d, o), R32(d, o + 32)

__device__ __forceinline__ void wgmma_n192(float (&d)[96], uint64_t da, uint64_t db, uint32_t acc) {
  asm volatile(
      "{\n.reg .pred p;\nsetp.ne.u32 p, %98, 0;\n"
      "wgmma.mma_async.sync.aligned.m64n192k16.f32.bf16.bf16 "
      "{%0,%1,%2,%3,%4,%5,%6,%7,%8,%9,%10,%11,%12,%13,%14,%15,%16,%17,%18,%19,%20,%21,%22,%23,%24,%25,%26,%27,%28,%29,%30,%31,"
      "%32,%33,%34,%35,%36,%37,%38,%39,%40,%41,%42,%43,%44,%45,%46,%47,%48,%49,%50,%51,%52,%53,%54,%55,%56,%57,%58,%59,%60,%61,%62,%63,"
      "%64,%65,%66,%67,%68,%69,%70,%71,%72,%73,%74,%75,%76,%77,%78,%79,%80,%81,%82,%83,%84,%85,%86,%87,%88,%89,%90,%91,%92,%93,%94,%95}, "
      "%96, %97, p, 1, 1, 0, 1;\n}\n"
      : R64(d, 0), R32(d, 64)
      : "l"(da), "l"(db), "r"(acc));
}
__device__ __forceinline__ void wgmma_n128(float (&d)[64], uint64_t da, uint64_t db, uint32_t acc) {
  asm volatile(
      "{\n.reg .pred p;\nsetp.ne.u32 p, %66, 0;\n"
      "wgmma.mma_async.sync.aligned.m64n128k16.f32.bf16.bf16 "
      "{%0,%1,%2,%3,%4,%5,%6,%7,%8,%9,%10,%11,%12,%13,%14,%15,%16,%17,%18,%19,%20,%21,%22,%23,%24,%25,%26,%27,%28,%29,%30,%31,"
      "%32,%33,%34,%35,%36,%37,%38,%39,%40,%41,%42,%43,%44,%45,%46,%47,%48,%49,%50,%51,%52,%53,%54,%55,%56,%57,%58,%59,%60,%61,%62,%63}, "
      "%64, %65, p, 1, 1, 0, 1;\n}\n"
      : R64(d, 0)
      : "l"(da), "l"(db), "r"(acc));
}
template <int N> __device__ __forceinline__ void fence_regs(float (&d)[N]) {
#pragma unroll
  for (int i = 0; i < N; i++) asm volatile("" : "+f"(d[i])::"memory");
}

__device__ __forceinline__ void mma16816(float (&d)[4], uint32_t a0, uint32_t a1, uint32_t a2, uint32_t a3, uint32_t b0,
                                         uint32_t b1) {
  asm("mma.sync.aligned.m16n8k16.row.col.f32.bf16.bf16.f32 {%0,%1,%2,%3}, {%4,%5,%6,%7}, {%8,%9}, {%0,%1,%2,%3};\n"
      : "+f"(d[0]), "+f"(d[1]), "+f"(d[2]), "+f"(d[3])
      : "r"(a0), "r"(a1), "r"(a2), "r"(a3), "r"(b0), "r"(b1));
}
__device__ __forceinline__ void mma16816_z(float (&d)[4], uint32_t a0, uint32_t a1, uint32_t a2, uint32_t a3, uint32_t b0,
                                           uint32_t b1) {
  asm("mma.sync.aligned.m16n8k16.row.col.f32.bf16.bf16.f32 {%0,%1,%2,%3}, {%4,%5,%6,%7}, {%8,%9}, {%10,%10,%10,%10};\n"
      : "=f"(d[0]), "=f"(d[1]), "=f"(d[2]), "=f"(d[3])
      : "r"(a0), "r"(a1), "r"(a2), "r"(a3), "r"(b0), "r"(b1), "f"(0.f));
}
__device__ __forceinline__ void ldsm4t(uint32_t (&r)[4], uint32_t a) {
  asm volatile("ldmatrix.sync.aligned.m8n8.x4.trans.shared.b16 {%0,%1,%2,%3}, [%4];\n"
               : "=r"(r[0]), "=r"(r[1]), "=r"(r[2]), "=r"(r[3]) : "r"(a) : "memory");
}
__device__ __forceinline__ void ldsm2t(uint32_t& r0, uint32_t& r1, uint32_t a) {
  asm volatile("ldmatrix.sync.aligned.m8n8.x2.trans.shared.b16 {%0,%1}, [%2];\n" : "=r"(r0), "=r"(r1) : "r"(a) : "memory");
}
__device__ __forceinline__ void st_async128(uint32_t a, uint32_t bar, uint32_t x, uint32_t y, uint32_t z, uint32_t w) {
  asm volatile("st.async.weak.shared::cluster.mbarrier::complete_tx::bytes.v4.b32 [%0], {%2,%3,%4,%5}, [%1];\n"
               ::"r"(a), "r"(bar), "r"(x), "r"(y), "r"(z), "r"(w) : "memory");
}
__device__ __forceinline__ void mbar_arrive(uint32_t a) {
  asm volatile("mbarrier.arrive.shared::cta.b64 _, [%0];\n" ::"r"(a) : "memory");
}
__device__ __forceinline__ void stsm4(uint32_t a, uint32_t r0, uint32_t r1, uint32_t r2, uint32_t r3) {
  asm volatile("stmatrix.sync.aligned.m8n8.x4.shared.b16 [%0], {%1,%2,%3,%4};\n"
               ::"r"(a), "r"(r0), "r"(r1), "r"(r2), "r"(r3) : "memory");
}
__device__ __forceinline__ void stsm4t(uint32_t a, uint32_t r0, uint32_t r1, uint32_t r2, uint32_t r3) {
  asm volatile("stmatrix.sync.aligned.m8n8.x4.trans.shared.b16 [%0], {%1,%2,%3,%4};\n"
               ::"r"(a), "r"(r0), "r"(r1), "r"(r2), "r"(r3) : "memory");
}
__device__ __forceinline__ uint2 lds64(uint32_t a) {
  uint2 v;
  asm volatile("ld.shared.v2.u32 {%0,%1}, [%2];\n" : "=r"(v.x), "=r"(v.y) : "r"(a));
  return v;
}
__device__ __forceinline__ uint4 lds128(uint32_t a) {
  uint4 v;
  asm volatile("ld.shared.v4.u32 {%0,%1,%2,%3}, [%4];\n" : "=r"(v.x), "=r"(v.y), "=r"(v.z), "=r"(v.w) : "r"(a) : "memory");
  return v;
}
__device__ __forceinline__ void sts128(uint32_t a, uint32_t x, uint32_t y, uint32_t z, uint32_t w) {
  asm volatile("st.shared.v4.u32 [%0], {%1,%2,%3,%4};\n" ::"r"(a), "r"(x), "r"(y), "r"(z), "r"(w) : "memory");
}
__device__ __forceinline__ void sts64(uint32_t a, uint32_t x, uint32_t y) {
  asm volatile("st.shared.v2.u32 [%0], {%1,%2};\n" ::"r"(a), "r"(x), "r"(y) : "memory");
}
__device__ __forceinline__ uint32_t pack_bf16(float lo, float hi) {
  uint32_t r;
  asm("cvt.rn.bf16x2.f32 %0, %1, %2;\n" : "=r"(r) : "f"(hi), "f"(lo));
  return r;
}
__device__ __forceinline__ uint32_t bmul2(uint32_t a, uint32_t b) {
  uint32_t r;
  asm("mul.rn.bf16x2 %0, %1, %2;\n" : "=r"(r) : "r"(a), "r"(b));
  return r;
}
__device__ __forceinline__ uint32_t bmax2(uint32_t a, uint32_t b) {
  uint32_t r;
  asm("max.bf16x2 %0, %1, %2;\n" : "=r"(r) : "r"(a), "r"(b));
  return r;
}
__device__ __forceinline__ uint32_t bfma2(uint32_t a, uint32_t b, uint32_t c) {
  uint32_t r;
  asm("fma.rn.bf16x2 %0, %1, %2, %3;\n" : "=r"(r) : "r"(a), "r"(b), "r"(c));
  return r;
}
__device__ __forceinline__ uint32_t badd2(uint32_t a, uint32_t b) {
  uint32_t r;
  asm("add.rn.bf16x2 %0, %1, %2;\n" : "=r"(r) : "r"(a), "r"(b));
  return r;
}
__device__ __forceinline__ void prefetch_l2(const void* p) { asm volatile("prefetch.global.L2 [%0];\n" ::"l"(p)); }
__device__ __forceinline__ void cp_async16n(uint32_t dst, const void* src) {
  asm volatile("cp.async.cg.shared.global [%0], [%1], 16;\n" ::"r"(dst), "l"(src) : "memory");
}
__device__ __forceinline__ void cp_async16(uint32_t dst, const void* src, uint32_t srcbytes) {
  asm volatile("cp.async.cg.shared.global.L2::256B [%0], [%1], 16, %2;\n" ::"r"(dst), "l"(src), "r"(srcbytes) : "memory");
}
__device__ __forceinline__ uint32_t ld_acquire(const uint32_t* p) {
  uint32_t v;
  asm volatile("ld.acquire.gpu.global.u32 %0, [%1];\n" : "=r"(v) : "l"(p) : "memory");
  return v;
}
__device__ __forceinline__ uint32_t ld_relaxed(const uint32_t* p) {
  uint32_t v;
  asm volatile("ld.relaxed.gpu.global.u32 %0, [%1];\n" : "=r"(v) : "l"(p) : "memory");
  return v;
}
__device__ __forceinline__ void st_release(uint32_t* p, uint32_t v) {
  asm volatile("st.release.gpu.global.u32 [%0], %1;\n" ::"l"(p), "r"(v) : "memory");
}
__device__ __forceinline__ void wait_flag(const uint32_t* p, uint32_t want) {
  int n = 0;
  while (ld_relaxed(p) != want && ++n < SPIN_LIMIT) __nanosleep(40);
  (void)ld_acquire(p);
}

struct Params {
  const __nv_bfloat16* x;
  const __nv_bfloat16* w;
  const __nv_bfloat16* q;
  const __nv_bfloat16* k;
  const __nv_bfloat16* v;
  const __nv_bfloat16* shift_k;
  const __nv_bfloat16* ssm_k;
  const __nv_bfloat16* ssm_D;
  const __nv_bfloat16* wo;
  __nv_bfloat16* out;
  uint32_t zero;
};

__device__ __forceinline__ uint32_t lds32(uint32_t a) {
  uint32_t v;
  asm volatile("ld.shared.u32 %0, [%1];\n" : "=r"(v) : "r"(a));
  return v;
}
__device__ __forceinline__ float bf_lo(uint32_t v) {
  uint32_t r;
  asm("prmt.b32 %0, %1, 0, 0x1044;\n" : "=r"(r) : "r"(v));
  return __uint_as_float(r);
}
__device__ __forceinline__ float bf_hi(uint32_t v) { return __uint_as_float(v & 0xffff0000u); }
__device__ __forceinline__ float ex2(float x) {
  float r;
  asm("ex2.approx.ftz.f32 %0, %1;\n" : "=f"(r) : "f"(x));
  return r;
}
__device__ __forceinline__ float rcp(float x) {
  float r;
  asm("rcp.approx.ftz.f32 %0, %1;\n" : "=f"(r) : "f"(x));
  return r;
}

#define Q4(c, d, o) c(d[o + 0]), c(d[o + 1]), c(d[o + 2]), c(d[o + 3])
#define Q8(c, d, o) Q4(c, d, o), Q4(c, d, o + 4)
#define Q16(c, d, o) Q8(c, d, o), Q8(c, d, o + 8)
#define Q32(c, d) Q16(c, d, 0), Q16(c, d, 16)
#define L8 "{%0,%1,%2,%3,%4,%5,%6,%7}"
#define L16 "{%0,%1,%2,%3,%4,%5,%6,%7,%8,%9,%10,%11,%12,%13,%14,%15}"
#define L32 "{%0,%1,%2,%3,%4,%5,%6,%7,%8,%9,%10,%11,%12,%13,%14,%15,%16,%17,%18,%19,%20,%21,%22,%23,%24,%25,%26,%27,%28,%29,%30,%31}"
__device__ __forceinline__ void fft_rows(uint32_t (&d)[32], const uint32_t (&a)[2][4], uint64_t db) {
  asm volatile("wgmma.mma_async.sync.aligned.m64n128k16.f16.f16.f16 " L32 ", {%32,%33,%34,%35}, %36, 0, 1, 1, 1;\n"
               : Q32("=r", d) : "r"(a[0][0]), "r"(a[0][1]), "r"(a[0][2]), "r"(a[0][3]), "l"(db));
  asm volatile("wgmma.mma_async.sync.aligned.m64n128k16.f16.f16.f16 " L32 ", {%32,%33,%34,%35}, %36, 1, 1, 1, 1;\n"
               : Q32("+r", d) : "r"(a[1][0]), "r"(a[1][1]), "r"(a[1][2]), "r"(a[1][3]), "l"(db + 128));
}
template <int INV> __device__ __forceinline__ void fft_cols(uint32_t (&d)[8], const uint32_t (&a)[2][4], uint64_t db) {
  asm volatile("wgmma.mma_async.sync.aligned.m64n32k16.f16.f16.f16 " L8 ", {%8,%9,%10,%11}, %12, 0, 1, 1, %13;\n"
               : Q8("=r", d, 0) : "r"(a[0][0]), "r"(a[0][1]), "r"(a[0][2]), "r"(a[0][3]), "l"(db), "n"(INV));
  asm volatile("wgmma.mma_async.sync.aligned.m64n32k16.f16.f16.f16 " L8 ", {%8,%9,%10,%11}, %12, 1, 1, 1, %13;\n"
               : Q8("+r", d, 0) : "r"(a[1][0]), "r"(a[1][1]), "r"(a[1][2]), "r"(a[1][3]), "l"(db + (INV ? 16 : 64)), "n"(INV));
}
__device__ __forceinline__ void fft_back(float (&d)[16], uint64_t da, uint64_t db) {
  asm volatile("wgmma.mma_async.sync.aligned.m64n32k16.f32.f16.f16 " L16 ", %16, %17, 0, 1, 1, 1, 1;\n"
               : Q16("=f", d, 0) : "l"(da), "l"(db));
#pragma unroll
  for (int i = 1; i < 4; i++)
    asm volatile("wgmma.mma_async.sync.aligned.m64n32k16.f32.f16.f16 " L16 ", %16, %17, 1, 1, 1, 1, 1;\n"
                 : Q16("+f", d, 0) : "l"(da + 32 * i), "l"(db + 64 * i));
}
__device__ __forceinline__ uint32_t hmul2(uint32_t a, uint32_t b) {
  uint32_t r;
  asm("mul.rn.f16x2 %0, %1, %2;\n" : "=r"(r) : "r"(a), "r"(b));
  return r;
}
__device__ __forceinline__ uint32_t hadd2(uint32_t a, uint32_t b) {
  uint32_t r;
  asm("add.rn.f16x2 %0, %1, %2;\n" : "=r"(r) : "r"(a), "r"(b));
  return r;
}
__device__ __forceinline__ uint32_t hneg2(uint32_t a) {
  uint32_t r;
  asm("neg.f16x2 %0, %1;\n" : "=r"(r) : "r"(a));
  return r;
}
__device__ __forceinline__ uint32_t hfma2(uint32_t a, uint32_t b, uint32_t c) {
  uint32_t r;
  asm("fma.rn.f16x2 %0, %1, %2, %3;\n" : "=r"(r) : "r"(a), "r"(b), "r"(c));
  return r;
}
__device__ __forceinline__ uint32_t pack_f16(float lo, float hi) {
  uint32_t r;
  asm("cvt.rn.f16x2.f32 %0, %1, %2;\n" : "=r"(r) : "f"(hi), "f"(lo));
  return r;
}
__device__ __forceinline__ uint32_t bmaxabs2(uint32_t a, uint32_t b) {
  uint32_t r;
  asm("max.xorsign.abs.bf16x2 %0, %1, %2;\n" : "=r"(r) : "r"(a), "r"(b));
  return r;
}
struct C2 { uint32_t r, i; };
__device__ __forceinline__ C2 cmul(C2 a, C2 b) {
  return C2{hfma2(a.r, b.r, hneg2(hmul2(a.i, b.i))), hfma2(a.r, b.i, hmul2(a.i, b.r))};
}
__device__ __forceinline__ C2 cfma(C2 a, C2 b, C2 c) {
  return C2{hfma2(a.r, b.r, hfma2(hneg2(a.i), b.i, c.r)), hfma2(a.r, b.i, hfma2(a.i, b.r, c.i))};
}
__device__ __forceinline__ C2 crot(C2 z, C2 t) {
  const uint32_t r = hfma2(t.r, z.i, z.r), i = hfma2(t.i, r, z.i);
  return C2{hfma2(t.r, i, r), i};
}
__device__ __forceinline__ C2 cget(const uint32_t (&e)[8], int j, int b) { return C2{e[4 * j + b], e[4 * j + 2 + b]}; }
template <int N> __device__ __forceinline__ void fence_regs(uint32_t (&d)[N]) {
#pragma unroll
  for (int i = 0; i < N; i++) asm volatile("" : "+r"(d[i])::"memory");
}
__device__ __forceinline__ void ldsm4(uint32_t (&r)[4], uint32_t a) {
  asm volatile("ldmatrix.sync.aligned.m8n8.x4.shared.b16 {%0,%1,%2,%3}, [%4];\n"
               : "=r"(r[0]), "=r"(r[1]), "=r"(r[2]), "=r"(r[3]) : "r"(a) : "memory");
}

__device__ __forceinline__ uint32_t movm(uint32_t a) {
  uint32_t r;
  asm volatile("movmatrix.sync.aligned.m8n8.trans.b16 %0, %1;\n" : "=r"(r) : "r"(a));
  return r;
}
template <int C0, int H, bool T> __device__ __forceinline__ void attn_pack(const float (&acc)[96], uint32_t (&d)[8]) {
#pragma unroll
  for (int c = 0; c < 8; c++) {
    asm volatile("cvt.rn.bf16x2.f32 %0, %1, %2;\n" : "=r"(d[c]) : "f"(acc[4 * (C0 + c) + 2 * H + 1]), "f"(acc[4 * (C0 + c) + 2 * H]));
    if (T) d[c] = movm(d[c]);
  }
}
__device__ __forceinline__ void attn_qk(float (&s)[4], const uint32_t (&qlo)[8], const uint32_t (&qhi)[8],
                                        const uint32_t (&k)[8], int c) {
  mma16816_z(s, qlo[c], qhi[c], qlo[c + 1], qhi[c + 1], k[c], k[c + 1]);
  mma16816(s, qlo[c + 2], qhi[c + 2], qlo[c + 3], qhi[c + 3], k[c + 2], k[c + 3]);
}
template <int N> __device__ __forceinline__ void quad_softmax(float (&x)[N][2], uint32_t (&pp)[N]) {
  const float c2 = 1.4426950408889634f;
  uint32_t q[N], mx[N / 2];
#pragma unroll
  for (int n = 0; n < N; n++) {
    const uint32_t r = pack_bf16(x[n][0], x[n][1]);
    q[n] = bfma2(r, 0x3e353e35u, bmul2(r, 0x379e379eu));
    x[n][0] = bf_lo(q[n]);
    x[n][1] = bf_hi(q[n]);
  }
#pragma unroll
  for (int n = 0; n < N / 2; n++)
    mx[n] = bmax2(__byte_perm(q[2 * n], q[2 * n + 1], 0x5410), __byte_perm(q[2 * n], q[2 * n + 1], 0x7632));
#pragma unroll
  for (int o = 1; o <= 2; o++) {
#pragma unroll
    for (int n = 0; n < N / 2; n++) mx[n] = bmax2(mx[n], __shfl_xor_sync(0xffffffffu, mx[n], o));
  }
  float m[N], t[N];
#pragma unroll
  for (int n = 0; n < N / 2; n++) {
    m[2 * n] = bf_lo(mx[n]);
    m[2 * n + 1] = bf_hi(mx[n]);
  }
#pragma unroll
  for (int n = 0; n < N; n++) {
    const float nm = -m[n] * c2;
    x[n][0] = ex2(fmaf(x[n][0], c2, nm));
    x[n][1] = ex2(fmaf(x[n][1], c2, nm));
  }
#pragma unroll
  for (int n = 0; n < N; n += 2) {
    float u0, u1;
    asm("mma.sync.aligned.m16n8k8.row.col.f32.tf32.tf32.f32 {%0,%1,%2,%3}, {%4,%5,%6,%7}, {%8,%8}, {%9,%9,%9,%9};\n"
        : "=f"(t[n]), "=f"(u0), "=f"(t[n + 1]), "=f"(u1)
        : "r"(__float_as_uint(x[n][0])), "r"(__float_as_uint(x[n + 1][0])), "r"(__float_as_uint(x[n][1])),
          "r"(__float_as_uint(x[n + 1][1])), "r"(0x3f800000u), "f"(0.f));
  }
#pragma unroll
  for (int n = 0; n < N; n++) {
    const float inv = rcp(t[n]);
    pp[n] = pack_bf16(x[n][0] * inv, x[n][1] * inv);
  }
}
__device__ __forceinline__ void attn_pv(uint32_t dst, const uint32_t (&vp)[8], const uint32_t (&vo)[8], int c, uint32_t pp,
                                        uint32_t maskLE) {
  const uint32_t b0 = pp & ~maskLE, b1 = pp & maskLE;
  float oa[4], ob[4];
  mma16816_z(oa, vp[c], vp[c + 1], vo[c], vo[c + 1], b0, b1);
  mma16816_z(ob, vp[c + 2], vp[c + 3], vo[c + 2], vo[c + 3], b0, b1);
  stsm4t(dst, pack_bf16(oa[0], oa[1]), pack_bf16(oa[2], oa[3]), pack_bf16(ob[0], ob[1]), pack_bf16(ob[2], ob[3]));
}

template <int MODE>
__global__ void __cluster_dims__(2, 1, 1) __launch_bounds__(NTHREADS, 1)
fused_kernel(const Params p, const __grid_constant__ CUtensorMap tmX, const __grid_constant__ CUtensorMap tmW,
             const __grid_constant__ CUtensorMap tmWo, const __grid_constant__ CUtensorMap tmQ,
             const __grid_constant__ CUtensorMap tmOb,
             const __grid_constant__ CUtensorMap tmXh, const __grid_constant__ CUtensorMap tmWh) {
  extern __shared__ __align__(1024) uint8_t smem[];
  if (threadIdx.x < 32) {
    const uint32_t i = (blockIdx.x & 127) * 16 + (threadIdx.x & 15);
    prefetch_l2(threadIdx.x & 16 ? (const char*)p.w + i * 128 : (const char*)p.x + i * 2048);
  }
  const uint32_t sb = smem_u32(smem);
  const uint32_t bars = sb + OFF_BAR;
  const int tid = threadIdx.x, lane = tid & 31, warp = __shfl_sync(0xffffffffu, tid >> 5, 0);
  const int rank = blockIdx.x & 1;
  const bool halo_cta = blockIdx.x < 4;
  if (halo_cta && MODE != 0) return;
  int grp, mem;
  {
    const int t = (blockIdx.x >> 1) - 4, u = t - 32;
    const int q7 = (u * 37) >> 8;
    const bool lo = (unsigned)t < 32u, mid = (unsigned)u < 28u;
    grp = lo ? (t & 7) : (mid ? 1 + u - 7 * q7 : 0);
    mem = lo ? (t >> 3) : (mid ? 4 + q7 : (t < 0 ? t + 6 : t - 54));
  }
  const int rg = (grp >> 2) * 4 + (mem >> 1), hp = (grp & 3) * 4 + (mem & 1) * 2 + rank;
  const int rb2 = (grp >> 2) * 8 + mem, cb2 = (grp & 3) * 2 + rank;
  const int chb = grp * 16 + mem * 2 + rank;
  const int cta = rg * 16 + hp;
#define G2WG 1
  const int g2wg = G2WG, hsel = rb2 & 1;
  const int par = rg >> 2, gidx = rg & 3;

  if (tid < 256 && !halo_cta && MODE != 2) {
    const int r = tid >> 3, c = tid & 7;
    const uint32_t so = r * 128 + ((c ^ (r & 7)) << 4);
    const __nv_bfloat16* wg0 = p.w + (size_t)r * (3 * DM) + hp * 64 + c * 8;
    const __nv_bfloat16* xg0 = p.x + (size_t)(2 * (gidx * 256 + r) + par) * DM + c * 8;
#pragma unroll
    for (int j = 0; j < 3; j++) cp_async16n(sb + OFF_1B + j * 4096 + so, wg0 + j * DM);
#pragma unroll
    for (int i = 0; i < 8; i++) cp_async16n(sb + i * 4096 + so, xg0 + (size_t)i * 64 * DM);
    asm volatile("cp.async.commit_group;\n" ::: "memory");
  }
  auto halo_issue = [&](int kb, int s) {
    const uint32_t fb = bars + 8 * (BAR_FULLB + s), st = sb + s * STGH;
    mbar_expect_tx(fb, STGH - 2048);
    tma_load_3d(st + 8192, &tmWh, fb, 0, kb * 64, 16 + blockIdx.x * 4);
    tma_load_3d(st + 8192 + 32768, &tmWh, fb, 0, kb * 64, 32 + blockIdx.x * 4);
    tma_load_4d(st, &tmXh, fb, kb * 64, 248, 0, 0);
  };
  if (tid == 256) {
    prefetch_tmap(halo_cta ? &tmXh : &tmX);
#pragma unroll
    for (int i = 0; i < NS1B; i++) mbar_init(bars + 8 * (BAR_FULLB + i), 1);
#pragma unroll
    for (int i = 0; i < NS1A; i++) mbar_init(bars + 8 * (BAR_FULLA + i), 1);
    asm volatile("fence.mbarrier_init.release.cluster;\n" ::: "memory");
    if (!halo_cta && MODE != 2) {
      mbar_expect_tx(bars + 8 * (BAR_FULLB + 1), STG1B);
      tma_load_3d(sb + OFF_1B + 1 * STG1B, &tmW, bars + 8 * (BAR_FULLB + 1), hp * 64, 32, 0);
      mbar_expect_tx(bars + 8 * (BAR_FULLB + 2), STG1B);
      tma_load_3d(sb + OFF_1B + 2 * STG1B, &tmW, bars + 8 * (BAR_FULLB + 2), hp * 64, 64, 0);
    } else if (halo_cta) {
      halo_issue(0, 0);
    }
  } else if (tid == 288) {
#pragma unroll
    for (int i = 0; i < NS1A; i++) mbar_init(bars + 8 * (BAR_EMPTYA + i), 4);
#pragma unroll
    for (int i = 0; i < NS1B; i++) mbar_init(bars + 8 * (BAR_EMPTYB + i), 2);
    mbar_init(bars + 8 * BAR_X, 4);
    mbar_init(bars + 8 * BAR_LAND, 17);
    mbar_init(bars + 8 * BAR_TAB, 16);
    mbar_init(bars + 8 * BAR_U, 1);
    mbar_init(bars + 8 * BAR_H, 1);
    mbar_init(bars + 8 * BAR_STG, 8);
    mbar_init(bars + 8 * BAR_HALO, 1);
    mbar_init(bars + 8 * BAR_Q, 1);
    mbar_init(bars + 8 * BAR_QFREE, 4);
    mbar_init(bars + 8 * (BAR_QFREE + 1), 4);
    asm volatile("fence.mbarrier_init.release.cluster;\n" ::: "memory");
  } else if (tid == 320) {
#pragma unroll
    for (int i = 0; i < NS2; i++) {
      mbar_init(bars + 8 * (BAR_FULL2 + i), 1);
      mbar_init(bars + 8 * (BAR_EMPTY2 + i), 2);
    }
    asm volatile("fence.mbarrier_init.release.cluster;\n" ::: "memory");
  } else if (tid == 352) {
#pragma unroll
    for (int i = 0; i < 8; i++) mbar_init(bars + 8 * (BAR_Y + i), 4);
    asm volatile("fence.mbarrier_init.release.cluster;\n" ::: "memory");
  }
  if (warp == 8) PROF2(23);
  cluster_sync_all();
  if (warp == 8) PROF2(24);

  if (warp >= 8) {
    const int hw = warp - 8;
    const int lr = lane & 7, lm = lane >> 3;
    auto g1_issue_a = [&](int j, int s) {
      const uint32_t fb = bars + 8 * (BAR_FULLA + s);
      mbar_expect_tx(fb, STG1A);
      tma_load_3d_mc(sb + s * STG1A + rank * 16384, &tmX, fb, j * 64, par, gidx * 256 + rank * 128);
    };
    auto g1_issue_b = [&](int kb, int s) {
      const uint32_t fb = bars + 8 * (BAR_FULLB + s);
      mbar_expect_tx(fb, STG1B);
      tma_load_3d(sb + OFF_1B + s * STG1B, &tmW, fb, hp * 64, kb * 32, 0);
    };
    asm volatile("setmaxnreg.dec.sync.aligned.u32 %0;\n" :: "n"(REG_HELP));

    if (halo_cta) {
      if (hw == 0) {
        int s = 1, ph = 1;
#pragma unroll 1
        for (int kb = 1; kb < 16; kb++) {
          mbar_wait(bars + 8 * (BAR_EMPTYB + s), ph);
          if (elect_one()) halo_issue(kb, s);
          if (++s == 3) { s = 0; ph ^= 1; }
        }
      }
      __syncwarp();
    } else if (hw == 0) {
      auto g2_k = [&](int kb) { return kb < 2 ? hp ^ kb : kb < 4 ? (hp & 14) ^ kb : ((hp & 12) + kb) & 15; };
      auto g2_issue_b = [&](int kb, int s, uint32_t bytes) {
        mbar_expect_tx(bars + 8 * (BAR_FULL2 + s), bytes);
        tma_load_3d(sb + g2_b(s), &tmWo, bars + 8 * (BAR_FULL2 + s), 0, g2_k(kb) * 64, cb2 * 2);
      };
      uint32_t epoch = 0;
      if (MODE == 2) {
        if (lane < NS2) mbar_arrive_cluster_n(mapa(bars, rank) + 8 * (BAR_EMPTY2 + lane), 2);
      } else {
      if (lane == 0) {
        mbar_expect_tx(bars + 8 * BAR_U, 32768);
        mbar_expect_tx(bars + 8 * BAR_LAND, 16384);
        mbar_expect_tx(bars + 8 * BAR_Q, 32768);
        prefetch_tmap(&tmQ);
      }
      {
        int sa = 1, pha = 1, sbb = 2, phb = 1;
#pragma unroll 1
        for (int kb = 2; kb < 32; kb++) {
          if (!(kb & 1)) {
            mbar_wait(bars + 8 * (BAR_EMPTYA + sa), pha);
            if (elect_one()) g1_issue_a(kb >> 1, sa);
            if (++sa == NS1A) { sa = 0; pha ^= 1; }
          }
          mbar_wait(bars + 8 * (BAR_EMPTYB + sbb), phb);
          if (kb > 2 && elect_one()) g1_issue_b(kb, sbb);
          __syncwarp();
          if (kb == 4) epoch = ld_relaxed(g_flag_o + cta);
          if (kb == 4) PROF2(27);
          if (kb == 1) PROF2(38);
          if (kb == 2) PROF2(39);
          if (++sbb == NS1B) { sbb = 0; phb ^= 1; }
        }
#pragma unroll 1
        for (int i = 0; i < 2; i++) {
          mbar_wait(bars + 8 * (i ? BAR_EMPTYB + 3 : BAR_EMPTYA + 1), i ? phb : pha);
          if (elect_one())
            asm volatile(
                "cp.async.bulk.tensor.5d.shared::cluster.global.mbarrier::complete_tx::bytes [%0], [%1, {%3, %4, %4, %4, %5}], [%2];\n"
                ::"r"(sb + g2_b(3 + i)), "l"(&tmQ), "r"(bars + 8 * BAR_Q), "r"((chb & ~1) * 8), "r"(0), "r"(rank * 64 + i * 32)
                : "memory");
          __syncwarp();
        }
      }
      epoch++;
      if (lane == 0) {
        prefetch_tmap(&tmWo);
        prefetch_tmap(&tmOb);
        if (gidx != 0) wait_flag(g_flag_h + (hp >> 2), epoch);
      }
      __syncwarp();
      {
        uint4 hk0 = make_uint4(0, 0, 0, 0), hk1 = hk0, hv0 = hk0, hv1 = hk0;
        if (gidx != 0) {
          const uint4* src = g_halo + cta * 128 + lane;
          hk0 = __ldcg(src); hk1 = __ldcg(src + 32); hv0 = __ldcg(src + 64); hv1 = __ldcg(src + 96);
        }
        if (gidx != 0) PROF(18);
        sts128(sb + OFF_L0 + lane * 16, hk0.x, hk0.y, hk0.z, hk0.w);
        sts128(sb + OFF_L0 + 512 + lane * 16, hk1.x, hk1.y, hk1.z, hk1.w);
        sts64(sb + OFF_L0 + 1024 + lane * 8, movm(hv0.x), movm(hv0.y));
        sts64(sb + OFF_L0 + 1280 + lane * 8, movm(hv0.z), movm(hv0.w));
        sts64(sb + OFF_L0 + 1536 + lane * 8, movm(hv1.x), movm(hv1.y));
        sts64(sb + OFF_L0 + 1792 + lane * 8, movm(hv1.z), movm(hv1.w));
        __syncwarp();
        if (lane == 0) mbar_arrive(bars + 8 * BAR_HALO);
      }
      nb_sync(NB_G1DONE, 288);
      if (elect_one()) {
        mbar_expect_tx(bars + 8 * BAR_X, 8192);
        bulk_load(sb + OFF_TAB, g_tab, 8192, bars + 8 * BAR_X);
      }
      const uint32_t rb = mapa(bars, lane & 1);
      nb_sync(NB_OREADY, 288);
      if (lane == 0) {
        asm volatile("cp.async.bulk.global.shared::cta.bulk_group [%0], [%1], %2;\n" ::"l"(g_o + (size_t)cta * 16384),
                     "r"(sb + OFF_OP), "r"(32768) : "memory");
        bulk_commit();
      }
      if (lane < 2) {
#pragma unroll
        for (int i = 0; i < 4; i++) mbar_arrive_cluster(rb + 8 * (BAR_EMPTY2 + i + i / 2));
      }
      if (lane == 0) {
        bulk_wait0();
        st_release(g_flag_o + cta, epoch);
      }
      __syncwarp();
      PROF2(17);
      if (lane < 2) mbar_arrive_cluster(rb + 8 * (BAR_EMPTY2 + 2));
      }
      if (MODE != 1) {
        const __nv_bfloat16* osrc = g_o + (size_t)(rb2 >> 1) * 16 * 16384 + hsel * 8192;
        mbar_wait(bars + 8 * (BAR_EMPTY2 + 1), 0);
        if (elect_one()) {
          if (MODE == 0) {
            asm volatile("cp.async.bulk.shared::cluster.shared::cta.mbarrier::complete_tx::bytes [%0], [%1], %2, [%3];\n"
                         ::"r"(mapa(sb + g2_a(1, hsel), rank ^ 1)), "r"(sb + g2_a(0, hsel)), "r"(16384),
                         "r"(mapa(bars + 8 * (BAR_FULL2 + 1), rank ^ 1)) : "memory");
          } else {
            bulk_load(sb + g2_a(0, hsel), osrc + hp * 16384, 16384, bars + 8 * BAR_FULL2);
            bulk_load(sb + g2_a(1, hsel), osrc + (hp ^ 1) * 16384, 16384, bars + 8 * (BAR_FULL2 + 1));
          }
#pragma unroll 1
          for (int kb = 0; kb < 3; kb++) g2_issue_b(kb, kb, kb || MODE ? STG2 : STG2 / 2);
        }
        __syncwarp();
        uint32_t ready = MODE == 0 ? 0u : ~0u;
        int s = 2, ph = 0;
#pragma unroll 1
        for (int kb = 2; kb < 16; kb++) {
          const int k = g2_k(kb);
          if (!(ready >> k & 1)) {
            for (int n = 0; n < SPIN_LIMIT && !(ready >> k & 1); n++)
              ready = __ballot_sync(0xffffffffu, ld_acquire(g_flag_o + (rb2 >> 1) * 16 + (lane & 15)) == epoch);
            fence_async_all();
          }
          if (kb == 2) PROF(21);
          mbar_wait(bars + 8 * (BAR_EMPTY2 + s), ph);
          if (MODE == 0 && kb == 4 && rank == 1) mbar_wait(bars + 8 * BAR_TAB, 0);
          if (elect_one()) {
            asm volatile(
                "cp.async.bulk.shared::cluster.global.mbarrier::complete_tx::bytes.multicast::cluster [%0], [%1], %2, [%3], %4;\n"
                ::"r"(sb + g2_a(s, hsel) + rank * 8192), "l"(osrc + k * 16384 + rank * 4096), "r"(8192),
                "r"(bars + 8 * (BAR_FULL2 + s)), "h"((uint16_t)3) : "memory");
          }
          if (MODE == 0 && (kb == 3 || kb == 4)) mbar_wait(bars + 8 * (BAR_QFREE + kb - 3), 0);
          if (kb >= 3 && elect_one()) g2_issue_b(kb, s, STG2);
          __syncwarp();
          if (++s == NS2) { s = 0; ph ^= 1; }
        }
      }
      __syncwarp();
    } else if (MODE != 2) {
      {
        const int g = lane >> 2, t = lane & 3;
        uint32_t w[2][4];
#pragma unroll
        for (int h = 0; h < 2; h++) {
          const uint2 x = __ldg(reinterpret_cast<const uint2*>(p.shift_k + ((chb & ~1) * 8 + h * 8 + g) * 4));
          w[h][0] = __byte_perm(x.x, x.x, 0x1010);
          w[h][1] = __byte_perm(x.x, x.x, 0x3232);
          w[h][2] = __byte_perm(x.y, x.y, 0x1010);
          w[h][3] = __byte_perm(x.y, x.y, 0x3232);
        }
        auto swz = [](int r) { return (((r & 29) | ((r ^ (r >> 2)) & 2)) << 5) | (r & 16); };
        const uint32_t kring = sb + OFF_X + 4096 + (hw - 1) * 2 * XT, vring = kring + XT;
        const int s0 = rank * 32 + (hw - 1) * 11, s1 = hw == 3 ? rank * 32 + 32 : s0 + 11;
        const size_t goff = (size_t)(lane >> 1) * DM + (chb & ~1) * 8 + (lane & 1) * 8;
        const __nv_bfloat16* kg = p.k + goff;
        const __nv_bfloat16* vg = p.v + goff;
        const uint32_t d0 = swz(lane >> 1) ^ ((lane & 1) << 4), d1 = swz(16 + (lane >> 1)) ^ ((lane & 1) << 4);
        auto issue = [&](int st) {
          const uint32_t so = (st & 3) << 10;
          cp_async16(kring + so + d0, kg + (size_t)st * 32 * DM, 16);
          cp_async16(kring + so + d1, kg + (size_t)(st * 32 + 16) * DM, 16);
          cp_async16(vring + so + d0, vg + (size_t)st * 32 * DM, 16);
          cp_async16(vring + so + d1, vg + (size_t)(st * 32 + 16) * DM, 16);
        };
        const int xa = 8 * (lr >> 1) + 2 * lm + (lr & 1), xb = 8 * (lr >> 1) - 4 + 2 * (lm & 1) + (lr & 1);
        const uint32_t la = swz(xa), lb = swz(xb & 31);
        const int backb = xb < 0 ? 1 : 0;
        const uint32_t ud[2] = {mapa(sb + OFF_X + g * XT + t * 16, 0), mapa(sb + OFF_X + g * XT + t * 16, 1)};
        const uint32_t ub[2] = {mapa(bars + 8 * BAR_U, 0), mapa(bars + 8 * BAR_U, 1)};
        if (lane == 0) mbar_wait(bars + 8 * (BAR_FULLB + NS1B - 1), 0);
        __syncwarp();
        if (lane >= 24) cp_async16(kring + (((s0 - 1) & 3) << 10) + d1, s0 > 0 ? kg + (size_t)(s0 * 32 - 16) * DM : kg, s0 > 0 ? 16 : 0);
        issue(s0);
        asm volatile("cp.async.commit_group;\n" ::: "memory");
        issue(s0 + 1);
        asm volatile("cp.async.commit_group;\n" ::: "memory");
#pragma unroll 1
        for (int st = s0; st < s1; st++) {
          if (st + 2 < s1) issue(st + 2);
          if (hw == 1 && st - s0 < 8) prefetch_l2(p.ssm_k + (size_t)(chb * 8 + st - s0) * SEQ + lane * 64);
          asm volatile("cp.async.commit_group;\n" ::: "memory");
          asm volatile("cp.async.wait_group 2;\n" ::: "memory");
          __syncwarp();
#pragma unroll
          for (int h = 0; h < 2; h++) {
            uint32_t e[6], vv[4], e4[4];
            ldsm4t(e4, kring + ((st & 3) << 10) + (la ^ (h << 4)));
            ldsm2t(e[0], e[1], kring + (((st - backb) & 3) << 10) + (lb ^ (h << 4)));
            ldsm4t(vv, vring + ((st & 3) << 10) + (la ^ (h << 4)));
            e[2] = e4[0]; e[3] = e4[1]; e[4] = e4[2]; e[5] = e4[3];
            uint32_t o[5];
#pragma unroll
            for (int i = 0; i < 5; i++) o[i] = __byte_perm(e[i], e[i + 1], 0x5432);
#pragma unroll
            for (int i = 0; i < 4; i++) {
              uint32_t a = bmul2(o[i], w[h][3]);
              a = bfma2(e[i + 1], w[h][2], a);
              a = bfma2(o[i + 1], w[h][1], a);
              a = bfma2(e[i + 2], w[h][0], a);
              vv[i] = bmul2(a, vv[i]);
            }
            st_async128(ud[h] + (st ^ (g & 1)) * 64, ub[h], vv[0], vv[1], vv[2], vv[3]);
          }
          __syncwarp();
        }
        fence_async_smem();
        PROF(16);
      }
      nb_sync(NB_HELP3, 96);
      if (hw == 1 && elect_one()) {
        mbar_expect_tx(bars + 8 * BAR_H, 8 * 4096);
#pragma unroll 1
        for (int c = 0; c < 8; c++)
          bulk_load(sb + OFF_X + c * XT + 4096, p.ssm_k + (size_t)(chb * 8 + c) * SEQ, 4096, bars + 8 * BAR_H);
      }
      __syncwarp();
      {
        const int ck = 16 * (lane >> 4) + 2 * lr + (((lane >> 3) ^ (lane >> 2)) & 1);
        const uint32_t xo = (ck >> 1) * 128, xs = ((ck & 1) ^ lr) << 4;
#pragma unroll 1
        for (int job = hw - 1; job < 16; job += 3) {
          const int c = job & 7;
          uint4 a[8];
          float dv = 0.f;
          if (job >= 8 && lane == 0) dv = __bfloat162float(p.ssm_D[chb * 8 + c]);
          if (job < 8) prefetch_l2(p.q + (size_t)chb * 16384 + c * 2048 + lane * 64);
          else if (lane < 16) prefetch_l2(p.wo + (size_t)chb * 8192 + c * 1024 + lane * 64);
          const uint32_t xt = sb + OFF_X + c * XT + (job >> 3) * 4096;
          mbar_wait(bars + 8 * (job < 8 ? BAR_U : BAR_H), 0);
#pragma unroll
          for (int i = 0; i < 8; i++) a[i] = lds128(xt + i * 512 + ((ck ^ (job < 8 ? (c & 1) << 2 : 0)) << 4));
          uint32_t m = pack_bf16(bf_lo(a[0].x) + dv, 0.f);
#pragma unroll
          for (int i = 0; i < 8; i++) m = bmaxabs2(bmaxabs2(m, bmaxabs2(a[i].x, a[i].y)), bmaxabs2(a[i].z, a[i].w));
          m = __reduce_max_sync(0xffffffffu, max(m & 0x7fffu, (m >> 16) & 0x7fffu));
          const uint32_t f = max(252 - (int)(m >> 7), 1), mul = f * 0x00800080u;
          if (lane == 0) asm volatile("st.shared.u32 [%0], %1;\n" ::"r"(sb + OFF_EX + job * 4), "r"(f) : "memory");
          auto cv = [&](uint32_t x) {
            x = bmul2(x, mul);
            return pack_f16(bf_lo(x), bf_hi(x));
          };
          const uint32_t x0 = bmul2(a[0].x, mul);
          const uint32_t dst = xt + xo;
#pragma unroll
          for (int i = 0; i < 8; i++)
            sts128(dst + (i & 1) * 2048 + (xs ^ ((i >> 1) << 5)),
                   i ? cv(a[i].x) : pack_f16(fmaf(dv, __uint_as_float(f << 23), bf_lo(x0)), bf_hi(x0)), cv(a[i].y), cv(a[i].z),
                   cv(a[i].w));
        }
        fence_async_smem();
        __syncwarp();
        if (lane == 0) mbar_arrive(bars + 8 * BAR_X);
        PROF(19);
      }
      if (hw < 3) {
        const uint32_t peer = mapa(sb, rank ^ 1);
#pragma unroll 1
        for (int ch = hw * 4 - 4; ch < hw * 4; ch++) {
          const uint32_t o = OFF_X + ch * XT + (rank ^ 1) * 4096;
          uint4 a[4];
          mbar_wait(bars + 8 * (BAR_Y + ch), 0);
#pragma unroll
          for (int i = 0; i < 4; i++) a[i] = lds128(sb + o + (i >> 1) * 2048 + (i & 1) * 512 + lane * 16);
#pragma unroll
          for (int i = 0; i < 4; i++)
            st_async128(peer + o + 1024 + (i >> 1) * 2048 + (i & 1) * 512 + lane * 16, peer + OFF_BAR + 8 * BAR_LAND, a[i].x,
                        a[i].y, a[i].z, a[i].w);
        }
      }
      PROF(32);
    }
    cluster_sync_all();
  } else {
    asm volatile("setmaxnreg.inc.sync.aligned.u32 %0;\n" :: "n"(REG_MATH));
    if (warp == 0) PROF2(26);
    const int wg = warp >> 2;
    const int wtid = tid & 127;
    const bool signaller = (wtid == 0) || (wtid == 32);
    const uint32_t rbars = mapa(bars, wtid >> 5 & 1);

    if (halo_cta) {
      const uint32_t epoch = ld_relaxed(g_flag_h + blockIdx.x) + 1;
      float acc0[64], acc1[64];
      int s = 0, ph = 0;
#pragma unroll 1
      for (int kb = 0; kb < 16; kb++) {
        mbar_wait(bars + 8 * (BAR_FULLB + s), ph);
        const uint32_t st = sb + s * STGH;
        const uint64_t da = mkdesc(st, 16, 1024, 1);
        const uint64_t db = mkdesc(st + 8192 + wg * 32768, 8192, 1024, 1);
        wg_fence();
#pragma unroll
        for (int kk = 0; kk < 4; kk++) {
          wgmma_n128(acc0, da + 2 * kk, db + 128 * kk, kb + kk);
          wgmma_n128(acc1, da + 2 * kk, db + 1024 + 128 * kk, kb + kk);
        }
        wg_commit();
        wg_wait<0>();
        if (kb == 15) PROF(37);
        if (wtid == 0) mbar_arrive(bars + 8 * (BAR_EMPTYB + s));
        if (++s == 3) { s = 0; ph ^= 1; }
      }
      fence_regs(acc0);
      fence_regs(acc1);
      if ((warp & 3) != 3) {
#pragma unroll
        for (int hh = 0; hh < 2; hh++) {
          uint4* dst = g_halo + ((hh * 4 + (warp & 3) + 1) * 16 + blockIdx.x * 4) * 128 + wg * 64 + lane;
#pragma unroll
          for (int j = 0; j < 4; j++) {
            const int o = 16 * j + 2 * hh;
            dst[(j >> 1) * 128 + (j & 1) * 32] =
                make_uint4(pack_bf16(acc0[o], acc0[o + 1]), pack_bf16(acc0[o + 4], acc0[o + 5]),
                           pack_bf16(acc0[o + 8], acc0[o + 9]), pack_bf16(acc0[o + 12], acc0[o + 13]));
            dst[(2 + (j >> 1)) * 128 + (j & 1) * 32] =
                make_uint4(pack_bf16(acc1[o], acc1[o + 1]), pack_bf16(acc1[o + 4], acc1[o + 5]),
                           pack_bf16(acc1[o + 8], acc1[o + 9]), pack_bf16(acc1[o + 12], acc1[o + 13]));
          }
        }
      }
      nb_sync(NB_G1DONE, 256);
      if (tid == 0) st_release(g_flag_h + blockIdx.x, epoch);
      PROF(36);
      cluster_sync_all();
      return;
    }

    if (MODE != 2) {
    uint32_t a1[2][4], sc[4];
    C2 t[2];
    {
      float acc0[96], acc1[96];
      int sa = 0, pha = 0, sbb = 0, phb = 0;
      asm volatile("cp.async.wait_group 0;\n" ::: "memory");
      fence_async_smem();
      nb_sync(NB_FIRST, 256);
      if (tid == 0) {
        mbar_arrive(bars + 8 * BAR_FULLA);
        mbar_arrive(bars + 8 * BAR_FULLB);
      }
      PROF(0 + wg);
#pragma unroll 1
      for (int kb = 0; kb < 30; kb++) {
        if (!(kb & 1)) mbar_wait(bars + 8 * (BAR_FULLA + sa), pha);
        mbar_wait(bars + 8 * (BAR_FULLB + sbb), phb);
        if (kb == 0) PROF2(0 + wg);
        if (kb == 4 && wg == 0) PROF2(28);
        if (kb == 8 && wg == 0) PROF2(29);
        if (kb == 16 && wg == 0) PROF2(30);
        const uint64_t da = mkdesc(sb + sa * STG1A + wg * 16384 + (kb & 1) * 64, 16, 2048, 1);
        const uint64_t db = mkdesc(sb + OFF_1B + sbb * STG1B, 4096, 1024, 1);
        wg_fence();
        wgmma_n192(acc0, da + 64, db, kb);
        wgmma_n192(acc1, da, db, kb);
        wgmma_n192(acc0, da + 66, db + 128, 1);
        wgmma_n192(acc1, da + 2, db + 128, 1);
        wg_commit();
        wg_wait<1>();
        if (kb > 0) {
          if (wtid == 64) mbar_arrive(bars + 8 * (BAR_EMPTYB + (sbb == 0 ? NS1B - 1 : sbb - 1)));
          if (!(kb & 1) && signaller) mbar_arrive_cluster(rbars + 8 * (BAR_EMPTYA + (sa == 0 ? NS1A - 1 : sa - 1)));
        }
        if (++sbb == NS1B) { sbb = 0; phb ^= 1; }
        if ((kb & 1) && ++sa == NS1A) { sa = 0; pha ^= 1; }
      }
      const int lr = lane & 7, lm = lane >> 3;
      const bool le0 = 2 * (lane & 3) <= (lane >> 2), le1 = 2 * (lane & 3) + 1 <= (lane >> 2);
      const uint32_t maskLE = (le0 ? 0x0000FFFFu : 0u) | (le1 ? 0xFFFF0000u : 0u);
      uint32_t q[4][8], k[5][8], vt[5][8];
      {
        static_assert(15 % NS1A == 0 && 30 % NS1B == 0, "slots of the last k blocks");
        mbar_wait(bars + 8 * BAR_FULLA, 1);
        mbar_wait(bars + 8 * BAR_FULLB, 0);
        mbar_wait(bars + 8 * (BAR_FULLB + 1), 0);
        mbar_wait(bars + 8 * (BAR_EMPTYA + 1), 0);
        const uint64_t da = mkdesc(sb + wg * 16384, 16, 2048, 1);
        const uint64_t db = mkdesc(sb + OFF_1B, 4096, 1024, 1);
        wg_fence();
#pragma unroll
        for (int i = 0; i < 4; i++) wgmma_n192(acc0, da + 64 + 2 * i, db + (i >> 1) * (STG1B >> 4) + (i & 1) * 128, 1);
        wg_commit();
        wg_wait<1>();
        nb_arrive(NB_G1DONE, 288);
#pragma unroll
        for (int i = 0; i < 2; i++) wgmma_n192(acc1, da + 2 * i, db + (i >> 1) * (STG1B >> 4) + (i & 1) * 128, 1);
        wg_commit();
        wg_wait<1>();
        fence_regs(acc0);
        PROFA(45, 0);
        attn_pack<8, 1, false>(acc0, k[4]);
        attn_pack<16, 1, true>(acc0, vt[4]);
        const uint32_t kh = sb + OFF_KH + warp * 2048 + lane * 16;
        sts128(kh, k[4][0], k[4][1], k[4][2], k[4][3]);
        sts128(kh + 512, k[4][4], k[4][5], k[4][6], k[4][7]);
#pragma unroll
        for (int i = 0; i < 4; i++) sts64(kh - lane * 8 + 1024 + 256 * i, vt[4][2 * i], vt[4][2 * i + 1]);
#pragma unroll
        for (int i = 2; i < 4; i++) wgmma_n192(acc1, da + 2 * i, db + (i >> 1) * (STG1B >> 4) + (i & 1) * 128, 1);
        wg_commit();
        attn_pack<0, 0, false>(acc0, q[1]);
        attn_pack<0, 1, false>(acc0, q[3]);
        attn_pack<8, 0, false>(acc0, k[2]);
        attn_pack<16, 0, true>(acc0, vt[2]);
        uint32_t z = p.zero;
#pragma unroll
        for (int i = 0; i < 8; i++) z &= q[1][i] & q[3][i];
#pragma unroll
        for (int i = 0; i < 8; i += 2) z &= k[2][i] & k[2][i + 1];
        __syncwarp();
        if (lane == 0) mbar_arrive(bars + 8 * BAR_STG + z);
        wg_wait<0>();
        fence_regs(acc1);
      }
      PROF(2 + wg);
      mbar_wait(bars + 8 * (warp == 0 ? BAR_HALO : BAR_STG), 0);
      {
        const uint32_t kh = sb + (warp == 0 ? OFF_L0 : OFF_KH + (warp - 1) * 2048) + lane * 16;
#pragma unroll
        for (int i = 0; i < 2; i++) {
          const uint4 t = lds128(kh + 512 * i);
          k[0][4 * i] = t.x; k[0][4 * i + 1] = t.y; k[0][4 * i + 2] = t.z; k[0][4 * i + 3] = t.w;
        }
#pragma unroll
        for (int i = 0; i < 4; i++) {
          const uint2 t = lds64(kh - lane * 8 + 1024 + 256 * i);
          vt[0][2 * i] = t.x; vt[0][2 * i + 1] = t.y;
        }
      }
      attn_pack<0, 0, false>(acc1, q[0]);
      attn_pack<0, 1, false>(acc1, q[2]);
      attn_pack<8, 0, false>(acc1, k[1]);
      attn_pack<8, 1, false>(acc1, k[3]);
      {
        float x[8][2];
        uint32_t pp[8];
        const bool first = warp == 0 && gidx == 0;
#pragma unroll
        for (int hd = 0; hd < 2; hd++) {
#pragma unroll
          for (int j = 0; j < 4; j += 2) {
            float s0[4], s1[4], s2[4];
            attn_qk(s2, q[j], q[j + 1], k[j + 2], 4 * hd);
            attn_qk(s1, q[j], q[j + 1], k[j + 1], 4 * hd);
            attn_qk(s0, q[j], q[j + 1], k[j], 4 * hd);
            if (j == 0 && first) s0[0] = s0[1] = -1e9f / 0.17677669529663687f;
            x[2 * j + hd][0] = le0 ? s1[0] : s0[0];
            x[2 * j + hd][1] = le1 ? s1[1] : s0[1];
            x[2 * j + 2 + hd][0] = le0 ? s2[2] : s1[2];
            x[2 * j + 2 + hd][1] = le1 ? s2[3] : s1[3];
          }
        }
        PROFA(40, __float_as_uint(x[1][0] + x[7][1]));
        attn_pack<16, 0, true>(acc1, vt[1]);
        attn_pack<16, 1, true>(acc1, vt[3]);
        quad_softmax<8>(x, pp);
        PROFA(41, pp[1] + pp[7]);
        mbar_wait(bars + 8 * BAR_X, 0);
        ldsm4(a1[0], sb + OFF_TAB + 2048 + (warp & 3) * 1024 + lane * 16);
        ldsm4(a1[1], sb + OFF_TAB + 2560 + (warp & 3) * 1024 + lane * 16);
        {
          const uint4 x = lds128(sb + OFF_TAB + 6144 + wtid * 16);
          t[0] = C2{x.x, x.z};
          t[1] = C2{x.y, x.w};
          const uint4 fh = lds128(sb + OFF_EX + wg * 16), fu = lds128(sb + OFF_EX + 32 + wg * 16);
          auto pw2 = [](uint32_t a, uint32_t b) { return min(max(381 - (int)a - (int)b, 1), 254) * 0x00800080u; };
          sc[0] = pw2(fh.x, fu.x); sc[1] = pw2(fh.y, fu.y); sc[2] = pw2(fh.z, fu.z); sc[3] = pw2(fh.w, fu.w);
        }
        const uint32_t obase = sb + OFF_OP + (warp * 32 + lr) * 128;
#pragma unroll
        for (int n = 0; n < 8; n++) {
          attn_pv(obase + (n >> 1) * 1024 + (((4 * (n & 1) + lm) ^ lr) << 4), vt[n >> 1], vt[(n >> 1) + 1], 4 * (n & 1), pp[n],
                  maskLE);
        }
      }
      PROFA(42, 0);
    }

    {
      const int w = warp & 3;
      const int lr = lane & 7, lm = lane >> 3;
      const uint32_t xb = sb + OFF_X + wg * 4 * XT;
      const uint64_t dc2 = mkdesc(sb + OFF_TAB, 512, 128, 0), dc3 = mkdesc(sb + OFF_TAB, 128, 512, 0);
      const uint64_t dc4 = mkdesc(sb + OFF_TAB + 2048, 128, 256, 0);
      const uint64_t dx = mkdesc(xb, 4096, 1024, 1), dz = mkdesc(xb, 2048, 256, 3);
      const uint32_t zs = xb + (w * 16 + (lm & 1) * 8 + lr) * 32 + (((lm >> 1) ^ (lr >> 2)) << 4);
      const uint32_t ys = xb + w * 2048 + (lm >> 1) * 256;
      const uint32_t yx = (lr * 32 + (((lm & 1) ^ (lr >> 2)) << 4)) ^ (rank << 6);
      const bool own = (w >> 1) == rank;
      const uint32_t ybar = mapa(bars, own ? rank ^ 1 : rank) + 8 * (BAR_Y + wg * 4);
      uint32_t d[2][32], pa[2][4][2][4], e[2][4][8], ya[2][2][2][4], v[2][2][8];
      float o[2][16];
      auto rows = [&](int c) {
        fft_rows(d[c & 1], a1, dx + (XT >> 4) * c);
        wg_commit();
      };
      auto cols = [&](int c) {
        const int s = c & 1;
        fence_regs(d[s]);
#pragma unroll
        for (int i = 0; i < 16; i++) {
          const C2 z = crot(C2{d[s][2 * i], d[s][2 * i + 1]}, t[i & 1]);
          pa[s][i >> 2][i & 1][(i >> 1) & 1] = z.r;
          pa[s][i >> 2][i & 1][2 + ((i >> 1) & 1)] = z.i;
        }
        wg_fence();
#pragma unroll
        for (int i = 0; i < 4; i++) fft_cols<0>(e[s][i], pa[s][i], dc2);
        wg_commit();
      };
      auto prod = [&](int c) {
        const int s = c & 1;
#pragma unroll
        for (int i = 0; i < 4; i++) fence_regs(e[s][i]);
#pragma unroll
        for (int j = 0; j < 2; j++) {
          const C2 u0 = cget(e[s][0], j, 0), u1 = cget(e[s][0], j, 1), u2 = cget(e[s][1], j, 0), u3 = cget(e[s][1], j, 1);
          const C2 h0 = cget(e[s][2], j, 0), h1 = cget(e[s][2], j, 1), h2 = cget(e[s][3], j, 0), h3 = cget(e[s][3], j, 1);
          const C2 s0 = cmul(h0, u0), s1 = cfma(h0, u1, cmul(h1, u0)), s2 = cfma(h0, u2, cfma(h2, u0, cmul(h1, u1)));
          const C2 y3 = cfma(h0, u3, cfma(h1, u2, cfma(h2, u1, cfma(h3, u0, C2{s2.i, hneg2(s2.r)}))));
          ya[s][0][j][0] = s0.r;
          ya[s][0][j][1] = hadd2(s1.r, s0.i);
          ya[s][0][j][2] = s0.i;
          ya[s][0][j][3] = hadd2(s1.i, hneg2(s0.r));
          ya[s][1][j][0] = hadd2(s2.r, s1.i);
          ya[s][1][j][1] = y3.r;
          ya[s][1][j][2] = hadd2(s2.i, hneg2(s1.r));
          ya[s][1][j][3] = y3.i;
        }
        wg_fence();
        fft_cols<1>(v[s][0], ya[s][0], dc3);
        fft_cols<1>(v[s][1], ya[s][1], dc3);
        wg_commit();
      };
      auto stage = [&](int c) {
        const int s = c & 1;
        fence_regs(v[s][0]);
        fence_regs(v[s][1]);
#pragma unroll
        for (int b = 0; b < 4; b++) {
          const C2 x0 = cget(v[s][b >> 1], 0, b & 1), x1 = cget(v[s][b >> 1], 1, b & 1);
          const C2 z0 = crot(C2{x0.i, x0.r}, t[0]), z1 = crot(C2{x1.i, x1.r}, t[1]);
          stsm4(zs + c * XT + b * 2048, z0.i, z0.r, z1.i, z1.r);
        }
      };
      auto back = [&](int c) {
        fft_back(o[c & 1], dz + (XT >> 4) * c, dc4);
        wg_commit();
      };
      auto out = [&](int c) {
        float (&r)[16] = o[c & 1];
        fence_regs(r);
#pragma unroll
        for (int i = 0; i < 16; i += 8)
          stsm4t(ys + c * XT + (yx ^ ((c & 1) << 5)) + 64 * i, bmul2(pack_bf16(r[i], r[i + 1]), sc[c]),
                 bmul2(pack_bf16(r[i + 2], r[i + 3]), sc[c]), bmul2(pack_bf16(r[i + 4], r[i + 5]), sc[c]),
                 bmul2(pack_bf16(r[i + 6], r[i + 7]), sc[c]));
        __syncwarp();
        if (lane == 0) {
          mbar_arrive_cluster(ybar + 8 * c);
          if (own) mbar_arrive(bars + 8 * BAR_LAND);
        }
      };
      wg_fence();
      rows(0);
      rows(1);
      fence_async_smem();
      nb_arrive(NB_OREADY, 288);
      PROF(34 + wg);
      wg_wait<1>();
      cols(0);
      wg_wait<1>();
      cols(1);
      rows(2);
      nb_sync(NB_CONV + wg, 128);
      wg_wait<2>();
      prod(0);
      wg_wait<1>();
      cols(2);
      rows(3);
      wg_wait<2>();
      stage(0);
      fence_async_smem();
      prod(1);
      nb_sync(NB_CONV + wg, 128);
      back(0);
      wg_wait<2>();
      cols(3);
      wg_wait<2>();
      stage(1);
      fence_async_smem();
      prod(2);
      nb_sync(NB_CONV + wg, 128);
      back(1);
      wg_wait<2>();
      out(0);
      wg_wait<1>();
      stage(2);
      fence_async_smem();
      prod(3);
      nb_sync(NB_CONV + wg, 128);
      back(2);
      wg_wait<2>();
      out(1);
      wg_wait<1>();
      stage(3);
      fence_async_smem();
      nb_sync(NB_CONV + wg, 128);
      wg_fence();
      back(3);
      wg_wait<1>();
      out(2);
      wg_wait<0>();
      if (lane == 0) mbar_arrive_cluster(mapa(bars, 1) + 8 * BAR_TAB);
      out(3);
      PROF(6 + wg);
      if (wg != g2wg) {
        const int frow = w * 64 + (lane & 2) * 4 + (lane >> 2);
        const uint32_t qo = w * 2048 + (lane >> 3) * 128 + (lane & 2) * 32 + (lane & 4) * 8 + (lane & 1) * 16;
        uint4 q[16];
        mbar_wait(bars + 8 * BAR_Q, 0);
#pragma unroll
        for (int h = 0; h < 2; h++) {
          uint32_t z = p.zero;
#pragma unroll
          for (int i = 0; i < 8; i++) {
            q[8 * h + i] = lds128(sb + g2_b(3 + h) + qo + (i & 3) * 512 + (i >> 2) * 8192);
            z &= q[8 * h + i].x;
          }
          __syncwarp();
          if (lane == 0) mbar_arrive(bars + 8 * (BAR_QFREE + h) + z);
        }
        const int c8 = 2 * lm + (lr & 1), src = (lr >> 1) & 1;
        const uint32_t fa = sb + OFF_X + c8 * XT + rank * 4096 + (src == rank ? 0 : 1024) + w * 128;
        const uint32_t fx = ((lr >> 2) ^ ((lr & 3) << 1) ^ (w & 1)) << 4;
        mbar_wait(bars + 8 * BAR_LAND, 0);
        PROF2(33);
#pragma unroll
        for (int i = 0; i < 16; i++) {
          uint32_t y[4];
          ldsm4t(y, fa + (i >> 3) * 2048 + ((i >> 2) & 1) * 512 + (fx ^ ((i & 3) << 5)));
          q[i] = make_uint4(bmul2(q[i].x, y[0]), bmul2(q[i].y, y[1]), bmul2(q[i].z, y[2]), bmul2(q[i].w, y[3]));
        }
        PROF2(20);
        uint4* og = reinterpret_cast<uint4*>(p.out + (size_t)(rank * 1024 + frow) * (2 * DM) + (chb & ~1) * 8 + (lane & 1) * 8);
        if (PACE0) __nanosleep(PACE0);
#pragma unroll
        for (int i = 0; i < 16; i++) {
          og[((i >> 2) * 256 + (i & 3) * 16) * (2 * DM / 8)] = q[i];
          if (PACE) __nanosleep(PACE);
        }
        PROF(22);
      }
    }
    }

    if (MODE != 1 && wg == g2wg) {
      float acc0[64], acc1[64];
      int s = 0, ph = 0, sprev = 0;
#pragma unroll 1
      for (int kb = 0; kb < 16 - ENDG; kb++) {
        mbar_wait(bars + 8 * (BAR_FULL2 + s), ph);
        if (kb == 0) PROF(8);
        if ((warp & 3) == 0) PROF2(40 + kb);
        const uint64_t da = mkdesc(sb + g2_a(s, hsel), 16, 1024, 1);
        const uint64_t db = mkdesc(sb + g2_b(s), 8192, 1024, 1);
        wg_fence();
        wgmma_n128(acc0, da, db, kb);
        wgmma_n128(acc1, da + 512, db, kb);
        wgmma_n128(acc0, da + 2, db + 128, 1);
        wgmma_n128(acc1, da + 514, db + 128, 1);
        wg_commit();
        wg_wait<1>();
        if (kb > 0 && kb + NS2 <= 16 && signaller) mbar_arrive_cluster(rbars + 8 * (BAR_EMPTY2 + sprev));
        wgmma_n128(acc0, da + 4, db + 256, 1);
        wgmma_n128(acc1, da + 516, db + 256, 1);
        wgmma_n128(acc0, da + 6, db + 384, 1);
        wgmma_n128(acc1, da + 518, db + 384, 1);
        wg_commit();
        wg_wait<1>();
        sprev = s;
        if (++s == NS2) { s = 0; ph ^= 1; }
      }
#pragma unroll
      for (int kb = 16 - ENDG; kb < 16; kb++) {
        mbar_wait(bars + 8 * (BAR_FULL2 + kb % NS2), (kb / NS2) & 1);
        if ((warp & 3) == 0) PROF2(40 + kb);
        const uint64_t da = mkdesc(sb + g2_a(kb % NS2, hsel), 16, 1024, 1);
        const uint64_t db = mkdesc(sb + g2_b(kb % NS2), 8192, 1024, 1);
        wg_fence();
#pragma unroll
        for (int i = 0; i < 4; i++) wgmma_n128(acc0, da + 2 * i, db + 128 * i, 1);
        wg_commit();
        if (kb == 16 - ENDG && kb + NS2 <= 16) {
          wg_wait<1>();
          if (signaller) mbar_arrive_cluster(rbars + 8 * (BAR_EMPTY2 + sprev));
        }
      }
      static_assert(ENDG <= NS2, "the last stages stay resident");
      auto second = [&](int i0, int i1) {
#pragma unroll
        for (int i = i0; i < i1; i++) {
          const int st = (16 - ENDG + (i >> 2)) % NS2;
          wgmma_n128(acc1, mkdesc(sb + g2_a(st, hsel) + 8192, 16, 1024, 1) + 2 * (i & 3),
                     mkdesc(sb + g2_b(st), 8192, 1024, 1) + 128 * (i & 3), 1);
        }
        wg_commit();
      };
      second(0, 4);
      const int lr = lane & 7, lm = lane >> 3;
      const uint32_t wb[2] = {sb + g2_a(1, 0) + (warp & 3) * 2048, sb + g2_a(3, 0) + (warp & 3) * 2048};
      const int orow = (rb2 & 7) * 128 + (warp & 3) * 16;
      auto stage_out = [&](const float (&acc)[64], uint32_t off, int j0, int j1) {
#pragma unroll
        for (int j = j0; j < j1; j += 2) {
          const uint32_t a = wb[j >> 3] + off + (lr + 8 * (lm & 1)) * 128 + ((((j & 7) + (lm >> 1)) ^ lr) << 4);
          stsm4(a, pack_bf16(acc[4 * j], acc[4 * j + 1]), pack_bf16(acc[4 * j + 2], acc[4 * j + 3]),
                pack_bf16(acc[4 * j + 4], acc[4 * j + 5]), pack_bf16(acc[4 * j + 6], acc[4 * j + 7]));
        }
      };
      auto store_tma = [&](uint32_t off, int row) {
        fence_async_smem();
        __syncwarp();
        if (elect_one()) {
          tma_store_3d(&tmOb, wb[0] + off, DM + cb2 * 128, rb2 >> 3, row);
          tma_store_3d(&tmOb, wb[1] + off, DM + cb2 * 128 + 64, rb2 >> 3, row);
          bulk_commit();
        }
      };
      wg_wait<1>();
      fence_regs(acc0);
      PROF(10);
#pragma unroll
      for (int c = 0; c < 4; c++) {
        stage_out(acc0, 0, 4 * c, 4 * c + 4);
        second(4 + ILV * c, 4 + ILV * (c + 1));
      }
      store_tma(0, orow);
      if (4 + 4 * ILV < 4 * ENDG) second(4 + 4 * ILV, 4 * ENDG);
      PROF(12);
      wg_wait<0>();
      fence_regs(acc1);
      PROF(11);
      stage_out(acc1, 8192, 0, 16);
      __syncwarp();
      {
        const int rr = lane >> 4, ck = lane & 7, hf = (lane >> 3) & 1;
        uint4* og = reinterpret_cast<uint4*>(p.out + (size_t)(2 * (orow + 64 + rr) + (rb2 >> 3)) * (2 * DM) + DM + cb2 * 128 + hf * 64 + ck * 8);
        uint4 v[8];
#pragma unroll
        for (int i = 0; i < 8; i++) v[i] = lds128((hf ? wb[1] : wb[0]) + 8192 + (2 * i + rr) * 128 + ((ck ^ ((2 * i + rr) & 7)) << 4));
#pragma unroll
        for (int i = 0; i < 8; i++) og[(size_t)i * 4 * (2 * DM / 8)] = v[i];
      }
      PROF(13);
      bulk_wait0();
    }
    cluster_sync_all();
  }
}

typedef CUresult (*EncodeFn)(CUtensorMap*, CUtensorMapDataType, cuuint32_t, void*, const cuuint64_t*, const cuuint64_t*,
                             const cuuint32_t*, const cuuint32_t*, CUtensorMapInterleave, CUtensorMapSwizzle,
                             CUtensorMapL2promotion, CUtensorMapFloatOOBfill);

void make_map(EncodeFn enc, CUtensorMap* tm, const void* base, int rank, const cuuint64_t* dims, const cuuint64_t* strides,
              const cuuint32_t* box, CUtensorMapSwizzle swz) {
  cuuint32_t es[5] = {1, 1, 1, 1, 1};
  enc(tm, CU_TENSOR_MAP_DATA_TYPE_BFLOAT16, rank, const_cast<void*>(base), dims, strides, box, es,
      CU_TENSOR_MAP_INTERLEAVE_NONE, swz, CU_TENSOR_MAP_L2_PROMOTION_L2_256B, CU_TENSOR_MAP_FLOAT_OOB_FILL_NONE);
}

}

extern "C" void kernel_launch(void* const* d_in, const int* in_sizes, int n_in, void* d_out, int out_size) {
  static EncodeFn enc = nullptr;
  static bool coresident = true;
  if (!enc) {
    void* fn = nullptr;
    cudaDriverEntryPointQueryResult qr;
    cudaGetDriverEntryPoint("cuTensorMapEncodeTiled", &fn, cudaEnableDefault, &qr);
    enc = (EncodeFn)fn;
    cudaFuncSetAttribute(fused_kernel<0>, cudaFuncAttributeMaxDynamicSharedMemorySize, SMEM_BYTES);
    cudaFuncSetAttribute(fused_kernel<1>, cudaFuncAttributeMaxDynamicSharedMemorySize, SMEM_BYTES);
    cudaFuncSetAttribute(fused_kernel<2>, cudaFuncAttributeMaxDynamicSharedMemorySize, SMEM_BYTES);
    cudaLaunchConfig_t cfg = {};
    cfg.gridDim = dim3(NCTA);
    cfg.blockDim = dim3(NTHREADS);
    cfg.dynamicSmemBytes = SMEM_BYTES;
    cudaLaunchAttribute at;
    at.id = cudaLaunchAttributeClusterDimension;
    at.val.clusterDim.x = 2;
    at.val.clusterDim.y = 1;
    at.val.clusterDim.z = 1;
    cfg.attrs = &at;
    cfg.numAttrs = 1;
    int nclusters = 0;
    if (cudaOccupancyMaxActiveClusters(&nclusters, fused_kernel<0>, &cfg) == cudaSuccess) coresident = nclusters >= NCTA / 2;
    (void)cudaGetLastError();
  }
  CUtensorMap tmX, tmW, tmWo, tmQ, tmOb, tmXh, tmWh;
  {
    cuuint64_t dims[3] = {1024, 2, 1024};
    cuuint64_t str[2] = {2048, 4096};
    cuuint32_t box[3] = {64, 1, 128};
    make_map(enc, &tmX, d_in[6], 3, dims, str, box, CU_TENSOR_MAP_SWIZZLE_128B);
  }
  {
    cuuint64_t dims[3] = {1024, 1024, 3};
    cuuint64_t str[2] = {6144, 2048};
    cuuint32_t box[3] = {64, 32, 3};
    make_map(enc, &tmW, d_in[7], 3, dims, str, box, CU_TENSOR_MAP_SWIZZLE_128B);
  }
  {
    cuuint64_t dims[3] = {64, 1024, 16};
    cuuint64_t str[2] = {2048, 128};
    cuuint32_t box[3] = {64, 64, 2};
    make_map(enc, &tmWo, d_in[8], 3, dims, str, box, CU_TENSOR_MAP_SWIZZLE_128B);
  }
  {
    cuuint64_t dims[5] = {1024, 2, 2, 4, 128};
    cuuint64_t str[4] = {2048, 8 * 2048, 2 * 2048, 16 * 2048};
    cuuint32_t box[5] = {16, 2, 2, 4, 32};
    make_map(enc, &tmQ, d_in[0], 5, dims, str, box, CU_TENSOR_MAP_SWIZZLE_NONE);
  }
  {
    cuuint64_t dims[3] = {2048, 2, 1024};
    cuuint64_t str[2] = {4096, 8192};
    cuuint32_t box[3] = {64, 1, 16};
    make_map(enc, &tmOb, d_out, 3, dims, str, box, CU_TENSOR_MAP_SWIZZLE_128B);
  }
  {
    cuuint64_t dims[4] = {1024, 256, 2, 4};
    cuuint64_t str[3] = {4096, 2048, 256 * 4096};
    cuuint32_t box[4] = {64, 8, 2, 3};
    make_map(enc, &tmXh, d_in[6], 4, dims, str, box, CU_TENSOR_MAP_SWIZZLE_128B);
  }
  {
    cuuint64_t dims[3] = {64, 1024, 48};
    cuuint64_t str[2] = {6144, 128};
    cuuint32_t box[3] = {64, 64, 4};
    make_map(enc, &tmWh, d_in[7], 3, dims, str, box, CU_TENSOR_MAP_SWIZZLE_128B);
  }
  Params p;
  p.q = (const __nv_bfloat16*)d_in[0];
  p.k = (const __nv_bfloat16*)d_in[1];
  p.v = (const __nv_bfloat16*)d_in[2];
  p.shift_k = (const __nv_bfloat16*)d_in[3];
  p.ssm_k = (const __nv_bfloat16*)d_in[4];
  p.ssm_D = (const __nv_bfloat16*)d_in[5];
  p.x = (const __nv_bfloat16*)d_in[6];
  p.w = (const __nv_bfloat16*)d_in[7];
  p.wo = (const __nv_bfloat16*)d_in[8];
  p.out = (__nv_bfloat16*)d_out;
  p.zero = 0;
  if (coresident) {
    fused_kernel<0><<<NCTA, NTHREADS, SMEM_BYTES>>>(p, tmX, tmW, tmWo, tmQ, tmOb, tmXh, tmWh);
  } else {
    fused_kernel<0><<<4, NTHREADS, SMEM_BYTES>>>(p, tmX, tmW, tmWo, tmQ, tmOb, tmXh, tmWh);
    fused_kernel<1><<<NCTA, NTHREADS, SMEM_BYTES>>>(p, tmX, tmW, tmWo, tmQ, tmOb, tmXh, tmWh);
    fused_kernel<2><<<NCTA, NTHREADS, SMEM_BYTES>>>(p, tmX, tmW, tmWo, tmQ, tmOb, tmXh, tmWh);
  }
}
```

```cpp
#include <cuda_runtime.h>
#include <cuda.h>
#include <cuda_bf16.h>
#include <stdint.h>

namespace {

constexpr int SEQ = 2048;
constexpr int DM = 1024;
constexpr int NCTA = 132;
constexpr int NTHREADS = 384;

constexpr int STG1A = 32768;
constexpr int NS1A = 3;
constexpr int STG1B = 12288;
constexpr int NS1B = 5;
constexpr int OFF_1B = NS1A * STG1A;
constexpr int STG2 = 32768;
constexpr int NS2 = 7;
#define G2SEQ 0x0432104321043210ull
constexpr unsigned long long G2_STAGE = G2SEQ;
__host__ __device__ constexpr int g2_stage(int kb) { return (int)(G2_STAGE >> (4 * kb)) & 7; }
constexpr unsigned g2_bits(bool reuse) {
  unsigned r = 0;
  for (int kb = 0; kb < 16; kb++) {
    int n = 0;
    for (int j = reuse ? kb + 1 : 0; j < (reuse ? 16 : kb); j++) n += g2_stage(j) == g2_stage(kb);
    r |= (unsigned)(reuse ? n > 0 : n & 1) << kb;
  }
  return r;
}
constexpr unsigned G2_PARITY = g2_bits(false);
constexpr unsigned G2_REUSE = g2_bits(true);
#define ILV 2
#define PACE 50
#define PACE0 4
#define POLL0 1500
#define QORD 1
#define BDEL 0
#define QPOS 1
#define G2W 0
#define ENDG 5
__device__ __forceinline__ uint32_t g2_a(int s, int hsel) { return (((0xca97524 >> (4 * s)) & 15) ^ (s & 5 ? 0 : hsel)) << 14; }
__device__ __forceinline__ uint32_t g2_b(int s) { return ((0xdb83610 >> (4 * s)) & 15) << 14; }
constexpr int STGH = 73728;
constexpr int OFF_KH = 1 * STG2;
constexpr int OFF_OP = 2 * STG2;
constexpr int OFF_T32 = 5 * STG2 - 4096;
constexpr int OFF_X = 5 * STG2;
constexpr int XT = 8192;
constexpr int OFF_BAR = OFF_X + 8 * XT;
constexpr int OFF_EX = OFF_BAR + 448;
constexpr int OFF_T16 = 230400;
constexpr int SMEM_BYTES = OFF_T16 + 2048;
static_assert(OFF_1B + NS1B * STG1B <= OFF_T32 && OFF_X % 1024 == 0, "layout");
static_assert(3 * STGH <= OFF_BAR && OFF_EX + 64 <= OFF_T16 && SMEM_BYTES <= 232448, "smem");

constexpr int BAR_FULLA = 0;
constexpr int BAR_EMPTYA = 3;
constexpr int BAR_FULLB = 6;
constexpr int BAR_EMPTYB = 11;
constexpr int BAR_FULL2 = 16;
constexpr int BAR_EMPTY2 = 44;
constexpr int BAR_X = 26;
constexpr int BAR_LAND = 27;
constexpr int BAR_TAB = 28;
constexpr int BAR_U = 29;
constexpr int BAR_H = 30;
constexpr int BAR_STG = 31;
constexpr int BAR_Y = 32;
constexpr int BAR_HALO = 40;
constexpr int BAR_Q = 41;
constexpr int BAR_QFREE = 42;

constexpr int NB_G1DONE = 1;
constexpr int NB_G1END = 3;
constexpr int NB_OREADY = 4;
constexpr int NB_CONV = 5;
constexpr int NB_HELP3 = 11;
constexpr int NB_FIRST = 13;

#define REG_MATH 224
#define REG_HELP 56
constexpr int SPIN_LIMIT = 1 << 20;

__device__ __align__(1024) __nv_bfloat16 g_o[SEQ * DM];
__device__ uint32_t g_flag_o[128];
__device__ uint32_t g_flag_h[4];
__device__ uint4 g_halo[128 * 128];
__device__ __align__(128) const uint32_t g_tab[2048] = {
  0x2fd93000,0x2ea72f64,0x2c722da8,0x263e2a1f,0x2ea73000,0xa63e2a1f,0xafd9ada8,0xac72af64,0x2c723000,0xafd9aa1f,0x263eada8,0x2ea72f64,
  0x263e3000,0xac72af64,0x2ea72da8,0xafd9aa1f,0xa63e3000,0x2c72af64,0xaea72da8,0x2fd9aa1f,0xac723000,0x2fd9aa1f,0xa63eada8,0xaea72f64,
  0xaea73000,0x263e2a1f,0x2fd9ada8,0x2c72af64,0xafd93000,0xaea72f64,0xac722da8,0xa63e2a1f,0x263e0000,0x2c722a1f,0x2ea72da8,0x2fd92f64,
  0x2c720000,0x2fd92f64,0x263e2da8,0xaea7aa1f,0x2ea70000,0x263e2f64,0xafd9ada8,0x2c72aa1f,0x2fd90000,0xaea72a1f,0x2c72ada8,0xa63e2f64,
  0x2fd90000,0xaea7aa1f,0x2c722da8,0xa63eaf64,0x2ea70000,0x263eaf64,0xafd92da8,0x2c722a1f,0x2c720000,0x2fd9af64,0x263eada8,0xaea72a1f,
  0x263e0000,0x2c72aa1f,0x2ea7ada8,0x2fd9af64,0xafd93000,0xaea72f64,0xac722da8,0xa63e2a1f,0xaea73000,0x263e2a1f,0x2fd9ada8,0x2c72af64,
  0xac723000,0x2fd9aa1f,0xa63eada8,0xaea72f64,0xa63e3000,0x2c72af64,0xaea72da8,0x2fd9aa1f,0x263e3000,0xac72af64,0x2ea72da8,0xafd9aa1f,
  0x2c723000,0xafd9aa1f,0x263eada8,0x2ea72f64,0x2ea73000,0xa63e2a1f,0xafd9ada8,0xac72af64,0x2fd93000,0x2ea72f64,0x2c722da8,0x263e2a1f,
  0xa63e0000,0xac722a1f,0xaea72da8,0xafd92f64,0xac720000,0xafd92f64,0xa63e2da8,0x2ea7aa1f,0xaea70000,0xa63e2f64,0x2fd9ada8,0xac72aa1f,
  0xafd90000,0x2ea72a1f,0xac72ada8,0x263e2f64,0xafd90000,0x2ea7aa1f,0xac722da8,0x263eaf64,0xaea70000,0xa63eaf64,0x2fd92da8,0xac722a1f,
  0xac720000,0xafd9af64,0xa63eada8,0x2ea72a1f,0xa63e0000,0xac72aa1f,0xaea7ada8,0xafd9af64,0xa63e0000,0xac72aa1f,0xaea7ada8,0xafd9af64,
  0xac720000,0xafd9af64,0xa63eada8,0x2ea72a1f,0xaea70000,0xa63eaf64,0x2fd92da8,0xac722a1f,0xafd90000,0x2ea7aa1f,0xac722da8,0x263eaf64,
  0xafd90000,0x2ea72a1f,0xac72ada8,0x263e2f64,0xaea70000,0xa63e2f64,0x2fd9ada8,0xac72aa1f,0xac720000,0xafd92f64,0xa63e2da8,0x2ea7aa1f,
  0xa63e0000,0xac722a1f,0xaea72da8,0xafd92f64,0x2fd93000,0x2ea72f64,0x2c722da8,0x263e2a1f,0x2ea73000,0xa63e2a1f,0xafd9ada8,0xac72af64,
  0x2c723000,0xafd9aa1f,0x263eada8,0x2ea72f64,0x263e3000,0xac72af64,0x2ea72da8,0xafd9aa1f,0xa63e3000,0x2c72af64,0xaea72da8,0x2fd9aa1f,
  0xac723000,0x2fd9aa1f,0xa63eada8,0xaea72f64,0xaea73000,0x263e2a1f,0x2fd9ada8,0x2c72af64,0xafd93000,0xaea72f64,0xac722da8,0xa63e2a1f,
  0x263e0000,0x2c72aa1f,0x2ea7ada8,0x2fd9af64,0x2c720000,0x2fd9af64,0x263eada8,0xaea72a1f,0x2ea70000,0x263eaf64,0xafd92da8,0x2c722a1f,
  0x2fd90000,0xaea7aa1f,0x2c722da8,0xa63eaf64,0x2fd90000,0xaea72a1f,0x2c72ada8,0xa63e2f64,0x2ea70000,0x263e2f64,0xafd9ada8,0x2c72aa1f,
  0x2c720000,0x2fd92f64,0x263e2da8,0xaea7aa1f,0x263e0000,0x2c722a1f,0x2ea72da8,0x2fd92f64,0xafd93000,0xaea72f64,0xac722da8,0xa63e2a1f,
  0xaea73000,0x263e2a1f,0x2fd9ada8,0x2c72af64,0xac723000,0x2fd9aa1f,0xa63eada8,0xaea72f64,0xa63e3000,0x2c72af64,0xaea72da8,0x2fd9aa1f,
  0x263e3000,0xac72af64,0x2ea72da8,0xafd9aa1f,0x2c723000,0xafd9aa1f,0x263eada8,0x2ea72f64,0x2ea73000,0xa63e2a1f,0xafd9ada8,0xac72af64,
  0x2fd93000,0x2ea72f64,0x2c722da8,0x263e2a1f,0xa63e0000,0xac72aa1f,0xaea7ada8,0xafd9af64,0x2c720000,0x2fd92f64,0x263e2da8,0xaea7aa1f,
  0xaea70000,0xa63eaf64,0x2fd92da8,0xac722a1f,0x2fd90000,0xaea72a1f,0x2c72ada8,0xa63e2f64,0xafd90000,0x2ea72a1f,0xac72ada8,0x263e2f64,
  0x2ea70000,0x263eaf64,0xafd92da8,0x2c722a1f,0xac720000,0xafd92f64,0xa63e2da8,0x2ea7aa1f,0x263e0000,0x2c72aa1f,0x2ea7ada8,0x2fd9af64,
  0x2fd93000,0x2ea72f64,0x2c722da8,0x263e2a1f,0xaea7b000,0x263eaa1f,0x2fd92da8,0x2c722f64,0x2c723000,0xafd9aa1f,0x263eada8,0x2ea72f64,
  0xa63eb000,0x2c722f64,0xaea7ada8,0x2fd92a1f,0xa63e3000,0x2c72af64,0xaea72da8,0x2fd9aa1f,0x2c72b000,0xafd92a1f,0x263e2da8,0x2ea7af64,
  0xaea73000,0x263e2a1f,0x2fd9ada8,0x2c72af64,0x2fd9b000,0x2ea7af64,0x2c72ada8,0x263eaa1f,0x263e0000,0x2c72aa1f,0x2ea7ada8,0x2fd9af64,
  0xac720000,0xafd92f64,0xa63e2da8,0x2ea7aa1f,0x2ea70000,0x263eaf64,0xafd92da8,0x2c722a1f,0xafd90000,0x2ea72a1f,0xac72ada8,0x263e2f64,
  0x2fd90000,0xaea72a1f,0x2c72ada8,0xa63e2f64,0xaea70000,0xa63eaf64,0x2fd92da8,0xac722a1f,0x2c720000,0x2fd92f64,0x263e2da8,0xaea7aa1f,
  0xa63e0000,0xac72aa1f,0xaea7ada8,0xafd9af64,0xafd93000,0xaea72f64,0xac722da8,0xa63e2a1f,0x2ea7b000,0xa63eaa1f,0xafd92da8,0xac722f64,
  0xac723000,0x2fd9aa1f,0xa63eada8,0xaea72f64,0x263eb000,0xac722f64,0x2ea7ada8,0xafd92a1f,0x263e3000,0xac72af64,0x2ea72da8,0xafd9aa1f,
  0xac72b000,0x2fd92a1f,0xa63e2da8,0xaea7af64,0x2ea73000,0xa63e2a1f,0xafd9ada8,0xac72af64,0xafd9b000,0xaea7af64,0xac72ada8,0xa63eaa1f,
  0xafd9b000,0xaea7af64,0xac72ada8,0xa63eaa1f,0x2ea73000,0xa63e2a1f,0xafd9ada8,0xac72af64,0xac72b000,0x2fd92a1f,0xa63e2da8,0xaea7af64,
  0x263e3000,0xac72af64,0x2ea72da8,0xafd9aa1f,0x263eb000,0xac722f64,0x2ea7ada8,0xafd92a1f,0xac723000,0x2fd9aa1f,0xa63eada8,0xaea72f64,
  0x2ea7b000,0xa63eaa1f,0xafd92da8,0xac722f64,0xafd93000,0xaea72f64,0xac722da8,0xa63e2a1f,0xa63e0000,0xac72aa1f,0xaea7ada8,0xafd9af64,
  0x2c720000,0x2fd92f64,0x263e2da8,0xaea7aa1f,0xaea70000,0xa63eaf64,0x2fd92da8,0xac722a1f,0x2fd90000,0xaea72a1f,0x2c72ada8,0xa63e2f64,
  0xafd90000,0x2ea72a1f,0xac72ada8,0x263e2f64,0x2ea70000,0x263eaf64,0xafd92da8,0x2c722a1f,0xac720000,0xafd92f64,0xa63e2da8,0x2ea7aa1f,
  0x263e0000,0x2c72aa1f,0x2ea7ada8,0x2fd9af64,0x2fd9b000,0x2ea7af64,0x2c72ada8,0x263eaa1f,0xaea73000,0x263e2a1f,0x2fd9ada8,0x2c72af64,
  0x2c72b000,0xafd92a1f,0x263e2da8,0x2ea7af64,0xa63e3000,0x2c72af64,0xaea72da8,0x2fd9aa1f,0xa63eb000,0x2c722f64,0xaea7ada8,0x2fd92a1f,
  0x2c723000,0xafd9aa1f,0x263eada8,0x2ea72f64,0xaea7b000,0x263eaa1f,0x2fd92da8,0x2c722f64,0x2fd93000,0x2ea72f64,0x2c722da8,0x263e2a1f,
  0x263e0000,0x2c72aa1f,0x2ea7ada8,0x2fd9af64,0xac720000,0xafd92f64,0xa63e2da8,0x2ea7aa1f,0x2ea70000,0x263eaf64,0xafd92da8,0x2c722a1f,
  0xafd90000,0x2ea72a1f,0xac72ada8,0x263e2f64,0x2fd90000,0xaea72a1f,0x2c72ada8,0xa63e2f64,0xaea70000,0xa63eaf64,0x2fd92da8,0xac722a1f,
  0x2c720000,0x2fd92f64,0x263e2da8,0xaea7aa1f,0xa63e0000,0xac72aa1f,0xaea7ada8,0xafd9af64,0x316c2fbd,0x343e32f7,0x35bc34ff,0x372c3676,
  0x371532c6,0x3a81392e,0x3bef3b71,0x3b7c3bf2,0x397034cf,0x3bfc3b6c,0x38b23b04,0xb40e31e8,0x3ae13631,0x39e73bf5,0xb6e83219,0xbbe8bb13,
  0x3bc23785,0x30be3aa9,0xbbfdb911,0x2a16b9aa,0x3bfe3865,0xb80f37a6,0xb82abc00,0x3bfd376f,0x3b9238fd,0xbb7f2311,0x3805b929,0x31223bde,
  0x3a85398b,0xbb96b742,0x3bff319e,0xbbb82f8b,0xbbe2bbf1,0xbbb7bbcf,0xbb78bb9a,0xbb27bb52,0xbb2cbbd2,0xb8a8ba19,0xb029b5df,0x35a52f59,
  0xb9dfbba1,0x2ba7b5f7,0x3a7a37b2,0x3bbd3bdd,0xb815bb60,0x39662e91,0x3b373bda,0xb0d7377a,0xb3d3bb10,0x3be9386f,0x2a7a3a31,0xbbfeb9a6,
  0x294dbab0,0x3ae53b07,0xbad51fdb,0xab43bb16,0x352fba41,0x35993c00,0xbaebba1d,0x3be531cf,0x38a3b9c5,0xb5173b21,0x2776bbe0,0x34323bf2,
  0x384537dd,0x38ea3899,0x39823937,0x3a0d39c9,0x39463a93,0x3340374e,0xb426a452,0xb979b7c8,0xbb45b924,0xbb32bc00,0xb371b902,0x38d63294,
  0xb08db9a1,0x3b3f379b,0x39583bd7,0xb8252dfb,0x3bea3a2d,0xb3ba3874,0xbb89bb0d,0x36d2b625,0xb6bb387f,0xb8d1bbf5,0x3be73602,0xb546391f,
  0xba00bb01,0x3bff35eb,0xba5c34db,0x3359bab6,0x3ac7b66b,0xb9413933,0x368dbabd,0xb0103bb3,0xbac4baf7,0xba50ba8c,0xb9cdba11,0xb93cb986,
  0x3a04388e,0x3bcb3b1e,0x3bba3c00,0x39d63afe,0x36af3a21,0xb6ffa17f,0xbbc8ba3d,0xba60bbd4,0xbbebb9af,0xb6c6bb0a,0x39f43263,0x3ad83bf7,
  0x30a6b916,0x3bc33aa5,0xb55e3790,0xbb3dbb63,0x3b423a9e,0xba642ec3,0xb0f0bb6a,0x3b8e3a25,0xb94a37bd,0x2884bb6f,0x38db3b9f,0xbbc9b85a,
  0xb840bb54,0x3a093a15,0xbb4cb850,0x3bef3457,0x3a893a4d,0x3af43ac1,0x3b4f3b24,0x3b983b76,0xbb94baba,0xbbe4bbf9,0xba58bb57,0xb699b8f8,
  0x3bfe3b18,0x394f3b5c,0xb109347b,0xbae8b884,0xbbc0bb68,0xa9b1b90c,0x3b8b387a,0x38bc3ba5,0x3ade3ba7,0xb8c1324b,0xb9f0bbf6,0x39eb9648,
  0xb96bbbd6,0x3bbf3487,0xb38939b3,0xb9f8bba3,0x370a3bf3,0xbb47b994,0x3bbc2d65,0xb8ad3889,0xb153bc00,0x37213b9c,0xb97dba90,0x3af138f3,
  0xb89eb8ee,0xb7e8b84a,0xb682b737,0xb50bb5c8,0x35233855,0xb13b2d33,0xb8e0b65f,0xbb4aba45,0xa8e8b764,0x39fc3648,0x3be63bae,0x380a3a9b,
  0xb3eb360e,0xbbfeba35,0xb552baa2,0x3a7334b7,0x381ab4ab,0x3a6f3bd8,0xb95d2e5f,0xb962bc00,0xb9e3327c,0xb402bbac,0x3bc6399d,0xb95434c3,
  0x3b2faf27,0xb6a439bc,0xb41abbf9,0x3a7e3a97,0xbbe3251b,0x3b2ab4f3,0xb9d23894,0x37f3ba49,0x3bce3bb5,0x3bf03be1,0x3bff3bfa,0x3bfb3bff,
  0x2c38b1b6,0x383a34e7,0x3aee39c0,0x3bff3bb2,0xbb81bbf8,0xb53ab999,0x38302ef5,0x3bed3ab3,0xb8cc9cb6,0xbb85bbab,0x2adeb86a,0x3bc5391b,
  0x38c73bf6,0xbadbb232,0xb6ddbba9,0x3b87361a,0x3b833201,0xb0743a39,0xba76bb5e,0x3b352dc9,0xac06bbb0,0x39743b59,0xbbeeb759,0x3aceb2ad,
  0xbbccb5d4,0x3bfb2d00,0xbb7a32de,0x3a54b7d2,0xb30fb44b,0xafefb185,0xa6adacce,0x2c9c25e4,0xbbfcbbdf,0xbacbbb9e,0xb7feb990,0xa81fb463,
  0xb58d2d97,0xbb90b9b8,0xbad1bbf4,0xb05bb85f,0x3a673c00,0xb5763493,0xbbfdbaac,0xb3a2ba29,0x3a6b2e2d,0x38203bd9,0xbb3ab49f,0xb56abb65,
  0xb581bbdc,0x3bec3907,0xb8b7363c,0xb6f4bbf8,0xbbfcb46f,0x39dab654,0xb0423b1b,0xb835bbd3,0xb3283b73,0xac6abbfa,0x35b13bd0,0xb8e5bafb,
  0x38ee3a0d,0xb84aba89,0x37373af4,0xb5c8bb4f,0x35df3a81,0x2f59bbef,0xb88e3b7c,0x3b1eb946,0x2d973ae8,0x39b8bb81,0xbbf4353a,0x385f3830,
  0xb2633b3f,0x3bf7b958,0xb60eb825,0xba353bc0,0xb7853b87,0x3aa9b3d3,0x3911bbe9,0xb9aa2a7a,0xb99d3bbf,0x34c33389,0x3bdcb9f8,0x3907bb83,
  0xbb013be5,0xb5eb394a,0x34db2884,0x3ab6b8db,0xbbd03bfb,0xbafb3b7a,0xb98b3a54,0xb74238a3,0x3a4db93c,0xbac1389e,0x3b24b7e8,0xbb763682,
  0x3b71b8a8,0xbbf23029,0x3a9335a5,0xb74eba04,0x3bf8b80a,0xb999b58d,0xaef53b90,0x3ab3bad1,0x3bd7b6c6,0xadfbb9f4,0xbb683ad8,0x390c33eb,
  0x3b10b56a,0x386fbbc2,0xba3130be,0xb9a63bfd,0x39b3b402,0x3ba3bbc6,0x3201b954,0xba393581,0x37bdb122,0x3b6fba00,0x3b9fbbff,0x385aba5c,
  0x32deac6a,0x37d2b5b1,0x39c5b8e5,0x3b21ba85,0x344b3b98,0xb185bbce,0x2cce3bf0,0x25e4bbff,0xbc003340,0x3afe3426,0xb855b979,0x2d333b94,
  0x34cfbbed,0xbb6c39df,0x3b042ba7,0xb1e8ba7a,0x3aa2a9b1,0x34b7bb8b,0xbc0038bc,0x349338cc,0xba2d3bfe,0x387430a6,0x3b0dbbc3,0xb625b55e,
  0xb63cb074,0xbbf83a76,0xb8653b35,0x37a6294d,0x3bf3bbc9,0x3994bb2f,0x2d65b6a4,0xb889341a,0xb19e3517,0x2f8b2776,0x366bb432,0x3933b840,
  0x3bb5b50b,0xbbe1330f,0x3bfaafef,0xbbff26ad,0xa4523bcb,0x37c8bbba,0xbaba39d6,0x3bf9b523,0xbba1305b,0x35f73970,0x37b2bbfc,0xbbdd38b2,
  0x387abbfe,0xbba53552,0x9cb63a73,0x3babba67,0x39162a16,0x3aa5bbea,0xb790b3ba,0xbb633b89,0xbb5e3bec,0xadc938b7,0x3ab0b6f4,0x3b07bbfe,
  0xaf27b359,0xb9bc370a,0xbbf93b47,0xba973bbc,0x3be0bb96,0x3bf2bbff,0x3b54bbb8,0x3a15bac7,0xafbd3bfb,0x32f7bbe2,0xb4ff3bb7,0x3676bb78,
  0x365fbbe4,0xba453a58,0x3bdfb699,0xbb9eac38,0xb9243bbd,0x3c00b6af,0xb902b6ff,0xb2943bc8,0x3aacbb85,0xba29aade,0xb6313bc5,0x3bf5b815,
  0xbba73b3d,0x324b381a,0x3bf6ba6f,0x9648b95d,0x3c00bae5,0x376fbad5,0xb87f2b43,0xbbf53b42,0xbbb03a7e,0xbb593bfc,0xb75939da,0x32ad3042,
  0x3abdba09,0x3bb3bb4c,0x3c00bbef,0x3b9cbbe3,0x3bf12c9c,0xbbcfb16c,0x3b9a343e,0xbb52b5bc,0xbb57b13b,0x38f838e0,0xb1b6bb4a,0xb4e73bfc,
  0x3a21340e,0x217fbb45,0xba3d3b32,0x3bd4b371,0xb86ab576,0xb91b3bfd,0x3b60b3a2,0x2e91bae1,0x34ab36d2,0x3bd8bade,0xae5fb8c1,0xbc0039f0,
  0x9fdbb80f,0xbb16382a,0xba9e3bfd,0x2ec336bb,0xb46f38ad,0x3654ac06,0x3b1bb974,0x3bd3bbee,0x3850b941,0x3457b68d,0xa51bb010,0xb4f33153,
  0xb7dd3b27,0x3899bac4,0xb9373a50,0x39c9b9cd,0x3990383a,0xb463baee,0xb2c63bff,0x392ebb2c,0x3b18ba60,0xbb5c28e8,0x347b39fc,0x3884bbe6,
  0xb219b966,0xbb133b37,0x39a130d7,0x379bbbeb,0xbbf63962,0xb2323a6b,0x3ba9b820,0x361abb3a,0xb6023a64,0x391fb0f0,0x3bd6bb8e,0x3487b9e3,
  0x3a41b835,0x3c00bb92,0x3a1dbb7f,0x31cfb805,0x3a90bb2a,0x38f3b9d2,0x35d4b7f3,0x2d00b328,0x3af7372c,0xba8cb845,0x3a1138ea,0xb986b982,
  0x39c0bacb,0xbbb237fe,0x3bd2a81f,0xba19b715,0xb764b8d6,0xb6483bfe,0x3baeb94f,0xba9bb109,0xbbda39e7,0x377a36e8,0x39afbbe8,0xbb0a308d,
  0xae2d39eb,0x3bd9b8c7,0x349fbadb,0xbb6536dd,0x3b6ab8d1,0x3a25bbe7,0xb27cb546,0xbbac396b,0x38fdbace,0xa311b52f,0xb9293599,0xbbde3aeb,
  0xb8943721,0xba49397d,0xbb733af1,0xbbfa3bcc,0xbbfb3bff,0xbbe23bf1,0xbbb73bcf,0xbb783b9a,0xbb7c3bf2,0xb9463a93,0xb340374e,0x3426a452,
  0xba603bd4,0xa8e83764,0x39fcb648,0x3be6bbae,0xb8bc3ba5,0x38cc9cb6,0x3b85bbab,0xaadeb86a,0xb56a3b65,0x3bc2b785,0x30bebaa9,0xbbfd3911,
  0xab433b16,0x3b42ba9e,0xba64aec3,0xb0f03b6a,0x33593ab6,0x370abbf3,0xbb473994,0x3bbcad65,0x37f33a49,0xb328bb73,0xac6a3bfa,0x35b1bbd0,
  0xac9c25e4,0xb16c2fbd,0xb43e32f7,0xb5bc34ff,0xb5a52f59,0xba04388e,0xbbcb3b1e,0xbbba3c00,0xb8d63294,0xbbfe3b18,0xb94f3b5c,0x3109347b,
  0xba7334b7,0xba673c00,0x35763493,0x3bfdbaac,0xbb87361a,0xb3d33b10,0x3be9b86f,0x2a7aba31,0xbbfd376f,0x36bb387f,0x38d1bbf5,0xbbe73602,
  0xbbc9385a,0x3b2f2f27,0xb6a4b9bc,0xb41a3bf9,0xbaf138f3,0x3bccb5d4,0xbbfb2d00,0x3b7a32de,0xbb273b52,0xbac43af7,0xba503a8c,0xb9cd3a11,
  0x3979b7c8,0x3b94baba,0x3be4bbf9,0x3a58bb57,0x380aba9b,0xb58dad97,0xbb9039b8,0xbad13bf4,0xbbc5391b,0xb8153b60,0x3966ae91,0x3b37bbda,
  0x2a1639aa,0x3beaba2d,0xb3bab874,0xbb893b0d,0x3b8eba25,0xb9e3b27c,0xb4023bac,0x3bc6b99d,0xb8adb889,0xac063bb0,0x3974bb59,0xbbee3759,
  0xb8e53afb,0x3a85b98b,0xbb963742,0x3bffb19e,0xb72c3676,0xb84537dd,0xb8ea3899,0xb9823937,0xb9d63afe,0xb5233855,0x313b2d33,0x38e0b65f,
  0x3ae8b884,0x3b81bbf8,0x353ab999,0xb8302ef5,0x33a2ba29,0xbae13631,0xb9e73bf5,0x36e83219,0xbbfe39a6,0x30a63916,0x3bc3baa5,0xb55eb790,
  0x3546391f,0x396bbbd6,0xbbbf3487,0x338939b3,0x3a7eba97,0xbbfc346f,0x39da3654,0xb042bb1b,0xba54b7d2,0x38a339c5,0xb517bb21,0x27763be0,
  0xb93c3986,0xb89e38ee,0xb7e8384a,0xb6823737,0x3699b8f8,0xac38b1b6,0xb83a34e7,0xbaee39c0,0xb05b385f,0x3970b4cf,0x3bfcbb6c,0x38b2bb04,
  0xb0d7b77a,0xbbeb39af,0xb6c63b0a,0x39f4b263,0x36d23625,0x3adebba7,0xb8c1b24b,0xb9f03bf6,0xb954b4c3,0xb5813bdc,0x3becb907,0xb8b7b63c,
  0x3ace32ad,0xb52fba41,0xb5993c00,0x3aebba1d,0xbbb8af8b,0x3ac7366b,0xb941b933,0x368d3abd,0xba0d39c9,0xba893a4d,0xbaf43ac1,0xbb4f3b24,
  0x3b4aba45,0x3bfcbbdf,0x3acbbb9e,0x37feb990,0xbbed3ab3,0xb9df3ba1,0x2ba735f7,0x3a7ab7b2,0x3be8bb13,0x308db9a1,0xbb3f379b,0xb9583bd7,
  0xbb3d3b63,0x381a34ab,0x3a6fbbd8,0xb95dae5f,0x39f8bba3,0xbb833201,0x30743a39,0x3a76bb5e,0xb8353bd3,0x3b92b8fd,0xbb7fa311,0x38053929,
  0x3432bbf2,0xb8403b54,0x3a09ba15,0xbb4c3850,0xb50b35c8,0xb30f344b,0xafef3185,0xa6ad2cce,0xbbff3bb2,0xbb2c3bd2,0xb8a83a19,0xb02935df,
  0xb40eb1e8,0xbb453924,0xbb323c00,0xb3713902,0x3ad8bbf7,0xb3ebb60e,0xbbfe3a35,0xb5523aa2,0x39eb1648,0x38c7bbf6,0xbadb3232,0xb6dd3ba9,
  0xb6f43bf8,0x3bfeb865,0xb80fb7a6,0xb82a3c00,0xbbe531cf,0x394a37bd,0xa884bb6f,0xb8db3b9f,0xb010bbb3,0xb1533c00,0x3721bb9c,0xb97d3a90,
  0xbb983b76,0xbbce3bb5,0xbbf03be1,0xbbff3bfa,0x281fb463,0xb71532c6,0xba81392e,0xbbef3b71,0x3bbdbbdd,0x36afba21,0xb6ff217f,0xbbc83a3d,
  0x38252dfb,0x3bc0bb68,0x29b1b90c,0xbb8b387a,0xb9623c00,0x3a6bae2d,0x3820bbd9,0xbb3a349f,0xbb352dc9,0x294d3ab0,0x3ae5bb07,0xbad59fdb,
  0x3122bbde,0xba003b01,0x3bffb5eb,0xba5cb4db,0x3befb457,0xbbe3a51b,0x3b2a34f3,0xb9d2b894,0x39c939cd,0xba4db93c,0x3ac1389e,0xbb24b7e8,
  0x3b1e3946,0xbc00b340,0x3afeb426,0xb8553979,0x3bdd38b2,0xba21340e,0xa17fbb45,0x3a3d3b32,0x3bf53815,0xb2193966,0xbb13bb37,0x39a1b0d7,
  0x3b6536dd,0x37853b87,0xbaa9b3d3,0xb911bbe9,0x3a393581,0x3b5e3bec,0x2dc938b7,0xbab0b6f4,0x3889341a,0x3bb03a7e,0x3b593bfc,0x375939da,
  0x34f33153,0x38943721,0x3a49397d,0x3b733af1,0xb9863982,0x38eeba0d,0xb84a3a89,0x3737baf4,0xb74e3a04,0xa452bbcb,0x37c83bba,0xbabab9d6,
  0xb1e83a7a,0xb924bbbd,0x3c0036af,0xb90236ff,0x2e913ae1,0xbbdab9e7,0x377ab6e8,0x39af3be8,0x361a3b3a,0xbb10b56a,0xb86fbbc2,0x3a3130be,
  0x39073b83,0xb63c3074,0xbbf8ba76,0xb865bb35,0x3a973bbc,0x346f38ad,0xb654ac06,0xbb1bb974,0x3b9c3be3,0x3a903b2a,0x38f339d2,0x35d437f3,
  0x3b763682,0xbbb5b50b,0x3be1330f,0xbbfaafef,0x2d33bb94,0x365f3be4,0xba45ba58,0x3bdf3699,0xbbd4b371,0x3764b8d6,0x36483bfe,0xbbaeb94f,
  0x379b3beb,0xbbd7b6c6,0x2dfbb9f4,0x3b683ad8,0x39aa2a7a,0x3a2d3bfe,0xb87430a6,0xbb0dbbc3,0xbb07bbfe,0x1fdbb80f,0x3b16382a,0x3a9e3bfd,
  0xb2ad3042,0xba41b835,0xbc00bb92,0xba1dbb7f,0x3bfa3bcc,0x3bd03bfb,0x3afb3b7a,0x398b3a54,0xb5c83b4f,0x344bbb98,0xb1853bce,0x2ccebbf0,
  0x3bf93523,0xbb57313b,0x38f8b8e0,0xb1b63b4a,0xb294bbc8,0x3b183a60,0xbb5ca8e8,0x347bb9fc,0xbb0ab08d,0xb263bb3f,0x3bf73958,0xb60e3825,
  0x39a63bfd,0xb9162a16,0xbaa5bbea,0x3790b3ba,0x37a6a94d,0x3c003ae5,0x376f3ad5,0xb87fab43,0xbbd3bbee,0xb8fdbace,0x2311b52f,0x39293599,
  0x2d003328,0xb2deac6a,0xb7d2b5b1,0xb9c5b8e5,0x3bff26ad,0xbbf12c9c,0x3bcfb16c,0xbb9a343e,0xbb9e2c38,0x3990b83a,0xb4633aee,0xb2c6bbff,
  0x3a9bb109,0xad973ae8,0xb9b8bb81,0x3bf4353a,0xb90c33eb,0xb87abbfe,0x3ba53552,0x1cb63a73,0x3625b55e,0x3ba73b3d,0xb24b381a,0xbbf6ba6f,
  0xaec336bb,0xbb6ab8d1,0xba25bbe7,0x327cb546,0xb1cfb805,0x37bd3122,0x3b6f3a00,0x3b9f3bff,0x374238a3,0x319e3517,0xaf8b2776,0xb66bb432,
  0x25e43bff,0xafbdbbfb,0x32f73be2,0xb4ffbbb7,0xb4e7bbfc,0x39c03acb,0xbbb2b7fe,0x3bd2281f,0x38843be6,0xbbf8b80a,0x3999b58d,0x2ef53b90,
  0xba35bbc0,0x3aa229b1,0x34b73b8b,0xbc00b8bc,0x3b633b89,0xb4ab36d2,0xbbd8bade,0x2e5fb8c1,0xbbf5bb42,0xb602ba64,0x391f30f0,0x3bd63b8e,
  0x3bde3aeb,0x3b013be5,0x35eb394a,0xb4db2884,0xbb21ba85,0xbbe0bb96,0xbbf2bbff,0xbb54bbb8,0x3b52b5bc,0xbaf7372c,0x3a8cb845,0xba1138ea,
  0x392e3b2c,0xbb71b8a8,0x3bf23029,0xba9335a5,0xb85f3830,0xb4cfbbed,0x3b6c39df,0xbb042ba7,0xbbabba67,0x386ab576,0x391b3bfd,0xbb60b3a2,
  0x1648b95d,0x3bf63962,0x32323a6b,0xbba9b820,0x3bac396b,0x399d3bbf,0xb4c33389,0xbbdcb9f8,0x385a3a5c,0xaf273359,0xb9bcb70a,0xbbf9bb47,
  0xb933b840,0xbabdba09,0xbbb3bb4c,0xbc00bbef,0x36763b78,0xb7ddbb27,0x38993ac4,0xb937ba50,0xba193715,0x35dfba81,0x2f593bef,0xb88ebb7c,
  0xbab3bad1,0x3ba1305b,0xb5f73970,0xb7b2bbfc,0x3493b8cc,0x3aac3b85,0xba292ade,0xb631bbc5,0x3c0039f0,0x2e2d39eb,0xbbd9b8c7,0xb49fbadb,
  0x348739e3,0xb9b3b402,0xbba3bbc6,0xb201b954,0xbab6b8db,0xbbf3bbc9,0xb994bb2f,0xad65b6a4,0xba15bac7,0xb850b941,0xb457b68d,0x251bb010,
  0xb9cfbb16,0x30ac2a31,0x3b9c3bf1,0xb493ae2d,0xb76fb8b4,0x35a133e3,0x3a1d3afe,0xb902b76f,0xb3e3b5a1,0x38b4376f,0x376f3902,0xbafeba1d,
  0xaa31b0ac,0x3b1639cf,0x2e2d3493,0xbbf1bb9c,0xb956ba74,0x305f29cc,0x3b633bd2,0xb44badc9,0xb6e7b859,0x353f335e,0x39d23ab6,0xb8bcb6ff,
  0xb35eb53f,0x385936e7,0x36ff38bc,0xbab6b9d2,0xa9ccb05f,0x3a743956,0x2dc9344b,0xbbd2bb63,0xb8e3b9de,0x30122967,0x3b1e3ba1,0xb402ad65,
  0xb662b801,0x34de32da,0x39823a67,0xb874b68d,0xb2dab4de,0x38013662,0x368d3874,0xba67b982,0xa967b012,0x39de38e3,0x2d653402,0xbba1bb1e,
  0xb876b952,0x2f8c2902,0x3ace3b60,0xb371ad00,0xb5e1b758,0x347e3257,0x392e3a11,0xb82ab61a,0xb257b47e,0x375835e1,0x361a382a,0xba11b92e,
  0xa902af8c,0x39523876,0x2d003371,0xbb60bace,0xb80db8ce,0x2ef3289e,0x3a733b10,0xb2deac9c,0xb562b6b3,0x342031d5,0x38d639b3,0xb7bdb5a5,
  0xb1d5b420,0x36b33562,0x35a537bd,0xb9b3b8d6,0xa89eaef3,0x38ce380d,0x2c9c32de,0xbb10ba73,0xb750b851,0x2e5a2839,0x3a0d3ab0,0xb24bac38,
  0xb4e5b613,0x33863153,0x387a394f,0xb721b52f,0xb153b386,0x361334e5,0x352f3721,0xb94fb87a,0xa839ae5a,0x38513750,0x2c38324b,0xbab0ba0d,
  0xb68eb7b4,0x2dc227a9,0x399d3a41,0xb1b6aba7,0xb46ab577,0x32cd30d2,0x381a38e5,0xb682b4b7,0xb0d2b2cd,0x3577346a,0x34b73682,0xb8e5b81a,
  0xa7a9adc2,0x37b4368e,0x2ba731b6,0xba41b99d,0xb5d2b6d1,0x2d2a26e0,0x392439c5,0xb122aade,0xb3e3b4de,0x32163052,0x376f3874,0xb5dfb43e,
  0xb052b216,0x34de33e3,0x343e35df,0xb874b76f,0xa6e0ad2a,0x36d135d2,0x2ade3122,0xb9c5b924,0xb51cb5f6,0x2c932617,0x38a3393c,0xb08daa16,
  0xb2f4b448,0x31602fa5,0x36a437fe,0xb53ab389,0xafa5b160,0x344832f4,0x3389353a,0xb7feb6a4,0xa617ac93,0x35f6351c,0x2a16308d,0xb93cb8a3,
  0xb46ab523,0x2bf6254d,0x381a38a8,0xafefa94d,0xb209b36b,0x30ac2ea7,0x35d4370a,0xb493b294,0xaea7b0ac,0x336b3209,0x32943493,0xb70ab5d4,
  0xa54dabf6,0x3523346a,0x294d2fef,0xb8a8b81a,0xb378b456,0x2ac82484,0x3715380a,0xaec3a884,0xb120b24a,0x2ff22da9,0x34ff360e,0xb3d3b19e,
  0xada9aff2,0x324a3120,0x319e33d3,0xb60eb4ff,0xa484aac8,0x34563378,0x28842ec3,0xb80ab715,0xb223b31c,0x29992376,0x35eb36c6,0xad97a776,
  0xb039b12d,0x2e8d2cac,0x3426350b,0xb27cb0a6,0xacacae8d,0x312d3039,0x30a6327c,0xb50bb426,0xa376a999,0x331c3223,0x27762d97,0xb6c6b5eb,
  0xb0d2b194,0x286b21e4,0x34b7356a,0xac6aa5e4,0xaea7b012,0x2d2a2b5f,0x32943402,0xb122af59,0xab5fad2a,0x30122ea7,0x2f593122,0xb402b294,
  0xa1e4a86b,0x319430d2,0x25e42c6a,0xb56ab4b7,0xaf0cb012,0x267b2052,0x32f73402,0xaa7aa452,0xacdeadf5,0x2b912967,0x30d731e8,0xaf8bad65,
  0xa967ab91,0x2df52cde,0x2d652f8b,0xb1e8b0d7,0xa052a67b,0x30122f0c,0x24522a7a,0xb402b2f7,0xac79ad2a,0x24201d7f,0x30743122,0xa81fa17f,
  0xaa31ab91,0x28d026e0,0x2e2d2f8b,0xacceaade,0xa6e0a8d0,0x2b912a31,0x2ade2cce,0xaf8bae2d,0x9d7fa420,0x2d2a2c79,0x217f281f,0xb122b074,
  0xa7a9a86b,0x1f1218b6,0x2ba72c6a,0xa3119cb6,0xa54da67b,0x242021e4,0x294d2a7a,0xa81fa5e4,0xa1e4a420,0x267b254d,0x25e4281f,0xaa7aa94d,
  0x98b69f12,0x286b27a9,0x1cb62311,0xac6aaba7,0x211b21e4,0x98b69248,0xa51ba5e4,0x1cb61648,0x1f122052,0x9d7f9bdb,0xa311a452,0x217f1fdb,
  0x1bdb1d7f,0xa0529f12,0x9fdba17f,0x24522311,0x124818b6,0xa1e4a11b,0x96489cb6,0x25e4251b,0x2a632b5f,0xa1e49bdb,0xae5faf59,0x25e41fdb,
  0x286b2967,0xa6e0a4e9,0xac6aad65,0x2ade28e8,0x24e926e0,0xa967a86b,0xa8e8aade,0x2d652c6a,0x1bdb21e4,0xab5faa63,0x9fdba5e4,0x2f592e5f,
  0x2dc22ea7,0xa54d9f12,0xb1b6b294,0x294d2311,0x2bf62cde,0xaa31a86b,0xafefb0d7,0x2e2d2c6a,0x286b2a31,0xacdeabf6,0xac6aae2d,0x30d72fef,
  0x1f12254d,0xaea7adc2,0xa311a94d,0x329431b6,0x302c30d2,0xa7a9a11b,0xb41ab4b7,0x2ba7251b,0x2dc22f0c,0xac79aa63,0xb1b6b2f7,0x30742e5f,
  0x2a632c79,0xaf0cadc2,0xae5fb074,0x32f731b6,0x211b27a9,0xb0d2b02c,0xa51baba7,0x34b7341a,0x317a3257,0xa902a2ad,0xb552b61a,0x2d0026ad,
  0x2f8c309f,0xaddcac2e,0xb371b487,0x31cf3029,0x2c2e2ddc,0xb09faf8c,0xb029b1cf,0x34873371,0x22ad2902,0xb257b17a,0xa6adad00,0x361a3552,
  0x32cd33e3,0xaa31a420,0xb682b76f,0x2e2d281f,0x30ac31bb,0xaf3fad2a,0xb493b58d,0x33283122,0x2d2a2f3f,0xb1bbb0ac,0xb122b328,0x358d3493,
  0x24202a31,0xb3e3b2cd,0xa81fae2d,0x376f3682,0x341334bc,0xab5fa4e9,0xb7a6b85a,0x2f5928e8,0x319432da,0xb052ae28,0xb56ab68d,0x343e3219,
  0x2e283052,0xb2dab194,0xb219b43e,0x368d356a,0x24e92b5f,0xb4bcb413,0xa8e8af59,0x385a37a6,0x34c3358c,0xac47a5b2,0xb85fb8f3,0x304229b1,
  0x327e33fd,0xb106af26,0xb63cb785,0x34e7330f,0x2f263106,0xb3fdb27e,0xb30fb4e7,0x3785363c,0x25b22c47,0xb58cb4c3,0xa9b1b042,0x38f3385f,
  0x35773662,0xacdea67b,0xb8e5b982,0x30d72a7a,0x336b3493,0xb1bbb012,0xb70ab83a,0x358d3402,0x301231bb,0xb493b36b,0xb402b58d,0x383a370a,
  0x267b2cde,0xb662b577,0xaa7ab0d7,0x398238e5,0x36303741,0xad76a744,0xb962ba04,0x316c2b43,0x342e352a,0xb271b092,0xb7d2b8ad,0x3631347b,
  0x30923271,0xb52ab42e,0xb47bb631,0x38ad37d2,0x27442d76,0xb741b630,0xab43b16c,0x3a043962,0x36ee3815,0xae0ea807,0xb9d6ba7a,0x32012c06,
  0x34a735c4,0xb329b113,0xb84ab91b,0x36d234f3,0x31133329,0xb5c4b4a7,0xb4f3b6d2,0x391b384a,0x28072e0e,0xb815b6ee,0xac06b201,0x3a7a39d6,
  0x37b4388e,0xaea7a86b,0xba41bae1,0x32942c6a,0x35233662,0xb3e3b194,0xb8a8b982,0x376f356a,0x319433e3,0xb662b523,0xb56ab76f,0x398238a8,
  0x286b2ea7,0xb88eb7b4,0xac6ab294,0x3ae13a41,0x3841390f,0xaf3fa8d0,0xbaa2bb3a,0x33282cce,0x35a13705,0xb44fb216,0xb902b9e3,0x380535df,
  0x3216344f,0xb705b5a1,0xb5dfb805,0x39e33902,0x28d02f3f,0xb90fb841,0xacceb328,0x3b3a3aa2,0x38ac3997,0xafd8a935,0xbaf7bb83,0x33ba2d33,
  0x362137ac,0xb4aeb298,0xb958ba3d,0x38503654,0x329834ae,0xb7acb621,0xb654b850,0x3a3d3958,0x29352fd8,0xb997b8ac,0xad33b3ba,0x3b833af7,
  0x391c3a28,0xb039a999,0xbb42bbbc,0x34262d97,0x36a4382d,0xb50eb31c,0xb9aaba90,0x389936c6,0x331c350e,0xb82db6a4,0xb6c6b899,0x3a9039aa,
  0x29993039,0xba28b91c,0xad97b426,0x3bbc3b42,0x39923ac3,0xb085a9fe,0xbb81bbe3,0x346f2dfb,0x372a3886,0xb570b3a0,0xb9f8badb,0x38e03737,
  0x33a03570,0xb886b72a,0xb737b8e0,0x3adb39f8,0x29fe3085,0xbac3b992,0xadfbb46f,0x3be33b81,
};

#define PROF(slot) do {} while (0)
#define PROF_DUMP() do {} while (0)
#define PROFA(slot, dep) do {} while (0)
#define PROF3(slot) do {} while (0)
#define PROF2(slot) do {} while (0)

__device__ __forceinline__ uint32_t smem_u32(const void* p) { return (uint32_t)__cvta_generic_to_shared(p); }

__device__ __forceinline__ void mbar_init(uint32_t a, uint32_t c) {
  asm volatile("mbarrier.init.shared::cta.b64 [%0], %1;\n" ::"r"(a), "r"(c) : "memory");
}
__device__ __forceinline__ void mbar_expect_tx(uint32_t a, uint32_t bytes) {
  asm volatile("mbarrier.arrive.expect_tx.shared::cta.b64 _, [%0], %1;\n" ::"r"(a), "r"(bytes) : "memory");
}
__device__ __forceinline__ void mbar_arrive_cluster(uint32_t cluster_addr) {
  asm volatile("mbarrier.arrive.shared::cluster.b64 _, [%0];\n" ::"r"(cluster_addr) : "memory");
}
__device__ __forceinline__ void mbar_arrive_cluster_n(uint32_t cluster_addr, uint32_t n) {
  asm volatile("mbarrier.arrive.shared::cluster.b64 _, [%0], %1;\n" ::"r"(cluster_addr), "r"(n) : "memory");
}
__device__ __forceinline__ bool mbar_try(uint32_t a, uint32_t parity) {
  uint32_t ok;
  asm volatile("{\n.reg .pred p;\nmbarrier.try_wait.parity.shared::cta.b64 p, [%1], %2;\nselp.u32 %0, 1, 0, p;\n}\n"
               : "=r"(ok) : "r"(a), "r"(parity) : "memory");
  return ok;
}
__device__ __forceinline__ void mbar_wait(uint32_t a, uint32_t parity) {
  if (mbar_try(a, parity)) return;
#pragma unroll 1
  for (int n = 0; n < SPIN_LIMIT; n++)
    if (mbar_try(a, parity)) break;
}
__device__ __forceinline__ bool elect_one() {
  uint32_t p;
  asm volatile("{\n.reg .pred P;\nelect.sync _|P, 0xffffffff;\nselp.u32 %0, 1, 0, P;\n}\n" : "=r"(p));
  return p;
}
__device__ __forceinline__ uint32_t mapa(uint32_t a, uint32_t rank) {
  uint32_t r;
  asm volatile("mapa.shared::cluster.u32 %0, %1, %2;\n" : "=r"(r) : "r"(a), "r"(rank));
  return r;
}
__device__ __forceinline__ void nb_sync(int id, int n) { asm volatile("bar.sync %0, %1;\n" ::"r"(id), "r"(n) : "memory"); }
__device__ __forceinline__ void nb_arrive(int id, int n) { asm volatile("bar.arrive %0, %1;\n" ::"r"(id), "r"(n) : "memory"); }
__device__ __forceinline__ void cluster_sync_all() {
  asm volatile("barrier.cluster.arrive.relaxed.aligned;\nbarrier.cluster.wait.aligned;\n" ::: "memory");
}
__device__ __forceinline__ void fence_async_smem() { asm volatile("fence.proxy.async.shared::cta;\n" ::: "memory"); }
__device__ __forceinline__ void fence_async_all() { asm volatile("fence.proxy.async.global;\n" ::: "memory"); }

__device__ __forceinline__ void tma_load_3d(uint32_t dst, const CUtensorMap* tm, uint32_t bar, int c0, int c1, int c2) {
  asm volatile(
      "cp.async.bulk.tensor.3d.shared::cluster.global.mbarrier::complete_tx::bytes [%0], [%1, {%3, %4, %5}], [%2];\n"
      ::"r"(dst), "l"(tm), "r"(bar), "r"(c0), "r"(c1), "r"(c2) : "memory");
}
__device__ __forceinline__ void tma_load_4d(uint32_t dst, const CUtensorMap* tm, uint32_t bar, int c0, int c1, int c2, int c3) {
  asm volatile(
      "cp.async.bulk.tensor.4d.shared::cluster.global.mbarrier::complete_tx::bytes [%0], [%1, {%3, %4, %5, %6}], [%2];\n"
      ::"r"(dst), "l"(tm), "r"(bar), "r"(c0), "r"(c1), "r"(c2), "r"(c3) : "memory");
}
__device__ __forceinline__ void tma_load_3d_mc(uint32_t dst, const CUtensorMap* tm, uint32_t bar, int c0, int c1, int c2) {
  asm volatile(
      "cp.async.bulk.tensor.3d.shared::cluster.global.mbarrier::complete_tx::bytes.multicast::cluster [%0], [%1, {%3, %4, %5}], [%2], %6;\n"
      ::"r"(dst), "l"(tm), "r"(bar), "r"(c0), "r"(c1), "r"(c2), "h"((uint16_t)3) : "memory");
}
__device__ __forceinline__ void bulk_load(uint32_t dst, const void* src, uint32_t bytes, uint32_t bar) {
  asm volatile("cp.async.bulk.shared::cluster.global.mbarrier::complete_tx::bytes [%0], [%1], %2, [%3];\n"
               ::"r"(dst), "l"(src), "r"(bytes), "r"(bar) : "memory");
}
__device__ __forceinline__ void tma_store_3d(const CUtensorMap* tm, uint32_t src, int c0, int c1, int c2) {
  asm volatile("cp.async.bulk.tensor.3d.global.shared::cta.bulk_group [%0, {%2, %3, %4}], [%1];\n"
               ::"l"(tm), "r"(src), "r"(c0), "r"(c1), "r"(c2) : "memory");
}
__device__ __forceinline__ void bulk_commit() { asm volatile("cp.async.bulk.commit_group;\n" ::: "memory"); }
__device__ __forceinline__ void bulk_wait0() { asm volatile("cp.async.bulk.wait_group 0;\n" ::: "memory"); }
__device__ __forceinline__ void prefetch_tmap(const CUtensorMap* tm) {
  asm volatile("prefetch.tensormap [%0];\n" ::"l"(tm) : "memory");
}

__device__ __forceinline__ void wg_fence() { asm volatile("wgmma.fence.sync.aligned;\n" ::: "memory"); }
__device__ __forceinline__ void wg_commit() { asm volatile("wgmma.commit_group.sync.aligned;\n" ::: "memory"); }
template <int N> __device__ __forceinline__ void wg_wait() {
  asm volatile("wgmma.wait_group.sync.aligned %0;\n" ::"n"(N) : "memory");
}
__device__ __forceinline__ uint64_t mkdesc(uint32_t addr, uint32_t lbo, uint32_t sbo, uint32_t swz) {
  return (uint64_t)((addr & 0x3FFFF) >> 4) | ((uint64_t)(lbo >> 4) << 16) | ((uint64_t)(sbo >> 4) << 32) |
         ((uint64_t)swz << 62);
}

#define R4(d, o) "+f"(d[o + 0]), "+f"(d[o + 1]), "+f"(d[o + 2]), "+f"(d[o + 3])
#define R8(d, o) R4(d, o), R4(d, o + 4)
#define R16(d, o) R8(d, o), R8(d, o + 8)
#define R32(d, o) R16(d, o), R16(d, o + 16)
#define R64(d, o) R32(d, o), R32(d, o + 32)

__device__ __forceinline__ void wgmma_n192(float (&d)[96], uint64_t da, uint64_t db, uint32_t acc) {
  asm volatile(
      "{\n.reg .pred p;\nsetp.ne.u32 p, %98, 0;\n"
      "wgmma.mma_async.sync.aligned.m64n192k16.f32.bf16.bf16 "
      "{%0,%1,%2,%3,%4,%5,%6,%7,%8,%9,%10,%11,%12,%13,%14,%15,%16,%17,%18,%19,%20,%21,%22,%23,%24,%25,%26,%27,%28,%29,%30,%31,"
      "%32,%33,%34,%35,%36,%37,%38,%39,%40,%41,%42,%43,%44,%45,%46,%47,%48,%49,%50,%51,%52,%53,%54,%55,%56,%57,%58,%59,%60,%61,%62,%63,"
      "%64,%65,%66,%67,%68,%69,%70,%71,%72,%73,%74,%75,%76,%77,%78,%79,%80,%81,%82,%83,%84,%85,%86,%87,%88,%89,%90,%91,%92,%93,%94,%95}, "
      "%96, %97, p, 1, 1, 0, 1;\n}\n"
      : R64(d, 0), R32(d, 64)
      : "l"(da), "l"(db), "r"(acc));
}
__device__ __forceinline__ void wgmma_n128(float (&d)[64], uint64_t da, uint64_t db, uint32_t acc) {
  asm volatile(
      "{\n.reg .pred p;\nsetp.ne.u32 p, %66, 0;\n"
      "wgmma.mma_async.sync.aligned.m64n128k16.f32.bf16.bf16 "
      "{%0,%1,%2,%3,%4,%5,%6,%7,%8,%9,%10,%11,%12,%13,%14,%15,%16,%17,%18,%19,%20,%21,%22,%23,%24,%25,%26,%27,%28,%29,%30,%31,"
      "%32,%33,%34,%35,%36,%37,%38,%39,%40,%41,%42,%43,%44,%45,%46,%47,%48,%49,%50,%51,%52,%53,%54,%55,%56,%57,%58,%59,%60,%61,%62,%63}, "
      "%64, %65, p, 1, 1, 0, 1;\n}\n"
      : R64(d, 0)
      : "l"(da), "l"(db), "r"(acc));
}
template <int N> __device__ __forceinline__ void fence_regs(float (&d)[N]) {
#pragma unroll
  for (int i = 0; i < N; i++) asm volatile("" : "+f"(d[i])::"memory");
}

__device__ __forceinline__ void mma16816(float (&d)[4], uint32_t a0, uint32_t a1, uint32_t a2, uint32_t a3, uint32_t b0,
                                         uint32_t b1) {
  asm("mma.sync.aligned.m16n8k16.row.col.f32.bf16.bf16.f32 {%0,%1,%2,%3}, {%4,%5,%6,%7}, {%8,%9}, {%0,%1,%2,%3};\n"
      : "+f"(d[0]), "+f"(d[1]), "+f"(d[2]), "+f"(d[3])
      : "r"(a0), "r"(a1), "r"(a2), "r"(a3), "r"(b0), "r"(b1));
}
__device__ __forceinline__ void mma16816_z(float (&d)[4], uint32_t a0, uint32_t a1, uint32_t a2, uint32_t a3, uint32_t b0,
                                           uint32_t b1) {
  asm("mma.sync.aligned.m16n8k16.row.col.f32.bf16.bf16.f32 {%0,%1,%2,%3}, {%4,%5,%6,%7}, {%8,%9}, {%10,%10,%10,%10};\n"
      : "=f"(d[0]), "=f"(d[1]), "=f"(d[2]), "=f"(d[3])
      : "r"(a0), "r"(a1), "r"(a2), "r"(a3), "r"(b0), "r"(b1), "f"(0.f));
}
__device__ __forceinline__ void ldsm4t(uint32_t (&r)[4], uint32_t a) {
  asm volatile("ldmatrix.sync.aligned.m8n8.x4.trans.shared.b16 {%0,%1,%2,%3}, [%4];\n"
               : "=r"(r[0]), "=r"(r[1]), "=r"(r[2]), "=r"(r[3]) : "r"(a) : "memory");
}
__device__ __forceinline__ void ldsm2t(uint32_t& r0, uint32_t& r1, uint32_t a) {
  asm volatile("ldmatrix.sync.aligned.m8n8.x2.trans.shared.b16 {%0,%1}, [%2];\n" : "=r"(r0), "=r"(r1) : "r"(a) : "memory");
}
__device__ __forceinline__ void st_async128(uint32_t a, uint32_t bar, uint32_t x, uint32_t y, uint32_t z, uint32_t w) {
  asm volatile("st.async.weak.shared::cluster.mbarrier::complete_tx::bytes.v4.b32 [%0], {%2,%3,%4,%5}, [%1];\n"
               ::"r"(a), "r"(bar), "r"(x), "r"(y), "r"(z), "r"(w) : "memory");
}
__device__ __forceinline__ void mbar_arrive(uint32_t a) {
  asm volatile("mbarrier.arrive.shared::cta.b64 _, [%0];\n" ::"r"(a) : "memory");
}
__device__ __forceinline__ void stsm4(uint32_t a, uint32_t r0, uint32_t r1, uint32_t r2, uint32_t r3) {
  asm volatile("stmatrix.sync.aligned.m8n8.x4.shared.b16 [%0], {%1,%2,%3,%4};\n"
               ::"r"(a), "r"(r0), "r"(r1), "r"(r2), "r"(r3) : "memory");
}
__device__ __forceinline__ void stsm4t(uint32_t a, uint32_t r0, uint32_t r1, uint32_t r2, uint32_t r3) {
  asm volatile("stmatrix.sync.aligned.m8n8.x4.trans.shared.b16 [%0], {%1,%2,%3,%4};\n"
               ::"r"(a), "r"(r0), "r"(r1), "r"(r2), "r"(r3) : "memory");
}
__device__ __forceinline__ uint2 lds64(uint32_t a) {
  uint2 v;
  asm volatile("ld.shared.v2.u32 {%0,%1}, [%2];\n" : "=r"(v.x), "=r"(v.y) : "r"(a));
  return v;
}
__device__ __forceinline__ uint4 lds128(uint32_t a) {
  uint4 v;
  asm volatile("ld.shared.v4.u32 {%0,%1,%2,%3}, [%4];\n" : "=r"(v.x), "=r"(v.y), "=r"(v.z), "=r"(v.w) : "r"(a) : "memory");
  return v;
}
__device__ __forceinline__ void sts128(uint32_t a, uint32_t x, uint32_t y, uint32_t z, uint32_t w) {
  asm volatile("st.shared.v4.u32 [%0], {%1,%2,%3,%4};\n" ::"r"(a), "r"(x), "r"(y), "r"(z), "r"(w) : "memory");
}
__device__ __forceinline__ void sts64(uint32_t a, uint32_t x, uint32_t y) {
  asm volatile("st.shared.v2.u32 [%0], {%1,%2};\n" ::"r"(a), "r"(x), "r"(y) : "memory");
}
__device__ __forceinline__ uint32_t pack_bf16(float lo, float hi) {
  uint32_t r;
  asm("cvt.rn.bf16x2.f32 %0, %1, %2;\n" : "=r"(r) : "f"(hi), "f"(lo));
  return r;
}
__device__ __forceinline__ uint32_t bmul2(uint32_t a, uint32_t b) {
  uint32_t r;
  asm("mul.rn.bf16x2 %0, %1, %2;\n" : "=r"(r) : "r"(a), "r"(b));
  return r;
}
__device__ __forceinline__ uint32_t bmax2(uint32_t a, uint32_t b) {
  uint32_t r;
  asm("max.bf16x2 %0, %1, %2;\n" : "=r"(r) : "r"(a), "r"(b));
  return r;
}
__device__ __forceinline__ uint32_t bfma2(uint32_t a, uint32_t b, uint32_t c) {
  uint32_t r;
  asm("fma.rn.bf16x2 %0, %1, %2, %3;\n" : "=r"(r) : "r"(a), "r"(b), "r"(c));
  return r;
}
__device__ __forceinline__ uint32_t badd2(uint32_t a, uint32_t b) {
  uint32_t r;
  asm("add.rn.bf16x2 %0, %1, %2;\n" : "=r"(r) : "r"(a), "r"(b));
  return r;
}
__device__ __forceinline__ void prefetch_l2(const void* p) { asm volatile("prefetch.global.L2 [%0];\n" ::"l"(p)); }
__device__ __forceinline__ void cp_async16n(uint32_t dst, const void* src) {
  asm volatile("cp.async.cg.shared.global [%0], [%1], 16;\n" ::"r"(dst), "l"(src) : "memory");
}
__device__ __forceinline__ void cp_async16(uint32_t dst, const void* src, uint32_t srcbytes) {
  asm volatile("cp.async.cg.shared.global.L2::256B [%0], [%1], 16, %2;\n" ::"r"(dst), "l"(src), "r"(srcbytes) : "memory");
}
__device__ __forceinline__ uint32_t ld_acquire(const uint32_t* p) {
  uint32_t v;
  asm volatile("ld.acquire.gpu.global.u32 %0, [%1];\n" : "=r"(v) : "l"(p) : "memory");
  return v;
}
__device__ __forceinline__ uint32_t ld_relaxed(const uint32_t* p) {
  uint32_t v;
  asm volatile("ld.relaxed.gpu.global.u32 %0, [%1];\n" : "=r"(v) : "l"(p) : "memory");
  return v;
}
__device__ __forceinline__ void st_release(uint32_t* p, uint32_t v) {
  asm volatile("st.release.gpu.global.u32 [%0], %1;\n" ::"l"(p), "r"(v) : "memory");
}
__device__ __forceinline__ void wait_flag(const uint32_t* p, uint32_t want) {
  int n = 0;
  while (ld_acquire(p) != want && ++n < SPIN_LIMIT) {}
}

struct Params {
  const __nv_bfloat16* x;
  const __nv_bfloat16* w;
  const __nv_bfloat16* q;
  const __nv_bfloat16* k;
  const __nv_bfloat16* v;
  const __nv_bfloat16* shift_k;
  const __nv_bfloat16* ssm_k;
  const __nv_bfloat16* ssm_D;
  const __nv_bfloat16* wo;
  __nv_bfloat16* out;
  uint32_t zero;
};

__device__ __forceinline__ uint32_t lds32(uint32_t a) {
  uint32_t v;
  asm volatile("ld.shared.u32 %0, [%1];\n" : "=r"(v) : "r"(a));
  return v;
}
__device__ __forceinline__ float bf_lo(uint32_t v) {
  uint32_t r;
  asm("prmt.b32 %0, %1, 0, 0x1044;\n" : "=r"(r) : "r"(v));
  return __uint_as_float(r);
}
__device__ __forceinline__ float bf_hi(uint32_t v) { return __uint_as_float(v & 0xffff0000u); }
__device__ __forceinline__ float ex2(float x) {
  float r;
  asm("ex2.approx.ftz.f32 %0, %1;\n" : "=f"(r) : "f"(x));
  return r;
}
__device__ __forceinline__ float rcp(float x) {
  float r;
  asm("rcp.approx.ftz.f32 %0, %1;\n" : "=f"(r) : "f"(x));
  return r;
}

#define Q4(c, d, o) c(d[o + 0]), c(d[o + 1]), c(d[o + 2]), c(d[o + 3])
#define Q8(c, d, o) Q4(c, d, o), Q4(c, d, o + 4)
#define Q16(c, d, o) Q8(c, d, o), Q8(c, d, o + 8)
#define Q32(c, d) Q16(c, d, 0), Q16(c, d, 16)
#define L8 "{%0,%1,%2,%3,%4,%5,%6,%7}"
#define L16 "{%0,%1,%2,%3,%4,%5,%6,%7,%8,%9,%10,%11,%12,%13,%14,%15}"
#define L32 "{%0,%1,%2,%3,%4,%5,%6,%7,%8,%9,%10,%11,%12,%13,%14,%15,%16,%17,%18,%19,%20,%21,%22,%23,%24,%25,%26,%27,%28,%29,%30,%31}"
__device__ __forceinline__ void fft_rows(uint32_t (&d)[32], const uint32_t (&a)[2][4], uint64_t db) {
  asm volatile("wgmma.mma_async.sync.aligned.m64n128k16.f16.f16.f16 " L32 ", {%32,%33,%34,%35}, %36, 0, 1, 1, 1;\n"
               : Q32("=r", d) : "r"(a[0][0]), "r"(a[0][1]), "r"(a[0][2]), "r"(a[0][3]), "l"(db));
  asm volatile("wgmma.mma_async.sync.aligned.m64n128k16.f16.f16.f16 " L32 ", {%32,%33,%34,%35}, %36, 1, 1, 1, 1;\n"
               : Q32("+r", d) : "r"(a[1][0]), "r"(a[1][1]), "r"(a[1][2]), "r"(a[1][3]), "l"(db + 128));
}
template <int INV> __device__ __forceinline__ void fft_cols(uint32_t (&d)[8], const uint32_t (&a)[2][4], uint64_t db) {
  asm volatile("wgmma.mma_async.sync.aligned.m64n32k16.f16.f16.f16 " L8 ", {%8,%9,%10,%11}, %12, 0, 1, 1, %13;\n"
               : Q8("=r", d, 0) : "r"(a[0][0]), "r"(a[0][1]), "r"(a[0][2]), "r"(a[0][3]), "l"(db), "n"(INV));
  asm volatile("wgmma.mma_async.sync.aligned.m64n32k16.f16.f16.f16 " L8 ", {%8,%9,%10,%11}, %12, 1, 1, 1, %13;\n"
               : Q8("+r", d, 0) : "r"(a[1][0]), "r"(a[1][1]), "r"(a[1][2]), "r"(a[1][3]), "l"(db + (INV ? 16 : 64)), "n"(INV));
}
__device__ __forceinline__ void fft_back(float (&d)[16], uint64_t da, uint64_t db) {
  asm volatile("wgmma.mma_async.sync.aligned.m64n32k16.f32.f16.f16 " L16 ", %16, %17, 0, 1, 1, 1, 1;\n"
               : Q16("=f", d, 0) : "l"(da), "l"(db));
#pragma unroll
  for (int i = 1; i < 4; i++)
    asm volatile("wgmma.mma_async.sync.aligned.m64n32k16.f32.f16.f16 " L16 ", %16, %17, 1, 1, 1, 1, 1;\n"
                 : Q16("+f", d, 0) : "l"(da + 32 * i), "l"(db + 64 * i));
}
__device__ __forceinline__ uint32_t hmul2(uint32_t a, uint32_t b) {
  uint32_t r;
  asm("mul.rn.f16x2 %0, %1, %2;\n" : "=r"(r) : "r"(a), "r"(b));
  return r;
}
__device__ __forceinline__ uint32_t hadd2(uint32_t a, uint32_t b) {
  uint32_t r;
  asm("add.rn.f16x2 %0, %1, %2;\n" : "=r"(r) : "r"(a), "r"(b));
  return r;
}
__device__ __forceinline__ uint32_t hneg2(uint32_t a) {
  uint32_t r;
  asm("neg.f16x2 %0, %1;\n" : "=r"(r) : "r"(a));
  return r;
}
__device__ __forceinline__ uint32_t hfma2(uint32_t a, uint32_t b, uint32_t c) {
  uint32_t r;
  asm("fma.rn.f16x2 %0, %1, %2, %3;\n" : "=r"(r) : "r"(a), "r"(b), "r"(c));
  return r;
}
__device__ __forceinline__ uint32_t pack_f16(float lo, float hi) {
  uint32_t r;
  asm("cvt.rn.f16x2.f32 %0, %1, %2;\n" : "=r"(r) : "f"(hi), "f"(lo));
  return r;
}
__device__ __forceinline__ uint32_t bmaxabs2(uint32_t a, uint32_t b) {
  uint32_t r;
  asm("max.xorsign.abs.bf16x2 %0, %1, %2;\n" : "=r"(r) : "r"(a), "r"(b));
  return r;
}
struct C2 { uint32_t r, i; };
__device__ __forceinline__ C2 cmul(C2 a, C2 b) {
  return C2{hfma2(a.r, b.r, hneg2(hmul2(a.i, b.i))), hfma2(a.r, b.i, hmul2(a.i, b.r))};
}
__device__ __forceinline__ C2 cfma(C2 a, C2 b, C2 c) {
  return C2{hfma2(a.r, b.r, hfma2(hneg2(a.i), b.i, c.r)), hfma2(a.r, b.i, hfma2(a.i, b.r, c.i))};
}
__device__ __forceinline__ C2 crot(C2 z, C2 t) {
  const uint32_t r = hfma2(t.r, z.i, z.r), i = hfma2(t.i, r, z.i);
  return C2{hfma2(t.r, i, r), i};
}
__device__ __forceinline__ C2 cget(const uint32_t (&e)[8], int j, int b) { return C2{e[4 * j + b], e[4 * j + 2 + b]}; }
template <int N> __device__ __forceinline__ void fence_regs(uint32_t (&d)[N]) {
#pragma unroll
  for (int i = 0; i < N; i++) asm volatile("" : "+r"(d[i])::"memory");
}
__device__ __forceinline__ void ldsm4(uint32_t (&r)[4], uint32_t a) {
  asm volatile("ldmatrix.sync.aligned.m8n8.x4.shared.b16 {%0,%1,%2,%3}, [%4];\n"
               : "=r"(r[0]), "=r"(r[1]), "=r"(r[2]), "=r"(r[3]) : "r"(a) : "memory");
}

__device__ __forceinline__ uint32_t movm(uint32_t a) {
  uint32_t r;
  asm volatile("movmatrix.sync.aligned.m8n8.trans.b16 %0, %1;\n" : "=r"(r) : "r"(a));
  return r;
}
template <int C0, int H, bool T> __device__ __forceinline__ void attn_pack(const float (&acc)[96], uint32_t (&d)[8]) {
#pragma unroll
  for (int c = 0; c < 8; c++) {
    asm volatile("cvt.rn.bf16x2.f32 %0, %1, %2;\n" : "=r"(d[c]) : "f"(acc[4 * (C0 + c) + 2 * H + 1]), "f"(acc[4 * (C0 + c) + 2 * H]));
    if (T) d[c] = movm(d[c]);
  }
}
__device__ __forceinline__ void attn_qk(float (&s)[4], const uint32_t (&qlo)[8], const uint32_t (&qhi)[8],
                                        const uint32_t (&k)[8], int c) {
  mma16816_z(s, qlo[c], qhi[c], qlo[c + 1], qhi[c + 1], k[c], k[c + 1]);
  mma16816(s, qlo[c + 2], qhi[c + 2], qlo[c + 3], qhi[c + 3], k[c + 2], k[c + 3]);
}
template <int N> __device__ __forceinline__ void quad_softmax(float (&x)[N][2], uint32_t (&pp)[N]) {
  const float c2 = 1.4426950408889634f;
  uint32_t q[N], mx[N / 2];
#pragma unroll
  for (int n = 0; n < N; n++) {
    const uint32_t r = pack_bf16(x[n][0], x[n][1]);
    q[n] = bfma2(r, 0x3e353e35u, bmul2(r, 0x379e379eu));
    x[n][0] = bf_lo(q[n]);
    x[n][1] = bf_hi(q[n]);
  }
#pragma unroll
  for (int n = 0; n < N / 2; n++)
    mx[n] = bmax2(__byte_perm(q[2 * n], q[2 * n + 1], 0x5410), __byte_perm(q[2 * n], q[2 * n + 1], 0x7632));
#pragma unroll
  for (int o = 1; o <= 2; o++) {
#pragma unroll
    for (int n = 0; n < N / 2; n++) mx[n] = bmax2(mx[n], __shfl_xor_sync(0xffffffffu, mx[n], o));
  }
  float m[N], t[N];
#pragma unroll
  for (int n = 0; n < N / 2; n++) {
    m[2 * n] = bf_lo(mx[n]);
    m[2 * n + 1] = bf_hi(mx[n]);
  }
#pragma unroll
  for (int n = 0; n < N; n++) {
    const float nm = -m[n] * c2;
    x[n][0] = ex2(fmaf(x[n][0], c2, nm));
    x[n][1] = ex2(fmaf(x[n][1], c2, nm));
  }
#pragma unroll
  for (int n = 0; n < N; n += 2) {
    float u0, u1;
    asm("mma.sync.aligned.m16n8k8.row.col.f32.tf32.tf32.f32 {%0,%1,%2,%3}, {%4,%5,%6,%7}, {%8,%8}, {%9,%9,%9,%9};\n"
        : "=f"(t[n]), "=f"(u0), "=f"(t[n + 1]), "=f"(u1)
        : "r"(__float_as_uint(x[n][0])), "r"(__float_as_uint(x[n + 1][0])), "r"(__float_as_uint(x[n][1])),
          "r"(__float_as_uint(x[n + 1][1])), "r"(0x3f800000u), "f"(0.f));
  }
#pragma unroll
  for (int n = 0; n < N; n++) {
    const float inv = rcp(t[n]);
    pp[n] = pack_bf16(x[n][0] * inv, x[n][1] * inv);
  }
}
__device__ __forceinline__ void attn_pv(uint32_t dst, const uint32_t (&vp)[8], const uint32_t (&vo)[8], int c, uint32_t pp,
                                        uint32_t maskLE) {
  const uint32_t b0 = pp & ~maskLE, b1 = pp & maskLE;
  float oa[4], ob[4];
  mma16816_z(oa, vp[c], vp[c + 1], vo[c], vo[c + 1], b0, b1);
  mma16816_z(ob, vp[c + 2], vp[c + 3], vo[c + 2], vo[c + 3], b0, b1);
  stsm4t(dst, pack_bf16(oa[0], oa[1]), pack_bf16(oa[2], oa[3]), pack_bf16(ob[0], ob[1]), pack_bf16(ob[2], ob[3]));
}

template <int MODE>
__global__ void __cluster_dims__(2, 1, 1) __launch_bounds__(NTHREADS, 1)
fused_kernel(const Params p, const __grid_constant__ CUtensorMap tmX, const __grid_constant__ CUtensorMap tmW,
             const __grid_constant__ CUtensorMap tmWo, const __grid_constant__ CUtensorMap tmQ,
             const __grid_constant__ CUtensorMap tmOb,
             const __grid_constant__ CUtensorMap tmXh, const __grid_constant__ CUtensorMap tmWh) {
  extern __shared__ __align__(1024) uint8_t smem[];
  if (threadIdx.x < 32) {
    const uint32_t i = (blockIdx.x & 127) * 16 + (threadIdx.x & 15);
    prefetch_l2(threadIdx.x & 16 ? (const char*)p.w + i * 128 : (const char*)p.x + i * 2048);
  }
  const uint32_t sb = smem_u32(smem);
  const uint32_t bars = sb + OFF_BAR;
  const int tid = threadIdx.x, lane = tid & 31, warp = __shfl_sync(0xffffffffu, tid >> 5, 0);
  const int rank = blockIdx.x & 1;
  const bool halo_cta = blockIdx.x < 4;
  if (halo_cta && MODE != 0) return;
  int grp, mem;
  {
    const int t = (blockIdx.x >> 1) - 4, u = t - 32;
    const int q7 = (u * 37) >> 8;
    const bool lo = (unsigned)t < 32u, mid = (unsigned)u < 28u;
    grp = lo ? (t & 7) : (mid ? 1 + u - 7 * q7 : 0);
    mem = lo ? (t >> 3) : (mid ? 4 + q7 : (t < 0 ? t + 6 : t - 54));
  }
  const int rg = (grp >> 2) * 4 + (mem >> 1), hp = (grp & 3) * 4 + (mem & 1) * 2 + rank;
  const int rb2 = (grp >> 2) * 8 + mem, cb2 = (grp & 3) * 2 + rank;
  const int chb = grp * 16 + mem * 2 + rank;
  const int cta = rg * 16 + hp;
  const int hsel = rb2 & 1;
  constexpr int g2wg = G2W;
  const int par = rg >> 2, gidx = rg & 3;

  if (tid < 256 && !halo_cta && MODE != 2) {
    const int r = tid >> 3, c = tid & 7;
    const uint32_t so = r * 128 + ((c ^ (r & 7)) << 4);
    const __nv_bfloat16* wg0 = p.w + (size_t)r * (3 * DM) + hp * 64 + c * 8;
    const __nv_bfloat16* xg0 = p.x + (size_t)(2 * (gidx * 256 + r) + par) * DM + c * 8;
#pragma unroll
    for (int j = 0; j < 3; j++) cp_async16n(sb + OFF_1B + j * 4096 + so, wg0 + j * DM);
#pragma unroll
    for (int i = 0; i < 8; i++) cp_async16n(sb + i * 4096 + so, xg0 + (size_t)i * 64 * DM);
    asm volatile("cp.async.commit_group;\n" ::: "memory");
  }
  auto halo_issue = [&](int kb, int s) {
    const uint32_t fb = bars + 8 * (BAR_FULLB + s), st = sb + s * STGH;
    mbar_expect_tx(fb, STGH - 2048);
    tma_load_3d(st + 8192, &tmWh, fb, 0, kb * 64, 16 + blockIdx.x * 4);
    tma_load_3d(st + 8192 + 32768, &tmWh, fb, 0, kb * 64, 32 + blockIdx.x * 4);
    tma_load_4d(st, &tmXh, fb, kb * 64, 248, 0, 0);
  };
  if (tid == 256) {
    prefetch_tmap(halo_cta ? &tmXh : &tmX);
#pragma unroll
    for (int i = 0; i < NS1B; i++) mbar_init(bars + 8 * (BAR_FULLB + i), 1);
#pragma unroll
    for (int i = 0; i < NS1A; i++) mbar_init(bars + 8 * (BAR_FULLA + i), 1);
    asm volatile("fence.mbarrier_init.release.cluster;\n" ::: "memory");
    if (!halo_cta && MODE != 2) {
      mbar_expect_tx(bars + 8 * (BAR_FULLB + 1), STG1B);
      tma_load_3d(sb + OFF_1B + 1 * STG1B, &tmW, bars + 8 * (BAR_FULLB + 1), hp * 64, 32, 0);
      mbar_expect_tx(bars + 8 * (BAR_FULLB + 2), STG1B);
      tma_load_3d(sb + OFF_1B + 2 * STG1B, &tmW, bars + 8 * (BAR_FULLB + 2), hp * 64, 64, 0);
    } else if (halo_cta) {
      halo_issue(0, 0);
    }
  } else if (tid == 288) {
#pragma unroll
    for (int i = 0; i < NS1A; i++) mbar_init(bars + 8 * (BAR_EMPTYA + i), 4);
#pragma unroll
    for (int i = 0; i < NS1B; i++) mbar_init(bars + 8 * (BAR_EMPTYB + i), 2);
    mbar_init(bars + 8 * BAR_X, 4);
    mbar_init(bars + 8 * BAR_LAND, 17);
    mbar_init(bars + 8 * BAR_TAB, 16);
    mbar_init(bars + 8 * BAR_U, 1);
    mbar_init(bars + 8 * BAR_H, 1);
    mbar_init(bars + 8 * BAR_STG, 8);
    mbar_init(bars + 8 * BAR_HALO, 1);
    mbar_init(bars + 8 * BAR_Q, 1);
    mbar_init(bars + 8 * BAR_QFREE, 4);
    mbar_init(bars + 8 * (BAR_QFREE + 1), 4);
    asm volatile("fence.mbarrier_init.release.cluster;\n" ::: "memory");
  } else if (tid == 320) {
#pragma unroll
    for (int i = 0; i < NS2; i++) {
      mbar_init(bars + 8 * (BAR_FULL2 + i), 1);
      mbar_init(bars + 8 * (BAR_EMPTY2 + i), i < 5 ? 2 : 8);
    }
    asm volatile("fence.mbarrier_init.release.cluster;\n" ::: "memory");
  } else if (tid == 352) {
#pragma unroll
    for (int i = 0; i < 8; i++) mbar_init(bars + 8 * (BAR_Y + i), 4);
    asm volatile("fence.mbarrier_init.release.cluster;\n" ::: "memory");
  }
  cluster_sync_all();
  if (warp == 8) PROF2(24);

  if (warp >= 8) {
    const int hw = warp - 8;
    const int lr = lane & 7, lm = lane >> 3;
    auto g1_issue_a = [&](int j, int s) {
      const uint32_t fb = bars + 8 * (BAR_FULLA + s);
      mbar_expect_tx(fb, STG1A);
      tma_load_3d_mc(sb + s * STG1A + rank * 16384, &tmX, fb, j * 64, par, gidx * 256 + rank * 128);
    };
    auto g1_issue_b = [&](int kb, int s) {
      const uint32_t fb = bars + 8 * (BAR_FULLB + s);
      mbar_expect_tx(fb, STG1B);
      tma_load_3d(sb + OFF_1B + s * STG1B, &tmW, fb, hp * 64, kb * 32, 0);
    };
    auto g2_k = [&](int kb) { return (kb < 2 ? hp : kb < 4 ? hp & 14 : hp & 12) ^ kb; };
    auto g2_issue_b = [&](int kb, int s) {
      mbar_expect_tx(bars + 8 * (BAR_FULL2 + s), kb || MODE ? STG2 : STG2 / 2);
      tma_load_3d(sb + g2_b(s), &tmWo, bars + 8 * (BAR_FULL2 + s), 0, g2_k(kb) * 64, cb2 * 2);
    };
    asm volatile("setmaxnreg.dec.sync.aligned.u32 %0;\n" :: "n"(REG_HELP));

    if (halo_cta) {
      if (hw == 0) {
        int s = 1, ph = 1;
#pragma unroll 1
        for (int kb = 1; kb < 16; kb++) {
          mbar_wait(bars + 8 * (BAR_EMPTYB + s), ph);
          if (elect_one()) halo_issue(kb, s);
          if (++s == 3) { s = 0; ph ^= 1; }
        }
      }
      __syncwarp();
    } else if (hw == 0) {
      uint32_t epoch = 0;
      if (MODE == 2) {
        if (lane < NS2) mbar_arrive_cluster_n(mapa(bars, rank) + 8 * (BAR_EMPTY2 + lane), lane < 5 ? 2 : 8);
      } else {
      if (lane == 0) {
        mbar_expect_tx(bars + 8 * BAR_U, 32768);
        mbar_expect_tx(bars + 8 * BAR_LAND, 16384);
        mbar_expect_tx(bars + 8 * BAR_Q, 32768);
        prefetch_tmap(&tmQ);
      }
      {
        int sa = 1, pha = 1, sbb = 2, phb = 1;
#pragma unroll 1
        for (int kb = 2; kb < 32; kb++) {
          if (!(kb & 1)) {
            mbar_wait(bars + 8 * (BAR_EMPTYA + sa), pha);
            if (elect_one()) g1_issue_a(kb >> 1, sa);
            if (++sa == NS1A) { sa = 0; pha ^= 1; }
          }
          mbar_wait(bars + 8 * (BAR_EMPTYB + sbb), phb);
          if (kb > 2 && elect_one()) g1_issue_b(kb, sbb);
          __syncwarp();
          if (kb == 4) epoch = ld_relaxed(g_flag_o + cta);
          if (kb == 4) PROF2(27);
          if (kb == 1) PROF2(38);
          if (kb == 2) PROF2(39);
          if (++sbb == NS1B) { sbb = 0; phb ^= 1; }
        }
      }
      auto q_issue = [&](int i) {
        mbar_wait(bars + 8 * (i ? BAR_EMPTYB + 3 : BAR_EMPTYA + 1), i);
        if (elect_one())
          asm volatile(
              "cp.async.bulk.tensor.5d.shared::cluster.global.mbarrier::complete_tx::bytes [%0], [%1, {%3, %4, %4, %4, %5}], [%2];\n"
              ::"r"(sb + g2_b(3 + i)), "l"(&tmQ), "r"(bars + 8 * BAR_Q), "r"((chb & ~1) * 8), "r"(0), "r"(rank * 64 + i * 32)
              : "memory");
        __syncwarp();
      };
      if (QORD < 2) q_issue(0);
      else mbar_wait(bars + 8 * (BAR_EMPTYA + 1), 0);
      if (QORD < 1) q_issue(1);
      epoch++;
      if (lane == 0) {
        prefetch_tmap(&tmWo);
        prefetch_tmap(&tmOb);
        if (gidx != 0) wait_flag(g_flag_h + (hp >> 2), epoch);
      }
      __syncwarp();
      {
        uint4 hk0 = make_uint4(0, 0, 0, 0), hk1 = hk0, hv0 = hk0, hv1 = hk0;
        if (gidx != 0) {
          const uint4* src = g_halo + cta * 128 + lane;
          hk0 = __ldcg(src); hk1 = __ldcg(src + 32); hv0 = __ldcg(src + 64); hv1 = __ldcg(src + 96);
        }
        if (gidx != 0) PROF(18);
        sts128(sb + OFF_KH + lane * 16, hk0.x, hk0.y, hk0.z, hk0.w);
        sts128(sb + OFF_KH + 512 + lane * 16, hk1.x, hk1.y, hk1.z, hk1.w);
        sts64(sb + OFF_KH + 1024 + lane * 8, movm(hv0.x), movm(hv0.y));
        sts64(sb + OFF_KH + 1280 + lane * 8, movm(hv0.z), movm(hv0.w));
        sts64(sb + OFF_KH + 1536 + lane * 8, movm(hv1.x), movm(hv1.y));
        sts64(sb + OFF_KH + 1792 + lane * 8, movm(hv1.z), movm(hv1.w));
        __syncwarp();
        if (lane == 0) mbar_arrive(bars + 8 * BAR_HALO);
      }
      if (QORD == 2) q_issue(0);
      if (QORD >= 1) q_issue(1);
      const uint32_t rb = mapa(bars, lane & 1);
      nb_sync(NB_OREADY, 288);
      if (lane == 0) {
        asm volatile("cp.async.bulk.global.shared::cta.bulk_group [%0], [%1], %2;\n" ::"l"(g_o + (size_t)cta * 16384),
                     "r"(sb + OFF_OP), "r"(32768) : "memory");
        bulk_commit();
      }
      if (lane < 2) {
#pragma unroll
        for (int i = 0; i < 4; i++) mbar_arrive_cluster(rb + 8 * (BAR_EMPTY2 + i + i / 2));
      }
      if (lane == 0) {
        bulk_wait0();
        st_release(g_flag_o + cta, epoch);
      }
      __syncwarp();
      PROF2(17);
      if (lane < 2) mbar_arrive_cluster(rb + 8 * (BAR_EMPTY2 + 2));
      }
      if (MODE != 1) {
        const __nv_bfloat16* osrc = g_o + (size_t)(rb2 >> 1) * 16 * 16384 + hsel * 8192;
        mbar_wait(bars + 8 * (BAR_EMPTY2 + 1), 0);
        if (elect_one()) {
          if (MODE == 0) {
            asm volatile("cp.async.bulk.shared::cluster.shared::cta.mbarrier::complete_tx::bytes [%0], [%1], %2, [%3];\n"
                         ::"r"(mapa(sb + g2_a(1, hsel), rank ^ 1)), "r"(sb + g2_a(0, hsel)), "r"(16384),
                         "r"(mapa(bars + 8 * (BAR_FULL2 + 1), rank ^ 1)) : "memory");
          } else {
            bulk_load(sb + g2_a(0, hsel), osrc + hp * 16384, 16384, bars + 8 * BAR_FULL2);
            bulk_load(sb + g2_a(1, hsel), osrc + (hp ^ 1) * 16384, 16384, bars + 8 * (BAR_FULL2 + 1));
          }
        }
        __syncwarp();
#pragma unroll 1
        for (int kb = 3; kb < 16; kb++) {
          const int s = g2_stage(kb);
          mbar_wait(bars + 8 * (MODE == 0 && kb < 5 ? BAR_QFREE + kb - 3 : BAR_EMPTY2 + s), (G2_PARITY >> kb) & 1);
          if (elect_one()) g2_issue_b(kb, s);
          __syncwarp();
        }
      }
      __syncwarp();
    } else {
      if (MODE != 2) {
      {
        const int g = lane >> 2, t = lane & 3;
        uint32_t w[2][4];
#pragma unroll
        for (int h = 0; h < 2; h++) {
          const uint2 x = __ldg(reinterpret_cast<const uint2*>(p.shift_k + ((chb & ~1) * 8 + h * 8 + g) * 4));
          w[h][0] = __byte_perm(x.x, x.x, 0x1010);
          w[h][1] = __byte_perm(x.x, x.x, 0x3232);
          w[h][2] = __byte_perm(x.y, x.y, 0x1010);
          w[h][3] = __byte_perm(x.y, x.y, 0x3232);
        }
        auto swz = [](int r) { return (((r & 29) | ((r ^ (r >> 2)) & 2)) << 5) | (r & 16); };
        const uint32_t kring = sb + OFF_X + 4096 + (hw - 1) * 2 * XT, vring = kring + XT;
        const int s0 = rank * 32 + (hw - 1) * 11, s1 = hw == 3 ? rank * 32 + 32 : s0 + 11;
        const size_t goff = (size_t)(lane >> 1) * DM + (chb & ~1) * 8 + (lane & 1) * 8;
        const __nv_bfloat16* kg = p.k + goff;
        const __nv_bfloat16* vg = p.v + goff;
        const uint32_t d0 = swz(lane >> 1) ^ ((lane & 1) << 4), d1 = swz(16 + (lane >> 1)) ^ ((lane & 1) << 4);
        auto issue = [&](int st) {
          const uint32_t so = (st & 3) << 10;
          cp_async16(kring + so + d0, kg + (size_t)st * 32 * DM, 16);
          cp_async16(kring + so + d1, kg + (size_t)(st * 32 + 16) * DM, 16);
          cp_async16(vring + so + d0, vg + (size_t)st * 32 * DM, 16);
          cp_async16(vring + so + d1, vg + (size_t)(st * 32 + 16) * DM, 16);
        };
        const int xa = 8 * (lr >> 1) + 2 * lm + (lr & 1), xb = 8 * (lr >> 1) - 4 + 2 * (lm & 1) + (lr & 1);
        const uint32_t la = swz(xa), lb = swz(xb & 31);
        const int backb = xb < 0 ? 1 : 0;
        const uint32_t ud[2] = {mapa(sb + OFF_X + g * XT + t * 16, 0), mapa(sb + OFF_X + g * XT + t * 16, 1)};
        const uint32_t ub[2] = {mapa(bars + 8 * BAR_U, 0), mapa(bars + 8 * BAR_U, 1)};
        if (tid == 320) prefetch_l2(g_tab + (chb & 63) * 32);
        if (lane == 0) mbar_wait(bars + 8 * (BAR_FULLB + NS1B - 1), 0);
        __syncwarp();
        if (lane >= 24) cp_async16(kring + (((s0 - 1) & 3) << 10) + d1, s0 > 0 ? kg + (size_t)(s0 * 32 - 16) * DM : kg, s0 > 0 ? 16 : 0);
        issue(s0);
        asm volatile("cp.async.commit_group;\n" ::: "memory");
        issue(s0 + 1);
        asm volatile("cp.async.commit_group;\n" ::: "memory");
#pragma unroll 1
        for (int st = s0; st < s1; st++) {
          if (st + 2 < s1) issue(st + 2);
          if (hw == 1 && st - s0 < 8) prefetch_l2(p.ssm_k + (size_t)(chb * 8 + st - s0) * SEQ + lane * 64);
          asm volatile("cp.async.commit_group;\n" ::: "memory");
          asm volatile("cp.async.wait_group 2;\n" ::: "memory");
          __syncwarp();
#pragma unroll
          for (int h = 0; h < 2; h++) {
            uint32_t e[6], vv[4], e4[4];
            ldsm4t(e4, kring + ((st & 3) << 10) + (la ^ (h << 4)));
            ldsm2t(e[0], e[1], kring + (((st - backb) & 3) << 10) + (lb ^ (h << 4)));
            ldsm4t(vv, vring + ((st & 3) << 10) + (la ^ (h << 4)));
            e[2] = e4[0]; e[3] = e4[1]; e[4] = e4[2]; e[5] = e4[3];
            uint32_t o[5];
#pragma unroll
            for (int i = 0; i < 5; i++) o[i] = __byte_perm(e[i], e[i + 1], 0x5432);
#pragma unroll
            for (int i = 0; i < 4; i++) {
              uint32_t a = bmul2(o[i], w[h][3]);
              a = bfma2(e[i + 1], w[h][2], a);
              a = bfma2(o[i + 1], w[h][1], a);
              a = bfma2(e[i + 2], w[h][0], a);
              vv[i] = bmul2(a, vv[i]);
            }
            st_async128(ud[h] + (st ^ (g & 1)) * 64, ub[h], vv[0], vv[1], vv[2], vv[3]);
          }
          __syncwarp();
        }
        fence_async_smem();
        PROF(16);
      }
      nb_sync(NB_HELP3, 96);
      if (hw == 1 && elect_one()) {
        mbar_expect_tx(bars + 8 * BAR_H, 8 * 4096);
#pragma unroll 1
        for (int c = 0; c < 8; c++)
          bulk_load(sb + OFF_X + c * XT + 4096, p.ssm_k + (size_t)(chb * 8 + c) * SEQ, 4096, bars + 8 * BAR_H);
        mbar_expect_tx(bars + 8 * BAR_X, 6144);
        bulk_load(sb + OFF_T16, g_tab, 2048, bars + 8 * BAR_X);
        bulk_load(sb + OFF_T32, g_tab + 512, 4096, bars + 8 * BAR_X);
      }
      __syncwarp();
      {
        const int ck = 16 * (lane >> 4) + 2 * lr + (((lane >> 3) ^ (lane >> 2)) & 1);
        const uint32_t xo = (ck >> 1) * 128, xs = ((ck & 1) ^ lr) << 4;
#pragma unroll 1
        for (int job = hw - 1; job < 16; job += 3) {
          const int c = job & 7;
          uint4 a[8];
          float dv = 0.f;
          if (job >= 8 && lane == 0) dv = __bfloat162float(p.ssm_D[chb * 8 + c]);
          if (job < 8) prefetch_l2(p.q + (size_t)chb * 16384 + c * 2048 + lane * 64);
          else if (lane < 16) prefetch_l2(p.wo + (size_t)chb * 8192 + c * 1024 + lane * 64);
          const uint32_t xt = sb + OFF_X + c * XT + (job >> 3) * 4096;
          mbar_wait(bars + 8 * (job < 8 ? BAR_U : BAR_H), 0);
#pragma unroll
          for (int i = 0; i < 8; i++) a[i] = lds128(xt + i * 512 + ((ck ^ (job < 8 ? (c & 1) << 2 : 0)) << 4));
          uint32_t m = pack_bf16(bf_lo(a[0].x) + dv, 0.f);
#pragma unroll
          for (int i = 0; i < 8; i++) m = bmaxabs2(bmaxabs2(m, bmaxabs2(a[i].x, a[i].y)), bmaxabs2(a[i].z, a[i].w));
          m = __reduce_max_sync(0xffffffffu, max(m & 0x7fffu, (m >> 16) & 0x7fffu));
          const uint32_t f = max(252 - (int)(m >> 7), 1), mul = f * 0x00800080u;
          if (lane == 0) asm volatile("st.shared.u32 [%0], %1;\n" ::"r"(sb + OFF_EX + job * 4), "r"(f) : "memory");
          auto cv = [&](uint32_t x) {
            x = bmul2(x, mul);
            return pack_f16(bf_lo(x), bf_hi(x));
          };
          const uint32_t x0 = bmul2(a[0].x, mul);
          const uint32_t dst = xt + xo;
#pragma unroll
          for (int i = 0; i < 8; i++)
            sts128(dst + (i & 1) * 2048 + (xs ^ ((i >> 1) << 5)),
                   i ? cv(a[i].x) : pack_f16(fmaf(dv, __uint_as_float(f << 23), bf_lo(x0)), bf_hi(x0)), cv(a[i].y), cv(a[i].z),
                   cv(a[i].w));
        }
        fence_async_smem();
        __syncwarp();
        if (lane == 0) mbar_arrive(bars + 8 * BAR_X);
        PROF(19);
      }
      if (hw < 3) {
        const uint32_t peer = mapa(sb, rank ^ 1);
#pragma unroll 1
        for (int n = 0; n < SPIN_LIMIT && !mbar_try(bars + 8 * (BAR_Y + hw * 4 - 4), 0); n++) __nanosleep(200);
#pragma unroll 1
        for (int ch = hw * 4 - 4; ch < hw * 4; ch++) {
          const uint32_t o = OFF_X + ch * XT + (rank ^ 1) * 4096;
          uint4 a[4];
          mbar_wait(bars + 8 * (BAR_Y + ch), 0);
#pragma unroll
          for (int i = 0; i < 4; i++) a[i] = lds128(sb + o + (i >> 1) * 2048 + (i & 1) * 512 + lane * 16);
#pragma unroll
          for (int i = 0; i < 4; i++)
            st_async128(peer + o + 1024 + (i >> 1) * 2048 + (i & 1) * 512 + lane * 16, peer + OFF_BAR + 8 * BAR_LAND, a[i].x,
                        a[i].y, a[i].z, a[i].w);
        }
      }
      PROF(32);
      }
      if (MODE != 1 && hw == 3) {
        const uint32_t epoch = ld_relaxed(g_flag_o + cta) + 1;
        if (MODE == 0) nb_sync(NB_G1END, 288);
        if (BDEL) __nanosleep(BDEL);
        if (elect_one()) {
#pragma unroll
          for (int kb = 0; kb < 3; kb++) g2_issue_b(kb, kb);
        }
        __syncwarp();
        const __nv_bfloat16* osrc = g_o + (size_t)(rb2 >> 1) * 16 * 16384 + hsel * 8192;
        if (MODE == 0) __nanosleep(POLL0);
        const uint32_t* flag = g_flag_o + (rb2 >> 1) * 16 + g2_k(lane & 15);
        uint32_t ready = MODE == 0 ? 0u : ~0u;
#pragma unroll 1
        for (int kb = 2; kb < 16; kb++) {
          const int s = g2_stage(kb);
          if (!(ready >> kb & 1)) {
#pragma unroll 1
            for (int n = 0; n < SPIN_LIMIT && !(ready >> kb & 1); n++)
              ready = __ballot_sync(0xffffffffu, ld_acquire(flag) == epoch);
            fence_async_all();
          }
          if (kb == 2) PROF(21);
          mbar_wait(bars + 8 * (BAR_EMPTY2 + s), (G2_PARITY >> kb) & 1);
          if (MODE == 0 && kb == 4 && rank == 1) mbar_wait(bars + 8 * BAR_TAB, 0);
          if (elect_one()) {
            asm volatile(
                "cp.async.bulk.shared::cluster.global.mbarrier::complete_tx::bytes.multicast::cluster [%0], [%1], %2, [%3], %4;\n"
                ::"r"(sb + g2_a(s, hsel) + rank * 8192), "l"(osrc + rank * 4096 + (uint32_t)g2_k(kb) * 16384), "r"(8192),
                "r"(bars + 8 * (BAR_FULL2 + s)), "h"((uint16_t)3) : "memory");
          }
          __syncwarp();
        }
      }
    }
    cluster_sync_all();
    PROF_DUMP();
  } else {
    asm volatile("setmaxnreg.inc.sync.aligned.u32 %0;\n" :: "n"(REG_MATH));
    if (warp == 0) PROF2(26);
    const int wg = warp >> 2;
    const int wtid = tid & 127;
    const bool signaller = (wtid == 0) || (wtid == 32);
    const uint32_t rbars = mapa(bars, wtid >> 5 & 1);

    if (halo_cta) {
      const uint32_t epoch = ld_relaxed(g_flag_h + blockIdx.x) + 1;
      float acc0[64], acc1[64];
      int s = 0, ph = 0;
#pragma unroll 1
      for (int kb = 0; kb < 16; kb++) {
        mbar_wait(bars + 8 * (BAR_FULLB + s), ph);
        const uint32_t st = sb + s * STGH;
        const uint64_t da = mkdesc(st, 16, 1024, 1);
        const uint64_t db = mkdesc(st + 8192 + wg * 32768, 8192, 1024, 1);
        wg_fence();
#pragma unroll
        for (int kk = 0; kk < 4; kk++) {
          wgmma_n128(acc0, da + 2 * kk, db + 128 * kk, kb + kk);
          wgmma_n128(acc1, da + 2 * kk, db + 1024 + 128 * kk, kb + kk);
        }
        wg_commit();
        wg_wait<0>();
        if (kb == 15) PROF(37);
        if (wtid == 0) mbar_arrive(bars + 8 * (BAR_EMPTYB + s));
        if (++s == 3) { s = 0; ph ^= 1; }
      }
      fence_regs(acc0);
      fence_regs(acc1);
      if ((warp & 3) != 3) {
#pragma unroll
        for (int hh = 0; hh < 2; hh++) {
          uint4* dst = g_halo + ((hh * 4 + (warp & 3) + 1) * 16 + blockIdx.x * 4) * 128 + wg * 64 + lane;
#pragma unroll
          for (int j = 0; j < 4; j++) {
            const int o = 16 * j + 2 * hh;
            dst[(j >> 1) * 128 + (j & 1) * 32] =
                make_uint4(pack_bf16(acc0[o], acc0[o + 1]), pack_bf16(acc0[o + 4], acc0[o + 5]),
                           pack_bf16(acc0[o + 8], acc0[o + 9]), pack_bf16(acc0[o + 12], acc0[o + 13]));
            dst[(2 + (j >> 1)) * 128 + (j & 1) * 32] =
                make_uint4(pack_bf16(acc1[o], acc1[o + 1]), pack_bf16(acc1[o + 4], acc1[o + 5]),
                           pack_bf16(acc1[o + 8], acc1[o + 9]), pack_bf16(acc1[o + 12], acc1[o + 13]));
          }
        }
      }
      nb_sync(NB_G1DONE, 256);
      if (tid == 0) st_release(g_flag_h + blockIdx.x, epoch);
      PROF(36);
      cluster_sync_all();
      return;
    }

    if (MODE != 2) {
    uint32_t a1[2][4], sc[4];
    C2 t[2];
    {
      float acc0[96], acc1[96];
      int sa = 0, pha = 0, sbb = 0, phb = 0;
      asm volatile("cp.async.wait_group 0;\n" ::: "memory");
      fence_async_smem();
      nb_sync(NB_FIRST, 256);
      if (tid == 0) {
        mbar_arrive(bars + 8 * BAR_FULLA);
        mbar_arrive(bars + 8 * BAR_FULLB);
      }
      PROF(0 + wg);
#pragma unroll 1
      for (int kb = 0; kb < 30; kb++) {
        if (!(kb & 1)) mbar_wait(bars + 8 * (BAR_FULLA + sa), pha);
        mbar_wait(bars + 8 * (BAR_FULLB + sbb), phb);
        if (kb == 0) PROF2(0 + wg);
        if (kb == 4 && wg == 0) PROF2(28);
        if (kb == 8 && wg == 0) PROF2(29);
        if (kb == 16 && wg == 0) PROF2(30);
        const uint64_t da = mkdesc(sb + sa * STG1A + wg * 16384 + (kb & 1) * 64, 16, 2048, 1);
        const uint64_t db = mkdesc(sb + OFF_1B + sbb * STG1B, 4096, 1024, 1);
        wg_fence();
        wgmma_n192(acc0, da + 64, db, kb);
        wgmma_n192(acc1, da, db, kb);
        wgmma_n192(acc0, da + 66, db + 128, 1);
        wgmma_n192(acc1, da + 2, db + 128, 1);
        wg_commit();
        wg_wait<1>();
        if (kb > 0) {
          if (wtid == 64) mbar_arrive(bars + 8 * (BAR_EMPTYB + (sbb == 0 ? NS1B - 1 : sbb - 1)));
          if (!(kb & 1) && signaller) mbar_arrive_cluster(rbars + 8 * (BAR_EMPTYA + (sa == 0 ? NS1A - 1 : sa - 1)));
        }
        if (++sbb == NS1B) { sbb = 0; phb ^= 1; }
        if ((kb & 1) && ++sa == NS1A) { sa = 0; pha ^= 1; }
      }
      const int lr = lane & 7, lm = lane >> 3;
      const bool le0 = 2 * (lane & 3) <= (lane >> 2), le1 = 2 * (lane & 3) + 1 <= (lane >> 2);
      const uint32_t maskLE = (le0 ? 0x0000FFFFu : 0u) | (le1 ? 0xFFFF0000u : 0u);
      uint32_t q[4][8], k[5][8], vt[5][8];
      {
        static_assert(15 % NS1A == 0 && 30 % NS1B == 0, "slots of the last k blocks");
        asm volatile("ld.global.nc.v4.u32 {%0,%1,%2,%3}, [%4];\n"
                     : "=r"(t[0].r), "=r"(t[1].r), "=r"(t[0].i), "=r"(t[1].i) : "l"(g_tab + 1536 + wtid * 4));
        mbar_wait(bars + 8 * BAR_FULLA, 1);
        mbar_wait(bars + 8 * BAR_FULLB, 0);
        mbar_wait(bars + 8 * (BAR_FULLB + 1), 0);
        mbar_wait(bars + 8 * (BAR_EMPTYA + 1), 0);
        const uint64_t da = mkdesc(sb + wg * 16384, 16, 2048, 1);
        const uint64_t db = mkdesc(sb + OFF_1B, 4096, 1024, 1);
        wg_fence();
#pragma unroll
        for (int i = 0; i < 4; i++) wgmma_n192(acc0, da + 64 + 2 * i, db + (i >> 1) * (STG1B >> 4) + (i & 1) * 128, 1);
        wg_commit();
#pragma unroll
        for (int i = 0; i < 2; i++) wgmma_n192(acc1, da + 2 * i, db + (i >> 1) * (STG1B >> 4) + (i & 1) * 128, 1);
        wg_commit();
        wg_wait<1>();
        fence_regs(acc0);
        PROFA(45, 0);
        attn_pack<8, 1, false>(acc0, k[4]);
        attn_pack<16, 1, true>(acc0, vt[4]);
        const uint32_t kh = sb + (warp == 7 ? OFF_OP + 7 * 4096 : OFF_KH + (warp + 1) * 2048) + lane * 16;
        sts128(kh, k[4][0], k[4][1], k[4][2], k[4][3]);
        sts128(kh + 512, k[4][4], k[4][5], k[4][6], k[4][7]);
#pragma unroll
        for (int i = 0; i < 4; i++) sts64(kh - lane * 8 + 1024 + 256 * i, vt[4][2 * i], vt[4][2 * i + 1]);
#pragma unroll
        for (int i = 2; i < 4; i++) wgmma_n192(acc1, da + 2 * i, db + (i >> 1) * (STG1B >> 4) + (i & 1) * 128, 1);
        wg_commit();
        attn_pack<0, 0, false>(acc0, q[1]);
        attn_pack<0, 1, false>(acc0, q[3]);
        attn_pack<8, 0, false>(acc0, k[2]);
        attn_pack<16, 0, true>(acc0, vt[2]);
        uint32_t z = p.zero;
#pragma unroll
        for (int i = 0; i < 8; i++) z &= q[1][i] & q[3][i];
#pragma unroll
        for (int i = 0; i < 8; i += 2) z &= k[2][i] & k[2][i + 1];
        __syncwarp();
        if (lane == 0) mbar_arrive(bars + 8 * BAR_STG + z);
        wg_wait<0>();
        fence_regs(acc1);
        if (MODE == 0) nb_arrive(NB_G1END, 288);
      }
      PROF(2 + wg);
      mbar_wait(bars + 8 * (warp == 0 ? BAR_HALO : BAR_STG), 0);
      {
        const uint32_t kh = sb + OFF_KH + warp * 2048 + lane * 16;
#pragma unroll
        for (int i = 0; i < 2; i++) {
          const uint4 t = lds128(kh + 512 * i);
          k[0][4 * i] = t.x; k[0][4 * i + 1] = t.y; k[0][4 * i + 2] = t.z; k[0][4 * i + 3] = t.w;
        }
#pragma unroll
        for (int i = 0; i < 4; i++) {
          const uint2 t = lds64(kh - lane * 8 + 1024 + 256 * i);
          vt[0][2 * i] = t.x; vt[0][2 * i + 1] = t.y;
        }
      }
      attn_pack<0, 0, false>(acc1, q[0]);
      attn_pack<0, 1, false>(acc1, q[2]);
      attn_pack<8, 0, false>(acc1, k[1]);
      attn_pack<8, 1, false>(acc1, k[3]);
      {
        float x[8][2];
        uint32_t pp[8];
        const bool first = warp == 0 && gidx == 0;
#pragma unroll
        for (int hd = 0; hd < 2; hd++) {
#pragma unroll
          for (int j = 0; j < 4; j += 2) {
            float s0[4], s1[4], s2[4];
            attn_qk(s2, q[j], q[j + 1], k[j + 2], 4 * hd);
            attn_qk(s1, q[j], q[j + 1], k[j + 1], 4 * hd);
            attn_qk(s0, q[j], q[j + 1], k[j], 4 * hd);
            if (j == 0 && first) s0[0] = s0[1] = -1e9f / 0.17677669529663687f;
            x[2 * j + hd][0] = le0 ? s1[0] : s0[0];
            x[2 * j + hd][1] = le1 ? s1[1] : s0[1];
            x[2 * j + 2 + hd][0] = le0 ? s2[2] : s1[2];
            x[2 * j + 2 + hd][1] = le1 ? s2[3] : s1[3];
          }
        }
        PROFA(40, __float_as_uint(x[1][0] + x[7][1]));
        attn_pack<16, 0, true>(acc1, vt[1]);
        attn_pack<16, 1, true>(acc1, vt[3]);
        quad_softmax<8>(x, pp);
        PROFA(41, pp[1] + pp[7]);
        mbar_wait(bars + 8 * BAR_X, 0);
        ldsm4(a1[0], sb + OFF_T32 + (warp & 3) * 1024 + lane * 16);
        ldsm4(a1[1], sb + OFF_T32 + 512 + (warp & 3) * 1024 + lane * 16);
        {
          const uint4 fh = lds128(sb + OFF_EX + wg * 16), fu = lds128(sb + OFF_EX + 32 + wg * 16);
          auto pw2 = [](uint32_t a, uint32_t b) { return min(max(381 - (int)a - (int)b, 1), 254) * 0x00800080u; };
          sc[0] = pw2(fh.x, fu.x); sc[1] = pw2(fh.y, fu.y); sc[2] = pw2(fh.z, fu.z); sc[3] = pw2(fh.w, fu.w);
        }
        const uint32_t obase = sb + OFF_OP + (warp * 32 + lr) * 128;
#pragma unroll
        for (int n = 0; n < 8; n++) {
          attn_pv(obase + (n >> 1) * 1024 + (((4 * (n & 1) + lm) ^ lr) << 4), vt[n >> 1], vt[(n >> 1) + 1], 4 * (n & 1), pp[n],
                  maskLE);
        }
      }
      PROFA(42, 0);
    }

    {
      const int w = warp & 3;
      const int lr = lane & 7, lm = lane >> 3;
      const uint32_t xb = sb + OFF_X + wg * 4 * XT;
      const uint64_t dc2 = mkdesc(sb + OFF_T16, 512, 128, 0), dc3 = mkdesc(sb + OFF_T16, 128, 512, 0);
      const uint64_t dc4 = mkdesc(sb + OFF_T32, 128, 256, 0);
      const uint64_t dx = mkdesc(xb, 4096, 1024, 1), dz = mkdesc(xb, 2048, 256, 3);
      const uint32_t zs = xb + (w * 16 + (lm & 1) * 8 + lr) * 32 + (((lm >> 1) ^ (lr >> 2)) << 4);
      const uint32_t ys = xb + w * 2048 + (lm >> 1) * 256;
      const uint32_t yx = (lr * 32 + (((lm & 1) ^ (lr >> 2)) << 4)) ^ (rank << 6);
      const bool own = (w >> 1) == rank;
      const uint32_t ybar = mapa(bars, own ? rank ^ 1 : rank) + 8 * (BAR_Y + wg * 4);
      uint32_t d[2][32], pa[2][4][2][4], e[2][4][8], ya[2][2][2][4], v[2][2][8];
      float o[2][16];
      auto rows = [&](int c) {
        fft_rows(d[c & 1], a1, dx + (XT >> 4) * c);
        wg_commit();
      };
      auto cols = [&](int c) {
        const int s = c & 1;
        fence_regs(d[s]);
#pragma unroll
        for (int i = 0; i < 16; i++) {
          const C2 z = crot(C2{d[s][2 * i], d[s][2 * i + 1]}, t[i & 1]);
          pa[s][i >> 2][i & 1][(i >> 1) & 1] = z.r;
          pa[s][i >> 2][i & 1][2 + ((i >> 1) & 1)] = z.i;
        }
        wg_fence();
#pragma unroll
        for (int i = 0; i < 4; i++) fft_cols<0>(e[s][i], pa[s][i], dc2);
        wg_commit();
      };
      auto prod = [&](int c) {
        const int s = c & 1;
#pragma unroll
        for (int i = 0; i < 4; i++) fence_regs(e[s][i]);
#pragma unroll
        for (int j = 0; j < 2; j++) {
          const C2 u0 = cget(e[s][0], j, 0), u1 = cget(e[s][0], j, 1), u2 = cget(e[s][1], j, 0), u3 = cget(e[s][1], j, 1);
          const C2 h0 = cget(e[s][2], j, 0), h1 = cget(e[s][2], j, 1), h2 = cget(e[s][3], j, 0), h3 = cget(e[s][3], j, 1);
          const C2 s0 = cmul(h0, u0), s1 = cfma(h0, u1, cmul(h1, u0)), s2 = cfma(h0, u2, cfma(h2, u0, cmul(h1, u1)));
          const C2 y3 = cfma(h0, u3, cfma(h1, u2, cfma(h2, u1, cfma(h3, u0, C2{s2.i, hneg2(s2.r)}))));
          ya[s][0][j][0] = s0.r;
          ya[s][0][j][1] = hadd2(s1.r, s0.i);
          ya[s][0][j][2] = s0.i;
          ya[s][0][j][3] = hadd2(s1.i, hneg2(s0.r));
          ya[s][1][j][0] = hadd2(s2.r, s1.i);
          ya[s][1][j][1] = y3.r;
          ya[s][1][j][2] = hadd2(s2.i, hneg2(s1.r));
          ya[s][1][j][3] = y3.i;
        }
        wg_fence();
        fft_cols<1>(v[s][0], ya[s][0], dc3);
        fft_cols<1>(v[s][1], ya[s][1], dc3);
        wg_commit();
      };
      auto stage = [&](int c) {
        const int s = c & 1;
        fence_regs(v[s][0]);
        fence_regs(v[s][1]);
#pragma unroll
        for (int b = 0; b < 4; b++) {
          const C2 x0 = cget(v[s][b >> 1], 0, b & 1), x1 = cget(v[s][b >> 1], 1, b & 1);
          const C2 z0 = crot(C2{x0.i, x0.r}, t[0]), z1 = crot(C2{x1.i, x1.r}, t[1]);
          stsm4(zs + c * XT + b * 2048, z0.i, z0.r, z1.i, z1.r);
        }
      };
      auto back = [&](int c) {
        fft_back(o[c & 1], dz + (XT >> 4) * c, dc4);
        wg_commit();
      };
      auto out = [&](int c) {
        float (&r)[16] = o[c & 1];
        fence_regs(r);
#pragma unroll
        for (int i = 0; i < 16; i += 8)
          stsm4t(ys + c * XT + (yx ^ ((c & 1) << 5)) + 64 * i, bmul2(pack_bf16(r[i], r[i + 1]), sc[c]),
                 bmul2(pack_bf16(r[i + 2], r[i + 3]), sc[c]), bmul2(pack_bf16(r[i + 4], r[i + 5]), sc[c]),
                 bmul2(pack_bf16(r[i + 6], r[i + 7]), sc[c]));
        __syncwarp();
        if (lane == 0) {
          mbar_arrive_cluster(ybar + 8 * c);
          if (own) mbar_arrive(bars + 8 * BAR_LAND);
        }
      };
      uint4 q[16];
      auto get_q = [&](int h) {
        if (wg != g2wg) {
          const uint32_t qo = w * 2048 + (lane >> 3) * 128 + (lane & 2) * 32 + (lane & 4) * 8 + (lane & 1) * 16;
          if (h == 0) mbar_wait(bars + 8 * BAR_Q, 0);
#pragma unroll
          for (int i = 0; i < 8; i++) q[8 * h + i] = lds128(sb + g2_b(3 + h) + qo + (i & 3) * 512 + (i >> 2) * 8192);
        }
      };
      auto got_q = [&](int h) {
        if (wg != g2wg) {
          uint32_t z = p.zero;
#pragma unroll
          for (int i = 0; i < 8; i++) z &= q[8 * h + i].x;
          __syncwarp();
          if (lane == 0) mbar_arrive(bars + 8 * (BAR_QFREE + h) + z);
        }
      };
      wg_fence();
      rows(0);
      rows(1);
      fence_async_smem();
      nb_arrive(NB_OREADY, 288);
      PROF(34 + wg);
      wg_wait<1>();
      cols(0);
      wg_wait<1>();
      cols(1);
      rows(2);
      nb_sync(NB_CONV + wg, 128);
      wg_wait<2>();
      prod(0);
      wg_wait<1>();
      cols(2);
      rows(3);
      wg_wait<2>();
      stage(0);
      fence_async_smem();
      prod(1);
      nb_sync(NB_CONV + wg, 128);
      back(0);
      wg_wait<2>();
      cols(3);
      wg_wait<2>();
      stage(1);
      fence_async_smem();
      if (QPOS == 0) get_q(0);
      prod(2);
      nb_sync(NB_CONV + wg, 128);
      back(1);
      wg_wait<2>();
      out(0);
      wg_wait<1>();
      stage(2);
      fence_async_smem();
      if (QPOS == 0) { got_q(0); get_q(1); }
      if (QPOS == 1) get_q(0);
      if (QPOS == 2) { get_q(0); get_q(1); }
      prod(3);
      nb_sync(NB_CONV + wg, 128);
      back(2);
      wg_wait<2>();
      out(1);
      wg_wait<1>();
      stage(3);
      fence_async_smem();
      if (QPOS == 0) got_q(1);
      if (QPOS == 1) got_q(0);
      if (QPOS == 2) { got_q(0); got_q(1); }
      nb_sync(NB_CONV + wg, 128);
      wg_fence();
      back(3);
      wg_wait<1>();
      out(2);
      wg_wait<0>();
      if (lane == 0) mbar_arrive_cluster(mapa(bars, 1) + 8 * BAR_TAB);
      out(3);
      PROF(6 + wg);
      if (wg != g2wg) {
        const int frow = w * 64 + (lane & 2) * 4 + (lane >> 2);
        const int c8 = 2 * lm + (lr & 1), src = (lr >> 1) & 1;
        const uint32_t fa = sb + OFF_X + c8 * XT + rank * 4096 + (src == rank ? 0 : 1024) + w * 128;
        const uint32_t fx = ((lr >> 2) ^ ((lr & 3) << 1) ^ (w & 1)) << 4;
        if (QPOS == 1) { get_q(1); got_q(1); }
        uint4* og = reinterpret_cast<uint4*>(p.out + (size_t)(rank * 1024 + frow) * (2 * DM) + (chb & ~1) * 8 + (lane & 1) * 8);
        mbar_wait(bars + 8 * BAR_LAND, 0);
        PROF2(33);
#pragma unroll
        for (int i = 0; i < 16; i++) {
          uint32_t y[4];
          ldsm4t(y, fa + (i >> 3) * 2048 + ((i >> 2) & 1) * 512 + (fx ^ ((i & 3) << 5)));
          q[i] = make_uint4(bmul2(q[i].x, y[0]), bmul2(q[i].y, y[1]), bmul2(q[i].z, y[2]), bmul2(q[i].w, y[3]));
          if (i % 6 == 0) og[(i / 6) * 16 * (2 * DM / 8)] = q[i / 6];
        }
        {
          uint32_t z = p.zero;
#pragma unroll
          for (int i = 0; i < 16; i++) z &= q[i].x;
          __syncwarp();
          if (lane < 4) mbar_arrive_cluster(mapa(bars, lane & 1) + 8 * (BAR_EMPTY2 + 5 + (lane >> 1)) + z);
        }
        PROF2(20);
#pragma unroll
        for (int i = 3; i < 16; i++) {
#pragma unroll
          for (int n = 0; n < PACE0; n++) __nanosleep(PACE);
          og[((i >> 2) * 256 + (i & 3) * 16) * (2 * DM / 8)] = q[i];
        }
        PROF(22);
      }
    }
    }

    if (MODE != 1 && wg == g2wg) {
      float acc0[64], acc1[64];
      int sprev = 0;
      mbar_wait(bars + 8 * BAR_EMPTY2, 0);
#pragma unroll 1
      for (int kb = 0; kb < 16 - ENDG; kb++) {
        const int s = (int)(G2_STAGE >> (4 * kb)) & 7;
        mbar_wait(bars + 8 * (BAR_FULL2 + s), (G2_PARITY >> kb) & 1);
        if (kb == 0) PROF(8);
        if ((warp & 3) == 0) PROF2(40 + kb);
        const uint64_t da = mkdesc(sb + g2_a(s, hsel), 16, 1024, 1);
        const uint64_t db = mkdesc(sb + g2_b(s), 8192, 1024, 1);
        wg_fence();
        wgmma_n128(acc0, da, db, kb);
        wgmma_n128(acc1, da + 512, db, kb);
        wgmma_n128(acc0, da + 2, db + 128, 1);
        wgmma_n128(acc1, da + 514, db + 128, 1);
        wg_commit();
        wg_wait<1>();
        if (((G2_REUSE << 1 >> kb) & 1) && signaller) mbar_arrive_cluster(rbars + 8 * (BAR_EMPTY2 + sprev));
        wgmma_n128(acc0, da + 4, db + 256, 1);
        wgmma_n128(acc1, da + 516, db + 256, 1);
        wgmma_n128(acc0, da + 6, db + 384, 1);
        wgmma_n128(acc1, da + 518, db + 384, 1);
        wg_commit();
        sprev = s;
      }
#pragma unroll
      for (int kb = 16 - ENDG; kb < 16; kb++) {
        mbar_wait(bars + 8 * (BAR_FULL2 + g2_stage(kb)), (G2_PARITY >> kb) & 1);
        if ((warp & 3) == 0) PROF2(40 + kb);
        const uint64_t da = mkdesc(sb + g2_a(g2_stage(kb), hsel), 16, 1024, 1);
        const uint64_t db = mkdesc(sb + g2_b(g2_stage(kb)), 8192, 1024, 1);
        wg_fence();
#pragma unroll
        for (int i = 0; i < 4; i++) wgmma_n128(acc0, da + 2 * i, db + 128 * i, 1);
        wg_commit();
        if (kb == 16 - ENDG && ((G2_REUSE >> (kb - 1)) & 1)) {
          wg_wait<1>();
          if (signaller) mbar_arrive_cluster(rbars + 8 * (BAR_EMPTY2 + sprev));
        }
      }
      static_assert((G2_REUSE >> (16 - ENDG)) == 0, "the last stages stay resident");
      auto second = [&](int i0, int i1) {
#pragma unroll
        for (int i = i0; i < i1; i++) {
          const int st = g2_stage(16 - ENDG + (i >> 2));
          wgmma_n128(acc1, mkdesc(sb + g2_a(st, hsel) + 8192, 16, 1024, 1) + 2 * (i & 3),
                     mkdesc(sb + g2_b(st), 8192, 1024, 1) + 128 * (i & 3), 1);
        }
        wg_commit();
      };
      second(0, 4);
      const int lr = lane & 7, lm = lane >> 3;
      const uint32_t wb[2] = {sb + g2_a(1, 0) + (warp & 3) * 2048, sb + g2_a(3, 0) + (warp & 3) * 2048};
      const int orow = (rb2 & 7) * 128 + (warp & 3) * 16;
      auto stage_out = [&](const float (&acc)[64], uint32_t off, int j0, int j1) {
#pragma unroll
        for (int j = j0; j < j1; j += 2) {
          const uint32_t a = wb[j >> 3] + off + (lr + 8 * (lm & 1)) * 128 + ((((j & 7) + (lm >> 1)) ^ lr) << 4);
          stsm4(a, pack_bf16(acc[4 * j], acc[4 * j + 1]), pack_bf16(acc[4 * j + 2], acc[4 * j + 3]),
                pack_bf16(acc[4 * j + 4], acc[4 * j + 5]), pack_bf16(acc[4 * j + 6], acc[4 * j + 7]));
        }
      };
      auto store_tma = [&](uint32_t off, int row) {
        fence_async_smem();
        __syncwarp();
        if (elect_one()) {
          tma_store_3d(&tmOb, wb[0] + off, DM + cb2 * 128, rb2 >> 3, row);
          tma_store_3d(&tmOb, wb[1] + off, DM + cb2 * 128 + 64, rb2 >> 3, row);
          bulk_commit();
        }
      };
      wg_wait<1>();
      fence_regs(acc0);
      PROF(10);
#pragma unroll
      for (int c = 0; c < 4; c++) {
        stage_out(acc0, 0, 4 * c, 4 * c + 4);
        second(4 + ILV * c, 4 + ILV * (c + 1));
      }
      store_tma(0, orow);
      if (4 + 4 * ILV < 4 * ENDG) second(4 + 4 * ILV, 4 * ENDG);
      PROF(12);
      wg_wait<0>();
      fence_regs(acc1);
      PROF(11);
      stage_out(acc1, 8192, 0, 16);
      __syncwarp();
      {
        const int rr = lane >> 4, ck = lane & 7, hf = (lane >> 3) & 1;
        uint4* og = reinterpret_cast<uint4*>(p.out + (size_t)(2 * (orow + 64 + rr) + (rb2 >> 3)) * (2 * DM) + DM + cb2 * 128 + hf * 64 + ck * 8);
        uint4 v[8];
#pragma unroll
        for (int i = 0; i < 8; i++) v[i] = lds128((hf ? wb[1] : wb[0]) + 8192 + (2 * i + rr) * 128 + ((ck ^ ((2 * i + rr) & 7)) << 4));
#pragma unroll
        for (int i = 0; i < 8; i++) og[(size_t)i * 4 * (2 * DM / 8)] = v[i];
      }
      PROF(13);
      bulk_wait0();
    }
    cluster_sync_all();
  }
}

typedef CUresult (*EncodeFn)(CUtensorMap*, CUtensorMapDataType, cuuint32_t, void*, const cuuint64_t*, const cuuint64_t*,
                             const cuuint32_t*, const cuuint32_t*, CUtensorMapInterleave, CUtensorMapSwizzle,
                             CUtensorMapL2promotion, CUtensorMapFloatOOBfill);

void make_map(EncodeFn enc, CUtensorMap* tm, const void* base, int rank, const cuuint64_t* dims, const cuuint64_t* strides,
              const cuuint32_t* box, CUtensorMapSwizzle swz) {
  cuuint32_t es[5] = {1, 1, 1, 1, 1};
  enc(tm, CU_TENSOR_MAP_DATA_TYPE_BFLOAT16, rank, const_cast<void*>(base), dims, strides, box, es,
      CU_TENSOR_MAP_INTERLEAVE_NONE, swz, CU_TENSOR_MAP_L2_PROMOTION_L2_256B, CU_TENSOR_MAP_FLOAT_OOB_FILL_NONE);
}

}

extern "C" void kernel_launch(void* const* d_in, const int* in_sizes, int n_in, void* d_out, int out_size) {
  static EncodeFn enc = nullptr;
  static bool coresident = true;
  if (!enc) {
    void* fn = nullptr;
    cudaDriverEntryPointQueryResult qr;
    cudaGetDriverEntryPoint("cuTensorMapEncodeTiled", &fn, cudaEnableDefault, &qr);
    enc = (EncodeFn)fn;
    cudaFuncSetAttribute(fused_kernel<0>, cudaFuncAttributeMaxDynamicSharedMemorySize, SMEM_BYTES);
    cudaFuncSetAttribute(fused_kernel<1>, cudaFuncAttributeMaxDynamicSharedMemorySize, SMEM_BYTES);
    cudaFuncSetAttribute(fused_kernel<2>, cudaFuncAttributeMaxDynamicSharedMemorySize, SMEM_BYTES);
    cudaLaunchConfig_t cfg = {};
    cfg.gridDim = dim3(NCTA);
    cfg.blockDim = dim3(NTHREADS);
    cfg.dynamicSmemBytes = SMEM_BYTES;
    cudaLaunchAttribute at;
    at.id = cudaLaunchAttributeClusterDimension;
    at.val.clusterDim.x = 2;
    at.val.clusterDim.y = 1;
    at.val.clusterDim.z = 1;
    cfg.attrs = &at;
    cfg.numAttrs = 1;
    int nclusters = 0;
    if (cudaOccupancyMaxActiveClusters(&nclusters, fused_kernel<0>, &cfg) == cudaSuccess) coresident = nclusters >= NCTA / 2;
    (void)cudaGetLastError();
  }
  CUtensorMap tmX, tmW, tmWo, tmQ, tmOb, tmXh, tmWh;
  {
    cuuint64_t dims[3] = {1024, 2, 1024};
    cuuint64_t str[2] = {2048, 4096};
    cuuint32_t box[3] = {64, 1, 128};
    make_map(enc, &tmX, d_in[6], 3, dims, str, box, CU_TENSOR_MAP_SWIZZLE_128B);
  }
  {
    cuuint64_t dims[3] = {1024, 1024, 3};
    cuuint64_t str[2] = {6144, 2048};
    cuuint32_t box[3] = {64, 32, 3};
    make_map(enc, &tmW, d_in[7], 3, dims, str, box, CU_TENSOR_MAP_SWIZZLE_128B);
  }
  {
    cuuint64_t dims[3] = {64, 1024, 16};
    cuuint64_t str[2] = {2048, 128};
    cuuint32_t box[3] = {64, 64, 2};
    make_map(enc, &tmWo, d_in[8], 3, dims, str, box, CU_TENSOR_MAP_SWIZZLE_128B);
  }
  {
    cuuint64_t dims[5] = {1024, 2, 2, 4, 128};
    cuuint64_t str[4] = {2048, 8 * 2048, 2 * 2048, 16 * 2048};
    cuuint32_t box[5] = {16, 2, 2, 4, 32};
    make_map(enc, &tmQ, d_in[0], 5, dims, str, box, CU_TENSOR_MAP_SWIZZLE_NONE);
  }
  {
    cuuint64_t dims[3] = {2048, 2, 1024};
    cuuint64_t str[2] = {4096, 8192};
    cuuint32_t box[3] = {64, 1, 16};
    make_map(enc, &tmOb, d_out, 3, dims, str, box, CU_TENSOR_MAP_SWIZZLE_128B);
  }
  {
    cuuint64_t dims[4] = {1024, 256, 2, 4};
    cuuint64_t str[3] = {4096, 2048, 256 * 4096};
    cuuint32_t box[4] = {64, 8, 2, 3};
    make_map(enc, &tmXh, d_in[6], 4, dims, str, box, CU_TENSOR_MAP_SWIZZLE_128B);
  }
  {
    cuuint64_t dims[3] = {64, 1024, 48};
    cuuint64_t str[2] = {6144, 128};
    cuuint32_t box[3] = {64, 64, 4};
    make_map(enc, &tmWh, d_in[7], 3, dims, str, box, CU_TENSOR_MAP_SWIZZLE_128B);
  }
  Params p;
  p.q = (const __nv_bfloat16*)d_in[0];
  p.k = (const __nv_bfloat16*)d_in[1];
  p.v = (const __nv_bfloat16*)d_in[2];
  p.shift_k = (const __nv_bfloat16*)d_in[3];
  p.ssm_k = (const __nv_bfloat16*)d_in[4];
  p.ssm_D = (const __nv_bfloat16*)d_in[5];
  p.x = (const __nv_bfloat16*)d_in[6];
  p.w = (const __nv_bfloat16*)d_in[7];
  p.wo = (const __nv_bfloat16*)d_in[8];
  p.out = (__nv_bfloat16*)d_out;
  p.zero = 0;
  if (coresident) {
    fused_kernel<0><<<NCTA, NTHREADS, SMEM_BYTES>>>(p, tmX, tmW, tmWo, tmQ, tmOb, tmXh, tmWh);
  } else {
    fused_kernel<0><<<4, NTHREADS, SMEM_BYTES>>>(p, tmX, tmW, tmWo, tmQ, tmOb, tmXh, tmWh);
    fused_kernel<1><<<NCTA, NTHREADS, SMEM_BYTES>>>(p, tmX, tmW, tmWo, tmQ, tmOb, tmXh, tmWh);
    fused_kernel<2><<<NCTA, NTHREADS, SMEM_BYTES>>>(p, tmX, tmW, tmWo, tmQ, tmOb, tmXh, tmWh);
  }
}
```

```cpp
#include <cuda_runtime.h>
#include <cuda.h>
#include <cuda_bf16.h>
#include <stdint.h>

namespace {

constexpr int SEQ = 2048;
constexpr int DM = 1024;
constexpr int NCTA = 132;
constexpr int NTHREADS = 384;

constexpr int STG1A = 32768;
constexpr int NS1A = 3;
constexpr int STG1B = 12288;
constexpr int NS1B = 5;
constexpr int OFF_1B = NS1A * STG1A;
constexpr int STG2 = 32768;
constexpr int NS2 = 7;
#define G2SEQ 0x0432104321043210ull
constexpr unsigned long long G2_STAGE = G2SEQ;
__host__ __device__ constexpr int g2_stage(int kb) { return (int)(G2_STAGE >> (4 * kb)) & 7; }
constexpr unsigned g2_bits(bool reuse) {
  unsigned r = 0;
  for (int kb = 0; kb < 16; kb++) {
    int n = 0;
    for (int j = reuse ? kb + 1 : 0; j < (reuse ? 16 : kb); j++) n += g2_stage(j) == g2_stage(kb);
    r |= (unsigned)(reuse ? n > 0 : n & 1) << kb;
  }
  return r;
}
constexpr unsigned G2_PARITY = g2_bits(false);
constexpr unsigned G2_REUSE = g2_bits(true);
#define ILV 2
#define PACE 50
#define PACE0 4
#define POLL0 1500
#define QORD 1
#define BDEL 0
#define QPOS 1
#define G2W 0
#define XPF 0
#define HPF0 3
#define PF0 8
#define PF1 12
#define PSTEP 1150
#define ENDG 5
__device__ __forceinline__ uint32_t g2_a(int s, int hsel) { return (((0xca97524 >> (4 * s)) & 15) ^ (s & 5 ? 0 : hsel)) << 14; }
__device__ __forceinline__ uint32_t g2_b(int s) { return ((0xdb83610 >> (4 * s)) & 15) << 14; }
constexpr int STGH = 73728;
constexpr int OFF_KH = 1 * STG2;
constexpr int OFF_OP = 2 * STG2;
constexpr int OFF_T32 = 5 * STG2 - 4096;
constexpr int OFF_X = 5 * STG2;
constexpr int XT = 8192;
constexpr int OFF_BAR = OFF_X + 8 * XT;
constexpr int OFF_EX = OFF_BAR + 448;
constexpr int OFF_T16 = 230400;
constexpr int SMEM_BYTES = OFF_T16 + 2048;
static_assert(OFF_1B + NS1B * STG1B <= OFF_T32 && OFF_X % 1024 == 0, "layout");
static_assert(3 * STGH <= OFF_BAR && OFF_EX + 64 <= OFF_T16 && SMEM_BYTES <= 232448, "smem");

constexpr int BAR_FULLA = 0;
constexpr int BAR_EMPTYA = 3;
constexpr int BAR_FULLB = 6;
constexpr int BAR_EMPTYB = 11;
constexpr int BAR_FULL2 = 16;
constexpr int BAR_EMPTY2 = 44;
constexpr int BAR_X = 26;
constexpr int BAR_LAND = 27;
constexpr int BAR_TAB = 28;
constexpr int BAR_U = 29;
constexpr int BAR_H = 30;
constexpr int BAR_STG = 31;
constexpr int BAR_Y = 32;
constexpr int BAR_HALO = 40;
constexpr int BAR_Q = 41;
constexpr int BAR_QFREE = 42;

constexpr int NB_G1DONE = 1;
constexpr int NB_G1END = 3;
constexpr int NB_OREADY = 4;
constexpr int NB_CONV = 5;
constexpr int NB_HELP3 = 11;
constexpr int NB_FIRST = 13;

#define REG_MATH 224
#define REG_HELP 56
constexpr int SPIN_LIMIT = 1 << 20;

__device__ __align__(1024) __nv_bfloat16 g_o[SEQ * DM];
__device__ uint32_t g_flag_o[128];
__device__ uint32_t g_flag_h[4];
__device__ uint4 g_halo[128 * 128];
__device__ __align__(128) const uint32_t g_tab[2048] = {
  0x2fd93000,0x2ea72f64,0x2c722da8,0x263e2a1f,0x2ea73000,0xa63e2a1f,0xafd9ada8,0xac72af64,0x2c723000,0xafd9aa1f,0x263eada8,0x2ea72f64,
  0x263e3000,0xac72af64,0x2ea72da8,0xafd9aa1f,0xa63e3000,0x2c72af64,0xaea72da8,0x2fd9aa1f,0xac723000,0x2fd9aa1f,0xa63eada8,0xaea72f64,
  0xaea73000,0x263e2a1f,0x2fd9ada8,0x2c72af64,0xafd93000,0xaea72f64,0xac722da8,0xa63e2a1f,0x263e0000,0x2c722a1f,0x2ea72da8,0x2fd92f64,
  0x2c720000,0x2fd92f64,0x263e2da8,0xaea7aa1f,0x2ea70000,0x263e2f64,0xafd9ada8,0x2c72aa1f,0x2fd90000,0xaea72a1f,0x2c72ada8,0xa63e2f64,
  0x2fd90000,0xaea7aa1f,0x2c722da8,0xa63eaf64,0x2ea70000,0x263eaf64,0xafd92da8,0x2c722a1f,0x2c720000,0x2fd9af64,0x263eada8,0xaea72a1f,
  0x263e0000,0x2c72aa1f,0x2ea7ada8,0x2fd9af64,0xafd93000,0xaea72f64,0xac722da8,0xa63e2a1f,0xaea73000,0x263e2a1f,0x2fd9ada8,0x2c72af64,
  0xac723000,0x2fd9aa1f,0xa63eada8,0xaea72f64,0xa63e3000,0x2c72af64,0xaea72da8,0x2fd9aa1f,0x263e3000,0xac72af64,0x2ea72da8,0xafd9aa1f,
  0x2c723000,0xafd9aa1f,0x263eada8,0x2ea72f64,0x2ea73000,0xa63e2a1f,0xafd9ada8,0xac72af64,0x2fd93000,0x2ea72f64,0x2c722da8,0x263e2a1f,
  0xa63e0000,0xac722a1f,0xaea72da8,0xafd92f64,0xac720000,0xafd92f64,0xa63e2da8,0x2ea7aa1f,0xaea70000,0xa63e2f64,0x2fd9ada8,0xac72aa1f,
  0xafd90000,0x2ea72a1f,0xac72ada8,0x263e2f64,0xafd90000,0x2ea7aa1f,0xac722da8,0x263eaf64,0xaea70000,0xa63eaf64,0x2fd92da8,0xac722a1f,
  0xac720000,0xafd9af64,0xa63eada8,0x2ea72a1f,0xa63e0000,0xac72aa1f,0xaea7ada8,0xafd9af64,0xa63e0000,0xac72aa1f,0xaea7ada8,0xafd9af64,
  0xac720000,0xafd9af64,0xa63eada8,0x2ea72a1f,0xaea70000,0xa63eaf64,0x2fd92da8,0xac722a1f,0xafd90000,0x2ea7aa1f,0xac722da8,0x263eaf64,
  0xafd90000,0x2ea72a1f,0xac72ada8,0x263e2f64,0xaea70000,0xa63e2f64,0x2fd9ada8,0xac72aa1f,0xac720000,0xafd92f64,0xa63e2da8,0x2ea7aa1f,
  0xa63e0000,0xac722a1f,0xaea72da8,0xafd92f64,0x2fd93000,0x2ea72f64,0x2c722da8,0x263e2a1f,0x2ea73000,0xa63e2a1f,0xafd9ada8,0xac72af64,
  0x2c723000,0xafd9aa1f,0x263eada8,0x2ea72f64,0x263e3000,0xac72af64,0x2ea72da8,0xafd9aa1f,0xa63e3000,0x2c72af64,0xaea72da8,0x2fd9aa1f,
  0xac723000,0x2fd9aa1f,0xa63eada8,0xaea72f64,0xaea73000,0x263e2a1f,0x2fd9ada8,0x2c72af64,0xafd93000,0xaea72f64,0xac722da8,0xa63e2a1f,
  0x263e0000,0x2c72aa1f,0x2ea7ada8,0x2fd9af64,0x2c720000,0x2fd9af64,0x263eada8,0xaea72a1f,0x2ea70000,0x263eaf64,0xafd92da8,0x2c722a1f,
  0x2fd90000,0xaea7aa1f,0x2c722da8,0xa63eaf64,0x2fd90000,0xaea72a1f,0x2c72ada8,0xa63e2f64,0x2ea70000,0x263e2f64,0xafd9ada8,0x2c72aa1f,
  0x2c720000,0x2fd92f64,0x263e2da8,0xaea7aa1f,0x263e0000,0x2c722a1f,0x2ea72da8,0x2fd92f64,0xafd93000,0xaea72f64,0xac722da8,0xa63e2a1f,
  0xaea73000,0x263e2a1f,0x2fd9ada8,0x2c72af64,0xac723000,0x2fd9aa1f,0xa63eada8,0xaea72f64,0xa63e3000,0x2c72af64,0xaea72da8,0x2fd9aa1f,
  0x263e3000,0xac72af64,0x2ea72da8,0xafd9aa1f,0x2c723000,0xafd9aa1f,0x263eada8,0x2ea72f64,0x2ea73000,0xa63e2a1f,0xafd9ada8,0xac72af64,
  0x2fd93000,0x2ea72f64,0x2c722da8,0x263e2a1f,0xa63e0000,0xac72aa1f,0xaea7ada8,0xafd9af64,0x2c720000,0x2fd92f64,0x263e2da8,0xaea7aa1f,
  0xaea70000,0xa63eaf64,0x2fd92da8,0xac722a1f,0x2fd90000,0xaea72a1f,0x2c72ada8,0xa63e2f64,0xafd90000,0x2ea72a1f,0xac72ada8,0x263e2f64,
  0x2ea70000,0x263eaf64,0xafd92da8,0x2c722a1f,0xac720000,0xafd92f64,0xa63e2da8,0x2ea7aa1f,0x263e0000,0x2c72aa1f,0x2ea7ada8,0x2fd9af64,
  0x2fd93000,0x2ea72f64,0x2c722da8,0x263e2a1f,0xaea7b000,0x263eaa1f,0x2fd92da8,0x2c722f64,0x2c723000,0xafd9aa1f,0x263eada8,0x2ea72f64,
  0xa63eb000,0x2c722f64,0xaea7ada8,0x2fd92a1f,0xa63e3000,0x2c72af64,0xaea72da8,0x2fd9aa1f,0x2c72b000,0xafd92a1f,0x263e2da8,0x2ea7af64,
  0xaea73000,0x263e2a1f,0x2fd9ada8,0x2c72af64,0x2fd9b000,0x2ea7af64,0x2c72ada8,0x263eaa1f,0x263e0000,0x2c72aa1f,0x2ea7ada8,0x2fd9af64,
  0xac720000,0xafd92f64,0xa63e2da8,0x2ea7aa1f,0x2ea70000,0x263eaf64,0xafd92da8,0x2c722a1f,0xafd90000,0x2ea72a1f,0xac72ada8,0x263e2f64,
  0x2fd90000,0xaea72a1f,0x2c72ada8,0xa63e2f64,0xaea70000,0xa63eaf64,0x2fd92da8,0xac722a1f,0x2c720000,0x2fd92f64,0x263e2da8,0xaea7aa1f,
  0xa63e0000,0xac72aa1f,0xaea7ada8,0xafd9af64,0xafd93000,0xaea72f64,0xac722da8,0xa63e2a1f,0x2ea7b000,0xa63eaa1f,0xafd92da8,0xac722f64,
  0xac723000,0x2fd9aa1f,0xa63eada8,0xaea72f64,0x263eb000,0xac722f64,0x2ea7ada8,0xafd92a1f,0x263e3000,0xac72af64,0x2ea72da8,0xafd9aa1f,
  0xac72b000,0x2fd92a1f,0xa63e2da8,0xaea7af64,0x2ea73000,0xa63e2a1f,0xafd9ada8,0xac72af64,0xafd9b000,0xaea7af64,0xac72ada8,0xa63eaa1f,
  0xafd9b000,0xaea7af64,0xac72ada8,0xa63eaa1f,0x2ea73000,0xa63e2a1f,0xafd9ada8,0xac72af64,0xac72b000,0x2fd92a1f,0xa63e2da8,0xaea7af64,
  0x263e3000,0xac72af64,0x2ea72da8,0xafd9aa1f,0x263eb000,0xac722f64,0x2ea7ada8,0xafd92a1f,0xac723000,0x2fd9aa1f,0xa63eada8,0xaea72f64,
  0x2ea7b000,0xa63eaa1f,0xafd92da8,0xac722f64,0xafd93000,0xaea72f64,0xac722da8,0xa63e2a1f,0xa63e0000,0xac72aa1f,0xaea7ada8,0xafd9af64,
  0x2c720000,0x2fd92f64,0x263e2da8,0xaea7aa1f,0xaea70000,0xa63eaf64,0x2fd92da8,0xac722a1f,0x2fd90000,0xaea72a1f,0x2c72ada8,0xa63e2f64,
  0xafd90000,0x2ea72a1f,0xac72ada8,0x263e2f64,0x2ea70000,0x263eaf64,0xafd92da8,0x2c722a1f,0xac720000,0xafd92f64,0xa63e2da8,0x2ea7aa1f,
  0x263e0000,0x2c72aa1f,0x2ea7ada8,0x2fd9af64,0x2fd9b000,0x2ea7af64,0x2c72ada8,0x263eaa1f,0xaea73000,0x263e2a1f,0x2fd9ada8,0x2c72af64,
  0x2c72b000,0xafd92a1f,0x263e2da8,0x2ea7af64,0xa63e3000,0x2c72af64,0xaea72da8,0x2fd9aa1f,0xa63eb000,0x2c722f64,0xaea7ada8,0x2fd92a1f,
  0x2c723000,0xafd9aa1f,0x263eada8,0x2ea72f64,0xaea7b000,0x263eaa1f,0x2fd92da8,0x2c722f64,0x2fd93000,0x2ea72f64,0x2c722da8,0x263e2a1f,
  0x263e0000,0x2c72aa1f,0x2ea7ada8,0x2fd9af64,0xac720000,0xafd92f64,0xa63e2da8,0x2ea7aa1f,0x2ea70000,0x263eaf64,0xafd92da8,0x2c722a1f,
  0xafd90000,0x2ea72a1f,0xac72ada8,0x263e2f64,0x2fd90000,0xaea72a1f,0x2c72ada8,0xa63e2f64,0xaea70000,0xa63eaf64,0x2fd92da8,0xac722a1f,
  0x2c720000,0x2fd92f64,0x263e2da8,0xaea7aa1f,0xa63e0000,0xac72aa1f,0xaea7ada8,0xafd9af64,0x316c2fbd,0x343e32f7,0x35bc34ff,0x372c3676,
  0x371532c6,0x3a81392e,0x3bef3b71,0x3b7c3bf2,0x397034cf,0x3bfc3b6c,0x38b23b04,0xb40e31e8,0x3ae13631,0x39e73bf5,0xb6e83219,0xbbe8bb13,
  0x3bc23785,0x30be3aa9,0xbbfdb911,0x2a16b9aa,0x3bfe3865,0xb80f37a6,0xb82abc00,0x3bfd376f,0x3b9238fd,0xbb7f2311,0x3805b929,0x31223bde,
  0x3a85398b,0xbb96b742,0x3bff319e,0xbbb82f8b,0xbbe2bbf1,0xbbb7bbcf,0xbb78bb9a,0xbb27bb52,0xbb2cbbd2,0xb8a8ba19,0xb029b5df,0x35a52f59,
  0xb9dfbba1,0x2ba7b5f7,0x3a7a37b2,0x3bbd3bdd,0xb815bb60,0x39662e91,0x3b373bda,0xb0d7377a,0xb3d3bb10,0x3be9386f,0x2a7a3a31,0xbbfeb9a6,
  0x294dbab0,0x3ae53b07,0xbad51fdb,0xab43bb16,0x352fba41,0x35993c00,0xbaebba1d,0x3be531cf,0x38a3b9c5,0xb5173b21,0x2776bbe0,0x34323bf2,
  0x384537dd,0x38ea3899,0x39823937,0x3a0d39c9,0x39463a93,0x3340374e,0xb426a452,0xb979b7c8,0xbb45b924,0xbb32bc00,0xb371b902,0x38d63294,
  0xb08db9a1,0x3b3f379b,0x39583bd7,0xb8252dfb,0x3bea3a2d,0xb3ba3874,0xbb89bb0d,0x36d2b625,0xb6bb387f,0xb8d1bbf5,0x3be73602,0xb546391f,
  0xba00bb01,0x3bff35eb,0xba5c34db,0x3359bab6,0x3ac7b66b,0xb9413933,0x368dbabd,0xb0103bb3,0xbac4baf7,0xba50ba8c,0xb9cdba11,0xb93cb986,
  0x3a04388e,0x3bcb3b1e,0x3bba3c00,0x39d63afe,0x36af3a21,0xb6ffa17f,0xbbc8ba3d,0xba60bbd4,0xbbebb9af,0xb6c6bb0a,0x39f43263,0x3ad83bf7,
  0x30a6b916,0x3bc33aa5,0xb55e3790,0xbb3dbb63,0x3b423a9e,0xba642ec3,0xb0f0bb6a,0x3b8e3a25,0xb94a37bd,0x2884bb6f,0x38db3b9f,0xbbc9b85a,
  0xb840bb54,0x3a093a15,0xbb4cb850,0x3bef3457,0x3a893a4d,0x3af43ac1,0x3b4f3b24,0x3b983b76,0xbb94baba,0xbbe4bbf9,0xba58bb57,0xb699b8f8,
  0x3bfe3b18,0x394f3b5c,0xb109347b,0xbae8b884,0xbbc0bb68,0xa9b1b90c,0x3b8b387a,0x38bc3ba5,0x3ade3ba7,0xb8c1324b,0xb9f0bbf6,0x39eb9648,
  0xb96bbbd6,0x3bbf3487,0xb38939b3,0xb9f8bba3,0x370a3bf3,0xbb47b994,0x3bbc2d65,0xb8ad3889,0xb153bc00,0x37213b9c,0xb97dba90,0x3af138f3,
  0xb89eb8ee,0xb7e8b84a,0xb682b737,0xb50bb5c8,0x35233855,0xb13b2d33,0xb8e0b65f,0xbb4aba45,0xa8e8b764,0x39fc3648,0x3be63bae,0x380a3a9b,
  0xb3eb360e,0xbbfeba35,0xb552baa2,0x3a7334b7,0x381ab4ab,0x3a6f3bd8,0xb95d2e5f,0xb962bc00,0xb9e3327c,0xb402bbac,0x3bc6399d,0xb95434c3,
  0x3b2faf27,0xb6a439bc,0xb41abbf9,0x3a7e3a97,0xbbe3251b,0x3b2ab4f3,0xb9d23894,0x37f3ba49,0x3bce3bb5,0x3bf03be1,0x3bff3bfa,0x3bfb3bff,
  0x2c38b1b6,0x383a34e7,0x3aee39c0,0x3bff3bb2,0xbb81bbf8,0xb53ab999,0x38302ef5,0x3bed3ab3,0xb8cc9cb6,0xbb85bbab,0x2adeb86a,0x3bc5391b,
  0x38c73bf6,0xbadbb232,0xb6ddbba9,0x3b87361a,0x3b833201,0xb0743a39,0xba76bb5e,0x3b352dc9,0xac06bbb0,0x39743b59,0xbbeeb759,0x3aceb2ad,
  0xbbccb5d4,0x3bfb2d00,0xbb7a32de,0x3a54b7d2,0xb30fb44b,0xafefb185,0xa6adacce,0x2c9c25e4,0xbbfcbbdf,0xbacbbb9e,0xb7feb990,0xa81fb463,
  0xb58d2d97,0xbb90b9b8,0xbad1bbf4,0xb05bb85f,0x3a673c00,0xb5763493,0xbbfdbaac,0xb3a2ba29,0x3a6b2e2d,0x38203bd9,0xbb3ab49f,0xb56abb65,
  0xb581bbdc,0x3bec3907,0xb8b7363c,0xb6f4bbf8,0xbbfcb46f,0x39dab654,0xb0423b1b,0xb835bbd3,0xb3283b73,0xac6abbfa,0x35b13bd0,0xb8e5bafb,
  0x38ee3a0d,0xb84aba89,0x37373af4,0xb5c8bb4f,0x35df3a81,0x2f59bbef,0xb88e3b7c,0x3b1eb946,0x2d973ae8,0x39b8bb81,0xbbf4353a,0x385f3830,
  0xb2633b3f,0x3bf7b958,0xb60eb825,0xba353bc0,0xb7853b87,0x3aa9b3d3,0x3911bbe9,0xb9aa2a7a,0xb99d3bbf,0x34c33389,0x3bdcb9f8,0x3907bb83,
  0xbb013be5,0xb5eb394a,0x34db2884,0x3ab6b8db,0xbbd03bfb,0xbafb3b7a,0xb98b3a54,0xb74238a3,0x3a4db93c,0xbac1389e,0x3b24b7e8,0xbb763682,
  0x3b71b8a8,0xbbf23029,0x3a9335a5,0xb74eba04,0x3bf8b80a,0xb999b58d,0xaef53b90,0x3ab3bad1,0x3bd7b6c6,0xadfbb9f4,0xbb683ad8,0x390c33eb,
  0x3b10b56a,0x386fbbc2,0xba3130be,0xb9a63bfd,0x39b3b402,0x3ba3bbc6,0x3201b954,0xba393581,0x37bdb122,0x3b6fba00,0x3b9fbbff,0x385aba5c,
  0x32deac6a,0x37d2b5b1,0x39c5b8e5,0x3b21ba85,0x344b3b98,0xb185bbce,0x2cce3bf0,0x25e4bbff,0xbc003340,0x3afe3426,0xb855b979,0x2d333b94,
  0x34cfbbed,0xbb6c39df,0x3b042ba7,0xb1e8ba7a,0x3aa2a9b1,0x34b7bb8b,0xbc0038bc,0x349338cc,0xba2d3bfe,0x387430a6,0x3b0dbbc3,0xb625b55e,
  0xb63cb074,0xbbf83a76,0xb8653b35,0x37a6294d,0x3bf3bbc9,0x3994bb2f,0x2d65b6a4,0xb889341a,0xb19e3517,0x2f8b2776,0x366bb432,0x3933b840,
  0x3bb5b50b,0xbbe1330f,0x3bfaafef,0xbbff26ad,0xa4523bcb,0x37c8bbba,0xbaba39d6,0x3bf9b523,0xbba1305b,0x35f73970,0x37b2bbfc,0xbbdd38b2,
  0x387abbfe,0xbba53552,0x9cb63a73,0x3babba67,0x39162a16,0x3aa5bbea,0xb790b3ba,0xbb633b89,0xbb5e3bec,0xadc938b7,0x3ab0b6f4,0x3b07bbfe,
  0xaf27b359,0xb9bc370a,0xbbf93b47,0xba973bbc,0x3be0bb96,0x3bf2bbff,0x3b54bbb8,0x3a15bac7,0xafbd3bfb,0x32f7bbe2,0xb4ff3bb7,0x3676bb78,
  0x365fbbe4,0xba453a58,0x3bdfb699,0xbb9eac38,0xb9243bbd,0x3c00b6af,0xb902b6ff,0xb2943bc8,0x3aacbb85,0xba29aade,0xb6313bc5,0x3bf5b815,
  0xbba73b3d,0x324b381a,0x3bf6ba6f,0x9648b95d,0x3c00bae5,0x376fbad5,0xb87f2b43,0xbbf53b42,0xbbb03a7e,0xbb593bfc,0xb75939da,0x32ad3042,
  0x3abdba09,0x3bb3bb4c,0x3c00bbef,0x3b9cbbe3,0x3bf12c9c,0xbbcfb16c,0x3b9a343e,0xbb52b5bc,0xbb57b13b,0x38f838e0,0xb1b6bb4a,0xb4e73bfc,
  0x3a21340e,0x217fbb45,0xba3d3b32,0x3bd4b371,0xb86ab576,0xb91b3bfd,0x3b60b3a2,0x2e91bae1,0x34ab36d2,0x3bd8bade,0xae5fb8c1,0xbc0039f0,
  0x9fdbb80f,0xbb16382a,0xba9e3bfd,0x2ec336bb,0xb46f38ad,0x3654ac06,0x3b1bb974,0x3bd3bbee,0x3850b941,0x3457b68d,0xa51bb010,0xb4f33153,
  0xb7dd3b27,0x3899bac4,0xb9373a50,0x39c9b9cd,0x3990383a,0xb463baee,0xb2c63bff,0x392ebb2c,0x3b18ba60,0xbb5c28e8,0x347b39fc,0x3884bbe6,
  0xb219b966,0xbb133b37,0x39a130d7,0x379bbbeb,0xbbf63962,0xb2323a6b,0x3ba9b820,0x361abb3a,0xb6023a64,0x391fb0f0,0x3bd6bb8e,0x3487b9e3,
  0x3a41b835,0x3c00bb92,0x3a1dbb7f,0x31cfb805,0x3a90bb2a,0x38f3b9d2,0x35d4b7f3,0x2d00b328,0x3af7372c,0xba8cb845,0x3a1138ea,0xb986b982,
  0x39c0bacb,0xbbb237fe,0x3bd2a81f,0xba19b715,0xb764b8d6,0xb6483bfe,0x3baeb94f,0xba9bb109,0xbbda39e7,0x377a36e8,0x39afbbe8,0xbb0a308d,
  0xae2d39eb,0x3bd9b8c7,0x349fbadb,0xbb6536dd,0x3b6ab8d1,0x3a25bbe7,0xb27cb546,0xbbac396b,0x38fdbace,0xa311b52f,0xb9293599,0xbbde3aeb,
  0xb8943721,0xba49397d,0xbb733af1,0xbbfa3bcc,0xbbfb3bff,0xbbe23bf1,0xbbb73bcf,0xbb783b9a,0xbb7c3bf2,0xb9463a93,0xb340374e,0x3426a452,
  0xba603bd4,0xa8e83764,0x39fcb648,0x3be6bbae,0xb8bc3ba5,0x38cc9cb6,0x3b85bbab,0xaadeb86a,0xb56a3b65,0x3bc2b785,0x30bebaa9,0xbbfd3911,
  0xab433b16,0x3b42ba9e,0xba64aec3,0xb0f03b6a,0x33593ab6,0x370abbf3,0xbb473994,0x3bbcad65,0x37f33a49,0xb328bb73,0xac6a3bfa,0x35b1bbd0,
  0xac9c25e4,0xb16c2fbd,0xb43e32f7,0xb5bc34ff,0xb5a52f59,0xba04388e,0xbbcb3b1e,0xbbba3c00,0xb8d63294,0xbbfe3b18,0xb94f3b5c,0x3109347b,
  0xba7334b7,0xba673c00,0x35763493,0x3bfdbaac,0xbb87361a,0xb3d33b10,0x3be9b86f,0x2a7aba31,0xbbfd376f,0x36bb387f,0x38d1bbf5,0xbbe73602,
  0xbbc9385a,0x3b2f2f27,0xb6a4b9bc,0xb41a3bf9,0xbaf138f3,0x3bccb5d4,0xbbfb2d00,0x3b7a32de,0xbb273b52,0xbac43af7,0xba503a8c,0xb9cd3a11,
  0x3979b7c8,0x3b94baba,0x3be4bbf9,0x3a58bb57,0x380aba9b,0xb58dad97,0xbb9039b8,0xbad13bf4,0xbbc5391b,0xb8153b60,0x3966ae91,0x3b37bbda,
  0x2a1639aa,0x3beaba2d,0xb3bab874,0xbb893b0d,0x3b8eba25,0xb9e3b27c,0xb4023bac,0x3bc6b99d,0xb8adb889,0xac063bb0,0x3974bb59,0xbbee3759,
  0xb8e53afb,0x3a85b98b,0xbb963742,0x3bffb19e,0xb72c3676,0xb84537dd,0xb8ea3899,0xb9823937,0xb9d63afe,0xb5233855,0x313b2d33,0x38e0b65f,
  0x3ae8b884,0x3b81bbf8,0x353ab999,0xb8302ef5,0x33a2ba29,0xbae13631,0xb9e73bf5,0x36e83219,0xbbfe39a6,0x30a63916,0x3bc3baa5,0xb55eb790,
  0x3546391f,0x396bbbd6,0xbbbf3487,0x338939b3,0x3a7eba97,0xbbfc346f,0x39da3654,0xb042bb1b,0xba54b7d2,0x38a339c5,0xb517bb21,0x27763be0,
  0xb93c3986,0xb89e38ee,0xb7e8384a,0xb6823737,0x3699b8f8,0xac38b1b6,0xb83a34e7,0xbaee39c0,0xb05b385f,0x3970b4cf,0x3bfcbb6c,0x38b2bb04,
  0xb0d7b77a,0xbbeb39af,0xb6c63b0a,0x39f4b263,0x36d23625,0x3adebba7,0xb8c1b24b,0xb9f03bf6,0xb954b4c3,0xb5813bdc,0x3becb907,0xb8b7b63c,
  0x3ace32ad,0xb52fba41,0xb5993c00,0x3aebba1d,0xbbb8af8b,0x3ac7366b,0xb941b933,0x368d3abd,0xba0d39c9,0xba893a4d,0xbaf43ac1,0xbb4f3b24,
  0x3b4aba45,0x3bfcbbdf,0x3acbbb9e,0x37feb990,0xbbed3ab3,0xb9df3ba1,0x2ba735f7,0x3a7ab7b2,0x3be8bb13,0x308db9a1,0xbb3f379b,0xb9583bd7,
  0xbb3d3b63,0x381a34ab,0x3a6fbbd8,0xb95dae5f,0x39f8bba3,0xbb833201,0x30743a39,0x3a76bb5e,0xb8353bd3,0x3b92b8fd,0xbb7fa311,0x38053929,
  0x3432bbf2,0xb8403b54,0x3a09ba15,0xbb4c3850,0xb50b35c8,0xb30f344b,0xafef3185,0xa6ad2cce,0xbbff3bb2,0xbb2c3bd2,0xb8a83a19,0xb02935df,
  0xb40eb1e8,0xbb453924,0xbb323c00,0xb3713902,0x3ad8bbf7,0xb3ebb60e,0xbbfe3a35,0xb5523aa2,0x39eb1648,0x38c7bbf6,0xbadb3232,0xb6dd3ba9,
  0xb6f43bf8,0x3bfeb865,0xb80fb7a6,0xb82a3c00,0xbbe531cf,0x394a37bd,0xa884bb6f,0xb8db3b9f,0xb010bbb3,0xb1533c00,0x3721bb9c,0xb97d3a90,
  0xbb983b76,0xbbce3bb5,0xbbf03be1,0xbbff3bfa,0x281fb463,0xb71532c6,0xba81392e,0xbbef3b71,0x3bbdbbdd,0x36afba21,0xb6ff217f,0xbbc83a3d,
  0x38252dfb,0x3bc0bb68,0x29b1b90c,0xbb8b387a,0xb9623c00,0x3a6bae2d,0x3820bbd9,0xbb3a349f,0xbb352dc9,0x294d3ab0,0x3ae5bb07,0xbad59fdb,
  0x3122bbde,0xba003b01,0x3bffb5eb,0xba5cb4db,0x3befb457,0xbbe3a51b,0x3b2a34f3,0xb9d2b894,0x39c939cd,0xba4db93c,0x3ac1389e,0xbb24b7e8,
  0x3b1e3946,0xbc00b340,0x3afeb426,0xb8553979,0x3bdd38b2,0xba21340e,0xa17fbb45,0x3a3d3b32,0x3bf53815,0xb2193966,0xbb13bb37,0x39a1b0d7,
  0x3b6536dd,0x37853b87,0xbaa9b3d3,0xb911bbe9,0x3a393581,0x3b5e3bec,0x2dc938b7,0xbab0b6f4,0x3889341a,0x3bb03a7e,0x3b593bfc,0x375939da,
  0x34f33153,0x38943721,0x3a49397d,0x3b733af1,0xb9863982,0x38eeba0d,0xb84a3a89,0x3737baf4,0xb74e3a04,0xa452bbcb,0x37c83bba,0xbabab9d6,
  0xb1e83a7a,0xb924bbbd,0x3c0036af,0xb90236ff,0x2e913ae1,0xbbdab9e7,0x377ab6e8,0x39af3be8,0x361a3b3a,0xbb10b56a,0xb86fbbc2,0x3a3130be,
  0x39073b83,0xb63c3074,0xbbf8ba76,0xb865bb35,0x3a973bbc,0x346f38ad,0xb654ac06,0xbb1bb974,0x3b9c3be3,0x3a903b2a,0x38f339d2,0x35d437f3,
  0x3b763682,0xbbb5b50b,0x3be1330f,0xbbfaafef,0x2d33bb94,0x365f3be4,0xba45ba58,0x3bdf3699,0xbbd4b371,0x3764b8d6,0x36483bfe,0xbbaeb94f,
  0x379b3beb,0xbbd7b6c6,0x2dfbb9f4,0x3b683ad8,0x39aa2a7a,0x3a2d3bfe,0xb87430a6,0xbb0dbbc3,0xbb07bbfe,0x1fdbb80f,0x3b16382a,0x3a9e3bfd,
  0xb2ad3042,0xba41b835,0xbc00bb92,0xba1dbb7f,0x3bfa3bcc,0x3bd03bfb,0x3afb3b7a,0x398b3a54,0xb5c83b4f,0x344bbb98,0xb1853bce,0x2ccebbf0,
  0x3bf93523,0xbb57313b,0x38f8b8e0,0xb1b63b4a,0xb294bbc8,0x3b183a60,0xbb5ca8e8,0x347bb9fc,0xbb0ab08d,0xb263bb3f,0x3bf73958,0xb60e3825,
  0x39a63bfd,0xb9162a16,0xbaa5bbea,0x3790b3ba,0x37a6a94d,0x3c003ae5,0x376f3ad5,0xb87fab43,0xbbd3bbee,0xb8fdbace,0x2311b52f,0x39293599,
  0x2d003328,0xb2deac6a,0xb7d2b5b1,0xb9c5b8e5,0x3bff26ad,0xbbf12c9c,0x3bcfb16c,0xbb9a343e,0xbb9e2c38,0x3990b83a,0xb4633aee,0xb2c6bbff,
  0x3a9bb109,0xad973ae8,0xb9b8bb81,0x3bf4353a,0xb90c33eb,0xb87abbfe,0x3ba53552,0x1cb63a73,0x3625b55e,0x3ba73b3d,0xb24b381a,0xbbf6ba6f,
  0xaec336bb,0xbb6ab8d1,0xba25bbe7,0x327cb546,0xb1cfb805,0x37bd3122,0x3b6f3a00,0x3b9f3bff,0x374238a3,0x319e3517,0xaf8b2776,0xb66bb432,
  0x25e43bff,0xafbdbbfb,0x32f73be2,0xb4ffbbb7,0xb4e7bbfc,0x39c03acb,0xbbb2b7fe,0x3bd2281f,0x38843be6,0xbbf8b80a,0x3999b58d,0x2ef53b90,
  0xba35bbc0,0x3aa229b1,0x34b73b8b,0xbc00b8bc,0x3b633b89,0xb4ab36d2,0xbbd8bade,0x2e5fb8c1,0xbbf5bb42,0xb602ba64,0x391f30f0,0x3bd63b8e,
  0x3bde3aeb,0x3b013be5,0x35eb394a,0xb4db2884,0xbb21ba85,0xbbe0bb96,0xbbf2bbff,0xbb54bbb8,0x3b52b5bc,0xbaf7372c,0x3a8cb845,0xba1138ea,
  0x392e3b2c,0xbb71b8a8,0x3bf23029,0xba9335a5,0xb85f3830,0xb4cfbbed,0x3b6c39df,0xbb042ba7,0xbbabba67,0x386ab576,0x391b3bfd,0xbb60b3a2,
  0x1648b95d,0x3bf63962,0x32323a6b,0xbba9b820,0x3bac396b,0x399d3bbf,0xb4c33389,0xbbdcb9f8,0x385a3a5c,0xaf273359,0xb9bcb70a,0xbbf9bb47,
  0xb933b840,0xbabdba09,0xbbb3bb4c,0xbc00bbef,0x36763b78,0xb7ddbb27,0x38993ac4,0xb937ba50,0xba193715,0x35dfba81,0x2f593bef,0xb88ebb7c,
  0xbab3bad1,0x3ba1305b,0xb5f73970,0xb7b2bbfc,0x3493b8cc,0x3aac3b85,0xba292ade,0xb631bbc5,0x3c0039f0,0x2e2d39eb,0xbbd9b8c7,0xb49fbadb,
  0x348739e3,0xb9b3b402,0xbba3bbc6,0xb201b954,0xbab6b8db,0xbbf3bbc9,0xb994bb2f,0xad65b6a4,0xba15bac7,0xb850b941,0xb457b68d,0x251bb010,
  0xb9cfbb16,0x30ac2a31,0x3b9c3bf1,0xb493ae2d,0xb76fb8b4,0x35a133e3,0x3a1d3afe,0xb902b76f,0xb3e3b5a1,0x38b4376f,0x376f3902,0xbafeba1d,
  0xaa31b0ac,0x3b1639cf,0x2e2d3493,0xbbf1bb9c,0xb956ba74,0x305f29cc,0x3b633bd2,0xb44badc9,0xb6e7b859,0x353f335e,0x39d23ab6,0xb8bcb6ff,
  0xb35eb53f,0x385936e7,0x36ff38bc,0xbab6b9d2,0xa9ccb05f,0x3a743956,0x2dc9344b,0xbbd2bb63,0xb8e3b9de,0x30122967,0x3b1e3ba1,0xb402ad65,
  0xb662b801,0x34de32da,0x39823a67,0xb874b68d,0xb2dab4de,0x38013662,0x368d3874,0xba67b982,0xa967b012,0x39de38e3,0x2d653402,0xbba1bb1e,
  0xb876b952,0x2f8c2902,0x3ace3b60,0xb371ad00,0xb5e1b758,0x347e3257,0x392e3a11,0xb82ab61a,0xb257b47e,0x375835e1,0x361a382a,0xba11b92e,
  0xa902af8c,0x39523876,0x2d003371,0xbb60bace,0xb80db8ce,0x2ef3289e,0x3a733b10,0xb2deac9c,0xb562b6b3,0x342031d5,0x38d639b3,0xb7bdb5a5,
  0xb1d5b420,0x36b33562,0x35a537bd,0xb9b3b8d6,0xa89eaef3,0x38ce380d,0x2c9c32de,0xbb10ba73,0xb750b851,0x2e5a2839,0x3a0d3ab0,0xb24bac38,
  0xb4e5b613,0x33863153,0x387a394f,0xb721b52f,0xb153b386,0x361334e5,0x352f3721,0xb94fb87a,0xa839ae5a,0x38513750,0x2c38324b,0xbab0ba0d,
  0xb68eb7b4,0x2dc227a9,0x399d3a41,0xb1b6aba7,0xb46ab577,0x32cd30d2,0x381a38e5,0xb682b4b7,0xb0d2b2cd,0x3577346a,0x34b73682,0xb8e5b81a,
  0xa7a9adc2,0x37b4368e,0x2ba731b6,0xba41b99d,0xb5d2b6d1,0x2d2a26e0,0x392439c5,0xb122aade,0xb3e3b4de,0x32163052,0x376f3874,0xb5dfb43e,
  0xb052b216,0x34de33e3,0x343e35df,0xb874b76f,0xa6e0ad2a,0x36d135d2,0x2ade3122,0xb9c5b924,0xb51cb5f6,0x2c932617,0x38a3393c,0xb08daa16,
  0xb2f4b448,0x31602fa5,0x36a437fe,0xb53ab389,0xafa5b160,0x344832f4,0x3389353a,0xb7feb6a4,0xa617ac93,0x35f6351c,0x2a16308d,0xb93cb8a3,
  0xb46ab523,0x2bf6254d,0x381a38a8,0xafefa94d,0xb209b36b,0x30ac2ea7,0x35d4370a,0xb493b294,0xaea7b0ac,0x336b3209,0x32943493,0xb70ab5d4,
  0xa54dabf6,0x3523346a,0x294d2fef,0xb8a8b81a,0xb378b456,0x2ac82484,0x3715380a,0xaec3a884,0xb120b24a,0x2ff22da9,0x34ff360e,0xb3d3b19e,
  0xada9aff2,0x324a3120,0x319e33d3,0xb60eb4ff,0xa484aac8,0x34563378,0x28842ec3,0xb80ab715,0xb223b31c,0x29992376,0x35eb36c6,0xad97a776,
  0xb039b12d,0x2e8d2cac,0x3426350b,0xb27cb0a6,0xacacae8d,0x312d3039,0x30a6327c,0xb50bb426,0xa376a999,0x331c3223,0x27762d97,0xb6c6b5eb,
  0xb0d2b194,0x286b21e4,0x34b7356a,0xac6aa5e4,0xaea7b012,0x2d2a2b5f,0x32943402,0xb122af59,0xab5fad2a,0x30122ea7,0x2f593122,0xb402b294,
  0xa1e4a86b,0x319430d2,0x25e42c6a,0xb56ab4b7,0xaf0cb012,0x267b2052,0x32f73402,0xaa7aa452,0xacdeadf5,0x2b912967,0x30d731e8,0xaf8bad65,
  0xa967ab91,0x2df52cde,0x2d652f8b,0xb1e8b0d7,0xa052a67b,0x30122f0c,0x24522a7a,0xb402b2f7,0xac79ad2a,0x24201d7f,0x30743122,0xa81fa17f,
  0xaa31ab91,0x28d026e0,0x2e2d2f8b,0xacceaade,0xa6e0a8d0,0x2b912a31,0x2ade2cce,0xaf8bae2d,0x9d7fa420,0x2d2a2c79,0x217f281f,0xb122b074,
  0xa7a9a86b,0x1f1218b6,0x2ba72c6a,0xa3119cb6,0xa54da67b,0x242021e4,0x294d2a7a,0xa81fa5e4,0xa1e4a420,0x267b254d,0x25e4281f,0xaa7aa94d,
  0x98b69f12,0x286b27a9,0x1cb62311,0xac6aaba7,0x211b21e4,0x98b69248,0xa51ba5e4,0x1cb61648,0x1f122052,0x9d7f9bdb,0xa311a452,0x217f1fdb,
  0x1bdb1d7f,0xa0529f12,0x9fdba17f,0x24522311,0x124818b6,0xa1e4a11b,0x96489cb6,0x25e4251b,0x2a632b5f,0xa1e49bdb,0xae5faf59,0x25e41fdb,
  0x286b2967,0xa6e0a4e9,0xac6aad65,0x2ade28e8,0x24e926e0,0xa967a86b,0xa8e8aade,0x2d652c6a,0x1bdb21e4,0xab5faa63,0x9fdba5e4,0x2f592e5f,
  0x2dc22ea7,0xa54d9f12,0xb1b6b294,0x294d2311,0x2bf62cde,0xaa31a86b,0xafefb0d7,0x2e2d2c6a,0x286b2a31,0xacdeabf6,0xac6aae2d,0x30d72fef,
  0x1f12254d,0xaea7adc2,0xa311a94d,0x329431b6,0x302c30d2,0xa7a9a11b,0xb41ab4b7,0x2ba7251b,0x2dc22f0c,0xac79aa63,0xb1b6b2f7,0x30742e5f,
  0x2a632c79,0xaf0cadc2,0xae5fb074,0x32f731b6,0x211b27a9,0xb0d2b02c,0xa51baba7,0x34b7341a,0x317a3257,0xa902a2ad,0xb552b61a,0x2d0026ad,
  0x2f8c309f,0xaddcac2e,0xb371b487,0x31cf3029,0x2c2e2ddc,0xb09faf8c,0xb029b1cf,0x34873371,0x22ad2902,0xb257b17a,0xa6adad00,0x361a3552,
  0x32cd33e3,0xaa31a420,0xb682b76f,0x2e2d281f,0x30ac31bb,0xaf3fad2a,0xb493b58d,0x33283122,0x2d2a2f3f,0xb1bbb0ac,0xb122b328,0x358d3493,
  0x24202a31,0xb3e3b2cd,0xa81fae2d,0x376f3682,0x341334bc,0xab5fa4e9,0xb7a6b85a,0x2f5928e8,0x319432da,0xb052ae28,0xb56ab68d,0x343e3219,
  0x2e283052,0xb2dab194,0xb219b43e,0x368d356a,0x24e92b5f,0xb4bcb413,0xa8e8af59,0x385a37a6,0x34c3358c,0xac47a5b2,0xb85fb8f3,0x304229b1,
  0x327e33fd,0xb106af26,0xb63cb785,0x34e7330f,0x2f263106,0xb3fdb27e,0xb30fb4e7,0x3785363c,0x25b22c47,0xb58cb4c3,0xa9b1b042,0x38f3385f,
  0x35773662,0xacdea67b,0xb8e5b982,0x30d72a7a,0x336b3493,0xb1bbb012,0xb70ab83a,0x358d3402,0x301231bb,0xb493b36b,0xb402b58d,0x383a370a,
  0x267b2cde,0xb662b577,0xaa7ab0d7,0x398238e5,0x36303741,0xad76a744,0xb962ba04,0x316c2b43,0x342e352a,0xb271b092,0xb7d2b8ad,0x3631347b,
  0x30923271,0xb52ab42e,0xb47bb631,0x38ad37d2,0x27442d76,0xb741b630,0xab43b16c,0x3a043962,0x36ee3815,0xae0ea807,0xb9d6ba7a,0x32012c06,
  0x34a735c4,0xb329b113,0xb84ab91b,0x36d234f3,0x31133329,0xb5c4b4a7,0xb4f3b6d2,0x391b384a,0x28072e0e,0xb815b6ee,0xac06b201,0x3a7a39d6,
  0x37b4388e,0xaea7a86b,0xba41bae1,0x32942c6a,0x35233662,0xb3e3b194,0xb8a8b982,0x376f356a,0x319433e3,0xb662b523,0xb56ab76f,0x398238a8,
  0x286b2ea7,0xb88eb7b4,0xac6ab294,0x3ae13a41,0x3841390f,0xaf3fa8d0,0xbaa2bb3a,0x33282cce,0x35a13705,0xb44fb216,0xb902b9e3,0x380535df,
  0x3216344f,0xb705b5a1,0xb5dfb805,0x39e33902,0x28d02f3f,0xb90fb841,0xacceb328,0x3b3a3aa2,0x38ac3997,0xafd8a935,0xbaf7bb83,0x33ba2d33,
  0x362137ac,0xb4aeb298,0xb958ba3d,0x38503654,0x329834ae,0xb7acb621,0xb654b850,0x3a3d3958,0x29352fd8,0xb997b8ac,0xad33b3ba,0x3b833af7,
  0x391c3a28,0xb039a999,0xbb42bbbc,0x34262d97,0x36a4382d,0xb50eb31c,0xb9aaba90,0x389936c6,0x331c350e,0xb82db6a4,0xb6c6b899,0x3a9039aa,
  0x29993039,0xba28b91c,0xad97b426,0x3bbc3b42,0x39923ac3,0xb085a9fe,0xbb81bbe3,0x346f2dfb,0x372a3886,0xb570b3a0,0xb9f8badb,0x38e03737,
  0x33a03570,0xb886b72a,0xb737b8e0,0x3adb39f8,0x29fe3085,0xbac3b992,0xadfbb46f,0x3be33b81,
};

#define PROF(slot) do {} while (0)
#define PROF_DUMP() do {} while (0)
#define PROFA(slot, dep) do {} while (0)
#define PROF3(slot) do {} while (0)
#define PROF2(slot) do {} while (0)

__device__ __forceinline__ uint32_t smem_u32(const void* p) { return (uint32_t)__cvta_generic_to_shared(p); }

__device__ __forceinline__ void mbar_init(uint32_t a, uint32_t c) {
  asm volatile("mbarrier.init.shared::cta.b64 [%0], %1;\n" ::"r"(a), "r"(c) : "memory");
}
__device__ __forceinline__ void mbar_expect_tx(uint32_t a, uint32_t bytes) {
  asm volatile("mbarrier.arrive.expect_tx.shared::cta.b64 _, [%0], %1;\n" ::"r"(a), "r"(bytes) : "memory");
}
__device__ __forceinline__ void mbar_arrive_cluster(uint32_t cluster_addr) {
  asm volatile("mbarrier.arrive.shared::cluster.b64 _, [%0];\n" ::"r"(cluster_addr) : "memory");
}
__device__ __forceinline__ void mbar_arrive_cluster_n(uint32_t cluster_addr, uint32_t n) {
  asm volatile("mbarrier.arrive.shared::cluster.b64 _, [%0], %1;\n" ::"r"(cluster_addr), "r"(n) : "memory");
}
__device__ __forceinline__ bool mbar_try(uint32_t a, uint32_t parity) {
  uint32_t ok;
  asm volatile("{\n.reg .pred p;\nmbarrier.try_wait.parity.shared::cta.b64 p, [%1], %2;\nselp.u32 %0, 1, 0, p;\n}\n"
               : "=r"(ok) : "r"(a), "r"(parity) : "memory");
  return ok;
}
__device__ __forceinline__ void mbar_wait(uint32_t a, uint32_t parity) {
  if (mbar_try(a, parity)) return;
#pragma unroll 1
  for (int n = 0; n < SPIN_LIMIT; n++)
    if (mbar_try(a, parity)) break;
}
__device__ __forceinline__ bool elect_one() {
  uint32_t p;
  asm volatile("{\n.reg .pred P;\nelect.sync _|P, 0xffffffff;\nselp.u32 %0, 1, 0, P;\n}\n" : "=r"(p));
  return p;
}
__device__ __forceinline__ uint32_t mapa(uint32_t a, uint32_t rank) {
  uint32_t r;
  asm volatile("mapa.shared::cluster.u32 %0, %1, %2;\n" : "=r"(r) : "r"(a), "r"(rank));
  return r;
}
__device__ __forceinline__ void nb_sync(int id, int n) { asm volatile("bar.sync %0, %1;\n" ::"r"(id), "r"(n) : "memory"); }
__device__ __forceinline__ void nb_arrive(int id, int n) { asm volatile("bar.arrive %0, %1;\n" ::"r"(id), "r"(n) : "memory"); }
__device__ __forceinline__ void cluster_sync_all() {
  asm volatile("barrier.cluster.arrive.relaxed.aligned;\nbarrier.cluster.wait.aligned;\n" ::: "memory");
}
__device__ __forceinline__ void fence_async_smem() { asm volatile("fence.proxy.async.shared::cta;\n" ::: "memory"); }
__device__ __forceinline__ void fence_async_all() { asm volatile("fence.proxy.async.global;\n" ::: "memory"); }

__device__ __forceinline__ void tma_load_3d(uint32_t dst, const CUtensorMap* tm, uint32_t bar, int c0, int c1, int c2) {
  asm volatile(
      "cp.async.bulk.tensor.3d.shared::cluster.global.mbarrier::complete_tx::bytes [%0], [%1, {%3, %4, %5}], [%2];\n"
      ::"r"(dst), "l"(tm), "r"(bar), "r"(c0), "r"(c1), "r"(c2) : "memory");
}
__device__ __forceinline__ void tma_load_4d(uint32_t dst, const CUtensorMap* tm, uint32_t bar, int c0, int c1, int c2, int c3) {
  asm volatile(
      "cp.async.bulk.tensor.4d.shared::cluster.global.mbarrier::complete_tx::bytes [%0], [%1, {%3, %4, %5, %6}], [%2];\n"
      ::"r"(dst), "l"(tm), "r"(bar), "r"(c0), "r"(c1), "r"(c2), "r"(c3) : "memory");
}
__device__ __forceinline__ void tma_load_3d_mc(uint32_t dst, const CUtensorMap* tm, uint32_t bar, int c0, int c1, int c2) {
  asm volatile(
      "cp.async.bulk.tensor.3d.shared::cluster.global.mbarrier::complete_tx::bytes.multicast::cluster [%0], [%1, {%3, %4, %5}], [%2], %6;\n"
      ::"r"(dst), "l"(tm), "r"(bar), "r"(c0), "r"(c1), "r"(c2), "h"((uint16_t)3) : "memory");
}
__device__ __forceinline__ void bulk_load(uint32_t dst, const void* src, uint32_t bytes, uint32_t bar) {
  asm volatile("cp.async.bulk.shared::cluster.global.mbarrier::complete_tx::bytes [%0], [%1], %2, [%3];\n"
               ::"r"(dst), "l"(src), "r"(bytes), "r"(bar) : "memory");
}
__device__ __forceinline__ void tma_store_3d(const CUtensorMap* tm, uint32_t src, int c0, int c1, int c2) {
  asm volatile("cp.async.bulk.tensor.3d.global.shared::cta.bulk_group [%0, {%2, %3, %4}], [%1];\n"
               ::"l"(tm), "r"(src), "r"(c0), "r"(c1), "r"(c2) : "memory");
}
__device__ __forceinline__ void bulk_commit() { asm volatile("cp.async.bulk.commit_group;\n" ::: "memory"); }
__device__ __forceinline__ void bulk_wait0() { asm volatile("cp.async.bulk.wait_group 0;\n" ::: "memory"); }
__device__ __forceinline__ void prefetch_tmap(const CUtensorMap* tm) {
  asm volatile("prefetch.tensormap [%0];\n" ::"l"(tm) : "memory");
}

__device__ __forceinline__ void wg_fence() { asm volatile("wgmma.fence.sync.aligned;\n" ::: "memory"); }
__device__ __forceinline__ void wg_commit() { asm volatile("wgmma.commit_group.sync.aligned;\n" ::: "memory"); }
template <int N> __device__ __forceinline__ void wg_wait() {
  asm volatile("wgmma.wait_group.sync.aligned %0;\n" ::"n"(N) : "memory");
}
__device__ __forceinline__ uint64_t mkdesc(uint32_t addr, uint32_t lbo, uint32_t sbo, uint32_t swz) {
  return (uint64_t)((addr & 0x3FFFF) >> 4) | ((uint64_t)(lbo >> 4) << 16) | ((uint64_t)(sbo >> 4) << 32) |
         ((uint64_t)swz << 62);
}

#define R4(d, o) "+f"(d[o + 0]), "+f"(d[o + 1]), "+f"(d[o + 2]), "+f"(d[o + 3])
#define R8(d, o) R4(d, o), R4(d, o + 4)
#define R16(d, o) R8(d, o), R8(d, o + 8)
#define R32(d, o) R16(d, o), R16(d, o + 16)
#define R64(d, o) R32(d, o), R32(d, o + 32)

__device__ __forceinline__ void wgmma_n192(float (&d)[96], uint64_t da, uint64_t db, uint32_t acc) {
  asm volatile(
      "{\n.reg .pred p;\nsetp.ne.u32 p, %98, 0;\n"
      "wgmma.mma_async.sync.aligned.m64n192k16.f32.bf16.bf16 "
      "{%0,%1,%2,%3,%4,%5,%6,%7,%8,%9,%10,%11,%12,%13,%14,%15,%16,%17,%18,%19,%20,%21,%22,%23,%24,%25,%26,%27,%28,%29,%30,%31,"
      "%32,%33,%34,%35,%36,%37,%38,%39,%40,%41,%42,%43,%44,%45,%46,%47,%48,%49,%50,%51,%52,%53,%54,%55,%56,%57,%58,%59,%60,%61,%62,%63,"
      "%64,%65,%66,%67,%68,%69,%70,%71,%72,%73,%74,%75,%76,%77,%78,%79,%80,%81,%82,%83,%84,%85,%86,%87,%88,%89,%90,%91,%92,%93,%94,%95}, "
      "%96, %97, p, 1, 1, 0, 1;\n}\n"
      : R64(d, 0), R32(d, 64)
      : "l"(da), "l"(db), "r"(acc));
}
__device__ __forceinline__ void wgmma_n128(float (&d)[64], uint64_t da, uint64_t db, uint32_t acc) {
  asm volatile(
      "{\n.reg .pred p;\nsetp.ne.u32 p, %66, 0;\n"
      "wgmma.mma_async.sync.aligned.m64n128k16.f32.bf16.bf16 "
      "{%0,%1,%2,%3,%4,%5,%6,%7,%8,%9,%10,%11,%12,%13,%14,%15,%16,%17,%18,%19,%20,%21,%22,%23,%24,%25,%26,%27,%28,%29,%30,%31,"
      "%32,%33,%34,%35,%36,%37,%38,%39,%40,%41,%42,%43,%44,%45,%46,%47,%48,%49,%50,%51,%52,%53,%54,%55,%56,%57,%58,%59,%60,%61,%62,%63}, "
      "%64, %65, p, 1, 1, 0, 1;\n}\n"
      : R64(d, 0)
      : "l"(da), "l"(db), "r"(acc));
}
template <int N> __device__ __forceinline__ void fence_regs(float (&d)[N]) {
#pragma unroll
  for (int i = 0; i < N; i++) asm volatile("" : "+f"(d[i])::"memory");
}

__device__ __forceinline__ void mma16816(float (&d)[4], uint32_t a0, uint32_t a1, uint32_t a2, uint32_t a3, uint32_t b0,
                                         uint32_t b1) {
  asm("mma.sync.aligned.m16n8k16.row.col.f32.bf16.bf16.f32 {%0,%1,%2,%3}, {%4,%5,%6,%7}, {%8,%9}, {%0,%1,%2,%3};\n"
      : "+f"(d[0]), "+f"(d[1]), "+f"(d[2]), "+f"(d[3])
      : "r"(a0), "r"(a1), "r"(a2), "r"(a3), "r"(b0), "r"(b1));
}
__device__ __forceinline__ void mma16816_z(float (&d)[4], uint32_t a0, uint32_t a1, uint32_t a2, uint32_t a3, uint32_t b0,
                                           uint32_t b1) {
  asm("mma.sync.aligned.m16n8k16.row.col.f32.bf16.bf16.f32 {%0,%1,%2,%3}, {%4,%5,%6,%7}, {%8,%9}, {%10,%10,%10,%10};\n"
      : "=f"(d[0]), "=f"(d[1]), "=f"(d[2]), "=f"(d[3])
      : "r"(a0), "r"(a1), "r"(a2), "r"(a3), "r"(b0), "r"(b1), "f"(0.f));
}
__device__ __forceinline__ void ldsm4t(uint32_t (&r)[4], uint32_t a) {
  asm volatile("ldmatrix.sync.aligned.m8n8.x4.trans.shared.b16 {%0,%1,%2,%3}, [%4];\n"
               : "=r"(r[0]), "=r"(r[1]), "=r"(r[2]), "=r"(r[3]) : "r"(a) : "memory");
}
__device__ __forceinline__ void ldsm2t(uint32_t& r0, uint32_t& r1, uint32_t a) {
  asm volatile("ldmatrix.sync.aligned.m8n8.x2.trans.shared.b16 {%0,%1}, [%2];\n" : "=r"(r0), "=r"(r1) : "r"(a) : "memory");
}
__device__ __forceinline__ void st_async128(uint32_t a, uint32_t bar, uint32_t x, uint32_t y, uint32_t z, uint32_t w) {
  asm volatile("st.async.weak.shared::cluster.mbarrier::complete_tx::bytes.v4.b32 [%0], {%2,%3,%4,%5}, [%1];\n"
               ::"r"(a), "r"(bar), "r"(x), "r"(y), "r"(z), "r"(w) : "memory");
}
__device__ __forceinline__ void mbar_arrive(uint32_t a) {
  asm volatile("mbarrier.arrive.shared::cta.b64 _, [%0];\n" ::"r"(a) : "memory");
}
__device__ __forceinline__ void stsm4(uint32_t a, uint32_t r0, uint32_t r1, uint32_t r2, uint32_t r3) {
  asm volatile("stmatrix.sync.aligned.m8n8.x4.shared.b16 [%0], {%1,%2,%3,%4};\n"
               ::"r"(a), "r"(r0), "r"(r1), "r"(r2), "r"(r3) : "memory");
}
__device__ __forceinline__ void stsm4t(uint32_t a, uint32_t r0, uint32_t r1, uint32_t r2, uint32_t r3) {
  asm volatile("stmatrix.sync.aligned.m8n8.x4.trans.shared.b16 [%0], {%1,%2,%3,%4};\n"
               ::"r"(a), "r"(r0), "r"(r1), "r"(r2), "r"(r3) : "memory");
}
__device__ __forceinline__ uint2 lds64(uint32_t a) {
  uint2 v;
  asm volatile("ld.shared.v2.u32 {%0,%1}, [%2];\n" : "=r"(v.x), "=r"(v.y) : "r"(a));
  return v;
}
__device__ __forceinline__ uint4 lds128(uint32_t a) {
  uint4 v;
  asm volatile("ld.shared.v4.u32 {%0,%1,%2,%3}, [%4];\n" : "=r"(v.x), "=r"(v.y), "=r"(v.z), "=r"(v.w) : "r"(a) : "memory");
  return v;
}
__device__ __forceinline__ void sts128(uint32_t a, uint32_t x, uint32_t y, uint32_t z, uint32_t w) {
  asm volatile("st.shared.v4.u32 [%0], {%1,%2,%3,%4};\n" ::"r"(a), "r"(x), "r"(y), "r"(z), "r"(w) : "memory");
}
__device__ __forceinline__ void sts64(uint32_t a, uint32_t x, uint32_t y) {
  asm volatile("st.shared.v2.u32 [%0], {%1,%2};\n" ::"r"(a), "r"(x), "r"(y) : "memory");
}
__device__ __forceinline__ uint32_t pack_bf16(float lo, float hi) {
  uint32_t r;
  asm("cvt.rn.bf16x2.f32 %0, %1, %2;\n" : "=r"(r) : "f"(hi), "f"(lo));
  return r;
}
__device__ __forceinline__ uint32_t bmul2(uint32_t a, uint32_t b) {
  uint32_t r;
  asm("mul.rn.bf16x2 %0, %1, %2;\n" : "=r"(r) : "r"(a), "r"(b));
  return r;
}
__device__ __forceinline__ uint32_t bmax2(uint32_t a, uint32_t b) {
  uint32_t r;
  asm("max.bf16x2 %0, %1, %2;\n" : "=r"(r) : "r"(a), "r"(b));
  return r;
}
__device__ __forceinline__ uint32_t bfma2(uint32_t a, uint32_t b, uint32_t c) {
  uint32_t r;
  asm("fma.rn.bf16x2 %0, %1, %2, %3;\n" : "=r"(r) : "r"(a), "r"(b), "r"(c));
  return r;
}
__device__ __forceinline__ uint32_t badd2(uint32_t a, uint32_t b) {
  uint32_t r;
  asm("add.rn.bf16x2 %0, %1, %2;\n" : "=r"(r) : "r"(a), "r"(b));
  return r;
}
__device__ __forceinline__ void prefetch_l2(const void* p) { asm volatile("prefetch.global.L2 [%0];\n" ::"l"(p)); }
__device__ __forceinline__ void cp_async16n(uint32_t dst, const void* src) {
  asm volatile("cp.async.cg.shared.global [%0], [%1], 16;\n" ::"r"(dst), "l"(src) : "memory");
}
__device__ __forceinline__ void cp_async16(uint32_t dst, const void* src, uint32_t srcbytes) {
  asm volatile("cp.async.cg.shared.global.L2::256B [%0], [%1], 16, %2;\n" ::"r"(dst), "l"(src), "r"(srcbytes) : "memory");
}
__device__ __forceinline__ uint32_t ld_acquire(const uint32_t* p) {
  uint32_t v;
  asm volatile("ld.acquire.gpu.global.u32 %0, [%1];\n" : "=r"(v) : "l"(p) : "memory");
  return v;
}
__device__ __forceinline__ uint32_t ld_relaxed(const uint32_t* p) {
  uint32_t v;
  asm volatile("ld.relaxed.gpu.global.u32 %0, [%1];\n" : "=r"(v) : "l"(p) : "memory");
  return v;
}
__device__ __forceinline__ void st_release(uint32_t* p, uint32_t v) {
  asm volatile("st.release.gpu.global.u32 [%0], %1;\n" ::"l"(p), "r"(v) : "memory");
}
__device__ __forceinline__ void wait_flag(const uint32_t* p, uint32_t want) {
  int n = 0;
  while (ld_acquire(p) != want && ++n < SPIN_LIMIT) {}
}

struct Params {
  const __nv_bfloat16* x;
  const __nv_bfloat16* w;
  const __nv_bfloat16* q;
  const __nv_bfloat16* k;
  const __nv_bfloat16* v;
  const __nv_bfloat16* shift_k;
  const __nv_bfloat16* ssm_k;
  const __nv_bfloat16* ssm_D;
  const __nv_bfloat16* wo;
  __nv_bfloat16* out;
  uint32_t zero;
};

__device__ __forceinline__ uint32_t lds32(uint32_t a) {
  uint32_t v;
  asm volatile("ld.shared.u32 %0, [%1];\n" : "=r"(v) : "r"(a));
  return v;
}
__device__ __forceinline__ float bf_lo(uint32_t v) {
  uint32_t r;
  asm("prmt.b32 %0, %1, 0, 0x1044;\n" : "=r"(r) : "r"(v));
  return __uint_as_float(r);
}
__device__ __forceinline__ float bf_hi(uint32_t v) { return __uint_as_float(v & 0xffff0000u); }
__device__ __forceinline__ float ex2(float x) {
  float r;
  asm("ex2.approx.ftz.f32 %0, %1;\n" : "=f"(r) : "f"(x));
  return r;
}
__device__ __forceinline__ float rcp(float x) {
  float r;
  asm("rcp.approx.ftz.f32 %0, %1;\n" : "=f"(r) : "f"(x));
  return r;
}

#define Q4(c, d, o) c(d[o + 0]), c(d[o + 1]), c(d[o + 2]), c(d[o + 3])
#define Q8(c, d, o) Q4(c, d, o), Q4(c, d, o + 4)
#define Q16(c, d, o) Q8(c, d, o), Q8(c, d, o + 8)
#define Q32(c, d) Q16(c, d, 0), Q16(c, d, 16)
#define L8 "{%0,%1,%2,%3,%4,%5,%6,%7}"
#define L16 "{%0,%1,%2,%3,%4,%5,%6,%7,%8,%9,%10,%11,%12,%13,%14,%15}"
#define L32 "{%0,%1,%2,%3,%4,%5,%6,%7,%8,%9,%10,%11,%12,%13,%14,%15,%16,%17,%18,%19,%20,%21,%22,%23,%24,%25,%26,%27,%28,%29,%30,%31}"
__device__ __forceinline__ void fft_rows(uint32_t (&d)[32], const uint32_t (&a)[2][4], uint64_t db) {
  asm volatile("wgmma.mma_async.sync.aligned.m64n128k16.f16.f16.f16 " L32 ", {%32,%33,%34,%35}, %36, 0, 1, 1, 1;\n"
               : Q32("=r", d) : "r"(a[0][0]), "r"(a[0][1]), "r"(a[0][2]), "r"(a[0][3]), "l"(db));
  asm volatile("wgmma.mma_async.sync.aligned.m64n128k16.f16.f16.f16 " L32 ", {%32,%33,%34,%35}, %36, 1, 1, 1, 1;\n"
               : Q32("+r", d) : "r"(a[1][0]), "r"(a[1][1]), "r"(a[1][2]), "r"(a[1][3]), "l"(db + 128));
}
template <int INV> __device__ __forceinline__ void fft_cols(uint32_t (&d)[8], const uint32_t (&a)[2][4], uint64_t db) {
  asm volatile("wgmma.mma_async.sync.aligned.m64n32k16.f16.f16.f16 " L8 ", {%8,%9,%10,%11}, %12, 0, 1, 1, %13;\n"
               : Q8("=r", d, 0) : "r"(a[0][0]), "r"(a[0][1]), "r"(a[0][2]), "r"(a[0][3]), "l"(db), "n"(INV));
  asm volatile("wgmma.mma_async.sync.aligned.m64n32k16.f16.f16.f16 " L8 ", {%8,%9,%10,%11}, %12, 1, 1, 1, %13;\n"
               : Q8("+r", d, 0) : "r"(a[1][0]), "r"(a[1][1]), "r"(a[1][2]), "r"(a[1][3]), "l"(db + (INV ? 16 : 64)), "n"(INV));
}
__device__ __forceinline__ void fft_back(float (&d)[16], uint64_t da, uint64_t db) {
  asm volatile("wgmma.mma_async.sync.aligned.m64n32k16.f32.f16.f16 " L16 ", %16, %17, 0, 1, 1, 1, 1;\n"
               : Q16("=f", d, 0) : "l"(da), "l"(db));
#pragma unroll
  for (int i = 1; i < 4; i++)
    asm volatile("wgmma.mma_async.sync.aligned.m64n32k16.f32.f16.f16 " L16 ", %16, %17, 1, 1, 1, 1, 1;\n"
                 : Q16("+f", d, 0) : "l"(da + 32 * i), "l"(db + 64 * i));
}
__device__ __forceinline__ uint32_t hmul2(uint32_t a, uint32_t b) {
  uint32_t r;
  asm("mul.rn.f16x2 %0, %1, %2;\n" : "=r"(r) : "r"(a), "r"(b));
  return r;
}
__device__ __forceinline__ uint32_t hadd2(uint32_t a, uint32_t b) {
  uint32_t r;
  asm("add.rn.f16x2 %0, %1, %2;\n" : "=r"(r) : "r"(a), "r"(b));
  return r;
}
__device__ __forceinline__ uint32_t hneg2(uint32_t a) {
  uint32_t r;
  asm("neg.f16x2 %0, %1;\n" : "=r"(r) : "r"(a));
  return r;
}
__device__ __forceinline__ uint32_t hfma2(uint32_t a, uint32_t b, uint32_t c) {
  uint32_t r;
  asm("fma.rn.f16x2 %0, %1, %2, %3;\n" : "=r"(r) : "r"(a), "r"(b), "r"(c));
  return r;
}
__device__ __forceinline__ uint32_t pack_f16(float lo, float hi) {
  uint32_t r;
  asm("cvt.rn.f16x2.f32 %0, %1, %2;\n" : "=r"(r) : "f"(hi), "f"(lo));
  return r;
}
__device__ __forceinline__ uint32_t bmaxabs2(uint32_t a, uint32_t b) {
  uint32_t r;
  asm("max.xorsign.abs.bf16x2 %0, %1, %2;\n" : "=r"(r) : "r"(a), "r"(b));
  return r;
}
struct C2 { uint32_t r, i; };
__device__ __forceinline__ C2 cmul(C2 a, C2 b) {
  return C2{hfma2(a.r, b.r, hneg2(hmul2(a.i, b.i))), hfma2(a.r, b.i, hmul2(a.i, b.r))};
}
__device__ __forceinline__ C2 cfma(C2 a, C2 b, C2 c) {
  return C2{hfma2(a.r, b.r, hfma2(hneg2(a.i), b.i, c.r)), hfma2(a.r, b.i, hfma2(a.i, b.r, c.i))};
}
__device__ __forceinline__ C2 crot(C2 z, C2 t) {
  const uint32_t r = hfma2(t.r, z.i, z.r), i = hfma2(t.i, r, z.i);
  return C2{hfma2(t.r, i, r), i};
}
__device__ __forceinline__ C2 cget(const uint32_t (&e)[8], int j, int b) { return C2{e[4 * j + b], e[4 * j + 2 + b]}; }
template <int N> __device__ __forceinline__ void fence_regs(uint32_t (&d)[N]) {
#pragma unroll
  for (int i = 0; i < N; i++) asm volatile("" : "+r"(d[i])::"memory");
}
__device__ __forceinline__ void ldsm4(uint32_t (&r)[4], uint32_t a) {
  asm volatile("ldmatrix.sync.aligned.m8n8.x4.shared.b16 {%0,%1,%2,%3}, [%4];\n"
               : "=r"(r[0]), "=r"(r[1]), "=r"(r[2]), "=r"(r[3]) : "r"(a) : "memory");
}

__device__ __forceinline__ uint32_t movm(uint32_t a) {
  uint32_t r;
  asm volatile("movmatrix.sync.aligned.m8n8.trans.b16 %0, %1;\n" : "=r"(r) : "r"(a));
  return r;
}
template <int C0, int H, bool T> __device__ __forceinline__ void attn_pack(const float (&acc)[96], uint32_t (&d)[8]) {
#pragma unroll
  for (int c = 0; c < 8; c++) {
    asm volatile("cvt.rn.bf16x2.f32 %0, %1, %2;\n" : "=r"(d[c]) : "f"(acc[4 * (C0 + c) + 2 * H + 1]), "f"(acc[4 * (C0 + c) + 2 * H]));
    if (T) d[c] = movm(d[c]);
  }
}
__device__ __forceinline__ void attn_qk(float (&s)[4], const uint32_t (&qlo)[8], const uint32_t (&qhi)[8],
                                        const uint32_t (&k)[8], int c) {
  mma16816_z(s, qlo[c], qhi[c], qlo[c + 1], qhi[c + 1], k[c], k[c + 1]);
  mma16816(s, qlo[c + 2], qhi[c + 2], qlo[c + 3], qhi[c + 3], k[c + 2], k[c + 3]);
}
template <int N> __device__ __forceinline__ void quad_softmax(float (&x)[N][2], uint32_t (&pp)[N]) {
  const float c2 = 1.4426950408889634f;
  uint32_t q[N], mx[N / 2];
#pragma unroll
  for (int n = 0; n < N; n++) {
    const uint32_t r = pack_bf16(x[n][0], x[n][1]);
    q[n] = bfma2(r, 0x3e353e35u, bmul2(r, 0x379e379eu));
    x[n][0] = bf_lo(q[n]);
    x[n][1] = bf_hi(q[n]);
  }
#pragma unroll
  for (int n = 0; n < N / 2; n++)
    mx[n] = bmax2(__byte_perm(q[2 * n], q[2 * n + 1], 0x5410), __byte_perm(q[2 * n], q[2 * n + 1], 0x7632));
#pragma unroll
  for (int o = 1; o <= 2; o++) {
#pragma unroll
    for (int n = 0; n < N / 2; n++) mx[n] = bmax2(mx[n], __shfl_xor_sync(0xffffffffu, mx[n], o));
  }
  float m[N], t[N];
#pragma unroll
  for (int n = 0; n < N / 2; n++) {
    m[2 * n] = bf_lo(mx[n]);
    m[2 * n + 1] = bf_hi(mx[n]);
  }
#pragma unroll
  for (int n = 0; n < N; n++) {
    const float nm = -m[n] * c2;
    x[n][0] = ex2(fmaf(x[n][0], c2, nm));
    x[n][1] = ex2(fmaf(x[n][1], c2, nm));
  }
#pragma unroll
  for (int n = 0; n < N; n += 2) {
    float u0, u1;
    asm("mma.sync.aligned.m16n8k8.row.col.f32.tf32.tf32.f32 {%0,%1,%2,%3}, {%4,%5,%6,%7}, {%8,%8}, {%9,%9,%9,%9};\n"
        : "=f"(t[n]), "=f"(u0), "=f"(t[n + 1]), "=f"(u1)
        : "r"(__float_as_uint(x[n][0])), "r"(__float_as_uint(x[n + 1][0])), "r"(__float_as_uint(x[n][1])),
          "r"(__float_as_uint(x[n + 1][1])), "r"(0x3f800000u), "f"(0.f));
  }
#pragma unroll
  for (int n = 0; n < N; n++) {
    const float inv = rcp(t[n]);
    pp[n] = pack_bf16(x[n][0] * inv, x[n][1] * inv);
  }
}
__device__ __forceinline__ void attn_pv(uint32_t dst, const uint32_t (&vp)[8], const uint32_t (&vo)[8], int c, uint32_t pp,
                                        uint32_t maskLE) {
  const uint32_t b0 = pp & ~maskLE, b1 = pp & maskLE;
  float oa[4], ob[4];
  mma16816_z(oa, vp[c], vp[c + 1], vo[c], vo[c + 1], b0, b1);
  mma16816_z(ob, vp[c + 2], vp[c + 3], vo[c + 2], vo[c + 3], b0, b1);
  stsm4t(dst, pack_bf16(oa[0], oa[1]), pack_bf16(oa[2], oa[3]), pack_bf16(ob[0], ob[1]), pack_bf16(ob[2], ob[3]));
}

template <int MODE>
__global__ void __cluster_dims__(2, 1, 1) __launch_bounds__(NTHREADS, 1)
fused_kernel(const Params p, const __grid_constant__ CUtensorMap tmX, const __grid_constant__ CUtensorMap tmW,
             const __grid_constant__ CUtensorMap tmWo, const __grid_constant__ CUtensorMap tmQ,
             const __grid_constant__ CUtensorMap tmOb,
             const __grid_constant__ CUtensorMap tmXh, const __grid_constant__ CUtensorMap tmWh) {
  extern __shared__ __align__(1024) uint8_t smem[];
  if (threadIdx.x < 32) {
    const uint32_t i = (blockIdx.x & 127) * 16 + (threadIdx.x & 15);
    prefetch_l2(threadIdx.x & 16 ? (const char*)p.w + i * 128 : (const char*)p.x + i * 2048);
  }
  const uint32_t sb = smem_u32(smem);
  const uint32_t bars = sb + OFF_BAR;
  const int tid = threadIdx.x, lane = tid & 31, warp = __shfl_sync(0xffffffffu, tid >> 5, 0);
  const int rank = blockIdx.x & 1;
  const bool halo_cta = blockIdx.x < 4;
  if (halo_cta && MODE != 0) return;
  int grp, mem;
  {
    const int t = (blockIdx.x >> 1) - 4, u = t - 32;
    const int q7 = (u * 37) >> 8;
    const bool lo = (unsigned)t < 32u, mid = (unsigned)u < 28u;
    grp = lo ? (t & 7) : (mid ? 1 + u - 7 * q7 : 0);
    mem = lo ? (t >> 3) : (mid ? 4 + q7 : (t < 0 ? t + 6 : t - 54));
  }
  const int rg = (grp >> 2) * 4 + (mem >> 1), hp = (grp & 3) * 4 + (mem & 1) * 2 + rank;
  const int rb2 = (grp >> 2) * 8 + mem, cb2 = (grp & 3) * 2 + rank;
  const int chb = grp * 16 + mem * 2 + rank;
  const int cta = rg * 16 + hp;
  const int hsel = rb2 & 1;
  constexpr int g2wg = G2W;
  const int par = rg >> 2, gidx = rg & 3;

  if (tid < 256 && !halo_cta && MODE != 2) {
    const int r = tid >> 3, c = tid & 7;
    const uint32_t so = r * 128 + ((c ^ (r & 7)) << 4);
    const __nv_bfloat16* wg0 = p.w + (size_t)r * (3 * DM) + hp * 64 + c * 8;
    const __nv_bfloat16* xg0 = p.x + (size_t)(2 * (gidx * 256 + r) + par) * DM + c * 8;
#pragma unroll
    for (int j = 0; j < 3; j++) cp_async16n(sb + OFF_1B + j * 4096 + so, wg0 + j * DM);
#pragma unroll
    for (int i = 0; i < 8; i++) cp_async16n(sb + i * 4096 + so, xg0 + (size_t)i * 64 * DM);
    asm volatile("cp.async.commit_group;\n" ::: "memory");
  }
  auto halo_issue = [&](int kb, int s) {
    const uint32_t fb = bars + 8 * (BAR_FULLB + s), st = sb + s * STGH;
    mbar_expect_tx(fb, STGH - 2048);
    tma_load_3d(st + 8192, &tmWh, fb, 0, kb * 64, 16 + blockIdx.x * 4);
    tma_load_3d(st + 8192 + 32768, &tmWh, fb, 0, kb * 64, 32 + blockIdx.x * 4);
    tma_load_4d(st, &tmXh, fb, kb * 64, 248, 0, 0);
  };
  if (tid == 256) {
    prefetch_tmap(halo_cta ? &tmXh : &tmX);
#pragma unroll
    for (int i = 0; i < NS1B; i++) mbar_init(bars + 8 * (BAR_FULLB + i), 1);
#pragma unroll
    for (int i = 0; i < NS1A; i++) mbar_init(bars + 8 * (BAR_FULLA + i), 1);
    asm volatile("fence.mbarrier_init.release.cluster;\n" ::: "memory");
    if (!halo_cta && MODE != 2) {
      mbar_expect_tx(bars + 8 * (BAR_FULLB + 1), STG1B);
      tma_load_3d(sb + OFF_1B + 1 * STG1B, &tmW, bars + 8 * (BAR_FULLB + 1), hp * 64, 32, 0);
      mbar_expect_tx(bars + 8 * (BAR_FULLB + 2), STG1B);
      tma_load_3d(sb + OFF_1B + 2 * STG1B, &tmW, bars + 8 * (BAR_FULLB + 2), hp * 64, 64, 0);
    } else if (halo_cta) {
      halo_issue(0, 0);
    }
  } else if (tid == 288) {
#pragma unroll
    for (int i = 0; i < NS1A; i++) mbar_init(bars + 8 * (BAR_EMPTYA + i), 4);
#pragma unroll
    for (int i = 0; i < NS1B; i++) mbar_init(bars + 8 * (BAR_EMPTYB + i), 2);
    mbar_init(bars + 8 * BAR_X, 4);
    mbar_init(bars + 8 * BAR_LAND, 17);
    mbar_init(bars + 8 * BAR_TAB, 16);
    mbar_init(bars + 8 * BAR_U, 1);
    mbar_init(bars + 8 * BAR_H, 1);
    mbar_init(bars + 8 * BAR_STG, 8);
    mbar_init(bars + 8 * BAR_HALO, 1);
    mbar_init(bars + 8 * BAR_Q, 1);
    mbar_init(bars + 8 * BAR_QFREE, 4);
    mbar_init(bars + 8 * (BAR_QFREE + 1), 4);
    asm volatile("fence.mbarrier_init.release.cluster;\n" ::: "memory");
  } else if (tid == 320) {
#pragma unroll
    for (int i = 0; i < NS2; i++) {
      mbar_init(bars + 8 * (BAR_FULL2 + i), 1);
      mbar_init(bars + 8 * (BAR_EMPTY2 + i), i < 5 ? 2 : 8);
    }
    asm volatile("fence.mbarrier_init.release.cluster;\n" ::: "memory");
  } else if (tid == 352) {
#pragma unroll
    for (int i = 0; i < 8; i++) mbar_init(bars + 8 * (BAR_Y + i), 4);
    asm volatile("fence.mbarrier_init.release.cluster;\n" ::: "memory");
  }
  cluster_sync_all();
  if (warp == 8) PROF2(24);

  if (warp >= 8) {
    const int hw = warp - 8;
    const int lr = lane & 7, lm = lane >> 3;
    auto g1_issue_a = [&](int j, int s) {
      const uint32_t fb = bars + 8 * (BAR_FULLA + s);
      mbar_expect_tx(fb, STG1A);
      tma_load_3d_mc(sb + s * STG1A + rank * 16384, &tmX, fb, j * 64, par, gidx * 256 + rank * 128);
    };
    auto g1_issue_b = [&](int kb, int s) {
      const uint32_t fb = bars + 8 * (BAR_FULLB + s);
      mbar_expect_tx(fb, STG1B);
      tma_load_3d(sb + OFF_1B + s * STG1B, &tmW, fb, hp * 64, kb * 32, 0);
    };
    auto g2_k = [&](int kb) { return (kb < 2 ? hp : kb < 4 ? hp & 14 : hp & 12) ^ kb; };
    auto g2_issue_b = [&](int kb, int s) {
      mbar_expect_tx(bars + 8 * (BAR_FULL2 + s), kb || MODE ? STG2 : STG2 / 2);
      tma_load_3d(sb + g2_b(s), &tmWo, bars + 8 * (BAR_FULL2 + s), 0, g2_k(kb) * 64, cb2 * 2);
    };
    asm volatile("setmaxnreg.dec.sync.aligned.u32 %0;\n" :: "n"(REG_HELP));

    if (halo_cta) {
      if (hw == 0) {
        int s = 1, ph = 1;
#pragma unroll 1
        for (int kb = 1; kb < 16; kb++) {
          mbar_wait(bars + 8 * (BAR_EMPTYB + s), ph);
          if (elect_one()) halo_issue(kb, s);
          if (++s == 3) { s = 0; ph ^= 1; }
        }
      }
      __syncwarp();
    } else if (hw == 0) {
      uint32_t epoch = 0;
      if (MODE == 2) {
        if (lane < NS2) mbar_arrive_cluster_n(mapa(bars, rank) + 8 * (BAR_EMPTY2 + lane), lane < 5 ? 2 : 8);
      } else {
      if (lane == 0) {
        mbar_expect_tx(bars + 8 * BAR_U, 32768);
        mbar_expect_tx(bars + 8 * BAR_LAND, 16384);
        mbar_expect_tx(bars + 8 * BAR_Q, 32768);
        prefetch_tmap(&tmQ);
      }
      {
        int sa = 1, pha = 1, sbb = 2, phb = 1;
#pragma unroll 1
        for (int kb = 2; kb < 32; kb++) {
          if (!(kb & 1)) {
            mbar_wait(bars + 8 * (BAR_EMPTYA + sa), pha);
            if (elect_one()) g1_issue_a(kb >> 1, sa);
            if (++sa == NS1A) { sa = 0; pha ^= 1; }
          }
          mbar_wait(bars + 8 * (BAR_EMPTYB + sbb), phb);
          if (kb > 2 && elect_one()) g1_issue_b(kb, sbb);
          __syncwarp();
          if (kb == 4) epoch = ld_relaxed(g_flag_o + cta);
          if (kb == 4) PROF2(27);
          if (kb == 1) PROF2(38);
          if (kb == 2) PROF2(39);
          if (++sbb == NS1B) { sbb = 0; phb ^= 1; }
        }
      }
      auto q_issue = [&](int i) {
        mbar_wait(bars + 8 * (i ? BAR_EMPTYB + 3 : BAR_EMPTYA + 1), i);
        if (elect_one())
          asm volatile(
              "cp.async.bulk.tensor.5d.shared::cluster.global.mbarrier::complete_tx::bytes [%0], [%1, {%3, %4, %4, %4, %5}], [%2];\n"
              ::"r"(sb + g2_b(3 + i)), "l"(&tmQ), "r"(bars + 8 * BAR_Q), "r"((chb & ~1) * 8), "r"(0), "r"(rank * 64 + i * 32)
              : "memory");
        __syncwarp();
      };
      if (QORD < 2) q_issue(0);
      else mbar_wait(bars + 8 * (BAR_EMPTYA + 1), 0);
      if (QORD < 1) q_issue(1);
      epoch++;
      if (lane == 0) {
        prefetch_tmap(&tmWo);
        prefetch_tmap(&tmOb);
        if (gidx != 0) wait_flag(g_flag_h + (hp >> 2), epoch);
      }
      __syncwarp();
      {
        uint4 hk0 = make_uint4(0, 0, 0, 0), hk1 = hk0, hv0 = hk0, hv1 = hk0;
        if (gidx != 0) {
          const uint4* src = g_halo + cta * 128 + lane;
          hk0 = __ldcg(src); hk1 = __ldcg(src + 32); hv0 = __ldcg(src + 64); hv1 = __ldcg(src + 96);
        }
        if (gidx != 0) PROF(18);
        sts128(sb + OFF_KH + lane * 16, hk0.x, hk0.y, hk0.z, hk0.w);
        sts128(sb + OFF_KH + 512 + lane * 16, hk1.x, hk1.y, hk1.z, hk1.w);
        sts64(sb + OFF_KH + 1024 + lane * 8, movm(hv0.x), movm(hv0.y));
        sts64(sb + OFF_KH + 1280 + lane * 8, movm(hv0.z), movm(hv0.w));
        sts64(sb + OFF_KH + 1536 + lane * 8, movm(hv1.x), movm(hv1.y));
        sts64(sb + OFF_KH + 1792 + lane * 8, movm(hv1.z), movm(hv1.w));
        __syncwarp();
        if (lane == 0) mbar_arrive(bars + 8 * BAR_HALO);
      }
      if (QORD == 2) q_issue(0);
      if (QORD >= 1) q_issue(1);
      const uint32_t rb = mapa(bars, lane & 1);
      nb_sync(NB_OREADY, 288);
      if (lane == 0) {
        asm volatile("cp.async.bulk.global.shared::cta.bulk_group [%0], [%1], %2;\n" ::"l"(g_o + (size_t)cta * 16384),
                     "r"(sb + OFF_OP), "r"(32768) : "memory");
        bulk_commit();
      }
      if (lane < 2) {
#pragma unroll
        for (int i = 0; i < 4; i++) mbar_arrive_cluster(rb + 8 * (BAR_EMPTY2 + i + i / 2));
      }
      if (lane == 0) {
        bulk_wait0();
        st_release(g_flag_o + cta, epoch);
      }
      __syncwarp();
      PROF2(17);
      if (lane < 2) mbar_arrive_cluster(rb + 8 * (BAR_EMPTY2 + 2));
      }
      if (MODE != 1) {
        const __nv_bfloat16* osrc = g_o + (size_t)(rb2 >> 1) * 16 * 16384 + hsel * 8192;
        mbar_wait(bars + 8 * (BAR_EMPTY2 + 1), 0);
        if (elect_one()) {
          if (MODE == 0) {
            asm volatile("cp.async.bulk.shared::cluster.shared::cta.mbarrier::complete_tx::bytes [%0], [%1], %2, [%3];\n"
                         ::"r"(mapa(sb + g2_a(1, hsel), rank ^ 1)), "r"(sb + g2_a(0, hsel)), "r"(16384),
                         "r"(mapa(bars + 8 * (BAR_FULL2 + 1), rank ^ 1)) : "memory");
          } else {
            bulk_load(sb + g2_a(0, hsel), osrc + hp * 16384, 16384, bars + 8 * BAR_FULL2);
            bulk_load(sb + g2_a(1, hsel), osrc + (hp ^ 1) * 16384, 16384, bars + 8 * (BAR_FULL2 + 1));
          }
        }
        __syncwarp();
#pragma unroll 1
        for (int kb = 3; kb < 16; kb++) {
          const int s = g2_stage(kb);
          mbar_wait(bars + 8 * (MODE == 0 && kb < 5 ? BAR_QFREE + kb - 3 : BAR_EMPTY2 + s), (G2_PARITY >> kb) & 1);
          if (elect_one()) g2_issue_b(kb, s);
          __syncwarp();
        }
      }
      __syncwarp();
    } else {
      if (MODE != 2) {
      const float dall = __bfloat162float(p.ssm_D[chb * 8 + lr]);
      {
        const int g = lane >> 2, t = lane & 3;
        uint32_t w[2][4];
#pragma unroll
        for (int h = 0; h < 2; h++) {
          const uint2 x = __ldg(reinterpret_cast<const uint2*>(p.shift_k + ((chb & ~1) * 8 + h * 8 + g) * 4));
          w[h][0] = __byte_perm(x.x, x.x, 0x1010);
          w[h][1] = __byte_perm(x.x, x.x, 0x3232);
          w[h][2] = __byte_perm(x.y, x.y, 0x1010);
          w[h][3] = __byte_perm(x.y, x.y, 0x3232);
        }
        auto swz = [](int r) { return (((r & 29) | ((r ^ (r >> 2)) & 2)) << 5) | (r & 16); };
        const uint32_t kring = sb + OFF_X + 4096 + (hw - 1) * 2 * XT, vring = kring + XT;
        const int s0 = rank * 32 + (hw - 1) * 11, s1 = hw == 3 ? rank * 32 + 32 : s0 + 11;
        const size_t goff = (size_t)(lane >> 1) * DM + (chb & ~1) * 8 + (lane & 1) * 8;
        const __nv_bfloat16* kg = p.k + goff;
        const __nv_bfloat16* vg = p.v + goff;
        const uint32_t d0 = swz(lane >> 1) ^ ((lane & 1) << 4), d1 = swz(16 + (lane >> 1)) ^ ((lane & 1) << 4);
        auto issue = [&](int st) {
          const uint32_t so = (st & 3) << 10;
          cp_async16(kring + so + d0, kg + (size_t)st * 32 * DM, 16);
          cp_async16(kring + so + d1, kg + (size_t)(st * 32 + 16) * DM, 16);
          cp_async16(vring + so + d0, vg + (size_t)st * 32 * DM, 16);
          cp_async16(vring + so + d1, vg + (size_t)(st * 32 + 16) * DM, 16);
        };
        const int xa = 8 * (lr >> 1) + 2 * lm + (lr & 1), xb = 8 * (lr >> 1) - 4 + 2 * (lm & 1) + (lr & 1);
        const uint32_t la = swz(xa), lb = swz(xb & 31);
        const int backb = xb < 0 ? 1 : 0;
        const uint32_t ud[2] = {mapa(sb + OFF_X + g * XT + t * 16, 0), mapa(sb + OFF_X + g * XT + t * 16, 1)};
        const uint32_t ub[2] = {mapa(bars + 8 * BAR_U, 0), mapa(bars + 8 * BAR_U, 1)};
        if (tid == 320) prefetch_l2(g_tab + (chb & 63) * 32);
        if (lane == 0) mbar_wait(bars + 8 * (BAR_FULLB + NS1B - 1), 0);
        __syncwarp();
        if (lane >= 24) cp_async16(kring + (((s0 - 1) & 3) << 10) + d1, s0 > 0 ? kg + (size_t)(s0 * 32 - 16) * DM : kg, s0 > 0 ? 16 : 0);
        issue(s0);
        asm volatile("cp.async.commit_group;\n" ::: "memory");
        issue(s0 + 1);
        asm volatile("cp.async.commit_group;\n" ::: "memory");
        uint32_t tn = (uint32_t)clock();
#pragma unroll 1
        for (int st = s0; st < s1; st++) {
          tn += PSTEP;
          while ((int)((uint32_t)clock() - tn) < 0) __nanosleep(100);
          if (st + 2 < s1) issue(st + 2);
          if (hw == 1 && (unsigned)(st - s0 - HPF0) < 8u) prefetch_l2(p.ssm_k + (size_t)(chb * 8 + st - s0 - HPF0) * SEQ + lane * 64);
          asm volatile("cp.async.commit_group;\n" ::: "memory");
          asm volatile("cp.async.wait_group 2;\n" ::: "memory");
          __syncwarp();
#pragma unroll
          for (int h = 0; h < 2; h++) {
            uint32_t e[6], vv[4], e4[4];
            ldsm4t(e4, kring + ((st & 3) << 10) + (la ^ (h << 4)));
            ldsm2t(e[0], e[1], kring + (((st - backb) & 3) << 10) + (lb ^ (h << 4)));
            ldsm4t(vv, vring + ((st & 3) << 10) + (la ^ (h << 4)));
            e[2] = e4[0]; e[3] = e4[1]; e[4] = e4[2]; e[5] = e4[3];
            uint32_t o[5];
#pragma unroll
            for (int i = 0; i < 5; i++) o[i] = __byte_perm(e[i], e[i + 1], 0x5432);
#pragma unroll
            for (int i = 0; i < 4; i++) {
              uint32_t a = bmul2(o[i], w[h][3]);
              a = bfma2(e[i + 1], w[h][2], a);
              a = bfma2(o[i + 1], w[h][1], a);
              a = bfma2(e[i + 2], w[h][0], a);
              vv[i] = bmul2(a, vv[i]);
            }
            st_async128(ud[h] + (st ^ (g & 1)) * 64, ub[h], vv[0], vv[1], vv[2], vv[3]);
          }
          __syncwarp();
        }
        fence_async_smem();
        PROF(16);
      }
      nb_sync(NB_HELP3, 96);
      if (hw == 1 && elect_one()) {
        mbar_expect_tx(bars + 8 * BAR_H, 8 * 4096);
#pragma unroll 1
        for (int c = 0; c < 8; c++)
          bulk_load(sb + OFF_X + c * XT + 4096, p.ssm_k + (size_t)(chb * 8 + c) * SEQ, 4096, bars + 8 * BAR_H);
        mbar_expect_tx(bars + 8 * BAR_X, 6144);
        bulk_load(sb + OFF_T16, g_tab, 2048, bars + 8 * BAR_X);
        bulk_load(sb + OFF_T32, g_tab + 512, 4096, bars + 8 * BAR_X);
      }
      __syncwarp();
      {
        const int ck = 16 * (lane >> 4) + 2 * lr + (((lane >> 3) ^ (lane >> 2)) & 1);
        const uint32_t xo = (ck >> 1) * 128, xs = ((ck & 1) ^ lr) << 4;
#pragma unroll 1
        for (int job = hw - 1; job < 16; job += 3) {
          const int c = job & 7;
          uint4 a[8];
          float dv = __shfl_sync(0xffffffffu, dall, c);
          if (job < 8 || lane) dv = 0.f;
          if (job >= PF0 && job < PF1) prefetch_l2((job < 8 ? p.q + (size_t)chb * 16384 : p.wo + (size_t)chb * 8192) + c * 2048 + lane * 64);
          const uint32_t xt = sb + OFF_X + c * XT + (job >> 3) * 4096;
          mbar_wait(bars + 8 * (job < 8 ? BAR_U : BAR_H), 0);
#pragma unroll
          for (int i = 0; i < 8; i++) a[i] = lds128(xt + i * 512 + ((ck ^ (job < 8 ? (c & 1) << 2 : 0)) << 4));
          dv += bf_lo(a[0].x);
          uint32_t m[4] = {bmaxabs2(a[0].x, pack_bf16(dv, 0.f)), a[0].y, a[0].z, a[0].w};
#pragma unroll
          for (int i = 1; i < 8; i++) {
            m[0] = bmaxabs2(m[0], a[i].x); m[1] = bmaxabs2(m[1], a[i].y);
            m[2] = bmaxabs2(m[2], a[i].z); m[3] = bmaxabs2(m[3], a[i].w);
          }
          m[0] = bmaxabs2(bmaxabs2(m[0], m[1]), bmaxabs2(m[2], m[3]));
          const int f = max(252 - (int)(__reduce_max_sync(0xffffffffu, max(m[0] & 0x7fffu, (m[0] >> 16) & 0x7fffu)) >> 7), 1);
          if (lane == 0) asm volatile("st.shared.u32 [%0], %1;\n" ::"r"(sb + OFF_EX + job * 4), "r"(f) : "memory");
          if (f < 113) {
#pragma unroll
            for (int i = 0; i < 8; i++)
              a[i] = make_uint4(bmul2(a[i].x, f * 0x00800080u), bmul2(a[i].y, f * 0x00800080u), bmul2(a[i].z, f * 0x00800080u),
                                bmul2(a[i].w, f * 0x00800080u));
          }
          const uint32_t mul = (f < 113 ? 15 : f - 112) * 0x00800080u;
          auto cv = [&](uint32_t x) {
            x = bmul2(x, mul);
            return (x & 0x0fff0fffu) * 7 + x;
          };
          const uint32_t dst = xt + xo;
#pragma unroll
          for (int i = 0; i < 8; i++)
            sts128(dst + (i & 1) * 2048 + (xs ^ ((i >> 1) << 5)),
                   i ? cv(a[i].x) : __byte_perm(pack_f16(dv * __uint_as_float(f << 23), 0.f), cv(a[i].x), 0x7610), cv(a[i].y),
                   cv(a[i].z), cv(a[i].w));
        }
        fence_async_smem();
        __syncwarp();
        if (lane == 0) mbar_arrive(bars + 8 * BAR_X);
        PROF(19);
      }
      if (hw < 3) {
        const uint32_t peer = mapa(sb, rank ^ 1);
#pragma unroll 1
        for (int n = 0; n < SPIN_LIMIT && !mbar_try(bars + 8 * (BAR_Y + hw * 4 - 4), 0); n++) __nanosleep(200);
#pragma unroll 1
        for (int ch = hw * 4 - 4; ch < hw * 4; ch++) {
          const uint32_t o = OFF_X + ch * XT + (rank ^ 1) * 4096;
          uint4 a[4];
          mbar_wait(bars + 8 * (BAR_Y + ch), 0);
#pragma unroll
          for (int i = 0; i < 4; i++) a[i] = lds128(sb + o + (i >> 1) * 2048 + (i & 1) * 512 + lane * 16);
#pragma unroll
          for (int i = 0; i < 4; i++)
            st_async128(peer + o + 1024 + (i >> 1) * 2048 + (i & 1) * 512 + lane * 16, peer + OFF_BAR + 8 * BAR_LAND, a[i].x,
                        a[i].y, a[i].z, a[i].w);
        }
      }
      PROF(32);
      }
      if (MODE != 1 && hw == 3) {
        const uint32_t epoch = ld_relaxed(g_flag_o + cta) + 1;
        if (MODE == 0) nb_sync(NB_G1END, 288);
        if (BDEL) __nanosleep(BDEL);
        if (elect_one()) {
#pragma unroll
          for (int kb = 0; kb < 3; kb++) g2_issue_b(kb, kb);
        }
        __syncwarp();
        const __nv_bfloat16* osrc = g_o + (size_t)(rb2 >> 1) * 16 * 16384 + hsel * 8192;
        if (MODE == 0) __nanosleep(POLL0);
        const uint32_t* flag = g_flag_o + (rb2 >> 1) * 16 + g2_k(lane & 15);
        uint32_t ready = MODE == 0 ? 0u : ~0u;
#pragma unroll 1
        for (int kb = 2; kb < 16; kb++) {
          const int s = g2_stage(kb);
          if (!(ready >> kb & 1)) {
#pragma unroll 1
            for (int n = 0; n < SPIN_LIMIT && !(ready >> kb & 1); n++)
              ready = __ballot_sync(0xffffffffu, ld_acquire(flag) == epoch);
            fence_async_all();
          }
          if (kb == 2) PROF(21);
          mbar_wait(bars + 8 * (BAR_EMPTY2 + s), (G2_PARITY >> kb) & 1);
          if (MODE == 0 && kb == 4 && rank == 1) mbar_wait(bars + 8 * BAR_TAB, 0);
          if (elect_one()) {
            asm volatile(
                "cp.async.bulk.shared::cluster.global.mbarrier::complete_tx::bytes.multicast::cluster [%0], [%1], %2, [%3], %4;\n"
                ::"r"(sb + g2_a(s, hsel) + rank * 8192), "l"(osrc + rank * 4096 + (uint32_t)g2_k(kb) * 16384), "r"(8192),
                "r"(bars + 8 * (BAR_FULL2 + s)), "h"((uint16_t)3) : "memory");
          }
          __syncwarp();
        }
      }
    }
    cluster_sync_all();
    PROF_DUMP();
  } else {
    asm volatile("setmaxnreg.inc.sync.aligned.u32 %0;\n" :: "n"(REG_MATH));
    if (warp == 0) PROF2(26);
    const int wg = warp >> 2;
    const int wtid = tid & 127;
    const bool signaller = (wtid == 0) || (wtid == 32);
    const uint32_t rbars = mapa(bars, wtid >> 5 & 1);

    if (halo_cta) {
      const uint32_t epoch = ld_relaxed(g_flag_h + blockIdx.x) + 1;
      float acc0[64], acc1[64];
      int s = 0, ph = 0;
#pragma unroll 1
      for (int kb = 0; kb < 16; kb++) {
        mbar_wait(bars + 8 * (BAR_FULLB + s), ph);
        const uint32_t st = sb + s * STGH;
        const uint64_t da = mkdesc(st, 16, 1024, 1);
        const uint64_t db = mkdesc(st + 8192 + wg * 32768, 8192, 1024, 1);
        wg_fence();
#pragma unroll
        for (int kk = 0; kk < 4; kk++) {
          wgmma_n128(acc0, da + 2 * kk, db + 128 * kk, kb + kk);
          wgmma_n128(acc1, da + 2 * kk, db + 1024 + 128 * kk, kb + kk);
        }
        wg_commit();
        wg_wait<0>();
        if (kb == 15) PROF(37);
        if (wtid == 0) mbar_arrive(bars + 8 * (BAR_EMPTYB + s));
        if (++s == 3) { s = 0; ph ^= 1; }
      }
      fence_regs(acc0);
      fence_regs(acc1);
      if ((warp & 3) != 3) {
#pragma unroll
        for (int hh = 0; hh < 2; hh++) {
          uint4* dst = g_halo + ((hh * 4 + (warp & 3) + 1) * 16 + blockIdx.x * 4) * 128 + wg * 64 + lane;
#pragma unroll
          for (int j = 0; j < 4; j++) {
            const int o = 16 * j + 2 * hh;
            dst[(j >> 1) * 128 + (j & 1) * 32] =
                make_uint4(pack_bf16(acc0[o], acc0[o + 1]), pack_bf16(acc0[o + 4], acc0[o + 5]),
                           pack_bf16(acc0[o + 8], acc0[o + 9]), pack_bf16(acc0[o + 12], acc0[o + 13]));
            dst[(2 + (j >> 1)) * 128 + (j & 1) * 32] =
                make_uint4(pack_bf16(acc1[o], acc1[o + 1]), pack_bf16(acc1[o + 4], acc1[o + 5]),
                           pack_bf16(acc1[o + 8], acc1[o + 9]), pack_bf16(acc1[o + 12], acc1[o + 13]));
          }
        }
      }
      nb_sync(NB_G1DONE, 256);
      if (tid == 0) st_release(g_flag_h + blockIdx.x, epoch);
      PROF(36);
      cluster_sync_all();
      return;
    }

    if (MODE != 2) {
    uint32_t a1[2][4], sc[4];
    C2 t[2];
    {
      float acc0[96], acc1[96];
      int sa = 0, pha = 0, sbb = 0, phb = 0;
      asm volatile("cp.async.wait_group 0;\n" ::: "memory");
      fence_async_smem();
      nb_sync(NB_FIRST, 256);
      if (tid == 0) {
        mbar_arrive(bars + 8 * BAR_FULLA);
        mbar_arrive(bars + 8 * BAR_FULLB);
      }
      PROF(0 + wg);
#pragma unroll 1
      for (int kb = 0; kb < 30; kb++) {
        if (!(kb & 1)) mbar_wait(bars + 8 * (BAR_FULLA + sa), pha);
        mbar_wait(bars + 8 * (BAR_FULLB + sbb), phb);
        if (kb == 0) PROF2(0 + wg);
        if (kb == 4 && wg == 0) PROF2(28);
        if (kb == 8 && wg == 0) PROF2(29);
        if (kb == 16 && wg == 0) PROF2(30);
        const uint64_t da = mkdesc(sb + sa * STG1A + wg * 16384 + (kb & 1) * 64, 16, 2048, 1);
        const uint64_t db = mkdesc(sb + OFF_1B + sbb * STG1B, 4096, 1024, 1);
        wg_fence();
        wgmma_n192(acc0, da + 64, db, kb);
        wgmma_n192(acc1, da, db, kb);
        wgmma_n192(acc0, da + 66, db + 128, 1);
        wgmma_n192(acc1, da + 2, db + 128, 1);
        wg_commit();
        wg_wait<1>();
        if (kb > 0) {
          if (wtid == 64) mbar_arrive(bars + 8 * (BAR_EMPTYB + (sbb == 0 ? NS1B - 1 : sbb - 1)));
          if (!(kb & 1) && signaller) mbar_arrive_cluster(rbars + 8 * (BAR_EMPTYA + (sa == 0 ? NS1A - 1 : sa - 1)));
        }
        if (++sbb == NS1B) { sbb = 0; phb ^= 1; }
        if ((kb & 1) && ++sa == NS1A) { sa = 0; pha ^= 1; }
      }
      const int lr = lane & 7, lm = lane >> 3;
      const bool le0 = 2 * (lane & 3) <= (lane >> 2), le1 = 2 * (lane & 3) + 1 <= (lane >> 2);
      const uint32_t maskLE = (le0 ? 0x0000FFFFu : 0u) | (le1 ? 0xFFFF0000u : 0u);
      uint32_t q[4][8], k[5][8], vt[5][8];
      {
        static_assert(15 % NS1A == 0 && 30 % NS1B == 0, "slots of the last k blocks");
        asm volatile("ld.global.nc.v4.u32 {%0,%1,%2,%3}, [%4];\n"
                     : "=r"(t[0].r), "=r"(t[1].r), "=r"(t[0].i), "=r"(t[1].i) : "l"(g_tab + 1536 + wtid * 4));
        mbar_wait(bars + 8 * BAR_FULLA, 1);
        mbar_wait(bars + 8 * BAR_FULLB, 0);
        mbar_wait(bars + 8 * (BAR_FULLB + 1), 0);
        mbar_wait(bars + 8 * (BAR_EMPTYA + 1), 0);
        const uint64_t da = mkdesc(sb + wg * 16384, 16, 2048, 1);
        const uint64_t db = mkdesc(sb + OFF_1B, 4096, 1024, 1);
        wg_fence();
#pragma unroll
        for (int i = 0; i < 4; i++) wgmma_n192(acc0, da + 64 + 2 * i, db + (i >> 1) * (STG1B >> 4) + (i & 1) * 128, 1);
        wg_commit();
#pragma unroll
        for (int i = 0; i < 2; i++) wgmma_n192(acc1, da + 2 * i, db + (i >> 1) * (STG1B >> 4) + (i & 1) * 128, 1);
        wg_commit();
        wg_wait<1>();
        fence_regs(acc0);
        PROFA(45, 0);
        attn_pack<8, 1, false>(acc0, k[4]);
        attn_pack<16, 1, true>(acc0, vt[4]);
        const uint32_t kh = sb + (warp == 7 ? OFF_OP + 7 * 4096 : OFF_KH + (warp + 1) * 2048) + lane * 16;
        sts128(kh, k[4][0], k[4][1], k[4][2], k[4][3]);
        sts128(kh + 512, k[4][4], k[4][5], k[4][6], k[4][7]);
#pragma unroll
        for (int i = 0; i < 4; i++) sts64(kh - lane * 8 + 1024 + 256 * i, vt[4][2 * i], vt[4][2 * i + 1]);
#pragma unroll
        for (int i = 2; i < 4; i++) wgmma_n192(acc1, da + 2 * i, db + (i >> 1) * (STG1B >> 4) + (i & 1) * 128, 1);
        wg_commit();
        attn_pack<0, 0, false>(acc0, q[1]);
        attn_pack<0, 1, false>(acc0, q[3]);
        attn_pack<8, 0, false>(acc0, k[2]);
        attn_pack<16, 0, true>(acc0, vt[2]);
        uint32_t z = p.zero;
#pragma unroll
        for (int i = 0; i < 8; i++) z &= q[1][i] & q[3][i];
#pragma unroll
        for (int i = 0; i < 8; i += 2) z &= k[2][i] & k[2][i + 1];
        __syncwarp();
        if (lane == 0) mbar_arrive(bars + 8 * BAR_STG + z);
        wg_wait<0>();
        fence_regs(acc1);
        if (MODE == 0) nb_arrive(NB_G1END, 288);
      }
      PROF(2 + wg);
      mbar_wait(bars + 8 * (warp == 0 ? BAR_HALO : BAR_STG), 0);
      {
        const uint32_t kh = sb + OFF_KH + warp * 2048 + lane * 16;
#pragma unroll
        for (int i = 0; i < 2; i++) {
          const uint4 t = lds128(kh + 512 * i);
          k[0][4 * i] = t.x; k[0][4 * i + 1] = t.y; k[0][4 * i + 2] = t.z; k[0][4 * i + 3] = t.w;
        }
#pragma unroll
        for (int i = 0; i < 4; i++) {
          const uint2 t = lds64(kh - lane * 8 + 1024 + 256 * i);
          vt[0][2 * i] = t.x; vt[0][2 * i + 1] = t.y;
        }
      }
      attn_pack<0, 0, false>(acc1, q[0]);
      attn_pack<0, 1, false>(acc1, q[2]);
      attn_pack<8, 0, false>(acc1, k[1]);
      attn_pack<8, 1, false>(acc1, k[3]);
      {
        float x[8][2];
        uint32_t pp[8];
        const bool first = warp == 0 && gidx == 0;
#pragma unroll
        for (int hd = 0; hd < 2; hd++) {
#pragma unroll
          for (int j = 0; j < 4; j += 2) {
            float s0[4], s1[4], s2[4];
            attn_qk(s2, q[j], q[j + 1], k[j + 2], 4 * hd);
            attn_qk(s1, q[j], q[j + 1], k[j + 1], 4 * hd);
            attn_qk(s0, q[j], q[j + 1], k[j], 4 * hd);
            if (j == 0 && first) s0[0] = s0[1] = -1e9f / 0.17677669529663687f;
            x[2 * j + hd][0] = le0 ? s1[0] : s0[0];
            x[2 * j + hd][1] = le1 ? s1[1] : s0[1];
            x[2 * j + 2 + hd][0] = le0 ? s2[2] : s1[2];
            x[2 * j + 2 + hd][1] = le1 ? s2[3] : s1[3];
          }
        }
        PROFA(40, __float_as_uint(x[1][0] + x[7][1]));
        attn_pack<16, 0, true>(acc1, vt[1]);
        attn_pack<16, 1, true>(acc1, vt[3]);
        quad_softmax<8>(x, pp);
        PROFA(41, pp[1] + pp[7]);
        mbar_wait(bars + 8 * BAR_X, 0);
        ldsm4(a1[0], sb + OFF_T32 + (warp & 3) * 1024 + lane * 16);
        ldsm4(a1[1], sb + OFF_T32 + 512 + (warp & 3) * 1024 + lane * 16);
        {
          const uint4 fh = lds128(sb + OFF_EX + wg * 16), fu = lds128(sb + OFF_EX + 32 + wg * 16);
          auto pw2 = [](uint32_t a, uint32_t b) { return min(max(381 - (int)a - (int)b, 1), 254) * 0x00800080u; };
          sc[0] = pw2(fh.x, fu.x); sc[1] = pw2(fh.y, fu.y); sc[2] = pw2(fh.z, fu.z); sc[3] = pw2(fh.w, fu.w);
        }
        const uint32_t obase = sb + OFF_OP + (warp * 32 + lr) * 128;
#pragma unroll
        for (int n = 0; n < 8; n++) {
          attn_pv(obase + (n >> 1) * 1024 + (((4 * (n & 1) + lm) ^ lr) << 4), vt[n >> 1], vt[(n >> 1) + 1], 4 * (n & 1), pp[n],
                  maskLE);
        }
      }
      PROFA(42, 0);
    }

    {
      const int w = warp & 3;
      const int lr = lane & 7, lm = lane >> 3;
      const uint32_t xb = sb + OFF_X + wg * 4 * XT;
      const uint64_t dc2 = mkdesc(sb + OFF_T16, 512, 128, 0), dc3 = mkdesc(sb + OFF_T16, 128, 512, 0);
      const uint64_t dc4 = mkdesc(sb + OFF_T32, 128, 256, 0);
      const uint64_t dx = mkdesc(xb, 4096, 1024, 1), dz = mkdesc(xb, 2048, 256, 3);
      const uint32_t zs = xb + (w * 16 + (lm & 1) * 8 + lr) * 32 + (((lm >> 1) ^ (lr >> 2)) << 4);
      const uint32_t ys = xb + w * 2048 + (lm >> 1) * 256;
      const uint32_t yx = (lr * 32 + (((lm & 1) ^ (lr >> 2)) << 4)) ^ (rank << 6);
      const bool own = (w >> 1) == rank;
      const uint32_t ybar = mapa(bars, own ? rank ^ 1 : rank) + 8 * (BAR_Y + wg * 4);
      uint32_t d[2][32], pa[2][4][2][4], e[2][4][8], ya[2][2][2][4], v[2][2][8];
      float o[2][16];
      auto rows = [&](int c) {
        fft_rows(d[c & 1], a1, dx + (XT >> 4) * c);
        wg_commit();
      };
      auto cols = [&](int c) {
        const int s = c & 1;
        fence_regs(d[s]);
#pragma unroll
        for (int i = 0; i < 16; i++) {
          const C2 z = crot(C2{d[s][2 * i], d[s][2 * i + 1]}, t[i & 1]);
          pa[s][i >> 2][i & 1][(i >> 1) & 1] = z.r;
          pa[s][i >> 2][i & 1][2 + ((i >> 1) & 1)] = z.i;
        }
        wg_fence();
#pragma unroll
        for (int i = 0; i < 4; i++) fft_cols<0>(e[s][i], pa[s][i], dc2);
        wg_commit();
      };
      auto prod = [&](int c) {
        const int s = c & 1;
#pragma unroll
        for (int i = 0; i < 4; i++) fence_regs(e[s][i]);
#pragma unroll
        for (int j = 0; j < 2; j++) {
          const C2 u0 = cget(e[s][0], j, 0), u1 = cget(e[s][0], j, 1), u2 = cget(e[s][1], j, 0), u3 = cget(e[s][1], j, 1);
          const C2 h0 = cget(e[s][2], j, 0), h1 = cget(e[s][2], j, 1), h2 = cget(e[s][3], j, 0), h3 = cget(e[s][3], j, 1);
          const C2 s0 = cmul(h0, u0), s1 = cfma(h0, u1, cmul(h1, u0)), s2 = cfma(h0, u2, cfma(h2, u0, cmul(h1, u1)));
          const C2 y3 = cfma(h0, u3, cfma(h1, u2, cfma(h2, u1, cfma(h3, u0, C2{s2.i, hneg2(s2.r)}))));
          ya[s][0][j][0] = s0.r;
          ya[s][0][j][1] = hadd2(s1.r, s0.i);
          ya[s][0][j][2] = s0.i;
          ya[s][0][j][3] = hadd2(s1.i, hneg2(s0.r));
          ya[s][1][j][0] = hadd2(s2.r, s1.i);
          ya[s][1][j][1] = y3.r;
          ya[s][1][j][2] = hadd2(s2.i, hneg2(s1.r));
          ya[s][1][j][3] = y3.i;
        }
        wg_fence();
        fft_cols<1>(v[s][0], ya[s][0], dc3);
        fft_cols<1>(v[s][1], ya[s][1], dc3);
        wg_commit();
      };
      auto stage = [&](int c) {
        const int s = c & 1;
        fence_regs(v[s][0]);
        fence_regs(v[s][1]);
#pragma unroll
        for (int b = 0; b < 4; b++) {
          const C2 x0 = cget(v[s][b >> 1], 0, b & 1), x1 = cget(v[s][b >> 1], 1, b & 1);
          const C2 z0 = crot(C2{x0.i, x0.r}, t[0]), z1 = crot(C2{x1.i, x1.r}, t[1]);
          stsm4(zs + c * XT + b * 2048, z0.i, z0.r, z1.i, z1.r);
        }
      };
      auto back = [&](int c) {
        fft_back(o[c & 1], dz + (XT >> 4) * c, dc4);
        wg_commit();
      };
      auto out = [&](int c) {
        float (&r)[16] = o[c & 1];
        fence_regs(r);
#pragma unroll
        for (int i = 0; i < 16; i += 8)
          stsm4t(ys + c * XT + (yx ^ ((c & 1) << 5)) + 64 * i, bmul2(pack_bf16(r[i], r[i + 1]), sc[c]),
                 bmul2(pack_bf16(r[i + 2], r[i + 3]), sc[c]), bmul2(pack_bf16(r[i + 4], r[i + 5]), sc[c]),
                 bmul2(pack_bf16(r[i + 6], r[i + 7]), sc[c]));
        __syncwarp();
        if (lane == 0) {
          mbar_arrive_cluster(ybar + 8 * c);
          if (own) mbar_arrive(bars + 8 * BAR_LAND);
        }
      };
      uint4 q[16];
      auto get_q = [&](int h) {
        if (wg != g2wg) {
          const uint32_t qo = w * 2048 + (lane >> 3) * 128 + (lane & 2) * 32 + (lane & 4) * 8 + (lane & 1) * 16;
          if (h == 0) mbar_wait(bars + 8 * BAR_Q, 0);
#pragma unroll
          for (int i = 0; i < 8; i++) q[8 * h + i] = lds128(sb + g2_b(3 + h) + qo + (i & 3) * 512 + (i >> 2) * 8192);
        }
      };
      auto got_q = [&](int h) {
        if (wg != g2wg) {
          uint32_t z = p.zero;
#pragma unroll
          for (int i = 0; i < 8; i++) z &= q[8 * h + i].x;
          __syncwarp();
          if (lane == 0) mbar_arrive(bars + 8 * (BAR_QFREE + h) + z);
        }
      };
      wg_fence();
      rows(0);
      rows(1);
      fence_async_smem();
      nb_arrive(NB_OREADY, 288);
      PROF(34 + wg);
      wg_wait<1>();
      cols(0);
      wg_wait<1>();
      cols(1);
      rows(2);
      nb_sync(NB_CONV + wg, 128);
      wg_wait<2>();
      prod(0);
      wg_wait<1>();
      cols(2);
      rows(3);
      wg_wait<2>();
      stage(0);
      fence_async_smem();
      prod(1);
      nb_sync(NB_CONV + wg, 128);
      back(0);
      wg_wait<2>();
      cols(3);
      wg_wait<2>();
      stage(1);
      fence_async_smem();
      if (QPOS == 0) get_q(0);
      prod(2);
      nb_sync(NB_CONV + wg, 128);
      back(1);
      wg_wait<2>();
      out(0);
      wg_wait<1>();
      stage(2);
      fence_async_smem();
      if (QPOS == 0) { got_q(0); get_q(1); }
      if (QPOS == 1) get_q(0);
      if (QPOS == 2) { get_q(0); get_q(1); }
      prod(3);
      nb_sync(NB_CONV + wg, 128);
      back(2);
      wg_wait<2>();
      out(1);
      wg_wait<1>();
      stage(3);
      fence_async_smem();
      if (QPOS == 0) got_q(1);
      if (QPOS == 1) got_q(0);
      if (QPOS == 2) { got_q(0); got_q(1); }
      nb_sync(NB_CONV + wg, 128);
      wg_fence();
      back(3);
      wg_wait<1>();
      out(2);
      wg_wait<0>();
      if (lane == 0) mbar_arrive_cluster(mapa(bars, 1) + 8 * BAR_TAB);
      out(3);
      PROF(6 + wg);
      if (wg != g2wg) {
        const int frow = w * 64 + (lane & 2) * 4 + (lane >> 2);
        const int c8 = 2 * lm + (lr & 1), src = (lr >> 1) & 1;
        const uint32_t fa = sb + OFF_X + c8 * XT + rank * 4096 + (src == rank ? 0 : 1024) + w * 128;
        const uint32_t fx = ((lr >> 2) ^ ((lr & 3) << 1) ^ (w & 1)) << 4;
        if (QPOS == 1) { get_q(1); got_q(1); }
        uint4* og = reinterpret_cast<uint4*>(p.out + (size_t)(rank * 1024 + frow) * (2 * DM) + (chb & ~1) * 8 + (lane & 1) * 8);
        mbar_wait(bars + 8 * BAR_LAND, 0);
        PROF2(33);
#pragma unroll
        for (int i = 0; i < 16; i++) {
          uint32_t y[4];
          ldsm4t(y, fa + (i >> 3) * 2048 + ((i >> 2) & 1) * 512 + (fx ^ ((i & 3) << 5)));
          q[i] = make_uint4(bmul2(q[i].x, y[0]), bmul2(q[i].y, y[1]), bmul2(q[i].z, y[2]), bmul2(q[i].w, y[3]));
          if (i % 6 == 0) og[(i / 6) * 16 * (2 * DM / 8)] = q[i / 6];
        }
        {
          uint32_t z = p.zero;
#pragma unroll
          for (int i = 0; i < 16; i++) z &= q[i].x;
          __syncwarp();
          if (lane < 4) mbar_arrive_cluster(mapa(bars, lane & 1) + 8 * (BAR_EMPTY2 + 5 + (lane >> 1)) + z);
        }
        PROF2(20);
#pragma unroll
        for (int i = 3; i < 16; i++) {
#pragma unroll
          for (int n = 0; n < PACE0; n++) __nanosleep(PACE);
          og[((i >> 2) * 256 + (i & 3) * 16) * (2 * DM / 8)] = q[i];
        }
        PROF(22);
      }
    }
    }

    if (MODE != 1 && wg == g2wg) {
      float acc0[64], acc1[64];
      int sprev = 0;
      mbar_wait(bars + 8 * BAR_EMPTY2, 0);
#pragma unroll 1
      for (int kb = 0; kb < 16 - ENDG; kb++) {
        const int s = (int)(G2_STAGE >> (4 * kb)) & 7;
        mbar_wait(bars + 8 * (BAR_FULL2 + s), (G2_PARITY >> kb) & 1);
        if (kb == 0) PROF(8);
        if ((warp & 3) == 0) PROF2(40 + kb);
        const uint64_t da = mkdesc(sb + g2_a(s, hsel), 16, 1024, 1);
        const uint64_t db = mkdesc(sb + g2_b(s), 8192, 1024, 1);
        wg_fence();
        wgmma_n128(acc0, da, db, kb);
        wgmma_n128(acc1, da + 512, db, kb);
        wgmma_n128(acc0, da + 2, db + 128, 1);
        wgmma_n128(acc1, da + 514, db + 128, 1);
        wg_commit();
        wg_wait<1>();
        if (((G2_REUSE << 1 >> kb) & 1) && signaller) mbar_arrive_cluster(rbars + 8 * (BAR_EMPTY2 + sprev));
        wgmma_n128(acc0, da + 4, db + 256, 1);
        wgmma_n128(acc1, da + 516, db + 256, 1);
        wgmma_n128(acc0, da + 6, db + 384, 1);
        wgmma_n128(acc1, da + 518, db + 384, 1);
        wg_commit();
        sprev = s;
      }
#pragma unroll
      for (int kb = 16 - ENDG; kb < 16; kb++) {
        mbar_wait(bars + 8 * (BAR_FULL2 + g2_stage(kb)), (G2_PARITY >> kb) & 1);
        if ((warp & 3) == 0) PROF2(40 + kb);
        const uint64_t da = mkdesc(sb + g2_a(g2_stage(kb), hsel), 16, 1024, 1);
        const uint64_t db = mkdesc(sb + g2_b(g2_stage(kb)), 8192, 1024, 1);
        wg_fence();
#pragma unroll
        for (int i = 0; i < 4; i++) wgmma_n128(acc0, da + 2 * i, db + 128 * i, 1);
        wg_commit();
        if (kb == 16 - ENDG && ((G2_REUSE >> (kb - 1)) & 1)) {
          wg_wait<1>();
          if (signaller) mbar_arrive_cluster(rbars + 8 * (BAR_EMPTY2 + sprev));
        }
      }
      static_assert((G2_REUSE >> (16 - ENDG)) == 0, "the last stages stay resident");
      auto second = [&](int i0, int i1) {
#pragma unroll
        for (int i = i0; i < i1; i++) {
          const int st = g2_stage(16 - ENDG + (i >> 2));
          wgmma_n128(acc1, mkdesc(sb + g2_a(st, hsel) + 8192, 16, 1024, 1) + 2 * (i & 3),
                     mkdesc(sb + g2_b(st), 8192, 1024, 1) + 128 * (i & 3), 1);
        }
        wg_commit();
      };
      second(0, 4);
      const int lr = lane & 7, lm = lane >> 3;
      const uint32_t wb[2] = {sb + g2_a(1, 0) + (warp & 3) * 2048, sb + g2_a(3, 0) + (warp & 3) * 2048};
      const int orow = (rb2 & 7) * 128 + (warp & 3) * 16;
      auto stage_out = [&](const float (&acc)[64], uint32_t off, int j0, int j1) {
#pragma unroll
        for (int j = j0; j < j1; j += 2) {
          const uint32_t a = wb[j >> 3] + off + (lr + 8 * (lm & 1)) * 128 + ((((j & 7) + (lm >> 1)) ^ lr) << 4);
          stsm4(a, pack_bf16(acc[4 * j], acc[4 * j + 1]), pack_bf16(acc[4 * j + 2], acc[4 * j + 3]),
                pack_bf16(acc[4 * j + 4], acc[4 * j + 5]), pack_bf16(acc[4 * j + 6], acc[4 * j + 7]));
        }
      };
      auto store_tma = [&](uint32_t off, int row) {
        fence_async_smem();
        __syncwarp();
        if (elect_one()) {
          tma_store_3d(&tmOb, wb[0] + off, DM + cb2 * 128, rb2 >> 3, row);
          tma_store_3d(&tmOb, wb[1] + off, DM + cb2 * 128 + 64, rb2 >> 3, row);
          bulk_commit();
        }
      };
      wg_wait<1>();
      fence_regs(acc0);
      PROF(10);
#pragma unroll
      for (int c = 0; c < 4; c++) {
        stage_out(acc0, 0, 4 * c, 4 * c + 4);
        second(4 + ILV * c, 4 + ILV * (c + 1));
      }
      store_tma(0, orow);
      if (4 + 4 * ILV < 4 * ENDG) second(4 + 4 * ILV, 4 * ENDG);
      PROF(12);
      wg_wait<0>();
      fence_regs(acc1);
      PROF(11);
      stage_out(acc1, 8192, 0, 16);
      __syncwarp();
      {
        const int rr = lane >> 4, ck = lane & 7, hf = (lane >> 3) & 1;
        uint4* og = reinterpret_cast<uint4*>(p.out + (size_t)(2 * (orow + 64 + rr) + (rb2 >> 3)) * (2 * DM) + DM + cb2 * 128 + hf * 64 + ck * 8);
        uint4 v[8];
#pragma unroll
        for (int i = 0; i < 8; i++) v[i] = lds128((hf ? wb[1] : wb[0]) + 8192 + (2 * i + rr) * 128 + ((ck ^ ((2 * i + rr) & 7)) << 4));
#pragma unroll
        for (int i = 0; i < 8; i++) og[(size_t)i * 4 * (2 * DM / 8)] = v[i];
      }
      PROF(13);
      bulk_wait0();
    }
    cluster_sync_all();
  }
}

typedef CUresult (*EncodeFn)(CUtensorMap*, CUtensorMapDataType, cuuint32_t, void*, const cuuint64_t*, const cuuint64_t*,
                             const cuuint32_t*, const cuuint32_t*, CUtensorMapInterleave, CUtensorMapSwizzle,
                             CUtensorMapL2promotion, CUtensorMapFloatOOBfill);

void make_map(EncodeFn enc, CUtensorMap* tm, const void* base, int rank, const cuuint64_t* dims, const cuuint64_t* strides,
              const cuuint32_t* box, CUtensorMapSwizzle swz) {
  cuuint32_t es[5] = {1, 1, 1, 1, 1};
  enc(tm, CU_TENSOR_MAP_DATA_TYPE_BFLOAT16, rank, const_cast<void*>(base), dims, strides, box, es,
      CU_TENSOR_MAP_INTERLEAVE_NONE, swz, CU_TENSOR_MAP_L2_PROMOTION_L2_256B, CU_TENSOR_MAP_FLOAT_OOB_FILL_NONE);
}

}

extern "C" void kernel_launch(void* const* d_in, const int* in_sizes, int n_in, void* d_out, int out_size) {
  static EncodeFn enc = nullptr;
  static bool coresident = true;
  if (!enc) {
    void* fn = nullptr;
    cudaDriverEntryPointQueryResult qr;
    cudaGetDriverEntryPoint("cuTensorMapEncodeTiled", &fn, cudaEnableDefault, &qr);
    enc = (EncodeFn)fn;
    cudaFuncSetAttribute(fused_kernel<0>, cudaFuncAttributeMaxDynamicSharedMemorySize, SMEM_BYTES);
    cudaFuncSetAttribute(fused_kernel<1>, cudaFuncAttributeMaxDynamicSharedMemorySize, SMEM_BYTES);
    cudaFuncSetAttribute(fused_kernel<2>, cudaFuncAttributeMaxDynamicSharedMemorySize, SMEM_BYTES);
    cudaLaunchConfig_t cfg = {};
    cfg.gridDim = dim3(NCTA);
    cfg.blockDim = dim3(NTHREADS);
    cfg.dynamicSmemBytes = SMEM_BYTES;
    cudaLaunchAttribute at;
    at.id = cudaLaunchAttributeClusterDimension;
    at.val.clusterDim.x = 2;
    at.val.clusterDim.y = 1;
    at.val.clusterDim.z = 1;
    cfg.attrs = &at;
    cfg.numAttrs = 1;
    int nclusters = 0;
    if (cudaOccupancyMaxActiveClusters(&nclusters, fused_kernel<0>, &cfg) == cudaSuccess) coresident = nclusters >= NCTA / 2;
    (void)cudaGetLastError();
  }
  CUtensorMap tmX, tmW, tmWo, tmQ, tmOb, tmXh, tmWh;
  {
    cuuint64_t dims[3] = {1024, 2, 1024};
    cuuint64_t str[2] = {2048, 4096};
    cuuint32_t box[3] = {64, 1, 128};
    make_map(enc, &tmX, d_in[6], 3, dims, str, box, CU_TENSOR_MAP_SWIZZLE_128B);
  }
  {
    cuuint64_t dims[3] = {1024, 1024, 3};
    cuuint64_t str[2] = {6144, 2048};
    cuuint32_t box[3] = {64, 32, 3};
    make_map(enc, &tmW, d_in[7], 3, dims, str, box, CU_TENSOR_MAP_SWIZZLE_128B);
  }
  {
    cuuint64_t dims[3] = {64, 1024, 16};
    cuuint64_t str[2] = {2048, 128};
    cuuint32_t box[3] = {64, 64, 2};
    make_map(enc, &tmWo, d_in[8], 3, dims, str, box, CU_TENSOR_MAP_SWIZZLE_128B);
  }
  {
    cuuint64_t dims[5] = {1024, 2, 2, 4, 128};
    cuuint64_t str[4] = {2048, 8 * 2048, 2 * 2048, 16 * 2048};
    cuuint32_t box[5] = {16, 2, 2, 4, 32};
    make_map(enc, &tmQ, d_in[0], 5, dims, str, box, CU_TENSOR_MAP_SWIZZLE_NONE);
  }
  {
    cuuint64_t dims[3] = {2048, 2, 1024};
    cuuint64_t str[2] = {4096, 8192};
    cuuint32_t box[3] = {64, 1, 16};
    make_map(enc, &tmOb, d_out, 3, dims, str, box, CU_TENSOR_MAP_SWIZZLE_128B);
  }
  {
    cuuint64_t dims[4] = {1024, 256, 2, 4};
    cuuint64_t str[3] = {4096, 2048, 256 * 4096};
    cuuint32_t box[4] = {64, 8, 2, 3};
    make_map(enc, &tmXh, d_in[6], 4, dims, str, box, CU_TENSOR_MAP_SWIZZLE_128B);
  }
  {
    cuuint64_t dims[3] = {64, 1024, 48};
    cuuint64_t str[2] = {6144, 128};
    cuuint32_t box[3] = {64, 64, 4};
    make_map(enc, &tmWh, d_in[7], 3, dims, str, box, CU_TENSOR_MAP_SWIZZLE_128B);
  }
  Params p;
  p.q = (const __nv_bfloat16*)d_in[0];
  p.k = (const __nv_bfloat16*)d_in[1];
  p.v = (const __nv_bfloat16*)d_in[2];
  p.shift_k = (const __nv_bfloat16*)d_in[3];
  p.ssm_k = (const __nv_bfloat16*)d_in[4];
  p.ssm_D = (const __nv_bfloat16*)d_in[5];
  p.x = (const __nv_bfloat16*)d_in[6];
  p.w = (const __nv_bfloat16*)d_in[7];
  p.wo = (const __nv_bfloat16*)d_in[8];
  p.out = (__nv_bfloat16*)d_out;
  p.zero = 0;
  if (coresident) {
    fused_kernel<0><<<NCTA, NTHREADS, SMEM_BYTES>>>(p, tmX, tmW, tmWo, tmQ, tmOb, tmXh, tmWh);
  } else {
    fused_kernel<0><<<4, NTHREADS, SMEM_BYTES>>>(p, tmX, tmW, tmWo, tmQ, tmOb, tmXh, tmWh);
    fused_kernel<1><<<NCTA, NTHREADS, SMEM_BYTES>>>(p, tmX, tmW, tmWo, tmQ, tmOb, tmXh, tmWh);
    fused_kernel<2><<<NCTA, NTHREADS, SMEM_BYTES>>>(p, tmX, tmW, tmWo, tmQ, tmOb, tmXh, tmWh);
  }
}
```

```cpp
#include <cuda_runtime.h>
#include <cuda.h>
#include <cuda_bf16.h>
#include <stdint.h>

namespace {

constexpr int SEQ = 2048;
constexpr int DM = 1024;
constexpr int NCTA = 132;
constexpr int NTHREADS = 384;

constexpr int STG1A = 32768;
constexpr int NS1A = 3;
constexpr int STG1B = 12288;
constexpr int NS1B = 5;
constexpr int OFF_1B = NS1A * STG1A;
constexpr int STG2 = 32768;
constexpr int NS2 = 5;
#define ILV 2
#define PACE 25
#define PACE0 7
#define POLL0 1500
#define QORD 1
#define BDEL 0
#define QPOS 1
#define G2W 0
#define XPF 0
#define HPF0 3
#define PF0 8
#define PF1 12
#define PSTEP 1150
#define PACE1 16
#define PACE2 2
#define ENDG 5
__device__ __forceinline__ uint32_t g2_a(int s, int hsel) { return (((0x97524 >> (4 * s)) & 15) ^ (s & 5 ? 0 : hsel)) << 14; }
constexpr int OFF_Q0 = 3 << 14, OFF_Q1 = 8 << 14;
constexpr int STGH = 73728;
constexpr int OFF_KH = 1 * STG2;
constexpr int OFF_OP = 2 * STG2;
constexpr int OFF_T32 = 5 * STG2 - 4096;
constexpr int OFF_X = 5 * STG2;
constexpr int XT = 8192;
__device__ __forceinline__ uint32_t g2_b(int s, int rank) {
  return s < 3 ? (s == 2 ? 6 : s) << 14 : OFF_X + (s - 3) * 2 * XT + (rank ^ 1) * 4096;
}
__device__ __forceinline__ uint32_t g2_bk(int s) { return s < 3 ? 4096 : 4 * XT; }
constexpr int OFF_BAR = OFF_X + 8 * XT;
constexpr int OFF_EX = OFF_BAR + 448;
constexpr int OFF_T16 = 230400;
constexpr int SMEM_BYTES = OFF_T16 + 2048;
static_assert(OFF_1B + NS1B * STG1B <= OFF_T32 && OFF_X % 1024 == 0, "layout");
static_assert(3 * STGH <= OFF_BAR && OFF_EX + 64 <= OFF_T16 && SMEM_BYTES <= 232448, "smem");

constexpr int BAR_FULLA = 0;
constexpr int BAR_EMPTYA = 3;
constexpr int BAR_FULLB = 6;
constexpr int BAR_EMPTYB = 11;
constexpr int BAR_FULL2 = 16;
constexpr int BAR_EMPTY2 = 21;
constexpr int BAR_X = 26;
constexpr int BAR_LAND = 27;
constexpr int BAR_TAB = 28;
constexpr int BAR_U = 29;
constexpr int BAR_H = 30;
constexpr int BAR_STG = 31;
constexpr int BAR_Y = 32;
constexpr int BAR_HALO = 40;
constexpr int BAR_Q = 41;
constexpr int BAR_XFREE = 42;

constexpr int NB_G1DONE = 1;
constexpr int NB_G1END = 3;
constexpr int NB_OREADY = 4;
constexpr int NB_CONV = 5;
constexpr int NB_HELP3 = 11;
constexpr int NB_FIRST = 13;

#define REG_MATH 224
#define REG_HELP 56
constexpr int SPIN_LIMIT = 1 << 20;

__device__ __align__(1024) __nv_bfloat16 g_o[SEQ * DM];
__device__ uint32_t g_flag_o[128];
__device__ uint32_t g_flag_h[4];
__device__ uint4 g_halo[128 * 128];
__device__ __align__(128) const uint32_t g_tab[2048] = {
  0x2fd93000,0x2ea72f64,0x2c722da8,0x263e2a1f,0x2ea73000,0xa63e2a1f,0xafd9ada8,0xac72af64,0x2c723000,0xafd9aa1f,0x263eada8,0x2ea72f64,
  0x263e3000,0xac72af64,0x2ea72da8,0xafd9aa1f,0xa63e3000,0x2c72af64,0xaea72da8,0x2fd9aa1f,0xac723000,0x2fd9aa1f,0xa63eada8,0xaea72f64,
  0xaea73000,0x263e2a1f,0x2fd9ada8,0x2c72af64,0xafd93000,0xaea72f64,0xac722da8,0xa63e2a1f,0x263e0000,0x2c722a1f,0x2ea72da8,0x2fd92f64,
  0x2c720000,0x2fd92f64,0x263e2da8,0xaea7aa1f,0x2ea70000,0x263e2f64,0xafd9ada8,0x2c72aa1f,0x2fd90000,0xaea72a1f,0x2c72ada8,0xa63e2f64,
  0x2fd90000,0xaea7aa1f,0x2c722da8,0xa63eaf64,0x2ea70000,0x263eaf64,0xafd92da8,0x2c722a1f,0x2c720000,0x2fd9af64,0x263eada8,0xaea72a1f,
  0x263e0000,0x2c72aa1f,0x2ea7ada8,0x2fd9af64,0xafd93000,0xaea72f64,0xac722da8,0xa63e2a1f,0xaea73000,0x263e2a1f,0x2fd9ada8,0x2c72af64,
  0xac723000,0x2fd9aa1f,0xa63eada8,0xaea72f64,0xa63e3000,0x2c72af64,0xaea72da8,0x2fd9aa1f,0x263e3000,0xac72af64,0x2ea72da8,0xafd9aa1f,
  0x2c723000,0xafd9aa1f,0x263eada8,0x2ea72f64,0x2ea73000,0xa63e2a1f,0xafd9ada8,0xac72af64,0x2fd93000,0x2ea72f64,0x2c722da8,0x263e2a1f,
  0xa63e0000,0xac722a1f,0xaea72da8,0xafd92f64,0xac720000,0xafd92f64,0xa63e2da8,0x2ea7aa1f,0xaea70000,0xa63e2f64,0x2fd9ada8,0xac72aa1f,
  0xafd90000,0x2ea72a1f,0xac72ada8,0x263e2f64,0xafd90000,0x2ea7aa1f,0xac722da8,0x263eaf64,0xaea70000,0xa63eaf64,0x2fd92da8,0xac722a1f,
  0xac720000,0xafd9af64,0xa63eada8,0x2ea72a1f,0xa63e0000,0xac72aa1f,0xaea7ada8,0xafd9af64,0xa63e0000,0xac72aa1f,0xaea7ada8,0xafd9af64,
  0xac720000,0xafd9af64,0xa63eada8,0x2ea72a1f,0xaea70000,0xa63eaf64,0x2fd92da8,0xac722a1f,0xafd90000,0x2ea7aa1f,0xac722da8,0x263eaf64,
  0xafd90000,0x2ea72a1f,0xac72ada8,0x263e2f64,0xaea70000,0xa63e2f64,0x2fd9ada8,0xac72aa1f,0xac720000,0xafd92f64,0xa63e2da8,0x2ea7aa1f,
  0xa63e0000,0xac722a1f,0xaea72da8,0xafd92f64,0x2fd93000,0x2ea72f64,0x2c722da8,0x263e2a1f,0x2ea73000,0xa63e2a1f,0xafd9ada8,0xac72af64,
  0x2c723000,0xafd9aa1f,0x263eada8,0x2ea72f64,0x263e3000,0xac72af64,0x2ea72da8,0xafd9aa1f,0xa63e3000,0x2c72af64,0xaea72da8,0x2fd9aa1f,
  0xac723000,0x2fd9aa1f,0xa63eada8,0xaea72f64,0xaea73000,0x263e2a1f,0x2fd9ada8,0x2c72af64,0xafd93000,0xaea72f64,0xac722da8,0xa63e2a1f,
  0x263e0000,0x2c72aa1f,0x2ea7ada8,0x2fd9af64,0x2c720000,0x2fd9af64,0x263eada8,0xaea72a1f,0x2ea70000,0x263eaf64,0xafd92da8,0x2c722a1f,
  0x2fd90000,0xaea7aa1f,0x2c722da8,0xa63eaf64,0x2fd90000,0xaea72a1f,0x2c72ada8,0xa63e2f64,0x2ea70000,0x263e2f64,0xafd9ada8,0x2c72aa1f,
  0x2c720000,0x2fd92f64,0x263e2da8,0xaea7aa1f,0x263e0000,0x2c722a1f,0x2ea72da8,0x2fd92f64,0xafd93000,0xaea72f64,0xac722da8,0xa63e2a1f,
  0xaea73000,0x263e2a1f,0x2fd9ada8,0x2c72af64,0xac723000,0x2fd9aa1f,0xa63eada8,0xaea72f64,0xa63e3000,0x2c72af64,0xaea72da8,0x2fd9aa1f,
  0x263e3000,0xac72af64,0x2ea72da8,0xafd9aa1f,0x2c723000,0xafd9aa1f,0x263eada8,0x2ea72f64,0x2ea73000,0xa63e2a1f,0xafd9ada8,0xac72af64,
  0x2fd93000,0x2ea72f64,0x2c722da8,0x263e2a1f,0xa63e0000,0xac72aa1f,0xaea7ada8,0xafd9af64,0x2c720000,0x2fd92f64,0x263e2da8,0xaea7aa1f,
  0xaea70000,0xa63eaf64,0x2fd92da8,0xac722a1f,0x2fd90000,0xaea72a1f,0x2c72ada8,0xa63e2f64,0xafd90000,0x2ea72a1f,0xac72ada8,0x263e2f64,
  0x2ea70000,0x263eaf64,0xafd92da8,0x2c722a1f,0xac720000,0xafd92f64,0xa63e2da8,0x2ea7aa1f,0x263e0000,0x2c72aa1f,0x2ea7ada8,0x2fd9af64,
  0x2fd93000,0x2ea72f64,0x2c722da8,0x263e2a1f,0xaea7b000,0x263eaa1f,0x2fd92da8,0x2c722f64,0x2c723000,0xafd9aa1f,0x263eada8,0x2ea72f64,
  0xa63eb000,0x2c722f64,0xaea7ada8,0x2fd92a1f,0xa63e3000,0x2c72af64,0xaea72da8,0x2fd9aa1f,0x2c72b000,0xafd92a1f,0x263e2da8,0x2ea7af64,
  0xaea73000,0x263e2a1f,0x2fd9ada8,0x2c72af64,0x2fd9b000,0x2ea7af64,0x2c72ada8,0x263eaa1f,0x263e0000,0x2c72aa1f,0x2ea7ada8,0x2fd9af64,
  0xac720000,0xafd92f64,0xa63e2da8,0x2ea7aa1f,0x2ea70000,0x263eaf64,0xafd92da8,0x2c722a1f,0xafd90000,0x2ea72a1f,0xac72ada8,0x263e2f64,
  0x2fd90000,0xaea72a1f,0x2c72ada8,0xa63e2f64,0xaea70000,0xa63eaf64,0x2fd92da8,0xac722a1f,0x2c720000,0x2fd92f64,0x263e2da8,0xaea7aa1f,
  0xa63e0000,0xac72aa1f,0xaea7ada8,0xafd9af64,0xafd93000,0xaea72f64,0xac722da8,0xa63e2a1f,0x2ea7b000,0xa63eaa1f,0xafd92da8,0xac722f64,
  0xac723000,0x2fd9aa1f,0xa63eada8,0xaea72f64,0x263eb000,0xac722f64,0x2ea7ada8,0xafd92a1f,0x263e3000,0xac72af64,0x2ea72da8,0xafd9aa1f,
  0xac72b000,0x2fd92a1f,0xa63e2da8,0xaea7af64,0x2ea73000,0xa63e2a1f,0xafd9ada8,0xac72af64,0xafd9b000,0xaea7af64,0xac72ada8,0xa63eaa1f,
  0xafd9b000,0xaea7af64,0xac72ada8,0xa63eaa1f,0x2ea73000,0xa63e2a1f,0xafd9ada8,0xac72af64,0xac72b000,0x2fd92a1f,0xa63e2da8,0xaea7af64,
  0x263e3000,0xac72af64,0x2ea72da8,0xafd9aa1f,0x263eb000,0xac722f64,0x2ea7ada8,0xafd92a1f,0xac723000,0x2fd9aa1f,0xa63eada8,0xaea72f64,
  0x2ea7b000,0xa63eaa1f,0xafd92da8,0xac722f64,0xafd93000,0xaea72f64,0xac722da8,0xa63e2a1f,0xa63e0000,0xac72aa1f,0xaea7ada8,0xafd9af64,
  0x2c720000,0x2fd92f64,0x263e2da8,0xaea7aa1f,0xaea70000,0xa63eaf64,0x2fd92da8,0xac722a1f,0x2fd90000,0xaea72a1f,0x2c72ada8,0xa63e2f64,
  0xafd90000,0x2ea72a1f,0xac72ada8,0x263e2f64,0x2ea70000,0x263eaf64,0xafd92da8,0x2c722a1f,0xac720000,0xafd92f64,0xa63e2da8,0x2ea7aa1f,
  0x263e0000,0x2c72aa1f,0x2ea7ada8,0x2fd9af64,0x2fd9b000,0x2ea7af64,0x2c72ada8,0x263eaa1f,0xaea73000,0x263e2a1f,0x2fd9ada8,0x2c72af64,
  0x2c72b000,0xafd92a1f,0x263e2da8,0x2ea7af64,0xa63e3000,0x2c72af64,0xaea72da8,0x2fd9aa1f,0xa63eb000,0x2c722f64,0xaea7ada8,0x2fd92a1f,
  0x2c723000,0xafd9aa1f,0x263eada8,0x2ea72f64,0xaea7b000,0x263eaa1f,0x2fd92da8,0x2c722f64,0x2fd93000,0x2ea72f64,0x2c722da8,0x263e2a1f,
  0x263e0000,0x2c72aa1f,0x2ea7ada8,0x2fd9af64,0xac720000,0xafd92f64,0xa63e2da8,0x2ea7aa1f,0x2ea70000,0x263eaf64,0xafd92da8,0x2c722a1f,
  0xafd90000,0x2ea72a1f,0xac72ada8,0x263e2f64,0x2fd90000,0xaea72a1f,0x2c72ada8,0xa63e2f64,0xaea70000,0xa63eaf64,0x2fd92da8,0xac722a1f,
  0x2c720000,0x2fd92f64,0x263e2da8,0xaea7aa1f,0xa63e0000,0xac72aa1f,0xaea7ada8,0xafd9af64,0x316c2fbd,0x343e32f7,0x35bc34ff,0x372c3676,
  0x371532c6,0x3a81392e,0x3bef3b71,0x3b7c3bf2,0x397034cf,0x3bfc3b6c,0x38b23b04,0xb40e31e8,0x3ae13631,0x39e73bf5,0xb6e83219,0xbbe8bb13,
  0x3bc23785,0x30be3aa9,0xbbfdb911,0x2a16b9aa,0x3bfe3865,0xb80f37a6,0xb82abc00,0x3bfd376f,0x3b9238fd,0xbb7f2311,0x3805b929,0x31223bde,
  0x3a85398b,0xbb96b742,0x3bff319e,0xbbb82f8b,0xbbe2bbf1,0xbbb7bbcf,0xbb78bb9a,0xbb27bb52,0xbb2cbbd2,0xb8a8ba19,0xb029b5df,0x35a52f59,
  0xb9dfbba1,0x2ba7b5f7,0x3a7a37b2,0x3bbd3bdd,0xb815bb60,0x39662e91,0x3b373bda,0xb0d7377a,0xb3d3bb10,0x3be9386f,0x2a7a3a31,0xbbfeb9a6,
  0x294dbab0,0x3ae53b07,0xbad51fdb,0xab43bb16,0x352fba41,0x35993c00,0xbaebba1d,0x3be531cf,0x38a3b9c5,0xb5173b21,0x2776bbe0,0x34323bf2,
  0x384537dd,0x38ea3899,0x39823937,0x3a0d39c9,0x39463a93,0x3340374e,0xb426a452,0xb979b7c8,0xbb45b924,0xbb32bc00,0xb371b902,0x38d63294,
  0xb08db9a1,0x3b3f379b,0x39583bd7,0xb8252dfb,0x3bea3a2d,0xb3ba3874,0xbb89bb0d,0x36d2b625,0xb6bb387f,0xb8d1bbf5,0x3be73602,0xb546391f,
  0xba00bb01,0x3bff35eb,0xba5c34db,0x3359bab6,0x3ac7b66b,0xb9413933,0x368dbabd,0xb0103bb3,0xbac4baf7,0xba50ba8c,0xb9cdba11,0xb93cb986,
  0x3a04388e,0x3bcb3b1e,0x3bba3c00,0x39d63afe,0x36af3a21,0xb6ffa17f,0xbbc8ba3d,0xba60bbd4,0xbbebb9af,0xb6c6bb0a,0x39f43263,0x3ad83bf7,
  0x30a6b916,0x3bc33aa5,0xb55e3790,0xbb3dbb63,0x3b423a9e,0xba642ec3,0xb0f0bb6a,0x3b8e3a25,0xb94a37bd,0x2884bb6f,0x38db3b9f,0xbbc9b85a,
  0xb840bb54,0x3a093a15,0xbb4cb850,0x3bef3457,0x3a893a4d,0x3af43ac1,0x3b4f3b24,0x3b983b76,0xbb94baba,0xbbe4bbf9,0xba58bb57,0xb699b8f8,
  0x3bfe3b18,0x394f3b5c,0xb109347b,0xbae8b884,0xbbc0bb68,0xa9b1b90c,0x3b8b387a,0x38bc3ba5,0x3ade3ba7,0xb8c1324b,0xb9f0bbf6,0x39eb9648,
  0xb96bbbd6,0x3bbf3487,0xb38939b3,0xb9f8bba3,0x370a3bf3,0xbb47b994,0x3bbc2d65,0xb8ad3889,0xb153bc00,0x37213b9c,0xb97dba90,0x3af138f3,
  0xb89eb8ee,0xb7e8b84a,0xb682b737,0xb50bb5c8,0x35233855,0xb13b2d33,0xb8e0b65f,0xbb4aba45,0xa8e8b764,0x39fc3648,0x3be63bae,0x380a3a9b,
  0xb3eb360e,0xbbfeba35,0xb552baa2,0x3a7334b7,0x381ab4ab,0x3a6f3bd8,0xb95d2e5f,0xb962bc00,0xb9e3327c,0xb402bbac,0x3bc6399d,0xb95434c3,
  0x3b2faf27,0xb6a439bc,0xb41abbf9,0x3a7e3a97,0xbbe3251b,0x3b2ab4f3,0xb9d23894,0x37f3ba49,0x3bce3bb5,0x3bf03be1,0x3bff3bfa,0x3bfb3bff,
  0x2c38b1b6,0x383a34e7,0x3aee39c0,0x3bff3bb2,0xbb81bbf8,0xb53ab999,0x38302ef5,0x3bed3ab3,0xb8cc9cb6,0xbb85bbab,0x2adeb86a,0x3bc5391b,
  0x38c73bf6,0xbadbb232,0xb6ddbba9,0x3b87361a,0x3b833201,0xb0743a39,0xba76bb5e,0x3b352dc9,0xac06bbb0,0x39743b59,0xbbeeb759,0x3aceb2ad,
  0xbbccb5d4,0x3bfb2d00,0xbb7a32de,0x3a54b7d2,0xb30fb44b,0xafefb185,0xa6adacce,0x2c9c25e4,0xbbfcbbdf,0xbacbbb9e,0xb7feb990,0xa81fb463,
  0xb58d2d97,0xbb90b9b8,0xbad1bbf4,0xb05bb85f,0x3a673c00,0xb5763493,0xbbfdbaac,0xb3a2ba29,0x3a6b2e2d,0x38203bd9,0xbb3ab49f,0xb56abb65,
  0xb581bbdc,0x3bec3907,0xb8b7363c,0xb6f4bbf8,0xbbfcb46f,0x39dab654,0xb0423b1b,0xb835bbd3,0xb3283b73,0xac6abbfa,0x35b13bd0,0xb8e5bafb,
  0x38ee3a0d,0xb84aba89,0x37373af4,0xb5c8bb4f,0x35df3a81,0x2f59bbef,0xb88e3b7c,0x3b1eb946,0x2d973ae8,0x39b8bb81,0xbbf4353a,0x385f3830,
  0xb2633b3f,0x3bf7b958,0xb60eb825,0xba353bc0,0xb7853b87,0x3aa9b3d3,0x3911bbe9,0xb9aa2a7a,0xb99d3bbf,0x34c33389,0x3bdcb9f8,0x3907bb83,
  0xbb013be5,0xb5eb394a,0x34db2884,0x3ab6b8db,0xbbd03bfb,0xbafb3b7a,0xb98b3a54,0xb74238a3,0x3a4db93c,0xbac1389e,0x3b24b7e8,0xbb763682,
  0x3b71b8a8,0xbbf23029,0x3a9335a5,0xb74eba04,0x3bf8b80a,0xb999b58d,0xaef53b90,0x3ab3bad1,0x3bd7b6c6,0xadfbb9f4,0xbb683ad8,0x390c33eb,
  0x3b10b56a,0x386fbbc2,0xba3130be,0xb9a63bfd,0x39b3b402,0x3ba3bbc6,0x3201b954,0xba393581,0x37bdb122,0x3b6fba00,0x3b9fbbff,0x385aba5c,
  0x32deac6a,0x37d2b5b1,0x39c5b8e5,0x3b21ba85,0x344b3b98,0xb185bbce,0x2cce3bf0,0x25e4bbff,0xbc003340,0x3afe3426,0xb855b979,0x2d333b94,
  0x34cfbbed,0xbb6c39df,0x3b042ba7,0xb1e8ba7a,0x3aa2a9b1,0x34b7bb8b,0xbc0038bc,0x349338cc,0xba2d3bfe,0x387430a6,0x3b0dbbc3,0xb625b55e,
  0xb63cb074,0xbbf83a76,0xb8653b35,0x37a6294d,0x3bf3bbc9,0x3994bb2f,0x2d65b6a4,0xb889341a,0xb19e3517,0x2f8b2776,0x366bb432,0x3933b840,
  0x3bb5b50b,0xbbe1330f,0x3bfaafef,0xbbff26ad,0xa4523bcb,0x37c8bbba,0xbaba39d6,0x3bf9b523,0xbba1305b,0x35f73970,0x37b2bbfc,0xbbdd38b2,
  0x387abbfe,0xbba53552,0x9cb63a73,0x3babba67,0x39162a16,0x3aa5bbea,0xb790b3ba,0xbb633b89,0xbb5e3bec,0xadc938b7,0x3ab0b6f4,0x3b07bbfe,
  0xaf27b359,0xb9bc370a,0xbbf93b47,0xba973bbc,0x3be0bb96,0x3bf2bbff,0x3b54bbb8,0x3a15bac7,0xafbd3bfb,0x32f7bbe2,0xb4ff3bb7,0x3676bb78,
  0x365fbbe4,0xba453a58,0x3bdfb699,0xbb9eac38,0xb9243bbd,0x3c00b6af,0xb902b6ff,0xb2943bc8,0x3aacbb85,0xba29aade,0xb6313bc5,0x3bf5b815,
  0xbba73b3d,0x324b381a,0x3bf6ba6f,0x9648b95d,0x3c00bae5,0x376fbad5,0xb87f2b43,0xbbf53b42,0xbbb03a7e,0xbb593bfc,0xb75939da,0x32ad3042,
  0x3abdba09,0x3bb3bb4c,0x3c00bbef,0x3b9cbbe3,0x3bf12c9c,0xbbcfb16c,0x3b9a343e,0xbb52b5bc,0xbb57b13b,0x38f838e0,0xb1b6bb4a,0xb4e73bfc,
  0x3a21340e,0x217fbb45,0xba3d3b32,0x3bd4b371,0xb86ab576,0xb91b3bfd,0x3b60b3a2,0x2e91bae1,0x34ab36d2,0x3bd8bade,0xae5fb8c1,0xbc0039f0,
  0x9fdbb80f,0xbb16382a,0xba9e3bfd,0x2ec336bb,0xb46f38ad,0x3654ac06,0x3b1bb974,0x3bd3bbee,0x3850b941,0x3457b68d,0xa51bb010,0xb4f33153,
  0xb7dd3b27,0x3899bac4,0xb9373a50,0x39c9b9cd,0x3990383a,0xb463baee,0xb2c63bff,0x392ebb2c,0x3b18ba60,0xbb5c28e8,0x347b39fc,0x3884bbe6,
  0xb219b966,0xbb133b37,0x39a130d7,0x379bbbeb,0xbbf63962,0xb2323a6b,0x3ba9b820,0x361abb3a,0xb6023a64,0x391fb0f0,0x3bd6bb8e,0x3487b9e3,
  0x3a41b835,0x3c00bb92,0x3a1dbb7f,0x31cfb805,0x3a90bb2a,0x38f3b9d2,0x35d4b7f3,0x2d00b328,0x3af7372c,0xba8cb845,0x3a1138ea,0xb986b982,
  0x39c0bacb,0xbbb237fe,0x3bd2a81f,0xba19b715,0xb764b8d6,0xb6483bfe,0x3baeb94f,0xba9bb109,0xbbda39e7,0x377a36e8,0x39afbbe8,0xbb0a308d,
  0xae2d39eb,0x3bd9b8c7,0x349fbadb,0xbb6536dd,0x3b6ab8d1,0x3a25bbe7,0xb27cb546,0xbbac396b,0x38fdbace,0xa311b52f,0xb9293599,0xbbde3aeb,
  0xb8943721,0xba49397d,0xbb733af1,0xbbfa3bcc,0xbbfb3bff,0xbbe23bf1,0xbbb73bcf,0xbb783b9a,0xbb7c3bf2,0xb9463a93,0xb340374e,0x3426a452,
  0xba603bd4,0xa8e83764,0x39fcb648,0x3be6bbae,0xb8bc3ba5,0x38cc9cb6,0x3b85bbab,0xaadeb86a,0xb56a3b65,0x3bc2b785,0x30bebaa9,0xbbfd3911,
  0xab433b16,0x3b42ba9e,0xba64aec3,0xb0f03b6a,0x33593ab6,0x370abbf3,0xbb473994,0x3bbcad65,0x37f33a49,0xb328bb73,0xac6a3bfa,0x35b1bbd0,
  0xac9c25e4,0xb16c2fbd,0xb43e32f7,0xb5bc34ff,0xb5a52f59,0xba04388e,0xbbcb3b1e,0xbbba3c00,0xb8d63294,0xbbfe3b18,0xb94f3b5c,0x3109347b,
  0xba7334b7,0xba673c00,0x35763493,0x3bfdbaac,0xbb87361a,0xb3d33b10,0x3be9b86f,0x2a7aba31,0xbbfd376f,0x36bb387f,0x38d1bbf5,0xbbe73602,
  0xbbc9385a,0x3b2f2f27,0xb6a4b9bc,0xb41a3bf9,0xbaf138f3,0x3bccb5d4,0xbbfb2d00,0x3b7a32de,0xbb273b52,0xbac43af7,0xba503a8c,0xb9cd3a11,
  0x3979b7c8,0x3b94baba,0x3be4bbf9,0x3a58bb57,0x380aba9b,0xb58dad97,0xbb9039b8,0xbad13bf4,0xbbc5391b,0xb8153b60,0x3966ae91,0x3b37bbda,
  0x2a1639aa,0x3beaba2d,0xb3bab874,0xbb893b0d,0x3b8eba25,0xb9e3b27c,0xb4023bac,0x3bc6b99d,0xb8adb889,0xac063bb0,0x3974bb59,0xbbee3759,
  0xb8e53afb,0x3a85b98b,0xbb963742,0x3bffb19e,0xb72c3676,0xb84537dd,0xb8ea3899,0xb9823937,0xb9d63afe,0xb5233855,0x313b2d33,0x38e0b65f,
  0x3ae8b884,0x3b81bbf8,0x353ab999,0xb8302ef5,0x33a2ba29,0xbae13631,0xb9e73bf5,0x36e83219,0xbbfe39a6,0x30a63916,0x3bc3baa5,0xb55eb790,
  0x3546391f,0x396bbbd6,0xbbbf3487,0x338939b3,0x3a7eba97,0xbbfc346f,0x39da3654,0xb042bb1b,0xba54b7d2,0x38a339c5,0xb517bb21,0x27763be0,
  0xb93c3986,0xb89e38ee,0xb7e8384a,0xb6823737,0x3699b8f8,0xac38b1b6,0xb83a34e7,0xbaee39c0,0xb05b385f,0x3970b4cf,0x3bfcbb6c,0x38b2bb04,
  0xb0d7b77a,0xbbeb39af,0xb6c63b0a,0x39f4b263,0x36d23625,0x3adebba7,0xb8c1b24b,0xb9f03bf6,0xb954b4c3,0xb5813bdc,0x3becb907,0xb8b7b63c,
  0x3ace32ad,0xb52fba41,0xb5993c00,0x3aebba1d,0xbbb8af8b,0x3ac7366b,0xb941b933,0x368d3abd,0xba0d39c9,0xba893a4d,0xbaf43ac1,0xbb4f3b24,
  0x3b4aba45,0x3bfcbbdf,0x3acbbb9e,0x37feb990,0xbbed3ab3,0xb9df3ba1,0x2ba735f7,0x3a7ab7b2,0x3be8bb13,0x308db9a1,0xbb3f379b,0xb9583bd7,
  0xbb3d3b63,0x381a34ab,0x3a6fbbd8,0xb95dae5f,0x39f8bba3,0xbb833201,0x30743a39,0x3a76bb5e,0xb8353bd3,0x3b92b8fd,0xbb7fa311,0x38053929,
  0x3432bbf2,0xb8403b54,0x3a09ba15,0xbb4c3850,0xb50b35c8,0xb30f344b,0xafef3185,0xa6ad2cce,0xbbff3bb2,0xbb2c3bd2,0xb8a83a19,0xb02935df,
  0xb40eb1e8,0xbb453924,0xbb323c00,0xb3713902,0x3ad8bbf7,0xb3ebb60e,0xbbfe3a35,0xb5523aa2,0x39eb1648,0x38c7bbf6,0xbadb3232,0xb6dd3ba9,
  0xb6f43bf8,0x3bfeb865,0xb80fb7a6,0xb82a3c00,0xbbe531cf,0x394a37bd,0xa884bb6f,0xb8db3b9f,0xb010bbb3,0xb1533c00,0x3721bb9c,0xb97d3a90,
  0xbb983b76,0xbbce3bb5,0xbbf03be1,0xbbff3bfa,0x281fb463,0xb71532c6,0xba81392e,0xbbef3b71,0x3bbdbbdd,0x36afba21,0xb6ff217f,0xbbc83a3d,
  0x38252dfb,0x3bc0bb68,0x29b1b90c,0xbb8b387a,0xb9623c00,0x3a6bae2d,0x3820bbd9,0xbb3a349f,0xbb352dc9,0x294d3ab0,0x3ae5bb07,0xbad59fdb,
  0x3122bbde,0xba003b01,0x3bffb5eb,0xba5cb4db,0x3befb457,0xbbe3a51b,0x3b2a34f3,0xb9d2b894,0x39c939cd,0xba4db93c,0x3ac1389e,0xbb24b7e8,
  0x3b1e3946,0xbc00b340,0x3afeb426,0xb8553979,0x3bdd38b2,0xba21340e,0xa17fbb45,0x3a3d3b32,0x3bf53815,0xb2193966,0xbb13bb37,0x39a1b0d7,
  0x3b6536dd,0x37853b87,0xbaa9b3d3,0xb911bbe9,0x3a393581,0x3b5e3bec,0x2dc938b7,0xbab0b6f4,0x3889341a,0x3bb03a7e,0x3b593bfc,0x375939da,
  0x34f33153,0x38943721,0x3a49397d,0x3b733af1,0xb9863982,0x38eeba0d,0xb84a3a89,0x3737baf4,0xb74e3a04,0xa452bbcb,0x37c83bba,0xbabab9d6,
  0xb1e83a7a,0xb924bbbd,0x3c0036af,0xb90236ff,0x2e913ae1,0xbbdab9e7,0x377ab6e8,0x39af3be8,0x361a3b3a,0xbb10b56a,0xb86fbbc2,0x3a3130be,
  0x39073b83,0xb63c3074,0xbbf8ba76,0xb865bb35,0x3a973bbc,0x346f38ad,0xb654ac06,0xbb1bb974,0x3b9c3be3,0x3a903b2a,0x38f339d2,0x35d437f3,
  0x3b763682,0xbbb5b50b,0x3be1330f,0xbbfaafef,0x2d33bb94,0x365f3be4,0xba45ba58,0x3bdf3699,0xbbd4b371,0x3764b8d6,0x36483bfe,0xbbaeb94f,
  0x379b3beb,0xbbd7b6c6,0x2dfbb9f4,0x3b683ad8,0x39aa2a7a,0x3a2d3bfe,0xb87430a6,0xbb0dbbc3,0xbb07bbfe,0x1fdbb80f,0x3b16382a,0x3a9e3bfd,
  0xb2ad3042,0xba41b835,0xbc00bb92,0xba1dbb7f,0x3bfa3bcc,0x3bd03bfb,0x3afb3b7a,0x398b3a54,0xb5c83b4f,0x344bbb98,0xb1853bce,0x2ccebbf0,
  0x3bf93523,0xbb57313b,0x38f8b8e0,0xb1b63b4a,0xb294bbc8,0x3b183a60,0xbb5ca8e8,0x347bb9fc,0xbb0ab08d,0xb263bb3f,0x3bf73958,0xb60e3825,
  0x39a63bfd,0xb9162a16,0xbaa5bbea,0x3790b3ba,0x37a6a94d,0x3c003ae5,0x376f3ad5,0xb87fab43,0xbbd3bbee,0xb8fdbace,0x2311b52f,0x39293599,
  0x2d003328,0xb2deac6a,0xb7d2b5b1,0xb9c5b8e5,0x3bff26ad,0xbbf12c9c,0x3bcfb16c,0xbb9a343e,0xbb9e2c38,0x3990b83a,0xb4633aee,0xb2c6bbff,
  0x3a9bb109,0xad973ae8,0xb9b8bb81,0x3bf4353a,0xb90c33eb,0xb87abbfe,0x3ba53552,0x1cb63a73,0x3625b55e,0x3ba73b3d,0xb24b381a,0xbbf6ba6f,
  0xaec336bb,0xbb6ab8d1,0xba25bbe7,0x327cb546,0xb1cfb805,0x37bd3122,0x3b6f3a00,0x3b9f3bff,0x374238a3,0x319e3517,0xaf8b2776,0xb66bb432,
  0x25e43bff,0xafbdbbfb,0x32f73be2,0xb4ffbbb7,0xb4e7bbfc,0x39c03acb,0xbbb2b7fe,0x3bd2281f,0x38843be6,0xbbf8b80a,0x3999b58d,0x2ef53b90,
  0xba35bbc0,0x3aa229b1,0x34b73b8b,0xbc00b8bc,0x3b633b89,0xb4ab36d2,0xbbd8bade,0x2e5fb8c1,0xbbf5bb42,0xb602ba64,0x391f30f0,0x3bd63b8e,
  0x3bde3aeb,0x3b013be5,0x35eb394a,0xb4db2884,0xbb21ba85,0xbbe0bb96,0xbbf2bbff,0xbb54bbb8,0x3b52b5bc,0xbaf7372c,0x3a8cb845,0xba1138ea,
  0x392e3b2c,0xbb71b8a8,0x3bf23029,0xba9335a5,0xb85f3830,0xb4cfbbed,0x3b6c39df,0xbb042ba7,0xbbabba67,0x386ab576,0x391b3bfd,0xbb60b3a2,
  0x1648b95d,0x3bf63962,0x32323a6b,0xbba9b820,0x3bac396b,0x399d3bbf,0xb4c33389,0xbbdcb9f8,0x385a3a5c,0xaf273359,0xb9bcb70a,0xbbf9bb47,
  0xb933b840,0xbabdba09,0xbbb3bb4c,0xbc00bbef,0x36763b78,0xb7ddbb27,0x38993ac4,0xb937ba50,0xba193715,0x35dfba81,0x2f593bef,0xb88ebb7c,
  0xbab3bad1,0x3ba1305b,0xb5f73970,0xb7b2bbfc,0x3493b8cc,0x3aac3b85,0xba292ade,0xb631bbc5,0x3c0039f0,0x2e2d39eb,0xbbd9b8c7,0xb49fbadb,
  0x348739e3,0xb9b3b402,0xbba3bbc6,0xb201b954,0xbab6b8db,0xbbf3bbc9,0xb994bb2f,0xad65b6a4,0xba15bac7,0xb850b941,0xb457b68d,0x251bb010,
  0xb9cfbb16,0x30ac2a31,0x3b9c3bf1,0xb493ae2d,0xb76fb8b4,0x35a133e3,0x3a1d3afe,0xb902b76f,0xb3e3b5a1,0x38b4376f,0x376f3902,0xbafeba1d,
  0xaa31b0ac,0x3b1639cf,0x2e2d3493,0xbbf1bb9c,0xb956ba74,0x305f29cc,0x3b633bd2,0xb44badc9,0xb6e7b859,0x353f335e,0x39d23ab6,0xb8bcb6ff,
  0xb35eb53f,0x385936e7,0x36ff38bc,0xbab6b9d2,0xa9ccb05f,0x3a743956,0x2dc9344b,0xbbd2bb63,0xb8e3b9de,0x30122967,0x3b1e3ba1,0xb402ad65,
  0xb662b801,0x34de32da,0x39823a67,0xb874b68d,0xb2dab4de,0x38013662,0x368d3874,0xba67b982,0xa967b012,0x39de38e3,0x2d653402,0xbba1bb1e,
  0xb876b952,0x2f8c2902,0x3ace3b60,0xb371ad00,0xb5e1b758,0x347e3257,0x392e3a11,0xb82ab61a,0xb257b47e,0x375835e1,0x361a382a,0xba11b92e,
  0xa902af8c,0x39523876,0x2d003371,0xbb60bace,0xb80db8ce,0x2ef3289e,0x3a733b10,0xb2deac9c,0xb562b6b3,0x342031d5,0x38d639b3,0xb7bdb5a5,
  0xb1d5b420,0x36b33562,0x35a537bd,0xb9b3b8d6,0xa89eaef3,0x38ce380d,0x2c9c32de,0xbb10ba73,0xb750b851,0x2e5a2839,0x3a0d3ab0,0xb24bac38,
  0xb4e5b613,0x33863153,0x387a394f,0xb721b52f,0xb153b386,0x361334e5,0x352f3721,0xb94fb87a,0xa839ae5a,0x38513750,0x2c38324b,0xbab0ba0d,
  0xb68eb7b4,0x2dc227a9,0x399d3a41,0xb1b6aba7,0xb46ab577,0x32cd30d2,0x381a38e5,0xb682b4b7,0xb0d2b2cd,0x3577346a,0x34b73682,0xb8e5b81a,
  0xa7a9adc2,0x37b4368e,0x2ba731b6,0xba41b99d,0xb5d2b6d1,0x2d2a26e0,0x392439c5,0xb122aade,0xb3e3b4de,0x32163052,0x376f3874,0xb5dfb43e,
  0xb052b216,0x34de33e3,0x343e35df,0xb874b76f,0xa6e0ad2a,0x36d135d2,0x2ade3122,0xb9c5b924,0xb51cb5f6,0x2c932617,0x38a3393c,0xb08daa16,
  0xb2f4b448,0x31602fa5,0x36a437fe,0xb53ab389,0xafa5b160,0x344832f4,0x3389353a,0xb7feb6a4,0xa617ac93,0x35f6351c,0x2a16308d,0xb93cb8a3,
  0xb46ab523,0x2bf6254d,0x381a38a8,0xafefa94d,0xb209b36b,0x30ac2ea7,0x35d4370a,0xb493b294,0xaea7b0ac,0x336b3209,0x32943493,0xb70ab5d4,
  0xa54dabf6,0x3523346a,0x294d2fef,0xb8a8b81a,0xb378b456,0x2ac82484,0x3715380a,0xaec3a884,0xb120b24a,0x2ff22da9,0x34ff360e,0xb3d3b19e,
  0xada9aff2,0x324a3120,0x319e33d3,0xb60eb4ff,0xa484aac8,0x34563378,0x28842ec3,0xb80ab715,0xb223b31c,0x29992376,0x35eb36c6,0xad97a776,
  0xb039b12d,0x2e8d2cac,0x3426350b,0xb27cb0a6,0xacacae8d,0x312d3039,0x30a6327c,0xb50bb426,0xa376a999,0x331c3223,0x27762d97,0xb6c6b5eb,
  0xb0d2b194,0x286b21e4,0x34b7356a,0xac6aa5e4,0xaea7b012,0x2d2a2b5f,0x32943402,0xb122af59,0xab5fad2a,0x30122ea7,0x2f593122,0xb402b294,
  0xa1e4a86b,0x319430d2,0x25e42c6a,0xb56ab4b7,0xaf0cb012,0x267b2052,0x32f73402,0xaa7aa452,0xacdeadf5,0x2b912967,0x30d731e8,0xaf8bad65,
  0xa967ab91,0x2df52cde,0x2d652f8b,0xb1e8b0d7,0xa052a67b,0x30122f0c,0x24522a7a,0xb402b2f7,0xac79ad2a,0x24201d7f,0x30743122,0xa81fa17f,
  0xaa31ab91,0x28d026e0,0x2e2d2f8b,0xacceaade,0xa6e0a8d0,0x2b912a31,0x2ade2cce,0xaf8bae2d,0x9d7fa420,0x2d2a2c79,0x217f281f,0xb122b074,
  0xa7a9a86b,0x1f1218b6,0x2ba72c6a,0xa3119cb6,0xa54da67b,0x242021e4,0x294d2a7a,0xa81fa5e4,0xa1e4a420,0x267b254d,0x25e4281f,0xaa7aa94d,
  0x98b69f12,0x286b27a9,0x1cb62311,0xac6aaba7,0x211b21e4,0x98b69248,0xa51ba5e4,0x1cb61648,0x1f122052,0x9d7f9bdb,0xa311a452,0x217f1fdb,
  0x1bdb1d7f,0xa0529f12,0x9fdba17f,0x24522311,0x124818b6,0xa1e4a11b,0x96489cb6,0x25e4251b,0x2a632b5f,0xa1e49bdb,0xae5faf59,0x25e41fdb,
  0x286b2967,0xa6e0a4e9,0xac6aad65,0x2ade28e8,0x24e926e0,0xa967a86b,0xa8e8aade,0x2d652c6a,0x1bdb21e4,0xab5faa63,0x9fdba5e4,0x2f592e5f,
  0x2dc22ea7,0xa54d9f12,0xb1b6b294,0x294d2311,0x2bf62cde,0xaa31a86b,0xafefb0d7,0x2e2d2c6a,0x286b2a31,0xacdeabf6,0xac6aae2d,0x30d72fef,
  0x1f12254d,0xaea7adc2,0xa311a94d,0x329431b6,0x302c30d2,0xa7a9a11b,0xb41ab4b7,0x2ba7251b,0x2dc22f0c,0xac79aa63,0xb1b6b2f7,0x30742e5f,
  0x2a632c79,0xaf0cadc2,0xae5fb074,0x32f731b6,0x211b27a9,0xb0d2b02c,0xa51baba7,0x34b7341a,0x317a3257,0xa902a2ad,0xb552b61a,0x2d0026ad,
  0x2f8c309f,0xaddcac2e,0xb371b487,0x31cf3029,0x2c2e2ddc,0xb09faf8c,0xb029b1cf,0x34873371,0x22ad2902,0xb257b17a,0xa6adad00,0x361a3552,
  0x32cd33e3,0xaa31a420,0xb682b76f,0x2e2d281f,0x30ac31bb,0xaf3fad2a,0xb493b58d,0x33283122,0x2d2a2f3f,0xb1bbb0ac,0xb122b328,0x358d3493,
  0x24202a31,0xb3e3b2cd,0xa81fae2d,0x376f3682,0x341334bc,0xab5fa4e9,0xb7a6b85a,0x2f5928e8,0x319432da,0xb052ae28,0xb56ab68d,0x343e3219,
  0x2e283052,0xb2dab194,0xb219b43e,0x368d356a,0x24e92b5f,0xb4bcb413,0xa8e8af59,0x385a37a6,0x34c3358c,0xac47a5b2,0xb85fb8f3,0x304229b1,
  0x327e33fd,0xb106af26,0xb63cb785,0x34e7330f,0x2f263106,0xb3fdb27e,0xb30fb4e7,0x3785363c,0x25b22c47,0xb58cb4c3,0xa9b1b042,0x38f3385f,
  0x35773662,0xacdea67b,0xb8e5b982,0x30d72a7a,0x336b3493,0xb1bbb012,0xb70ab83a,0x358d3402,0x301231bb,0xb493b36b,0xb402b58d,0x383a370a,
  0x267b2cde,0xb662b577,0xaa7ab0d7,0x398238e5,0x36303741,0xad76a744,0xb962ba04,0x316c2b43,0x342e352a,0xb271b092,0xb7d2b8ad,0x3631347b,
  0x30923271,0xb52ab42e,0xb47bb631,0x38ad37d2,0x27442d76,0xb741b630,0xab43b16c,0x3a043962,0x36ee3815,0xae0ea807,0xb9d6ba7a,0x32012c06,
  0x34a735c4,0xb329b113,0xb84ab91b,0x36d234f3,0x31133329,0xb5c4b4a7,0xb4f3b6d2,0x391b384a,0x28072e0e,0xb815b6ee,0xac06b201,0x3a7a39d6,
  0x37b4388e,0xaea7a86b,0xba41bae1,0x32942c6a,0x35233662,0xb3e3b194,0xb8a8b982,0x376f356a,0x319433e3,0xb662b523,0xb56ab76f,0x398238a8,
  0x286b2ea7,0xb88eb7b4,0xac6ab294,0x3ae13a41,0x3841390f,0xaf3fa8d0,0xbaa2bb3a,0x33282cce,0x35a13705,0xb44fb216,0xb902b9e3,0x380535df,
  0x3216344f,0xb705b5a1,0xb5dfb805,0x39e33902,0x28d02f3f,0xb90fb841,0xacceb328,0x3b3a3aa2,0x38ac3997,0xafd8a935,0xbaf7bb83,0x33ba2d33,
  0x362137ac,0xb4aeb298,0xb958ba3d,0x38503654,0x329834ae,0xb7acb621,0xb654b850,0x3a3d3958,0x29352fd8,0xb997b8ac,0xad33b3ba,0x3b833af7,
  0x391c3a28,0xb039a999,0xbb42bbbc,0x34262d97,0x36a4382d,0xb50eb31c,0xb9aaba90,0x389936c6,0x331c350e,0xb82db6a4,0xb6c6b899,0x3a9039aa,
  0x29993039,0xba28b91c,0xad97b426,0x3bbc3b42,0x39923ac3,0xb085a9fe,0xbb81bbe3,0x346f2dfb,0x372a3886,0xb570b3a0,0xb9f8badb,0x38e03737,
  0x33a03570,0xb886b72a,0xb737b8e0,0x3adb39f8,0x29fe3085,0xbac3b992,0xadfbb46f,0x3be33b81,
};

#define PROF(slot) do {} while (0)
#define PROF_DUMP() do {} while (0)
#define PROFA(slot, dep) do {} while (0)
#define PROF3(slot) do {} while (0)
#define PROF2(slot) do {} while (0)

__device__ __forceinline__ uint32_t smem_u32(const void* p) { return (uint32_t)__cvta_generic_to_shared(p); }

__device__ __forceinline__ void mbar_init(uint32_t a, uint32_t c) {
  asm volatile("mbarrier.init.shared::cta.b64 [%0], %1;\n" ::"r"(a), "r"(c) : "memory");
}
__device__ __forceinline__ void mbar_expect_tx(uint32_t a, uint32_t bytes) {
  asm volatile("mbarrier.arrive.expect_tx.shared::cta.b64 _, [%0], %1;\n" ::"r"(a), "r"(bytes) : "memory");
}
__device__ __forceinline__ void mbar_arrive_cluster(uint32_t cluster_addr) {
  asm volatile("mbarrier.arrive.shared::cluster.b64 _, [%0];\n" ::"r"(cluster_addr) : "memory");
}
__device__ __forceinline__ void mbar_arrive_cluster_n(uint32_t cluster_addr, uint32_t n) {
  asm volatile("mbarrier.arrive.shared::cluster.b64 _, [%0], %1;\n" ::"r"(cluster_addr), "r"(n) : "memory");
}
__device__ __forceinline__ bool mbar_try(uint32_t a, uint32_t parity) {
  uint32_t ok;
  asm volatile("{\n.reg .pred p;\nmbarrier.try_wait.parity.shared::cta.b64 p, [%1], %2;\nselp.u32 %0, 1, 0, p;\n}\n"
               : "=r"(ok) : "r"(a), "r"(parity) : "memory");
  return ok;
}
__device__ __forceinline__ void mbar_wait(uint32_t a, uint32_t parity) {
  if (mbar_try(a, parity)) return;
#pragma unroll 1
  for (int n = 0; n < SPIN_LIMIT; n++)
    if (mbar_try(a, parity)) break;
}
__device__ __forceinline__ bool elect_one() {
  uint32_t p;
  asm volatile("{\n.reg .pred P;\nelect.sync _|P, 0xffffffff;\nselp.u32 %0, 1, 0, P;\n}\n" : "=r"(p));
  return p;
}
__device__ __forceinline__ uint32_t mapa(uint32_t a, uint32_t rank) {
  uint32_t r;
  asm volatile("mapa.shared::cluster.u32 %0, %1, %2;\n" : "=r"(r) : "r"(a), "r"(rank));
  return r;
}
__device__ __forceinline__ void nb_sync(int id, int n) { asm volatile("bar.sync %0, %1;\n" ::"r"(id), "r"(n) : "memory"); }
__device__ __forceinline__ void nb_arrive(int id, int n) { asm volatile("bar.arrive %0, %1;\n" ::"r"(id), "r"(n) : "memory"); }
__device__ __forceinline__ void cluster_sync_all() {
  asm volatile("barrier.cluster.arrive.relaxed.aligned;\nbarrier.cluster.wait.aligned;\n" ::: "memory");
}
__device__ __forceinline__ void fence_async_smem() { asm volatile("fence.proxy.async.shared::cta;\n" ::: "memory"); }
__device__ __forceinline__ void fence_async_all() { asm volatile("fence.proxy.async.global;\n" ::: "memory"); }

__device__ __forceinline__ void tma_load_3d(uint32_t dst, const CUtensorMap* tm, uint32_t bar, int c0, int c1, int c2) {
  asm volatile(
      "cp.async.bulk.tensor.3d.shared::cluster.global.mbarrier::complete_tx::bytes [%0], [%1, {%3, %4, %5}], [%2];\n"
      ::"r"(dst), "l"(tm), "r"(bar), "r"(c0), "r"(c1), "r"(c2) : "memory");
}
__device__ __forceinline__ void tma_load_4d(uint32_t dst, const CUtensorMap* tm, uint32_t bar, int c0, int c1, int c2, int c3) {
  asm volatile(
      "cp.async.bulk.tensor.4d.shared::cluster.global.mbarrier::complete_tx::bytes [%0], [%1, {%3, %4, %5, %6}], [%2];\n"
      ::"r"(dst), "l"(tm), "r"(bar), "r"(c0), "r"(c1), "r"(c2), "r"(c3) : "memory");
}
__device__ __forceinline__ void tma_load_3d_mc(uint32_t dst, const CUtensorMap* tm, uint32_t bar, int c0, int c1, int c2) {
  asm volatile(
      "cp.async.bulk.tensor.3d.shared::cluster.global.mbarrier::complete_tx::bytes.multicast::cluster [%0], [%1, {%3, %4, %5}], [%2], %6;\n"
      ::"r"(dst), "l"(tm), "r"(bar), "r"(c0), "r"(c1), "r"(c2), "h"((uint16_t)3) : "memory");
}
__device__ __forceinline__ void bulk_load(uint32_t dst, const void* src, uint32_t bytes, uint32_t bar) {
  asm volatile("cp.async.bulk.shared::cluster.global.mbarrier::complete_tx::bytes [%0], [%1], %2, [%3];\n"
               ::"r"(dst), "l"(src), "r"(bytes), "r"(bar) : "memory");
}
__device__ __forceinline__ void tma_store_3d(const CUtensorMap* tm, uint32_t src, int c0, int c1, int c2) {
  asm volatile("cp.async.bulk.tensor.3d.global.shared::cta.bulk_group [%0, {%2, %3, %4}], [%1];\n"
               ::"l"(tm), "r"(src), "r"(c0), "r"(c1), "r"(c2) : "memory");
}
__device__ __forceinline__ void bulk_commit() { asm volatile("cp.async.bulk.commit_group;\n" ::: "memory"); }
__device__ __forceinline__ void bulk_wait0() { asm volatile("cp.async.bulk.wait_group 0;\n" ::: "memory"); }
__device__ __forceinline__ void prefetch_tmap(const CUtensorMap* tm) {
  asm volatile("prefetch.tensormap [%0];\n" ::"l"(tm) : "memory");
}

__device__ __forceinline__ void wg_fence() { asm volatile("wgmma.fence.sync.aligned;\n" ::: "memory"); }
__device__ __forceinline__ void wg_commit() { asm volatile("wgmma.commit_group.sync.aligned;\n" ::: "memory"); }
template <int N> __device__ __forceinline__ void wg_wait() {
  asm volatile("wgmma.wait_group.sync.aligned %0;\n" ::"n"(N) : "memory");
}
__device__ __forceinline__ uint64_t mkdesc(uint32_t addr, uint32_t lbo, uint32_t sbo, uint32_t swz) {
  return (uint64_t)((addr & 0x3FFFF) >> 4) | ((uint64_t)(lbo >> 4) << 16) | ((uint64_t)(sbo >> 4) << 32) |
         ((uint64_t)swz << 62);
}

#define R4(d, o) "+f"(d[o + 0]), "+f"(d[o + 1]), "+f"(d[o + 2]), "+f"(d[o + 3])
#define R8(d, o) R4(d, o), R4(d, o + 4)
#define R16(d, o) R8(d, o), R8(d, o + 8)
#define R32(d, o) R16(d, o), R16(d, o + 16)
#define R64(d, o) R32(d, o), R32(d, o + 32)

__device__ __forceinline__ void wgmma_n192(float (&d)[96], uint64_t da, uint64_t db, uint32_t acc) {
  asm volatile(
      "{\n.reg .pred p;\nsetp.ne.u32 p, %98, 0;\n"
      "wgmma.mma_async.sync.aligned.m64n192k16.f32.bf16.bf16 "
      "{%0,%1,%2,%3,%4,%5,%6,%7,%8,%9,%10,%11,%12,%13,%14,%15,%16,%17,%18,%19,%20,%21,%22,%23,%24,%25,%26,%27,%28,%29,%30,%31,"
      "%32,%33,%34,%35,%36,%37,%38,%39,%40,%41,%42,%43,%44,%45,%46,%47,%48,%49,%50,%51,%52,%53,%54,%55,%56,%57,%58,%59,%60,%61,%62,%63,"
      "%64,%65,%66,%67,%68,%69,%70,%71,%72,%73,%74,%75,%76,%77,%78,%79,%80,%81,%82,%83,%84,%85,%86,%87,%88,%89,%90,%91,%92,%93,%94,%95}, "
      "%96, %97, p, 1, 1, 0, 1;\n}\n"
      : R64(d, 0), R32(d, 64)
      : "l"(da), "l"(db), "r"(acc));
}
__device__ __forceinline__ void wgmma_n128(float (&d)[64], uint64_t da, uint64_t db, uint32_t acc) {
  asm volatile(
      "{\n.reg .pred p;\nsetp.ne.u32 p, %66, 0;\n"
      "wgmma.mma_async.sync.aligned.m64n128k16.f32.bf16.bf16 "
      "{%0,%1,%2,%3,%4,%5,%6,%7,%8,%9,%10,%11,%12,%13,%14,%15,%16,%17,%18,%19,%20,%21,%22,%23,%24,%25,%26,%27,%28,%29,%30,%31,"
      "%32,%33,%34,%35,%36,%37,%38,%39,%40,%41,%42,%43,%44,%45,%46,%47,%48,%49,%50,%51,%52,%53,%54,%55,%56,%57,%58,%59,%60,%61,%62,%63}, "
      "%64, %65, p, 1, 1, 0, 1;\n}\n"
      : R64(d, 0)
      : "l"(da), "l"(db), "r"(acc));
}
template <int N> __device__ __forceinline__ void fence_regs(float (&d)[N]) {
#pragma unroll
  for (int i = 0; i < N; i++) asm volatile("" : "+f"(d[i])::"memory");
}

__device__ __forceinline__ void mma16816(float (&d)[4], uint32_t a0, uint32_t a1, uint32_t a2, uint32_t a3, uint32_t b0,
                                         uint32_t b1) {
  asm("mma.sync.aligned.m16n8k16.row.col.f32.bf16.bf16.f32 {%0,%1,%2,%3}, {%4,%5,%6,%7}, {%8,%9}, {%0,%1,%2,%3};\n"
      : "+f"(d[0]), "+f"(d[1]), "+f"(d[2]), "+f"(d[3])
      : "r"(a0), "r"(a1), "r"(a2), "r"(a3), "r"(b0), "r"(b1));
}
__device__ __forceinline__ void mma16816_z(float (&d)[4], uint32_t a0, uint32_t a1, uint32_t a2, uint32_t a3, uint32_t b0,
                                           uint32_t b1) {
  asm("mma.sync.aligned.m16n8k16.row.col.f32.bf16.bf16.f32 {%0,%1,%2,%3}, {%4,%5,%6,%7}, {%8,%9}, {%10,%10,%10,%10};\n"
      : "=f"(d[0]), "=f"(d[1]), "=f"(d[2]), "=f"(d[3])
      : "r"(a0), "r"(a1), "r"(a2), "r"(a3), "r"(b0), "r"(b1), "f"(0.f));
}
__device__ __forceinline__ void ldsm4t(uint32_t (&r)[4], uint32_t a) {
  asm volatile("ldmatrix.sync.aligned.m8n8.x4.trans.shared.b16 {%0,%1,%2,%3}, [%4];\n"
               : "=r"(r[0]), "=r"(r[1]), "=r"(r[2]), "=r"(r[3]) : "r"(a) : "memory");
}
__device__ __forceinline__ void ldsm2t(uint32_t& r0, uint32_t& r1, uint32_t a) {
  asm volatile("ldmatrix.sync.aligned.m8n8.x2.trans.shared.b16 {%0,%1}, [%2];\n" : "=r"(r0), "=r"(r1) : "r"(a) : "memory");
}
__device__ __forceinline__ void st_async128(uint32_t a, uint32_t bar, uint32_t x, uint32_t y, uint32_t z, uint32_t w) {
  asm volatile("st.async.weak.shared::cluster.mbarrier::complete_tx::bytes.v4.b32 [%0], {%2,%3,%4,%5}, [%1];\n"
               ::"r"(a), "r"(bar), "r"(x), "r"(y), "r"(z), "r"(w) : "memory");
}
__device__ __forceinline__ void mbar_arrive(uint32_t a) {
  asm volatile("mbarrier.arrive.shared::cta.b64 _, [%0];\n" ::"r"(a) : "memory");
}
__device__ __forceinline__ void stsm4(uint32_t a, uint32_t r0, uint32_t r1, uint32_t r2, uint32_t r3) {
  asm volatile("stmatrix.sync.aligned.m8n8.x4.shared.b16 [%0], {%1,%2,%3,%4};\n"
               ::"r"(a), "r"(r0), "r"(r1), "r"(r2), "r"(r3) : "memory");
}
__device__ __forceinline__ void stsm4t(uint32_t a, uint32_t r0, uint32_t r1, uint32_t r2, uint32_t r3) {
  asm volatile("stmatrix.sync.aligned.m8n8.x4.trans.shared.b16 [%0], {%1,%2,%3,%4};\n"
               ::"r"(a), "r"(r0), "r"(r1), "r"(r2), "r"(r3) : "memory");
}
__device__ __forceinline__ uint2 lds64(uint32_t a) {
  uint2 v;
  asm volatile("ld.shared.v2.u32 {%0,%1}, [%2];\n" : "=r"(v.x), "=r"(v.y) : "r"(a));
  return v;
}
__device__ __forceinline__ uint4 lds128(uint32_t a) {
  uint4 v;
  asm volatile("ld.shared.v4.u32 {%0,%1,%2,%3}, [%4];\n" : "=r"(v.x), "=r"(v.y), "=r"(v.z), "=r"(v.w) : "r"(a) : "memory");
  return v;
}
__device__ __forceinline__ void sts128(uint32_t a, uint32_t x, uint32_t y, uint32_t z, uint32_t w) {
  asm volatile("st.shared.v4.u32 [%0], {%1,%2,%3,%4};\n" ::"r"(a), "r"(x), "r"(y), "r"(z), "r"(w) : "memory");
}
__device__ __forceinline__ void sts64(uint32_t a, uint32_t x, uint32_t y) {
  asm volatile("st.shared.v2.u32 [%0], {%1,%2};\n" ::"r"(a), "r"(x), "r"(y) : "memory");
}
__device__ __forceinline__ uint32_t pack_bf16(float lo, float hi) {
  uint32_t r;
  asm("cvt.rn.bf16x2.f32 %0, %1, %2;\n" : "=r"(r) : "f"(hi), "f"(lo));
  return r;
}
__device__ __forceinline__ uint32_t bmul2(uint32_t a, uint32_t b) {
  uint32_t r;
  asm("mul.rn.bf16x2 %0, %1, %2;\n" : "=r"(r) : "r"(a), "r"(b));
  return r;
}
__device__ __forceinline__ uint32_t bmax2(uint32_t a, uint32_t b) {
  uint32_t r;
  asm("max.bf16x2 %0, %1, %2;\n" : "=r"(r) : "r"(a), "r"(b));
  return r;
}
__device__ __forceinline__ uint32_t bfma2(uint32_t a, uint32_t b, uint32_t c) {
  uint32_t r;
  asm("fma.rn.bf16x2 %0, %1, %2, %3;\n" : "=r"(r) : "r"(a), "r"(b), "r"(c));
  return r;
}
__device__ __forceinline__ uint32_t badd2(uint32_t a, uint32_t b) {
  uint32_t r;
  asm("add.rn.bf16x2 %0, %1, %2;\n" : "=r"(r) : "r"(a), "r"(b));
  return r;
}
__device__ __forceinline__ void prefetch_l2(const void* p) { asm volatile("prefetch.global.L2 [%0];\n" ::"l"(p)); }
__device__ __forceinline__ void cp_async16n(uint32_t dst, const void* src) {
  asm volatile("cp.async.cg.shared.global [%0], [%1], 16;\n" ::"r"(dst), "l"(src) : "memory");
}
__device__ __forceinline__ void cp_async16(uint32_t dst, const void* src, uint32_t srcbytes) {
  asm volatile("cp.async.cg.shared.global.L2::256B [%0], [%1], 16, %2;\n" ::"r"(dst), "l"(src), "r"(srcbytes) : "memory");
}
__device__ __forceinline__ uint32_t ld_acquire(const uint32_t* p) {
  uint32_t v;
  asm volatile("ld.acquire.gpu.global.u32 %0, [%1];\n" : "=r"(v) : "l"(p) : "memory");
  return v;
}
__device__ __forceinline__ uint32_t ld_relaxed(const uint32_t* p) {
  uint32_t v;
  asm volatile("ld.relaxed.gpu.global.u32 %0, [%1];\n" : "=r"(v) : "l"(p) : "memory");
  return v;
}
__device__ __forceinline__ void st_release(uint32_t* p, uint32_t v) {
  asm volatile("st.release.gpu.global.u32 [%0], %1;\n" ::"l"(p), "r"(v) : "memory");
}
__device__ __forceinline__ void wait_flag(const uint32_t* p, uint32_t want) {
  int n = 0;
  while (ld_acquire(p) != want && ++n < SPIN_LIMIT) {}
}

struct Params {
  const __nv_bfloat16* x;
  const __nv_bfloat16* w;
  const __nv_bfloat16* q;
  const __nv_bfloat16* k;
  const __nv_bfloat16* v;
  const __nv_bfloat16* shift_k;
  const __nv_bfloat16* ssm_k;
  const __nv_bfloat16* ssm_D;
  const __nv_bfloat16* wo;
  __nv_bfloat16* out;
  uint32_t zero;
};

__device__ __forceinline__ uint32_t lds32(uint32_t a) {
  uint32_t v;
  asm volatile("ld.shared.u32 %0, [%1];\n" : "=r"(v) : "r"(a));
  return v;
}
__device__ __forceinline__ float bf_lo(uint32_t v) {
  uint32_t r;
  asm("prmt.b32 %0, %1, 0, 0x1044;\n" : "=r"(r) : "r"(v));
  return __uint_as_float(r);
}
__device__ __forceinline__ float bf_hi(uint32_t v) { return __uint_as_float(v & 0xffff0000u); }
__device__ __forceinline__ float ex2(float x) {
  float r;
  asm("ex2.approx.ftz.f32 %0, %1;\n" : "=f"(r) : "f"(x));
  return r;
}
__device__ __forceinline__ float rcp(float x) {
  float r;
  asm("rcp.approx.ftz.f32 %0, %1;\n" : "=f"(r) : "f"(x));
  return r;
}

#define Q4(c, d, o) c(d[o + 0]), c(d[o + 1]), c(d[o + 2]), c(d[o + 3])
#define Q8(c, d, o) Q4(c, d, o), Q4(c, d, o + 4)
#define Q16(c, d, o) Q8(c, d, o), Q8(c, d, o + 8)
#define Q32(c, d) Q16(c, d, 0), Q16(c, d, 16)
#define L8 "{%0,%1,%2,%3,%4,%5,%6,%7}"
#define L16 "{%0,%1,%2,%3,%4,%5,%6,%7,%8,%9,%10,%11,%12,%13,%14,%15}"
#define L32 "{%0,%1,%2,%3,%4,%5,%6,%7,%8,%9,%10,%11,%12,%13,%14,%15,%16,%17,%18,%19,%20,%21,%22,%23,%24,%25,%26,%27,%28,%29,%30,%31}"
__device__ __forceinline__ void fft_rows(uint32_t (&d)[32], const uint32_t (&a)[2][4], uint64_t db) {
  asm volatile("wgmma.mma_async.sync.aligned.m64n128k16.f16.f16.f16 " L32 ", {%32,%33,%34,%35}, %36, 0, 1, 1, 1;\n"
               : Q32("=r", d) : "r"(a[0][0]), "r"(a[0][1]), "r"(a[0][2]), "r"(a[0][3]), "l"(db));
  asm volatile("wgmma.mma_async.sync.aligned.m64n128k16.f16.f16.f16 " L32 ", {%32,%33,%34,%35}, %36, 1, 1, 1, 1;\n"
               : Q32("+r", d) : "r"(a[1][0]), "r"(a[1][1]), "r"(a[1][2]), "r"(a[1][3]), "l"(db + 128));
}
template <int INV> __device__ __forceinline__ void fft_cols(uint32_t (&d)[8], const uint32_t (&a)[2][4], uint64_t db) {
  asm volatile("wgmma.mma_async.sync.aligned.m64n32k16.f16.f16.f16 " L8 ", {%8,%9,%10,%11}, %12, 0, 1, 1, %13;\n"
               : Q8("=r", d, 0) : "r"(a[0][0]), "r"(a[0][1]), "r"(a[0][2]), "r"(a[0][3]), "l"(db), "n"(INV));
  asm volatile("wgmma.mma_async.sync.aligned.m64n32k16.f16.f16.f16 " L8 ", {%8,%9,%10,%11}, %12, 1, 1, 1, %13;\n"
               : Q8("+r", d, 0) : "r"(a[1][0]), "r"(a[1][1]), "r"(a[1][2]), "r"(a[1][3]), "l"(db + (INV ? 16 : 64)), "n"(INV));
}
__device__ __forceinline__ void fft_back(float (&d)[16], uint64_t da, uint64_t db) {
  asm volatile("wgmma.mma_async.sync.aligned.m64n32k16.f32.f16.f16 " L16 ", %16, %17, 0, 1, 1, 1, 1;\n"
               : Q16("=f", d, 0) : "l"(da), "l"(db));
#pragma unroll
  for (int i = 1; i < 4; i++)
    asm volatile("wgmma.mma_async.sync.aligned.m64n32k16.f32.f16.f16 " L16 ", %16, %17, 1, 1, 1, 1, 1;\n"
                 : Q16("+f", d, 0) : "l"(da + 32 * i), "l"(db + 64 * i));
}
__device__ __forceinline__ uint32_t hmul2(uint32_t a, uint32_t b) {
  uint32_t r;
  asm("mul.rn.f16x2 %0, %1, %2;\n" : "=r"(r) : "r"(a), "r"(b));
  return r;
}
__device__ __forceinline__ uint32_t hadd2(uint32_t a, uint32_t b) {
  uint32_t r;
  asm("add.rn.f16x2 %0, %1, %2;\n" : "=r"(r) : "r"(a), "r"(b));
  return r;
}
__device__ __forceinline__ uint32_t hneg2(uint32_t a) {
  uint32_t r;
  asm("neg.f16x2 %0, %1;\n" : "=r"(r) : "r"(a));
  return r;
}
__device__ __forceinline__ uint32_t hfma2(uint32_t a, uint32_t b, uint32_t c) {
  uint32_t r;
  asm("fma.rn.f16x2 %0, %1, %2, %3;\n" : "=r"(r) : "r"(a), "r"(b), "r"(c));
  return r;
}
__device__ __forceinline__ uint32_t pack_f16(float lo, float hi) {
  uint32_t r;
  asm("cvt.rn.f16x2.f32 %0, %1, %2;\n" : "=r"(r) : "f"(hi), "f"(lo));
  return r;
}
__device__ __forceinline__ uint32_t bmaxabs2(uint32_t a, uint32_t b) {
  uint32_t r;
  asm("max.xorsign.abs.bf16x2 %0, %1, %2;\n" : "=r"(r) : "r"(a), "r"(b));
  return r;
}
struct C2 { uint32_t r, i; };
__device__ __forceinline__ C2 cmul(C2 a, C2 b) {
  return C2{hfma2(a.r, b.r, hneg2(hmul2(a.i, b.i))), hfma2(a.r, b.i, hmul2(a.i, b.r))};
}
__device__ __forceinline__ C2 cfma(C2 a, C2 b, C2 c) {
  return C2{hfma2(a.r, b.r, hfma2(hneg2(a.i), b.i, c.r)), hfma2(a.r, b.i, hfma2(a.i, b.r, c.i))};
}
__device__ __forceinline__ C2 crot(C2 z, C2 t) {
  const uint32_t r = hfma2(t.r, z.i, z.r), i = hfma2(t.i, r, z.i);
  return C2{hfma2(t.r, i, r), i};
}
__device__ __forceinline__ C2 cget(const uint32_t (&e)[8], int j, int b) { return C2{e[4 * j + b], e[4 * j + 2 + b]}; }
template <int N> __device__ __forceinline__ void fence_regs(uint32_t (&d)[N]) {
#pragma unroll
  for (int i = 0; i < N; i++) asm volatile("" : "+r"(d[i])::"memory");
}
__device__ __forceinline__ void ldsm4(uint32_t (&r)[4], uint32_t a) {
  asm volatile("ldmatrix.sync.aligned.m8n8.x4.shared.b16 {%0,%1,%2,%3}, [%4];\n"
               : "=r"(r[0]), "=r"(r[1]), "=r"(r[2]), "=r"(r[3]) : "r"(a) : "memory");
}

__device__ __forceinline__ uint32_t movm(uint32_t a) {
  uint32_t r;
  asm volatile("movmatrix.sync.aligned.m8n8.trans.b16 %0, %1;\n" : "=r"(r) : "r"(a));
  return r;
}
template <int C0, int H, bool T> __device__ __forceinline__ void attn_pack(const float (&acc)[96], uint32_t (&d)[8]) {
#pragma unroll
  for (int c = 0; c < 8; c++) {
    asm volatile("cvt.rn.bf16x2.f32 %0, %1, %2;\n" : "=r"(d[c]) : "f"(acc[4 * (C0 + c) + 2 * H + 1]), "f"(acc[4 * (C0 + c) + 2 * H]));
    if (T) d[c] = movm(d[c]);
  }
}
__device__ __forceinline__ void attn_qk(float (&s)[4], const uint32_t (&qlo)[8], const uint32_t (&qhi)[8],
                                        const uint32_t (&k)[8], int c) {
  mma16816_z(s, qlo[c], qhi[c], qlo[c + 1], qhi[c + 1], k[c], k[c + 1]);
  mma16816(s, qlo[c + 2], qhi[c + 2], qlo[c + 3], qhi[c + 3], k[c + 2], k[c + 3]);
}
template <int N> __device__ __forceinline__ void quad_softmax(float (&x)[N][2], uint32_t (&pp)[N]) {
  const float c2 = 1.4426950408889634f;
  uint32_t q[N], mx[N / 2];
#pragma unroll
  for (int n = 0; n < N; n++) {
    const uint32_t r = pack_bf16(x[n][0], x[n][1]);
    q[n] = bfma2(r, 0x3e353e35u, bmul2(r, 0x379e379eu));
    x[n][0] = bf_lo(q[n]);
    x[n][1] = bf_hi(q[n]);
  }
#pragma unroll
  for (int n = 0; n < N / 2; n++)
    mx[n] = bmax2(__byte_perm(q[2 * n], q[2 * n + 1], 0x5410), __byte_perm(q[2 * n], q[2 * n + 1], 0x7632));
#pragma unroll
  for (int o = 1; o <= 2; o++) {
#pragma unroll
    for (int n = 0; n < N / 2; n++) mx[n] = bmax2(mx[n], __shfl_xor_sync(0xffffffffu, mx[n], o));
  }
  float m[N], t[N];
#pragma unroll
  for (int n = 0; n < N / 2; n++) {
    m[2 * n] = bf_lo(mx[n]);
    m[2 * n + 1] = bf_hi(mx[n]);
  }
#pragma unroll
  for (int n = 0; n < N; n++) {
    const float nm = -m[n] * c2;
    x[n][0] = ex2(fmaf(x[n][0], c2, nm));
    x[n][1] = ex2(fmaf(x[n][1], c2, nm));
  }
#pragma unroll
  for (int n = 0; n < N; n += 2) {
    float u0, u1;
    asm("mma.sync.aligned.m16n8k8.row.col.f32.tf32.tf32.f32 {%0,%1,%2,%3}, {%4,%5,%6,%7}, {%8,%8}, {%9,%9,%9,%9};\n"
        : "=f"(t[n]), "=f"(u0), "=f"(t[n + 1]), "=f"(u1)
        : "r"(__float_as_uint(x[n][0])), "r"(__float_as_uint(x[n + 1][0])), "r"(__float_as_uint(x[n][1])),
          "r"(__float_as_uint(x[n + 1][1])), "r"(0x3f800000u), "f"(0.f));
  }
#pragma unroll
  for (int n = 0; n < N; n++) {
    const float inv = rcp(t[n]);
    pp[n] = pack_bf16(x[n][0] * inv, x[n][1] * inv);
  }
}
__device__ __forceinline__ void attn_pv(uint32_t dst, const uint32_t (&vp)[8], const uint32_t (&vo)[8], int c, uint32_t pp,
                                        uint32_t maskLE) {
  const uint32_t b0 = pp & ~maskLE, b1 = pp & maskLE;
  float oa[4], ob[4];
  mma16816_z(oa, vp[c], vp[c + 1], vo[c], vo[c + 1], b0, b1);
  mma16816_z(ob, vp[c + 2], vp[c + 3], vo[c + 2], vo[c + 3], b0, b1);
  stsm4t(dst, pack_bf16(oa[0], oa[1]), pack_bf16(oa[2], oa[3]), pack_bf16(ob[0], ob[1]), pack_bf16(ob[2], ob[3]));
}

template <int MODE>
__global__ void __cluster_dims__(2, 1, 1) __launch_bounds__(NTHREADS, 1)
fused_kernel(const Params p, const __grid_constant__ CUtensorMap tmX, const __grid_constant__ CUtensorMap tmW,
             const __grid_constant__ CUtensorMap tmWo, const __grid_constant__ CUtensorMap tmWp,
             const __grid_constant__ CUtensorMap tmQ,
             const __grid_constant__ CUtensorMap tmOb,
             const __grid_constant__ CUtensorMap tmXh, const __grid_constant__ CUtensorMap tmWh) {
  extern __shared__ __align__(1024) uint8_t smem[];
  if (threadIdx.x < 32) {
    const uint32_t i = (blockIdx.x & 127) * 16 + (threadIdx.x & 15);
    prefetch_l2(threadIdx.x & 16 ? (const char*)p.w + i * 128 : (const char*)p.x + i * 2048);
  }
  const uint32_t sb = smem_u32(smem);
  const uint32_t bars = sb + OFF_BAR;
  const int tid = threadIdx.x, lane = tid & 31, warp = __shfl_sync(0xffffffffu, tid >> 5, 0);
  const int rank = blockIdx.x & 1;
  const bool halo_cta = blockIdx.x < 4;
  if (halo_cta && MODE != 0) return;
  int grp, mem;
  {
    const int t = (blockIdx.x >> 1) - 4, u = t - 32;
    const int q7 = (u * 37) >> 8;
    const bool lo = (unsigned)t < 32u, mid = (unsigned)u < 28u;
    grp = lo ? (t & 7) : (mid ? 1 + u - 7 * q7 : 0);
    mem = lo ? (t >> 3) : (mid ? 4 + q7 : (t < 0 ? t + 6 : t - 54));
  }
  const int rg = (grp >> 2) * 4 + (mem >> 1), hp = (grp & 3) * 4 + (mem & 1) * 2 + rank;
  const int rb2 = (grp >> 2) * 8 + mem, cb2 = (grp & 3) * 2 + rank;
  const int chb = grp * 16 + mem * 2 + rank;
  const int cta = rg * 16 + hp;
  const int hsel = rb2 & 1;
  constexpr int g2wg = G2W;
  const int par = rg >> 2, gidx = rg & 3;

  if (tid < 256 && !halo_cta && MODE != 2) {
    const int r = tid >> 3, c = tid & 7;
    const uint32_t so = r * 128 + ((c ^ (r & 7)) << 4);
    const __nv_bfloat16* wg0 = p.w + (size_t)r * (3 * DM) + hp * 64 + c * 8;
    const __nv_bfloat16* xg0 = p.x + (size_t)(2 * (gidx * 256 + r) + par) * DM + c * 8;
#pragma unroll
    for (int j = 0; j < 3; j++) cp_async16n(sb + OFF_1B + j * 4096 + so, wg0 + j * DM);
#pragma unroll
    for (int i = 0; i < 8; i++) cp_async16n(sb + i * 4096 + so, xg0 + (size_t)i * 64 * DM);
    asm volatile("cp.async.commit_group;\n" ::: "memory");
  }
  auto halo_issue = [&](int kb, int s) {
    const uint32_t fb = bars + 8 * (BAR_FULLB + s), st = sb + s * STGH;
    mbar_expect_tx(fb, STGH - 2048);
    tma_load_3d(st + 8192, &tmWh, fb, 0, kb * 64, 16 + blockIdx.x * 4);
    tma_load_3d(st + 8192 + 32768, &tmWh, fb, 0, kb * 64, 32 + blockIdx.x * 4);
    tma_load_4d(st, &tmXh, fb, kb * 64, 248, 0, 0);
  };
  if (tid == 256) {
    prefetch_tmap(halo_cta ? &tmXh : &tmX);
#pragma unroll
    for (int i = 0; i < NS1B; i++) mbar_init(bars + 8 * (BAR_FULLB + i), 1);
#pragma unroll
    for (int i = 0; i < NS1A; i++) mbar_init(bars + 8 * (BAR_FULLA + i), 1);
    asm volatile("fence.mbarrier_init.release.cluster;\n" ::: "memory");
    if (!halo_cta && MODE != 2) {
      mbar_expect_tx(bars + 8 * (BAR_FULLB + 1), STG1B);
      tma_load_3d(sb + OFF_1B + 1 * STG1B, &tmW, bars + 8 * (BAR_FULLB + 1), hp * 64, 32, 0);
      mbar_expect_tx(bars + 8 * (BAR_FULLB + 2), STG1B);
      tma_load_3d(sb + OFF_1B + 2 * STG1B, &tmW, bars + 8 * (BAR_FULLB + 2), hp * 64, 64, 0);
    } else if (halo_cta) {
      halo_issue(0, 0);
    }
  } else if (tid == 288) {
#pragma unroll
    for (int i = 0; i < NS1A; i++) mbar_init(bars + 8 * (BAR_EMPTYA + i), 4);
#pragma unroll
    for (int i = 0; i < NS1B; i++) mbar_init(bars + 8 * (BAR_EMPTYB + i), 2);
    mbar_init(bars + 8 * BAR_X, 4);
    mbar_init(bars + 8 * BAR_LAND, 17);
    mbar_init(bars + 8 * BAR_TAB, 16);
    mbar_init(bars + 8 * BAR_U, 1);
    mbar_init(bars + 8 * BAR_H, 1);
    mbar_init(bars + 8 * BAR_STG, 8);
    mbar_init(bars + 8 * BAR_HALO, 1);
    mbar_init(bars + 8 * BAR_Q, 1);
    mbar_init(bars + 8 * BAR_XFREE, 2);
    mbar_init(bars + 8 * (BAR_XFREE + 1), 2);
    asm volatile("fence.mbarrier_init.release.cluster;\n" ::: "memory");
  } else if (tid == 320) {
#pragma unroll
    for (int i = 0; i < NS2; i++) {
      mbar_init(bars + 8 * (BAR_FULL2 + i), 1);
      mbar_init(bars + 8 * (BAR_EMPTY2 + i), 2);
    }
    asm volatile("fence.mbarrier_init.release.cluster;\n" ::: "memory");
  } else if (tid == 352) {
#pragma unroll
    for (int i = 0; i < 8; i++) mbar_init(bars + 8 * (BAR_Y + i), 4);
    asm volatile("fence.mbarrier_init.release.cluster;\n" ::: "memory");
  }
  cluster_sync_all();
  if (warp == 8) PROF2(24);

  if (warp >= 8) {
    const int hw = warp - 8;
    const int lr = lane & 7, lm = lane >> 3;
    auto g1_issue_a = [&](int j, int s) {
      const uint32_t fb = bars + 8 * (BAR_FULLA + s);
      mbar_expect_tx(fb, STG1A);
      tma_load_3d_mc(sb + s * STG1A + rank * 16384, &tmX, fb, j * 64, par, gidx * 256 + rank * 128);
    };
    auto g1_issue_b = [&](int kb, int s) {
      const uint32_t fb = bars + 8 * (BAR_FULLB + s);
      mbar_expect_tx(fb, STG1B);
      tma_load_3d(sb + OFF_1B + s * STG1B, &tmW, fb, hp * 64, kb * 32, 0);
    };
    auto g2_k = [&](int kb) { return (kb < 2 ? hp : kb < 4 ? hp & 14 : hp & 12) ^ kb; };
    auto g2_issue_b = [&](int kb, int s) {
      const uint32_t fb = bars + 8 * (BAR_FULL2 + s), dst = sb + g2_b(s, rank);
      mbar_expect_tx(fb, kb || MODE ? STG2 : STG2 / 2);
      if (s < 3) {
        tma_load_3d(dst, &tmWo, fb, 0, g2_k(kb) * 64, cb2 * 2);
      } else {
#pragma unroll
        for (int i = 0; i < 4; i++)
          tma_load_3d(dst + (i & 1) * XT + (i >> 1) * 4 * XT, &tmWp, fb, 0, g2_k(kb) * 64 + (i >> 1) * 32, cb2 * 2 + (i & 1));
      }
    };
    asm volatile("setmaxnreg.dec.sync.aligned.u32 %0;\n" :: "n"(REG_HELP));

    if (halo_cta) {
      if (hw == 0) {
        int s = 1, ph = 1;
#pragma unroll 1
        for (int kb = 1; kb < 16; kb++) {
          mbar_wait(bars + 8 * (BAR_EMPTYB + s), ph);
          if (elect_one()) halo_issue(kb, s);
          if (++s == 3) { s = 0; ph ^= 1; }
        }
      }
      __syncwarp();
    } else if (hw == 0) {
      uint32_t epoch = 0;
      if (MODE == 2) {
        if (lane < NS2) mbar_arrive_cluster_n(mapa(bars, rank) + 8 * (BAR_EMPTY2 + lane), 2);
      } else {
      if (lane == 0) {
        mbar_expect_tx(bars + 8 * BAR_U, 32768);
        mbar_expect_tx(bars + 8 * BAR_LAND, 16384);
        mbar_expect_tx(bars + 8 * BAR_Q, 32768);
        prefetch_tmap(&tmQ);
      }
      {
        int sa = 1, pha = 1, sbb = 2, phb = 1;
#pragma unroll 1
        for (int kb = 2; kb < 32; kb++) {
          if (!(kb & 1)) {
            mbar_wait(bars + 8 * (BAR_EMPTYA + sa), pha);
            if (elect_one()) g1_issue_a(kb >> 1, sa);
            if (++sa == NS1A) { sa = 0; pha ^= 1; }
          }
          mbar_wait(bars + 8 * (BAR_EMPTYB + sbb), phb);
          if (kb > 2 && elect_one()) g1_issue_b(kb, sbb);
          __syncwarp();
          if (kb == 4) epoch = ld_relaxed(g_flag_o + cta);
          if (kb == 4) PROF2(27);
          if (kb == 1) PROF2(38);
          if (kb == 2) PROF2(39);
          if (++sbb == NS1B) { sbb = 0; phb ^= 1; }
        }
      }
      auto q_issue = [&](int i) {
        mbar_wait(bars + 8 * (i ? BAR_EMPTYB + 3 : BAR_EMPTYA + 1), i);
        if (elect_one())
          asm volatile(
              "cp.async.bulk.tensor.5d.shared::cluster.global.mbarrier::complete_tx::bytes [%0], [%1, {%3, %4, %4, %4, %5}], [%2];\n"
              ::"r"(sb + (i ? OFF_Q1 : OFF_Q0)), "l"(&tmQ), "r"(bars + 8 * BAR_Q), "r"((chb & ~1) * 8), "r"(0), "r"(rank * 64 + i * 32)
              : "memory");
        __syncwarp();
      };
      if (QORD < 2) q_issue(0);
      else mbar_wait(bars + 8 * (BAR_EMPTYA + 1), 0);
      if (QORD < 1) q_issue(1);
      epoch++;
      if (lane == 0) {
        prefetch_tmap(&tmWo);
        prefetch_tmap(&tmWp);
        prefetch_tmap(&tmOb);
        if (gidx != 0) wait_flag(g_flag_h + (hp >> 2), epoch);
      }
      __syncwarp();
      {
        uint4 hk0 = make_uint4(0, 0, 0, 0), hk1 = hk0, hv0 = hk0, hv1 = hk0;
        if (gidx != 0) {
          const uint4* src = g_halo + cta * 128 + lane;
          hk0 = __ldcg(src); hk1 = __ldcg(src + 32); hv0 = __ldcg(src + 64); hv1 = __ldcg(src + 96);
        }
        if (gidx != 0) PROF(18);
        sts128(sb + OFF_KH + lane * 16, hk0.x, hk0.y, hk0.z, hk0.w);
        sts128(sb + OFF_KH + 512 + lane * 16, hk1.x, hk1.y, hk1.z, hk1.w);
        sts64(sb + OFF_KH + 1024 + lane * 8, movm(hv0.x), movm(hv0.y));
        sts64(sb + OFF_KH + 1280 + lane * 8, movm(hv0.z), movm(hv0.w));
        sts64(sb + OFF_KH + 1536 + lane * 8, movm(hv1.x), movm(hv1.y));
        sts64(sb + OFF_KH + 1792 + lane * 8, movm(hv1.z), movm(hv1.w));
        __syncwarp();
        if (lane == 0) mbar_arrive(bars + 8 * BAR_HALO);
      }
      if (QORD == 2) q_issue(0);
      if (QORD >= 1) q_issue(1);
      const uint32_t rb = mapa(bars, lane & 1);
      nb_sync(NB_OREADY, 288);
      if (lane == 0) {
        asm volatile("cp.async.bulk.global.shared::cta.bulk_group [%0], [%1], %2;\n" ::"l"(g_o + (size_t)cta * 16384),
                     "r"(sb + OFF_OP), "r"(32768) : "memory");
        bulk_commit();
      }
      if (lane < 2) {
#pragma unroll
        for (int i = 0; i < 4; i++) mbar_arrive_cluster(rb + 8 * (BAR_EMPTY2 + i + i / 2));
      }
      if (lane == 0) {
        bulk_wait0();
        st_release(g_flag_o + cta, epoch);
      }
      __syncwarp();
      PROF2(17);
      if (lane < 2) mbar_arrive_cluster(rb + 8 * (BAR_EMPTY2 + 2));
      }
      if (MODE != 1) {
        const __nv_bfloat16* osrc = g_o + (size_t)(rb2 >> 1) * 16 * 16384 + hsel * 8192;
        mbar_wait(bars + 8 * (BAR_EMPTY2 + 1), 0);
        if (elect_one()) {
          if (MODE == 0) {
            asm volatile("cp.async.bulk.shared::cluster.shared::cta.mbarrier::complete_tx::bytes [%0], [%1], %2, [%3];\n"
                         ::"r"(mapa(sb + g2_a(1, hsel), rank ^ 1)), "r"(sb + g2_a(0, hsel)), "r"(16384),
                         "r"(mapa(bars + 8 * (BAR_FULL2 + 1), rank ^ 1)) : "memory");
          } else {
            bulk_load(sb + g2_a(0, hsel), osrc + hp * 16384, 16384, bars + 8 * BAR_FULL2);
            bulk_load(sb + g2_a(1, hsel), osrc + (hp ^ 1) * 16384, 16384, bars + 8 * (BAR_FULL2 + 1));
          }
        }
        __syncwarp();
        int s = 3, ph = 0;
#pragma unroll 1
        for (int kb = 3; kb < 16; kb++) {
          mbar_wait(bars + 8 * (MODE == 0 && kb < 5 ? BAR_XFREE + kb - 3 : BAR_EMPTY2 + s), ph);
          if (elect_one()) g2_issue_b(kb, s);
          __syncwarp();
          if (++s == NS2) { s = 0; ph ^= 1; }
        }
      }
      __syncwarp();
    } else {
      if (MODE != 2) {
      const float dall = __bfloat162float(p.ssm_D[chb * 8 + lr]);
      {
        const int g = lane >> 2, t = lane & 3;
        uint32_t w[2][4];
#pragma unroll
        for (int h = 0; h < 2; h++) {
          const uint2 x = __ldg(reinterpret_cast<const uint2*>(p.shift_k + ((chb & ~1) * 8 + h * 8 + g) * 4));
          w[h][0] = __byte_perm(x.x, x.x, 0x1010);
          w[h][1] = __byte_perm(x.x, x.x, 0x3232);
          w[h][2] = __byte_perm(x.y, x.y, 0x1010);
          w[h][3] = __byte_perm(x.y, x.y, 0x3232);
        }
        auto swz = [](int r) { return (((r & 29) | ((r ^ (r >> 2)) & 2)) << 5) | (r & 16); };
        const uint32_t kring = sb + OFF_X + 4096 + (hw - 1) * 2 * XT, vring = kring + XT;
        const int s0 = rank * 32 + (hw - 1) * 11, s1 = hw == 3 ? rank * 32 + 32 : s0 + 11;
        const size_t goff = (size_t)(lane >> 1) * DM + (chb & ~1) * 8 + (lane & 1) * 8;
        const __nv_bfloat16* kg = p.k + goff;
        const __nv_bfloat16* vg = p.v + goff;
        const uint32_t d0 = swz(lane >> 1) ^ ((lane & 1) << 4), d1 = swz(16 + (lane >> 1)) ^ ((lane & 1) << 4);
        auto issue = [&](int st) {
          const uint32_t so = (st & 3) << 10;
          cp_async16(kring + so + d0, kg + (size_t)st * 32 * DM, 16);
          cp_async16(kring + so + d1, kg + (size_t)(st * 32 + 16) * DM, 16);
          cp_async16(vring + so + d0, vg + (size_t)st * 32 * DM, 16);
          cp_async16(vring + so + d1, vg + (size_t)(st * 32 + 16) * DM, 16);
        };
        const int xa = 8 * (lr >> 1) + 2 * lm + (lr & 1), xb = 8 * (lr >> 1) - 4 + 2 * (lm & 1) + (lr & 1);
        const uint32_t la = swz(xa), lb = swz(xb & 31);
        const int backb = xb < 0 ? 1 : 0;
        const uint32_t ud[2] = {mapa(sb + OFF_X + g * XT + t * 16, 0), mapa(sb + OFF_X + g * XT + t * 16, 1)};
        const uint32_t ub[2] = {mapa(bars + 8 * BAR_U, 0), mapa(bars + 8 * BAR_U, 1)};
        if (tid == 320) prefetch_l2(g_tab + (chb & 63) * 32);
        if (lane == 0) mbar_wait(bars + 8 * (BAR_FULLB + NS1B - 1), 0);
        __syncwarp();
        if (lane >= 24) cp_async16(kring + (((s0 - 1) & 3) << 10) + d1, s0 > 0 ? kg + (size_t)(s0 * 32 - 16) * DM : kg, s0 > 0 ? 16 : 0);
        issue(s0);
        asm volatile("cp.async.commit_group;\n" ::: "memory");
        issue(s0 + 1);
        asm volatile("cp.async.commit_group;\n" ::: "memory");
        uint32_t tn = (uint32_t)clock();
#pragma unroll 1
        for (int st = s0; st < s1; st++) {
          tn += PSTEP;
          while ((int)((uint32_t)clock() - tn) < 0) __nanosleep(100);
          if (st + 2 < s1) issue(st + 2);
          if (hw == 1 && (unsigned)(st - s0 - HPF0) < 8u) prefetch_l2(p.ssm_k + (size_t)(chb * 8 + st - s0 - HPF0) * SEQ + lane * 64);
          asm volatile("cp.async.commit_group;\n" ::: "memory");
          asm volatile("cp.async.wait_group 2;\n" ::: "memory");
          __syncwarp();
#pragma unroll
          for (int h = 0; h < 2; h++) {
            uint32_t e[6], vv[4], e4[4];
            ldsm4t(e4, kring + ((st & 3) << 10) + (la ^ (h << 4)));
            ldsm2t(e[0], e[1], kring + (((st - backb) & 3) << 10) + (lb ^ (h << 4)));
            ldsm4t(vv, vring + ((st & 3) << 10) + (la ^ (h << 4)));
            e[2] = e4[0]; e[3] = e4[1]; e[4] = e4[2]; e[5] = e4[3];
            uint32_t o[5];
#pragma unroll
            for (int i = 0; i < 5; i++) o[i] = __byte_perm(e[i], e[i + 1], 0x5432);
#pragma unroll
            for (int i = 0; i < 4; i++) {
              uint32_t a = bmul2(o[i], w[h][3]);
              a = bfma2(e[i + 1], w[h][2], a);
              a = bfma2(o[i + 1], w[h][1], a);
              a = bfma2(e[i + 2], w[h][0], a);
              vv[i] = bmul2(a, vv[i]);
            }
            st_async128(ud[h] + (st ^ (g & 1)) * 64, ub[h], vv[0], vv[1], vv[2], vv[3]);
          }
          __syncwarp();
        }
        fence_async_smem();
        PROF(16);
      }
      nb_sync(NB_HELP3, 96);
      if (hw == 1 && elect_one()) {
        mbar_expect_tx(bars + 8 * BAR_H, 8 * 4096);
#pragma unroll 1
        for (int c = 0; c < 8; c++)
          bulk_load(sb + OFF_X + c * XT + 4096, p.ssm_k + (size_t)(chb * 8 + c) * SEQ, 4096, bars + 8 * BAR_H);
        mbar_expect_tx(bars + 8 * BAR_X, 6144);
        bulk_load(sb + OFF_T16, g_tab, 2048, bars + 8 * BAR_X);
        bulk_load(sb + OFF_T32, g_tab + 512, 4096, bars + 8 * BAR_X);
      }
      __syncwarp();
      {
        const int ck = 16 * (lane >> 4) + 2 * lr + (((lane >> 3) ^ (lane >> 2)) & 1);
        const uint32_t xo = (ck >> 1) * 128, xs = ((ck & 1) ^ lr) << 4;
#pragma unroll 1
        for (int job = hw - 1; job < 16; job += 3) {
          const int c = job & 7;
          uint4 a[8];
          float dv = __shfl_sync(0xffffffffu, dall, c);
          if (job < 8 || lane) dv = 0.f;
          if (job >= PF0 && job < PF1) prefetch_l2((job < 8 ? p.q + (size_t)chb * 16384 : p.wo + (size_t)chb * 8192) + c * 2048 + lane * 64);
          const uint32_t xt = sb + OFF_X + c * XT + (job >> 3) * 4096;
          mbar_wait(bars + 8 * (job < 8 ? BAR_U : BAR_H), 0);
#pragma unroll
          for (int i = 0; i < 8; i++) a[i] = lds128(xt + i * 512 + ((ck ^ (job < 8 ? (c & 1) << 2 : 0)) << 4));
          dv += bf_lo(a[0].x);
          uint32_t m[4] = {bmaxabs2(a[0].x, pack_bf16(dv, 0.f)), a[0].y, a[0].z, a[0].w};
#pragma unroll
          for (int i = 1; i < 8; i++) {
            m[0] = bmaxabs2(m[0], a[i].x); m[1] = bmaxabs2(m[1], a[i].y);
            m[2] = bmaxabs2(m[2], a[i].z); m[3] = bmaxabs2(m[3], a[i].w);
          }
          m[0] = bmaxabs2(bmaxabs2(m[0], m[1]), bmaxabs2(m[2], m[3]));
          const int f = max(252 - (int)(__reduce_max_sync(0xffffffffu, max(m[0] & 0x7fffu, (m[0] >> 16) & 0x7fffu)) >> 7), 1);
          if (lane == 0) asm volatile("st.shared.u32 [%0], %1;\n" ::"r"(sb + OFF_EX + job * 4), "r"(f) : "memory");
          if (f < 113) {
#pragma unroll
            for (int i = 0; i < 8; i++)
              a[i] = make_uint4(bmul2(a[i].x, f * 0x00800080u), bmul2(a[i].y, f * 0x00800080u), bmul2(a[i].z, f * 0x00800080u),
                                bmul2(a[i].w, f * 0x00800080u));
          }
          const uint32_t mul = (f < 113 ? 15 : f - 112) * 0x00800080u;
          auto cv = [&](uint32_t x) {
            x = bmul2(x, mul);
            return (x & 0x0fff0fffu) * 7 + x;
          };
          const uint32_t dst = xt + xo;
#pragma unroll
          for (int i = 0; i < 8; i++)
            sts128(dst + (i & 1) * 2048 + (xs ^ ((i >> 1) << 5)),
                   i ? cv(a[i].x) : __byte_perm(pack_f16(dv * __uint_as_float(f << 23), 0.f), cv(a[i].x), 0x7610), cv(a[i].y),
                   cv(a[i].z), cv(a[i].w));
        }
        fence_async_smem();
        __syncwarp();
        if (lane == 0) mbar_arrive(bars + 8 * BAR_X);
        PROF(19);
      }
      if (hw < 3) {
        const uint32_t peer = mapa(sb, rank ^ 1);
#pragma unroll 1
        for (int n = 0; n < SPIN_LIMIT && !mbar_try(bars + 8 * (BAR_Y + hw * 4 - 4), 0); n++) __nanosleep(200);
#pragma unroll 1
        for (int ch = hw * 4 - 4; ch < hw * 4; ch++) {
          const uint32_t o = OFF_X + ch * XT + (rank ^ 1) * 4096;
          uint4 a[4];
          mbar_wait(bars + 8 * (BAR_Y + ch), 0);
#pragma unroll
          for (int i = 0; i < 4; i++) a[i] = lds128(sb + o + (i >> 1) * 2048 + (i & 1) * 512 + lane * 16);
#pragma unroll
          for (int i = 0; i < 4; i++)
            st_async128(peer + o + 1024 + (i >> 1) * 2048 + (i & 1) * 512 + lane * 16, peer + OFF_BAR + 8 * BAR_LAND, a[i].x,
                        a[i].y, a[i].z, a[i].w);
          if (ch & 1) {
            fence_async_smem();
            __syncwarp();
            if (lane == 0) mbar_arrive(bars + 8 * (BAR_XFREE + ((ch >> 1) & 1)));
          }
        }
      }
      PROF(32);
      }
      if (MODE != 1 && hw == 3) {
        const uint32_t epoch = ld_relaxed(g_flag_o + cta) + 1;
        if (MODE == 0) nb_sync(NB_G1END, 288);
        if (BDEL) __nanosleep(BDEL);
        if (elect_one()) {
#pragma unroll
          for (int kb = 0; kb < 3; kb++) g2_issue_b(kb, kb);
        }
        __syncwarp();
        const __nv_bfloat16* osrc = g_o + (size_t)(rb2 >> 1) * 16 * 16384 + hsel * 8192;
        if (MODE == 0) __nanosleep(POLL0);
        const uint32_t* flag = g_flag_o + (rb2 >> 1) * 16 + g2_k(lane & 15);
        uint32_t ready = MODE == 0 ? 0u : ~0u;
        int s = 2, ph = 0;
#pragma unroll 1
        for (int kb = 2; kb < 16; kb++) {
          if (!(ready >> kb & 1)) {
#pragma unroll 1
            for (int n = 0; n < SPIN_LIMIT && !(ready >> kb & 1); n++)
              ready = __ballot_sync(0xffffffffu, ld_acquire(flag) == epoch);
            fence_async_all();
          }
          if (kb == 2) PROF(21);
          mbar_wait(bars + 8 * (BAR_EMPTY2 + s), ph);
          if (MODE == 0 && kb == 4 && rank == 1) mbar_wait(bars + 8 * BAR_TAB, 0);
          if (elect_one()) {
            asm volatile(
                "cp.async.bulk.shared::cluster.global.mbarrier::complete_tx::bytes.multicast::cluster [%0], [%1], %2, [%3], %4;\n"
                ::"r"(sb + g2_a(s, hsel) + rank * 8192), "l"(osrc + rank * 4096 + (uint32_t)g2_k(kb) * 16384), "r"(8192),
                "r"(bars + 8 * (BAR_FULL2 + s)), "h"((uint16_t)3) : "memory");
          }
          __syncwarp();
          if (++s == NS2) { s = 0; ph ^= 1; }
        }
      }
    }
    cluster_sync_all();
    PROF_DUMP();
  } else {
    asm volatile("setmaxnreg.inc.sync.aligned.u32 %0;\n" :: "n"(REG_MATH));
    if (warp == 0) PROF2(26);
    const int wg = warp >> 2;
    const int wtid = tid & 127;
    const bool signaller = (wtid == 0) || (wtid == 32);
    const uint32_t rbars = mapa(bars, wtid >> 5 & 1);

    if (halo_cta) {
      const uint32_t epoch = ld_relaxed(g_flag_h + blockIdx.x) + 1;
      float acc0[64], acc1[64];
      int s = 0, ph = 0;
#pragma unroll 1
      for (int kb = 0; kb < 16; kb++) {
        mbar_wait(bars + 8 * (BAR_FULLB + s), ph);
        const uint32_t st = sb + s * STGH;
        const uint64_t da = mkdesc(st, 16, 1024, 1);
        const uint64_t db = mkdesc(st + 8192 + wg * 32768, 8192, 1024, 1);
        wg_fence();
#pragma unroll
        for (int kk = 0; kk < 4; kk++) {
          wgmma_n128(acc0, da + 2 * kk, db + 128 * kk, kb + kk);
          wgmma_n128(acc1, da + 2 * kk, db + 1024 + 128 * kk, kb + kk);
        }
        wg_commit();
        wg_wait<0>();
        if (kb == 15) PROF(37);
        if (wtid == 0) mbar_arrive(bars + 8 * (BAR_EMPTYB + s));
        if (++s == 3) { s = 0; ph ^= 1; }
      }
      fence_regs(acc0);
      fence_regs(acc1);
      if ((warp & 3) != 3) {
#pragma unroll
        for (int hh = 0; hh < 2; hh++) {
          uint4* dst = g_halo + ((hh * 4 + (warp & 3) + 1) * 16 + blockIdx.x * 4) * 128 + wg * 64 + lane;
#pragma unroll
          for (int j = 0; j < 4; j++) {
            const int o = 16 * j + 2 * hh;
            dst[(j >> 1) * 128 + (j & 1) * 32] =
                make_uint4(pack_bf16(acc0[o], acc0[o + 1]), pack_bf16(acc0[o + 4], acc0[o + 5]),
                           pack_bf16(acc0[o + 8], acc0[o + 9]), pack_bf16(acc0[o + 12], acc0[o + 13]));
            dst[(2 + (j >> 1)) * 128 + (j & 1) * 32] =
                make_uint4(pack_bf16(acc1[o], acc1[o + 1]), pack_bf16(acc1[o + 4], acc1[o + 5]),
                           pack_bf16(acc1[o + 8], acc1[o + 9]), pack_bf16(acc1[o + 12], acc1[o + 13]));
          }
        }
      }
      nb_sync(NB_G1DONE, 256);
      if (tid == 0) st_release(g_flag_h + blockIdx.x, epoch);
      PROF(36);
      cluster_sync_all();
      return;
    }

    if (MODE != 2) {
    uint32_t a1[2][4], sc[4];
    C2 t[2];
    {
      float acc0[96], acc1[96];
      int sa = 0, pha = 0, sbb = 0, phb = 0;
      asm volatile("cp.async.wait_group 0;\n" ::: "memory");
      fence_async_smem();
      nb_sync(NB_FIRST, 256);
      if (tid == 0) {
        mbar_arrive(bars + 8 * BAR_FULLA);
        mbar_arrive(bars + 8 * BAR_FULLB);
      }
      PROF(0 + wg);
#pragma unroll 1
      for (int kb = 0; kb < 30; kb++) {
        if (!(kb & 1)) mbar_wait(bars + 8 * (BAR_FULLA + sa), pha);
        mbar_wait(bars + 8 * (BAR_FULLB + sbb), phb);
        if (kb == 0) PROF2(0 + wg);
        if (kb == 4 && wg == 0) PROF2(28);
        if (kb == 8 && wg == 0) PROF2(29);
        if (kb == 16 && wg == 0) PROF2(30);
        const uint64_t da = mkdesc(sb + sa * STG1A + wg * 16384 + (kb & 1) * 64, 16, 2048, 1);
        const uint64_t db = mkdesc(sb + OFF_1B + sbb * STG1B, 4096, 1024, 1);
        wg_fence();
        wgmma_n192(acc0, da + 64, db, kb);
        wgmma_n192(acc1, da, db, kb);
        wgmma_n192(acc0, da + 66, db + 128, 1);
        wgmma_n192(acc1, da + 2, db + 128, 1);
        wg_commit();
        wg_wait<1>();
        if (kb > 0) {
          if (wtid == 64) mbar_arrive(bars + 8 * (BAR_EMPTYB + (sbb == 0 ? NS1B - 1 : sbb - 1)));
          if (!(kb & 1) && signaller) mbar_arrive_cluster(rbars + 8 * (BAR_EMPTYA + (sa == 0 ? NS1A - 1 : sa - 1)));
        }
        if (++sbb == NS1B) { sbb = 0; phb ^= 1; }
        if ((kb & 1) && ++sa == NS1A) { sa = 0; pha ^= 1; }
      }
      const int lr = lane & 7, lm = lane >> 3;
      const bool le0 = 2 * (lane & 3) <= (lane >> 2), le1 = 2 * (lane & 3) + 1 <= (lane >> 2);
      const uint32_t maskLE = (le0 ? 0x0000FFFFu : 0u) | (le1 ? 0xFFFF0000u : 0u);
      uint32_t q[4][8], k[5][8], vt[5][8];
      {
        static_assert(15 % NS1A == 0 && 30 % NS1B == 0, "slots of the last k blocks");
        asm volatile("ld.global.nc.v4.u32 {%0,%1,%2,%3}, [%4];\n"
                     : "=r"(t[0].r), "=r"(t[1].r), "=r"(t[0].i), "=r"(t[1].i) : "l"(g_tab + 1536 + wtid * 4));
        mbar_wait(bars + 8 * BAR_FULLA, 1);
        mbar_wait(bars + 8 * BAR_FULLB, 0);
        mbar_wait(bars + 8 * (BAR_FULLB + 1), 0);
        mbar_wait(bars + 8 * (BAR_EMPTYA + 1), 0);
        const uint64_t da = mkdesc(sb + wg * 16384, 16, 2048, 1);
        const uint64_t db = mkdesc(sb + OFF_1B, 4096, 1024, 1);
        wg_fence();
#pragma unroll
        for (int i = 0; i < 4; i++) wgmma_n192(acc0, da + 64 + 2 * i, db + (i >> 1) * (STG1B >> 4) + (i & 1) * 128, 1);
        wg_commit();
#pragma unroll
        for (int i = 0; i < 2; i++) wgmma_n192(acc1, da + 2 * i, db + (i >> 1) * (STG1B >> 4) + (i & 1) * 128, 1);
        wg_commit();
        wg_wait<1>();
        fence_regs(acc0);
        PROFA(45, 0);
        attn_pack<8, 1, false>(acc0, k[4]);
        attn_pack<16, 1, true>(acc0, vt[4]);
        const uint32_t kh = sb + (warp == 7 ? OFF_OP + 7 * 4096 : OFF_KH + (warp + 1) * 2048) + lane * 16;
        sts128(kh, k[4][0], k[4][1], k[4][2], k[4][3]);
        sts128(kh + 512, k[4][4], k[4][5], k[4][6], k[4][7]);
#pragma unroll
        for (int i = 0; i < 4; i++) sts64(kh - lane * 8 + 1024 + 256 * i, vt[4][2 * i], vt[4][2 * i + 1]);
#pragma unroll
        for (int i = 2; i < 4; i++) wgmma_n192(acc1, da + 2 * i, db + (i >> 1) * (STG1B >> 4) + (i & 1) * 128, 1);
        wg_commit();
        attn_pack<0, 0, false>(acc0, q[1]);
        attn_pack<0, 1, false>(acc0, q[3]);
        attn_pack<8, 0, false>(acc0, k[2]);
        attn_pack<16, 0, true>(acc0, vt[2]);
        uint32_t z = p.zero;
#pragma unroll
        for (int i = 0; i < 8; i++) z &= q[1][i] & q[3][i];
#pragma unroll
        for (int i = 0; i < 8; i += 2) z &= k[2][i] & k[2][i + 1];
        __syncwarp();
        if (lane == 0) mbar_arrive(bars + 8 * BAR_STG + z);
        wg_wait<0>();
        fence_regs(acc1);
        if (MODE == 0) nb_arrive(NB_G1END, 288);
      }
      PROF(2 + wg);
      mbar_wait(bars + 8 * (warp == 0 ? BAR_HALO : BAR_STG), 0);
      {
        const uint32_t kh = sb + OFF_KH + warp * 2048 + lane * 16;
#pragma unroll
        for (int i = 0; i < 2; i++) {
          const uint4 t = lds128(kh + 512 * i);
          k[0][4 * i] = t.x; k[0][4 * i + 1] = t.y; k[0][4 * i + 2] = t.z; k[0][4 * i + 3] = t.w;
        }
#pragma unroll
        for (int i = 0; i < 4; i++) {
          const uint2 t = lds64(kh - lane * 8 + 1024 + 256 * i);
          vt[0][2 * i] = t.x; vt[0][2 * i + 1] = t.y;
        }
      }
      attn_pack<0, 0, false>(acc1, q[0]);
      attn_pack<0, 1, false>(acc1, q[2]);
      attn_pack<8, 0, false>(acc1, k[1]);
      attn_pack<8, 1, false>(acc1, k[3]);
      {
        float x[8][2];
        uint32_t pp[8];
        const bool first = warp == 0 && gidx == 0;
#pragma unroll
        for (int hd = 0; hd < 2; hd++) {
#pragma unroll
          for (int j = 0; j < 4; j += 2) {
            float s0[4], s1[4], s2[4];
            attn_qk(s2, q[j], q[j + 1], k[j + 2], 4 * hd);
            attn_qk(s1, q[j], q[j + 1], k[j + 1], 4 * hd);
            attn_qk(s0, q[j], q[j + 1], k[j], 4 * hd);
            if (j == 0 && first) s0[0] = s0[1] = -1e9f / 0.17677669529663687f;
            x[2 * j + hd][0] = le0 ? s1[0] : s0[0];
            x[2 * j + hd][1] = le1 ? s1[1] : s0[1];
            x[2 * j + 2 + hd][0] = le0 ? s2[2] : s1[2];
            x[2 * j + 2 + hd][1] = le1 ? s2[3] : s1[3];
          }
        }
        PROFA(40, __float_as_uint(x[1][0] + x[7][1]));
        attn_pack<16, 0, true>(acc1, vt[1]);
        attn_pack<16, 1, true>(acc1, vt[3]);
        quad_softmax<8>(x, pp);
        PROFA(41, pp[1] + pp[7]);
        mbar_wait(bars + 8 * BAR_X, 0);
        ldsm4(a1[0], sb + OFF_T32 + (warp & 3) * 1024 + lane * 16);
        ldsm4(a1[1], sb + OFF_T32 + 512 + (warp & 3) * 1024 + lane * 16);
        {
          const uint4 fh = lds128(sb + OFF_EX + wg * 16), fu = lds128(sb + OFF_EX + 32 + wg * 16);
          auto pw2 = [](uint32_t a, uint32_t b) { return min(max(381 - (int)a - (int)b, 1), 254) * 0x00800080u; };
          sc[0] = pw2(fh.x, fu.x); sc[1] = pw2(fh.y, fu.y); sc[2] = pw2(fh.z, fu.z); sc[3] = pw2(fh.w, fu.w);
        }
        const uint32_t obase = sb + OFF_OP + (warp * 32 + lr) * 128;
#pragma unroll
        for (int n = 0; n < 8; n++) {
          attn_pv(obase + (n >> 1) * 1024 + (((4 * (n & 1) + lm) ^ lr) << 4), vt[n >> 1], vt[(n >> 1) + 1], 4 * (n & 1), pp[n],
                  maskLE);
        }
      }
      PROFA(42, 0);
    }

    {
      const int w = warp & 3;
      const int lr = lane & 7, lm = lane >> 3;
      const uint32_t xb = sb + OFF_X + wg * 4 * XT;
      const uint64_t dc2 = mkdesc(sb + OFF_T16, 512, 128, 0), dc3 = mkdesc(sb + OFF_T16, 128, 512, 0);
      const uint64_t dc4 = mkdesc(sb + OFF_T32, 128, 256, 0);
      const uint64_t dx = mkdesc(xb, 4096, 1024, 1), dz = mkdesc(xb, 2048, 256, 3);
      const uint32_t zs = xb + (w * 16 + (lm & 1) * 8 + lr) * 32 + (((lm >> 1) ^ (lr >> 2)) << 4);
      const uint32_t ys = xb + w * 2048 + (lm >> 1) * 256;
      const uint32_t yx = (lr * 32 + (((lm & 1) ^ (lr >> 2)) << 4)) ^ (rank << 6);
      const bool own = (w >> 1) == rank;
      const uint32_t ybar = mapa(bars, own ? rank ^ 1 : rank) + 8 * (BAR_Y + wg * 4);
      uint32_t d[2][32], pa[2][4][2][4], e[2][4][8], ya[2][2][2][4], v[2][2][8];
      float o[2][16];
      auto rows = [&](int c) {
        fft_rows(d[c & 1], a1, dx + (XT >> 4) * c);
        wg_commit();
      };
      auto cols = [&](int c) {
        const int s = c & 1;
        fence_regs(d[s]);
#pragma unroll
        for (int i = 0; i < 16; i++) {
          const C2 z = crot(C2{d[s][2 * i], d[s][2 * i + 1]}, t[i & 1]);
          pa[s][i >> 2][i & 1][(i >> 1) & 1] = z.r;
          pa[s][i >> 2][i & 1][2 + ((i >> 1) & 1)] = z.i;
        }
        wg_fence();
#pragma unroll
        for (int i = 0; i < 4; i++) fft_cols<0>(e[s][i], pa[s][i], dc2);
        wg_commit();
      };
      auto prod = [&](int c) {
        const int s = c & 1;
#pragma unroll
        for (int i = 0; i < 4; i++) fence_regs(e[s][i]);
#pragma unroll
        for (int j = 0; j < 2; j++) {
          const C2 u0 = cget(e[s][0], j, 0), u1 = cget(e[s][0], j, 1), u2 = cget(e[s][1], j, 0), u3 = cget(e[s][1], j, 1);
          const C2 h0 = cget(e[s][2], j, 0), h1 = cget(e[s][2], j, 1), h2 = cget(e[s][3], j, 0), h3 = cget(e[s][3], j, 1);
          const C2 s0 = cmul(h0, u0), s1 = cfma(h0, u1, cmul(h1, u0)), s2 = cfma(h0, u2, cfma(h2, u0, cmul(h1, u1)));
          const C2 y3 = cfma(h0, u3, cfma(h1, u2, cfma(h2, u1, cfma(h3, u0, C2{s2.i, hneg2(s2.r)}))));
          ya[s][0][j][0] = s0.r;
          ya[s][0][j][1] = hadd2(s1.r, s0.i);
          ya[s][0][j][2] = s0.i;
          ya[s][0][j][3] = hadd2(s1.i, hneg2(s0.r));
          ya[s][1][j][0] = hadd2(s2.r, s1.i);
          ya[s][1][j][1] = y3.r;
          ya[s][1][j][2] = hadd2(s2.i, hneg2(s1.r));
          ya[s][1][j][3] = y3.i;
        }
        wg_fence();
        fft_cols<1>(v[s][0], ya[s][0], dc3);
        fft_cols<1>(v[s][1], ya[s][1], dc3);
        wg_commit();
      };
      auto stage = [&](int c) {
        const int s = c & 1;
        fence_regs(v[s][0]);
        fence_regs(v[s][1]);
#pragma unroll
        for (int b = 0; b < 4; b++) {
          const C2 x0 = cget(v[s][b >> 1], 0, b & 1), x1 = cget(v[s][b >> 1], 1, b & 1);
          const C2 z0 = crot(C2{x0.i, x0.r}, t[0]), z1 = crot(C2{x1.i, x1.r}, t[1]);
          stsm4(zs + c * XT + b * 2048, z0.i, z0.r, z1.i, z1.r);
        }
      };
      auto back = [&](int c) {
        fft_back(o[c & 1], dz + (XT >> 4) * c, dc4);
        wg_commit();
      };
      auto out = [&](int c) {
        float (&r)[16] = o[c & 1];
        fence_regs(r);
#pragma unroll
        for (int i = 0; i < 16; i += 8)
          stsm4t(ys + c * XT + (yx ^ ((c & 1) << 5)) + 64 * i, bmul2(pack_bf16(r[i], r[i + 1]), sc[c]),
                 bmul2(pack_bf16(r[i + 2], r[i + 3]), sc[c]), bmul2(pack_bf16(r[i + 4], r[i + 5]), sc[c]),
                 bmul2(pack_bf16(r[i + 6], r[i + 7]), sc[c]));
        __syncwarp();
        if (lane == 0) {
          mbar_arrive_cluster(ybar + 8 * c);
          if (own) mbar_arrive(bars + 8 * BAR_LAND);
        }
      };
      wg_fence();
      rows(0);
      rows(1);
      fence_async_smem();
      nb_arrive(NB_OREADY, 288);
      PROF(34 + wg);
      wg_wait<1>();
      cols(0);
      wg_wait<1>();
      cols(1);
      rows(2);
      nb_sync(NB_CONV + wg, 128);
      wg_wait<2>();
      prod(0);
      wg_wait<1>();
      cols(2);
      rows(3);
      wg_wait<2>();
      stage(0);
      fence_async_smem();
      prod(1);
      nb_sync(NB_CONV + wg, 128);
      back(0);
      wg_wait<2>();
      cols(3);
      wg_wait<2>();
      stage(1);
      fence_async_smem();
      prod(2);
      nb_sync(NB_CONV + wg, 128);
      back(1);
      wg_wait<2>();
      out(0);
      wg_wait<1>();
      stage(2);
      fence_async_smem();
      prod(3);
      nb_sync(NB_CONV + wg, 128);
      back(2);
      wg_wait<2>();
      out(1);
      wg_wait<1>();
      stage(3);
      fence_async_smem();
      nb_sync(NB_CONV + wg, 128);
      wg_fence();
      back(3);
      wg_wait<1>();
      out(2);
      wg_wait<0>();
      if (lane == 0) mbar_arrive_cluster(mapa(bars, 1) + 8 * BAR_TAB);
      out(3);
      PROF(6 + wg);
      if (wg != g2wg) {
        const int c8 = 2 * lm + (lr & 1), src = (lr >> 1) & 1;
        const uint32_t fa = sb + OFF_X + c8 * XT + rank * 4096 + (src == rank ? 0 : 1024) + w * 128;
        const uint32_t fx = ((lr >> 2) ^ ((lr & 3) << 1) ^ (w & 1)) << 4;
        const uint32_t qa = sb + w * 2048 + (lane >> 3) * 128 + (lane & 2) * 32 + (lane & 4) * 8 + (lane & 1) * 16;
        uint4* og = reinterpret_cast<uint4*>(p.out + (size_t)(rank * 1024 + w * 64 + (lane & 2) * 4 + (lane >> 2)) * (2 * DM) +
                                             (chb & ~1) * 8 + (lane & 1) * 8);
        mbar_wait(bars + 8 * BAR_Q, 0);
        mbar_wait(bars + 8 * BAR_LAND, 0);
        PROF2(33);
#pragma unroll
        for (int i = 0; i < 16; i++) {
          uint32_t y[4];
          const uint4 q = lds128(qa + (i < 8 ? OFF_Q0 : OFF_Q1) + (i & 3) * 512 + ((i >> 2) & 1) * 8192);
          ldsm4t(y, fa + (i >> 3) * 2048 + ((i >> 2) & 1) * 512 + (fx ^ ((i & 3) << 5)));
          if (i) {
#pragma unroll
            for (int n = 0; n < (i < PACE1 ? PACE0 : PACE2); n++) __nanosleep(PACE);
          }
          og[((i >> 2) * 256 + (i & 3) * 16) * (2 * DM / 8)] =
              make_uint4(bmul2(q.x, y[0]), bmul2(q.y, y[1]), bmul2(q.z, y[2]), bmul2(q.w, y[3]));
        }
        PROF(22);
      }
    }
    }

    if (MODE != 1 && wg == g2wg) {
      float acc0[64], acc1[64];
      int s = 0, ph = 0, sprev = 0;
      mbar_wait(bars + 8 * BAR_EMPTY2, 0);
#pragma unroll 1
      for (int kb = 0; kb < 16 - ENDG; kb++) {
        mbar_wait(bars + 8 * (BAR_FULL2 + s), ph);
        if (kb == 0) PROF(8);
        if ((warp & 3) == 0) PROF2(40 + kb);
        const uint64_t da = mkdesc(sb + g2_a(s, hsel), 16, 1024, 1);
        const uint64_t db = mkdesc(sb + g2_b(s, rank), 8192, 1024, 1), dc = db + (g2_bk(s) >> 4);
        wg_fence();
        wgmma_n128(acc0, da, db, kb);
        wgmma_n128(acc1, da + 512, db, kb);
        wgmma_n128(acc0, da + 2, db + 128, 1);
        wgmma_n128(acc1, da + 514, db + 128, 1);
        wg_commit();
        wg_wait<1>();
        if (kb > 0 && kb + NS2 <= 16 && signaller) mbar_arrive_cluster(rbars + 8 * (BAR_EMPTY2 + sprev));
        wgmma_n128(acc0, da + 4, dc, 1);
        wgmma_n128(acc1, da + 516, dc, 1);
        wgmma_n128(acc0, da + 6, dc + 128, 1);
        wgmma_n128(acc1, da + 518, dc + 128, 1);
        wg_commit();
        sprev = s;
        if (++s == NS2) { s = 0; ph ^= 1; }
      }
#pragma unroll
      for (int kb = 16 - ENDG; kb < 16; kb++) {
        mbar_wait(bars + 8 * (BAR_FULL2 + kb % NS2), (kb / NS2) & 1);
        if ((warp & 3) == 0) PROF2(40 + kb);
        const uint64_t da = mkdesc(sb + g2_a(kb % NS2, hsel), 16, 1024, 1);
        const uint64_t db = mkdesc(sb + g2_b(kb % NS2, rank), 8192, 1024, 1);
        wg_fence();
#pragma unroll
        for (int i = 0; i < 4; i++) wgmma_n128(acc0, da + 2 * i, db + 128 * (i & 1) + (i >> 1) * (g2_bk(kb % NS2) >> 4), 1);
        wg_commit();
        if (kb == 16 - ENDG && kb + NS2 <= 16) {
          wg_wait<1>();
          if (signaller) mbar_arrive_cluster(rbars + 8 * (BAR_EMPTY2 + sprev));
        }
      }
      static_assert(ENDG <= NS2, "the last stages stay resident");
      auto second = [&](int i0, int i1) {
#pragma unroll
        for (int i = i0; i < i1; i++) {
          const int st = (16 - ENDG + (i >> 2)) % NS2;
          wgmma_n128(acc1, mkdesc(sb + g2_a(st, hsel) + 8192, 16, 1024, 1) + 2 * (i & 3),
                     mkdesc(sb + g2_b(st, rank), 8192, 1024, 1) + 128 * (i & 1) + ((i >> 1) & 1) * (g2_bk(st) >> 4), 1);
        }
        wg_commit();
      };
      second(0, 4);
      const int lr = lane & 7, lm = lane >> 3;
      const uint32_t wb[2] = {sb + g2_a(1, 0) + (warp & 3) * 2048, sb + g2_a(3, 0) + (warp & 3) * 2048};
      const int orow = (rb2 & 7) * 128 + (warp & 3) * 16;
      auto stage_out = [&](const float (&acc)[64], uint32_t off, int j0, int j1) {
#pragma unroll
        for (int j = j0; j < j1; j += 2) {
          const uint32_t a = wb[j >> 3] + off + (lr + 8 * (lm & 1)) * 128 + ((((j & 7) + (lm >> 1)) ^ lr) << 4);
          stsm4(a, pack_bf16(acc[4 * j], acc[4 * j + 1]), pack_bf16(acc[4 * j + 2], acc[4 * j + 3]),
                pack_bf16(acc[4 * j + 4], acc[4 * j + 5]), pack_bf16(acc[4 * j + 6], acc[4 * j + 7]));
        }
      };
      auto store_tma = [&](uint32_t off, int row) {
        fence_async_smem();
        __syncwarp();
        if (elect_one()) {
          tma_store_3d(&tmOb, wb[0] + off, DM + cb2 * 128, rb2 >> 3, row);
          tma_store_3d(&tmOb, wb[1] + off, DM + cb2 * 128 + 64, rb2 >> 3, row);
          bulk_commit();
        }
      };
      wg_wait<1>();
      fence_regs(acc0);
      PROF(10);
#pragma unroll
      for (int c = 0; c < 4; c++) {
        stage_out(acc0, 0, 4 * c, 4 * c + 4);
        second(4 + ILV * c, 4 + ILV * (c + 1));
      }
      store_tma(0, orow);
      if (4 + 4 * ILV < 4 * ENDG) second(4 + 4 * ILV, 4 * ENDG);
      PROF(12);
      wg_wait<0>();
      fence_regs(acc1);
      PROF(11);
      stage_out(acc1, 8192, 0, 16);
      __syncwarp();
      {
        const int rr = lane >> 4, ck = lane & 7, hf = (lane >> 3) & 1;
        uint4* og = reinterpret_cast<uint4*>(p.out + (size_t)(2 * (orow + 64 + rr) + (rb2 >> 3)) * (2 * DM) + DM + cb2 * 128 + hf * 64 + ck * 8);
        uint4 v[8];
#pragma unroll
        for (int i = 0; i < 8; i++) v[i] = lds128((hf ? wb[1] : wb[0]) + 8192 + (2 * i + rr) * 128 + ((ck ^ ((2 * i + rr) & 7)) << 4));
#pragma unroll
        for (int i = 0; i < 8; i++) og[(size_t)i * 4 * (2 * DM / 8)] = v[i];
      }
      PROF(13);
      bulk_wait0();
    }
    cluster_sync_all();
  }
}

typedef CUresult (*EncodeFn)(CUtensorMap*, CUtensorMapDataType, cuuint32_t, void*, const cuuint64_t*, const cuuint64_t*,
                             const cuuint32_t*, const cuuint32_t*, CUtensorMapInterleave, CUtensorMapSwizzle,
                             CUtensorMapL2promotion, CUtensorMapFloatOOBfill);

void make_map(EncodeFn enc, CUtensorMap* tm, const void* base, int rank, const cuuint64_t* dims, const cuuint64_t* strides,
              const cuuint32_t* box, CUtensorMapSwizzle swz) {
  cuuint32_t es[5] = {1, 1, 1, 1, 1};
  enc(tm, CU_TENSOR_MAP_DATA_TYPE_BFLOAT16, rank, const_cast<void*>(base), dims, strides, box, es,
      CU_TENSOR_MAP_INTERLEAVE_NONE, swz, CU_TENSOR_MAP_L2_PROMOTION_L2_256B, CU_TENSOR_MAP_FLOAT_OOB_FILL_NONE);
}

}

extern "C" void kernel_launch(void* const* d_in, const int* in_sizes, int n_in, void* d_out, int out_size) {
  static EncodeFn enc = nullptr;
  static bool coresident = true;
  if (!enc) {
    void* fn = nullptr;
    cudaDriverEntryPointQueryResult qr;
    cudaGetDriverEntryPoint("cuTensorMapEncodeTiled", &fn, cudaEnableDefault, &qr);
    enc = (EncodeFn)fn;
    cudaFuncSetAttribute(fused_kernel<0>, cudaFuncAttributeMaxDynamicSharedMemorySize, SMEM_BYTES);
    cudaFuncSetAttribute(fused_kernel<1>, cudaFuncAttributeMaxDynamicSharedMemorySize, SMEM_BYTES);
    cudaFuncSetAttribute(fused_kernel<2>, cudaFuncAttributeMaxDynamicSharedMemorySize, SMEM_BYTES);
    cudaLaunchConfig_t cfg = {};
    cfg.gridDim = dim3(NCTA);
    cfg.blockDim = dim3(NTHREADS);
    cfg.dynamicSmemBytes = SMEM_BYTES;
    cudaLaunchAttribute at;
    at.id = cudaLaunchAttributeClusterDimension;
    at.val.clusterDim.x = 2;
    at.val.clusterDim.y = 1;
    at.val.clusterDim.z = 1;
    cfg.attrs = &at;
    cfg.numAttrs = 1;
    int nclusters = 0;
    if (cudaOccupancyMaxActiveClusters(&nclusters, fused_kernel<0>, &cfg) == cudaSuccess) coresident = nclusters >= NCTA / 2;
    (void)cudaGetLastError();
  }
  CUtensorMap tmX, tmW, tmWo, tmWp, tmQ, tmOb, tmXh, tmWh;
  {
    cuuint64_t dims[3] = {1024, 2, 1024};
    cuuint64_t str[2] = {2048, 4096};
    cuuint32_t box[3] = {64, 1, 128};
    make_map(enc, &tmX, d_in[6], 3, dims, str, box, CU_TENSOR_MAP_SWIZZLE_128B);
  }
  {
    cuuint64_t dims[3] = {1024, 1024, 3};
    cuuint64_t str[2] = {6144, 2048};
    cuuint32_t box[3] = {64, 32, 3};
    make_map(enc, &tmW, d_in[7], 3, dims, str, box, CU_TENSOR_MAP_SWIZZLE_128B);
  }
  {
    cuuint64_t dims[3] = {64, 1024, 16};
    cuuint64_t str[2] = {2048, 128};
    cuuint32_t box[3] = {64, 64, 2};
    cuuint32_t piece[3] = {64, 32, 1};
    make_map(enc, &tmWo, d_in[8], 3, dims, str, box, CU_TENSOR_MAP_SWIZZLE_128B);
    make_map(enc, &tmWp, d_in[8], 3, dims, str, piece, CU_TENSOR_MAP_SWIZZLE_128B);
  }
  {
    cuuint64_t dims[5] = {1024, 2, 2, 4, 128};
    cuuint64_t str[4] = {2048, 8 * 2048, 2 * 2048, 16 * 2048};
    cuuint32_t box[5] = {16, 2, 2, 4, 32};
    make_map(enc, &tmQ, d_in[0], 5, dims, str, box, CU_TENSOR_MAP_SWIZZLE_NONE);
  }
  {
    cuuint64_t dims[3] = {2048, 2, 1024};
    cuuint64_t str[2] = {4096, 8192};
    cuuint32_t box[3] = {64, 1, 16};
    make_map(enc, &tmOb, d_out, 3, dims, str, box, CU_TENSOR_MAP_SWIZZLE_128B);
  }
  {
    cuuint64_t dims[4] = {1024, 256, 2, 4};
    cuuint64_t str[3] = {4096, 2048, 256 * 4096};
    cuuint32_t box[4] = {64, 8, 2, 3};
    make_map(enc, &tmXh, d_in[6], 4, dims, str, box, CU_TENSOR_MAP_SWIZZLE_128B);
  }
  {
    cuuint64_t dims[3] = {64, 1024, 48};
    cuuint64_t str[2] = {6144, 128};
    cuuint32_t box[3] = {64, 64, 4};
    make_map(enc, &tmWh, d_in[7], 3, dims, str, box, CU_TENSOR_MAP_SWIZZLE_128B);
  }
  Params p;
  p.q = (const __nv_bfloat16*)d_in[0];
  p.k = (const __nv_bfloat16*)d_in[1];
  p.v = (const __nv_bfloat16*)d_in[2];
  p.shift_k = (const __nv_bfloat16*)d_in[3];
  p.ssm_k = (const __nv_bfloat16*)d_in[4];
  p.ssm_D = (const __nv_bfloat16*)d_in[5];
  p.x = (const __nv_bfloat16*)d_in[6];
  p.w = (const __nv_bfloat16*)d_in[7];
  p.wo = (const __nv_bfloat16*)d_in[8];
  p.out = (__nv_bfloat16*)d_out;
  p.zero = 0;
  if (coresident) {
    fused_kernel<0><<<NCTA, NTHREADS, SMEM_BYTES>>>(p, tmX, tmW, tmWo, tmWp, tmQ, tmOb, tmXh, tmWh);
  } else {
    fused_kernel<0><<<4, NTHREADS, SMEM_BYTES>>>(p, tmX, tmW, tmWo, tmWp, tmQ, tmOb, tmXh, tmWh);
    fused_kernel<1><<<NCTA, NTHREADS, SMEM_BYTES>>>(p, tmX, tmW, tmWo, tmWp, tmQ, tmOb, tmXh, tmWh);
    fused_kernel<2><<<NCTA, NTHREADS, SMEM_BYTES>>>(p, tmX, tmW, tmWo, tmWp, tmQ, tmOb, tmXh, tmWh);
  }
}
```

```cpp
#include <cuda_runtime.h>
#include <cuda.h>
#include <cuda_bf16.h>
#include <stdint.h>

namespace {

constexpr int SEQ = 2048;
constexpr int DM = 1024;
constexpr int NCTA = 132;
constexpr int NTHREADS = 384;

constexpr int STG1A = 32768;
constexpr int NS1A = 3;
constexpr int STG1B = 12288;
constexpr int NS1B = 5;
constexpr int OFF_1B = NS1A * STG1A;
constexpr int STG2 = 32768;
constexpr int NS2 = 5;
#define POLL0 1500
#define QORD 1
#define BDEL 0
#define XPF 0
#define HPF0 3
#define PF0 8
#define PF1 12
#define PSTEP 1150
#define FPACE 195
#define LEADWG 1
#define LEADKB 15
#define OTMA 1
#define ENDG 5
__device__ __forceinline__ uint32_t g2_a(int s, int hsel) { return (((0x97524 >> (4 * s)) & 15) ^ (s & 5 ? 0 : hsel)) << 14; }
constexpr int OFF_Q0 = 3 << 14, OFF_Q1 = 8 << 14;
constexpr int STGH = 73728;
constexpr int OFF_KH = 1 * STG2;
constexpr int OFF_OP = 2 * STG2;
constexpr int OFF_T32 = 5 * STG2 - 4096;
constexpr int OFF_X = 5 * STG2;
constexpr int XT = 8192;
__device__ __forceinline__ uint32_t g2_b(int s, int rank) {
  return s < 3 ? (s == 2 ? 6 : s) << 14 : OFF_X + (s - 3) * 2 * XT + (rank ^ 1) * 4096;
}
__device__ __forceinline__ uint32_t g2_bk(int s) { return s < 3 ? 4096 : 4 * XT; }
constexpr int OFF_BAR = OFF_X + 8 * XT;
constexpr int OFF_EX = OFF_BAR + 448;
constexpr int OFF_T16 = 230400;
constexpr int SMEM_BYTES = OFF_T16 + 2048;
static_assert(OFF_1B + NS1B * STG1B <= OFF_T32 && OFF_X % 1024 == 0, "layout");
static_assert(3 * STGH <= OFF_BAR && OFF_EX + 64 <= OFF_T16 && SMEM_BYTES <= 232448, "smem");

constexpr int BAR_FULLA = 0;
constexpr int BAR_EMPTYA = 3;
constexpr int BAR_FULLB = 6;
constexpr int BAR_EMPTYB = 11;
constexpr int BAR_FULL2 = 16;
constexpr int BAR_EMPTY2 = 21;
constexpr int BAR_X = 26;
constexpr int BAR_LAND = 27;
constexpr int BAR_TAB = 28;
constexpr int BAR_U = 29;
constexpr int BAR_H = 30;
constexpr int BAR_STG = 31;
constexpr int BAR_Y = 32;
constexpr int BAR_HALO = 40;
constexpr int BAR_Q = 41;
constexpr int BAR_XFREE = 42;

constexpr int NB_G1DONE = 1;
constexpr int NB_LEAD = 2;
constexpr int NB_G1END = 3;
constexpr int NB_OREADY = 4;
constexpr int NB_CONV = 5;
constexpr int NB_HELP3 = 11;
constexpr int NB_FIRST = 13;

#define REG_MATH 224
#define REG_HELP 56
constexpr int SPIN_LIMIT = 1 << 20;

__device__ __align__(1024) __nv_bfloat16 g_o[SEQ * DM];
__device__ uint32_t g_flag_o[128];
__device__ uint32_t g_flag_h[4];
__device__ uint4 g_halo[128 * 128];
__device__ __align__(128) const uint32_t g_tab[2048] = {
  0x2fd93000,0x2ea72f64,0x2c722da8,0x263e2a1f,0x2ea73000,0xa63e2a1f,0xafd9ada8,0xac72af64,0x2c723000,0xafd9aa1f,0x263eada8,0x2ea72f64,
  0x263e3000,0xac72af64,0x2ea72da8,0xafd9aa1f,0xa63e3000,0x2c72af64,0xaea72da8,0x2fd9aa1f,0xac723000,0x2fd9aa1f,0xa63eada8,0xaea72f64,
  0xaea73000,0x263e2a1f,0x2fd9ada8,0x2c72af64,0xafd93000,0xaea72f64,0xac722da8,0xa63e2a1f,0x263e0000,0x2c722a1f,0x2ea72da8,0x2fd92f64,
  0x2c720000,0x2fd92f64,0x263e2da8,0xaea7aa1f,0x2ea70000,0x263e2f64,0xafd9ada8,0x2c72aa1f,0x2fd90000,0xaea72a1f,0x2c72ada8,0xa63e2f64,
  0x2fd90000,0xaea7aa1f,0x2c722da8,0xa63eaf64,0x2ea70000,0x263eaf64,0xafd92da8,0x2c722a1f,0x2c720000,0x2fd9af64,0x263eada8,0xaea72a1f,
  0x263e0000,0x2c72aa1f,0x2ea7ada8,0x2fd9af64,0xafd93000,0xaea72f64,0xac722da8,0xa63e2a1f,0xaea73000,0x263e2a1f,0x2fd9ada8,0x2c72af64,
  0xac723000,0x2fd9aa1f,0xa63eada8,0xaea72f64,0xa63e3000,0x2c72af64,0xaea72da8,0x2fd9aa1f,0x263e3000,0xac72af64,0x2ea72da8,0xafd9aa1f,
  0x2c723000,0xafd9aa1f,0x263eada8,0x2ea72f64,0x2ea73000,0xa63e2a1f,0xafd9ada8,0xac72af64,0x2fd93000,0x2ea72f64,0x2c722da8,0x263e2a1f,
  0xa63e0000,0xac722a1f,0xaea72da8,0xafd92f64,0xac720000,0xafd92f64,0xa63e2da8,0x2ea7aa1f,0xaea70000,0xa63e2f64,0x2fd9ada8,0xac72aa1f,
  0xafd90000,0x2ea72a1f,0xac72ada8,0x263e2f64,0xafd90000,0x2ea7aa1f,0xac722da8,0x263eaf64,0xaea70000,0xa63eaf64,0x2fd92da8,0xac722a1f,
  0xac720000,0xafd9af64,0xa63eada8,0x2ea72a1f,0xa63e0000,0xac72aa1f,0xaea7ada8,0xafd9af64,0xa63e0000,0xac72aa1f,0xaea7ada8,0xafd9af64,
  0xac720000,0xafd9af64,0xa63eada8,0x2ea72a1f,0xaea70000,0xa63eaf64,0x2fd92da8,0xac722a1f,0xafd90000,0x2ea7aa1f,0xac722da8,0x263eaf64,
  0xafd90000,0x2ea72a1f,0xac72ada8,0x263e2f64,0xaea70000,0xa63e2f64,0x2fd9ada8,0xac72aa1f,0xac720000,0xafd92f64,0xa63e2da8,0x2ea7aa1f,
  0xa63e0000,0xac722a1f,0xaea72da8,0xafd92f64,0x2fd93000,0x2ea72f64,0x2c722da8,0x263e2a1f,0x2ea73000,0xa63e2a1f,0xafd9ada8,0xac72af64,
  0x2c723000,0xafd9aa1f,0x263eada8,0x2ea72f64,0x263e3000,0xac72af64,0x2ea72da8,0xafd9aa1f,0xa63e3000,0x2c72af64,0xaea72da8,0x2fd9aa1f,
  0xac723000,0x2fd9aa1f,0xa63eada8,0xaea72f64,0xaea73000,0x263e2a1f,0x2fd9ada8,0x2c72af64,0xafd93000,0xaea72f64,0xac722da8,0xa63e2a1f,
  0x263e0000,0x2c72aa1f,0x2ea7ada8,0x2fd9af64,0x2c720000,0x2fd9af64,0x263eada8,0xaea72a1f,0x2ea70000,0x263eaf64,0xafd92da8,0x2c722a1f,
  0x2fd90000,0xaea7aa1f,0x2c722da8,0xa63eaf64,0x2fd90000,0xaea72a1f,0x2c72ada8,0xa63e2f64,0x2ea70000,0x263e2f64,0xafd9ada8,0x2c72aa1f,
  0x2c720000,0x2fd92f64,0x263e2da8,0xaea7aa1f,0x263e0000,0x2c722a1f,0x2ea72da8,0x2fd92f64,0xafd93000,0xaea72f64,0xac722da8,0xa63e2a1f,
  0xaea73000,0x263e2a1f,0x2fd9ada8,0x2c72af64,0xac723000,0x2fd9aa1f,0xa63eada8,0xaea72f64,0xa63e3000,0x2c72af64,0xaea72da8,0x2fd9aa1f,
  0x263e3000,0xac72af64,0x2ea72da8,0xafd9aa1f,0x2c723000,0xafd9aa1f,0x263eada8,0x2ea72f64,0x2ea73000,0xa63e2a1f,0xafd9ada8,0xac72af64,
  0x2fd93000,0x2ea72f64,0x2c722da8,0x263e2a1f,0xa63e0000,0xac72aa1f,0xaea7ada8,0xafd9af64,0x2c720000,0x2fd92f64,0x263e2da8,0xaea7aa1f,
  0xaea70000,0xa63eaf64,0x2fd92da8,0xac722a1f,0x2fd90000,0xaea72a1f,0x2c72ada8,0xa63e2f64,0xafd90000,0x2ea72a1f,0xac72ada8,0x263e2f64,
  0x2ea70000,0x263eaf64,0xafd92da8,0x2c722a1f,0xac720000,0xafd92f64,0xa63e2da8,0x2ea7aa1f,0x263e0000,0x2c72aa1f,0x2ea7ada8,0x2fd9af64,
  0x2fd93000,0x2ea72f64,0x2c722da8,0x263e2a1f,0xaea7b000,0x263eaa1f,0x2fd92da8,0x2c722f64,0x2c723000,0xafd9aa1f,0x263eada8,0x2ea72f64,
  0xa63eb000,0x2c722f64,0xaea7ada8,0x2fd92a1f,0xa63e3000,0x2c72af64,0xaea72da8,0x2fd9aa1f,0x2c72b000,0xafd92a1f,0x263e2da8,0x2ea7af64,
  0xaea73000,0x263e2a1f,0x2fd9ada8,0x2c72af64,0x2fd9b000,0x2ea7af64,0x2c72ada8,0x263eaa1f,0x263e0000,0x2c72aa1f,0x2ea7ada8,0x2fd9af64,
  0xac720000,0xafd92f64,0xa63e2da8,0x2ea7aa1f,0x2ea70000,0x263eaf64,0xafd92da8,0x2c722a1f,0xafd90000,0x2ea72a1f,0xac72ada8,0x263e2f64,
  0x2fd90000,0xaea72a1f,0x2c72ada8,0xa63e2f64,0xaea70000,0xa63eaf64,0x2fd92da8,0xac722a1f,0x2c720000,0x2fd92f64,0x263e2da8,0xaea7aa1f,
  0xa63e0000,0xac72aa1f,0xaea7ada8,0xafd9af64,0xafd93000,0xaea72f64,0xac722da8,0xa63e2a1f,0x2ea7b000,0xa63eaa1f,0xafd92da8,0xac722f64,
  0xac723000,0x2fd9aa1f,0xa63eada8,0xaea72f64,0x263eb000,0xac722f64,0x2ea7ada8,0xafd92a1f,0x263e3000,0xac72af64,0x2ea72da8,0xafd9aa1f,
  0xac72b000,0x2fd92a1f,0xa63e2da8,0xaea7af64,0x2ea73000,0xa63e2a1f,0xafd9ada8,0xac72af64,0xafd9b000,0xaea7af64,0xac72ada8,0xa63eaa1f,
  0xafd9b000,0xaea7af64,0xac72ada8,0xa63eaa1f,0x2ea73000,0xa63e2a1f,0xafd9ada8,0xac72af64,0xac72b000,0x2fd92a1f,0xa63e2da8,0xaea7af64,
  0x263e3000,0xac72af64,0x2ea72da8,0xafd9aa1f,0x263eb000,0xac722f64,0x2ea7ada8,0xafd92a1f,0xac723000,0x2fd9aa1f,0xa63eada8,0xaea72f64,
  0x2ea7b000,0xa63eaa1f,0xafd92da8,0xac722f64,0xafd93000,0xaea72f64,0xac722da8,0xa63e2a1f,0xa63e0000,0xac72aa1f,0xaea7ada8,0xafd9af64,
  0x2c720000,0x2fd92f64,0x263e2da8,0xaea7aa1f,0xaea70000,0xa63eaf64,0x2fd92da8,0xac722a1f,0x2fd90000,0xaea72a1f,0x2c72ada8,0xa63e2f64,
  0xafd90000,0x2ea72a1f,0xac72ada8,0x263e2f64,0x2ea70000,0x263eaf64,0xafd92da8,0x2c722a1f,0xac720000,0xafd92f64,0xa63e2da8,0x2ea7aa1f,
  0x263e0000,0x2c72aa1f,0x2ea7ada8,0x2fd9af64,0x2fd9b000,0x2ea7af64,0x2c72ada8,0x263eaa1f,0xaea73000,0x263e2a1f,0x2fd9ada8,0x2c72af64,
  0x2c72b000,0xafd92a1f,0x263e2da8,0x2ea7af64,0xa63e3000,0x2c72af64,0xaea72da8,0x2fd9aa1f,0xa63eb000,0x2c722f64,0xaea7ada8,0x2fd92a1f,
  0x2c723000,0xafd9aa1f,0x263eada8,0x2ea72f64,0xaea7b000,0x263eaa1f,0x2fd92da8,0x2c722f64,0x2fd93000,0x2ea72f64,0x2c722da8,0x263e2a1f,
  0x263e0000,0x2c72aa1f,0x2ea7ada8,0x2fd9af64,0xac720000,0xafd92f64,0xa63e2da8,0x2ea7aa1f,0x2ea70000,0x263eaf64,0xafd92da8,0x2c722a1f,
  0xafd90000,0x2ea72a1f,0xac72ada8,0x263e2f64,0x2fd90000,0xaea72a1f,0x2c72ada8,0xa63e2f64,0xaea70000,0xa63eaf64,0x2fd92da8,0xac722a1f,
  0x2c720000,0x2fd92f64,0x263e2da8,0xaea7aa1f,0xa63e0000,0xac72aa1f,0xaea7ada8,0xafd9af64,0x316c2fbd,0x343e32f7,0x35bc34ff,0x372c3676,
  0x371532c6,0x3a81392e,0x3bef3b71,0x3b7c3bf2,0x397034cf,0x3bfc3b6c,0x38b23b04,0xb40e31e8,0x3ae13631,0x39e73bf5,0xb6e83219,0xbbe8bb13,
  0x3bc23785,0x30be3aa9,0xbbfdb911,0x2a16b9aa,0x3bfe3865,0xb80f37a6,0xb82abc00,0x3bfd376f,0x3b9238fd,0xbb7f2311,0x3805b929,0x31223bde,
  0x3a85398b,0xbb96b742,0x3bff319e,0xbbb82f8b,0xbbe2bbf1,0xbbb7bbcf,0xbb78bb9a,0xbb27bb52,0xbb2cbbd2,0xb8a8ba19,0xb029b5df,0x35a52f59,
  0xb9dfbba1,0x2ba7b5f7,0x3a7a37b2,0x3bbd3bdd,0xb815bb60,0x39662e91,0x3b373bda,0xb0d7377a,0xb3d3bb10,0x3be9386f,0x2a7a3a31,0xbbfeb9a6,
  0x294dbab0,0x3ae53b07,0xbad51fdb,0xab43bb16,0x352fba41,0x35993c00,0xbaebba1d,0x3be531cf,0x38a3b9c5,0xb5173b21,0x2776bbe0,0x34323bf2,
  0x384537dd,0x38ea3899,0x39823937,0x3a0d39c9,0x39463a93,0x3340374e,0xb426a452,0xb979b7c8,0xbb45b924,0xbb32bc00,0xb371b902,0x38d63294,
  0xb08db9a1,0x3b3f379b,0x39583bd7,0xb8252dfb,0x3bea3a2d,0xb3ba3874,0xbb89bb0d,0x36d2b625,0xb6bb387f,0xb8d1bbf5,0x3be73602,0xb546391f,
  0xba00bb01,0x3bff35eb,0xba5c34db,0x3359bab6,0x3ac7b66b,0xb9413933,0x368dbabd,0xb0103bb3,0xbac4baf7,0xba50ba8c,0xb9cdba11,0xb93cb986,
  0x3a04388e,0x3bcb3b1e,0x3bba3c00,0x39d63afe,0x36af3a21,0xb6ffa17f,0xbbc8ba3d,0xba60bbd4,0xbbebb9af,0xb6c6bb0a,0x39f43263,0x3ad83bf7,
  0x30a6b916,0x3bc33aa5,0xb55e3790,0xbb3dbb63,0x3b423a9e,0xba642ec3,0xb0f0bb6a,0x3b8e3a25,0xb94a37bd,0x2884bb6f,0x38db3b9f,0xbbc9b85a,
  0xb840bb54,0x3a093a15,0xbb4cb850,0x3bef3457,0x3a893a4d,0x3af43ac1,0x3b4f3b24,0x3b983b76,0xbb94baba,0xbbe4bbf9,0xba58bb57,0xb699b8f8,
  0x3bfe3b18,0x394f3b5c,0xb109347b,0xbae8b884,0xbbc0bb68,0xa9b1b90c,0x3b8b387a,0x38bc3ba5,0x3ade3ba7,0xb8c1324b,0xb9f0bbf6,0x39eb9648,
  0xb96bbbd6,0x3bbf3487,0xb38939b3,0xb9f8bba3,0x370a3bf3,0xbb47b994,0x3bbc2d65,0xb8ad3889,0xb153bc00,0x37213b9c,0xb97dba90,0x3af138f3,
  0xb89eb8ee,0xb7e8b84a,0xb682b737,0xb50bb5c8,0x35233855,0xb13b2d33,0xb8e0b65f,0xbb4aba45,0xa8e8b764,0x39fc3648,0x3be63bae,0x380a3a9b,
  0xb3eb360e,0xbbfeba35,0xb552baa2,0x3a7334b7,0x381ab4ab,0x3a6f3bd8,0xb95d2e5f,0xb962bc00,0xb9e3327c,0xb402bbac,0x3bc6399d,0xb95434c3,
  0x3b2faf27,0xb6a439bc,0xb41abbf9,0x3a7e3a97,0xbbe3251b,0x3b2ab4f3,0xb9d23894,0x37f3ba49,0x3bce3bb5,0x3bf03be1,0x3bff3bfa,0x3bfb3bff,
  0x2c38b1b6,0x383a34e7,0x3aee39c0,0x3bff3bb2,0xbb81bbf8,0xb53ab999,0x38302ef5,0x3bed3ab3,0xb8cc9cb6,0xbb85bbab,0x2adeb86a,0x3bc5391b,
  0x38c73bf6,0xbadbb232,0xb6ddbba9,0x3b87361a,0x3b833201,0xb0743a39,0xba76bb5e,0x3b352dc9,0xac06bbb0,0x39743b59,0xbbeeb759,0x3aceb2ad,
  0xbbccb5d4,0x3bfb2d00,0xbb7a32de,0x3a54b7d2,0xb30fb44b,0xafefb185,0xa6adacce,0x2c9c25e4,0xbbfcbbdf,0xbacbbb9e,0xb7feb990,0xa81fb463,
  0xb58d2d97,0xbb90b9b8,0xbad1bbf4,0xb05bb85f,0x3a673c00,0xb5763493,0xbbfdbaac,0xb3a2ba29,0x3a6b2e2d,0x38203bd9,0xbb3ab49f,0xb56abb65,
  0xb581bbdc,0x3bec3907,0xb8b7363c,0xb6f4bbf8,0xbbfcb46f,0x39dab654,0xb0423b1b,0xb835bbd3,0xb3283b73,0xac6abbfa,0x35b13bd0,0xb8e5bafb,
  0x38ee3a0d,0xb84aba89,0x37373af4,0xb5c8bb4f,0x35df3a81,0x2f59bbef,0xb88e3b7c,0x3b1eb946,0x2d973ae8,0x39b8bb81,0xbbf4353a,0x385f3830,
  0xb2633b3f,0x3bf7b958,0xb60eb825,0xba353bc0,0xb7853b87,0x3aa9b3d3,0x3911bbe9,0xb9aa2a7a,0xb99d3bbf,0x34c33389,0x3bdcb9f8,0x3907bb83,
  0xbb013be5,0xb5eb394a,0x34db2884,0x3ab6b8db,0xbbd03bfb,0xbafb3b7a,0xb98b3a54,0xb74238a3,0x3a4db93c,0xbac1389e,0x3b24b7e8,0xbb763682,
  0x3b71b8a8,0xbbf23029,0x3a9335a5,0xb74eba04,0x3bf8b80a,0xb999b58d,0xaef53b90,0x3ab3bad1,0x3bd7b6c6,0xadfbb9f4,0xbb683ad8,0x390c33eb,
  0x3b10b56a,0x386fbbc2,0xba3130be,0xb9a63bfd,0x39b3b402,0x3ba3bbc6,0x3201b954,0xba393581,0x37bdb122,0x3b6fba00,0x3b9fbbff,0x385aba5c,
  0x32deac6a,0x37d2b5b1,0x39c5b8e5,0x3b21ba85,0x344b3b98,0xb185bbce,0x2cce3bf0,0x25e4bbff,0xbc003340,0x3afe3426,0xb855b979,0x2d333b94,
  0x34cfbbed,0xbb6c39df,0x3b042ba7,0xb1e8ba7a,0x3aa2a9b1,0x34b7bb8b,0xbc0038bc,0x349338cc,0xba2d3bfe,0x387430a6,0x3b0dbbc3,0xb625b55e,
  0xb63cb074,0xbbf83a76,0xb8653b35,0x37a6294d,0x3bf3bbc9,0x3994bb2f,0x2d65b6a4,0xb889341a,0xb19e3517,0x2f8b2776,0x366bb432,0x3933b840,
  0x3bb5b50b,0xbbe1330f,0x3bfaafef,0xbbff26ad,0xa4523bcb,0x37c8bbba,0xbaba39d6,0x3bf9b523,0xbba1305b,0x35f73970,0x37b2bbfc,0xbbdd38b2,
  0x387abbfe,0xbba53552,0x9cb63a73,0x3babba67,0x39162a16,0x3aa5bbea,0xb790b3ba,0xbb633b89,0xbb5e3bec,0xadc938b7,0x3ab0b6f4,0x3b07bbfe,
  0xaf27b359,0xb9bc370a,0xbbf93b47,0xba973bbc,0x3be0bb96,0x3bf2bbff,0x3b54bbb8,0x3a15bac7,0xafbd3bfb,0x32f7bbe2,0xb4ff3bb7,0x3676bb78,
  0x365fbbe4,0xba453a58,0x3bdfb699,0xbb9eac38,0xb9243bbd,0x3c00b6af,0xb902b6ff,0xb2943bc8,0x3aacbb85,0xba29aade,0xb6313bc5,0x3bf5b815,
  0xbba73b3d,0x324b381a,0x3bf6ba6f,0x9648b95d,0x3c00bae5,0x376fbad5,0xb87f2b43,0xbbf53b42,0xbbb03a7e,0xbb593bfc,0xb75939da,0x32ad3042,
  0x3abdba09,0x3bb3bb4c,0x3c00bbef,0x3b9cbbe3,0x3bf12c9c,0xbbcfb16c,0x3b9a343e,0xbb52b5bc,0xbb57b13b,0x38f838e0,0xb1b6bb4a,0xb4e73bfc,
  0x3a21340e,0x217fbb45,0xba3d3b32,0x3bd4b371,0xb86ab576,0xb91b3bfd,0x3b60b3a2,0x2e91bae1,0x34ab36d2,0x3bd8bade,0xae5fb8c1,0xbc0039f0,
  0x9fdbb80f,0xbb16382a,0xba9e3bfd,0x2ec336bb,0xb46f38ad,0x3654ac06,0x3b1bb974,0x3bd3bbee,0x3850b941,0x3457b68d,0xa51bb010,0xb4f33153,
  0xb7dd3b27,0x3899bac4,0xb9373a50,0x39c9b9cd,0x3990383a,0xb463baee,0xb2c63bff,0x392ebb2c,0x3b18ba60,0xbb5c28e8,0x347b39fc,0x3884bbe6,
  0xb219b966,0xbb133b37,0x39a130d7,0x379bbbeb,0xbbf63962,0xb2323a6b,0x3ba9b820,0x361abb3a,0xb6023a64,0x391fb0f0,0x3bd6bb8e,0x3487b9e3,
  0x3a41b835,0x3c00bb92,0x3a1dbb7f,0x31cfb805,0x3a90bb2a,0x38f3b9d2,0x35d4b7f3,0x2d00b328,0x3af7372c,0xba8cb845,0x3a1138ea,0xb986b982,
  0x39c0bacb,0xbbb237fe,0x3bd2a81f,0xba19b715,0xb764b8d6,0xb6483bfe,0x3baeb94f,0xba9bb109,0xbbda39e7,0x377a36e8,0x39afbbe8,0xbb0a308d,
  0xae2d39eb,0x3bd9b8c7,0x349fbadb,0xbb6536dd,0x3b6ab8d1,0x3a25bbe7,0xb27cb546,0xbbac396b,0x38fdbace,0xa311b52f,0xb9293599,0xbbde3aeb,
  0xb8943721,0xba49397d,0xbb733af1,0xbbfa3bcc,0xbbfb3bff,0xbbe23bf1,0xbbb73bcf,0xbb783b9a,0xbb7c3bf2,0xb9463a93,0xb340374e,0x3426a452,
  0xba603bd4,0xa8e83764,0x39fcb648,0x3be6bbae,0xb8bc3ba5,0x38cc9cb6,0x3b85bbab,0xaadeb86a,0xb56a3b65,0x3bc2b785,0x30bebaa9,0xbbfd3911,
  0xab433b16,0x3b42ba9e,0xba64aec3,0xb0f03b6a,0x33593ab6,0x370abbf3,0xbb473994,0x3bbcad65,0x37f33a49,0xb328bb73,0xac6a3bfa,0x35b1bbd0,
  0xac9c25e4,0xb16c2fbd,0xb43e32f7,0xb5bc34ff,0xb5a52f59,0xba04388e,0xbbcb3b1e,0xbbba3c00,0xb8d63294,0xbbfe3b18,0xb94f3b5c,0x3109347b,
  0xba7334b7,0xba673c00,0x35763493,0x3bfdbaac,0xbb87361a,0xb3d33b10,0x3be9b86f,0x2a7aba31,0xbbfd376f,0x36bb387f,0x38d1bbf5,0xbbe73602,
  0xbbc9385a,0x3b2f2f27,0xb6a4b9bc,0xb41a3bf9,0xbaf138f3,0x3bccb5d4,0xbbfb2d00,0x3b7a32de,0xbb273b52,0xbac43af7,0xba503a8c,0xb9cd3a11,
  0x3979b7c8,0x3b94baba,0x3be4bbf9,0x3a58bb57,0x380aba9b,0xb58dad97,0xbb9039b8,0xbad13bf4,0xbbc5391b,0xb8153b60,0x3966ae91,0x3b37bbda,
  0x2a1639aa,0x3beaba2d,0xb3bab874,0xbb893b0d,0x3b8eba25,0xb9e3b27c,0xb4023bac,0x3bc6b99d,0xb8adb889,0xac063bb0,0x3974bb59,0xbbee3759,
  0xb8e53afb,0x3a85b98b,0xbb963742,0x3bffb19e,0xb72c3676,0xb84537dd,0xb8ea3899,0xb9823937,0xb9d63afe,0xb5233855,0x313b2d33,0x38e0b65f,
  0x3ae8b884,0x3b81bbf8,0x353ab999,0xb8302ef5,0x33a2ba29,0xbae13631,0xb9e73bf5,0x36e83219,0xbbfe39a6,0x30a63916,0x3bc3baa5,0xb55eb790,
  0x3546391f,0x396bbbd6,0xbbbf3487,0x338939b3,0x3a7eba97,0xbbfc346f,0x39da3654,0xb042bb1b,0xba54b7d2,0x38a339c5,0xb517bb21,0x27763be0,
  0xb93c3986,0xb89e38ee,0xb7e8384a,0xb6823737,0x3699b8f8,0xac38b1b6,0xb83a34e7,0xbaee39c0,0xb05b385f,0x3970b4cf,0x3bfcbb6c,0x38b2bb04,
  0xb0d7b77a,0xbbeb39af,0xb6c63b0a,0x39f4b263,0x36d23625,0x3adebba7,0xb8c1b24b,0xb9f03bf6,0xb954b4c3,0xb5813bdc,0x3becb907,0xb8b7b63c,
  0x3ace32ad,0xb52fba41,0xb5993c00,0x3aebba1d,0xbbb8af8b,0x3ac7366b,0xb941b933,0x368d3abd,0xba0d39c9,0xba893a4d,0xbaf43ac1,0xbb4f3b24,
  0x3b4aba45,0x3bfcbbdf,0x3acbbb9e,0x37feb990,0xbbed3ab3,0xb9df3ba1,0x2ba735f7,0x3a7ab7b2,0x3be8bb13,0x308db9a1,0xbb3f379b,0xb9583bd7,
  0xbb3d3b63,0x381a34ab,0x3a6fbbd8,0xb95dae5f,0x39f8bba3,0xbb833201,0x30743a39,0x3a76bb5e,0xb8353bd3,0x3b92b8fd,0xbb7fa311,0x38053929,
  0x3432bbf2,0xb8403b54,0x3a09ba15,0xbb4c3850,0xb50b35c8,0xb30f344b,0xafef3185,0xa6ad2cce,0xbbff3bb2,0xbb2c3bd2,0xb8a83a19,0xb02935df,
  0xb40eb1e8,0xbb453924,0xbb323c00,0xb3713902,0x3ad8bbf7,0xb3ebb60e,0xbbfe3a35,0xb5523aa2,0x39eb1648,0x38c7bbf6,0xbadb3232,0xb6dd3ba9,
  0xb6f43bf8,0x3bfeb865,0xb80fb7a6,0xb82a3c00,0xbbe531cf,0x394a37bd,0xa884bb6f,0xb8db3b9f,0xb010bbb3,0xb1533c00,0x3721bb9c,0xb97d3a90,
  0xbb983b76,0xbbce3bb5,0xbbf03be1,0xbbff3bfa,0x281fb463,0xb71532c6,0xba81392e,0xbbef3b71,0x3bbdbbdd,0x36afba21,0xb6ff217f,0xbbc83a3d,
  0x38252dfb,0x3bc0bb68,0x29b1b90c,0xbb8b387a,0xb9623c00,0x3a6bae2d,0x3820bbd9,0xbb3a349f,0xbb352dc9,0x294d3ab0,0x3ae5bb07,0xbad59fdb,
  0x3122bbde,0xba003b01,0x3bffb5eb,0xba5cb4db,0x3befb457,0xbbe3a51b,0x3b2a34f3,0xb9d2b894,0x39c939cd,0xba4db93c,0x3ac1389e,0xbb24b7e8,
  0x3b1e3946,0xbc00b340,0x3afeb426,0xb8553979,0x3bdd38b2,0xba21340e,0xa17fbb45,0x3a3d3b32,0x3bf53815,0xb2193966,0xbb13bb37,0x39a1b0d7,
  0x3b6536dd,0x37853b87,0xbaa9b3d3,0xb911bbe9,0x3a393581,0x3b5e3bec,0x2dc938b7,0xbab0b6f4,0x3889341a,0x3bb03a7e,0x3b593bfc,0x375939da,
  0x34f33153,0x38943721,0x3a49397d,0x3b733af1,0xb9863982,0x38eeba0d,0xb84a3a89,0x3737baf4,0xb74e3a04,0xa452bbcb,0x37c83bba,0xbabab9d6,
  0xb1e83a7a,0xb924bbbd,0x3c0036af,0xb90236ff,0x2e913ae1,0xbbdab9e7,0x377ab6e8,0x39af3be8,0x361a3b3a,0xbb10b56a,0xb86fbbc2,0x3a3130be,
  0x39073b83,0xb63c3074,0xbbf8ba76,0xb865bb35,0x3a973bbc,0x346f38ad,0xb654ac06,0xbb1bb974,0x3b9c3be3,0x3a903b2a,0x38f339d2,0x35d437f3,
  0x3b763682,0xbbb5b50b,0x3be1330f,0xbbfaafef,0x2d33bb94,0x365f3be4,0xba45ba58,0x3bdf3699,0xbbd4b371,0x3764b8d6,0x36483bfe,0xbbaeb94f,
  0x379b3beb,0xbbd7b6c6,0x2dfbb9f4,0x3b683ad8,0x39aa2a7a,0x3a2d3bfe,0xb87430a6,0xbb0dbbc3,0xbb07bbfe,0x1fdbb80f,0x3b16382a,0x3a9e3bfd,
  0xb2ad3042,0xba41b835,0xbc00bb92,0xba1dbb7f,0x3bfa3bcc,0x3bd03bfb,0x3afb3b7a,0x398b3a54,0xb5c83b4f,0x344bbb98,0xb1853bce,0x2ccebbf0,
  0x3bf93523,0xbb57313b,0x38f8b8e0,0xb1b63b4a,0xb294bbc8,0x3b183a60,0xbb5ca8e8,0x347bb9fc,0xbb0ab08d,0xb263bb3f,0x3bf73958,0xb60e3825,
  0x39a63bfd,0xb9162a16,0xbaa5bbea,0x3790b3ba,0x37a6a94d,0x3c003ae5,0x376f3ad5,0xb87fab43,0xbbd3bbee,0xb8fdbace,0x2311b52f,0x39293599,
  0x2d003328,0xb2deac6a,0xb7d2b5b1,0xb9c5b8e5,0x3bff26ad,0xbbf12c9c,0x3bcfb16c,0xbb9a343e,0xbb9e2c38,0x3990b83a,0xb4633aee,0xb2c6bbff,
  0x3a9bb109,0xad973ae8,0xb9b8bb81,0x3bf4353a,0xb90c33eb,0xb87abbfe,0x3ba53552,0x1cb63a73,0x3625b55e,0x3ba73b3d,0xb24b381a,0xbbf6ba6f,
  0xaec336bb,0xbb6ab8d1,0xba25bbe7,0x327cb546,0xb1cfb805,0x37bd3122,0x3b6f3a00,0x3b9f3bff,0x374238a3,0x319e3517,0xaf8b2776,0xb66bb432,
  0x25e43bff,0xafbdbbfb,0x32f73be2,0xb4ffbbb7,0xb4e7bbfc,0x39c03acb,0xbbb2b7fe,0x3bd2281f,0x38843be6,0xbbf8b80a,0x3999b58d,0x2ef53b90,
  0xba35bbc0,0x3aa229b1,0x34b73b8b,0xbc00b8bc,0x3b633b89,0xb4ab36d2,0xbbd8bade,0x2e5fb8c1,0xbbf5bb42,0xb602ba64,0x391f30f0,0x3bd63b8e,
  0x3bde3aeb,0x3b013be5,0x35eb394a,0xb4db2884,0xbb21ba85,0xbbe0bb96,0xbbf2bbff,0xbb54bbb8,0x3b52b5bc,0xbaf7372c,0x3a8cb845,0xba1138ea,
  0x392e3b2c,0xbb71b8a8,0x3bf23029,0xba9335a5,0xb85f3830,0xb4cfbbed,0x3b6c39df,0xbb042ba7,0xbbabba67,0x386ab576,0x391b3bfd,0xbb60b3a2,
  0x1648b95d,0x3bf63962,0x32323a6b,0xbba9b820,0x3bac396b,0x399d3bbf,0xb4c33389,0xbbdcb9f8,0x385a3a5c,0xaf273359,0xb9bcb70a,0xbbf9bb47,
  0xb933b840,0xbabdba09,0xbbb3bb4c,0xbc00bbef,0x36763b78,0xb7ddbb27,0x38993ac4,0xb937ba50,0xba193715,0x35dfba81,0x2f593bef,0xb88ebb7c,
  0xbab3bad1,0x3ba1305b,0xb5f73970,0xb7b2bbfc,0x3493b8cc,0x3aac3b85,0xba292ade,0xb631bbc5,0x3c0039f0,0x2e2d39eb,0xbbd9b8c7,0xb49fbadb,
  0x348739e3,0xb9b3b402,0xbba3bbc6,0xb201b954,0xbab6b8db,0xbbf3bbc9,0xb994bb2f,0xad65b6a4,0xba15bac7,0xb850b941,0xb457b68d,0x251bb010,
  0xb9cfbb16,0x30ac2a31,0x3b9c3bf1,0xb493ae2d,0xb76fb8b4,0x35a133e3,0x3a1d3afe,0xb902b76f,0xb3e3b5a1,0x38b4376f,0x376f3902,0xbafeba1d,
  0xaa31b0ac,0x3b1639cf,0x2e2d3493,0xbbf1bb9c,0xb956ba74,0x305f29cc,0x3b633bd2,0xb44badc9,0xb6e7b859,0x353f335e,0x39d23ab6,0xb8bcb6ff,
  0xb35eb53f,0x385936e7,0x36ff38bc,0xbab6b9d2,0xa9ccb05f,0x3a743956,0x2dc9344b,0xbbd2bb63,0xb8e3b9de,0x30122967,0x3b1e3ba1,0xb402ad65,
  0xb662b801,0x34de32da,0x39823a67,0xb874b68d,0xb2dab4de,0x38013662,0x368d3874,0xba67b982,0xa967b012,0x39de38e3,0x2d653402,0xbba1bb1e,
  0xb876b952,0x2f8c2902,0x3ace3b60,0xb371ad00,0xb5e1b758,0x347e3257,0x392e3a11,0xb82ab61a,0xb257b47e,0x375835e1,0x361a382a,0xba11b92e,
  0xa902af8c,0x39523876,0x2d003371,0xbb60bace,0xb80db8ce,0x2ef3289e,0x3a733b10,0xb2deac9c,0xb562b6b3,0x342031d5,0x38d639b3,0xb7bdb5a5,
  0xb1d5b420,0x36b33562,0x35a537bd,0xb9b3b8d6,0xa89eaef3,0x38ce380d,0x2c9c32de,0xbb10ba73,0xb750b851,0x2e5a2839,0x3a0d3ab0,0xb24bac38,
  0xb4e5b613,0x33863153,0x387a394f,0xb721b52f,0xb153b386,0x361334e5,0x352f3721,0xb94fb87a,0xa839ae5a,0x38513750,0x2c38324b,0xbab0ba0d,
  0xb68eb7b4,0x2dc227a9,0x399d3a41,0xb1b6aba7,0xb46ab577,0x32cd30d2,0x381a38e5,0xb682b4b7,0xb0d2b2cd,0x3577346a,0x34b73682,0xb8e5b81a,
  0xa7a9adc2,0x37b4368e,0x2ba731b6,0xba41b99d,0xb5d2b6d1,0x2d2a26e0,0x392439c5,0xb122aade,0xb3e3b4de,0x32163052,0x376f3874,0xb5dfb43e,
  0xb052b216,0x34de33e3,0x343e35df,0xb874b76f,0xa6e0ad2a,0x36d135d2,0x2ade3122,0xb9c5b924,0xb51cb5f6,0x2c932617,0x38a3393c,0xb08daa16,
  0xb2f4b448,0x31602fa5,0x36a437fe,0xb53ab389,0xafa5b160,0x344832f4,0x3389353a,0xb7feb6a4,0xa617ac93,0x35f6351c,0x2a16308d,0xb93cb8a3,
  0xb46ab523,0x2bf6254d,0x381a38a8,0xafefa94d,0xb209b36b,0x30ac2ea7,0x35d4370a,0xb493b294,0xaea7b0ac,0x336b3209,0x32943493,0xb70ab5d4,
  0xa54dabf6,0x3523346a,0x294d2fef,0xb8a8b81a,0xb378b456,0x2ac82484,0x3715380a,0xaec3a884,0xb120b24a,0x2ff22da9,0x34ff360e,0xb3d3b19e,
  0xada9aff2,0x324a3120,0x319e33d3,0xb60eb4ff,0xa484aac8,0x34563378,0x28842ec3,0xb80ab715,0xb223b31c,0x29992376,0x35eb36c6,0xad97a776,
  0xb039b12d,0x2e8d2cac,0x3426350b,0xb27cb0a6,0xacacae8d,0x312d3039,0x30a6327c,0xb50bb426,0xa376a999,0x331c3223,0x27762d97,0xb6c6b5eb,
  0xb0d2b194,0x286b21e4,0x34b7356a,0xac6aa5e4,0xaea7b012,0x2d2a2b5f,0x32943402,0xb122af59,0xab5fad2a,0x30122ea7,0x2f593122,0xb402b294,
  0xa1e4a86b,0x319430d2,0x25e42c6a,0xb56ab4b7,0xaf0cb012,0x267b2052,0x32f73402,0xaa7aa452,0xacdeadf5,0x2b912967,0x30d731e8,0xaf8bad65,
  0xa967ab91,0x2df52cde,0x2d652f8b,0xb1e8b0d7,0xa052a67b,0x30122f0c,0x24522a7a,0xb402b2f7,0xac79ad2a,0x24201d7f,0x30743122,0xa81fa17f,
  0xaa31ab91,0x28d026e0,0x2e2d2f8b,0xacceaade,0xa6e0a8d0,0x2b912a31,0x2ade2cce,0xaf8bae2d,0x9d7fa420,0x2d2a2c79,0x217f281f,0xb122b074,
  0xa7a9a86b,0x1f1218b6,0x2ba72c6a,0xa3119cb6,0xa54da67b,0x242021e4,0x294d2a7a,0xa81fa5e4,0xa1e4a420,0x267b254d,0x25e4281f,0xaa7aa94d,
  0x98b69f12,0x286b27a9,0x1cb62311,0xac6aaba7,0x211b21e4,0x98b69248,0xa51ba5e4,0x1cb61648,0x1f122052,0x9d7f9bdb,0xa311a452,0x217f1fdb,
  0x1bdb1d7f,0xa0529f12,0x9fdba17f,0x24522311,0x124818b6,0xa1e4a11b,0x96489cb6,0x25e4251b,0x2a632b5f,0xa1e49bdb,0xae5faf59,0x25e41fdb,
  0x286b2967,0xa6e0a4e9,0xac6aad65,0x2ade28e8,0x24e926e0,0xa967a86b,0xa8e8aade,0x2d652c6a,0x1bdb21e4,0xab5faa63,0x9fdba5e4,0x2f592e5f,
  0x2dc22ea7,0xa54d9f12,0xb1b6b294,0x294d2311,0x2bf62cde,0xaa31a86b,0xafefb0d7,0x2e2d2c6a,0x286b2a31,0xacdeabf6,0xac6aae2d,0x30d72fef,
  0x1f12254d,0xaea7adc2,0xa311a94d,0x329431b6,0x302c30d2,0xa7a9a11b,0xb41ab4b7,0x2ba7251b,0x2dc22f0c,0xac79aa63,0xb1b6b2f7,0x30742e5f,
  0x2a632c79,0xaf0cadc2,0xae5fb074,0x32f731b6,0x211b27a9,0xb0d2b02c,0xa51baba7,0x34b7341a,0x317a3257,0xa902a2ad,0xb552b61a,0x2d0026ad,
  0x2f8c309f,0xaddcac2e,0xb371b487,0x31cf3029,0x2c2e2ddc,0xb09faf8c,0xb029b1cf,0x34873371,0x22ad2902,0xb257b17a,0xa6adad00,0x361a3552,
  0x32cd33e3,0xaa31a420,0xb682b76f,0x2e2d281f,0x30ac31bb,0xaf3fad2a,0xb493b58d,0x33283122,0x2d2a2f3f,0xb1bbb0ac,0xb122b328,0x358d3493,
  0x24202a31,0xb3e3b2cd,0xa81fae2d,0x376f3682,0x341334bc,0xab5fa4e9,0xb7a6b85a,0x2f5928e8,0x319432da,0xb052ae28,0xb56ab68d,0x343e3219,
  0x2e283052,0xb2dab194,0xb219b43e,0x368d356a,0x24e92b5f,0xb4bcb413,0xa8e8af59,0x385a37a6,0x34c3358c,0xac47a5b2,0xb85fb8f3,0x304229b1,
  0x327e33fd,0xb106af26,0xb63cb785,0x34e7330f,0x2f263106,0xb3fdb27e,0xb30fb4e7,0x3785363c,0x25b22c47,0xb58cb4c3,0xa9b1b042,0x38f3385f,
  0x35773662,0xacdea67b,0xb8e5b982,0x30d72a7a,0x336b3493,0xb1bbb012,0xb70ab83a,0x358d3402,0x301231bb,0xb493b36b,0xb402b58d,0x383a370a,
  0x267b2cde,0xb662b577,0xaa7ab0d7,0x398238e5,0x36303741,0xad76a744,0xb962ba04,0x316c2b43,0x342e352a,0xb271b092,0xb7d2b8ad,0x3631347b,
  0x30923271,0xb52ab42e,0xb47bb631,0x38ad37d2,0x27442d76,0xb741b630,0xab43b16c,0x3a043962,0x36ee3815,0xae0ea807,0xb9d6ba7a,0x32012c06,
  0x34a735c4,0xb329b113,0xb84ab91b,0x36d234f3,0x31133329,0xb5c4b4a7,0xb4f3b6d2,0x391b384a,0x28072e0e,0xb815b6ee,0xac06b201,0x3a7a39d6,
  0x37b4388e,0xaea7a86b,0xba41bae1,0x32942c6a,0x35233662,0xb3e3b194,0xb8a8b982,0x376f356a,0x319433e3,0xb662b523,0xb56ab76f,0x398238a8,
  0x286b2ea7,0xb88eb7b4,0xac6ab294,0x3ae13a41,0x3841390f,0xaf3fa8d0,0xbaa2bb3a,0x33282cce,0x35a13705,0xb44fb216,0xb902b9e3,0x380535df,
  0x3216344f,0xb705b5a1,0xb5dfb805,0x39e33902,0x28d02f3f,0xb90fb841,0xacceb328,0x3b3a3aa2,0x38ac3997,0xafd8a935,0xbaf7bb83,0x33ba2d33,
  0x362137ac,0xb4aeb298,0xb958ba3d,0x38503654,0x329834ae,0xb7acb621,0xb654b850,0x3a3d3958,0x29352fd8,0xb997b8ac,0xad33b3ba,0x3b833af7,
  0x391c3a28,0xb039a999,0xbb42bbbc,0x34262d97,0x36a4382d,0xb50eb31c,0xb9aaba90,0x389936c6,0x331c350e,0xb82db6a4,0xb6c6b899,0x3a9039aa,
  0x29993039,0xba28b91c,0xad97b426,0x3bbc3b42,0x39923ac3,0xb085a9fe,0xbb81bbe3,0x346f2dfb,0x372a3886,0xb570b3a0,0xb9f8badb,0x38e03737,
  0x33a03570,0xb886b72a,0xb737b8e0,0x3adb39f8,0x29fe3085,0xbac3b992,0xadfbb46f,0x3be33b81,
};

#define PROF(slot) do {} while (0)
#define PROF_DUMP() do {} while (0)
#define PROFA(slot, dep) do {} while (0)
#define PROF3(slot) do {} while (0)
#define PROF2(slot) do {} while (0)

__device__ __forceinline__ uint32_t smem_u32(const void* p) { return (uint32_t)__cvta_generic_to_shared(p); }

__device__ __forceinline__ void mbar_init(uint32_t a, uint32_t c) {
  asm volatile("mbarrier.init.shared::cta.b64 [%0], %1;\n" ::"r"(a), "r"(c) : "memory");
}
__device__ __forceinline__ void mbar_expect_tx(uint32_t a, uint32_t bytes) {
  asm volatile("mbarrier.arrive.expect_tx.shared::cta.b64 _, [%0], %1;\n" ::"r"(a), "r"(bytes) : "memory");
}
__device__ __forceinline__ void mbar_arrive_cluster(uint32_t cluster_addr) {
  asm volatile("mbarrier.arrive.shared::cluster.b64 _, [%0];\n" ::"r"(cluster_addr) : "memory");
}
__device__ __forceinline__ void mbar_arrive_cluster_n(uint32_t cluster_addr, uint32_t n) {
  asm volatile("mbarrier.arrive.shared::cluster.b64 _, [%0], %1;\n" ::"r"(cluster_addr), "r"(n) : "memory");
}
__device__ __forceinline__ bool mbar_try(uint32_t a, uint32_t parity) {
  uint32_t ok;
  asm volatile("{\n.reg .pred p;\nmbarrier.try_wait.parity.shared::cta.b64 p, [%1], %2;\nselp.u32 %0, 1, 0, p;\n}\n"
               : "=r"(ok) : "r"(a), "r"(parity) : "memory");
  return ok;
}
__device__ __forceinline__ void mbar_wait(uint32_t a, uint32_t parity) {
  if (mbar_try(a, parity)) return;
#pragma unroll 1
  for (int n = 0; n < SPIN_LIMIT; n++)
    if (mbar_try(a, parity)) break;
}
__device__ __forceinline__ bool elect_one() {
  uint32_t p;
  asm volatile("{\n.reg .pred P;\nelect.sync _|P, 0xffffffff;\nselp.u32 %0, 1, 0, P;\n}\n" : "=r"(p));
  return p;
}
__device__ __forceinline__ uint32_t mapa(uint32_t a, uint32_t rank) {
  uint32_t r;
  asm volatile("mapa.shared::cluster.u32 %0, %1, %2;\n" : "=r"(r) : "r"(a), "r"(rank));
  return r;
}
__device__ __forceinline__ void nb_sync(int id, int n) { asm volatile("bar.sync %0, %1;\n" ::"r"(id), "r"(n) : "memory"); }
__device__ __forceinline__ void nb_arrive(int id, int n) { asm volatile("bar.arrive %0, %1;\n" ::"r"(id), "r"(n) : "memory"); }
__device__ __forceinline__ void cluster_sync_all() {
  asm volatile("barrier.cluster.arrive.relaxed.aligned;\nbarrier.cluster.wait.aligned;\n" ::: "memory");
}
__device__ __forceinline__ void fence_async_smem() { asm volatile("fence.proxy.async.shared::cta;\n" ::: "memory"); }
__device__ __forceinline__ void fence_async_all() { asm volatile("fence.proxy.async.global;\n" ::: "memory"); }

__device__ __forceinline__ void tma_load_3d(uint32_t dst, const CUtensorMap* tm, uint32_t bar, int c0, int c1, int c2) {
  asm volatile(
      "cp.async.bulk.tensor.3d.shared::cluster.global.mbarrier::complete_tx::bytes [%0], [%1, {%3, %4, %5}], [%2];\n"
      ::"r"(dst), "l"(tm), "r"(bar), "r"(c0), "r"(c1), "r"(c2) : "memory");
}
__device__ __forceinline__ void tma_load_4d(uint32_t dst, const CUtensorMap* tm, uint32_t bar, int c0, int c1, int c2, int c3) {
  asm volatile(
      "cp.async.bulk.tensor.4d.shared::cluster.global.mbarrier::complete_tx::bytes [%0], [%1, {%3, %4, %5, %6}], [%2];\n"
      ::"r"(dst), "l"(tm), "r"(bar), "r"(c0), "r"(c1), "r"(c2), "r"(c3) : "memory");
}
__device__ __forceinline__ void tma_load_3d_mc(uint32_t dst, const CUtensorMap* tm, uint32_t bar, int c0, int c1, int c2) {
  asm volatile(
      "cp.async.bulk.tensor.3d.shared::cluster.global.mbarrier::complete_tx::bytes.multicast::cluster [%0], [%1, {%3, %4, %5}], [%2], %6;\n"
      ::"r"(dst), "l"(tm), "r"(bar), "r"(c0), "r"(c1), "r"(c2), "h"((uint16_t)3) : "memory");
}
__device__ __forceinline__ void bulk_load(uint32_t dst, const void* src, uint32_t bytes, uint32_t bar) {
  asm volatile("cp.async.bulk.shared::cluster.global.mbarrier::complete_tx::bytes [%0], [%1], %2, [%3];\n"
               ::"r"(dst), "l"(src), "r"(bytes), "r"(bar) : "memory");
}
__device__ __forceinline__ void tma_store_3d(const CUtensorMap* tm, uint32_t src, int c0, int c1, int c2) {
  asm volatile("cp.async.bulk.tensor.3d.global.shared::cta.bulk_group [%0, {%2, %3, %4}], [%1];\n"
               ::"l"(tm), "r"(src), "r"(c0), "r"(c1), "r"(c2) : "memory");
}
__device__ __forceinline__ void bulk_commit() { asm volatile("cp.async.bulk.commit_group;\n" ::: "memory"); }
__device__ __forceinline__ void bulk_wait0() { asm volatile("cp.async.bulk.wait_group 0;\n" ::: "memory"); }
__device__ __forceinline__ void prefetch_tmap(const CUtensorMap* tm) {
  asm volatile("prefetch.tensormap [%0];\n" ::"l"(tm) : "memory");
}

__device__ __forceinline__ void wg_fence() { asm volatile("wgmma.fence.sync.aligned;\n" ::: "memory"); }
__device__ __forceinline__ void wg_commit() { asm volatile("wgmma.commit_group.sync.aligned;\n" ::: "memory"); }
template <int N> __device__ __forceinline__ void wg_wait() {
  asm volatile("wgmma.wait_group.sync.aligned %0;\n" ::"n"(N) : "memory");
}
__device__ __forceinline__ uint64_t mkdesc(uint32_t addr, uint32_t lbo, uint32_t sbo, uint32_t swz) {
  return (uint64_t)((addr & 0x3FFFF) >> 4) | ((uint64_t)(lbo >> 4) << 16) | ((uint64_t)(sbo >> 4) << 32) |
         ((uint64_t)swz << 62);
}

#define R4(d, o) "+f"(d[o + 0]), "+f"(d[o + 1]), "+f"(d[o + 2]), "+f"(d[o + 3])
#define R8(d, o) R4(d, o), R4(d, o + 4)
#define R16(d, o) R8(d, o), R8(d, o + 8)
#define R32(d, o) R16(d, o), R16(d, o + 16)
#define R64(d, o) R32(d, o), R32(d, o + 32)

__device__ __forceinline__ void wgmma_n192(float (&d)[96], uint64_t da, uint64_t db, uint32_t acc) {
  asm volatile(
      "{\n.reg .pred p;\nsetp.ne.u32 p, %98, 0;\n"
      "wgmma.mma_async.sync.aligned.m64n192k16.f32.bf16.bf16 "
      "{%0,%1,%2,%3,%4,%5,%6,%7,%8,%9,%10,%11,%12,%13,%14,%15,%16,%17,%18,%19,%20,%21,%22,%23,%24,%25,%26,%27,%28,%29,%30,%31,"
      "%32,%33,%34,%35,%36,%37,%38,%39,%40,%41,%42,%43,%44,%45,%46,%47,%48,%49,%50,%51,%52,%53,%54,%55,%56,%57,%58,%59,%60,%61,%62,%63,"
      "%64,%65,%66,%67,%68,%69,%70,%71,%72,%73,%74,%75,%76,%77,%78,%79,%80,%81,%82,%83,%84,%85,%86,%87,%88,%89,%90,%91,%92,%93,%94,%95}, "
      "%96, %97, p, 1, 1, 0, 1;\n}\n"
      : R64(d, 0), R32(d, 64)
      : "l"(da), "l"(db), "r"(acc));
}
__device__ __forceinline__ void wgmma_n128(float (&d)[64], uint64_t da, uint64_t db, uint32_t acc) {
  asm volatile(
      "{\n.reg .pred p;\nsetp.ne.u32 p, %66, 0;\n"
      "wgmma.mma_async.sync.aligned.m64n128k16.f32.bf16.bf16 "
      "{%0,%1,%2,%3,%4,%5,%6,%7,%8,%9,%10,%11,%12,%13,%14,%15,%16,%17,%18,%19,%20,%21,%22,%23,%24,%25,%26,%27,%28,%29,%30,%31,"
      "%32,%33,%34,%35,%36,%37,%38,%39,%40,%41,%42,%43,%44,%45,%46,%47,%48,%49,%50,%51,%52,%53,%54,%55,%56,%57,%58,%59,%60,%61,%62,%63}, "
      "%64, %65, p, 1, 1, 0, 1;\n}\n"
      : R64(d, 0)
      : "l"(da), "l"(db), "r"(acc));
}
template <int N> __device__ __forceinline__ void fence_regs(float (&d)[N]) {
#pragma unroll
  for (int i = 0; i < N; i++) asm volatile("" : "+f"(d[i])::"memory");
}

__device__ __forceinline__ void mma16816(float (&d)[4], uint32_t a0, uint32_t a1, uint32_t a2, uint32_t a3, uint32_t b0,
                                         uint32_t b1) {
  asm("mma.sync.aligned.m16n8k16.row.col.f32.bf16.bf16.f32 {%0,%1,%2,%3}, {%4,%5,%6,%7}, {%8,%9}, {%0,%1,%2,%3};\n"
      : "+f"(d[0]), "+f"(d[1]), "+f"(d[2]), "+f"(d[3])
      : "r"(a0), "r"(a1), "r"(a2), "r"(a3), "r"(b0), "r"(b1));
}
__device__ __forceinline__ void mma16816_z(float (&d)[4], uint32_t a0, uint32_t a1, uint32_t a2, uint32_t a3, uint32_t b0,
                                           uint32_t b1) {
  asm("mma.sync.aligned.m16n8k16.row.col.f32.bf16.bf16.f32 {%0,%1,%2,%3}, {%4,%5,%6,%7}, {%8,%9}, {%10,%10,%10,%10};\n"
      : "=f"(d[0]), "=f"(d[1]), "=f"(d[2]), "=f"(d[3])
      : "r"(a0), "r"(a1), "r"(a2), "r"(a3), "r"(b0), "r"(b1), "f"(0.f));
}
__device__ __forceinline__ void ldsm4t(uint32_t (&r)[4], uint32_t a) {
  asm volatile("ldmatrix.sync.aligned.m8n8.x4.trans.shared.b16 {%0,%1,%2,%3}, [%4];\n"
               : "=r"(r[0]), "=r"(r[1]), "=r"(r[2]), "=r"(r[3]) : "r"(a) : "memory");
}
__device__ __forceinline__ void ldsm2t(uint32_t& r0, uint32_t& r1, uint32_t a) {
  asm volatile("ldmatrix.sync.aligned.m8n8.x2.trans.shared.b16 {%0,%1}, [%2];\n" : "=r"(r0), "=r"(r1) : "r"(a) : "memory");
}
__device__ __forceinline__ void st_async128(uint32_t a, uint32_t bar, uint32_t x, uint32_t y, uint32_t z, uint32_t w) {
  asm volatile("st.async.weak.shared::cluster.mbarrier::complete_tx::bytes.v4.b32 [%0], {%2,%3,%4,%5}, [%1];\n"
               ::"r"(a), "r"(bar), "r"(x), "r"(y), "r"(z), "r"(w) : "memory");
}
__device__ __forceinline__ void mbar_arrive(uint32_t a) {
  asm volatile("mbarrier.arrive.shared::cta.b64 _, [%0];\n" ::"r"(a) : "memory");
}
__device__ __forceinline__ void stsm4(uint32_t a, uint32_t r0, uint32_t r1, uint32_t r2, uint32_t r3) {
  asm volatile("stmatrix.sync.aligned.m8n8.x4.shared.b16 [%0], {%1,%2,%3,%4};\n"
               ::"r"(a), "r"(r0), "r"(r1), "r"(r2), "r"(r3) : "memory");
}
__device__ __forceinline__ void stsm4t(uint32_t a, uint32_t r0, uint32_t r1, uint32_t r2, uint32_t r3) {
  asm volatile("stmatrix.sync.aligned.m8n8.x4.trans.shared.b16 [%0], {%1,%2,%3,%4};\n"
               ::"r"(a), "r"(r0), "r"(r1), "r"(r2), "r"(r3) : "memory");
}
__device__ __forceinline__ uint2 lds64(uint32_t a) {
  uint2 v;
  asm volatile("ld.shared.v2.u32 {%0,%1}, [%2];\n" : "=r"(v.x), "=r"(v.y) : "r"(a));
  return v;
}
__device__ __forceinline__ uint4 lds128(uint32_t a) {
  uint4 v;
  asm volatile("ld.shared.v4.u32 {%0,%1,%2,%3}, [%4];\n" : "=r"(v.x), "=r"(v.y), "=r"(v.z), "=r"(v.w) : "r"(a) : "memory");
  return v;
}
__device__ __forceinline__ void sts128(uint32_t a, uint32_t x, uint32_t y, uint32_t z, uint32_t w) {
  asm volatile("st.shared.v4.u32 [%0], {%1,%2,%3,%4};\n" ::"r"(a), "r"(x), "r"(y), "r"(z), "r"(w) : "memory");
}
__device__ __forceinline__ void sts64(uint32_t a, uint32_t x, uint32_t y) {
  asm volatile("st.shared.v2.u32 [%0], {%1,%2};\n" ::"r"(a), "r"(x), "r"(y) : "memory");
}
__device__ __forceinline__ uint32_t pack_bf16(float lo, float hi) {
  uint32_t r;
  asm("cvt.rn.bf16x2.f32 %0, %1, %2;\n" : "=r"(r) : "f"(hi), "f"(lo));
  return r;
}
__device__ __forceinline__ uint32_t bmul2(uint32_t a, uint32_t b) {
  uint32_t r;
  asm("mul.rn.bf16x2 %0, %1, %2;\n" : "=r"(r) : "r"(a), "r"(b));
  return r;
}
__device__ __forceinline__ uint32_t bmax2(uint32_t a, uint32_t b) {
  uint32_t r;
  asm("max.bf16x2 %0, %1, %2;\n" : "=r"(r) : "r"(a), "r"(b));
  return r;
}
__device__ __forceinline__ uint32_t bfma2(uint32_t a, uint32_t b, uint32_t c) {
  uint32_t r;
  asm("fma.rn.bf16x2 %0, %1, %2, %3;\n" : "=r"(r) : "r"(a), "r"(b), "r"(c));
  return r;
}
__device__ __forceinline__ uint32_t badd2(uint32_t a, uint32_t b) {
  uint32_t r;
  asm("add.rn.bf16x2 %0, %1, %2;\n" : "=r"(r) : "r"(a), "r"(b));
  return r;
}
__device__ __forceinline__ void prefetch_l2(const void* p) { asm volatile("prefetch.global.L2 [%0];\n" ::"l"(p)); }
__device__ __forceinline__ void cp_async16n(uint32_t dst, const void* src) {
  asm volatile("cp.async.cg.shared.global [%0], [%1], 16;\n" ::"r"(dst), "l"(src) : "memory");
}
__device__ __forceinline__ void cp_async16(uint32_t dst, const void* src, uint32_t srcbytes) {
  asm volatile("cp.async.cg.shared.global.L2::256B [%0], [%1], 16, %2;\n" ::"r"(dst), "l"(src), "r"(srcbytes) : "memory");
}
__device__ __forceinline__ uint32_t ld_acquire(const uint32_t* p) {
  uint32_t v;
  asm volatile("ld.acquire.gpu.global.u32 %0, [%1];\n" : "=r"(v) : "l"(p) : "memory");
  return v;
}
__device__ __forceinline__ uint32_t ld_relaxed(const uint32_t* p) {
  uint32_t v;
  asm volatile("ld.relaxed.gpu.global.u32 %0, [%1];\n" : "=r"(v) : "l"(p) : "memory");
  return v;
}
__device__ __forceinline__ void st_release(uint32_t* p, uint32_t v) {
  asm volatile("st.release.gpu.global.u32 [%0], %1;\n" ::"l"(p), "r"(v) : "memory");
}
__device__ __forceinline__ void wait_flag(const uint32_t* p, uint32_t want) {
  int n = 0;
  while (ld_acquire(p) != want && ++n < SPIN_LIMIT) {}
}

struct Params {
  const __nv_bfloat16* x;
  const __nv_bfloat16* w;
  const __nv_bfloat16* q;
  const __nv_bfloat16* k;
  const __nv_bfloat16* v;
  const __nv_bfloat16* shift_k;
  const __nv_bfloat16* ssm_k;
  const __nv_bfloat16* ssm_D;
  const __nv_bfloat16* wo;
  __nv_bfloat16* out;
  uint32_t zero;
};

__device__ __forceinline__ uint32_t lds32(uint32_t a) {
  uint32_t v;
  asm volatile("ld.shared.u32 %0, [%1];\n" : "=r"(v) : "r"(a));
  return v;
}
__device__ __forceinline__ float bf_lo(uint32_t v) {
  uint32_t r;
  asm("prmt.b32 %0, %1, 0, 0x1044;\n" : "=r"(r) : "r"(v));
  return __uint_as_float(r);
}
__device__ __forceinline__ float bf_hi(uint32_t v) { return __uint_as_float(v & 0xffff0000u); }
__device__ __forceinline__ float ex2(float x) {
  float r;
  asm("ex2.approx.ftz.f32 %0, %1;\n" : "=f"(r) : "f"(x));
  return r;
}
__device__ __forceinline__ float rcp(float x) {
  float r;
  asm("rcp.approx.ftz.f32 %0, %1;\n" : "=f"(r) : "f"(x));
  return r;
}

#define Q4(c, d, o) c(d[o + 0]), c(d[o + 1]), c(d[o + 2]), c(d[o + 3])
#define Q8(c, d, o) Q4(c, d, o), Q4(c, d, o + 4)
#define Q16(c, d, o) Q8(c, d, o), Q8(c, d, o + 8)
#define Q32(c, d) Q16(c, d, 0), Q16(c, d, 16)
#define L8 "{%0,%1,%2,%3,%4,%5,%6,%7}"
#define L16 "{%0,%1,%2,%3,%4,%5,%6,%7,%8,%9,%10,%11,%12,%13,%14,%15}"
#define L32 "{%0,%1,%2,%3,%4,%5,%6,%7,%8,%9,%10,%11,%12,%13,%14,%15,%16,%17,%18,%19,%20,%21,%22,%23,%24,%25,%26,%27,%28,%29,%30,%31}"
__device__ __forceinline__ void fft_rows(uint32_t (&d)[32], const uint32_t (&a)[2][4], uint64_t db) {
  asm volatile("wgmma.mma_async.sync.aligned.m64n128k16.f16.f16.f16 " L32 ", {%32,%33,%34,%35}, %36, 0, 1, 1, 1;\n"
               : Q32("=r", d) : "r"(a[0][0]), "r"(a[0][1]), "r"(a[0][2]), "r"(a[0][3]), "l"(db));
  asm volatile("wgmma.mma_async.sync.aligned.m64n128k16.f16.f16.f16 " L32 ", {%32,%33,%34,%35}, %36, 1, 1, 1, 1;\n"
               : Q32("+r", d) : "r"(a[1][0]), "r"(a[1][1]), "r"(a[1][2]), "r"(a[1][3]), "l"(db + 128));
}
template <int INV> __device__ __forceinline__ void fft_cols(uint32_t (&d)[8], const uint32_t (&a)[2][4], uint64_t db) {
  asm volatile("wgmma.mma_async.sync.aligned.m64n32k16.f16.f16.f16 " L8 ", {%8,%9,%10,%11}, %12, 0, 1, 1, %13;\n"
               : Q8("=r", d, 0) : "r"(a[0][0]), "r"(a[0][1]), "r"(a[0][2]), "r"(a[0][3]), "l"(db), "n"(INV));
  asm volatile("wgmma.mma_async.sync.aligned.m64n32k16.f16.f16.f16 " L8 ", {%8,%9,%10,%11}, %12, 1, 1, 1, %13;\n"
               : Q8("+r", d, 0) : "r"(a[1][0]), "r"(a[1][1]), "r"(a[1][2]), "r"(a[1][3]), "l"(db + (INV ? 16 : 64)), "n"(INV));
}
__device__ __forceinline__ void fft_back(float (&d)[16], uint64_t da, uint64_t db) {
  asm volatile("wgmma.mma_async.sync.aligned.m64n32k16.f32.f16.f16 " L16 ", %16, %17, 0, 1, 1, 1, 1;\n"
               : Q16("=f", d, 0) : "l"(da), "l"(db));
#pragma unroll
  for (int i = 1; i < 4; i++)
    asm volatile("wgmma.mma_async.sync.aligned.m64n32k16.f32.f16.f16 " L16 ", %16, %17, 1, 1, 1, 1, 1;\n"
                 : Q16("+f", d, 0) : "l"(da + 32 * i), "l"(db + 64 * i));
}
__device__ __forceinline__ uint32_t hmul2(uint32_t a, uint32_t b) {
  uint32_t r;
  asm("mul.rn.f16x2 %0, %1, %2;\n" : "=r"(r) : "r"(a), "r"(b));
  return r;
}
__device__ __forceinline__ uint32_t hadd2(uint32_t a, uint32_t b) {
  uint32_t r;
  asm("add.rn.f16x2 %0, %1, %2;\n" : "=r"(r) : "r"(a), "r"(b));
  return r;
}
__device__ __forceinline__ uint32_t hneg2(uint32_t a) {
  uint32_t r;
  asm("neg.f16x2 %0, %1;\n" : "=r"(r) : "r"(a));
  return r;
}
__device__ __forceinline__ uint32_t hfma2(uint32_t a, uint32_t b, uint32_t c) {
  uint32_t r;
  asm("fma.rn.f16x2 %0, %1, %2, %3;\n" : "=r"(r) : "r"(a), "r"(b), "r"(c));
  return r;
}
__device__ __forceinline__ uint32_t pack_f16(float lo, float hi) {
  uint32_t r;
  asm("cvt.rn.f16x2.f32 %0, %1, %2;\n" : "=r"(r) : "f"(hi), "f"(lo));
  return r;
}
__device__ __forceinline__ uint32_t bmaxabs2(uint32_t a, uint32_t b) {
  uint32_t r;
  asm("max.xorsign.abs.bf16x2 %0, %1, %2;\n" : "=r"(r) : "r"(a), "r"(b));
  return r;
}
struct C2 { uint32_t r, i; };
__device__ __forceinline__ C2 cmul(C2 a, C2 b) {
  return C2{hfma2(a.r, b.r, hneg2(hmul2(a.i, b.i))), hfma2(a.r, b.i, hmul2(a.i, b.r))};
}
__device__ __forceinline__ C2 cfma(C2 a, C2 b, C2 c) {
  return C2{hfma2(a.r, b.r, hfma2(hneg2(a.i), b.i, c.r)), hfma2(a.r, b.i, hfma2(a.i, b.r, c.i))};
}
__device__ __forceinline__ C2 crot(C2 z, C2 t) {
  const uint32_t r = hfma2(t.r, z.i, z.r), i = hfma2(t.i, r, z.i);
  return C2{hfma2(t.r, i, r), i};
}
__device__ __forceinline__ C2 cget(const uint32_t (&e)[8], int j, int b) { return C2{e[4 * j + b], e[4 * j + 2 + b]}; }
template <int N> __device__ __forceinline__ void fence_regs(uint32_t (&d)[N]) {
#pragma unroll
  for (int i = 0; i < N; i++) asm volatile("" : "+r"(d[i])::"memory");
}
__device__ __forceinline__ void ldsm4(uint32_t (&r)[4], uint32_t a) {
  asm volatile("ldmatrix.sync.aligned.m8n8.x4.shared.b16 {%0,%1,%2,%3}, [%4];\n"
               : "=r"(r[0]), "=r"(r[1]), "=r"(r[2]), "=r"(r[3]) : "r"(a) : "memory");
}

__device__ __forceinline__ uint32_t movm(uint32_t a) {
  uint32_t r;
  asm volatile("movmatrix.sync.aligned.m8n8.trans.b16 %0, %1;\n" : "=r"(r) : "r"(a));
  return r;
}
template <int C0, int H, bool T> __device__ __forceinline__ void attn_pack(const float (&acc)[96], uint32_t (&d)[8]) {
#pragma unroll
  for (int c = 0; c < 8; c++) {
    asm volatile("cvt.rn.bf16x2.f32 %0, %1, %2;\n" : "=r"(d[c]) : "f"(acc[4 * (C0 + c) + 2 * H + 1]), "f"(acc[4 * (C0 + c) + 2 * H]));
    if (T) d[c] = movm(d[c]);
  }
}
__device__ __forceinline__ void attn_qk(float (&s)[4], const uint32_t (&qlo)[8], const uint32_t (&qhi)[8],
                                        const uint32_t (&k)[8], int c) {
  mma16816_z(s, qlo[c], qhi[c], qlo[c + 1], qhi[c + 1], k[c], k[c + 1]);
  mma16816(s, qlo[c + 2], qhi[c + 2], qlo[c + 3], qhi[c + 3], k[c + 2], k[c + 3]);
}
template <int N> __device__ __forceinline__ void quad_softmax(float (&x)[N][2], uint32_t (&pp)[N]) {
  const float c2 = 1.4426950408889634f;
  uint32_t q[N], mx[N / 2];
#pragma unroll
  for (int n = 0; n < N; n++) {
    const uint32_t r = pack_bf16(x[n][0], x[n][1]);
    q[n] = bfma2(r, 0x3e353e35u, bmul2(r, 0x379e379eu));
    x[n][0] = bf_lo(q[n]);
    x[n][1] = bf_hi(q[n]);
  }
#pragma unroll
  for (int n = 0; n < N / 2; n++)
    mx[n] = bmax2(__byte_perm(q[2 * n], q[2 * n + 1], 0x5410), __byte_perm(q[2 * n], q[2 * n + 1], 0x7632));
#pragma unroll
  for (int o = 1; o <= 2; o++) {
#pragma unroll
    for (int n = 0; n < N / 2; n++) mx[n] = bmax2(mx[n], __shfl_xor_sync(0xffffffffu, mx[n], o));
  }
  float m[N], t[N];
#pragma unroll
  for (int n = 0; n < N / 2; n++) {
    m[2 * n] = bf_lo(mx[n]);
    m[2 * n + 1] = bf_hi(mx[n]);
  }
#pragma unroll
  for (int n = 0; n < N; n++) {
    const float nm = -m[n] * c2;
    x[n][0] = ex2(fmaf(x[n][0], c2, nm));
    x[n][1] = ex2(fmaf(x[n][1], c2, nm));
  }
#pragma unroll
  for (int n = 0; n < N; n += 2) {
    float u0, u1;
    asm("mma.sync.aligned.m16n8k8.row.col.f32.tf32.tf32.f32 {%0,%1,%2,%3}, {%4,%5,%6,%7}, {%8,%8}, {%9,%9,%9,%9};\n"
        : "=f"(t[n]), "=f"(u0), "=f"(t[n + 1]), "=f"(u1)
        : "r"(__float_as_uint(x[n][0])), "r"(__float_as_uint(x[n + 1][0])), "r"(__float_as_uint(x[n][1])),
          "r"(__float_as_uint(x[n + 1][1])), "r"(0x3f800000u), "f"(0.f));
  }
#pragma unroll
  for (int n = 0; n < N; n++) {
    const float inv = rcp(t[n]);
    pp[n] = pack_bf16(x[n][0] * inv, x[n][1] * inv);
  }
}
__device__ __forceinline__ void attn_pv(uint32_t dst, const uint32_t (&vp)[8], const uint32_t (&vo)[8], int c, uint32_t pp,
                                        uint32_t maskLE) {
  const uint32_t b0 = pp & ~maskLE, b1 = pp & maskLE;
  float oa[4], ob[4];
  mma16816_z(oa, vp[c], vp[c + 1], vo[c], vo[c + 1], b0, b1);
  mma16816_z(ob, vp[c + 2], vp[c + 3], vo[c + 2], vo[c + 3], b0, b1);
  stsm4t(dst, pack_bf16(oa[0], oa[1]), pack_bf16(oa[2], oa[3]), pack_bf16(ob[0], ob[1]), pack_bf16(ob[2], ob[3]));
}

template <int MODE>
__global__ void __cluster_dims__(2, 1, 1) __launch_bounds__(NTHREADS, 1)
fused_kernel(const Params p, const __grid_constant__ CUtensorMap tmX, const __grid_constant__ CUtensorMap tmW,
             const __grid_constant__ CUtensorMap tmWo, const __grid_constant__ CUtensorMap tmWp,
             const __grid_constant__ CUtensorMap tmQ,
             const __grid_constant__ CUtensorMap tmOb,
             const __grid_constant__ CUtensorMap tmXh, const __grid_constant__ CUtensorMap tmWh) {
  extern __shared__ __align__(1024) uint8_t smem[];
  if (threadIdx.x < 32) {
    const uint32_t i = (blockIdx.x & 127) * 16 + (threadIdx.x & 15);
    prefetch_l2(threadIdx.x & 16 ? (const char*)p.w + i * 128 : (const char*)p.x + i * 2048);
  }
  const uint32_t sb = smem_u32(smem);
  const uint32_t bars = sb + OFF_BAR;
  const int tid = threadIdx.x, lane = tid & 31, warp = __shfl_sync(0xffffffffu, tid >> 5, 0);
  const int rank = blockIdx.x & 1;
  const bool halo_cta = blockIdx.x < 4;
  if (halo_cta && MODE != 0) return;
  int grp, mem;
  {
    const int t = (blockIdx.x >> 1) - 4, u = t - 32;
    const int q7 = (u * 37) >> 8;
    const bool lo = (unsigned)t < 32u, mid = (unsigned)u < 28u;
    grp = lo ? (t & 7) : (mid ? 1 + u - 7 * q7 : 0);
    mem = lo ? (t >> 3) : (mid ? 4 + q7 : (t < 0 ? t + 6 : t - 54));
  }
  const int rg = (grp >> 2) * 4 + (mem >> 1), hp = (grp & 3) * 4 + (mem & 1) * 2 + rank;
  const int rb2 = (grp >> 2) * 8 + mem, cb2 = (grp & 3) * 2 + rank;
  const int chb = grp * 16 + mem * 2 + rank;
  const int cta = rg * 16 + hp;
  const int hsel = rb2 & 1;
  const int par = rg >> 2, gidx = rg & 3;

  if (tid < 256 && !halo_cta && MODE != 2) {
    const int r = tid >> 3, c = tid & 7;
    const uint32_t so = r * 128 + ((c ^ (r & 7)) << 4);
    const __nv_bfloat16* wg0 = p.w + (size_t)r * (3 * DM) + hp * 64 + c * 8;
    const __nv_bfloat16* xg0 = p.x + (size_t)(2 * (gidx * 256 + r) + par) * DM + c * 8;
#pragma unroll
    for (int j = 0; j < 3; j++) cp_async16n(sb + OFF_1B + j * 4096 + so, wg0 + j * DM);
#pragma unroll
    for (int i = 0; i < 8; i++) cp_async16n(sb + i * 4096 + so, xg0 + (size_t)i * 64 * DM);
    asm volatile("cp.async.commit_group;\n" ::: "memory");
  }
  auto halo_issue = [&](int kb, int s) {
    const uint32_t fb = bars + 8 * (BAR_FULLB + s), st = sb + s * STGH;
    mbar_expect_tx(fb, STGH - 2048);
    tma_load_3d(st + 8192, &tmWh, fb, 0, kb * 64, 16 + blockIdx.x * 4);
    tma_load_3d(st + 8192 + 32768, &tmWh, fb, 0, kb * 64, 32 + blockIdx.x * 4);
    tma_load_4d(st, &tmXh, fb, kb * 64, 248, 0, 0);
  };
  if (tid == 256) {
    prefetch_tmap(halo_cta ? &tmXh : &tmX);
#pragma unroll
    for (int i = 0; i < NS1B; i++) mbar_init(bars + 8 * (BAR_FULLB + i), 1);
#pragma unroll
    for (int i = 0; i < NS1A; i++) mbar_init(bars + 8 * (BAR_FULLA + i), 1);
    asm volatile("fence.mbarrier_init.release.cluster;\n" ::: "memory");
    if (!halo_cta && MODE != 2) {
      mbar_expect_tx(bars + 8 * (BAR_FULLB + 1), STG1B);
      tma_load_3d(sb + OFF_1B + 1 * STG1B, &tmW, bars + 8 * (BAR_FULLB + 1), hp * 64, 32, 0);
      mbar_expect_tx(bars + 8 * (BAR_FULLB + 2), STG1B);
      tma_load_3d(sb + OFF_1B + 2 * STG1B, &tmW, bars + 8 * (BAR_FULLB + 2), hp * 64, 64, 0);
    } else if (halo_cta) {
      halo_issue(0, 0);
    }
  } else if (tid == 288) {
#pragma unroll
    for (int i = 0; i < NS1A; i++) mbar_init(bars + 8 * (BAR_EMPTYA + i), 4);
#pragma unroll
    for (int i = 0; i < NS1B; i++) mbar_init(bars + 8 * (BAR_EMPTYB + i), 2);
    mbar_init(bars + 8 * BAR_X, 4);
    mbar_init(bars + 8 * BAR_LAND, 17);
    mbar_init(bars + 8 * BAR_TAB, 16);
    mbar_init(bars + 8 * BAR_U, 1);
    mbar_init(bars + 8 * BAR_H, 1);
    mbar_init(bars + 8 * BAR_STG, 8);
    mbar_init(bars + 8 * BAR_HALO, 1);
    mbar_init(bars + 8 * BAR_Q, 1);
    mbar_init(bars + 8 * BAR_XFREE, 2);
    mbar_init(bars + 8 * (BAR_XFREE + 1), 2);
    asm volatile("fence.mbarrier_init.release.cluster;\n" ::: "memory");
  } else if (tid == 320) {
#pragma unroll
    for (int i = 0; i < NS2; i++) {
      mbar_init(bars + 8 * (BAR_FULL2 + i), 1);
      mbar_init(bars + 8 * (BAR_EMPTY2 + i), 4);
    }
    asm volatile("fence.mbarrier_init.release.cluster;\n" ::: "memory");
  } else if (tid == 352) {
#pragma unroll
    for (int i = 0; i < 8; i++) mbar_init(bars + 8 * (BAR_Y + i), 4);
    asm volatile("fence.mbarrier_init.release.cluster;\n" ::: "memory");
  }
  cluster_sync_all();
  if (warp == 8) PROF2(24);

  if (warp >= 8) {
    const int hw = warp - 8;
    const int lr = lane & 7, lm = lane >> 3;
    auto g1_issue_a = [&](int j, int s) {
      const uint32_t fb = bars + 8 * (BAR_FULLA + s);
      mbar_expect_tx(fb, STG1A);
      tma_load_3d_mc(sb + s * STG1A + rank * 16384, &tmX, fb, j * 64, par, gidx * 256 + rank * 128);
    };
    auto g1_issue_b = [&](int kb, int s) {
      const uint32_t fb = bars + 8 * (BAR_FULLB + s);
      mbar_expect_tx(fb, STG1B);
      tma_load_3d(sb + OFF_1B + s * STG1B, &tmW, fb, hp * 64, kb * 32, 0);
    };
    auto g2_k = [&](int kb) { return (kb < 2 ? hp : kb < 4 ? hp & 14 : hp & 12) ^ kb; };
    auto g2_issue_b = [&](int kb, int s) {
      const uint32_t fb = bars + 8 * (BAR_FULL2 + s), dst = sb + g2_b(s, rank);
      mbar_expect_tx(fb, kb || MODE ? STG2 : STG2 / 2);
      if (s < 3) {
        tma_load_3d(dst, &tmWo, fb, 0, g2_k(kb) * 64, cb2 * 2);
      } else {
#pragma unroll
        for (int i = 0; i < 4; i++)
          tma_load_3d(dst + (i & 1) * XT + (i >> 1) * 4 * XT, &tmWp, fb, 0, g2_k(kb) * 64 + (i >> 1) * 32, cb2 * 2 + (i & 1));
      }
    };
    asm volatile("setmaxnreg.dec.sync.aligned.u32 %0;\n" :: "n"(REG_HELP));

    if (halo_cta) {
      if (hw == 0) {
        int s = 1, ph = 1;
#pragma unroll 1
        for (int kb = 1; kb < 16; kb++) {
          mbar_wait(bars + 8 * (BAR_EMPTYB + s), ph);
          if (elect_one()) halo_issue(kb, s);
          if (++s == 3) { s = 0; ph ^= 1; }
        }
      }
      __syncwarp();
    } else if (hw == 0) {
      uint32_t epoch = 0;
      if (MODE == 2) {
        if (lane < NS2) mbar_arrive_cluster_n(mapa(bars, rank) + 8 * (BAR_EMPTY2 + lane), 4);
      } else {
      if (lane == 0) {
        mbar_expect_tx(bars + 8 * BAR_U, 32768);
        mbar_expect_tx(bars + 8 * BAR_LAND, 16384);
        mbar_expect_tx(bars + 8 * BAR_Q, 32768);
        prefetch_tmap(&tmQ);
      }
      {
        int sa = 1, pha = 1, sbb = 2, phb = 1;
#pragma unroll 1
        for (int kb = 2; kb < 32; kb++) {
          if (!(kb & 1)) {
            mbar_wait(bars + 8 * (BAR_EMPTYA + sa), pha);
            if (elect_one()) g1_issue_a(kb >> 1, sa);
            if (++sa == NS1A) { sa = 0; pha ^= 1; }
          }
          mbar_wait(bars + 8 * (BAR_EMPTYB + sbb), phb);
          if (kb > 2 && elect_one()) g1_issue_b(kb, sbb);
          __syncwarp();
          if (kb == 4) epoch = ld_relaxed(g_flag_o + cta);
          if (kb == 4) PROF2(27);
          if (kb == 1) PROF2(38);
          if (kb == 2) PROF2(39);
          if (++sbb == NS1B) { sbb = 0; phb ^= 1; }
        }
      }
      auto q_issue = [&](int i) {
        mbar_wait(bars + 8 * (i ? BAR_EMPTYB + 3 : BAR_EMPTYA + 1), i);
        if (elect_one())
          asm volatile(
              "cp.async.bulk.tensor.5d.shared::cluster.global.mbarrier::complete_tx::bytes [%0], [%1, {%3, %4, %4, %4, %5}], [%2];\n"
              ::"r"(sb + (i ? OFF_Q1 : OFF_Q0)), "l"(&tmQ), "r"(bars + 8 * BAR_Q), "r"((chb & ~1) * 8), "r"(0), "r"(rank * 64 + i * 32)
              : "memory");
        __syncwarp();
      };
      if (QORD < 2) q_issue(0);
      else mbar_wait(bars + 8 * (BAR_EMPTYA + 1), 0);
      if (QORD < 1) q_issue(1);
      epoch++;
      if (lane == 0) {
        prefetch_tmap(&tmWo);
        prefetch_tmap(&tmWp);
        prefetch_tmap(&tmOb);
        if (gidx != 0) wait_flag(g_flag_h + (hp >> 2), epoch);
      }
      __syncwarp();
      {
        uint4 hk0 = make_uint4(0, 0, 0, 0), hk1 = hk0, hv0 = hk0, hv1 = hk0;
        if (gidx != 0) {
          const uint4* src = g_halo + cta * 128 + lane;
          hk0 = __ldcg(src); hk1 = __ldcg(src + 32); hv0 = __ldcg(src + 64); hv1 = __ldcg(src + 96);
        }
        if (gidx != 0) PROF(18);
        sts128(sb + OFF_KH + lane * 16, hk0.x, hk0.y, hk0.z, hk0.w);
        sts128(sb + OFF_KH + 512 + lane * 16, hk1.x, hk1.y, hk1.z, hk1.w);
        sts64(sb + OFF_KH + 1024 + lane * 8, movm(hv0.x), movm(hv0.y));
        sts64(sb + OFF_KH + 1280 + lane * 8, movm(hv0.z), movm(hv0.w));
        sts64(sb + OFF_KH + 1536 + lane * 8, movm(hv1.x), movm(hv1.y));
        sts64(sb + OFF_KH + 1792 + lane * 8, movm(hv1.z), movm(hv1.w));
        __syncwarp();
        if (lane == 0) mbar_arrive(bars + 8 * BAR_HALO);
      }
      if (QORD == 2) q_issue(0);
      if (QORD >= 1) q_issue(1);
      const uint32_t rb = mapa(bars, lane & 1);
      nb_sync(NB_OREADY, 288);
      if (lane == 0) {
        asm volatile("cp.async.bulk.global.shared::cta.bulk_group [%0], [%1], %2;\n" ::"l"(g_o + (size_t)cta * 16384),
                     "r"(sb + OFF_OP), "r"(32768) : "memory");
        bulk_commit();
      }
      if (lane < 2) {
#pragma unroll
        for (int i = 0; i < 4; i++) mbar_arrive_cluster_n(rb + 8 * (BAR_EMPTY2 + i + i / 2), 2);
      }
      if (lane == 0) {
        bulk_wait0();
        st_release(g_flag_o + cta, epoch);
      }
      __syncwarp();
      PROF2(17);
      if (lane < 2) mbar_arrive_cluster_n(rb + 8 * (BAR_EMPTY2 + 2), 2);
      }
      if (MODE != 1) {
        const __nv_bfloat16* osrc = g_o + (size_t)(rb2 >> 1) * 16 * 16384 + hsel * 8192;
        mbar_wait(bars + 8 * (BAR_EMPTY2 + 1), 0);
        if (elect_one()) {
          if (MODE == 0) {
            asm volatile("cp.async.bulk.shared::cluster.shared::cta.mbarrier::complete_tx::bytes [%0], [%1], %2, [%3];\n"
                         ::"r"(mapa(sb + g2_a(1, hsel), rank ^ 1)), "r"(sb + g2_a(0, hsel)), "r"(16384),
                         "r"(mapa(bars + 8 * (BAR_FULL2 + 1), rank ^ 1)) : "memory");
          } else {
            bulk_load(sb + g2_a(0, hsel), osrc + hp * 16384, 16384, bars + 8 * BAR_FULL2);
            bulk_load(sb + g2_a(1, hsel), osrc + (hp ^ 1) * 16384, 16384, bars + 8 * (BAR_FULL2 + 1));
          }
        }
        __syncwarp();
        int s = 3, ph = 0;
#pragma unroll 1
        for (int kb = 3; kb < 16; kb++) {
          mbar_wait(bars + 8 * (MODE == 0 && kb < 5 ? BAR_XFREE + kb - 3 : BAR_EMPTY2 + s), ph);
          if (elect_one()) g2_issue_b(kb, s);
          __syncwarp();
          if (++s == NS2) { s = 0; ph ^= 1; }
        }
      }
      __syncwarp();
    } else {
      if (MODE != 2) {
      const float dall = __bfloat162float(p.ssm_D[chb * 8 + lr]);
      {
        const int g = lane >> 2, t = lane & 3;
        uint32_t w[2][4];
#pragma unroll
        for (int h = 0; h < 2; h++) {
          const uint2 x = __ldg(reinterpret_cast<const uint2*>(p.shift_k + ((chb & ~1) * 8 + h * 8 + g) * 4));
          w[h][0] = __byte_perm(x.x, x.x, 0x1010);
          w[h][1] = __byte_perm(x.x, x.x, 0x3232);
          w[h][2] = __byte_perm(x.y, x.y, 0x1010);
          w[h][3] = __byte_perm(x.y, x.y, 0x3232);
        }
        auto swz = [](int r) { return (((r & 29) | ((r ^ (r >> 2)) & 2)) << 5) | (r & 16); };
        const uint32_t kring = sb + OFF_X + 4096 + (hw - 1) * 2 * XT, vring = kring + XT;
        const int s0 = rank * 32 + (hw - 1) * 11, s1 = hw == 3 ? rank * 32 + 32 : s0 + 11;
        const size_t goff = (size_t)(lane >> 1) * DM + (chb & ~1) * 8 + (lane & 1) * 8;
        const __nv_bfloat16* kg = p.k + goff;
        const __nv_bfloat16* vg = p.v + goff;
        const uint32_t d0 = swz(lane >> 1) ^ ((lane & 1) << 4), d1 = swz(16 + (lane >> 1)) ^ ((lane & 1) << 4);
        auto issue = [&](int st) {
          const uint32_t so = (st & 3) << 10;
          cp_async16(kring + so + d0, kg + (size_t)st * 32 * DM, 16);
          cp_async16(kring + so + d1, kg + (size_t)(st * 32 + 16) * DM, 16);
          cp_async16(vring + so + d0, vg + (size_t)st * 32 * DM, 16);
          cp_async16(vring + so + d1, vg + (size_t)(st * 32 + 16) * DM, 16);
        };
        const int xa = 8 * (lr >> 1) + 2 * lm + (lr & 1), xb = 8 * (lr >> 1) - 4 + 2 * (lm & 1) + (lr & 1);
        const uint32_t la = swz(xa), lb = swz(xb & 31);
        const int backb = xb < 0 ? 1 : 0;
        const uint32_t ud[2] = {mapa(sb + OFF_X + g * XT + t * 16, 0), mapa(sb + OFF_X + g * XT + t * 16, 1)};
        const uint32_t ub[2] = {mapa(bars + 8 * BAR_U, 0), mapa(bars + 8 * BAR_U, 1)};
        if (tid == 320) prefetch_l2(g_tab + (chb & 63) * 32);
        if (lane == 0) mbar_wait(bars + 8 * (BAR_FULLB + NS1B - 1), 0);
        __syncwarp();
        if (lane >= 24) cp_async16(kring + (((s0 - 1) & 3) << 10) + d1, s0 > 0 ? kg + (size_t)(s0 * 32 - 16) * DM : kg, s0 > 0 ? 16 : 0);
        issue(s0);
        asm volatile("cp.async.commit_group;\n" ::: "memory");
        issue(s0 + 1);
        asm volatile("cp.async.commit_group;\n" ::: "memory");
        uint32_t tn = (uint32_t)clock();
#pragma unroll 1
        for (int st = s0; st < s1; st++) {
          tn += PSTEP;
          while ((int)((uint32_t)clock() - tn) < 0) __nanosleep(100);
          if (st + 2 < s1) issue(st + 2);
          if (hw == 1 && (unsigned)(st - s0 - HPF0) < 8u) prefetch_l2(p.ssm_k + (size_t)(chb * 8 + st - s0 - HPF0) * SEQ + lane * 64);
          asm volatile("cp.async.commit_group;\n" ::: "memory");
          asm volatile("cp.async.wait_group 2;\n" ::: "memory");
          __syncwarp();
#pragma unroll
          for (int h = 0; h < 2; h++) {
            uint32_t e[6], vv[4], e4[4];
            ldsm4t(e4, kring + ((st & 3) << 10) + (la ^ (h << 4)));
            ldsm2t(e[0], e[1], kring + (((st - backb) & 3) << 10) + (lb ^ (h << 4)));
            ldsm4t(vv, vring + ((st & 3) << 10) + (la ^ (h << 4)));
            e[2] = e4[0]; e[3] = e4[1]; e[4] = e4[2]; e[5] = e4[3];
            uint32_t o[5];
#pragma unroll
            for (int i = 0; i < 5; i++) o[i] = __byte_perm(e[i], e[i + 1], 0x5432);
#pragma unroll
            for (int i = 0; i < 4; i++) {
              uint32_t a = bmul2(o[i], w[h][3]);
              a = bfma2(e[i + 1], w[h][2], a);
              a = bfma2(o[i + 1], w[h][1], a);
              a = bfma2(e[i + 2], w[h][0], a);
              vv[i] = bmul2(a, vv[i]);
            }
            st_async128(ud[h] + (st ^ (g & 1)) * 64, ub[h], vv[0], vv[1], vv[2], vv[3]);
          }
          __syncwarp();
        }
        fence_async_smem();
        PROF(16);
      }
      nb_sync(NB_HELP3, 96);
      if (hw == 1 && elect_one()) {
        mbar_expect_tx(bars + 8 * BAR_H, 8 * 4096);
#pragma unroll 1
        for (int c = 0; c < 8; c++)
          bulk_load(sb + OFF_X + c * XT + 4096, p.ssm_k + (size_t)(chb * 8 + c) * SEQ, 4096, bars + 8 * BAR_H);
        mbar_expect_tx(bars + 8 * BAR_X, 6144);
        bulk_load(sb + OFF_T16, g_tab, 2048, bars + 8 * BAR_X);
        bulk_load(sb + OFF_T32, g_tab + 512, 4096, bars + 8 * BAR_X);
      }
      __syncwarp();
      {
        const int ck = 16 * (lane >> 4) + 2 * lr + (((lane >> 3) ^ (lane >> 2)) & 1);
        const uint32_t xo = (ck >> 1) * 128, xs = ((ck & 1) ^ lr) << 4;
#pragma unroll 1
        for (int job = hw - 1; job < 16; job += 3) {
          const int c = job & 7;
          uint4 a[8];
          float dv = __shfl_sync(0xffffffffu, dall, c);
          if (job < 8 || lane) dv = 0.f;
          if (job >= PF0 && job < PF1) prefetch_l2((job < 8 ? p.q + (size_t)chb * 16384 : p.wo + (size_t)chb * 8192) + c * 2048 + lane * 64);
          const uint32_t xt = sb + OFF_X + c * XT + (job >> 3) * 4096;
          mbar_wait(bars + 8 * (job < 8 ? BAR_U : BAR_H), 0);
#pragma unroll
          for (int i = 0; i < 8; i++) a[i] = lds128(xt + i * 512 + ((ck ^ (job < 8 ? (c & 1) << 2 : 0)) << 4));
          dv += bf_lo(a[0].x);
          uint32_t m[4] = {bmaxabs2(a[0].x, pack_bf16(dv, 0.f)), a[0].y, a[0].z, a[0].w};
#pragma unroll
          for (int i = 1; i < 8; i++) {
            m[0] = bmaxabs2(m[0], a[i].x); m[1] = bmaxabs2(m[1], a[i].y);
            m[2] = bmaxabs2(m[2], a[i].z); m[3] = bmaxabs2(m[3], a[i].w);
          }
          m[0] = bmaxabs2(bmaxabs2(m[0], m[1]), bmaxabs2(m[2], m[3]));
          const int f = max(252 - (int)(__reduce_max_sync(0xffffffffu, max(m[0] & 0x7fffu, (m[0] >> 16) & 0x7fffu)) >> 7), 1);
          if (lane == 0) asm volatile("st.shared.u32 [%0], %1;\n" ::"r"(sb + OFF_EX + job * 4), "r"(f) : "memory");
          if (f < 113) {
#pragma unroll
            for (int i = 0; i < 8; i++)
              a[i] = make_uint4(bmul2(a[i].x, f * 0x00800080u), bmul2(a[i].y, f * 0x00800080u), bmul2(a[i].z, f * 0x00800080u),
                                bmul2(a[i].w, f * 0x00800080u));
          }
          const uint32_t mul = (f < 113 ? 15 : f - 112) * 0x00800080u;
          auto cv = [&](uint32_t x) {
            x = bmul2(x, mul);
            return (x & 0x0fff0fffu) * 7 + x;
          };
          const uint32_t dst = xt + xo;
#pragma unroll
          for (int i = 0; i < 8; i++)
            sts128(dst + (i & 1) * 2048 + (xs ^ ((i >> 1) << 5)),
                   i ? cv(a[i].x) : __byte_perm(pack_f16(dv * __uint_as_float(f << 23), 0.f), cv(a[i].x), 0x7610), cv(a[i].y),
                   cv(a[i].z), cv(a[i].w));
        }
        fence_async_smem();
        __syncwarp();
        if (lane == 0) mbar_arrive(bars + 8 * BAR_X);
        PROF(19);
      }
      if (hw < 3) {
        const uint32_t peer = mapa(sb, rank ^ 1);
#pragma unroll 1
        for (int n = 0; n < SPIN_LIMIT && !mbar_try(bars + 8 * (BAR_Y + hw * 4 - 4), 0); n++) __nanosleep(200);
#pragma unroll 1
        for (int ch = hw * 4 - 4; ch < hw * 4; ch++) {
          const uint32_t o = OFF_X + ch * XT + (rank ^ 1) * 4096;
          uint4 a[4];
          mbar_wait(bars + 8 * (BAR_Y + ch), 0);
#pragma unroll
          for (int i = 0; i < 4; i++) a[i] = lds128(sb + o + (i >> 1) * 2048 + (i & 1) * 512 + lane * 16);
#pragma unroll
          for (int i = 0; i < 4; i++)
            st_async128(peer + o + 1024 + (i >> 1) * 2048 + (i & 1) * 512 + lane * 16, peer + OFF_BAR + 8 * BAR_LAND, a[i].x,
                        a[i].y, a[i].z, a[i].w);
          if (ch & 1) {
            fence_async_smem();
            __syncwarp();
            if (lane == 0) mbar_arrive(bars + 8 * (BAR_XFREE + ((ch >> 1) & 1)));
          }
        }
        PROF(32);
        const int c8 = 2 * lm + (lr & 1), src = (lr >> 1) & 1;
        uint32_t fa = sb + OFF_X + c8 * XT + rank * 4096 + (src == rank ? 0 : 1024) + (hw - 1) * 2048;
        const uint32_t fx = ((lr >> 2) ^ ((lr & 3) << 1)) << 4;
        uint32_t qa = sb + (hw == 1 ? OFF_Q0 : OFF_Q1) + (lane >> 3) * 128 + (lane & 2) * 32 + (lane & 4) * 8 + (lane & 1) * 16;
        uint4* og = reinterpret_cast<uint4*>(p.out + (size_t)(rank * 1024 + (hw - 1) * 512 + (lane & 2) * 4 + (lane >> 2)) * (2 * DM) +
                                             (chb & ~1) * 8 + (lane & 1) * 8);
        mbar_wait(bars + 8 * BAR_Q, 0);
        mbar_wait(bars + 8 * BAR_LAND, 0);
        PROF2(33);
        uint32_t tn = (uint32_t)clock() + (hw - 1) * (FPACE / 2);
#pragma unroll 1
        for (int j = 0; j < 4; j++) {
#pragma unroll
          for (int i = 0; i < 8; i++) {
            uint32_t y[4];
            const uint4 q = lds128(qa + i * 512);
            ldsm4t(y, fa + (i >> 2) * 128 + (fx ^ ((i & 3) << 5) ^ ((i >> 2) << 4)));
            while ((int)((uint32_t)clock() - tn) < 0) __nanosleep(20);
            tn += FPACE;
            og[i * 16 * (2 * DM / 8)] = make_uint4(bmul2(q.x, y[0]), bmul2(q.y, y[1]), bmul2(q.z, y[2]), bmul2(q.w, y[3]));
          }
          qa += 4096;
          fa += 256;
          og += 128 * (2 * DM / 8);
        }
        PROF(22);
      }
      }
      if (MODE != 1 && hw == 3) {
        const uint32_t epoch = ld_relaxed(g_flag_o + cta) + 1;
        if (MODE == 0) nb_sync(NB_G1END, 288);
        if (BDEL) __nanosleep(BDEL);
        if (elect_one()) {
#pragma unroll
          for (int kb = 0; kb < 3; kb++) g2_issue_b(kb, kb);
        }
        __syncwarp();
        const __nv_bfloat16* osrc = g_o + (size_t)(rb2 >> 1) * 16 * 16384 + hsel * 8192;
        if (MODE == 0) __nanosleep(POLL0);
        const uint32_t* flag = g_flag_o + (rb2 >> 1) * 16 + g2_k(lane & 15);
        uint32_t ready = MODE == 0 ? 0u : ~0u;
        int s = 2, ph = 0;
#pragma unroll 1
        for (int kb = 2; kb < 16; kb++) {
          if (!(ready >> kb & 1)) {
#pragma unroll 1
            for (int n = 0; n < SPIN_LIMIT && !(ready >> kb & 1); n++)
              ready = __ballot_sync(0xffffffffu, ld_acquire(flag) == epoch);
            fence_async_all();
          }
          if (kb == 2) PROF(21);
          mbar_wait(bars + 8 * (BAR_EMPTY2 + s), ph);
          if (MODE == 0 && kb == 4 && rank == 1) mbar_wait(bars + 8 * BAR_TAB, 0);
          if (elect_one()) {
            asm volatile(
                "cp.async.bulk.shared::cluster.global.mbarrier::complete_tx::bytes.multicast::cluster [%0], [%1], %2, [%3], %4;\n"
                ::"r"(sb + g2_a(s, hsel) + rank * 8192), "l"(osrc + rank * 4096 + (uint32_t)g2_k(kb) * 16384), "r"(8192),
                "r"(bars + 8 * (BAR_FULL2 + s)), "h"((uint16_t)3) : "memory");
          }
          __syncwarp();
          if (++s == NS2) { s = 0; ph ^= 1; }
        }
      }
    }
    cluster_sync_all();
    PROF_DUMP();
  } else {
    asm volatile("setmaxnreg.inc.sync.aligned.u32 %0;\n" :: "n"(REG_MATH));
    if (warp == 0) PROF2(26);
    const int wg = warp >> 2;
    const int wtid = tid & 127;
    const bool signaller = (wtid == 0) || (wtid == 32);
    const uint32_t rbars = mapa(bars, wtid >> 5 & 1);

    if (halo_cta) {
      const uint32_t epoch = ld_relaxed(g_flag_h + blockIdx.x) + 1;
      float acc0[64], acc1[64];
      int s = 0, ph = 0;
#pragma unroll 1
      for (int kb = 0; kb < 16; kb++) {
        mbar_wait(bars + 8 * (BAR_FULLB + s), ph);
        const uint32_t st = sb + s * STGH;
        const uint64_t da = mkdesc(st, 16, 1024, 1);
        const uint64_t db = mkdesc(st + 8192 + wg * 32768, 8192, 1024, 1);
        wg_fence();
#pragma unroll
        for (int kk = 0; kk < 4; kk++) {
          wgmma_n128(acc0, da + 2 * kk, db + 128 * kk, kb + kk);
          wgmma_n128(acc1, da + 2 * kk, db + 1024 + 128 * kk, kb + kk);
        }
        wg_commit();
        wg_wait<0>();
        if (kb == 15) PROF(37);
        if (wtid == 0) mbar_arrive(bars + 8 * (BAR_EMPTYB + s));
        if (++s == 3) { s = 0; ph ^= 1; }
      }
      fence_regs(acc0);
      fence_regs(acc1);
      if ((warp & 3) != 3) {
#pragma unroll
        for (int hh = 0; hh < 2; hh++) {
          uint4* dst = g_halo + ((hh * 4 + (warp & 3) + 1) * 16 + blockIdx.x * 4) * 128 + wg * 64 + lane;
#pragma unroll
          for (int j = 0; j < 4; j++) {
            const int o = 16 * j + 2 * hh;
            dst[(j >> 1) * 128 + (j & 1) * 32] =
                make_uint4(pack_bf16(acc0[o], acc0[o + 1]), pack_bf16(acc0[o + 4], acc0[o + 5]),
                           pack_bf16(acc0[o + 8], acc0[o + 9]), pack_bf16(acc0[o + 12], acc0[o + 13]));
            dst[(2 + (j >> 1)) * 128 + (j & 1) * 32] =
                make_uint4(pack_bf16(acc1[o], acc1[o + 1]), pack_bf16(acc1[o + 4], acc1[o + 5]),
                           pack_bf16(acc1[o + 8], acc1[o + 9]), pack_bf16(acc1[o + 12], acc1[o + 13]));
          }
        }
      }
      nb_sync(NB_G1DONE, 256);
      if (tid == 0) st_release(g_flag_h + blockIdx.x, epoch);
      PROF(36);
      cluster_sync_all();
      return;
    }

    if (MODE != 2) {
    uint32_t a1[2][4], sc[4];
    C2 t[2];
    {
      float acc0[96], acc1[96];
      int sa = 0, pha = 0, sbb = 0, phb = 0;
      asm volatile("cp.async.wait_group 0;\n" ::: "memory");
      fence_async_smem();
      nb_sync(NB_FIRST, 256);
      if (tid == 0) {
        mbar_arrive(bars + 8 * BAR_FULLA);
        mbar_arrive(bars + 8 * BAR_FULLB);
      }
      PROF(0 + wg);
#pragma unroll 1
      for (int kb = 0; kb < 30; kb++) {
        if (!(kb & 1)) mbar_wait(bars + 8 * (BAR_FULLA + sa), pha);
        mbar_wait(bars + 8 * (BAR_FULLB + sbb), phb);
        if (kb == 0) PROF2(0 + wg);
        if (kb == 4 && wg == 0) PROF2(28);
        if (kb == 8 && wg == 0) PROF2(29);
        if (kb == 16 && wg == 0) PROF2(30);
        const uint64_t da = mkdesc(sb + sa * STG1A + wg * 16384 + (kb & 1) * 64, 16, 2048, 1);
        const uint64_t db = mkdesc(sb + OFF_1B + sbb * STG1B, 4096, 1024, 1);
        wg_fence();
        wgmma_n192(acc0, da + 64, db, kb);
        wgmma_n192(acc1, da, db, kb);
        wgmma_n192(acc0, da + 66, db + 128, 1);
        wgmma_n192(acc1, da + 2, db + 128, 1);
        wg_commit();
        wg_wait<1>();
        if (kb > 0) {
          if (wtid == 64) mbar_arrive(bars + 8 * (BAR_EMPTYB + (sbb == 0 ? NS1B - 1 : sbb - 1)));
          if (!(kb & 1) && signaller) mbar_arrive_cluster(rbars + 8 * (BAR_EMPTYA + (sa == 0 ? NS1A - 1 : sa - 1)));
        }
        if (++sbb == NS1B) { sbb = 0; phb ^= 1; }
        if ((kb & 1) && ++sa == NS1A) { sa = 0; pha ^= 1; }
      }
      const int lr = lane & 7, lm = lane >> 3;
      const bool le0 = 2 * (lane & 3) <= (lane >> 2), le1 = 2 * (lane & 3) + 1 <= (lane >> 2);
      const uint32_t maskLE = (le0 ? 0x0000FFFFu : 0u) | (le1 ? 0xFFFF0000u : 0u);
      uint32_t q[4][8], k[5][8], vt[5][8];
      {
        static_assert(15 % NS1A == 0 && 30 % NS1B == 0, "slots of the last k blocks");
        asm volatile("ld.global.nc.v4.u32 {%0,%1,%2,%3}, [%4];\n"
                     : "=r"(t[0].r), "=r"(t[1].r), "=r"(t[0].i), "=r"(t[1].i) : "l"(g_tab + 1536 + wtid * 4));
        mbar_wait(bars + 8 * BAR_FULLA, 1);
        mbar_wait(bars + 8 * BAR_FULLB, 0);
        mbar_wait(bars + 8 * (BAR_FULLB + 1), 0);
        mbar_wait(bars + 8 * (BAR_EMPTYA + 1), 0);
        const uint64_t da = mkdesc(sb + wg * 16384, 16, 2048, 1);
        const uint64_t db = mkdesc(sb + OFF_1B, 4096, 1024, 1);
        wg_fence();
#pragma unroll
        for (int i = 0; i < 4; i++) wgmma_n192(acc0, da + 64 + 2 * i, db + (i >> 1) * (STG1B >> 4) + (i & 1) * 128, 1);
        wg_commit();
#pragma unroll
        for (int i = 0; i < 2; i++) wgmma_n192(acc1, da + 2 * i, db + (i >> 1) * (STG1B >> 4) + (i & 1) * 128, 1);
        wg_commit();
        wg_wait<1>();
        fence_regs(acc0);
        PROFA(45, 0);
        attn_pack<8, 1, false>(acc0, k[4]);
        attn_pack<16, 1, true>(acc0, vt[4]);
        const uint32_t kh = sb + (warp == 7 ? OFF_OP + 7 * 4096 : OFF_KH + (warp + 1) * 2048) + lane * 16;
        sts128(kh, k[4][0], k[4][1], k[4][2], k[4][3]);
        sts128(kh + 512, k[4][4], k[4][5], k[4][6], k[4][7]);
#pragma unroll
        for (int i = 0; i < 4; i++) sts64(kh - lane * 8 + 1024 + 256 * i, vt[4][2 * i], vt[4][2 * i + 1]);
#pragma unroll
        for (int i = 2; i < 4; i++) wgmma_n192(acc1, da + 2 * i, db + (i >> 1) * (STG1B >> 4) + (i & 1) * 128, 1);
        wg_commit();
        attn_pack<0, 0, false>(acc0, q[1]);
        attn_pack<0, 1, false>(acc0, q[3]);
        attn_pack<8, 0, false>(acc0, k[2]);
        attn_pack<16, 0, true>(acc0, vt[2]);
        uint32_t z = p.zero;
#pragma unroll
        for (int i = 0; i < 8; i++) z &= q[1][i] & q[3][i];
#pragma unroll
        for (int i = 0; i < 8; i += 2) z &= k[2][i] & k[2][i + 1];
        __syncwarp();
        if (lane == 0) mbar_arrive(bars + 8 * BAR_STG + z);
        wg_wait<0>();
        fence_regs(acc1);
        if (MODE == 0) nb_arrive(NB_G1END, 288);
      }
      PROF(2 + wg);
      mbar_wait(bars + 8 * (warp == 0 ? BAR_HALO : BAR_STG), 0);
      {
        const uint32_t kh = sb + OFF_KH + warp * 2048 + lane * 16;
#pragma unroll
        for (int i = 0; i < 2; i++) {
          const uint4 t = lds128(kh + 512 * i);
          k[0][4 * i] = t.x; k[0][4 * i + 1] = t.y; k[0][4 * i + 2] = t.z; k[0][4 * i + 3] = t.w;
        }
#pragma unroll
        for (int i = 0; i < 4; i++) {
          const uint2 t = lds64(kh - lane * 8 + 1024 + 256 * i);
          vt[0][2 * i] = t.x; vt[0][2 * i + 1] = t.y;
        }
      }
      attn_pack<0, 0, false>(acc1, q[0]);
      attn_pack<0, 1, false>(acc1, q[2]);
      attn_pack<8, 0, false>(acc1, k[1]);
      attn_pack<8, 1, false>(acc1, k[3]);
      {
        float x[8][2];
        uint32_t pp[8];
        const bool first = warp == 0 && gidx == 0;
#pragma unroll
        for (int hd = 0; hd < 2; hd++) {
#pragma unroll
          for (int j = 0; j < 4; j += 2) {
            float s0[4], s1[4], s2[4];
            attn_qk(s2, q[j], q[j + 1], k[j + 2], 4 * hd);
            attn_qk(s1, q[j], q[j + 1], k[j + 1], 4 * hd);
            attn_qk(s0, q[j], q[j + 1], k[j], 4 * hd);
            if (j == 0 && first) s0[0] = s0[1] = -1e9f / 0.17677669529663687f;
            x[2 * j + hd][0] = le0 ? s1[0] : s0[0];
            x[2 * j + hd][1] = le1 ? s1[1] : s0[1];
            x[2 * j + 2 + hd][0] = le0 ? s2[2] : s1[2];
            x[2 * j + 2 + hd][1] = le1 ? s2[3] : s1[3];
          }
        }
        PROFA(40, __float_as_uint(x[1][0] + x[7][1]));
        attn_pack<16, 0, true>(acc1, vt[1]);
        attn_pack<16, 1, true>(acc1, vt[3]);
        quad_softmax<8>(x, pp);
        PROFA(41, pp[1] + pp[7]);
        mbar_wait(bars + 8 * BAR_X, 0);
        ldsm4(a1[0], sb + OFF_T32 + (warp & 3) * 1024 + lane * 16);
        ldsm4(a1[1], sb + OFF_T32 + 512 + (warp & 3) * 1024 + lane * 16);
        {
          const uint4 fh = lds128(sb + OFF_EX + wg * 16), fu = lds128(sb + OFF_EX + 32 + wg * 16);
          auto pw2 = [](uint32_t a, uint32_t b) { return min(max(381 - (int)a - (int)b, 1), 254) * 0x00800080u; };
          sc[0] = pw2(fh.x, fu.x); sc[1] = pw2(fh.y, fu.y); sc[2] = pw2(fh.z, fu.z); sc[3] = pw2(fh.w, fu.w);
        }
        const uint32_t obase = sb + OFF_OP + (warp * 32 + lr) * 128;
#pragma unroll
        for (int n = 0; n < 8; n++) {
          attn_pv(obase + (n >> 1) * 1024 + (((4 * (n & 1) + lm) ^ lr) << 4), vt[n >> 1], vt[(n >> 1) + 1], 4 * (n & 1), pp[n],
                  maskLE);
        }
      }
      PROFA(42, 0);
    }

    {
      const int w = warp & 3;
      const int lr = lane & 7, lm = lane >> 3;
      const uint32_t xb = sb + OFF_X + wg * 4 * XT;
      const uint64_t dc2 = mkdesc(sb + OFF_T16, 512, 128, 0), dc3 = mkdesc(sb + OFF_T16, 128, 512, 0);
      const uint64_t dc4 = mkdesc(sb + OFF_T32, 128, 256, 0);
      const uint64_t dx = mkdesc(xb, 4096, 1024, 1), dz = mkdesc(xb, 2048, 256, 3);
      const uint32_t zs = xb + (w * 16 + (lm & 1) * 8 + lr) * 32 + (((lm >> 1) ^ (lr >> 2)) << 4);
      const uint32_t ys = xb + w * 2048 + (lm >> 1) * 256;
      const uint32_t yx = (lr * 32 + (((lm & 1) ^ (lr >> 2)) << 4)) ^ (rank << 6);
      const bool own = (w >> 1) == rank;
      const uint32_t ybar = mapa(bars, own ? rank ^ 1 : rank) + 8 * (BAR_Y + wg * 4);
      uint32_t d[2][32], pa[2][4][2][4], e[2][4][8], ya[2][2][2][4], v[2][2][8];
      float o[2][16];
      auto rows = [&](int c) {
        fft_rows(d[c & 1], a1, dx + (XT >> 4) * c);
        wg_commit();
      };
      auto cols = [&](int c) {
        const int s = c & 1;
        fence_regs(d[s]);
#pragma unroll
        for (int i = 0; i < 16; i++) {
          const C2 z = crot(C2{d[s][2 * i], d[s][2 * i + 1]}, t[i & 1]);
          pa[s][i >> 2][i & 1][(i >> 1) & 1] = z.r;
          pa[s][i >> 2][i & 1][2 + ((i >> 1) & 1)] = z.i;
        }
        wg_fence();
#pragma unroll
        for (int i = 0; i < 4; i++) fft_cols<0>(e[s][i], pa[s][i], dc2);
        wg_commit();
      };
      auto prod = [&](int c) {
        const int s = c & 1;
#pragma unroll
        for (int i = 0; i < 4; i++) fence_regs(e[s][i]);
#pragma unroll
        for (int j = 0; j < 2; j++) {
          const C2 u0 = cget(e[s][0], j, 0), u1 = cget(e[s][0], j, 1), u2 = cget(e[s][1], j, 0), u3 = cget(e[s][1], j, 1);
          const C2 h0 = cget(e[s][2], j, 0), h1 = cget(e[s][2], j, 1), h2 = cget(e[s][3], j, 0), h3 = cget(e[s][3], j, 1);
          const C2 s0 = cmul(h0, u0), s1 = cfma(h0, u1, cmul(h1, u0)), s2 = cfma(h0, u2, cfma(h2, u0, cmul(h1, u1)));
          const C2 y3 = cfma(h0, u3, cfma(h1, u2, cfma(h2, u1, cfma(h3, u0, C2{s2.i, hneg2(s2.r)}))));
          ya[s][0][j][0] = s0.r;
          ya[s][0][j][1] = hadd2(s1.r, s0.i);
          ya[s][0][j][2] = s0.i;
          ya[s][0][j][3] = hadd2(s1.i, hneg2(s0.r));
          ya[s][1][j][0] = hadd2(s2.r, s1.i);
          ya[s][1][j][1] = y3.r;
          ya[s][1][j][2] = hadd2(s2.i, hneg2(s1.r));
          ya[s][1][j][3] = y3.i;
        }
        wg_fence();
        fft_cols<1>(v[s][0], ya[s][0], dc3);
        fft_cols<1>(v[s][1], ya[s][1], dc3);
        wg_commit();
      };
      auto stage = [&](int c) {
        const int s = c & 1;
        fence_regs(v[s][0]);
        fence_regs(v[s][1]);
#pragma unroll
        for (int b = 0; b < 4; b++) {
          const C2 x0 = cget(v[s][b >> 1], 0, b & 1), x1 = cget(v[s][b >> 1], 1, b & 1);
          const C2 z0 = crot(C2{x0.i, x0.r}, t[0]), z1 = crot(C2{x1.i, x1.r}, t[1]);
          stsm4(zs + c * XT + b * 2048, z0.i, z0.r, z1.i, z1.r);
        }
      };
      auto back = [&](int c) {
        fft_back(o[c & 1], dz + (XT >> 4) * c, dc4);
        wg_commit();
      };
      auto out = [&](int c) {
        float (&r)[16] = o[c & 1];
        fence_regs(r);
#pragma unroll
        for (int i = 0; i < 16; i += 8)
          stsm4t(ys + c * XT + (yx ^ ((c & 1) << 5)) + 64 * i, bmul2(pack_bf16(r[i], r[i + 1]), sc[c]),
                 bmul2(pack_bf16(r[i + 2], r[i + 3]), sc[c]), bmul2(pack_bf16(r[i + 4], r[i + 5]), sc[c]),
                 bmul2(pack_bf16(r[i + 6], r[i + 7]), sc[c]));
        __syncwarp();
        if (lane == 0) {
          mbar_arrive_cluster(ybar + 8 * c);
          if (own) mbar_arrive(bars + 8 * BAR_LAND);
        }
      };
      wg_fence();
      rows(0);
      rows(1);
      fence_async_smem();
      nb_arrive(NB_OREADY, 288);
      PROF(34 + wg);
      wg_wait<1>();
      cols(0);
      wg_wait<1>();
      cols(1);
      rows(2);
      nb_sync(NB_CONV + wg, 128);
      wg_wait<2>();
      prod(0);
      wg_wait<1>();
      cols(2);
      rows(3);
      wg_wait<2>();
      stage(0);
      fence_async_smem();
      prod(1);
      nb_sync(NB_CONV + wg, 128);
      back(0);
      wg_wait<2>();
      cols(3);
      wg_wait<2>();
      stage(1);
      fence_async_smem();
      prod(2);
      nb_sync(NB_CONV + wg, 128);
      back(1);
      wg_wait<2>();
      out(0);
      wg_wait<1>();
      stage(2);
      fence_async_smem();
      prod(3);
      nb_sync(NB_CONV + wg, 128);
      back(2);
      wg_wait<2>();
      out(1);
      wg_wait<1>();
      stage(3);
      fence_async_smem();
      nb_sync(NB_CONV + wg, 128);
      wg_fence();
      back(3);
      wg_wait<1>();
      out(2);
      wg_wait<0>();
      if (lane == 0) mbar_arrive_cluster(mapa(bars, 1) + 8 * BAR_TAB);
      out(3);
      PROF(6 + wg);
    }
    }

    if (MODE != 1) {
      float acc[64];
      int s = 0, ph = 0, sprev = 0;
      mbar_wait(bars + 8 * BAR_EMPTY2, 0);
#pragma unroll 1
      for (int kb = 0; kb < 16; kb++) {
        const bool rel = kb > 0 && kb + NS2 <= 16 && signaller;
        const bool hold = kb == 16 - ENDG && wg != LEADWG;
        if (hold) {
          wg_wait<0>();
          if (rel) mbar_arrive_cluster(rbars + 8 * (BAR_EMPTY2 + sprev));
          nb_sync(NB_LEAD, 256);
        }
        mbar_wait(bars + 8 * (BAR_FULL2 + s), ph);
        if (kb == 0) PROF(8 + wg);
        if (warp == LEADWG * 4) PROF2(40 + kb);
        const uint64_t da = mkdesc(sb + g2_a(s, hsel) + wg * 8192, 16, 1024, 1);
        const uint64_t db = mkdesc(sb + g2_b(s, rank), 8192, 1024, 1), dc = db + (g2_bk(s) >> 4);
        wg_fence();
        wgmma_n128(acc, da, db, kb);
        wgmma_n128(acc, da + 2, db + 128, 1);
        wgmma_n128(acc, da + 4, dc, 1);
        wgmma_n128(acc, da + 6, dc + 128, 1);
        wg_commit();
        if (kb == LEADKB && wg == LEADWG) nb_arrive(NB_LEAD, 256);
        wg_wait<1>();
        if (rel && !hold) mbar_arrive_cluster(rbars + 8 * (BAR_EMPTY2 + sprev));
        sprev = s;
        if (++s == NS2) { s = 0; ph ^= 1; }
      }
      static_assert(ENDG <= NS2, "the last stages stay resident");
      const int lr = lane & 7, lm = lane >> 3;
      const uint32_t wb = sb + g2_a(1, 0) + warp * 2048;
      const int orow = (rb2 & 7) * 128 + warp * 16;
      const int rr = lane >> 3;
      uint4* og = reinterpret_cast<uint4*>(p.out + (size_t)(2 * (orow + rr) + (rb2 >> 3)) * (2 * DM) + DM + cb2 * 128 + lr * 8);
      wg_wait<0>();
      fence_regs(acc);
      PROF(10 + wg);
#pragma unroll
      for (int h = 0; h < 2; h++) {
        const uint32_t b = wb + h * (g2_a(3, 0) - g2_a(1, 0));
#pragma unroll
        for (int j = 8 * h; j < 8 * h + 8; j += 2)
          stsm4(b + (lr + 8 * (lm & 1)) * 128 + ((((j & 7) + (lm >> 1)) ^ lr) << 4), pack_bf16(acc[4 * j], acc[4 * j + 1]),
                pack_bf16(acc[4 * j + 2], acc[4 * j + 3]), pack_bf16(acc[4 * j + 4], acc[4 * j + 5]),
                pack_bf16(acc[4 * j + 6], acc[4 * j + 7]));
        if (OTMA == 2 || (OTMA == 1 && wg == LEADWG)) {
          fence_async_smem();
          __syncwarp();
          if (elect_one()) {
            tma_store_3d(&tmOb, b, DM + cb2 * 128 + h * 64, rb2 >> 3, orow);
            bulk_commit();
          }
        } else {
          __syncwarp();
          uint4 v[4];
#pragma unroll
          for (int i = 0; i < 4; i++) v[i] = lds128(b + (4 * i + rr) * 128 + ((lr ^ ((4 * i + rr) & 7)) << 4));
#pragma unroll
          for (int i = 0; i < 4; i++) og[(size_t)i * 8 * (2 * DM / 8) + h * 8] = v[i];
        }
      }
      PROF(12 + wg);
      if (OTMA) bulk_wait0();
    }
    cluster_sync_all();
  }
}

typedef CUresult (*EncodeFn)(CUtensorMap*, CUtensorMapDataType, cuuint32_t, void*, const cuuint64_t*, const cuuint64_t*,
                             const cuuint32_t*, const cuuint32_t*, CUtensorMapInterleave, CUtensorMapSwizzle,
                             CUtensorMapL2promotion, CUtensorMapFloatOOBfill);

void make_map(EncodeFn enc, CUtensorMap* tm, const void* base, int rank, const cuuint64_t* dims, const cuuint64_t* strides,
              const cuuint32_t* box, CUtensorMapSwizzle swz) {
  cuuint32_t es[5] = {1, 1, 1, 1, 1};
  enc(tm, CU_TENSOR_MAP_DATA_TYPE_BFLOAT16, rank, const_cast<void*>(base), dims, strides, box, es,
      CU_TENSOR_MAP_INTERLEAVE_NONE, swz, CU_TENSOR_MAP_L2_PROMOTION_L2_256B, CU_TENSOR_MAP_FLOAT_OOB_FILL_NONE);
}

}

extern "C" void kernel_launch(void* const* d_in, const int* in_sizes, int n_in, void* d_out, int out_size) {
  static EncodeFn enc = nullptr;
  static bool coresident = true;
  if (!enc) {
    void* fn = nullptr;
    cudaDriverEntryPointQueryResult qr;
    cudaGetDriverEntryPoint("cuTensorMapEncodeTiled", &fn, cudaEnableDefault, &qr);
    enc = (EncodeFn)fn;
    cudaFuncSetAttribute(fused_kernel<0>, cudaFuncAttributeMaxDynamicSharedMemorySize, SMEM_BYTES);
    cudaFuncSetAttribute(fused_kernel<1>, cudaFuncAttributeMaxDynamicSharedMemorySize, SMEM_BYTES);
    cudaFuncSetAttribute(fused_kernel<2>, cudaFuncAttributeMaxDynamicSharedMemorySize, SMEM_BYTES);
    cudaLaunchConfig_t cfg = {};
    cfg.gridDim = dim3(NCTA);
    cfg.blockDim = dim3(NTHREADS);
    cfg.dynamicSmemBytes = SMEM_BYTES;
    cudaLaunchAttribute at;
    at.id = cudaLaunchAttributeClusterDimension;
    at.val.clusterDim.x = 2;
    at.val.clusterDim.y = 1;
    at.val.clusterDim.z = 1;
    cfg.attrs = &at;
    cfg.numAttrs = 1;
    int nclusters = 0;
    if (cudaOccupancyMaxActiveClusters(&nclusters, fused_kernel<0>, &cfg) == cudaSuccess) coresident = nclusters >= NCTA / 2;
    (void)cudaGetLastError();
  }
  CUtensorMap tmX, tmW, tmWo, tmWp, tmQ, tmOb, tmXh, tmWh;
  {
    cuuint64_t dims[3] = {1024, 2, 1024};
    cuuint64_t str[2] = {2048, 4096};
    cuuint32_t box[3] = {64, 1, 128};
    make_map(enc, &tmX, d_in[6], 3, dims, str, box, CU_TENSOR_MAP_SWIZZLE_128B);
  }
  {
    cuuint64_t dims[3] = {1024, 1024, 3};
    cuuint64_t str[2] = {6144, 2048};
    cuuint32_t box[3] = {64, 32, 3};
    make_map(enc, &tmW, d_in[7], 3, dims, str, box, CU_TENSOR_MAP_SWIZZLE_128B);
  }
  {
    cuuint64_t dims[3] = {64, 1024, 16};
    cuuint64_t str[2] = {2048, 128};
    cuuint32_t box[3] = {64, 64, 2};
    cuuint32_t piece[3] = {64, 32, 1};
    make_map(enc, &tmWo, d_in[8], 3, dims, str, box, CU_TENSOR_MAP_SWIZZLE_128B);
    make_map(enc, &tmWp, d_in[8], 3, dims, str, piece, CU_TENSOR_MAP_SWIZZLE_128B);
  }
  {
    cuuint64_t dims[5] = {1024, 2, 2, 4, 128};
    cuuint64_t str[4] = {2048, 8 * 2048, 2 * 2048, 16 * 2048};
    cuuint32_t box[5] = {16, 2, 2, 4, 32};
    make_map(enc, &tmQ, d_in[0], 5, dims, str, box, CU_TENSOR_MAP_SWIZZLE_NONE);
  }
  {
    cuuint64_t dims[3] = {2048, 2, 1024};
    cuuint64_t str[2] = {4096, 8192};
    cuuint32_t box[3] = {64, 1, 16};
    make_map(enc, &tmOb, d_out, 3, dims, str, box, CU_TENSOR_MAP_SWIZZLE_128B);
  }
  {
    cuuint64_t dims[4] = {1024, 256, 2, 4};
    cuuint64_t str[3] = {4096, 2048, 256 * 4096};
    cuuint32_t box[4] = {64, 8, 2, 3};
    make_map(enc, &tmXh, d_in[6], 4, dims, str, box, CU_TENSOR_MAP_SWIZZLE_128B);
  }
  {
    cuuint64_t dims[3] = {64, 1024, 48};
    cuuint64_t str[2] = {6144, 128};
    cuuint32_t box[3] = {64, 64, 4};
    make_map(enc, &tmWh, d_in[7], 3, dims, str, box, CU_TENSOR_MAP_SWIZZLE_128B);
  }
  Params p;
  p.q = (const __nv_bfloat16*)d_in[0];
  p.k = (const __nv_bfloat16*)d_in[1];
  p.v = (const __nv_bfloat16*)d_in[2];
  p.shift_k = (const __nv_bfloat16*)d_in[3];
  p.ssm_k = (const __nv_bfloat16*)d_in[4];
  p.ssm_D = (const __nv_bfloat16*)d_in[5];
  p.x = (const __nv_bfloat16*)d_in[6];
  p.w = (const __nv_bfloat16*)d_in[7];
  p.wo = (const __nv_bfloat16*)d_in[8];
  p.out = (__nv_bfloat16*)d_out;
  p.zero = 0;
  if (coresident) {
    fused_kernel<0><<<NCTA, NTHREADS, SMEM_BYTES>>>(p, tmX, tmW, tmWo, tmWp, tmQ, tmOb, tmXh, tmWh);
  } else {
    fused_kernel<0><<<4, NTHREADS, SMEM_BYTES>>>(p, tmX, tmW, tmWo, tmWp, tmQ, tmOb, tmXh, tmWh);
    fused_kernel<1><<<NCTA, NTHREADS, SMEM_BYTES>>>(p, tmX, tmW, tmWo, tmWp, tmQ, tmOb, tmXh, tmWh);
    fused_kernel<2><<<NCTA, NTHREADS, SMEM_BYTES>>>(p, tmX, tmW, tmWo, tmWp, tmQ, tmOb, tmXh, tmWh);
  }
}
```

```cpp
#include <cuda_runtime.h>
#include <cuda.h>
#include <cuda_bf16.h>
#include <stdint.h>

namespace {

constexpr int SEQ = 2048;
constexpr int DM = 1024;
constexpr int NCTA = 132;
constexpr int NTHREADS = 384;

constexpr int STG1A = 32768;
constexpr int NS1A = 3;
constexpr int STG1B = 12288;
constexpr int NS1B = 5;
constexpr int OFF_1B = NS1A * STG1A;
constexpr int STG2 = 32768;
constexpr int NS2 = 5;
#define G2SEQ 0x0432104321043210ull
constexpr unsigned long long g2_seq() {
  unsigned long long r = G2SEQ;
  for (int kb = 0; kb < 16; kb++)
    for (int j = 0; j < kb; j++)
      if (((G2SEQ >> (4 * j)) & 7) == ((G2SEQ >> (4 * kb)) & 7)) r ^= 8ull << (4 * kb);
  return r;
}
constexpr unsigned long long G2_SEQ = g2_seq();
constexpr int g2_first4() {
  int kb = 0;
  while (((G2SEQ >> (4 * kb)) & 7) != 4) kb++;
  return kb;
}
constexpr int G2_KB4 = g2_first4();
#define POLL0 1500
#define QORD 1
#define BDEL 0
#define XPF 0
#define HPF0 3
#define PF0 8
#define PF1 12
#define PSTEP 1150
#define FPACE 195
#define LEADWG 1
#define LEADKB 15
#define OTMA 1
#define EARLY 1
#define R3 0
#define ENDG 5
__device__ __forceinline__ uint32_t g2_a(int s, int hsel) { return (((0x97524 >> (4 * s)) & 15) ^ (s & 5 ? 0 : hsel)) << 14; }
constexpr int OFF_Q0 = 3 << 14, OFF_Q1 = 8 << 14;
constexpr int STGH = 73728;
constexpr int OFF_KH = 1 * STG2;
constexpr int OFF_OP = 2 * STG2;
constexpr int OFF_T32 = 5 * STG2 - 4096;
constexpr int OFF_X = 5 * STG2;
constexpr int XT = 8192;
__device__ __forceinline__ uint32_t g2_b(int s, int rank) {
  return s < 3 ? (s == 2 ? 6 : s) << 14 : OFF_X + (s - 3) * 2 * XT + (rank ^ 1) * 4096;
}
__device__ __forceinline__ uint32_t g2_bk(int s) { return s < 3 ? 4096 : 4 * XT; }
constexpr int OFF_BAR = OFF_X + 8 * XT;
constexpr int OFF_EX = OFF_BAR + 448;
constexpr int OFF_T16 = 230400;
constexpr int SMEM_BYTES = OFF_T16 + 2048;
static_assert(OFF_1B + NS1B * STG1B <= OFF_T32 && OFF_X % 1024 == 0, "layout");
static_assert(3 * STGH <= OFF_BAR && OFF_EX + 64 <= OFF_T16 && SMEM_BYTES <= 232448, "smem");

constexpr int BAR_FULLA = 0;
constexpr int BAR_EMPTYA = 3;
constexpr int BAR_FULLB = 6;
constexpr int BAR_EMPTYB = 11;
constexpr int BAR_FULL2 = 16;
constexpr int BAR_EMPTY2 = 21;
constexpr int BAR_EMPTY2B = 44;
constexpr int BAR_X = 26;
constexpr int BAR_LAND = 42;
constexpr int BAR_TAB = 28;
constexpr int BAR_U = 29;
constexpr int BAR_H = 30;
constexpr int BAR_STG = 31;
constexpr int BAR_Y = 32;
constexpr int BAR_HALO = 40;
constexpr int BAR_Q = 41;

constexpr int NB_G1DONE = 1;
constexpr int NB_LEAD = 2;
constexpr int NB_G1END = 3;
constexpr int NB_OREADY = 4;
constexpr int NB_CONV = 5;
constexpr int NB_HELP3 = 11;
constexpr int NB_FIRST = 13;

#define REG_MATH 224
#define REG_HELP 56
constexpr int SPIN_LIMIT = 1 << 20;

__device__ __align__(1024) __nv_bfloat16 g_o[SEQ * DM];
__device__ uint32_t g_flag_o[128];
__device__ uint32_t g_flag_h[4];
__device__ uint4 g_halo[128 * 128];
__device__ __align__(128) const uint32_t g_tab[2048] = {
  0x2fd93000,0x2ea72f64,0x2c722da8,0x263e2a1f,0x2ea73000,0xa63e2a1f,0xafd9ada8,0xac72af64,0x2c723000,0xafd9aa1f,0x263eada8,0x2ea72f64,
  0x263e3000,0xac72af64,0x2ea72da8,0xafd9aa1f,0xa63e3000,0x2c72af64,0xaea72da8,0x2fd9aa1f,0xac723000,0x2fd9aa1f,0xa63eada8,0xaea72f64,
  0xaea73000,0x263e2a1f,0x2fd9ada8,0x2c72af64,0xafd93000,0xaea72f64,0xac722da8,0xa63e2a1f,0x263e0000,0x2c722a1f,0x2ea72da8,0x2fd92f64,
  0x2c720000,0x2fd92f64,0x263e2da8,0xaea7aa1f,0x2ea70000,0x263e2f64,0xafd9ada8,0x2c72aa1f,0x2fd90000,0xaea72a1f,0x2c72ada8,0xa63e2f64,
  0x2fd90000,0xaea7aa1f,0x2c722da8,0xa63eaf64,0x2ea70000,0x263eaf64,0xafd92da8,0x2c722a1f,0x2c720000,0x2fd9af64,0x263eada8,0xaea72a1f,
  0x263e0000,0x2c72aa1f,0x2ea7ada8,0x2fd9af64,0xafd93000,0xaea72f64,0xac722da8,0xa63e2a1f,0xaea73000,0x263e2a1f,0x2fd9ada8,0x2c72af64,
  0xac723000,0x2fd9aa1f,0xa63eada8,0xaea72f64,0xa63e3000,0x2c72af64,0xaea72da8,0x2fd9aa1f,0x263e3000,0xac72af64,0x2ea72da8,0xafd9aa1f,
  0x2c723000,0xafd9aa1f,0x263eada8,0x2ea72f64,0x2ea73000,0xa63e2a1f,0xafd9ada8,0xac72af64,0x2fd93000,0x2ea72f64,0x2c722da8,0x263e2a1f,
  0xa63e0000,0xac722a1f,0xaea72da8,0xafd92f64,0xac720000,0xafd92f64,0xa63e2da8,0x2ea7aa1f,0xaea70000,0xa63e2f64,0x2fd9ada8,0xac72aa1f,
  0xafd90000,0x2ea72a1f,0xac72ada8,0x263e2f64,0xafd90000,0x2ea7aa1f,0xac722da8,0x263eaf64,0xaea70000,0xa63eaf64,0x2fd92da8,0xac722a1f,
  0xac720000,0xafd9af64,0xa63eada8,0x2ea72a1f,0xa63e0000,0xac72aa1f,0xaea7ada8,0xafd9af64,0xa63e0000,0xac72aa1f,0xaea7ada8,0xafd9af64,
  0xac720000,0xafd9af64,0xa63eada8,0x2ea72a1f,0xaea70000,0xa63eaf64,0x2fd92da8,0xac722a1f,0xafd90000,0x2ea7aa1f,0xac722da8,0x263eaf64,
  0xafd90000,0x2ea72a1f,0xac72ada8,0x263e2f64,0xaea70000,0xa63e2f64,0x2fd9ada8,0xac72aa1f,0xac720000,0xafd92f64,0xa63e2da8,0x2ea7aa1f,
  0xa63e0000,0xac722a1f,0xaea72da8,0xafd92f64,0x2fd93000,0x2ea72f64,0x2c722da8,0x263e2a1f,0x2ea73000,0xa63e2a1f,0xafd9ada8,0xac72af64,
  0x2c723000,0xafd9aa1f,0x263eada8,0x2ea72f64,0x263e3000,0xac72af64,0x2ea72da8,0xafd9aa1f,0xa63e3000,0x2c72af64,0xaea72da8,0x2fd9aa1f,
  0xac723000,0x2fd9aa1f,0xa63eada8,0xaea72f64,0xaea73000,0x263e2a1f,0x2fd9ada8,0x2c72af64,0xafd93000,0xaea72f64,0xac722da8,0xa63e2a1f,
  0x263e0000,0x2c72aa1f,0x2ea7ada8,0x2fd9af64,0x2c720000,0x2fd9af64,0x263eada8,0xaea72a1f,0x2ea70000,0x263eaf64,0xafd92da8,0x2c722a1f,
  0x2fd90000,0xaea7aa1f,0x2c722da8,0xa63eaf64,0x2fd90000,0xaea72a1f,0x2c72ada8,0xa63e2f64,0x2ea70000,0x263e2f64,0xafd9ada8,0x2c72aa1f,
  0x2c720000,0x2fd92f64,0x263e2da8,0xaea7aa1f,0x263e0000,0x2c722a1f,0x2ea72da8,0x2fd92f64,0xafd93000,0xaea72f64,0xac722da8,0xa63e2a1f,
  0xaea73000,0x263e2a1f,0x2fd9ada8,0x2c72af64,0xac723000,0x2fd9aa1f,0xa63eada8,0xaea72f64,0xa63e3000,0x2c72af64,0xaea72da8,0x2fd9aa1f,
  0x263e3000,0xac72af64,0x2ea72da8,0xafd9aa1f,0x2c723000,0xafd9aa1f,0x263eada8,0x2ea72f64,0x2ea73000,0xa63e2a1f,0xafd9ada8,0xac72af64,
  0x2fd93000,0x2ea72f64,0x2c722da8,0x263e2a1f,0xa63e0000,0xac72aa1f,0xaea7ada8,0xafd9af64,0x2c720000,0x2fd92f64,0x263e2da8,0xaea7aa1f,
  0xaea70000,0xa63eaf64,0x2fd92da8,0xac722a1f,0x2fd90000,0xaea72a1f,0x2c72ada8,0xa63e2f64,0xafd90000,0x2ea72a1f,0xac72ada8,0x263e2f64,
  0x2ea70000,0x263eaf64,0xafd92da8,0x2c722a1f,0xac720000,0xafd92f64,0xa63e2da8,0x2ea7aa1f,0x263e0000,0x2c72aa1f,0x2ea7ada8,0x2fd9af64,
  0x2fd93000,0x2ea72f64,0x2c722da8,0x263e2a1f,0xaea7b000,0x263eaa1f,0x2fd92da8,0x2c722f64,0x2c723000,0xafd9aa1f,0x263eada8,0x2ea72f64,
  0xa63eb000,0x2c722f64,0xaea7ada8,0x2fd92a1f,0xa63e3000,0x2c72af64,0xaea72da8,0x2fd9aa1f,0x2c72b000,0xafd92a1f,0x263e2da8,0x2ea7af64,
  0xaea73000,0x263e2a1f,0x2fd9ada8,0x2c72af64,0x2fd9b000,0x2ea7af64,0x2c72ada8,0x263eaa1f,0x263e0000,0x2c72aa1f,0x2ea7ada8,0x2fd9af64,
  0xac720000,0xafd92f64,0xa63e2da8,0x2ea7aa1f,0x2ea70000,0x263eaf64,0xafd92da8,0x2c722a1f,0xafd90000,0x2ea72a1f,0xac72ada8,0x263e2f64,
  0x2fd90000,0xaea72a1f,0x2c72ada8,0xa63e2f64,0xaea70000,0xa63eaf64,0x2fd92da8,0xac722a1f,0x2c720000,0x2fd92f64,0x263e2da8,0xaea7aa1f,
  0xa63e0000,0xac72aa1f,0xaea7ada8,0xafd9af64,0xafd93000,0xaea72f64,0xac722da8,0xa63e2a1f,0x2ea7b000,0xa63eaa1f,0xafd92da8,0xac722f64,
  0xac723000,0x2fd9aa1f,0xa63eada8,0xaea72f64,0x263eb000,0xac722f64,0x2ea7ada8,0xafd92a1f,0x263e3000,0xac72af64,0x2ea72da8,0xafd9aa1f,
  0xac72b000,0x2fd92a1f,0xa63e2da8,0xaea7af64,0x2ea73000,0xa63e2a1f,0xafd9ada8,0xac72af64,0xafd9b000,0xaea7af64,0xac72ada8,0xa63eaa1f,
  0xafd9b000,0xaea7af64,0xac72ada8,0xa63eaa1f,0x2ea73000,0xa63e2a1f,0xafd9ada8,0xac72af64,0xac72b000,0x2fd92a1f,0xa63e2da8,0xaea7af64,
  0x263e3000,0xac72af64,0x2ea72da8,0xafd9aa1f,0x263eb000,0xac722f64,0x2ea7ada8,0xafd92a1f,0xac723000,0x2fd9aa1f,0xa63eada8,0xaea72f64,
  0x2ea7b000,0xa63eaa1f,0xafd92da8,0xac722f64,0xafd93000,0xaea72f64,0xac722da8,0xa63e2a1f,0xa63e0000,0xac72aa1f,0xaea7ada8,0xafd9af64,
  0x2c720000,0x2fd92f64,0x263e2da8,0xaea7aa1f,0xaea70000,0xa63eaf64,0x2fd92da8,0xac722a1f,0x2fd90000,0xaea72a1f,0x2c72ada8,0xa63e2f64,
  0xafd90000,0x2ea72a1f,0xac72ada8,0x263e2f64,0x2ea70000,0x263eaf64,0xafd92da8,0x2c722a1f,0xac720000,0xafd92f64,0xa63e2da8,0x2ea7aa1f,
  0x263e0000,0x2c72aa1f,0x2ea7ada8,0x2fd9af64,0x2fd9b000,0x2ea7af64,0x2c72ada8,0x263eaa1f,0xaea73000,0x263e2a1f,0x2fd9ada8,0x2c72af64,
  0x2c72b000,0xafd92a1f,0x263e2da8,0x2ea7af64,0xa63e3000,0x2c72af64,0xaea72da8,0x2fd9aa1f,0xa63eb000,0x2c722f64,0xaea7ada8,0x2fd92a1f,
  0x2c723000,0xafd9aa1f,0x263eada8,0x2ea72f64,0xaea7b000,0x263eaa1f,0x2fd92da8,0x2c722f64,0x2fd93000,0x2ea72f64,0x2c722da8,0x263e2a1f,
  0x263e0000,0x2c72aa1f,0x2ea7ada8,0x2fd9af64,0xac720000,0xafd92f64,0xa63e2da8,0x2ea7aa1f,0x2ea70000,0x263eaf64,0xafd92da8,0x2c722a1f,
  0xafd90000,0x2ea72a1f,0xac72ada8,0x263e2f64,0x2fd90000,0xaea72a1f,0x2c72ada8,0xa63e2f64,0xaea70000,0xa63eaf64,0x2fd92da8,0xac722a1f,
  0x2c720000,0x2fd92f64,0x263e2da8,0xaea7aa1f,0xa63e0000,0xac72aa1f,0xaea7ada8,0xafd9af64,0x316c2fbd,0x343e32f7,0x35bc34ff,0x372c3676,
  0x371532c6,0x3a81392e,0x3bef3b71,0x3b7c3bf2,0x397034cf,0x3bfc3b6c,0x38b23b04,0xb40e31e8,0x3ae13631,0x39e73bf5,0xb6e83219,0xbbe8bb13,
  0x3bc23785,0x30be3aa9,0xbbfdb911,0x2a16b9aa,0x3bfe3865,0xb80f37a6,0xb82abc00,0x3bfd376f,0x3b9238fd,0xbb7f2311,0x3805b929,0x31223bde,
  0x3a85398b,0xbb96b742,0x3bff319e,0xbbb82f8b,0xbbe2bbf1,0xbbb7bbcf,0xbb78bb9a,0xbb27bb52,0xbb2cbbd2,0xb8a8ba19,0xb029b5df,0x35a52f59,
  0xb9dfbba1,0x2ba7b5f7,0x3a7a37b2,0x3bbd3bdd,0xb815bb60,0x39662e91,0x3b373bda,0xb0d7377a,0xb3d3bb10,0x3be9386f,0x2a7a3a31,0xbbfeb9a6,
  0x294dbab0,0x3ae53b07,0xbad51fdb,0xab43bb16,0x352fba41,0x35993c00,0xbaebba1d,0x3be531cf,0x38a3b9c5,0xb5173b21,0x2776bbe0,0x34323bf2,
  0x384537dd,0x38ea3899,0x39823937,0x3a0d39c9,0x39463a93,0x3340374e,0xb426a452,0xb979b7c8,0xbb45b924,0xbb32bc00,0xb371b902,0x38d63294,
  0xb08db9a1,0x3b3f379b,0x39583bd7,0xb8252dfb,0x3bea3a2d,0xb3ba3874,0xbb89bb0d,0x36d2b625,0xb6bb387f,0xb8d1bbf5,0x3be73602,0xb546391f,
  0xba00bb01,0x3bff35eb,0xba5c34db,0x3359bab6,0x3ac7b66b,0xb9413933,0x368dbabd,0xb0103bb3,0xbac4baf7,0xba50ba8c,0xb9cdba11,0xb93cb986,
  0x3a04388e,0x3bcb3b1e,0x3bba3c00,0x39d63afe,0x36af3a21,0xb6ffa17f,0xbbc8ba3d,0xba60bbd4,0xbbebb9af,0xb6c6bb0a,0x39f43263,0x3ad83bf7,
  0x30a6b916,0x3bc33aa5,0xb55e3790,0xbb3dbb63,0x3b423a9e,0xba642ec3,0xb0f0bb6a,0x3b8e3a25,0xb94a37bd,0x2884bb6f,0x38db3b9f,0xbbc9b85a,
  0xb840bb54,0x3a093a15,0xbb4cb850,0x3bef3457,0x3a893a4d,0x3af43ac1,0x3b4f3b24,0x3b983b76,0xbb94baba,0xbbe4bbf9,0xba58bb57,0xb699b8f8,
  0x3bfe3b18,0x394f3b5c,0xb109347b,0xbae8b884,0xbbc0bb68,0xa9b1b90c,0x3b8b387a,0x38bc3ba5,0x3ade3ba7,0xb8c1324b,0xb9f0bbf6,0x39eb9648,
  0xb96bbbd6,0x3bbf3487,0xb38939b3,0xb9f8bba3,0x370a3bf3,0xbb47b994,0x3bbc2d65,0xb8ad3889,0xb153bc00,0x37213b9c,0xb97dba90,0x3af138f3,
  0xb89eb8ee,0xb7e8b84a,0xb682b737,0xb50bb5c8,0x35233855,0xb13b2d33,0xb8e0b65f,0xbb4aba45,0xa8e8b764,0x39fc3648,0x3be63bae,0x380a3a9b,
  0xb3eb360e,0xbbfeba35,0xb552baa2,0x3a7334b7,0x381ab4ab,0x3a6f3bd8,0xb95d2e5f,0xb962bc00,0xb9e3327c,0xb402bbac,0x3bc6399d,0xb95434c3,
  0x3b2faf27,0xb6a439bc,0xb41abbf9,0x3a7e3a97,0xbbe3251b,0x3b2ab4f3,0xb9d23894,0x37f3ba49,0x3bce3bb5,0x3bf03be1,0x3bff3bfa,0x3bfb3bff,
  0x2c38b1b6,0x383a34e7,0x3aee39c0,0x3bff3bb2,0xbb81bbf8,0xb53ab999,0x38302ef5,0x3bed3ab3,0xb8cc9cb6,0xbb85bbab,0x2adeb86a,0x3bc5391b,
  0x38c73bf6,0xbadbb232,0xb6ddbba9,0x3b87361a,0x3b833201,0xb0743a39,0xba76bb5e,0x3b352dc9,0xac06bbb0,0x39743b59,0xbbeeb759,0x3aceb2ad,
  0xbbccb5d4,0x3bfb2d00,0xbb7a32de,0x3a54b7d2,0xb30fb44b,0xafefb185,0xa6adacce,0x2c9c25e4,0xbbfcbbdf,0xbacbbb9e,0xb7feb990,0xa81fb463,
  0xb58d2d97,0xbb90b9b8,0xbad1bbf4,0xb05bb85f,0x3a673c00,0xb5763493,0xbbfdbaac,0xb3a2ba29,0x3a6b2e2d,0x38203bd9,0xbb3ab49f,0xb56abb65,
  0xb581bbdc,0x3bec3907,0xb8b7363c,0xb6f4bbf8,0xbbfcb46f,0x39dab654,0xb0423b1b,0xb835bbd3,0xb3283b73,0xac6abbfa,0x35b13bd0,0xb8e5bafb,
  0x38ee3a0d,0xb84aba89,0x37373af4,0xb5c8bb4f,0x35df3a81,0x2f59bbef,0xb88e3b7c,0x3b1eb946,0x2d973ae8,0x39b8bb81,0xbbf4353a,0x385f3830,
  0xb2633b3f,0x3bf7b958,0xb60eb825,0xba353bc0,0xb7853b87,0x3aa9b3d3,0x3911bbe9,0xb9aa2a7a,0xb99d3bbf,0x34c33389,0x3bdcb9f8,0x3907bb83,
  0xbb013be5,0xb5eb394a,0x34db2884,0x3ab6b8db,0xbbd03bfb,0xbafb3b7a,0xb98b3a54,0xb74238a3,0x3a4db93c,0xbac1389e,0x3b24b7e8,0xbb763682,
  0x3b71b8a8,0xbbf23029,0x3a9335a5,0xb74eba04,0x3bf8b80a,0xb999b58d,0xaef53b90,0x3ab3bad1,0x3bd7b6c6,0xadfbb9f4,0xbb683ad8,0x390c33eb,
  0x3b10b56a,0x386fbbc2,0xba3130be,0xb9a63bfd,0x39b3b402,0x3ba3bbc6,0x3201b954,0xba393581,0x37bdb122,0x3b6fba00,0x3b9fbbff,0x385aba5c,
  0x32deac6a,0x37d2b5b1,0x39c5b8e5,0x3b21ba85,0x344b3b98,0xb185bbce,0x2cce3bf0,0x25e4bbff,0xbc003340,0x3afe3426,0xb855b979,0x2d333b94,
  0x34cfbbed,0xbb6c39df,0x3b042ba7,0xb1e8ba7a,0x3aa2a9b1,0x34b7bb8b,0xbc0038bc,0x349338cc,0xba2d3bfe,0x387430a6,0x3b0dbbc3,0xb625b55e,
  0xb63cb074,0xbbf83a76,0xb8653b35,0x37a6294d,0x3bf3bbc9,0x3994bb2f,0x2d65b6a4,0xb889341a,0xb19e3517,0x2f8b2776,0x366bb432,0x3933b840,
  0x3bb5b50b,0xbbe1330f,0x3bfaafef,0xbbff26ad,0xa4523bcb,0x37c8bbba,0xbaba39d6,0x3bf9b523,0xbba1305b,0x35f73970,0x37b2bbfc,0xbbdd38b2,
  0x387abbfe,0xbba53552,0x9cb63a73,0x3babba67,0x39162a16,0x3aa5bbea,0xb790b3ba,0xbb633b89,0xbb5e3bec,0xadc938b7,0x3ab0b6f4,0x3b07bbfe,
  0xaf27b359,0xb9bc370a,0xbbf93b47,0xba973bbc,0x3be0bb96,0x3bf2bbff,0x3b54bbb8,0x3a15bac7,0xafbd3bfb,0x32f7bbe2,0xb4ff3bb7,0x3676bb78,
  0x365fbbe4,0xba453a58,0x3bdfb699,0xbb9eac38,0xb9243bbd,0x3c00b6af,0xb902b6ff,0xb2943bc8,0x3aacbb85,0xba29aade,0xb6313bc5,0x3bf5b815,
  0xbba73b3d,0x324b381a,0x3bf6ba6f,0x9648b95d,0x3c00bae5,0x376fbad5,0xb87f2b43,0xbbf53b42,0xbbb03a7e,0xbb593bfc,0xb75939da,0x32ad3042,
  0x3abdba09,0x3bb3bb4c,0x3c00bbef,0x3b9cbbe3,0x3bf12c9c,0xbbcfb16c,0x3b9a343e,0xbb52b5bc,0xbb57b13b,0x38f838e0,0xb1b6bb4a,0xb4e73bfc,
  0x3a21340e,0x217fbb45,0xba3d3b32,0x3bd4b371,0xb86ab576,0xb91b3bfd,0x3b60b3a2,0x2e91bae1,0x34ab36d2,0x3bd8bade,0xae5fb8c1,0xbc0039f0,
  0x9fdbb80f,0xbb16382a,0xba9e3bfd,0x2ec336bb,0xb46f38ad,0x3654ac06,0x3b1bb974,0x3bd3bbee,0x3850b941,0x3457b68d,0xa51bb010,0xb4f33153,
  0xb7dd3b27,0x3899bac4,0xb9373a50,0x39c9b9cd,0x3990383a,0xb463baee,0xb2c63bff,0x392ebb2c,0x3b18ba60,0xbb5c28e8,0x347b39fc,0x3884bbe6,
  0xb219b966,0xbb133b37,0x39a130d7,0x379bbbeb,0xbbf63962,0xb2323a6b,0x3ba9b820,0x361abb3a,0xb6023a64,0x391fb0f0,0x3bd6bb8e,0x3487b9e3,
  0x3a41b835,0x3c00bb92,0x3a1dbb7f,0x31cfb805,0x3a90bb2a,0x38f3b9d2,0x35d4b7f3,0x2d00b328,0x3af7372c,0xba8cb845,0x3a1138ea,0xb986b982,
  0x39c0bacb,0xbbb237fe,0x3bd2a81f,0xba19b715,0xb764b8d6,0xb6483bfe,0x3baeb94f,0xba9bb109,0xbbda39e7,0x377a36e8,0x39afbbe8,0xbb0a308d,
  0xae2d39eb,0x3bd9b8c7,0x349fbadb,0xbb6536dd,0x3b6ab8d1,0x3a25bbe7,0xb27cb546,0xbbac396b,0x38fdbace,0xa311b52f,0xb9293599,0xbbde3aeb,
  0xb8943721,0xba49397d,0xbb733af1,0xbbfa3bcc,0xbbfb3bff,0xbbe23bf1,0xbbb73bcf,0xbb783b9a,0xbb7c3bf2,0xb9463a93,0xb340374e,0x3426a452,
  0xba603bd4,0xa8e83764,0x39fcb648,0x3be6bbae,0xb8bc3ba5,0x38cc9cb6,0x3b85bbab,0xaadeb86a,0xb56a3b65,0x3bc2b785,0x30bebaa9,0xbbfd3911,
  0xab433b16,0x3b42ba9e,0xba64aec3,0xb0f03b6a,0x33593ab6,0x370abbf3,0xbb473994,0x3bbcad65,0x37f33a49,0xb328bb73,0xac6a3bfa,0x35b1bbd0,
  0xac9c25e4,0xb16c2fbd,0xb43e32f7,0xb5bc34ff,0xb5a52f59,0xba04388e,0xbbcb3b1e,0xbbba3c00,0xb8d63294,0xbbfe3b18,0xb94f3b5c,0x3109347b,
  0xba7334b7,0xba673c00,0x35763493,0x3bfdbaac,0xbb87361a,0xb3d33b10,0x3be9b86f,0x2a7aba31,0xbbfd376f,0x36bb387f,0x38d1bbf5,0xbbe73602,
  0xbbc9385a,0x3b2f2f27,0xb6a4b9bc,0xb41a3bf9,0xbaf138f3,0x3bccb5d4,0xbbfb2d00,0x3b7a32de,0xbb273b52,0xbac43af7,0xba503a8c,0xb9cd3a11,
  0x3979b7c8,0x3b94baba,0x3be4bbf9,0x3a58bb57,0x380aba9b,0xb58dad97,0xbb9039b8,0xbad13bf4,0xbbc5391b,0xb8153b60,0x3966ae91,0x3b37bbda,
  0x2a1639aa,0x3beaba2d,0xb3bab874,0xbb893b0d,0x3b8eba25,0xb9e3b27c,0xb4023bac,0x3bc6b99d,0xb8adb889,0xac063bb0,0x3974bb59,0xbbee3759,
  0xb8e53afb,0x3a85b98b,0xbb963742,0x3bffb19e,0xb72c3676,0xb84537dd,0xb8ea3899,0xb9823937,0xb9d63afe,0xb5233855,0x313b2d33,0x38e0b65f,
  0x3ae8b884,0x3b81bbf8,0x353ab999,0xb8302ef5,0x33a2ba29,0xbae13631,0xb9e73bf5,0x36e83219,0xbbfe39a6,0x30a63916,0x3bc3baa5,0xb55eb790,
  0x3546391f,0x396bbbd6,0xbbbf3487,0x338939b3,0x3a7eba97,0xbbfc346f,0x39da3654,0xb042bb1b,0xba54b7d2,0x38a339c5,0xb517bb21,0x27763be0,
  0xb93c3986,0xb89e38ee,0xb7e8384a,0xb6823737,0x3699b8f8,0xac38b1b6,0xb83a34e7,0xbaee39c0,0xb05b385f,0x3970b4cf,0x3bfcbb6c,0x38b2bb04,
  0xb0d7b77a,0xbbeb39af,0xb6c63b0a,0x39f4b263,0x36d23625,0x3adebba7,0xb8c1b24b,0xb9f03bf6,0xb954b4c3,0xb5813bdc,0x3becb907,0xb8b7b63c,
  0x3ace32ad,0xb52fba41,0xb5993c00,0x3aebba1d,0xbbb8af8b,0x3ac7366b,0xb941b933,0x368d3abd,0xba0d39c9,0xba893a4d,0xbaf43ac1,0xbb4f3b24,
  0x3b4aba45,0x3bfcbbdf,0x3acbbb9e,0x37feb990,0xbbed3ab3,0xb9df3ba1,0x2ba735f7,0x3a7ab7b2,0x3be8bb13,0x308db9a1,0xbb3f379b,0xb9583bd7,
  0xbb3d3b63,0x381a34ab,0x3a6fbbd8,0xb95dae5f,0x39f8bba3,0xbb833201,0x30743a39,0x3a76bb5e,0xb8353bd3,0x3b92b8fd,0xbb7fa311,0x38053929,
  0x3432bbf2,0xb8403b54,0x3a09ba15,0xbb4c3850,0xb50b35c8,0xb30f344b,0xafef3185,0xa6ad2cce,0xbbff3bb2,0xbb2c3bd2,0xb8a83a19,0xb02935df,
  0xb40eb1e8,0xbb453924,0xbb323c00,0xb3713902,0x3ad8bbf7,0xb3ebb60e,0xbbfe3a35,0xb5523aa2,0x39eb1648,0x38c7bbf6,0xbadb3232,0xb6dd3ba9,
  0xb6f43bf8,0x3bfeb865,0xb80fb7a6,0xb82a3c00,0xbbe531cf,0x394a37bd,0xa884bb6f,0xb8db3b9f,0xb010bbb3,0xb1533c00,0x3721bb9c,0xb97d3a90,
  0xbb983b76,0xbbce3bb5,0xbbf03be1,0xbbff3bfa,0x281fb463,0xb71532c6,0xba81392e,0xbbef3b71,0x3bbdbbdd,0x36afba21,0xb6ff217f,0xbbc83a3d,
  0x38252dfb,0x3bc0bb68,0x29b1b90c,0xbb8b387a,0xb9623c00,0x3a6bae2d,0x3820bbd9,0xbb3a349f,0xbb352dc9,0x294d3ab0,0x3ae5bb07,0xbad59fdb,
  0x3122bbde,0xba003b01,0x3bffb5eb,0xba5cb4db,0x3befb457,0xbbe3a51b,0x3b2a34f3,0xb9d2b894,0x39c939cd,0xba4db93c,0x3ac1389e,0xbb24b7e8,
  0x3b1e3946,0xbc00b340,0x3afeb426,0xb8553979,0x3bdd38b2,0xba21340e,0xa17fbb45,0x3a3d3b32,0x3bf53815,0xb2193966,0xbb13bb37,0x39a1b0d7,
  0x3b6536dd,0x37853b87,0xbaa9b3d3,0xb911bbe9,0x3a393581,0x3b5e3bec,0x2dc938b7,0xbab0b6f4,0x3889341a,0x3bb03a7e,0x3b593bfc,0x375939da,
  0x34f33153,0x38943721,0x3a49397d,0x3b733af1,0xb9863982,0x38eeba0d,0xb84a3a89,0x3737baf4,0xb74e3a04,0xa452bbcb,0x37c83bba,0xbabab9d6,
  0xb1e83a7a,0xb924bbbd,0x3c0036af,0xb90236ff,0x2e913ae1,0xbbdab9e7,0x377ab6e8,0x39af3be8,0x361a3b3a,0xbb10b56a,0xb86fbbc2,0x3a3130be,
  0x39073b83,0xb63c3074,0xbbf8ba76,0xb865bb35,0x3a973bbc,0x346f38ad,0xb654ac06,0xbb1bb974,0x3b9c3be3,0x3a903b2a,0x38f339d2,0x35d437f3,
  0x3b763682,0xbbb5b50b,0x3be1330f,0xbbfaafef,0x2d33bb94,0x365f3be4,0xba45ba58,0x3bdf3699,0xbbd4b371,0x3764b8d6,0x36483bfe,0xbbaeb94f,
  0x379b3beb,0xbbd7b6c6,0x2dfbb9f4,0x3b683ad8,0x39aa2a7a,0x3a2d3bfe,0xb87430a6,0xbb0dbbc3,0xbb07bbfe,0x1fdbb80f,0x3b16382a,0x3a9e3bfd,
  0xb2ad3042,0xba41b835,0xbc00bb92,0xba1dbb7f,0x3bfa3bcc,0x3bd03bfb,0x3afb3b7a,0x398b3a54,0xb5c83b4f,0x344bbb98,0xb1853bce,0x2ccebbf0,
  0x3bf93523,0xbb57313b,0x38f8b8e0,0xb1b63b4a,0xb294bbc8,0x3b183a60,0xbb5ca8e8,0x347bb9fc,0xbb0ab08d,0xb263bb3f,0x3bf73958,0xb60e3825,
  0x39a63bfd,0xb9162a16,0xbaa5bbea,0x3790b3ba,0x37a6a94d,0x3c003ae5,0x376f3ad5,0xb87fab43,0xbbd3bbee,0xb8fdbace,0x2311b52f,0x39293599,
  0x2d003328,0xb2deac6a,0xb7d2b5b1,0xb9c5b8e5,0x3bff26ad,0xbbf12c9c,0x3bcfb16c,0xbb9a343e,0xbb9e2c38,0x3990b83a,0xb4633aee,0xb2c6bbff,
  0x3a9bb109,0xad973ae8,0xb9b8bb81,0x3bf4353a,0xb90c33eb,0xb87abbfe,0x3ba53552,0x1cb63a73,0x3625b55e,0x3ba73b3d,0xb24b381a,0xbbf6ba6f,
  0xaec336bb,0xbb6ab8d1,0xba25bbe7,0x327cb546,0xb1cfb805,0x37bd3122,0x3b6f3a00,0x3b9f3bff,0x374238a3,0x319e3517,0xaf8b2776,0xb66bb432,
  0x25e43bff,0xafbdbbfb,0x32f73be2,0xb4ffbbb7,0xb4e7bbfc,0x39c03acb,0xbbb2b7fe,0x3bd2281f,0x38843be6,0xbbf8b80a,0x3999b58d,0x2ef53b90,
  0xba35bbc0,0x3aa229b1,0x34b73b8b,0xbc00b8bc,0x3b633b89,0xb4ab36d2,0xbbd8bade,0x2e5fb8c1,0xbbf5bb42,0xb602ba64,0x391f30f0,0x3bd63b8e,
  0x3bde3aeb,0x3b013be5,0x35eb394a,0xb4db2884,0xbb21ba85,0xbbe0bb96,0xbbf2bbff,0xbb54bbb8,0x3b52b5bc,0xbaf7372c,0x3a8cb845,0xba1138ea,
  0x392e3b2c,0xbb71b8a8,0x3bf23029,0xba9335a5,0xb85f3830,0xb4cfbbed,0x3b6c39df,0xbb042ba7,0xbbabba67,0x386ab576,0x391b3bfd,0xbb60b3a2,
  0x1648b95d,0x3bf63962,0x32323a6b,0xbba9b820,0x3bac396b,0x399d3bbf,0xb4c33389,0xbbdcb9f8,0x385a3a5c,0xaf273359,0xb9bcb70a,0xbbf9bb47,
  0xb933b840,0xbabdba09,0xbbb3bb4c,0xbc00bbef,0x36763b78,0xb7ddbb27,0x38993ac4,0xb937ba50,0xba193715,0x35dfba81,0x2f593bef,0xb88ebb7c,
  0xbab3bad1,0x3ba1305b,0xb5f73970,0xb7b2bbfc,0x3493b8cc,0x3aac3b85,0xba292ade,0xb631bbc5,0x3c0039f0,0x2e2d39eb,0xbbd9b8c7,0xb49fbadb,
  0x348739e3,0xb9b3b402,0xbba3bbc6,0xb201b954,0xbab6b8db,0xbbf3bbc9,0xb994bb2f,0xad65b6a4,0xba15bac7,0xb850b941,0xb457b68d,0x251bb010,
  0xb9cfbb16,0x30ac2a31,0x3b9c3bf1,0xb493ae2d,0xb76fb8b4,0x35a133e3,0x3a1d3afe,0xb902b76f,0xb3e3b5a1,0x38b4376f,0x376f3902,0xbafeba1d,
  0xaa31b0ac,0x3b1639cf,0x2e2d3493,0xbbf1bb9c,0xb956ba74,0x305f29cc,0x3b633bd2,0xb44badc9,0xb6e7b859,0x353f335e,0x39d23ab6,0xb8bcb6ff,
  0xb35eb53f,0x385936e7,0x36ff38bc,0xbab6b9d2,0xa9ccb05f,0x3a743956,0x2dc9344b,0xbbd2bb63,0xb8e3b9de,0x30122967,0x3b1e3ba1,0xb402ad65,
  0xb662b801,0x34de32da,0x39823a67,0xb874b68d,0xb2dab4de,0x38013662,0x368d3874,0xba67b982,0xa967b012,0x39de38e3,0x2d653402,0xbba1bb1e,
  0xb876b952,0x2f8c2902,0x3ace3b60,0xb371ad00,0xb5e1b758,0x347e3257,0x392e3a11,0xb82ab61a,0xb257b47e,0x375835e1,0x361a382a,0xba11b92e,
  0xa902af8c,0x39523876,0x2d003371,0xbb60bace,0xb80db8ce,0x2ef3289e,0x3a733b10,0xb2deac9c,0xb562b6b3,0x342031d5,0x38d639b3,0xb7bdb5a5,
  0xb1d5b420,0x36b33562,0x35a537bd,0xb9b3b8d6,0xa89eaef3,0x38ce380d,0x2c9c32de,0xbb10ba73,0xb750b851,0x2e5a2839,0x3a0d3ab0,0xb24bac38,
  0xb4e5b613,0x33863153,0x387a394f,0xb721b52f,0xb153b386,0x361334e5,0x352f3721,0xb94fb87a,0xa839ae5a,0x38513750,0x2c38324b,0xbab0ba0d,
  0xb68eb7b4,0x2dc227a9,0x399d3a41,0xb1b6aba7,0xb46ab577,0x32cd30d2,0x381a38e5,0xb682b4b7,0xb0d2b2cd,0x3577346a,0x34b73682,0xb8e5b81a,
  0xa7a9adc2,0x37b4368e,0x2ba731b6,0xba41b99d,0xb5d2b6d1,0x2d2a26e0,0x392439c5,0xb122aade,0xb3e3b4de,0x32163052,0x376f3874,0xb5dfb43e,
  0xb052b216,0x34de33e3,0x343e35df,0xb874b76f,0xa6e0ad2a,0x36d135d2,0x2ade3122,0xb9c5b924,0xb51cb5f6,0x2c932617,0x38a3393c,0xb08daa16,
  0xb2f4b448,0x31602fa5,0x36a437fe,0xb53ab389,0xafa5b160,0x344832f4,0x3389353a,0xb7feb6a4,0xa617ac93,0x35f6351c,0x2a16308d,0xb93cb8a3,
  0xb46ab523,0x2bf6254d,0x381a38a8,0xafefa94d,0xb209b36b,0x30ac2ea7,0x35d4370a,0xb493b294,0xaea7b0ac,0x336b3209,0x32943493,0xb70ab5d4,
  0xa54dabf6,0x3523346a,0x294d2fef,0xb8a8b81a,0xb378b456,0x2ac82484,0x3715380a,0xaec3a884,0xb120b24a,0x2ff22da9,0x34ff360e,0xb3d3b19e,
  0xada9aff2,0x324a3120,0x319e33d3,0xb60eb4ff,0xa484aac8,0x34563378,0x28842ec3,0xb80ab715,0xb223b31c,0x29992376,0x35eb36c6,0xad97a776,
  0xb039b12d,0x2e8d2cac,0x3426350b,0xb27cb0a6,0xacacae8d,0x312d3039,0x30a6327c,0xb50bb426,0xa376a999,0x331c3223,0x27762d97,0xb6c6b5eb,
  0xb0d2b194,0x286b21e4,0x34b7356a,0xac6aa5e4,0xaea7b012,0x2d2a2b5f,0x32943402,0xb122af59,0xab5fad2a,0x30122ea7,0x2f593122,0xb402b294,
  0xa1e4a86b,0x319430d2,0x25e42c6a,0xb56ab4b7,0xaf0cb012,0x267b2052,0x32f73402,0xaa7aa452,0xacdeadf5,0x2b912967,0x30d731e8,0xaf8bad65,
  0xa967ab91,0x2df52cde,0x2d652f8b,0xb1e8b0d7,0xa052a67b,0x30122f0c,0x24522a7a,0xb402b2f7,0xac79ad2a,0x24201d7f,0x30743122,0xa81fa17f,
  0xaa31ab91,0x28d026e0,0x2e2d2f8b,0xacceaade,0xa6e0a8d0,0x2b912a31,0x2ade2cce,0xaf8bae2d,0x9d7fa420,0x2d2a2c79,0x217f281f,0xb122b074,
  0xa7a9a86b,0x1f1218b6,0x2ba72c6a,0xa3119cb6,0xa54da67b,0x242021e4,0x294d2a7a,0xa81fa5e4,0xa1e4a420,0x267b254d,0x25e4281f,0xaa7aa94d,
  0x98b69f12,0x286b27a9,0x1cb62311,0xac6aaba7,0x211b21e4,0x98b69248,0xa51ba5e4,0x1cb61648,0x1f122052,0x9d7f9bdb,0xa311a452,0x217f1fdb,
  0x1bdb1d7f,0xa0529f12,0x9fdba17f,0x24522311,0x124818b6,0xa1e4a11b,0x96489cb6,0x25e4251b,0x2a632b5f,0xa1e49bdb,0xae5faf59,0x25e41fdb,
  0x286b2967,0xa6e0a4e9,0xac6aad65,0x2ade28e8,0x24e926e0,0xa967a86b,0xa8e8aade,0x2d652c6a,0x1bdb21e4,0xab5faa63,0x9fdba5e4,0x2f592e5f,
  0x2dc22ea7,0xa54d9f12,0xb1b6b294,0x294d2311,0x2bf62cde,0xaa31a86b,0xafefb0d7,0x2e2d2c6a,0x286b2a31,0xacdeabf6,0xac6aae2d,0x30d72fef,
  0x1f12254d,0xaea7adc2,0xa311a94d,0x329431b6,0x302c30d2,0xa7a9a11b,0xb41ab4b7,0x2ba7251b,0x2dc22f0c,0xac79aa63,0xb1b6b2f7,0x30742e5f,
  0x2a632c79,0xaf0cadc2,0xae5fb074,0x32f731b6,0x211b27a9,0xb0d2b02c,0xa51baba7,0x34b7341a,0x317a3257,0xa902a2ad,0xb552b61a,0x2d0026ad,
  0x2f8c309f,0xaddcac2e,0xb371b487,0x31cf3029,0x2c2e2ddc,0xb09faf8c,0xb029b1cf,0x34873371,0x22ad2902,0xb257b17a,0xa6adad00,0x361a3552,
  0x32cd33e3,0xaa31a420,0xb682b76f,0x2e2d281f,0x30ac31bb,0xaf3fad2a,0xb493b58d,0x33283122,0x2d2a2f3f,0xb1bbb0ac,0xb122b328,0x358d3493,
  0x24202a31,0xb3e3b2cd,0xa81fae2d,0x376f3682,0x341334bc,0xab5fa4e9,0xb7a6b85a,0x2f5928e8,0x319432da,0xb052ae28,0xb56ab68d,0x343e3219,
  0x2e283052,0xb2dab194,0xb219b43e,0x368d356a,0x24e92b5f,0xb4bcb413,0xa8e8af59,0x385a37a6,0x34c3358c,0xac47a5b2,0xb85fb8f3,0x304229b1,
  0x327e33fd,0xb106af26,0xb63cb785,0x34e7330f,0x2f263106,0xb3fdb27e,0xb30fb4e7,0x3785363c,0x25b22c47,0xb58cb4c3,0xa9b1b042,0x38f3385f,
  0x35773662,0xacdea67b,0xb8e5b982,0x30d72a7a,0x336b3493,0xb1bbb012,0xb70ab83a,0x358d3402,0x301231bb,0xb493b36b,0xb402b58d,0x383a370a,
  0x267b2cde,0xb662b577,0xaa7ab0d7,0x398238e5,0x36303741,0xad76a744,0xb962ba04,0x316c2b43,0x342e352a,0xb271b092,0xb7d2b8ad,0x3631347b,
  0x30923271,0xb52ab42e,0xb47bb631,0x38ad37d2,0x27442d76,0xb741b630,0xab43b16c,0x3a043962,0x36ee3815,0xae0ea807,0xb9d6ba7a,0x32012c06,
  0x34a735c4,0xb329b113,0xb84ab91b,0x36d234f3,0x31133329,0xb5c4b4a7,0xb4f3b6d2,0x391b384a,0x28072e0e,0xb815b6ee,0xac06b201,0x3a7a39d6,
  0x37b4388e,0xaea7a86b,0xba41bae1,0x32942c6a,0x35233662,0xb3e3b194,0xb8a8b982,0x376f356a,0x319433e3,0xb662b523,0xb56ab76f,0x398238a8,
  0x286b2ea7,0xb88eb7b4,0xac6ab294,0x3ae13a41,0x3841390f,0xaf3fa8d0,0xbaa2bb3a,0x33282cce,0x35a13705,0xb44fb216,0xb902b9e3,0x380535df,
  0x3216344f,0xb705b5a1,0xb5dfb805,0x39e33902,0x28d02f3f,0xb90fb841,0xacceb328,0x3b3a3aa2,0x38ac3997,0xafd8a935,0xbaf7bb83,0x33ba2d33,
  0x362137ac,0xb4aeb298,0xb958ba3d,0x38503654,0x329834ae,0xb7acb621,0xb654b850,0x3a3d3958,0x29352fd8,0xb997b8ac,0xad33b3ba,0x3b833af7,
  0x391c3a28,0xb039a999,0xbb42bbbc,0x34262d97,0x36a4382d,0xb50eb31c,0xb9aaba90,0x389936c6,0x331c350e,0xb82db6a4,0xb6c6b899,0x3a9039aa,
  0x29993039,0xba28b91c,0xad97b426,0x3bbc3b42,0x39923ac3,0xb085a9fe,0xbb81bbe3,0x346f2dfb,0x372a3886,0xb570b3a0,0xb9f8badb,0x38e03737,
  0x33a03570,0xb886b72a,0xb737b8e0,0x3adb39f8,0x29fe3085,0xbac3b992,0xadfbb46f,0x3be33b81,
};

#define PROF(slot) do {} while (0)
#define PROF_DUMP() do {} while (0)
#define PROFA(slot, dep) do {} while (0)
#define PROF3(slot) do {} while (0)
#define PROF2(slot) do {} while (0)

__device__ __forceinline__ uint32_t smem_u32(const void* p) { return (uint32_t)__cvta_generic_to_shared(p); }

__device__ __forceinline__ void mbar_init(uint32_t a, uint32_t c) {
  asm volatile("mbarrier.init.shared::cta.b64 [%0], %1;\n" ::"r"(a), "r"(c) : "memory");
}
__device__ __forceinline__ void mbar_expect_tx(uint32_t a, uint32_t bytes) {
  asm volatile("mbarrier.arrive.expect_tx.shared::cta.b64 _, [%0], %1;\n" ::"r"(a), "r"(bytes) : "memory");
}
__device__ __forceinline__ void mbar_arrive_cluster(uint32_t cluster_addr) {
  asm volatile("mbarrier.arrive.shared::cluster.b64 _, [%0];\n" ::"r"(cluster_addr) : "memory");
}
__device__ __forceinline__ void mbar_arrive_cluster_n(uint32_t cluster_addr, uint32_t n) {
  asm volatile("mbarrier.arrive.shared::cluster.b64 _, [%0], %1;\n" ::"r"(cluster_addr), "r"(n) : "memory");
}
__device__ __forceinline__ bool mbar_try(uint32_t a, uint32_t parity) {
  uint32_t ok;
  asm volatile("{\n.reg .pred p;\nmbarrier.try_wait.parity.shared::cta.b64 p, [%1], %2;\nselp.u32 %0, 1, 0, p;\n}\n"
               : "=r"(ok) : "r"(a), "r"(parity) : "memory");
  return ok;
}
__device__ __forceinline__ void mbar_wait(uint32_t a, uint32_t parity) {
  if (mbar_try(a, parity)) return;
#pragma unroll 1
  for (int n = 0; n < SPIN_LIMIT; n++)
    if (mbar_try(a, parity)) break;
}
__device__ __forceinline__ bool elect_one() {
  uint32_t p;
  asm volatile("{\n.reg .pred P;\nelect.sync _|P, 0xffffffff;\nselp.u32 %0, 1, 0, P;\n}\n" : "=r"(p));
  return p;
}
__device__ __forceinline__ uint32_t mapa(uint32_t a, uint32_t rank) {
  uint32_t r;
  asm volatile("mapa.shared::cluster.u32 %0, %1, %2;\n" : "=r"(r) : "r"(a), "r"(rank));
  return r;
}
__device__ __forceinline__ void nb_sync(int id, int n) { asm volatile("bar.sync %0, %1;\n" ::"r"(id), "r"(n) : "memory"); }
__device__ __forceinline__ void nb_arrive(int id, int n) { asm volatile("bar.arrive %0, %1;\n" ::"r"(id), "r"(n) : "memory"); }
__device__ __forceinline__ void cluster_sync_all() {
  asm volatile("barrier.cluster.arrive.relaxed.aligned;\nbarrier.cluster.wait.aligned;\n" ::: "memory");
}
__device__ __forceinline__ void fence_async_smem() { asm volatile("fence.proxy.async.shared::cta;\n" ::: "memory"); }
__device__ __forceinline__ void fence_async_all() { asm volatile("fence.proxy.async.global;\n" ::: "memory"); }

__device__ __forceinline__ void tma_load_3d(uint32_t dst, const CUtensorMap* tm, uint32_t bar, int c0, int c1, int c2) {
  asm volatile(
      "cp.async.bulk.tensor.3d.shared::cluster.global.mbarrier::complete_tx::bytes [%0], [%1, {%3, %4, %5}], [%2];\n"
      ::"r"(dst), "l"(tm), "r"(bar), "r"(c0), "r"(c1), "r"(c2) : "memory");
}
__device__ __forceinline__ void tma_load_4d(uint32_t dst, const CUtensorMap* tm, uint32_t bar, int c0, int c1, int c2, int c3) {
  asm volatile(
      "cp.async.bulk.tensor.4d.shared::cluster.global.mbarrier::complete_tx::bytes [%0], [%1, {%3, %4, %5, %6}], [%2];\n"
      ::"r"(dst), "l"(tm), "r"(bar), "r"(c0), "r"(c1), "r"(c2), "r"(c3) : "memory");
}
__device__ __forceinline__ void tma_load_3d_mc(uint32_t dst, const CUtensorMap* tm, uint32_t bar, int c0, int c1, int c2) {
  asm volatile(
      "cp.async.bulk.tensor.3d.shared::cluster.global.mbarrier::complete_tx::bytes.multicast::cluster [%0], [%1, {%3, %4, %5}], [%2], %6;\n"
      ::"r"(dst), "l"(tm), "r"(bar), "r"(c0), "r"(c1), "r"(c2), "h"((uint16_t)3) : "memory");
}
__device__ __forceinline__ void bulk_load(uint32_t dst, const void* src, uint32_t bytes, uint32_t bar) {
  asm volatile("cp.async.bulk.shared::cluster.global.mbarrier::complete_tx::bytes [%0], [%1], %2, [%3];\n"
               ::"r"(dst), "l"(src), "r"(bytes), "r"(bar) : "memory");
}
__device__ __forceinline__ void tma_store_3d(const CUtensorMap* tm, uint32_t src, int c0, int c1, int c2) {
  asm volatile("cp.async.bulk.tensor.3d.global.shared::cta.bulk_group [%0, {%2, %3, %4}], [%1];\n"
               ::"l"(tm), "r"(src), "r"(c0), "r"(c1), "r"(c2) : "memory");
}
__device__ __forceinline__ void bulk_commit() { asm volatile("cp.async.bulk.commit_group;\n" ::: "memory"); }
__device__ __forceinline__ void bulk_wait0() { asm volatile("cp.async.bulk.wait_group 0;\n" ::: "memory"); }
__device__ __forceinline__ void prefetch_tmap(const CUtensorMap* tm) {
  asm volatile("prefetch.tensormap [%0];\n" ::"l"(tm) : "memory");
}

__device__ __forceinline__ void wg_fence() { asm volatile("wgmma.fence.sync.aligned;\n" ::: "memory"); }
__device__ __forceinline__ void wg_commit() { asm volatile("wgmma.commit_group.sync.aligned;\n" ::: "memory"); }
template <int N> __device__ __forceinline__ void wg_wait() {
  asm volatile("wgmma.wait_group.sync.aligned %0;\n" ::"n"(N) : "memory");
}
__device__ __forceinline__ uint64_t mkdesc(uint32_t addr, uint32_t lbo, uint32_t sbo, uint32_t swz) {
  return (uint64_t)((addr & 0x3FFFF) >> 4) | ((uint64_t)(lbo >> 4) << 16) | ((uint64_t)(sbo >> 4) << 32) |
         ((uint64_t)swz << 62);
}

#define R4(d, o) "+f"(d[o + 0]), "+f"(d[o + 1]), "+f"(d[o + 2]), "+f"(d[o + 3])
#define R8(d, o) R4(d, o), R4(d, o + 4)
#define R16(d, o) R8(d, o), R8(d, o + 8)
#define R32(d, o) R16(d, o), R16(d, o + 16)
#define R64(d, o) R32(d, o), R32(d, o + 32)

__device__ __forceinline__ void wgmma_n192(float (&d)[96], uint64_t da, uint64_t db, uint32_t acc) {
  asm volatile(
      "{\n.reg .pred p;\nsetp.ne.u32 p, %98, 0;\n"
      "wgmma.mma_async.sync.aligned.m64n192k16.f32.bf16.bf16 "
      "{%0,%1,%2,%3,%4,%5,%6,%7,%8,%9,%10,%11,%12,%13,%14,%15,%16,%17,%18,%19,%20,%21,%22,%23,%24,%25,%26,%27,%28,%29,%30,%31,"
      "%32,%33,%34,%35,%36,%37,%38,%39,%40,%41,%42,%43,%44,%45,%46,%47,%48,%49,%50,%51,%52,%53,%54,%55,%56,%57,%58,%59,%60,%61,%62,%63,"
      "%64,%65,%66,%67,%68,%69,%70,%71,%72,%73,%74,%75,%76,%77,%78,%79,%80,%81,%82,%83,%84,%85,%86,%87,%88,%89,%90,%91,%92,%93,%94,%95}, "
      "%96, %97, p, 1, 1, 0, 1;\n}\n"
      : R64(d, 0), R32(d, 64)
      : "l"(da), "l"(db), "r"(acc));
}
__device__ __forceinline__ void wgmma_n128(float (&d)[64], uint64_t da, uint64_t db, uint32_t acc) {
  asm volatile(
      "{\n.reg .pred p;\nsetp.ne.u32 p, %66, 0;\n"
      "wgmma.mma_async.sync.aligned.m64n128k16.f32.bf16.bf16 "
      "{%0,%1,%2,%3,%4,%5,%6,%7,%8,%9,%10,%11,%12,%13,%14,%15,%16,%17,%18,%19,%20,%21,%22,%23,%24,%25,%26,%27,%28,%29,%30,%31,"
      "%32,%33,%34,%35,%36,%37,%38,%39,%40,%41,%42,%43,%44,%45,%46,%47,%48,%49,%50,%51,%52,%53,%54,%55,%56,%57,%58,%59,%60,%61,%62,%63}, "
      "%64, %65, p, 1, 1, 0, 1;\n}\n"
      : R64(d, 0)
      : "l"(da), "l"(db), "r"(acc));
}
#define Z4(d, o) "=f"(d[o + 0]), "=f"(d[o + 1]), "=f"(d[o + 2]), "=f"(d[o + 3])
#define Z16(d, o) Z4(d, o), Z4(d, o + 4), Z4(d, o + 8), Z4(d, o + 12)
__device__ __forceinline__ void wgmma_n128z(float (&d)[64], uint64_t da, uint64_t db) {
  asm volatile(
      "wgmma.mma_async.sync.aligned.m64n128k16.f32.bf16.bf16 "
      "{%0,%1,%2,%3,%4,%5,%6,%7,%8,%9,%10,%11,%12,%13,%14,%15,%16,%17,%18,%19,%20,%21,%22,%23,%24,%25,%26,%27,%28,%29,%30,%31,"
      "%32,%33,%34,%35,%36,%37,%38,%39,%40,%41,%42,%43,%44,%45,%46,%47,%48,%49,%50,%51,%52,%53,%54,%55,%56,%57,%58,%59,%60,%61,%62,%63}, "
      "%64, %65, 0, 1, 1, 0, 1;\n"
      : Z16(d, 0), Z16(d, 16), Z16(d, 32), Z16(d, 48)
      : "l"(da), "l"(db));
}
template <int N> __device__ __forceinline__ void fence_regs(float (&d)[N]) {
#pragma unroll
  for (int i = 0; i < N; i++) asm volatile("" : "+f"(d[i])::"memory");
}

__device__ __forceinline__ void mma16816(float (&d)[4], uint32_t a0, uint32_t a1, uint32_t a2, uint32_t a3, uint32_t b0,
                                         uint32_t b1) {
  asm("mma.sync.aligned.m16n8k16.row.col.f32.bf16.bf16.f32 {%0,%1,%2,%3}, {%4,%5,%6,%7}, {%8,%9}, {%0,%1,%2,%3};\n"
      : "+f"(d[0]), "+f"(d[1]), "+f"(d[2]), "+f"(d[3])
      : "r"(a0), "r"(a1), "r"(a2), "r"(a3), "r"(b0), "r"(b1));
}
__device__ __forceinline__ void mma16816_z(float (&d)[4], uint32_t a0, uint32_t a1, uint32_t a2, uint32_t a3, uint32_t b0,
                                           uint32_t b1) {
  asm("mma.sync.aligned.m16n8k16.row.col.f32.bf16.bf16.f32 {%0,%1,%2,%3}, {%4,%5,%6,%7}, {%8,%9}, {%10,%10,%10,%10};\n"
      : "=f"(d[0]), "=f"(d[1]), "=f"(d[2]), "=f"(d[3])
      : "r"(a0), "r"(a1), "r"(a2), "r"(a3), "r"(b0), "r"(b1), "f"(0.f));
}
__device__ __forceinline__ void ldsm4t(uint32_t (&r)[4], uint32_t a) {
  asm volatile("ldmatrix.sync.aligned.m8n8.x4.trans.shared.b16 {%0,%1,%2,%3}, [%4];\n"
               : "=r"(r[0]), "=r"(r[1]), "=r"(r[2]), "=r"(r[3]) : "r"(a) : "memory");
}
__device__ __forceinline__ void ldsm2t(uint32_t& r0, uint32_t& r1, uint32_t a) {
  asm volatile("ldmatrix.sync.aligned.m8n8.x2.trans.shared.b16 {%0,%1}, [%2];\n" : "=r"(r0), "=r"(r1) : "r"(a) : "memory");
}
__device__ __forceinline__ void st_async128(uint32_t a, uint32_t bar, uint32_t x, uint32_t y, uint32_t z, uint32_t w) {
  asm volatile("st.async.weak.shared::cluster.mbarrier::complete_tx::bytes.v4.b32 [%0], {%2,%3,%4,%5}, [%1];\n"
               ::"r"(a), "r"(bar), "r"(x), "r"(y), "r"(z), "r"(w) : "memory");
}
__device__ __forceinline__ void mbar_arrive(uint32_t a) {
  asm volatile("mbarrier.arrive.shared::cta.b64 _, [%0];\n" ::"r"(a) : "memory");
}
__device__ __forceinline__ void stsm4(uint32_t a, uint32_t r0, uint32_t r1, uint32_t r2, uint32_t r3) {
  asm volatile("stmatrix.sync.aligned.m8n8.x4.shared.b16 [%0], {%1,%2,%3,%4};\n"
               ::"r"(a), "r"(r0), "r"(r1), "r"(r2), "r"(r3) : "memory");
}
__device__ __forceinline__ void stsm4t(uint32_t a, uint32_t r0, uint32_t r1, uint32_t r2, uint32_t r3) {
  asm volatile("stmatrix.sync.aligned.m8n8.x4.trans.shared.b16 [%0], {%1,%2,%3,%4};\n"
               ::"r"(a), "r"(r0), "r"(r1), "r"(r2), "r"(r3) : "memory");
}
__device__ __forceinline__ uint2 lds64(uint32_t a) {
  uint2 v;
  asm volatile("ld.shared.v2.u32 {%0,%1}, [%2];\n" : "=r"(v.x), "=r"(v.y) : "r"(a));
  return v;
}
__device__ __forceinline__ uint4 lds128(uint32_t a) {
  uint4 v;
  asm volatile("ld.shared.v4.u32 {%0,%1,%2,%3}, [%4];\n" : "=r"(v.x), "=r"(v.y), "=r"(v.z), "=r"(v.w) : "r"(a) : "memory");
  return v;
}
__device__ __forceinline__ void sts128(uint32_t a, uint32_t x, uint32_t y, uint32_t z, uint32_t w) {
  asm volatile("st.shared.v4.u32 [%0], {%1,%2,%3,%4};\n" ::"r"(a), "r"(x), "r"(y), "r"(z), "r"(w) : "memory");
}
__device__ __forceinline__ void sts64(uint32_t a, uint32_t x, uint32_t y) {
  asm volatile("st.shared.v2.u32 [%0], {%1,%2};\n" ::"r"(a), "r"(x), "r"(y) : "memory");
}
__device__ __forceinline__ uint32_t pack_bf16(float lo, float hi) {
  uint32_t r;
  asm("cvt.rn.bf16x2.f32 %0, %1, %2;\n" : "=r"(r) : "f"(hi), "f"(lo));
  return r;
}
__device__ __forceinline__ uint32_t bmul2(uint32_t a, uint32_t b) {
  uint32_t r;
  asm("mul.rn.bf16x2 %0, %1, %2;\n" : "=r"(r) : "r"(a), "r"(b));
  return r;
}
__device__ __forceinline__ uint32_t bmax2(uint32_t a, uint32_t b) {
  uint32_t r;
  asm("max.bf16x2 %0, %1, %2;\n" : "=r"(r) : "r"(a), "r"(b));
  return r;
}
__device__ __forceinline__ uint32_t bfma2(uint32_t a, uint32_t b, uint32_t c) {
  uint32_t r;
  asm("fma.rn.bf16x2 %0, %1, %2, %3;\n" : "=r"(r) : "r"(a), "r"(b), "r"(c));
  return r;
}
__device__ __forceinline__ uint32_t badd2(uint32_t a, uint32_t b) {
  uint32_t r;
  asm("add.rn.bf16x2 %0, %1, %2;\n" : "=r"(r) : "r"(a), "r"(b));
  return r;
}
__device__ __forceinline__ void prefetch_l2(const void* p) { asm volatile("prefetch.global.L2 [%0];\n" ::"l"(p)); }
__device__ __forceinline__ void cp_async16n(uint32_t dst, const void* src) {
  asm volatile("cp.async.cg.shared.global [%0], [%1], 16;\n" ::"r"(dst), "l"(src) : "memory");
}
__device__ __forceinline__ void cp_async16(uint32_t dst, const void* src, uint32_t srcbytes) {
  asm volatile("cp.async.cg.shared.global.L2::256B [%0], [%1], 16, %2;\n" ::"r"(dst), "l"(src), "r"(srcbytes) : "memory");
}
__device__ __forceinline__ uint32_t ld_acquire(const uint32_t* p) {
  uint32_t v;
  asm volatile("ld.acquire.gpu.global.u32 %0, [%1];\n" : "=r"(v) : "l"(p) : "memory");
  return v;
}
__device__ __forceinline__ uint32_t ld_relaxed(const uint32_t* p) {
  uint32_t v;
  asm volatile("ld.relaxed.gpu.global.u32 %0, [%1];\n" : "=r"(v) : "l"(p) : "memory");
  return v;
}
__device__ __forceinline__ void st_release(uint32_t* p, uint32_t v) {
  asm volatile("st.release.gpu.global.u32 [%0], %1;\n" ::"l"(p), "r"(v) : "memory");
}
__device__ __forceinline__ void wait_flag(const uint32_t* p, uint32_t want) {
  int n = 0;
  while (ld_acquire(p) != want && ++n < SPIN_LIMIT) {}
}

struct Params {
  const __nv_bfloat16* x;
  const __nv_bfloat16* w;
  const __nv_bfloat16* q;
  const __nv_bfloat16* k;
  const __nv_bfloat16* v;
  const __nv_bfloat16* shift_k;
  const __nv_bfloat16* ssm_k;
  const __nv_bfloat16* ssm_D;
  const __nv_bfloat16* wo;
  __nv_bfloat16* out;
  uint32_t zero;
};

__device__ __forceinline__ uint32_t lds32(uint32_t a) {
  uint32_t v;
  asm volatile("ld.shared.u32 %0, [%1];\n" : "=r"(v) : "r"(a));
  return v;
}
__device__ __forceinline__ float bf_lo(uint32_t v) {
  uint32_t r;
  asm("prmt.b32 %0, %1, 0, 0x1044;\n" : "=r"(r) : "r"(v));
  return __uint_as_float(r);
}
__device__ __forceinline__ float bf_hi(uint32_t v) { return __uint_as_float(v & 0xffff0000u); }
__device__ __forceinline__ float ex2(float x) {
  float r;
  asm("ex2.approx.ftz.f32 %0, %1;\n" : "=f"(r) : "f"(x));
  return r;
}
__device__ __forceinline__ float rcp(float x) {
  float r;
  asm("rcp.approx.ftz.f32 %0, %1;\n" : "=f"(r) : "f"(x));
  return r;
}

#define Q4(c, d, o) c(d[o + 0]), c(d[o + 1]), c(d[o + 2]), c(d[o + 3])
#define Q8(c, d, o) Q4(c, d, o), Q4(c, d, o + 4)
#define Q16(c, d, o) Q8(c, d, o), Q8(c, d, o + 8)
#define Q32(c, d) Q16(c, d, 0), Q16(c, d, 16)
#define L8 "{%0,%1,%2,%3,%4,%5,%6,%7}"
#define L16 "{%0,%1,%2,%3,%4,%5,%6,%7,%8,%9,%10,%11,%12,%13,%14,%15}"
#define L32 "{%0,%1,%2,%3,%4,%5,%6,%7,%8,%9,%10,%11,%12,%13,%14,%15,%16,%17,%18,%19,%20,%21,%22,%23,%24,%25,%26,%27,%28,%29,%30,%31}"
__device__ __forceinline__ void fft_rows(uint32_t (&d)[32], const uint32_t (&a)[2][4], uint64_t db) {
  asm volatile("wgmma.mma_async.sync.aligned.m64n128k16.f16.f16.f16 " L32 ", {%32,%33,%34,%35}, %36, 0, 1, 1, 1;\n"
               : Q32("=r", d) : "r"(a[0][0]), "r"(a[0][1]), "r"(a[0][2]), "r"(a[0][3]), "l"(db));
  asm volatile("wgmma.mma_async.sync.aligned.m64n128k16.f16.f16.f16 " L32 ", {%32,%33,%34,%35}, %36, 1, 1, 1, 1;\n"
               : Q32("+r", d) : "r"(a[1][0]), "r"(a[1][1]), "r"(a[1][2]), "r"(a[1][3]), "l"(db + 64));
}
template <int INV> __device__ __forceinline__ void fft_cols(uint32_t (&d)[8], const uint32_t (&a)[2][4], uint64_t db) {
  asm volatile("wgmma.mma_async.sync.aligned.m64n32k16.f16.f16.f16 " L8 ", {%8,%9,%10,%11}, %12, 0, 1, 1, %13;\n"
               : Q8("=r", d, 0) : "r"(a[0][0]), "r"(a[0][1]), "r"(a[0][2]), "r"(a[0][3]), "l"(db), "n"(INV));
  asm volatile("wgmma.mma_async.sync.aligned.m64n32k16.f16.f16.f16 " L8 ", {%8,%9,%10,%11}, %12, 1, 1, 1, %13;\n"
               : Q8("+r", d, 0) : "r"(a[1][0]), "r"(a[1][1]), "r"(a[1][2]), "r"(a[1][3]), "l"(db + (INV ? 16 : 64)), "n"(INV));
}
__device__ __forceinline__ void fft_back(float (&d)[16], uint64_t da, uint64_t db) {
  asm volatile("wgmma.mma_async.sync.aligned.m64n32k16.f32.f16.f16 " L16 ", %16, %17, 0, 1, 1, 1, 1;\n"
               : Q16("=f", d, 0) : "l"(da), "l"(db));
#pragma unroll
  for (int i = 1; i < 4; i++)
    asm volatile("wgmma.mma_async.sync.aligned.m64n32k16.f32.f16.f16 " L16 ", %16, %17, 1, 1, 1, 1, 1;\n"
                 : Q16("+f", d, 0) : "l"(da + 32 * i), "l"(db + 64 * i));
}
__device__ __forceinline__ uint32_t hmul2(uint32_t a, uint32_t b) {
  uint32_t r;
  asm("mul.rn.f16x2 %0, %1, %2;\n" : "=r"(r) : "r"(a), "r"(b));
  return r;
}
__device__ __forceinline__ uint32_t hadd2(uint32_t a, uint32_t b) {
  uint32_t r;
  asm("add.rn.f16x2 %0, %1, %2;\n" : "=r"(r) : "r"(a), "r"(b));
  return r;
}
__device__ __forceinline__ uint32_t hneg2(uint32_t a) {
  uint32_t r;
  asm("neg.f16x2 %0, %1;\n" : "=r"(r) : "r"(a));
  return r;
}
__device__ __forceinline__ uint32_t hfma2(uint32_t a, uint32_t b, uint32_t c) {
  uint32_t r;
  asm("fma.rn.f16x2 %0, %1, %2, %3;\n" : "=r"(r) : "r"(a), "r"(b), "r"(c));
  return r;
}
__device__ __forceinline__ uint32_t pack_f16(float lo, float hi) {
  uint32_t r;
  asm("cvt.rn.f16x2.f32 %0, %1, %2;\n" : "=r"(r) : "f"(hi), "f"(lo));
  return r;
}
__device__ __forceinline__ uint32_t bmaxabs2(uint32_t a, uint32_t b) {
  uint32_t r;
  asm("max.xorsign.abs.bf16x2 %0, %1, %2;\n" : "=r"(r) : "r"(a), "r"(b));
  return r;
}
struct C2 { uint32_t r, i; };
__device__ __forceinline__ C2 cmul(C2 a, C2 b) {
  return C2{hfma2(a.r, b.r, hneg2(hmul2(a.i, b.i))), hfma2(a.r, b.i, hmul2(a.i, b.r))};
}
__device__ __forceinline__ C2 cfma(C2 a, C2 b, C2 c) {
  return C2{hfma2(a.r, b.r, hfma2(hneg2(a.i), b.i, c.r)), hfma2(a.r, b.i, hfma2(a.i, b.r, c.i))};
}
__device__ __forceinline__ C2 crot(C2 z, C2 t) {
  const uint32_t r = hfma2(t.r, z.i, z.r), i = hfma2(t.i, r, z.i);
  return C2{hfma2(t.r, i, r), i};
}
__device__ __forceinline__ C2 cget(const uint32_t (&e)[8], int j, int b) { return C2{e[4 * j + b], e[4 * j + 2 + b]}; }
template <int N> __device__ __forceinline__ void fence_regs(uint32_t (&d)[N]) {
#pragma unroll
  for (int i = 0; i < N; i++) asm volatile("" : "+r"(d[i])::"memory");
}
__device__ __forceinline__ void ldsm4(uint32_t (&r)[4], uint32_t a) {
  asm volatile("ldmatrix.sync.aligned.m8n8.x4.shared.b16 {%0,%1,%2,%3}, [%4];\n"
               : "=r"(r[0]), "=r"(r[1]), "=r"(r[2]), "=r"(r[3]) : "r"(a) : "memory");
}

__device__ __forceinline__ uint32_t movm(uint32_t a) {
  uint32_t r;
  asm volatile("movmatrix.sync.aligned.m8n8.trans.b16 %0, %1;\n" : "=r"(r) : "r"(a));
  return r;
}
template <int C0, int H, bool T> __device__ __forceinline__ void attn_pack(const float (&acc)[96], uint32_t (&d)[8]) {
#pragma unroll
  for (int c = 0; c < 8; c++) {
    asm volatile("cvt.rn.bf16x2.f32 %0, %1, %2;\n" : "=r"(d[c]) : "f"(acc[4 * (C0 + c) + 2 * H + 1]), "f"(acc[4 * (C0 + c) + 2 * H]));
    if (T) d[c] = movm(d[c]);
  }
}
__device__ __forceinline__ void attn_qk(float (&s)[4], const uint32_t (&qlo)[8], const uint32_t (&qhi)[8],
                                        const uint32_t (&k)[8], int c) {
  mma16816_z(s, qlo[c], qhi[c], qlo[c + 1], qhi[c + 1], k[c], k[c + 1]);
  mma16816(s, qlo[c + 2], qhi[c + 2], qlo[c + 3], qhi[c + 3], k[c + 2], k[c + 3]);
}
template <int N> __device__ __forceinline__ void quad_softmax(float (&x)[N][2], uint32_t (&pp)[N]) {
  const float c2 = 1.4426950408889634f;
  uint32_t q[N], mx[N / 2];
#pragma unroll
  for (int n = 0; n < N; n++) {
    const uint32_t r = pack_bf16(x[n][0], x[n][1]);
    q[n] = bfma2(r, 0x3e353e35u, bmul2(r, 0x379e379eu));
    x[n][0] = bf_lo(q[n]);
    x[n][1] = bf_hi(q[n]);
  }
#pragma unroll
  for (int n = 0; n < N / 2; n++)
    mx[n] = bmax2(__byte_perm(q[2 * n], q[2 * n + 1], 0x5410), __byte_perm(q[2 * n], q[2 * n + 1], 0x7632));
#pragma unroll
  for (int o = 1; o <= 2; o++) {
#pragma unroll
    for (int n = 0; n < N / 2; n++) mx[n] = bmax2(mx[n], __shfl_xor_sync(0xffffffffu, mx[n], o));
  }
  float m[N], t[N];
#pragma unroll
  for (int n = 0; n < N / 2; n++) {
    m[2 * n] = bf_lo(mx[n]);
    m[2 * n + 1] = bf_hi(mx[n]);
  }
#pragma unroll
  for (int n = 0; n < N; n++) {
    const float nm = -m[n] * c2;
    x[n][0] = ex2(fmaf(x[n][0], c2, nm));
    x[n][1] = ex2(fmaf(x[n][1], c2, nm));
  }
#pragma unroll
  for (int n = 0; n < N; n += 2) {
    float u0, u1;
    asm("mma.sync.aligned.m16n8k8.row.col.f32.tf32.tf32.f32 {%0,%1,%2,%3}, {%4,%5,%6,%7}, {%8,%8}, {%9,%9,%9,%9};\n"
        : "=f"(t[n]), "=f"(u0), "=f"(t[n + 1]), "=f"(u1)
        : "r"(__float_as_uint(x[n][0])), "r"(__float_as_uint(x[n + 1][0])), "r"(__float_as_uint(x[n][1])),
          "r"(__float_as_uint(x[n + 1][1])), "r"(0x3f800000u), "f"(0.f));
  }
#pragma unroll
  for (int n = 0; n < N; n++) {
    const float inv = rcp(t[n]);
    pp[n] = pack_bf16(x[n][0] * inv, x[n][1] * inv);
  }
}
__device__ __forceinline__ void attn_pv(uint32_t dst, const uint32_t (&vp)[8], const uint32_t (&vo)[8], int c, uint32_t pp,
                                        uint32_t maskLE) {
  const uint32_t b0 = pp & ~maskLE, b1 = pp & maskLE;
  float oa[4], ob[4];
  mma16816_z(oa, vp[c], vp[c + 1], vo[c], vo[c + 1], b0, b1);
  mma16816_z(ob, vp[c + 2], vp[c + 3], vo[c + 2], vo[c + 3], b0, b1);
  stsm4t(dst, pack_bf16(oa[0], oa[1]), pack_bf16(oa[2], oa[3]), pack_bf16(ob[0], ob[1]), pack_bf16(ob[2], ob[3]));
}

template <int MODE>
__global__ void __cluster_dims__(2, 1, 1) __launch_bounds__(NTHREADS, 1)
fused_kernel(const Params p, const __grid_constant__ CUtensorMap tmX, const __grid_constant__ CUtensorMap tmW,
             const __grid_constant__ CUtensorMap tmWo, const __grid_constant__ CUtensorMap tmWp,
             const __grid_constant__ CUtensorMap tmQ,
             const __grid_constant__ CUtensorMap tmOb,
             const __grid_constant__ CUtensorMap tmXh, const __grid_constant__ CUtensorMap tmWh) {
  extern __shared__ __align__(1024) uint8_t smem[];
  if (threadIdx.x < 32) {
    const uint32_t i = (blockIdx.x & 127) * 16 + (threadIdx.x & 15);
    prefetch_l2(threadIdx.x & 16 ? (const char*)p.w + i * 128 : (const char*)p.x + i * 2048);
  }
  const uint32_t sb = smem_u32(smem);
  const uint32_t bars = sb + OFF_BAR;
  const int tid = threadIdx.x, lane = tid & 31, warp = __shfl_sync(0xffffffffu, tid >> 5, 0);
  const int rank = blockIdx.x & 1;
  const bool halo_cta = blockIdx.x < 4;
  if (halo_cta && MODE != 0) return;
  int grp, mem;
  {
    const int t = (blockIdx.x >> 1) - 4, u = t - 32;
    const int q7 = (u * 37) >> 8;
    const bool lo = (unsigned)t < 32u, mid = (unsigned)u < 28u;
    grp = lo ? (t & 7) : (mid ? 1 + u - 7 * q7 : 0);
    mem = lo ? (t >> 3) : (mid ? 4 + q7 : (t < 0 ? t + 6 : t - 54));
  }
  const int rg = (grp >> 2) * 4 + (mem >> 1), hp = (grp & 3) * 4 + (mem & 1) * 2 + rank;
  const int rb2 = (grp >> 2) * 8 + mem, cb2 = (grp & 3) * 2 + rank;
  const int chb = grp * 16 + mem * 2 + rank;
  const int cta = rg * 16 + hp;
  const int hsel = rb2 & 1;
  const int par = rg >> 2, gidx = rg & 3;

  if (tid < 256 && !halo_cta && MODE != 2) {
    const int r = tid >> 3, c = tid & 7;
    const uint32_t so = r * 128 + ((c ^ (r & 7)) << 4);
    const __nv_bfloat16* wg0 = p.w + (size_t)r * (3 * DM) + hp * 64 + c * 8;
    const __nv_bfloat16* xg0 = p.x + (size_t)(2 * (gidx * 256 + r) + par) * DM + c * 8;
#pragma unroll
    for (int j = 0; j < 3; j++) cp_async16n(sb + OFF_1B + j * 4096 + so, wg0 + j * DM);
#pragma unroll
    for (int i = 0; i < 8; i++) cp_async16n(sb + i * 4096 + so, xg0 + (size_t)i * 64 * DM);
    asm volatile("cp.async.commit_group;\n" ::: "memory");
  }
  auto halo_issue = [&](int kb, int s) {
    const uint32_t fb = bars + 8 * (BAR_FULLB + s), st = sb + s * STGH;
    mbar_expect_tx(fb, STGH - 2048);
    tma_load_3d(st + 8192, &tmWh, fb, 0, kb * 64, 16 + blockIdx.x * 4);
    tma_load_3d(st + 8192 + 32768, &tmWh, fb, 0, kb * 64, 32 + blockIdx.x * 4);
    tma_load_4d(st, &tmXh, fb, kb * 64, 248, 0, 0);
  };
  if (tid == 256) {
    prefetch_tmap(halo_cta ? &tmXh : &tmX);
#pragma unroll
    for (int i = 0; i < NS1B; i++) mbar_init(bars + 8 * (BAR_FULLB + i), 1);
#pragma unroll
    for (int i = 0; i < NS1A; i++) mbar_init(bars + 8 * (BAR_FULLA + i), 1);
    asm volatile("fence.mbarrier_init.release.cluster;\n" ::: "memory");
    if (!halo_cta && MODE != 2) {
      mbar_expect_tx(bars + 8 * (BAR_FULLB + 1), STG1B);
      tma_load_3d(sb + OFF_1B + 1 * STG1B, &tmW, bars + 8 * (BAR_FULLB + 1), hp * 64, 32, 0);
      mbar_expect_tx(bars + 8 * (BAR_FULLB + 2), STG1B);
      tma_load_3d(sb + OFF_1B + 2 * STG1B, &tmW, bars + 8 * (BAR_FULLB + 2), hp * 64, 64, 0);
    } else if (halo_cta) {
      halo_issue(0, 0);
    }
  } else if (tid == 288) {
#pragma unroll
    for (int i = 0; i < NS1A; i++) mbar_init(bars + 8 * (BAR_EMPTYA + i), 4);
#pragma unroll
    for (int i = 0; i < NS1B; i++) mbar_init(bars + 8 * (BAR_EMPTYB + i), 2);
    mbar_init(bars + 8 * BAR_X, 4);
    mbar_init(bars + 8 * BAR_TAB, 16);
    mbar_init(bars + 8 * BAR_U, 1);
    mbar_init(bars + 8 * BAR_H, 1);
    mbar_init(bars + 8 * BAR_STG, 8);
    mbar_init(bars + 8 * BAR_HALO, 1);
    mbar_init(bars + 8 * BAR_Q, 1);
    mbar_init(bars + 8 * BAR_LAND, 5);
    mbar_init(bars + 8 * (BAR_LAND + 1), 5);
    asm volatile("fence.mbarrier_init.release.cluster;\n" ::: "memory");
  } else if (tid == 320) {
#pragma unroll
    for (int i = 0; i < NS2; i++) {
      mbar_init(bars + 8 * (BAR_FULL2 + i), 1);
      mbar_init(bars + 8 * (BAR_EMPTY2 + i), 2);
      mbar_init(bars + 8 * (BAR_EMPTY2B + i), 2);
    }
    asm volatile("fence.mbarrier_init.release.cluster;\n" ::: "memory");
  } else if (tid == 352) {
#pragma unroll
    for (int i = 0; i < 4; i++) mbar_init(bars + 8 * (BAR_Y + i), i < 2 ? 4 : i == 2 ? 10 : 8);
    asm volatile("fence.mbarrier_init.release.cluster;\n" ::: "memory");
  }
  cluster_sync_all();
  if (warp == 8) PROF2(24);

  if (warp >= 8) {
    const int hw = warp - 8;
    const int lr = lane & 7, lm = lane >> 3;
    auto g1_issue_a = [&](int j, int s) {
      const uint32_t fb = bars + 8 * (BAR_FULLA + s);
      mbar_expect_tx(fb, STG1A);
      tma_load_3d_mc(sb + s * STG1A + rank * 16384, &tmX, fb, j * 64, par, gidx * 256 + rank * 128);
    };
    auto g1_issue_b = [&](int kb, int s) {
      const uint32_t fb = bars + 8 * (BAR_FULLB + s);
      mbar_expect_tx(fb, STG1B);
      tma_load_3d(sb + OFF_1B + s * STG1B, &tmW, fb, hp * 64, kb * 32, 0);
    };
    auto g2_k = [&](int kb) { return (kb < 2 ? hp : kb < 4 ? hp & 14 : hp & 12) ^ kb; };
    auto g2_issue_b = [&](uint32_t fb, uint32_t bytes, uint32_t dst, int k0, bool whole) {
      if (whole) {
        tma_load_3d(dst, &tmWo, fb, 0, k0, cb2 * 2);
      } else {
#pragma unroll
        for (int i = 0; i < 4; i++)
          tma_load_3d(dst + (i & 1) * XT + (i >> 1) * 4 * XT, &tmWp, fb, 0, k0 + (i >> 1) * 32, cb2 * 2 + (i & 1));
      }
      mbar_expect_tx(fb, bytes);
    };
    auto send_y = [&](uint32_t o, uint32_t step, int half) {
      const uint32_t peer = mapa(sb, rank ^ 1);
      o += OFF_X + (rank ^ 1) * 4096 + half * 2048 + lane * 16;
      uint4 a[8];
#pragma unroll
      for (int i = 0; i < 8; i++) a[i] = lds128(sb + o + (i >> 2) * step + (i & 2) * (XT / 2) + (i & 1) * 512);
#pragma unroll
      for (int i = 0; i < 8; i++)
        st_async128(peer + o + 1024 + (i >> 2) * step + (i & 2) * (XT / 2) + (i & 1) * 512,
                    peer + OFF_BAR + 8 * (BAR_LAND + half), a[i].x, a[i].y, a[i].z, a[i].w);
    };
    asm volatile("setmaxnreg.dec.sync.aligned.u32 %0;\n" :: "n"(REG_HELP));

    if (halo_cta) {
      if (hw == 0) {
        int s = 1, ph = 1;
#pragma unroll 1
        for (int kb = 1; kb < 16; kb++) {
          mbar_wait(bars + 8 * (BAR_EMPTYB + s), ph);
          if (elect_one()) halo_issue(kb, s);
          if (++s == 3) { s = 0; ph ^= 1; }
        }
      }
      __syncwarp();
    } else if (hw == 0) {
      uint32_t epoch = 0;
      if (MODE == 2) {
        if (lane < NS2) mbar_arrive_cluster_n(mapa(bars, rank) + 8 * (BAR_EMPTY2 + lane), 2);
      } else {
      if (lane == 0) {
        mbar_expect_tx(bars + 8 * BAR_U, 32768);
        mbar_expect_tx(bars + 8 * BAR_LAND, 8192);
        mbar_expect_tx(bars + 8 * (BAR_LAND + 1), 8192);
        mbar_expect_tx(bars + 8 * BAR_Q, 32768);
        prefetch_tmap(&tmQ);
      }
      {
        int sa = 1, pha = 1, sbb = 2, phb = 1;
#pragma unroll 1
        for (int kb = 2; kb < 32; kb++) {
          if (!(kb & 1)) {
            mbar_wait(bars + 8 * (BAR_EMPTYA + sa), pha);
            if (elect_one()) g1_issue_a(kb >> 1, sa);
            if (++sa == NS1A) { sa = 0; pha ^= 1; }
          }
          mbar_wait(bars + 8 * (BAR_EMPTYB + sbb), phb);
          if (kb > 2 && elect_one()) g1_issue_b(kb, sbb);
          __syncwarp();
          if (kb == 4) epoch = ld_relaxed(g_flag_o + cta);
          if (kb == 4) PROF2(27);
          if (kb == 1) PROF2(38);
          if (kb == 2) PROF2(39);
          if (++sbb == NS1B) { sbb = 0; phb ^= 1; }
        }
      }
      auto q_issue = [&](int i) {
        mbar_wait(bars + 8 * (i ? BAR_EMPTYB + 3 : BAR_EMPTYA + 1), i);
        if (elect_one())
          asm volatile(
              "cp.async.bulk.tensor.5d.shared::cluster.global.mbarrier::complete_tx::bytes [%0], [%1, {%3, %4, %4, %4, %5}], [%2];\n"
              ::"r"(sb + (i ? OFF_Q1 : OFF_Q0)), "l"(&tmQ), "r"(bars + 8 * BAR_Q), "r"((chb & ~1) * 8), "r"(0), "r"(rank * 32 + i * 64)
              : "memory");
        __syncwarp();
      };
      if (QORD < 2) q_issue(0);
      else mbar_wait(bars + 8 * (BAR_EMPTYA + 1), 0);
      if (QORD < 1) q_issue(1);
      epoch++;
      if (lane == 0) {
        prefetch_tmap(&tmWo);
        prefetch_tmap(&tmWp);
        prefetch_tmap(&tmOb);
        if (gidx != 0) wait_flag(g_flag_h + (hp >> 2), epoch);
      }
      __syncwarp();
      {
        uint4 hk0 = make_uint4(0, 0, 0, 0), hk1 = hk0, hv0 = hk0, hv1 = hk0;
        if (gidx != 0) {
          const uint4* src = g_halo + cta * 128 + lane;
          hk0 = __ldcg(src); hk1 = __ldcg(src + 32); hv0 = __ldcg(src + 64); hv1 = __ldcg(src + 96);
        }
        if (gidx != 0) PROF(18);
        sts128(sb + OFF_KH + lane * 16, hk0.x, hk0.y, hk0.z, hk0.w);
        sts128(sb + OFF_KH + 512 + lane * 16, hk1.x, hk1.y, hk1.z, hk1.w);
        sts64(sb + OFF_KH + 1024 + lane * 8, movm(hv0.x), movm(hv0.y));
        sts64(sb + OFF_KH + 1280 + lane * 8, movm(hv0.z), movm(hv0.w));
        sts64(sb + OFF_KH + 1536 + lane * 8, movm(hv1.x), movm(hv1.y));
        sts64(sb + OFF_KH + 1792 + lane * 8, movm(hv1.z), movm(hv1.w));
        __syncwarp();
        if (lane == 0) mbar_arrive(bars + 8 * BAR_HALO);
      }
      if (QORD == 2) q_issue(0);
      if (QORD >= 1) q_issue(1);
      const uint32_t rb = mapa(bars, lane & 1);
      nb_sync(NB_OREADY, 288);
      if (lane == 0) {
        asm volatile("cp.async.bulk.global.shared::cta.bulk_group [%0], [%1], %2;\n" ::"l"(g_o + (size_t)cta * 16384),
                     "r"(sb + OFF_OP), "r"(32768) : "memory");
        bulk_commit();
      }
      if (lane < 2) {
#pragma unroll
        for (int i = 0; i < 4; i++) mbar_arrive_cluster(rb + 8 * (BAR_EMPTY2 + i + i / 2));
      }
      if (lane == 0) {
        bulk_wait0();
        st_release(g_flag_o + cta, epoch);
      }
      __syncwarp();
      PROF2(17);
      if (lane < 2) mbar_arrive_cluster(rb + 8 * (BAR_EMPTY2 + 2));
      }
      if (MODE == 1) {
        for (int h = 0; h < 2; h++) {
          mbar_wait(bars + 8 * (BAR_Y + 2 + h), 0);
          send_y(h * 2 * XT, 4 * XT, 1);
        }
      }
      if (MODE != 1) {
        const __nv_bfloat16* osrc = g_o + (size_t)(rb2 >> 1) * 16 * 16384 + hsel * 8192;
        mbar_wait(bars + 8 * (BAR_EMPTY2 + 1), 0);
        if (elect_one()) {
          if (MODE == 0) {
            asm volatile("cp.async.bulk.shared::cluster.shared::cta.mbarrier::complete_tx::bytes [%0], [%1], %2, [%3];\n"
                         ::"r"(mapa(sb + g2_a(1, hsel), rank ^ 1)), "r"(sb + g2_a(0, hsel)), "r"(16384),
                         "r"(mapa(bars + 8 * (BAR_FULL2 + 1), rank ^ 1)) : "memory");
          } else {
            bulk_load(sb + g2_a(0, hsel), osrc + hp * 16384, 16384, bars + 8 * BAR_FULL2);
            bulk_load(sb + g2_a(1, hsel), osrc + (hp ^ 1) * 16384, 16384, bars + 8 * (BAR_FULL2 + 1));
          }
        }
        __syncwarp();
        unsigned long long seq = G2_SEQ >> 12;
        uint32_t wbar = bars + 8 * (BAR_Y + 2), fb = bars + 8 * (BAR_FULL2 + 3), dst = sb + g2_b(3, rank), ph = MODE ? 1 : 0;
        int k0 = g2_k(3) * 64;
        bool whole = false;
#pragma unroll 1
        for (int kb = 4; kb <= 16; kb++) {
          mbar_wait(wbar, ph);
          if (MODE == 0 && (kb == 4 || kb == G2_KB4 + 1)) {
            send_y(kb == 4 ? 0 : 2 * XT, 4 * XT, 1);
            fence_async_smem();
            __syncwarp();
          }
          if (elect_one()) g2_issue_b(fb, STG2, dst, k0, whole);
          __syncwarp();
          seq >>= 4;
          const int s = seq & 7;
          wbar = bars + 8 * (kb == G2_KB4 ? BAR_Y + 3 : BAR_EMPTY2B + s);
          ph = ((uint32_t)seq >> 3 & 1) ^ (kb == G2_KB4 && MODE == 0 ? 0 : 1);
          fb = bars + 8 * (BAR_FULL2 + s);
          dst = sb + g2_b(s, rank);
          k0 = ((hp & 12) ^ kb) * 64;
          whole = s < 3;
        }
      }
      __syncwarp();
    } else {
      if (MODE != 2) {
      const float dall = __bfloat162float(p.ssm_D[chb * 8 + lr]);
      {
        const int g = lane >> 2, t = lane & 3;
        uint32_t w[2][4];
#pragma unroll
        for (int h = 0; h < 2; h++) {
          const uint2 x = __ldg(reinterpret_cast<const uint2*>(p.shift_k + ((chb & ~1) * 8 + h * 8 + g) * 4));
          w[h][0] = __byte_perm(x.x, x.x, 0x1010);
          w[h][1] = __byte_perm(x.x, x.x, 0x3232);
          w[h][2] = __byte_perm(x.y, x.y, 0x1010);
          w[h][3] = __byte_perm(x.y, x.y, 0x3232);
        }
        auto swz = [](int r) { return (((r & 29) | ((r ^ (r >> 2)) & 2)) << 5) | (r & 16); };
        const uint32_t kring = sb + OFF_X + 4096 + (hw - 1) * 2 * XT, vring = kring + XT;
        const int s0 = rank * 32 + (hw - 1) * 11, s1 = hw == 3 ? rank * 32 + 32 : s0 + 11;
        const size_t goff = (size_t)(lane >> 1) * DM + (chb & ~1) * 8 + (lane & 1) * 8;
        const __nv_bfloat16* kg = p.k + goff;
        const __nv_bfloat16* vg = p.v + goff;
        const uint32_t d0 = swz(lane >> 1) ^ ((lane & 1) << 4), d1 = swz(16 + (lane >> 1)) ^ ((lane & 1) << 4);
        auto issue = [&](int st) {
          const uint32_t so = (st & 3) << 10;
          cp_async16(kring + so + d0, kg + (size_t)st * 32 * DM, 16);
          cp_async16(kring + so + d1, kg + (size_t)(st * 32 + 16) * DM, 16);
          cp_async16(vring + so + d0, vg + (size_t)st * 32 * DM, 16);
          cp_async16(vring + so + d1, vg + (size_t)(st * 32 + 16) * DM, 16);
        };
        const int xa = 8 * (lr >> 1) + 2 * lm + (lr & 1), xb = 8 * (lr >> 1) - 4 + 2 * (lm & 1) + (lr & 1);
        const uint32_t la = swz(xa), lb = swz(xb & 31);
        const int backb = xb < 0 ? 1 : 0;
        const uint32_t ud[2] = {mapa(sb + OFF_X + g * XT + t * 16, 0), mapa(sb + OFF_X + g * XT + t * 16, 1)};
        const uint32_t ub[2] = {mapa(bars + 8 * BAR_U, 0), mapa(bars + 8 * BAR_U, 1)};
        if (tid == 320) prefetch_l2(g_tab + (chb & 63) * 32);
        if (lane == 0) mbar_wait(bars + 8 * (BAR_FULLB + NS1B - 1), 0);
        __syncwarp();
        if (lane >= 24) cp_async16(kring + (((s0 - 1) & 3) << 10) + d1, s0 > 0 ? kg + (size_t)(s0 * 32 - 16) * DM : kg, s0 > 0 ? 16 : 0);
        issue(s0);
        asm volatile("cp.async.commit_group;\n" ::: "memory");
        issue(s0 + 1);
        asm volatile("cp.async.commit_group;\n" ::: "memory");
        uint32_t tn = (uint32_t)clock();
#pragma unroll 1
        for (int st = s0; st < s1; st++) {
          tn += PSTEP;
          while ((int)((uint32_t)clock() - tn) < 0) __nanosleep(100);
          if (st + 2 < s1) issue(st + 2);
          if (hw == 1 && (unsigned)(st - s0 - HPF0) < 8u) prefetch_l2(p.ssm_k + (size_t)(chb * 8 + st - s0 - HPF0) * SEQ + lane * 64);
          asm volatile("cp.async.commit_group;\n" ::: "memory");
          asm volatile("cp.async.wait_group 2;\n" ::: "memory");
          __syncwarp();
#pragma unroll
          for (int h = 0; h < 2; h++) {
            uint32_t e[6], vv[4], e4[4];
            ldsm4t(e4, kring + ((st & 3) << 10) + (la ^ (h << 4)));
            ldsm2t(e[0], e[1], kring + (((st - backb) & 3) << 10) + (lb ^ (h << 4)));
            ldsm4t(vv, vring + ((st & 3) << 10) + (la ^ (h << 4)));
            e[2] = e4[0]; e[3] = e4[1]; e[4] = e4[2]; e[5] = e4[3];
            uint32_t o[5];
#pragma unroll
            for (int i = 0; i < 5; i++) o[i] = __byte_perm(e[i], e[i + 1], 0x5432);
#pragma unroll
            for (int i = 0; i < 4; i++) {
              uint32_t a = bmul2(o[i], w[h][3]);
              a = bfma2(e[i + 1], w[h][2], a);
              a = bfma2(o[i + 1], w[h][1], a);
              a = bfma2(e[i + 2], w[h][0], a);
              vv[i] = bmul2(a, vv[i]);
            }
            st_async128(ud[h] + (st ^ (g & 1)) * 64, ub[h], vv[0], vv[1], vv[2], vv[3]);
          }
          __syncwarp();
        }
        fence_async_smem();
        PROF(16);
      }
      nb_sync(NB_HELP3, 96);
      if (hw == 1 && elect_one()) {
        mbar_expect_tx(bars + 8 * BAR_H, 8 * 4096);
#pragma unroll 1
        for (int c = 0; c < 8; c++)
          bulk_load(sb + OFF_X + c * XT + 4096, p.ssm_k + (size_t)(chb * 8 + c) * SEQ, 4096, bars + 8 * BAR_H);
        mbar_expect_tx(bars + 8 * BAR_X, 6144);
        bulk_load(sb + OFF_T16, g_tab, 2048, bars + 8 * BAR_X);
        bulk_load(sb + OFF_T32, g_tab + 512, 4096, bars + 8 * BAR_X);
      }
      __syncwarp();
      {
        const int ck = 16 * (lane >> 4) + 2 * lr + (((lane >> 3) ^ (lane >> 2)) & 1);
        const uint32_t xo = (ck >> 1) * 64, xs = ((ck & 1) ^ (lr >> 1)) << 4;
#pragma unroll 1
        for (int job = hw - 1; job < 16; job += 3) {
          const int c = job & 7;
          uint4 a[8];
          float dv = __shfl_sync(0xffffffffu, dall, c);
          if (job < 8 || lane) dv = 0.f;
          if (job >= PF0 && job < PF1) prefetch_l2((job < 8 ? p.q + (size_t)chb * 16384 : p.wo + (size_t)chb * 8192) + c * 2048 + lane * 64);
          const uint32_t xt = sb + OFF_X + c * XT + (job >> 3) * 4096;
          mbar_wait(bars + 8 * (job < 8 ? BAR_U : BAR_H), 0);
#pragma unroll
          for (int i = 0; i < 8; i++) a[i] = lds128(xt + i * 512 + ((ck ^ (job < 8 ? (c & 1) << 2 : 0)) << 4));
          dv += bf_lo(a[0].x);
          uint32_t m[2] = {bmaxabs2(pack_bf16(dv, 0.f), bmaxabs2(a[0].x, a[0].y)), bmaxabs2(a[0].z, a[0].w)};
#pragma unroll
          for (int i = 1; i < 8; i++) {
            m[0] = bmaxabs2(bmaxabs2(m[0], a[i].x), a[i].y);
            m[1] = bmaxabs2(bmaxabs2(m[1], a[i].z), a[i].w);
          }
          m[0] = bmaxabs2(m[0], m[1]);
          const int f = max(252 - (int)(__reduce_max_sync(0xffffffffu, max(m[0] & 0x7fffu, (m[0] >> 16) & 0x7fffu)) >> 7), 1);
          if (lane == 0) asm volatile("st.shared.u32 [%0], %1;\n" ::"r"(sb + OFF_EX + job * 4), "r"(f) : "memory");
          if (f < 113) {
#pragma unroll
            for (int i = 0; i < 8; i++)
              a[i] = make_uint4(bmul2(a[i].x, f * 0x00800080u), bmul2(a[i].y, f * 0x00800080u), bmul2(a[i].z, f * 0x00800080u),
                                bmul2(a[i].w, f * 0x00800080u));
          }
          const uint32_t mul = (f < 113 ? 15 : f - 112) * 0x00800080u;
          auto cv = [&](uint32_t x) {
            x = bmul2(x, mul);
            return (x & 0x0fff0fffu) * 7 + x;
          };
          const uint32_t dst = xt + xo;
#pragma unroll
          for (int i = 0; i < 8; i++)
            sts128(dst + (i >> 2) * 2048 + (i & 1) * 1024 + (xs ^ ((i & 2) << 4)),
                   i ? cv(a[i].x) : __byte_perm(pack_f16(dv * __uint_as_float(f << 23), 0.f), cv(a[i].x), 0x7610), cv(a[i].y),
                   cv(a[i].z), cv(a[i].w));
        }
        fence_async_smem();
        __syncwarp();
        if (lane == 0) mbar_arrive(bars + 8 * BAR_X);
        PROF(19);
      }
      if (hw < 3) {
#pragma unroll 1
        for (int n = 0; n < SPIN_LIMIT && !mbar_try(bars + 8 * (BAR_Y + hw - 1), 0); n++) __nanosleep(100);
        send_y((hw - 1) * 4 * XT, 2 * XT, 0);
        __syncwarp();
        if (lane == 0) mbar_arrive(bars + 8 * (BAR_Y + 2));
        PROF(32);
        const int c8 = 2 * lm + (lr & 1), src = (lr >> 1) & 1;
        uint32_t fa = sb + OFF_X + c8 * XT + rank * 4096 + (src == rank ? 0 : 1024) + (hw - 1) * 512;
        const uint32_t fx = ((lr >> 2) ^ ((lr & 3) << 1)) << 4;
        uint32_t qa = sb + OFF_Q0 + (hw - 1) * 8192 + (lane >> 3) * 128 + (lane & 2) * 32 + (lane & 4) * 8 + (lane & 1) * 16;
        uint4* og = reinterpret_cast<uint4*>(p.out + (size_t)(rank * 512 + (hw - 1) * 256 + (lane & 2) * 4 + (lane >> 2)) * (2 * DM) +
                                             (chb & ~1) * 8 + (lane & 1) * 8);
        mbar_wait(bars + 8 * BAR_Q, 0);
        uint32_t tn = 0;
#pragma unroll 1
        for (int j = 0; j < 4; j++) {
          if (!(j & 1)) {
            mbar_wait(bars + 8 * (BAR_LAND + (j >> 1)), 0);
            tn = (uint32_t)clock() + (hw - 1) * (FPACE / 2);
            PROF2(33 + j * 2);
          }
#pragma unroll
          for (int i = 0; i < 8; i++) {
            uint32_t y[4];
            const uint4 q = lds128(qa + i * 512);
            ldsm4t(y, fa + (i >> 2) * 128 + (fx ^ ((i & 3) << 5) ^ ((i >> 2) << 4)));
            while ((int)((uint32_t)clock() - tn) < 0) __nanosleep(20);
            tn += FPACE;
            og[i * 16 * (2 * DM / 8)] = make_uint4(bmul2(q.x, y[0]), bmul2(q.y, y[1]), bmul2(q.z, y[2]), bmul2(q.w, y[3]));
          }
          qa += j & 1 ? OFF_Q1 - OFF_Q0 - 4096 : 4096;
          fa += j & 1 ? 2048 - 256 : 256;
          og += (j & 1 ? 1024 - 128 : 128) * (2 * DM / 8);
        }
        PROF(22);
      }
      }
      if (MODE != 1 && hw == 3) {
        const uint32_t epoch = ld_relaxed(g_flag_o + cta) + 1;
        if (MODE == 0) nb_sync(NB_G1END, 288);
        if (BDEL) __nanosleep(BDEL);
        if (elect_one()) {
#pragma unroll
          for (int kb = 0; kb < 3; kb++)
            g2_issue_b(bars + 8 * (BAR_FULL2 + kb), kb || MODE ? STG2 : STG2 / 2, sb + g2_b(kb, 0), g2_k(kb) * 64, true);
        }
        __syncwarp();
        const __nv_bfloat16* osrc = g_o + (size_t)(rb2 >> 1) * 16 * 16384 + hsel * 8192;
        if (MODE == 0) __nanosleep(POLL0);
        const uint32_t* flag = g_flag_o + (rb2 >> 1) * 16 + g2_k(lane & 15);
        uint32_t ready = MODE == 0 ? 0u : ~0u;
        unsigned long long seq = G2_SEQ >> 8;
#pragma unroll 1
        for (int kb = 2; kb < 16; kb++, seq >>= 4) {
          uint32_t so = bars + (seq & 7) * 8, dst = sb + g2_a(seq & 7, hsel) + rank * 8192;
          const uint32_t ph = (uint32_t)seq >> 3 & 1;
          const __nv_bfloat16* src = osrc + rank * 4096 + (uint32_t)g2_k(kb) * 16384;
          asm volatile("" : "+r"(so), "+r"(dst), "+l"(src));
          if (!(ready >> kb & 1)) {
#pragma unroll 1
            for (int n = 0; n < SPIN_LIMIT && !(ready >> kb & 1); n++)
              ready = __ballot_sync(0xffffffffu, ld_acquire(flag) == epoch);
            fence_async_all();
          }
          if (kb == 2) PROF(21);
          if (MODE == 0 && kb == G2_KB4 && rank == 1) mbar_wait(bars + 8 * BAR_TAB, 0);
          mbar_wait(so + 8 * BAR_EMPTY2, ph);
          if (elect_one()) {
            asm volatile(
                "cp.async.bulk.shared::cluster.global.mbarrier::complete_tx::bytes.multicast::cluster [%0], [%1], %2, [%3], %4;\n"
                ::"r"(dst), "l"(src), "r"(8192), "r"(so + 8 * BAR_FULL2), "h"((uint16_t)3) : "memory");
          }
          __syncwarp();
        }
      }
    }
    cluster_sync_all();
    PROF_DUMP();
  } else {
    asm volatile("setmaxnreg.inc.sync.aligned.u32 %0;\n" :: "n"(REG_MATH));
    if (warp == 0) PROF2(26);
    const int wg = warp >> 2;
    const int wtid = tid & 127;
    const bool signaller = (wtid == 0) || (wtid == 32);
    const uint32_t rbars = mapa(bars, wtid >> 5 & 1);

    if (halo_cta) {
      const uint32_t epoch = ld_relaxed(g_flag_h + blockIdx.x) + 1;
      float acc0[64], acc1[64];
      int s = 0, ph = 0;
#pragma unroll 1
      for (int kb = 0; kb < 16; kb++) {
        mbar_wait(bars + 8 * (BAR_FULLB + s), ph);
        const uint32_t st = sb + s * STGH;
        const uint64_t da = mkdesc(st, 16, 1024, 1);
        const uint64_t db = mkdesc(st + 8192 + wg * 32768, 8192, 1024, 1);
        wg_fence();
#pragma unroll
        for (int kk = 0; kk < 4; kk++) {
          wgmma_n128(acc0, da + 2 * kk, db + 128 * kk, kb + kk);
          wgmma_n128(acc1, da + 2 * kk, db + 1024 + 128 * kk, kb + kk);
        }
        wg_commit();
        wg_wait<0>();
        if (kb == 15) PROF(37);
        if (wtid == 0) mbar_arrive(bars + 8 * (BAR_EMPTYB + s));
        if (++s == 3) { s = 0; ph ^= 1; }
      }
      fence_regs(acc0);
      fence_regs(acc1);
      if ((warp & 3) != 3) {
#pragma unroll
        for (int hh = 0; hh < 2; hh++) {
          uint4* dst = g_halo + ((hh * 4 + (warp & 3) + 1) * 16 + blockIdx.x * 4) * 128 + wg * 64 + lane;
#pragma unroll
          for (int j = 0; j < 4; j++) {
            const int o = 16 * j + 2 * hh;
            dst[(j >> 1) * 128 + (j & 1) * 32] =
                make_uint4(pack_bf16(acc0[o], acc0[o + 1]), pack_bf16(acc0[o + 4], acc0[o + 5]),
                           pack_bf16(acc0[o + 8], acc0[o + 9]), pack_bf16(acc0[o + 12], acc0[o + 13]));
            dst[(2 + (j >> 1)) * 128 + (j & 1) * 32] =
                make_uint4(pack_bf16(acc1[o], acc1[o + 1]), pack_bf16(acc1[o + 4], acc1[o + 5]),
                           pack_bf16(acc1[o + 8], acc1[o + 9]), pack_bf16(acc1[o + 12], acc1[o + 13]));
          }
        }
      }
      nb_sync(NB_G1DONE, 256);
      if (tid == 0) st_release(g_flag_h + blockIdx.x, epoch);
      PROF(36);
      cluster_sync_all();
      return;
    }

    float acc[64];
    const uint32_t g2rel = wtid ? mapa(bars, rank) + 8 * BAR_EMPTY2B : mapa(bars, wg) + 8 * BAR_EMPTY2;
    auto g2_block = [&](int kb, int s, int ph) {
      mbar_wait(bars + 8 * (BAR_FULL2 + s), ph);
      const uint64_t da = mkdesc(sb + g2_a(s, hsel) + wg * 8192, 16, 1024, 1);
      const uint64_t db = mkdesc(sb + g2_b(s, rank), 8192, 1024, 1), dc = db + (g2_bk(s) >> 4);
      wg_fence();
      if (kb == 0) wgmma_n128z(acc, da, db);
      else wgmma_n128(acc, da, db, 1);
      wgmma_n128(acc, da + 2, db + 128, 1);
      wgmma_n128(acc, da + 4, dc, 1);
      wgmma_n128(acc, da + 6, dc + 128, 1);
      wg_commit();
    };
    if (MODE != 2) {
    uint32_t a1[2][4], sc[2];
    C2 t[2];
    {
      float acc0[96], acc1[96];
      int sa = 0, pha = 0, sbb = 0, phb = 0;
      asm volatile("cp.async.wait_group 0;\n" ::: "memory");
      fence_async_smem();
      nb_sync(NB_FIRST, 256);
      if (tid == 0) {
        mbar_arrive(bars + 8 * BAR_FULLA);
        mbar_arrive(bars + 8 * BAR_FULLB);
      }
      PROF(0 + wg);
#pragma unroll 1
      for (int kb = 0; kb < 30; kb++) {
        if (!(kb & 1)) mbar_wait(bars + 8 * (BAR_FULLA + sa), pha);
        mbar_wait(bars + 8 * (BAR_FULLB + sbb), phb);
        if (kb == 0) PROF2(0 + wg);
        if (kb == 4 && wg == 0) PROF2(28);
        if (kb == 8 && wg == 0) PROF2(29);
        if (kb == 16 && wg == 0) PROF2(30);
        const uint64_t da = mkdesc(sb + sa * STG1A + wg * 16384 + (kb & 1) * 64, 16, 2048, 1);
        const uint64_t db = mkdesc(sb + OFF_1B + sbb * STG1B, 4096, 1024, 1);
        wg_fence();
        wgmma_n192(acc0, da + 64, db, kb);
        wgmma_n192(acc1, da, db, kb);
        wgmma_n192(acc0, da + 66, db + 128, 1);
        wgmma_n192(acc1, da + 2, db + 128, 1);
        wg_commit();
        wg_wait<1>();
        if (kb > 0) {
          if (wtid == 64) mbar_arrive(bars + 8 * (BAR_EMPTYB + (sbb == 0 ? NS1B - 1 : sbb - 1)));
          if (!(kb & 1) && signaller) mbar_arrive_cluster(rbars + 8 * (BAR_EMPTYA + (sa == 0 ? NS1A - 1 : sa - 1)));
        }
        if (++sbb == NS1B) { sbb = 0; phb ^= 1; }
        if ((kb & 1) && ++sa == NS1A) { sa = 0; pha ^= 1; }
      }
      const int lr = lane & 7, lm = lane >> 3;
      const bool le0 = 2 * (lane & 3) <= (lane >> 2), le1 = 2 * (lane & 3) + 1 <= (lane >> 2);
      const uint32_t maskLE = (le0 ? 0x0000FFFFu : 0u) | (le1 ? 0xFFFF0000u : 0u);
      uint32_t q[4][8], k[5][8], vt[5][8];
      {
        static_assert(15 % NS1A == 0 && 30 % NS1B == 0, "slots of the last k blocks");
        asm volatile("ld.volatile.global.v4.u32 {%0,%1,%2,%3}, [%4];\n"
                     : "=r"(t[0].r), "=r"(t[1].r), "=r"(t[0].i), "=r"(t[1].i) : "l"(g_tab + 1536 + wtid * 4) : "memory");
        mbar_wait(bars + 8 * BAR_FULLA, 1);
        mbar_wait(bars + 8 * BAR_FULLB, 0);
        mbar_wait(bars + 8 * (BAR_FULLB + 1), 0);
        mbar_wait(bars + 8 * (BAR_EMPTYA + 1), 0);
        const uint64_t da = mkdesc(sb + wg * 16384, 16, 2048, 1);
        const uint64_t db = mkdesc(sb + OFF_1B, 4096, 1024, 1);
        wg_fence();
#pragma unroll
        for (int i = 0; i < 4; i++) wgmma_n192(acc0, da + 64 + 2 * i, db + (i >> 1) * (STG1B >> 4) + (i & 1) * 128, 1);
        wg_commit();
#pragma unroll
        for (int i = 0; i < 2; i++) wgmma_n192(acc1, da + 2 * i, db + (i >> 1) * (STG1B >> 4) + (i & 1) * 128, 1);
        wg_commit();
        wg_wait<1>();
        fence_regs(acc0);
        PROFA(45, 0);
        attn_pack<8, 1, false>(acc0, k[4]);
        attn_pack<16, 1, true>(acc0, vt[4]);
        const uint32_t kh = sb + (warp == 7 ? OFF_OP + 7 * 4096 : OFF_KH + (warp + 1) * 2048) + lane * 16;
        sts128(kh, k[4][0], k[4][1], k[4][2], k[4][3]);
        sts128(kh + 512, k[4][4], k[4][5], k[4][6], k[4][7]);
#pragma unroll
        for (int i = 0; i < 4; i++) sts64(kh - lane * 8 + 1024 + 256 * i, vt[4][2 * i], vt[4][2 * i + 1]);
#pragma unroll
        for (int i = 2; i < 4; i++) wgmma_n192(acc1, da + 2 * i, db + (i >> 1) * (STG1B >> 4) + (i & 1) * 128, 1);
        wg_commit();
        attn_pack<0, 0, false>(acc0, q[1]);
        attn_pack<0, 1, false>(acc0, q[3]);
        attn_pack<8, 0, false>(acc0, k[2]);
        attn_pack<16, 0, true>(acc0, vt[2]);
        uint32_t z = p.zero;
#pragma unroll
        for (int i = 0; i < 8; i++) z &= q[1][i] & q[3][i];
#pragma unroll
        for (int i = 0; i < 8; i += 2) z &= k[2][i] & k[2][i + 1];
        __syncwarp();
        if (lane == 0) mbar_arrive(bars + 8 * BAR_STG + z);
        wg_wait<0>();
        fence_regs(acc1);
        if (MODE == 0) nb_arrive(NB_G1END, 288);
      }
      PROF(2 + wg);
      mbar_wait(bars + 8 * (warp == 0 ? BAR_HALO : BAR_STG), 0);
      {
        const uint32_t kh = sb + OFF_KH + warp * 2048 + lane * 16;
#pragma unroll
        for (int i = 0; i < 2; i++) {
          const uint4 t = lds128(kh + 512 * i);
          k[0][4 * i] = t.x; k[0][4 * i + 1] = t.y; k[0][4 * i + 2] = t.z; k[0][4 * i + 3] = t.w;
        }
#pragma unroll
        for (int i = 0; i < 4; i++) {
          const uint2 t = lds64(kh - lane * 8 + 1024 + 256 * i);
          vt[0][2 * i] = t.x; vt[0][2 * i + 1] = t.y;
        }
      }
      attn_pack<0, 0, false>(acc1, q[0]);
      attn_pack<0, 1, false>(acc1, q[2]);
      attn_pack<8, 0, false>(acc1, k[1]);
      attn_pack<8, 1, false>(acc1, k[3]);
      {
        float x[8][2];
        uint32_t pp[8];
        const bool first = warp == 0 && gidx == 0;
#pragma unroll
        for (int hd = 0; hd < 2; hd++) {
#pragma unroll
          for (int j = 0; j < 4; j += 2) {
            float s0[4], s1[4], s2[4];
            attn_qk(s2, q[j], q[j + 1], k[j + 2], 4 * hd);
            attn_qk(s1, q[j], q[j + 1], k[j + 1], 4 * hd);
            attn_qk(s0, q[j], q[j + 1], k[j], 4 * hd);
            if (j == 0 && first) s0[0] = s0[1] = -1e9f / 0.17677669529663687f;
            x[2 * j + hd][0] = le0 ? s1[0] : s0[0];
            x[2 * j + hd][1] = le1 ? s1[1] : s0[1];
            x[2 * j + 2 + hd][0] = le0 ? s2[2] : s1[2];
            x[2 * j + 2 + hd][1] = le1 ? s2[3] : s1[3];
          }
        }
        PROFA(40, __float_as_uint(x[1][0] + x[7][1]));
        attn_pack<16, 0, true>(acc1, vt[1]);
        attn_pack<16, 1, true>(acc1, vt[3]);
        quad_softmax<8>(x, pp);
        PROFA(41, pp[1] + pp[7]);
        mbar_wait(bars + 8 * BAR_X, 0);
        ldsm4(a1[0], sb + OFF_T32 + (warp & 3) * 1024 + lane * 16);
        ldsm4(a1[1], sb + OFF_T32 + 512 + (warp & 3) * 1024 + lane * 16);
        {
          const uint32_t ex = sb + OFF_EX + wg * 16 + (warp & 2) * 2;
#pragma unroll
          for (int i = 0; i < 2; i++) sc[i] = min(max(381 - (int)lds32(ex + 8 * i) - (int)lds32(ex + 32 + 8 * i), 1), 254) * 0x00800080u;
        }
        const uint32_t obase = sb + OFF_OP + (warp * 32 + lr) * 128;
#pragma unroll
        for (int n = 0; n < 8; n++) {
          attn_pv(obase + (n >> 1) * 1024 + (((4 * (n & 1) + lm) ^ lr) << 4), vt[n >> 1], vt[(n >> 1) + 1], 4 * (n & 1), pp[n],
                  maskLE);
        }
      }
      PROFA(42, 0);
    }

    {
      const int w = warp & 3;
      const int lr = lane & 7, lm = lane >> 3;
      const uint32_t xb = sb + OFF_X + wg * 4 * XT;
      auto uo = [](int c) { return (c & 1) * 2 * XT + (c >> 1) * 2048; };
      const uint64_t dc2 = mkdesc(sb + OFF_T16, 512, 128, 0), dc3 = mkdesc(sb + OFF_T16, 128, 512, 0);
      const uint64_t dc4 = mkdesc(sb + OFF_T32, 128, 256, 0);
      const uint64_t dx = mkdesc(xb, 4096, 512, 2), dz = mkdesc(xb, 4096, 256, 3);
      const uint32_t zs = xb + (w * 16 + (lm & 1) * 8 + lr) * 32 + (((lm >> 1) ^ (lr >> 2)) << 4);
      const uint32_t ys = xb + w * 4096 + (lm >> 1) * 256 + ((lr * 32 + (((lm & 1) ^ (lr >> 2)) << 4)) ^ (rank << 6) ^ ((w & 2) << 4));
      const bool own = (w & 1) == rank;
      const uint32_t ybar = mapa(bars, own ? rank ^ 1 : rank) + 8 * BAR_Y;
      uint32_t d[2][32], pa[2][4][2][4], e[4][4][8], ya[2][2][2][4], v[2][2][8];
      C2 s1[2][2][2];
      float o[2][16];
      auto rows = [&](int c) {
        fft_rows(d[c & 1], a1, dx + (uo(c) >> 4));
        wg_commit();
      };
      auto cols = [&](int c) {
        const int s = c & 1;
        fence_regs(d[s]);
#pragma unroll
        for (int i = 0; i < 16; i++) {
          const C2 z = crot(C2{d[s][2 * i], d[s][2 * i + 1]}, t[i & 1]);
          pa[s][i >> 2][i & 1][(i >> 1) & 1] = z.r;
          pa[s][i >> 2][i & 1][2 + ((i >> 1) & 1)] = z.i;
        }
        wg_fence();
#pragma unroll
        for (int i = 0; i < 4; i++) fft_cols<0>(e[c][i], pa[s][i], dc2);
        wg_commit();
      };
      auto prod = [&](int c, int n) {
        const int s = c & 1;
        fence_regs(e[c][2 * n]);
        fence_regs(e[c][2 * n + 1]);
#pragma unroll
        for (int j = 0; j < 2; j++) {
          const C2 u0 = cget(e[s][2 * n], j, 0), u1 = cget(e[s][2 * n], j, 1);
          const C2 h0 = cget(e[s][2 * n + 1], j, 0), h1 = cget(e[s][2 * n + 1], j, 1);
          C2 y0, y1;
          if (c < 2) {
            y0 = cmul(h0, u0);
            s1[s][n][j] = cfma(h0, u1, cmul(h1, u0));
            y1 = C2{hadd2(s1[s][n][j].r, y0.i), hadd2(s1[s][n][j].i, hneg2(y0.r))};
          } else {
            const C2 u2 = cget(e[c][2 * n], j, 0), u3 = cget(e[c][2 * n], j, 1);
            const C2 h2 = cget(e[c][2 * n + 1], j, 0), h3 = cget(e[c][2 * n + 1], j, 1);
            const C2 s2 = cfma(h0, u2, cfma(h2, u0, cmul(h1, u1)));
            y0 = C2{hadd2(s2.r, s1[s][n][j].i), hadd2(s2.i, hneg2(s1[s][n][j].r))};
            y1 = cfma(h0, u3, cfma(h1, u2, cfma(h2, u1, cfma(h3, u0, C2{s2.i, hneg2(s2.r)}))));
          }
          ya[s][n][j][0] = y0.r;
          ya[s][n][j][1] = y1.r;
          ya[s][n][j][2] = y0.i;
          ya[s][n][j][3] = y1.i;
        }
      };
      auto icols = [&](int c) {
        wg_fence();
        fft_cols<1>(v[c & 1][0], ya[c & 1][0], dc3);
        fft_cols<1>(v[c & 1][1], ya[c & 1][1], dc3);
        wg_commit();
      };
      auto stage = [&](int c) {
        const int s = c & 1;
        fence_regs(v[s][0]);
        fence_regs(v[s][1]);
#pragma unroll
        for (int b = 0; b < 4; b++) {
          const C2 x0 = cget(v[s][b >> 1], 0, b & 1), x1 = cget(v[s][b >> 1], 1, b & 1);
          const C2 z0 = crot(C2{x0.i, x0.r}, t[0]), z1 = crot(C2{x1.i, x1.r}, t[1]);
          stsm4(zs + uo(c) + b * 4096, z0.i, z0.r, z1.i, z1.r);
        }
      };
      auto back = [&](int c) {
        fft_back(o[c & 1], dz + (uo(c) >> 4), dc4);
        wg_commit();
      };
      auto out = [&](int c) {
        float (&r)[16] = o[c & 1];
        fence_regs(r);
#pragma unroll
        for (int i = 0; i < 16; i += 8)
          stsm4t(ys + uo(c) + 64 * i, bmul2(pack_bf16(r[i], r[i + 1]), sc[c & 1]), bmul2(pack_bf16(r[i + 2], r[i + 3]), sc[c & 1]),
                 bmul2(pack_bf16(r[i + 4], r[i + 5]), sc[c & 1]), bmul2(pack_bf16(r[i + 6], r[i + 7]), sc[c & 1]));
      };
      auto signal = [&](int yb, int land) {
        __syncwarp();
        if (lane == 0) {
          mbar_arrive_cluster(ybar + 8 * yb);
          if (own && land >= 0) mbar_arrive(bars + 8 * (BAR_LAND + land));
        }
      };
      wg_fence();
      rows(0);
      rows(1);
      fence_async_smem();
      nb_arrive(NB_OREADY, 288);
      PROF(34 + wg);
      wg_wait<1>();
      cols(0);
      wg_wait<1>();
      cols(1);
      rows(2);
      nb_sync(NB_CONV + wg, 128);
      wg_wait<2>();
      prod(0, 0);
      prod(0, 1);
      icols(0);
      wg_wait<2>();
      prod(1, 0);
      prod(1, 1);
      icols(1);
      PROF3(40 + 10 * wg);
      wg_wait<1>();
      stage(0);
      wg_wait<0>();
      stage(1);
      fence_async_smem();
      cols(2);
      PROF3(41 + 10 * wg);
      nb_sync(NB_CONV + wg, 128);
      back(0);
      back(1);
      wg_wait<2>();
      wg_fence();
      rows(3);
      prod(2, 0);
      wg_wait<1>();
      out(0);
      out(1);
      signal(wg, 0);
      PROF3(42 + 10 * wg);
      prod(2, 1);
      icols(2);
      wg_wait<1>();
      cols(3);
      PROF3(43 + 10 * wg);
      wg_wait<1>();
      stage(2);
      fence_async_smem();
      wg_wait<0>();
      prod(3, 0);
      nb_sync(NB_CONV + wg, 128);
      wg_fence();
      back(2);
      prod(3, 1);
      icols(3);
      PROF3(44 + 10 * wg);
      wg_wait<1>();
      out(2);
      signal(2, -1);
      wg_wait<0>();
      stage(3);
      PROF3(45 + 10 * wg);
      fence_async_smem();
      nb_sync(NB_CONV + wg, 128);
      wg_fence();
      back(3);
      constexpr int G = MODE == 0 && EARLY;
      if (MODE == 0) mbar_wait(bars + 8 * (BAR_EMPTY2 + 4), 0);
      if (G) g2_block(0, 0, 0);
      wg_wait<G>();
      if (lane == 0) mbar_arrive_cluster(mapa(bars, 1) + 8 * BAR_TAB);
      out(3);
      signal(3, 1);
      PROF(6 + wg);
    }
    }

    if (MODE != 1) {
      if (MODE == 2 || !EARLY) g2_block(0, 0, 0);
      int sprev = 0;
      unsigned long long seq = G2_SEQ >> 4;
#pragma unroll 1
      for (int kb = 1; kb < 16; kb++, seq >>= 4) {
        const int s = seq & 7, ph = (seq >> 3) & 1;
        const bool rel = kb + NS2 <= 16 && signaller;
        const bool hold = kb == 16 - ENDG && wg != LEADWG;
        if (hold) {
          wg_wait<0>();
          if (rel) mbar_arrive_cluster(g2rel + 8 * sprev);
          nb_sync(NB_LEAD, 256);
        }
        g2_block(1, s, ph);
        if (kb == 2) PROF(8 + wg);
        if (warp == LEADWG * 4) PROF2(40 + kb);
        if (kb == LEADKB && wg == LEADWG) nb_arrive(NB_LEAD, 256);
        wg_wait<1>();
        if (rel && !hold) mbar_arrive_cluster(g2rel + 8 * sprev);
        sprev = s;
      }
      static_assert(ENDG <= NS2, "the last stages stay resident");
      const int lr = lane & 7, lm = lane >> 3;
      const uint32_t wb = sb + g2_a(1, 0) + warp * 2048;
      const int orow = (rb2 & 7) * 128 + warp * 16;
      const int rr = lane >> 3;
      uint4* og = reinterpret_cast<uint4*>(p.out + (size_t)(2 * (orow + rr) + (rb2 >> 3)) * (2 * DM) + DM + cb2 * 128 + lr * 8);
      wg_wait<0>();
      fence_regs(acc);
      PROF(10 + wg);
#pragma unroll
      for (int h = 0; h < 2; h++) {
        const uint32_t b = wb + h * (g2_a(3, 0) - g2_a(1, 0));
#pragma unroll
        for (int j = 8 * h; j < 8 * h + 8; j += 2)
          stsm4(b + (lr + 8 * (lm & 1)) * 128 + ((((j & 7) + (lm >> 1)) ^ lr) << 4), pack_bf16(acc[4 * j], acc[4 * j + 1]),
                pack_bf16(acc[4 * j + 2], acc[4 * j + 3]), pack_bf16(acc[4 * j + 4], acc[4 * j + 5]),
                pack_bf16(acc[4 * j + 6], acc[4 * j + 7]));
        if (OTMA == 2 || (OTMA == 1 && wg == LEADWG)) {
          fence_async_smem();
          __syncwarp();
          if (elect_one()) {
            tma_store_3d(&tmOb, b, DM + cb2 * 128 + h * 64, rb2 >> 3, orow);
            bulk_commit();
          }
        } else {
          __syncwarp();
          uint4 v[4];
#pragma unroll
          for (int i = 0; i < 4; i++) v[i] = lds128(b + (4 * i + rr) * 128 + ((lr ^ ((4 * i + rr) & 7)) << 4));
#pragma unroll
          for (int i = 0; i < 4; i++) og[(size_t)i * 8 * (2 * DM / 8) + h * 8] = v[i];
        }
      }
      PROF(12 + wg);
      if (OTMA) bulk_wait0();
    }
    cluster_sync_all();
  }
}

typedef CUresult (*EncodeFn)(CUtensorMap*, CUtensorMapDataType, cuuint32_t, void*, const cuuint64_t*, const cuuint64_t*,
                             const cuuint32_t*, const cuuint32_t*, CUtensorMapInterleave, CUtensorMapSwizzle,
                             CUtensorMapL2promotion, CUtensorMapFloatOOBfill);

void make_map(EncodeFn enc, CUtensorMap* tm, const void* base, int rank, const cuuint64_t* dims, const cuuint64_t* strides,
              const cuuint32_t* box, CUtensorMapSwizzle swz) {
  cuuint32_t es[5] = {1, 1, 1, 1, 1};
  enc(tm, CU_TENSOR_MAP_DATA_TYPE_BFLOAT16, rank, const_cast<void*>(base), dims, strides, box, es,
      CU_TENSOR_MAP_INTERLEAVE_NONE, swz, CU_TENSOR_MAP_L2_PROMOTION_L2_256B, CU_TENSOR_MAP_FLOAT_OOB_FILL_NONE);
}

}

extern "C" void kernel_launch(void* const* d_in, const int* in_sizes, int n_in, void* d_out, int out_size) {
  static EncodeFn enc = nullptr;
  static bool coresident = true;
  if (!enc) {
    void* fn = nullptr;
    cudaDriverEntryPointQueryResult qr;
    cudaGetDriverEntryPoint("cuTensorMapEncodeTiled", &fn, cudaEnableDefault, &qr);
    enc = (EncodeFn)fn;
    cudaFuncSetAttribute(fused_kernel<0>, cudaFuncAttributeMaxDynamicSharedMemorySize, SMEM_BYTES);
    cudaFuncSetAttribute(fused_kernel<1>, cudaFuncAttributeMaxDynamicSharedMemorySize, SMEM_BYTES);
    cudaFuncSetAttribute(fused_kernel<2>, cudaFuncAttributeMaxDynamicSharedMemorySize, SMEM_BYTES);
    cudaLaunchConfig_t cfg = {};
    cfg.gridDim = dim3(NCTA);
    cfg.blockDim = dim3(NTHREADS);
    cfg.dynamicSmemBytes = SMEM_BYTES;
    cudaLaunchAttribute at;
    at.id = cudaLaunchAttributeClusterDimension;
    at.val.clusterDim.x = 2;
    at.val.clusterDim.y = 1;
    at.val.clusterDim.z = 1;
    cfg.attrs = &at;
    cfg.numAttrs = 1;
    int nclusters = 0;
    if (cudaOccupancyMaxActiveClusters(&nclusters, fused_kernel<0>, &cfg) == cudaSuccess) coresident = nclusters >= NCTA / 2;
    (void)cudaGetLastError();
  }
  CUtensorMap tmX, tmW, tmWo, tmWp, tmQ, tmOb, tmXh, tmWh;
  {
    cuuint64_t dims[3] = {1024, 2, 1024};
    cuuint64_t str[2] = {2048, 4096};
    cuuint32_t box[3] = {64, 1, 128};
    make_map(enc, &tmX, d_in[6], 3, dims, str, box, CU_TENSOR_MAP_SWIZZLE_128B);
  }
  {
    cuuint64_t dims[3] = {1024, 1024, 3};
    cuuint64_t str[2] = {6144, 2048};
    cuuint32_t box[3] = {64, 32, 3};
    make_map(enc, &tmW, d_in[7], 3, dims, str, box, CU_TENSOR_MAP_SWIZZLE_128B);
  }
  {
    cuuint64_t dims[3] = {64, 1024, 16};
    cuuint64_t str[2] = {2048, 128};
    cuuint32_t box[3] = {64, 64, 2};
    cuuint32_t piece[3] = {64, 32, 1};
    make_map(enc, &tmWo, d_in[8], 3, dims, str, box, CU_TENSOR_MAP_SWIZZLE_128B);
    make_map(enc, &tmWp, d_in[8], 3, dims, str, piece, CU_TENSOR_MAP_SWIZZLE_128B);
  }
  {
    cuuint64_t dims[5] = {1024, 2, 2, 4, 128};
    cuuint64_t str[4] = {2048, 8 * 2048, 2 * 2048, 16 * 2048};
    cuuint32_t box[5] = {16, 2, 2, 4, 32};
    make_map(enc, &tmQ, d_in[0], 5, dims, str, box, CU_TENSOR_MAP_SWIZZLE_NONE);
  }
  {
    cuuint64_t dims[3] = {2048, 2, 1024};
    cuuint64_t str[2] = {4096, 8192};
    cuuint32_t box[3] = {64, 1, 16};
    make_map(enc, &tmOb, d_out, 3, dims, str, box, CU_TENSOR_MAP_SWIZZLE_128B);
  }
  {
    cuuint64_t dims[4] = {1024, 256, 2, 4};
    cuuint64_t str[3] = {4096, 2048, 256 * 4096};
    cuuint32_t box[4] = {64, 8, 2, 3};
    make_map(enc, &tmXh, d_in[6], 4, dims, str, box, CU_TENSOR_MAP_SWIZZLE_128B);
  }
  {
    cuuint64_t dims[3] = {64, 1024, 48};
    cuuint64_t str[2] = {6144, 128};
    cuuint32_t box[3] = {64, 64, 4};
    make_map(enc, &tmWh, d_in[7], 3, dims, str, box, CU_TENSOR_MAP_SWIZZLE_128B);
  }
  Params p;
  p.q = (const __nv_bfloat16*)d_in[0];
  p.k = (const __nv_bfloat16*)d_in[1];
  p.v = (const __nv_bfloat16*)d_in[2];
  p.shift_k = (const __nv_bfloat16*)d_in[3];
  p.ssm_k = (const __nv_bfloat16*)d_in[4];
  p.ssm_D = (const __nv_bfloat16*)d_in[5];
  p.x = (const __nv_bfloat16*)d_in[6];
  p.w = (const __nv_bfloat16*)d_in[7];
  p.wo = (const __nv_bfloat16*)d_in[8];
  p.out = (__nv_bfloat16*)d_out;
  p.zero = 0;
  if (coresident) {
    fused_kernel<0><<<NCTA, NTHREADS, SMEM_BYTES>>>(p, tmX, tmW, tmWo, tmWp, tmQ, tmOb, tmXh, tmWh);
  } else {
    fused_kernel<0><<<4, NTHREADS, SMEM_BYTES>>>(p, tmX, tmW, tmWo, tmWp, tmQ, tmOb, tmXh, tmWh);
    fused_kernel<1><<<NCTA, NTHREADS, SMEM_BYTES>>>(p, tmX, tmW, tmWo, tmWp, tmQ, tmOb, tmXh, tmWh);
    fused_kernel<2><<<NCTA, NTHREADS, SMEM_BYTES>>>(p, tmX, tmW, tmWo, tmWp, tmQ, tmOb, tmXh, tmWh);
  }
}
```

```cpp
#include <cuda_runtime.h>
#include <cuda.h>
#include <cuda_bf16.h>
#include <stdint.h>

namespace {

constexpr int SEQ = 2048;
constexpr int DM = 1024;
constexpr int NCTA = 132;
constexpr int NTHREADS = 384;

constexpr int STG1A = 32768;
constexpr int NS1A = 3;
constexpr int STG1B = 12288;
constexpr int NS1B = 5;
constexpr int OFF_1B = NS1A * STG1A;
constexpr int STG2 = 32768;
constexpr int NS2 = 5;
#define G2SEQ 0x4032140321403210ull
constexpr unsigned long long g2_seq() {
  unsigned long long r = G2SEQ;
  for (int kb = 0; kb < 16; kb++)
    for (int j = 0; j < kb; j++)
      if (((G2SEQ >> (4 * j)) & 7) == ((G2SEQ >> (4 * kb)) & 7)) r ^= 8ull << (4 * kb);
  return r;
}
constexpr unsigned long long G2_SEQ = g2_seq();
constexpr int g2_first4() {
  int kb = 0;
  while (((G2SEQ >> (4 * kb)) & 7) != 4) kb++;
  return kb;
}
constexpr int G2_KB4 = g2_first4();
#define POLL0 1500
#define QORD 1
#define BDEL 0
#define XPF 0
#define HPF0 3
#define PF0 8
#define PF1 12
#define PSTEP 1150
#define FPACE 260
#define LEADWG 1
#define OTMA 1
#define EARLY 1
#define R3 0
#define FSL 50
#define ENDG 5
__device__ __forceinline__ uint32_t g2_a(int s, int hsel) { return (((0x97524 >> (4 * s)) & 15) ^ (s & 5 ? 0 : hsel)) << 14; }
constexpr int OFF_Q0 = 3 << 14, OFF_Q1 = 8 << 14;
constexpr int STGH = 73728;
constexpr int OFF_KH = 1 * STG2;
constexpr int OFF_OP = 2 * STG2;
constexpr int OFF_T32 = 5 * STG2 - 4096;
constexpr int OFF_X = 5 * STG2;
constexpr int XT = 8192;
__device__ __forceinline__ uint32_t g2_b(int s, int rank) {
  return s < 3 ? (s == 2 ? 6 : s) << 14 : OFF_X + (s - 3) * 2 * XT + (rank ^ 1) * 4096;
}
__device__ __forceinline__ uint32_t g2_bk(int s) { return s < 3 ? 4096 : 4 * XT; }
constexpr int OFF_BAR = OFF_X + 8 * XT;
constexpr int OFF_EX = OFF_BAR + 448;
constexpr int OFF_T16 = 230400;
constexpr int SMEM_BYTES = OFF_T16 + 2048;
static_assert(OFF_1B + NS1B * STG1B <= OFF_T32 && OFF_X % 1024 == 0, "layout");
static_assert(3 * STGH <= OFF_BAR && OFF_EX + 64 <= OFF_T16 && SMEM_BYTES <= 232448, "smem");

constexpr int BAR_FULLA = 0;
constexpr int BAR_EMPTYA = 3;
constexpr int BAR_FULLB = 6;
constexpr int BAR_EMPTYB = 11;
constexpr int BAR_FULL2 = 16;
constexpr int BAR_EMPTY2 = 21;
constexpr int BAR_EMPTY2B = 44;
constexpr int BAR_X = 26;
constexpr int BAR_LAND = 42;
constexpr int BAR_TAB = 28;
constexpr int BAR_U = 29;
constexpr int BAR_H = 30;
constexpr int BAR_STG = 31;
constexpr int BAR_Y = 32;
constexpr int BAR_XFREE = 38;
constexpr int BAR_HALO = 40;
constexpr int BAR_Q = 41;

constexpr int NB_G1DONE = 1;
constexpr int NB_LEAD = 2;
constexpr int NB_G1END = 3;
constexpr int NB_OREADY = 4;
constexpr int NB_CONV = 5;
constexpr int NB_HELP3 = 11;
constexpr int NB_FIRST = 13;

#define REG_MATH 224
#define REG_HELP 56
constexpr int SPIN_LIMIT = 1 << 20;

__device__ __align__(1024) __nv_bfloat16 g_o[SEQ * DM];
__device__ uint32_t g_flag_o[128];
__device__ uint32_t g_flag_h[4];
__device__ uint4 g_halo[128 * 128];
__device__ __align__(128) const uint32_t g_tab[2048] = {
  0x2fd93000,0x2ea72f64,0x2c722da8,0x263e2a1f,0x2ea73000,0xa63e2a1f,0xafd9ada8,0xac72af64,0x2c723000,0xafd9aa1f,0x263eada8,0x2ea72f64,
  0x263e3000,0xac72af64,0x2ea72da8,0xafd9aa1f,0xa63e3000,0x2c72af64,0xaea72da8,0x2fd9aa1f,0xac723000,0x2fd9aa1f,0xa63eada8,0xaea72f64,
  0xaea73000,0x263e2a1f,0x2fd9ada8,0x2c72af64,0xafd93000,0xaea72f64,0xac722da8,0xa63e2a1f,0x263e0000,0x2c722a1f,0x2ea72da8,0x2fd92f64,
  0x2c720000,0x2fd92f64,0x263e2da8,0xaea7aa1f,0x2ea70000,0x263e2f64,0xafd9ada8,0x2c72aa1f,0x2fd90000,0xaea72a1f,0x2c72ada8,0xa63e2f64,
  0x2fd90000,0xaea7aa1f,0x2c722da8,0xa63eaf64,0x2ea70000,0x263eaf64,0xafd92da8,0x2c722a1f,0x2c720000,0x2fd9af64,0x263eada8,0xaea72a1f,
  0x263e0000,0x2c72aa1f,0x2ea7ada8,0x2fd9af64,0xafd93000,0xaea72f64,0xac722da8,0xa63e2a1f,0xaea73000,0x263e2a1f,0x2fd9ada8,0x2c72af64,
  0xac723000,0x2fd9aa1f,0xa63eada8,0xaea72f64,0xa63e3000,0x2c72af64,0xaea72da8,0x2fd9aa1f,0x263e3000,0xac72af64,0x2ea72da8,0xafd9aa1f,
  0x2c723000,0xafd9aa1f,0x263eada8,0x2ea72f64,0x2ea73000,0xa63e2a1f,0xafd9ada8,0xac72af64,0x2fd93000,0x2ea72f64,0x2c722da8,0x263e2a1f,
  0xa63e0000,0xac722a1f,0xaea72da8,0xafd92f64,0xac720000,0xafd92f64,0xa63e2da8,0x2ea7aa1f,0xaea70000,0xa63e2f64,0x2fd9ada8,0xac72aa1f,
  0xafd90000,0x2ea72a1f,0xac72ada8,0x263e2f64,0xafd90000,0x2ea7aa1f,0xac722da8,0x263eaf64,0xaea70000,0xa63eaf64,0x2fd92da8,0xac722a1f,
  0xac720000,0xafd9af64,0xa63eada8,0x2ea72a1f,0xa63e0000,0xac72aa1f,0xaea7ada8,0xafd9af64,0xa63e0000,0xac72aa1f,0xaea7ada8,0xafd9af64,
  0xac720000,0xafd9af64,0xa63eada8,0x2ea72a1f,0xaea70000,0xa63eaf64,0x2fd92da8,0xac722a1f,0xafd90000,0x2ea7aa1f,0xac722da8,0x263eaf64,
  0xafd90000,0x2ea72a1f,0xac72ada8,0x263e2f64,0xaea70000,0xa63e2f64,0x2fd9ada8,0xac72aa1f,0xac720000,0xafd92f64,0xa63e2da8,0x2ea7aa1f,
  0xa63e0000,0xac722a1f,0xaea72da8,0xafd92f64,0x2fd93000,0x2ea72f64,0x2c722da8,0x263e2a1f,0x2ea73000,0xa63e2a1f,0xafd9ada8,0xac72af64,
  0x2c723000,0xafd9aa1f,0x263eada8,0x2ea72f64,0x263e3000,0xac72af64,0x2ea72da8,0xafd9aa1f,0xa63e3000,0x2c72af64,0xaea72da8,0x2fd9aa1f,
  0xac723000,0x2fd9aa1f,0xa63eada8,0xaea72f64,0xaea73000,0x263e2a1f,0x2fd9ada8,0x2c72af64,0xafd93000,0xaea72f64,0xac722da8,0xa63e2a1f,
  0x263e0000,0x2c72aa1f,0x2ea7ada8,0x2fd9af64,0x2c720000,0x2fd9af64,0x263eada8,0xaea72a1f,0x2ea70000,0x263eaf64,0xafd92da8,0x2c722a1f,
  0x2fd90000,0xaea7aa1f,0x2c722da8,0xa63eaf64,0x2fd90000,0xaea72a1f,0x2c72ada8,0xa63e2f64,0x2ea70000,0x263e2f64,0xafd9ada8,0x2c72aa1f,
  0x2c720000,0x2fd92f64,0x263e2da8,0xaea7aa1f,0x263e0000,0x2c722a1f,0x2ea72da8,0x2fd92f64,0xafd93000,0xaea72f64,0xac722da8,0xa63e2a1f,
  0xaea73000,0x263e2a1f,0x2fd9ada8,0x2c72af64,0xac723000,0x2fd9aa1f,0xa63eada8,0xaea72f64,0xa63e3000,0x2c72af64,0xaea72da8,0x2fd9aa1f,
  0x263e3000,0xac72af64,0x2ea72da8,0xafd9aa1f,0x2c723000,0xafd9aa1f,0x263eada8,0x2ea72f64,0x2ea73000,0xa63e2a1f,0xafd9ada8,0xac72af64,
  0x2fd93000,0x2ea72f64,0x2c722da8,0x263e2a1f,0xa63e0000,0xac72aa1f,0xaea7ada8,0xafd9af64,0x2c720000,0x2fd92f64,0x263e2da8,0xaea7aa1f,
  0xaea70000,0xa63eaf64,0x2fd92da8,0xac722a1f,0x2fd90000,0xaea72a1f,0x2c72ada8,0xa63e2f64,0xafd90000,0x2ea72a1f,0xac72ada8,0x263e2f64,
  0x2ea70000,0x263eaf64,0xafd92da8,0x2c722a1f,0xac720000,0xafd92f64,0xa63e2da8,0x2ea7aa1f,0x263e0000,0x2c72aa1f,0x2ea7ada8,0x2fd9af64,
  0x2fd93000,0x2ea72f64,0x2c722da8,0x263e2a1f,0xaea7b000,0x263eaa1f,0x2fd92da8,0x2c722f64,0x2c723000,0xafd9aa1f,0x263eada8,0x2ea72f64,
  0xa63eb000,0x2c722f64,0xaea7ada8,0x2fd92a1f,0xa63e3000,0x2c72af64,0xaea72da8,0x2fd9aa1f,0x2c72b000,0xafd92a1f,0x263e2da8,0x2ea7af64,
  0xaea73000,0x263e2a1f,0x2fd9ada8,0x2c72af64,0x2fd9b000,0x2ea7af64,0x2c72ada8,0x263eaa1f,0x263e0000,0x2c72aa1f,0x2ea7ada8,0x2fd9af64,
  0xac720000,0xafd92f64,0xa63e2da8,0x2ea7aa1f,0x2ea70000,0x263eaf64,0xafd92da8,0x2c722a1f,0xafd90000,0x2ea72a1f,0xac72ada8,0x263e2f64,
  0x2fd90000,0xaea72a1f,0x2c72ada8,0xa63e2f64,0xaea70000,0xa63eaf64,0x2fd92da8,0xac722a1f,0x2c720000,0x2fd92f64,0x263e2da8,0xaea7aa1f,
  0xa63e0000,0xac72aa1f,0xaea7ada8,0xafd9af64,0xafd93000,0xaea72f64,0xac722da8,0xa63e2a1f,0x2ea7b000,0xa63eaa1f,0xafd92da8,0xac722f64,
  0xac723000,0x2fd9aa1f,0xa63eada8,0xaea72f64,0x263eb000,0xac722f64,0x2ea7ada8,0xafd92a1f,0x263e3000,0xac72af64,0x2ea72da8,0xafd9aa1f,
  0xac72b000,0x2fd92a1f,0xa63e2da8,0xaea7af64,0x2ea73000,0xa63e2a1f,0xafd9ada8,0xac72af64,0xafd9b000,0xaea7af64,0xac72ada8,0xa63eaa1f,
  0xafd9b000,0xaea7af64,0xac72ada8,0xa63eaa1f,0x2ea73000,0xa63e2a1f,0xafd9ada8,0xac72af64,0xac72b000,0x2fd92a1f,0xa63e2da8,0xaea7af64,
  0x263e3000,0xac72af64,0x2ea72da8,0xafd9aa1f,0x263eb000,0xac722f64,0x2ea7ada8,0xafd92a1f,0xac723000,0x2fd9aa1f,0xa63eada8,0xaea72f64,
  0x2ea7b000,0xa63eaa1f,0xafd92da8,0xac722f64,0xafd93000,0xaea72f64,0xac722da8,0xa63e2a1f,0xa63e0000,0xac72aa1f,0xaea7ada8,0xafd9af64,
  0x2c720000,0x2fd92f64,0x263e2da8,0xaea7aa1f,0xaea70000,0xa63eaf64,0x2fd92da8,0xac722a1f,0x2fd90000,0xaea72a1f,0x2c72ada8,0xa63e2f64,
  0xafd90000,0x2ea72a1f,0xac72ada8,0x263e2f64,0x2ea70000,0x263eaf64,0xafd92da8,0x2c722a1f,0xac720000,0xafd92f64,0xa63e2da8,0x2ea7aa1f,
  0x263e0000,0x2c72aa1f,0x2ea7ada8,0x2fd9af64,0x2fd9b000,0x2ea7af64,0x2c72ada8,0x263eaa1f,0xaea73000,0x263e2a1f,0x2fd9ada8,0x2c72af64,
  0x2c72b000,0xafd92a1f,0x263e2da8,0x2ea7af64,0xa63e3000,0x2c72af64,0xaea72da8,0x2fd9aa1f,0xa63eb000,0x2c722f64,0xaea7ada8,0x2fd92a1f,
  0x2c723000,0xafd9aa1f,0x263eada8,0x2ea72f64,0xaea7b000,0x263eaa1f,0x2fd92da8,0x2c722f64,0x2fd93000,0x2ea72f64,0x2c722da8,0x263e2a1f,
  0x263e0000,0x2c72aa1f,0x2ea7ada8,0x2fd9af64,0xac720000,0xafd92f64,0xa63e2da8,0x2ea7aa1f,0x2ea70000,0x263eaf64,0xafd92da8,0x2c722a1f,
  0xafd90000,0x2ea72a1f,0xac72ada8,0x263e2f64,0x2fd90000,0xaea72a1f,0x2c72ada8,0xa63e2f64,0xaea70000,0xa63eaf64,0x2fd92da8,0xac722a1f,
  0x2c720000,0x2fd92f64,0x263e2da8,0xaea7aa1f,0xa63e0000,0xac72aa1f,0xaea7ada8,0xafd9af64,0x316c2fbd,0x343e32f7,0x35bc34ff,0x372c3676,
  0x371532c6,0x3a81392e,0x3bef3b71,0x3b7c3bf2,0x397034cf,0x3bfc3b6c,0x38b23b04,0xb40e31e8,0x3ae13631,0x39e73bf5,0xb6e83219,0xbbe8bb13,
  0x3bc23785,0x30be3aa9,0xbbfdb911,0x2a16b9aa,0x3bfe3865,0xb80f37a6,0xb82abc00,0x3bfd376f,0x3b9238fd,0xbb7f2311,0x3805b929,0x31223bde,
  0x3a85398b,0xbb96b742,0x3bff319e,0xbbb82f8b,0xbbe2bbf1,0xbbb7bbcf,0xbb78bb9a,0xbb27bb52,0xbb2cbbd2,0xb8a8ba19,0xb029b5df,0x35a52f59,
  0xb9dfbba1,0x2ba7b5f7,0x3a7a37b2,0x3bbd3bdd,0xb815bb60,0x39662e91,0x3b373bda,0xb0d7377a,0xb3d3bb10,0x3be9386f,0x2a7a3a31,0xbbfeb9a6,
  0x294dbab0,0x3ae53b07,0xbad51fdb,0xab43bb16,0x352fba41,0x35993c00,0xbaebba1d,0x3be531cf,0x38a3b9c5,0xb5173b21,0x2776bbe0,0x34323bf2,
  0x384537dd,0x38ea3899,0x39823937,0x3a0d39c9,0x39463a93,0x3340374e,0xb426a452,0xb979b7c8,0xbb45b924,0xbb32bc00,0xb371b902,0x38d63294,
  0xb08db9a1,0x3b3f379b,0x39583bd7,0xb8252dfb,0x3bea3a2d,0xb3ba3874,0xbb89bb0d,0x36d2b625,0xb6bb387f,0xb8d1bbf5,0x3be73602,0xb546391f,
  0xba00bb01,0x3bff35eb,0xba5c34db,0x3359bab6,0x3ac7b66b,0xb9413933,0x368dbabd,0xb0103bb3,0xbac4baf7,0xba50ba8c,0xb9cdba11,0xb93cb986,
  0x3a04388e,0x3bcb3b1e,0x3bba3c00,0x39d63afe,0x36af3a21,0xb6ffa17f,0xbbc8ba3d,0xba60bbd4,0xbbebb9af,0xb6c6bb0a,0x39f43263,0x3ad83bf7,
  0x30a6b916,0x3bc33aa5,0xb55e3790,0xbb3dbb63,0x3b423a9e,0xba642ec3,0xb0f0bb6a,0x3b8e3a25,0xb94a37bd,0x2884bb6f,0x38db3b9f,0xbbc9b85a,
  0xb840bb54,0x3a093a15,0xbb4cb850,0x3bef3457,0x3a893a4d,0x3af43ac1,0x3b4f3b24,0x3b983b76,0xbb94baba,0xbbe4bbf9,0xba58bb57,0xb699b8f8,
  0x3bfe3b18,0x394f3b5c,0xb109347b,0xbae8b884,0xbbc0bb68,0xa9b1b90c,0x3b8b387a,0x38bc3ba5,0x3ade3ba7,0xb8c1324b,0xb9f0bbf6,0x39eb9648,
  0xb96bbbd6,0x3bbf3487,0xb38939b3,0xb9f8bba3,0x370a3bf3,0xbb47b994,0x3bbc2d65,0xb8ad3889,0xb153bc00,0x37213b9c,0xb97dba90,0x3af138f3,
  0xb89eb8ee,0xb7e8b84a,0xb682b737,0xb50bb5c8,0x35233855,0xb13b2d33,0xb8e0b65f,0xbb4aba45,0xa8e8b764,0x39fc3648,0x3be63bae,0x380a3a9b,
  0xb3eb360e,0xbbfeba35,0xb552baa2,0x3a7334b7,0x381ab4ab,0x3a6f3bd8,0xb95d2e5f,0xb962bc00,0xb9e3327c,0xb402bbac,0x3bc6399d,0xb95434c3,
  0x3b2faf27,0xb6a439bc,0xb41abbf9,0x3a7e3a97,0xbbe3251b,0x3b2ab4f3,0xb9d23894,0x37f3ba49,0x3bce3bb5,0x3bf03be1,0x3bff3bfa,0x3bfb3bff,
  0x2c38b1b6,0x383a34e7,0x3aee39c0,0x3bff3bb2,0xbb81bbf8,0xb53ab999,0x38302ef5,0x3bed3ab3,0xb8cc9cb6,0xbb85bbab,0x2adeb86a,0x3bc5391b,
  0x38c73bf6,0xbadbb232,0xb6ddbba9,0x3b87361a,0x3b833201,0xb0743a39,0xba76bb5e,0x3b352dc9,0xac06bbb0,0x39743b59,0xbbeeb759,0x3aceb2ad,
  0xbbccb5d4,0x3bfb2d00,0xbb7a32de,0x3a54b7d2,0xb30fb44b,0xafefb185,0xa6adacce,0x2c9c25e4,0xbbfcbbdf,0xbacbbb9e,0xb7feb990,0xa81fb463,
  0xb58d2d97,0xbb90b9b8,0xbad1bbf4,0xb05bb85f,0x3a673c00,0xb5763493,0xbbfdbaac,0xb3a2ba29,0x3a6b2e2d,0x38203bd9,0xbb3ab49f,0xb56abb65,
  0xb581bbdc,0x3bec3907,0xb8b7363c,0xb6f4bbf8,0xbbfcb46f,0x39dab654,0xb0423b1b,0xb835bbd3,0xb3283b73,0xac6abbfa,0x35b13bd0,0xb8e5bafb,
  0x38ee3a0d,0xb84aba89,0x37373af4,0xb5c8bb4f,0x35df3a81,0x2f59bbef,0xb88e3b7c,0x3b1eb946,0x2d973ae8,0x39b8bb81,0xbbf4353a,0x385f3830,
  0xb2633b3f,0x3bf7b958,0xb60eb825,0xba353bc0,0xb7853b87,0x3aa9b3d3,0x3911bbe9,0xb9aa2a7a,0xb99d3bbf,0x34c33389,0x3bdcb9f8,0x3907bb83,
  0xbb013be5,0xb5eb394a,0x34db2884,0x3ab6b8db,0xbbd03bfb,0xbafb3b7a,0xb98b3a54,0xb74238a3,0x3a4db93c,0xbac1389e,0x3b24b7e8,0xbb763682,
  0x3b71b8a8,0xbbf23029,0x3a9335a5,0xb74eba04,0x3bf8b80a,0xb999b58d,0xaef53b90,0x3ab3bad1,0x3bd7b6c6,0xadfbb9f4,0xbb683ad8,0x390c33eb,
  0x3b10b56a,0x386fbbc2,0xba3130be,0xb9a63bfd,0x39b3b402,0x3ba3bbc6,0x3201b954,0xba393581,0x37bdb122,0x3b6fba00,0x3b9fbbff,0x385aba5c,
  0x32deac6a,0x37d2b5b1,0x39c5b8e5,0x3b21ba85,0x344b3b98,0xb185bbce,0x2cce3bf0,0x25e4bbff,0xbc003340,0x3afe3426,0xb855b979,0x2d333b94,
  0x34cfbbed,0xbb6c39df,0x3b042ba7,0xb1e8ba7a,0x3aa2a9b1,0x34b7bb8b,0xbc0038bc,0x349338cc,0xba2d3bfe,0x387430a6,0x3b0dbbc3,0xb625b55e,
  0xb63cb074,0xbbf83a76,0xb8653b35,0x37a6294d,0x3bf3bbc9,0x3994bb2f,0x2d65b6a4,0xb889341a,0xb19e3517,0x2f8b2776,0x366bb432,0x3933b840,
  0x3bb5b50b,0xbbe1330f,0x3bfaafef,0xbbff26ad,0xa4523bcb,0x37c8bbba,0xbaba39d6,0x3bf9b523,0xbba1305b,0x35f73970,0x37b2bbfc,0xbbdd38b2,
  0x387abbfe,0xbba53552,0x9cb63a73,0x3babba67,0x39162a16,0x3aa5bbea,0xb790b3ba,0xbb633b89,0xbb5e3bec,0xadc938b7,0x3ab0b6f4,0x3b07bbfe,
  0xaf27b359,0xb9bc370a,0xbbf93b47,0xba973bbc,0x3be0bb96,0x3bf2bbff,0x3b54bbb8,0x3a15bac7,0xafbd3bfb,0x32f7bbe2,0xb4ff3bb7,0x3676bb78,
  0x365fbbe4,0xba453a58,0x3bdfb699,0xbb9eac38,0xb9243bbd,0x3c00b6af,0xb902b6ff,0xb2943bc8,0x3aacbb85,0xba29aade,0xb6313bc5,0x3bf5b815,
  0xbba73b3d,0x324b381a,0x3bf6ba6f,0x9648b95d,0x3c00bae5,0x376fbad5,0xb87f2b43,0xbbf53b42,0xbbb03a7e,0xbb593bfc,0xb75939da,0x32ad3042,
  0x3abdba09,0x3bb3bb4c,0x3c00bbef,0x3b9cbbe3,0x3bf12c9c,0xbbcfb16c,0x3b9a343e,0xbb52b5bc,0xbb57b13b,0x38f838e0,0xb1b6bb4a,0xb4e73bfc,
  0x3a21340e,0x217fbb45,0xba3d3b32,0x3bd4b371,0xb86ab576,0xb91b3bfd,0x3b60b3a2,0x2e91bae1,0x34ab36d2,0x3bd8bade,0xae5fb8c1,0xbc0039f0,
  0x9fdbb80f,0xbb16382a,0xba9e3bfd,0x2ec336bb,0xb46f38ad,0x3654ac06,0x3b1bb974,0x3bd3bbee,0x3850b941,0x3457b68d,0xa51bb010,0xb4f33153,
  0xb7dd3b27,0x3899bac4,0xb9373a50,0x39c9b9cd,0x3990383a,0xb463baee,0xb2c63bff,0x392ebb2c,0x3b18ba60,0xbb5c28e8,0x347b39fc,0x3884bbe6,
  0xb219b966,0xbb133b37,0x39a130d7,0x379bbbeb,0xbbf63962,0xb2323a6b,0x3ba9b820,0x361abb3a,0xb6023a64,0x391fb0f0,0x3bd6bb8e,0x3487b9e3,
  0x3a41b835,0x3c00bb92,0x3a1dbb7f,0x31cfb805,0x3a90bb2a,0x38f3b9d2,0x35d4b7f3,0x2d00b328,0x3af7372c,0xba8cb845,0x3a1138ea,0xb986b982,
  0x39c0bacb,0xbbb237fe,0x3bd2a81f,0xba19b715,0xb764b8d6,0xb6483bfe,0x3baeb94f,0xba9bb109,0xbbda39e7,0x377a36e8,0x39afbbe8,0xbb0a308d,
  0xae2d39eb,0x3bd9b8c7,0x349fbadb,0xbb6536dd,0x3b6ab8d1,0x3a25bbe7,0xb27cb546,0xbbac396b,0x38fdbace,0xa311b52f,0xb9293599,0xbbde3aeb,
  0xb8943721,0xba49397d,0xbb733af1,0xbbfa3bcc,0xbbfb3bff,0xbbe23bf1,0xbbb73bcf,0xbb783b9a,0xbb7c3bf2,0xb9463a93,0xb340374e,0x3426a452,
  0xba603bd4,0xa8e83764,0x39fcb648,0x3be6bbae,0xb8bc3ba5,0x38cc9cb6,0x3b85bbab,0xaadeb86a,0xb56a3b65,0x3bc2b785,0x30bebaa9,0xbbfd3911,
  0xab433b16,0x3b42ba9e,0xba64aec3,0xb0f03b6a,0x33593ab6,0x370abbf3,0xbb473994,0x3bbcad65,0x37f33a49,0xb328bb73,0xac6a3bfa,0x35b1bbd0,
  0xac9c25e4,0xb16c2fbd,0xb43e32f7,0xb5bc34ff,0xb5a52f59,0xba04388e,0xbbcb3b1e,0xbbba3c00,0xb8d63294,0xbbfe3b18,0xb94f3b5c,0x3109347b,
  0xba7334b7,0xba673c00,0x35763493,0x3bfdbaac,0xbb87361a,0xb3d33b10,0x3be9b86f,0x2a7aba31,0xbbfd376f,0x36bb387f,0x38d1bbf5,0xbbe73602,
  0xbbc9385a,0x3b2f2f27,0xb6a4b9bc,0xb41a3bf9,0xbaf138f3,0x3bccb5d4,0xbbfb2d00,0x3b7a32de,0xbb273b52,0xbac43af7,0xba503a8c,0xb9cd3a11,
  0x3979b7c8,0x3b94baba,0x3be4bbf9,0x3a58bb57,0x380aba9b,0xb58dad97,0xbb9039b8,0xbad13bf4,0xbbc5391b,0xb8153b60,0x3966ae91,0x3b37bbda,
  0x2a1639aa,0x3beaba2d,0xb3bab874,0xbb893b0d,0x3b8eba25,0xb9e3b27c,0xb4023bac,0x3bc6b99d,0xb8adb889,0xac063bb0,0x3974bb59,0xbbee3759,
  0xb8e53afb,0x3a85b98b,0xbb963742,0x3bffb19e,0xb72c3676,0xb84537dd,0xb8ea3899,0xb9823937,0xb9d63afe,0xb5233855,0x313b2d33,0x38e0b65f,
  0x3ae8b884,0x3b81bbf8,0x353ab999,0xb8302ef5,0x33a2ba29,0xbae13631,0xb9e73bf5,0x36e83219,0xbbfe39a6,0x30a63916,0x3bc3baa5,0xb55eb790,
  0x3546391f,0x396bbbd6,0xbbbf3487,0x338939b3,0x3a7eba97,0xbbfc346f,0x39da3654,0xb042bb1b,0xba54b7d2,0x38a339c5,0xb517bb21,0x27763be0,
  0xb93c3986,0xb89e38ee,0xb7e8384a,0xb6823737,0x3699b8f8,0xac38b1b6,0xb83a34e7,0xbaee39c0,0xb05b385f,0x3970b4cf,0x3bfcbb6c,0x38b2bb04,
  0xb0d7b77a,0xbbeb39af,0xb6c63b0a,0x39f4b263,0x36d23625,0x3adebba7,0xb8c1b24b,0xb9f03bf6,0xb954b4c3,0xb5813bdc,0x3becb907,0xb8b7b63c,
  0x3ace32ad,0xb52fba41,0xb5993c00,0x3aebba1d,0xbbb8af8b,0x3ac7366b,0xb941b933,0x368d3abd,0xba0d39c9,0xba893a4d,0xbaf43ac1,0xbb4f3b24,
  0x3b4aba45,0x3bfcbbdf,0x3acbbb9e,0x37feb990,0xbbed3ab3,0xb9df3ba1,0x2ba735f7,0x3a7ab7b2,0x3be8bb13,0x308db9a1,0xbb3f379b,0xb9583bd7,
  0xbb3d3b63,0x381a34ab,0x3a6fbbd8,0xb95dae5f,0x39f8bba3,0xbb833201,0x30743a39,0x3a76bb5e,0xb8353bd3,0x3b92b8fd,0xbb7fa311,0x38053929,
  0x3432bbf2,0xb8403b54,0x3a09ba15,0xbb4c3850,0xb50b35c8,0xb30f344b,0xafef3185,0xa6ad2cce,0xbbff3bb2,0xbb2c3bd2,0xb8a83a19,0xb02935df,
  0xb40eb1e8,0xbb453924,0xbb323c00,0xb3713902,0x3ad8bbf7,0xb3ebb60e,0xbbfe3a35,0xb5523aa2,0x39eb1648,0x38c7bbf6,0xbadb3232,0xb6dd3ba9,
  0xb6f43bf8,0x3bfeb865,0xb80fb7a6,0xb82a3c00,0xbbe531cf,0x394a37bd,0xa884bb6f,0xb8db3b9f,0xb010bbb3,0xb1533c00,0x3721bb9c,0xb97d3a90,
  0xbb983b76,0xbbce3bb5,0xbbf03be1,0xbbff3bfa,0x281fb463,0xb71532c6,0xba81392e,0xbbef3b71,0x3bbdbbdd,0x36afba21,0xb6ff217f,0xbbc83a3d,
  0x38252dfb,0x3bc0bb68,0x29b1b90c,0xbb8b387a,0xb9623c00,0x3a6bae2d,0x3820bbd9,0xbb3a349f,0xbb352dc9,0x294d3ab0,0x3ae5bb07,0xbad59fdb,
  0x3122bbde,0xba003b01,0x3bffb5eb,0xba5cb4db,0x3befb457,0xbbe3a51b,0x3b2a34f3,0xb9d2b894,0x39c939cd,0xba4db93c,0x3ac1389e,0xbb24b7e8,
  0x3b1e3946,0xbc00b340,0x3afeb426,0xb8553979,0x3bdd38b2,0xba21340e,0xa17fbb45,0x3a3d3b32,0x3bf53815,0xb2193966,0xbb13bb37,0x39a1b0d7,
  0x3b6536dd,0x37853b87,0xbaa9b3d3,0xb911bbe9,0x3a393581,0x3b5e3bec,0x2dc938b7,0xbab0b6f4,0x3889341a,0x3bb03a7e,0x3b593bfc,0x375939da,
  0x34f33153,0x38943721,0x3a49397d,0x3b733af1,0xb9863982,0x38eeba0d,0xb84a3a89,0x3737baf4,0xb74e3a04,0xa452bbcb,0x37c83bba,0xbabab9d6,
  0xb1e83a7a,0xb924bbbd,0x3c0036af,0xb90236ff,0x2e913ae1,0xbbdab9e7,0x377ab6e8,0x39af3be8,0x361a3b3a,0xbb10b56a,0xb86fbbc2,0x3a3130be,
  0x39073b83,0xb63c3074,0xbbf8ba76,0xb865bb35,0x3a973bbc,0x346f38ad,0xb654ac06,0xbb1bb974,0x3b9c3be3,0x3a903b2a,0x38f339d2,0x35d437f3,
  0x3b763682,0xbbb5b50b,0x3be1330f,0xbbfaafef,0x2d33bb94,0x365f3be4,0xba45ba58,0x3bdf3699,0xbbd4b371,0x3764b8d6,0x36483bfe,0xbbaeb94f,
  0x379b3beb,0xbbd7b6c6,0x2dfbb9f4,0x3b683ad8,0x39aa2a7a,0x3a2d3bfe,0xb87430a6,0xbb0dbbc3,0xbb07bbfe,0x1fdbb80f,0x3b16382a,0x3a9e3bfd,
  0xb2ad3042,0xba41b835,0xbc00bb92,0xba1dbb7f,0x3bfa3bcc,0x3bd03bfb,0x3afb3b7a,0x398b3a54,0xb5c83b4f,0x344bbb98,0xb1853bce,0x2ccebbf0,
  0x3bf93523,0xbb57313b,0x38f8b8e0,0xb1b63b4a,0xb294bbc8,0x3b183a60,0xbb5ca8e8,0x347bb9fc,0xbb0ab08d,0xb263bb3f,0x3bf73958,0xb60e3825,
  0x39a63bfd,0xb9162a16,0xbaa5bbea,0x3790b3ba,0x37a6a94d,0x3c003ae5,0x376f3ad5,0xb87fab43,0xbbd3bbee,0xb8fdbace,0x2311b52f,0x39293599,
  0x2d003328,0xb2deac6a,0xb7d2b5b1,0xb9c5b8e5,0x3bff26ad,0xbbf12c9c,0x3bcfb16c,0xbb9a343e,0xbb9e2c38,0x3990b83a,0xb4633aee,0xb2c6bbff,
  0x3a9bb109,0xad973ae8,0xb9b8bb81,0x3bf4353a,0xb90c33eb,0xb87abbfe,0x3ba53552,0x1cb63a73,0x3625b55e,0x3ba73b3d,0xb24b381a,0xbbf6ba6f,
  0xaec336bb,0xbb6ab8d1,0xba25bbe7,0x327cb546,0xb1cfb805,0x37bd3122,0x3b6f3a00,0x3b9f3bff,0x374238a3,0x319e3517,0xaf8b2776,0xb66bb432,
  0x25e43bff,0xafbdbbfb,0x32f73be2,0xb4ffbbb7,0xb4e7bbfc,0x39c03acb,0xbbb2b7fe,0x3bd2281f,0x38843be6,0xbbf8b80a,0x3999b58d,0x2ef53b90,
  0xba35bbc0,0x3aa229b1,0x34b73b8b,0xbc00b8bc,0x3b633b89,0xb4ab36d2,0xbbd8bade,0x2e5fb8c1,0xbbf5bb42,0xb602ba64,0x391f30f0,0x3bd63b8e,
  0x3bde3aeb,0x3b013be5,0x35eb394a,0xb4db2884,0xbb21ba85,0xbbe0bb96,0xbbf2bbff,0xbb54bbb8,0x3b52b5bc,0xbaf7372c,0x3a8cb845,0xba1138ea,
  0x392e3b2c,0xbb71b8a8,0x3bf23029,0xba9335a5,0xb85f3830,0xb4cfbbed,0x3b6c39df,0xbb042ba7,0xbbabba67,0x386ab576,0x391b3bfd,0xbb60b3a2,
  0x1648b95d,0x3bf63962,0x32323a6b,0xbba9b820,0x3bac396b,0x399d3bbf,0xb4c33389,0xbbdcb9f8,0x385a3a5c,0xaf273359,0xb9bcb70a,0xbbf9bb47,
  0xb933b840,0xbabdba09,0xbbb3bb4c,0xbc00bbef,0x36763b78,0xb7ddbb27,0x38993ac4,0xb937ba50,0xba193715,0x35dfba81,0x2f593bef,0xb88ebb7c,
  0xbab3bad1,0x3ba1305b,0xb5f73970,0xb7b2bbfc,0x3493b8cc,0x3aac3b85,0xba292ade,0xb631bbc5,0x3c0039f0,0x2e2d39eb,0xbbd9b8c7,0xb49fbadb,
  0x348739e3,0xb9b3b402,0xbba3bbc6,0xb201b954,0xbab6b8db,0xbbf3bbc9,0xb994bb2f,0xad65b6a4,0xba15bac7,0xb850b941,0xb457b68d,0x251bb010,
  0xb9cfbb16,0x30ac2a31,0x3b9c3bf1,0xb493ae2d,0xb76fb8b4,0x35a133e3,0x3a1d3afe,0xb902b76f,0xb3e3b5a1,0x38b4376f,0x376f3902,0xbafeba1d,
  0xaa31b0ac,0x3b1639cf,0x2e2d3493,0xbbf1bb9c,0xb956ba74,0x305f29cc,0x3b633bd2,0xb44badc9,0xb6e7b859,0x353f335e,0x39d23ab6,0xb8bcb6ff,
  0xb35eb53f,0x385936e7,0x36ff38bc,0xbab6b9d2,0xa9ccb05f,0x3a743956,0x2dc9344b,0xbbd2bb63,0xb8e3b9de,0x30122967,0x3b1e3ba1,0xb402ad65,
  0xb662b801,0x34de32da,0x39823a67,0xb874b68d,0xb2dab4de,0x38013662,0x368d3874,0xba67b982,0xa967b012,0x39de38e3,0x2d653402,0xbba1bb1e,
  0xb876b952,0x2f8c2902,0x3ace3b60,0xb371ad00,0xb5e1b758,0x347e3257,0x392e3a11,0xb82ab61a,0xb257b47e,0x375835e1,0x361a382a,0xba11b92e,
  0xa902af8c,0x39523876,0x2d003371,0xbb60bace,0xb80db8ce,0x2ef3289e,0x3a733b10,0xb2deac9c,0xb562b6b3,0x342031d5,0x38d639b3,0xb7bdb5a5,
  0xb1d5b420,0x36b33562,0x35a537bd,0xb9b3b8d6,0xa89eaef3,0x38ce380d,0x2c9c32de,0xbb10ba73,0xb750b851,0x2e5a2839,0x3a0d3ab0,0xb24bac38,
  0xb4e5b613,0x33863153,0x387a394f,0xb721b52f,0xb153b386,0x361334e5,0x352f3721,0xb94fb87a,0xa839ae5a,0x38513750,0x2c38324b,0xbab0ba0d,
  0xb68eb7b4,0x2dc227a9,0x399d3a41,0xb1b6aba7,0xb46ab577,0x32cd30d2,0x381a38e5,0xb682b4b7,0xb0d2b2cd,0x3577346a,0x34b73682,0xb8e5b81a,
  0xa7a9adc2,0x37b4368e,0x2ba731b6,0xba41b99d,0xb5d2b6d1,0x2d2a26e0,0x392439c5,0xb122aade,0xb3e3b4de,0x32163052,0x376f3874,0xb5dfb43e,
  0xb052b216,0x34de33e3,0x343e35df,0xb874b76f,0xa6e0ad2a,0x36d135d2,0x2ade3122,0xb9c5b924,0xb51cb5f6,0x2c932617,0x38a3393c,0xb08daa16,
  0xb2f4b448,0x31602fa5,0x36a437fe,0xb53ab389,0xafa5b160,0x344832f4,0x3389353a,0xb7feb6a4,0xa617ac93,0x35f6351c,0x2a16308d,0xb93cb8a3,
  0xb46ab523,0x2bf6254d,0x381a38a8,0xafefa94d,0xb209b36b,0x30ac2ea7,0x35d4370a,0xb493b294,0xaea7b0ac,0x336b3209,0x32943493,0xb70ab5d4,
  0xa54dabf6,0x3523346a,0x294d2fef,0xb8a8b81a,0xb378b456,0x2ac82484,0x3715380a,0xaec3a884,0xb120b24a,0x2ff22da9,0x34ff360e,0xb3d3b19e,
  0xada9aff2,0x324a3120,0x319e33d3,0xb60eb4ff,0xa484aac8,0x34563378,0x28842ec3,0xb80ab715,0xb223b31c,0x29992376,0x35eb36c6,0xad97a776,
  0xb039b12d,0x2e8d2cac,0x3426350b,0xb27cb0a6,0xacacae8d,0x312d3039,0x30a6327c,0xb50bb426,0xa376a999,0x331c3223,0x27762d97,0xb6c6b5eb,
  0xb0d2b194,0x286b21e4,0x34b7356a,0xac6aa5e4,0xaea7b012,0x2d2a2b5f,0x32943402,0xb122af59,0xab5fad2a,0x30122ea7,0x2f593122,0xb402b294,
  0xa1e4a86b,0x319430d2,0x25e42c6a,0xb56ab4b7,0xaf0cb012,0x267b2052,0x32f73402,0xaa7aa452,0xacdeadf5,0x2b912967,0x30d731e8,0xaf8bad65,
  0xa967ab91,0x2df52cde,0x2d652f8b,0xb1e8b0d7,0xa052a67b,0x30122f0c,0x24522a7a,0xb402b2f7,0xac79ad2a,0x24201d7f,0x30743122,0xa81fa17f,
  0xaa31ab91,0x28d026e0,0x2e2d2f8b,0xacceaade,0xa6e0a8d0,0x2b912a31,0x2ade2cce,0xaf8bae2d,0x9d7fa420,0x2d2a2c79,0x217f281f,0xb122b074,
  0xa7a9a86b,0x1f1218b6,0x2ba72c6a,0xa3119cb6,0xa54da67b,0x242021e4,0x294d2a7a,0xa81fa5e4,0xa1e4a420,0x267b254d,0x25e4281f,0xaa7aa94d,
  0x98b69f12,0x286b27a9,0x1cb62311,0xac6aaba7,0x211b21e4,0x98b69248,0xa51ba5e4,0x1cb61648,0x1f122052,0x9d7f9bdb,0xa311a452,0x217f1fdb,
  0x1bdb1d7f,0xa0529f12,0x9fdba17f,0x24522311,0x124818b6,0xa1e4a11b,0x96489cb6,0x25e4251b,0x2a632b5f,0xa1e49bdb,0xae5faf59,0x25e41fdb,
  0x286b2967,0xa6e0a4e9,0xac6aad65,0x2ade28e8,0x24e926e0,0xa967a86b,0xa8e8aade,0x2d652c6a,0x1bdb21e4,0xab5faa63,0x9fdba5e4,0x2f592e5f,
  0x2dc22ea7,0xa54d9f12,0xb1b6b294,0x294d2311,0x2bf62cde,0xaa31a86b,0xafefb0d7,0x2e2d2c6a,0x286b2a31,0xacdeabf6,0xac6aae2d,0x30d72fef,
  0x1f12254d,0xaea7adc2,0xa311a94d,0x329431b6,0x302c30d2,0xa7a9a11b,0xb41ab4b7,0x2ba7251b,0x2dc22f0c,0xac79aa63,0xb1b6b2f7,0x30742e5f,
  0x2a632c79,0xaf0cadc2,0xae5fb074,0x32f731b6,0x211b27a9,0xb0d2b02c,0xa51baba7,0x34b7341a,0x317a3257,0xa902a2ad,0xb552b61a,0x2d0026ad,
  0x2f8c309f,0xaddcac2e,0xb371b487,0x31cf3029,0x2c2e2ddc,0xb09faf8c,0xb029b1cf,0x34873371,0x22ad2902,0xb257b17a,0xa6adad00,0x361a3552,
  0x32cd33e3,0xaa31a420,0xb682b76f,0x2e2d281f,0x30ac31bb,0xaf3fad2a,0xb493b58d,0x33283122,0x2d2a2f3f,0xb1bbb0ac,0xb122b328,0x358d3493,
  0x24202a31,0xb3e3b2cd,0xa81fae2d,0x376f3682,0x341334bc,0xab5fa4e9,0xb7a6b85a,0x2f5928e8,0x319432da,0xb052ae28,0xb56ab68d,0x343e3219,
  0x2e283052,0xb2dab194,0xb219b43e,0x368d356a,0x24e92b5f,0xb4bcb413,0xa8e8af59,0x385a37a6,0x34c3358c,0xac47a5b2,0xb85fb8f3,0x304229b1,
  0x327e33fd,0xb106af26,0xb63cb785,0x34e7330f,0x2f263106,0xb3fdb27e,0xb30fb4e7,0x3785363c,0x25b22c47,0xb58cb4c3,0xa9b1b042,0x38f3385f,
  0x35773662,0xacdea67b,0xb8e5b982,0x30d72a7a,0x336b3493,0xb1bbb012,0xb70ab83a,0x358d3402,0x301231bb,0xb493b36b,0xb402b58d,0x383a370a,
  0x267b2cde,0xb662b577,0xaa7ab0d7,0x398238e5,0x36303741,0xad76a744,0xb962ba04,0x316c2b43,0x342e352a,0xb271b092,0xb7d2b8ad,0x3631347b,
  0x30923271,0xb52ab42e,0xb47bb631,0x38ad37d2,0x27442d76,0xb741b630,0xab43b16c,0x3a043962,0x36ee3815,0xae0ea807,0xb9d6ba7a,0x32012c06,
  0x34a735c4,0xb329b113,0xb84ab91b,0x36d234f3,0x31133329,0xb5c4b4a7,0xb4f3b6d2,0x391b384a,0x28072e0e,0xb815b6ee,0xac06b201,0x3a7a39d6,
  0x37b4388e,0xaea7a86b,0xba41bae1,0x32942c6a,0x35233662,0xb3e3b194,0xb8a8b982,0x376f356a,0x319433e3,0xb662b523,0xb56ab76f,0x398238a8,
  0x286b2ea7,0xb88eb7b4,0xac6ab294,0x3ae13a41,0x3841390f,0xaf3fa8d0,0xbaa2bb3a,0x33282cce,0x35a13705,0xb44fb216,0xb902b9e3,0x380535df,
  0x3216344f,0xb705b5a1,0xb5dfb805,0x39e33902,0x28d02f3f,0xb90fb841,0xacceb328,0x3b3a3aa2,0x38ac3997,0xafd8a935,0xbaf7bb83,0x33ba2d33,
  0x362137ac,0xb4aeb298,0xb958ba3d,0x38503654,0x329834ae,0xb7acb621,0xb654b850,0x3a3d3958,0x29352fd8,0xb997b8ac,0xad33b3ba,0x3b833af7,
  0x391c3a28,0xb039a999,0xbb42bbbc,0x34262d97,0x36a4382d,0xb50eb31c,0xb9aaba90,0x389936c6,0x331c350e,0xb82db6a4,0xb6c6b899,0x3a9039aa,
  0x29993039,0xba28b91c,0xad97b426,0x3bbc3b42,0x39923ac3,0xb085a9fe,0xbb81bbe3,0x346f2dfb,0x372a3886,0xb570b3a0,0xb9f8badb,0x38e03737,
  0x33a03570,0xb886b72a,0xb737b8e0,0x3adb39f8,0x29fe3085,0xbac3b992,0xadfbb46f,0x3be33b81,
};

#define PROF(slot) do {} while (0)
#define PROF_DUMP() do {} while (0)
#define PROFA(slot, dep) do {} while (0)
#define PROF3(slot) do {} while (0)
#define PROF2(slot) do {} while (0)

__device__ __forceinline__ uint32_t smem_u32(const void* p) { return (uint32_t)__cvta_generic_to_shared(p); }

__device__ __forceinline__ void mbar_init(uint32_t a, uint32_t c) {
  asm volatile("mbarrier.init.shared::cta.b64 [%0], %1;\n" ::"r"(a), "r"(c) : "memory");
}
__device__ __forceinline__ void mbar_expect_tx(uint32_t a, uint32_t bytes) {
  asm volatile("mbarrier.arrive.expect_tx.shared::cta.b64 _, [%0], %1;\n" ::"r"(a), "r"(bytes) : "memory");
}
__device__ __forceinline__ void mbar_arrive_cluster(uint32_t cluster_addr) {
  asm volatile("mbarrier.arrive.shared::cluster.b64 _, [%0];\n" ::"r"(cluster_addr) : "memory");
}
__device__ __forceinline__ void mbar_arrive_cluster_n(uint32_t cluster_addr, uint32_t n) {
  asm volatile("mbarrier.arrive.shared::cluster.b64 _, [%0], %1;\n" ::"r"(cluster_addr), "r"(n) : "memory");
}
__device__ __forceinline__ bool mbar_try(uint32_t a, uint32_t parity) {
  uint32_t ok;
  asm volatile("{\n.reg .pred p;\nmbarrier.try_wait.parity.shared::cta.b64 p, [%1], %2;\nselp.u32 %0, 1, 0, p;\n}\n"
               : "=r"(ok) : "r"(a), "r"(parity) : "memory");
  return ok;
}
__device__ __forceinline__ bool mbar_test(uint32_t a, uint32_t parity) {
  uint32_t ok;
  asm volatile("{\n.reg .pred p;\nmbarrier.test_wait.parity.shared::cta.b64 p, [%1], %2;\nselp.u32 %0, 1, 0, p;\n}\n"
               : "=r"(ok) : "r"(a), "r"(parity) : "memory");
  return ok;
}
__device__ __forceinline__ void mbar_wait(uint32_t a, uint32_t parity) {
  if (mbar_try(a, parity)) return;
#pragma unroll 1
  for (int n = 0; n < SPIN_LIMIT; n++)
    if (mbar_try(a, parity)) break;
}
__device__ __forceinline__ bool elect_one() {
  uint32_t p;
  asm volatile("{\n.reg .pred P;\nelect.sync _|P, 0xffffffff;\nselp.u32 %0, 1, 0, P;\n}\n" : "=r"(p));
  return p;
}
__device__ __forceinline__ uint32_t mapa(uint32_t a, uint32_t rank) {
  uint32_t r;
  asm volatile("mapa.shared::cluster.u32 %0, %1, %2;\n" : "=r"(r) : "r"(a), "r"(rank));
  return r;
}
__device__ __forceinline__ void nb_sync(int id, int n) { asm volatile("bar.sync %0, %1;\n" ::"r"(id), "r"(n) : "memory"); }
__device__ __forceinline__ void nb_arrive(int id, int n) { asm volatile("bar.arrive %0, %1;\n" ::"r"(id), "r"(n) : "memory"); }
__device__ __forceinline__ void cluster_sync_all() {
  asm volatile("barrier.cluster.arrive.relaxed.aligned;\nbarrier.cluster.wait.aligned;\n" ::: "memory");
}
__device__ __forceinline__ void fence_async_smem() { asm volatile("fence.proxy.async.shared::cta;\n" ::: "memory"); }
__device__ __forceinline__ void fence_async_all() { asm volatile("fence.proxy.async.global;\n" ::: "memory"); }

__device__ __forceinline__ void tma_load_3d(uint32_t dst, const CUtensorMap* tm, uint32_t bar, int c0, int c1, int c2) {
  asm volatile(
      "cp.async.bulk.tensor.3d.shared::cluster.global.mbarrier::complete_tx::bytes [%0], [%1, {%3, %4, %5}], [%2];\n"
      ::"r"(dst), "l"(tm), "r"(bar), "r"(c0), "r"(c1), "r"(c2) : "memory");
}
__device__ __forceinline__ void tma_load_4d(uint32_t dst, const CUtensorMap* tm, uint32_t bar, int c0, int c1, int c2, int c3) {
  asm volatile(
      "cp.async.bulk.tensor.4d.shared::cluster.global.mbarrier::complete_tx::bytes [%0], [%1, {%3, %4, %5, %6}], [%2];\n"
      ::"r"(dst), "l"(tm), "r"(bar), "r"(c0), "r"(c1), "r"(c2), "r"(c3) : "memory");
}
__device__ __forceinline__ void tma_load_3d_mc(uint32_t dst, const CUtensorMap* tm, uint32_t bar, int c0, int c1, int c2) {
  asm volatile(
      "cp.async.bulk.tensor.3d.shared::cluster.global.mbarrier::complete_tx::bytes.multicast::cluster [%0], [%1, {%3, %4, %5}], [%2], %6;\n"
      ::"r"(dst), "l"(tm), "r"(bar), "r"(c0), "r"(c1), "r"(c2), "h"((uint16_t)3) : "memory");
}
__device__ __forceinline__ void bulk_load(uint32_t dst, const void* src, uint32_t bytes, uint32_t bar) {
  asm volatile("cp.async.bulk.shared::cluster.global.mbarrier::complete_tx::bytes [%0], [%1], %2, [%3];\n"
               ::"r"(dst), "l"(src), "r"(bytes), "r"(bar) : "memory");
}
__device__ __forceinline__ void tma_store_3d(const CUtensorMap* tm, uint32_t src, int c0, int c1, int c2) {
  asm volatile("cp.async.bulk.tensor.3d.global.shared::cta.bulk_group [%0, {%2, %3, %4}], [%1];\n"
               ::"l"(tm), "r"(src), "r"(c0), "r"(c1), "r"(c2) : "memory");
}
__device__ __forceinline__ void bulk_commit() { asm volatile("cp.async.bulk.commit_group;\n" ::: "memory"); }
__device__ __forceinline__ void bulk_wait0() { asm volatile("cp.async.bulk.wait_group 0;\n" ::: "memory"); }
__device__ __forceinline__ void prefetch_tmap(const CUtensorMap* tm) {
  asm volatile("prefetch.tensormap [%0];\n" ::"l"(tm) : "memory");
}

__device__ __forceinline__ void wg_fence() { asm volatile("wgmma.fence.sync.aligned;\n" ::: "memory"); }
__device__ __forceinline__ void wg_commit() { asm volatile("wgmma.commit_group.sync.aligned;\n" ::: "memory"); }
template <int N> __device__ __forceinline__ void wg_wait() {
  asm volatile("wgmma.wait_group.sync.aligned %0;\n" ::"n"(N) : "memory");
}
__device__ __forceinline__ uint64_t mkdesc(uint32_t addr, uint32_t lbo, uint32_t sbo, uint32_t swz) {
  return (uint64_t)((addr & 0x3FFFF) >> 4) | ((uint64_t)(lbo >> 4) << 16) | ((uint64_t)(sbo >> 4) << 32) |
         ((uint64_t)swz << 62);
}

#define R4(d, o) "+f"(d[o + 0]), "+f"(d[o + 1]), "+f"(d[o + 2]), "+f"(d[o + 3])
#define R8(d, o) R4(d, o), R4(d, o + 4)
#define R16(d, o) R8(d, o), R8(d, o + 8)
#define R32(d, o) R16(d, o), R16(d, o + 16)
#define R64(d, o) R32(d, o), R32(d, o + 32)

__device__ __forceinline__ void wgmma_n192(float (&d)[96], uint64_t da, uint64_t db, uint32_t acc) {
  asm volatile(
      "{\n.reg .pred p;\nsetp.ne.u32 p, %98, 0;\n"
      "wgmma.mma_async.sync.aligned.m64n192k16.f32.bf16.bf16 "
      "{%0,%1,%2,%3,%4,%5,%6,%7,%8,%9,%10,%11,%12,%13,%14,%15,%16,%17,%18,%19,%20,%21,%22,%23,%24,%25,%26,%27,%28,%29,%30,%31,"
      "%32,%33,%34,%35,%36,%37,%38,%39,%40,%41,%42,%43,%44,%45,%46,%47,%48,%49,%50,%51,%52,%53,%54,%55,%56,%57,%58,%59,%60,%61,%62,%63,"
      "%64,%65,%66,%67,%68,%69,%70,%71,%72,%73,%74,%75,%76,%77,%78,%79,%80,%81,%82,%83,%84,%85,%86,%87,%88,%89,%90,%91,%92,%93,%94,%95}, "
      "%96, %97, p, 1, 1, 0, 1;\n}\n"
      : R64(d, 0), R32(d, 64)
      : "l"(da), "l"(db), "r"(acc));
}
__device__ __forceinline__ void wgmma_n128(float (&d)[64], uint64_t da, uint64_t db, uint32_t acc) {
  asm volatile(
      "{\n.reg .pred p;\nsetp.ne.u32 p, %66, 0;\n"
      "wgmma.mma_async.sync.aligned.m64n128k16.f32.bf16.bf16 "
      "{%0,%1,%2,%3,%4,%5,%6,%7,%8,%9,%10,%11,%12,%13,%14,%15,%16,%17,%18,%19,%20,%21,%22,%23,%24,%25,%26,%27,%28,%29,%30,%31,"
      "%32,%33,%34,%35,%36,%37,%38,%39,%40,%41,%42,%43,%44,%45,%46,%47,%48,%49,%50,%51,%52,%53,%54,%55,%56,%57,%58,%59,%60,%61,%62,%63}, "
      "%64, %65, p, 1, 1, 0, 1;\n}\n"
      : R64(d, 0)
      : "l"(da), "l"(db), "r"(acc));
}
#define WG128(C, ACC)                                                                                                      \
  asm volatile(                                                                                                            \
      "{\n.reg .b64 a, b;\nmov.b64 a, {%64, %66};\nmov.b64 b, {%65, %66};\n"                                               \
      "wgmma.mma_async.sync.aligned.m64n128k16.f32.bf16.bf16 "                                                             \
      "{%0,%1,%2,%3,%4,%5,%6,%7,%8,%9,%10,%11,%12,%13,%14,%15,%16,%17,%18,%19,%20,%21,%22,%23,%24,%25,%26,%27,%28,%29,%30,%31," \
      "%32,%33,%34,%35,%36,%37,%38,%39,%40,%41,%42,%43,%44,%45,%46,%47,%48,%49,%50,%51,%52,%53,%54,%55,%56,%57,%58,%59,%60,%61," \
      "%62,%63}, a, b, " ACC ", 1, 1, 0, 1;\n}\n"                                                                          \
      : Z16(C, d, 0), Z16(C, d, 16), Z16(C, d, 32), Z16(C, d, 48)                                                          \
      : "r"(da), "r"(db), "r"(0x40000040))
#define Z4(C, d, o) C(d[o + 0]), C(d[o + 1]), C(d[o + 2]), C(d[o + 3])
#define Z16(C, d, o) Z4(C, d, o), Z4(C, d, o + 4), Z4(C, d, o + 8), Z4(C, d, o + 12)
__device__ __forceinline__ void wgmma_n128z(float (&d)[64], uint32_t da, uint32_t db) { WG128("=f", "0"); }
__device__ __forceinline__ void wgmma_n128a(float (&d)[64], uint32_t da, uint32_t db) { WG128("+f", "1"); }
template <int N> __device__ __forceinline__ void fence_regs(float (&d)[N]) {
#pragma unroll
  for (int i = 0; i < N; i++) asm volatile("" : "+f"(d[i])::"memory");
}

__device__ __forceinline__ void mma16816(float (&d)[4], uint32_t a0, uint32_t a1, uint32_t a2, uint32_t a3, uint32_t b0,
                                         uint32_t b1) {
  asm("mma.sync.aligned.m16n8k16.row.col.f32.bf16.bf16.f32 {%0,%1,%2,%3}, {%4,%5,%6,%7}, {%8,%9}, {%0,%1,%2,%3};\n"
      : "+f"(d[0]), "+f"(d[1]), "+f"(d[2]), "+f"(d[3])
      : "r"(a0), "r"(a1), "r"(a2), "r"(a3), "r"(b0), "r"(b1));
}
__device__ __forceinline__ void mma16816_z(float (&d)[4], uint32_t a0, uint32_t a1, uint32_t a2, uint32_t a3, uint32_t b0,
                                           uint32_t b1) {
  asm("mma.sync.aligned.m16n8k16.row.col.f32.bf16.bf16.f32 {%0,%1,%2,%3}, {%4,%5,%6,%7}, {%8,%9}, {%10,%10,%10,%10};\n"
      : "=f"(d[0]), "=f"(d[1]), "=f"(d[2]), "=f"(d[3])
      : "r"(a0), "r"(a1), "r"(a2), "r"(a3), "r"(b0), "r"(b1), "f"(0.f));
}
__device__ __forceinline__ void ldsm4t(uint32_t (&r)[4], uint32_t a) {
  asm volatile("ldmatrix.sync.aligned.m8n8.x4.trans.shared.b16 {%0,%1,%2,%3}, [%4];\n"
               : "=r"(r[0]), "=r"(r[1]), "=r"(r[2]), "=r"(r[3]) : "r"(a) : "memory");
}
__device__ __forceinline__ void ldsm2t(uint32_t& r0, uint32_t& r1, uint32_t a) {
  asm volatile("ldmatrix.sync.aligned.m8n8.x2.trans.shared.b16 {%0,%1}, [%2];\n" : "=r"(r0), "=r"(r1) : "r"(a) : "memory");
}
__device__ __forceinline__ void st_async128(uint32_t a, uint32_t bar, uint32_t x, uint32_t y, uint32_t z, uint32_t w) {
  asm volatile("st.async.weak.shared::cluster.mbarrier::complete_tx::bytes.v4.b32 [%0], {%2,%3,%4,%5}, [%1];\n"
               ::"r"(a), "r"(bar), "r"(x), "r"(y), "r"(z), "r"(w) : "memory");
}
__device__ __forceinline__ void mbar_arrive(uint32_t a) {
  asm volatile("mbarrier.arrive.shared::cta.b64 _, [%0];\n" ::"r"(a) : "memory");
}
__device__ __forceinline__ void stsm4(uint32_t a, uint32_t r0, uint32_t r1, uint32_t r2, uint32_t r3) {
  asm volatile("stmatrix.sync.aligned.m8n8.x4.shared.b16 [%0], {%1,%2,%3,%4};\n"
               ::"r"(a), "r"(r0), "r"(r1), "r"(r2), "r"(r3) : "memory");
}
__device__ __forceinline__ void stsm4t(uint32_t a, uint32_t r0, uint32_t r1, uint32_t r2, uint32_t r3) {
  asm volatile("stmatrix.sync.aligned.m8n8.x4.trans.shared.b16 [%0], {%1,%2,%3,%4};\n"
               ::"r"(a), "r"(r0), "r"(r1), "r"(r2), "r"(r3) : "memory");
}
__device__ __forceinline__ uint2 lds64(uint32_t a) {
  uint2 v;
  asm volatile("ld.shared.v2.u32 {%0,%1}, [%2];\n" : "=r"(v.x), "=r"(v.y) : "r"(a));
  return v;
}
__device__ __forceinline__ uint4 lds128(uint32_t a) {
  uint4 v;
  asm volatile("ld.shared.v4.u32 {%0,%1,%2,%3}, [%4];\n" : "=r"(v.x), "=r"(v.y), "=r"(v.z), "=r"(v.w) : "r"(a) : "memory");
  return v;
}
__device__ __forceinline__ void sts128(uint32_t a, uint32_t x, uint32_t y, uint32_t z, uint32_t w) {
  asm volatile("st.shared.v4.u32 [%0], {%1,%2,%3,%4};\n" ::"r"(a), "r"(x), "r"(y), "r"(z), "r"(w) : "memory");
}
__device__ __forceinline__ void sts64(uint32_t a, uint32_t x, uint32_t y) {
  asm volatile("st.shared.v2.u32 [%0], {%1,%2};\n" ::"r"(a), "r"(x), "r"(y) : "memory");
}
__device__ __forceinline__ uint32_t pack_bf16(float lo, float hi) {
  uint32_t r;
  asm("cvt.rn.bf16x2.f32 %0, %1, %2;\n" : "=r"(r) : "f"(hi), "f"(lo));
  return r;
}
__device__ __forceinline__ uint32_t bmul2(uint32_t a, uint32_t b) {
  uint32_t r;
  asm("mul.rn.bf16x2 %0, %1, %2;\n" : "=r"(r) : "r"(a), "r"(b));
  return r;
}
__device__ __forceinline__ uint32_t bmax2(uint32_t a, uint32_t b) {
  uint32_t r;
  asm("max.bf16x2 %0, %1, %2;\n" : "=r"(r) : "r"(a), "r"(b));
  return r;
}
__device__ __forceinline__ uint32_t bfma2(uint32_t a, uint32_t b, uint32_t c) {
  uint32_t r;
  asm("fma.rn.bf16x2 %0, %1, %2, %3;\n" : "=r"(r) : "r"(a), "r"(b), "r"(c));
  return r;
}
__device__ __forceinline__ uint32_t badd2(uint32_t a, uint32_t b) {
  uint32_t r;
  asm("add.rn.bf16x2 %0, %1, %2;\n" : "=r"(r) : "r"(a), "r"(b));
  return r;
}
__device__ __forceinline__ void prefetch_l2(const void* p) { asm volatile("prefetch.global.L2 [%0];\n" ::"l"(p)); }
__device__ __forceinline__ void cp_async16n(uint32_t dst, const void* src) {
  asm volatile("cp.async.cg.shared.global [%0], [%1], 16;\n" ::"r"(dst), "l"(src) : "memory");
}
__device__ __forceinline__ void cp_async16(uint32_t dst, const void* src, uint32_t srcbytes) {
  asm volatile("cp.async.cg.shared.global.L2::256B [%0], [%1], 16, %2;\n" ::"r"(dst), "l"(src), "r"(srcbytes) : "memory");
}
__device__ __forceinline__ uint32_t ld_acquire(const uint32_t* p) {
  uint32_t v;
  asm volatile("ld.acquire.gpu.global.u32 %0, [%1];\n" : "=r"(v) : "l"(p) : "memory");
  return v;
}
__device__ __forceinline__ uint32_t ld_relaxed(const uint32_t* p) {
  uint32_t v;
  asm volatile("ld.relaxed.gpu.global.u32 %0, [%1];\n" : "=r"(v) : "l"(p) : "memory");
  return v;
}
__device__ __forceinline__ void st_release(uint32_t* p, uint32_t v) {
  asm volatile("st.release.gpu.global.u32 [%0], %1;\n" ::"l"(p), "r"(v) : "memory");
}
__device__ __forceinline__ void wait_flag(const uint32_t* p, uint32_t want) {
  int n = 0;
  while (ld_acquire(p) != want && ++n < SPIN_LIMIT) {}
}

struct Params {
  const __nv_bfloat16* x;
  const __nv_bfloat16* w;
  const __nv_bfloat16* q;
  const __nv_bfloat16* k;
  const __nv_bfloat16* v;
  const __nv_bfloat16* shift_k;
  const __nv_bfloat16* ssm_k;
  const __nv_bfloat16* ssm_D;
  const __nv_bfloat16* wo;
  __nv_bfloat16* out;
  uint32_t zero;
};

__device__ __forceinline__ uint32_t lds32(uint32_t a) {
  uint32_t v;
  asm volatile("ld.shared.u32 %0, [%1];\n" : "=r"(v) : "r"(a));
  return v;
}
__device__ __forceinline__ float bf_lo(uint32_t v) {
  uint32_t r;
  asm("prmt.b32 %0, %1, 0, 0x1044;\n" : "=r"(r) : "r"(v));
  return __uint_as_float(r);
}
__device__ __forceinline__ float bf_hi(uint32_t v) { return __uint_as_float(v & 0xffff0000u); }
__device__ __forceinline__ float ex2(float x) {
  float r;
  asm("ex2.approx.ftz.f32 %0, %1;\n" : "=f"(r) : "f"(x));
  return r;
}
__device__ __forceinline__ float rcp(float x) {
  float r;
  asm("rcp.approx.ftz.f32 %0, %1;\n" : "=f"(r) : "f"(x));
  return r;
}

#define Q4(c, d, o) c(d[o + 0]), c(d[o + 1]), c(d[o + 2]), c(d[o + 3])
#define Q8(c, d, o) Q4(c, d, o), Q4(c, d, o + 4)
#define Q16(c, d, o) Q8(c, d, o), Q8(c, d, o + 8)
#define Q32(c, d) Q16(c, d, 0), Q16(c, d, 16)
#define L8 "{%0,%1,%2,%3,%4,%5,%6,%7}"
#define L16 "{%0,%1,%2,%3,%4,%5,%6,%7,%8,%9,%10,%11,%12,%13,%14,%15}"
#define L32 "{%0,%1,%2,%3,%4,%5,%6,%7,%8,%9,%10,%11,%12,%13,%14,%15,%16,%17,%18,%19,%20,%21,%22,%23,%24,%25,%26,%27,%28,%29,%30,%31}"
__device__ __forceinline__ void fft_rows(uint32_t (&d)[32], const uint32_t (&a)[2][4], uint64_t db) {
  asm volatile("wgmma.mma_async.sync.aligned.m64n128k16.f16.f16.f16 " L32 ", {%32,%33,%34,%35}, %36, 0, 1, 1, 1;\n"
               : Q32("=r", d) : "r"(a[0][0]), "r"(a[0][1]), "r"(a[0][2]), "r"(a[0][3]), "l"(db));
  asm volatile("wgmma.mma_async.sync.aligned.m64n128k16.f16.f16.f16 " L32 ", {%32,%33,%34,%35}, %36, 1, 1, 1, 1;\n"
               : Q32("+r", d) : "r"(a[1][0]), "r"(a[1][1]), "r"(a[1][2]), "r"(a[1][3]), "l"(db + 64));
}
template <int INV> __device__ __forceinline__ void fft_cols(uint32_t (&d)[8], const uint32_t (&a)[2][4], uint64_t db) {
  asm volatile("wgmma.mma_async.sync.aligned.m64n32k16.f16.f16.f16 " L8 ", {%8,%9,%10,%11}, %12, 0, 1, 1, %13;\n"
               : Q8("=r", d, 0) : "r"(a[0][0]), "r"(a[0][1]), "r"(a[0][2]), "r"(a[0][3]), "l"(db), "n"(INV));
  asm volatile("wgmma.mma_async.sync.aligned.m64n32k16.f16.f16.f16 " L8 ", {%8,%9,%10,%11}, %12, 1, 1, 1, %13;\n"
               : Q8("+r", d, 0) : "r"(a[1][0]), "r"(a[1][1]), "r"(a[1][2]), "r"(a[1][3]), "l"(db + (INV ? 16 : 64)), "n"(INV));
}
__device__ __forceinline__ void fft_back(float (&d)[16], uint64_t da, uint64_t db) {
  asm volatile("wgmma.mma_async.sync.aligned.m64n32k16.f32.f16.f16 " L16 ", %16, %17, 0, 1, 1, 1, 1;\n"
               : Q16("=f", d, 0) : "l"(da), "l"(db));
#pragma unroll
  for (int i = 1; i < 4; i++)
    asm volatile("wgmma.mma_async.sync.aligned.m64n32k16.f32.f16.f16 " L16 ", %16, %17, 1, 1, 1, 1, 1;\n"
                 : Q16("+f", d, 0) : "l"(da + 32 * i), "l"(db + 64 * i));
}
__device__ __forceinline__ uint32_t hmul2(uint32_t a, uint32_t b) {
  uint32_t r;
  asm("mul.rn.f16x2 %0, %1, %2;\n" : "=r"(r) : "r"(a), "r"(b));
  return r;
}
__device__ __forceinline__ uint32_t hadd2(uint32_t a, uint32_t b) {
  uint32_t r;
  asm("add.rn.f16x2 %0, %1, %2;\n" : "=r"(r) : "r"(a), "r"(b));
  return r;
}
__device__ __forceinline__ uint32_t hneg2(uint32_t a) {
  uint32_t r;
  asm("neg.f16x2 %0, %1;\n" : "=r"(r) : "r"(a));
  return r;
}
__device__ __forceinline__ uint32_t hfma2(uint32_t a, uint32_t b, uint32_t c) {
  uint32_t r;
  asm("fma.rn.f16x2 %0, %1, %2, %3;\n" : "=r"(r) : "r"(a), "r"(b), "r"(c));
  return r;
}
__device__ __forceinline__ uint32_t pack_f16(float lo, float hi) {
  uint32_t r;
  asm("cvt.rn.f16x2.f32 %0, %1, %2;\n" : "=r"(r) : "f"(hi), "f"(lo));
  return r;
}
__device__ __forceinline__ uint32_t bmaxabs2(uint32_t a, uint32_t b) {
  uint32_t r;
  asm("max.xorsign.abs.bf16x2 %0, %1, %2;\n" : "=r"(r) : "r"(a), "r"(b));
  return r;
}
struct C2 { uint32_t r, i; };
__device__ __forceinline__ C2 cmul(C2 a, C2 b) {
  return C2{hfma2(a.r, b.r, hneg2(hmul2(a.i, b.i))), hfma2(a.r, b.i, hmul2(a.i, b.r))};
}
__device__ __forceinline__ C2 cfma(C2 a, C2 b, C2 c) {
  return C2{hfma2(a.r, b.r, hfma2(hneg2(a.i), b.i, c.r)), hfma2(a.r, b.i, hfma2(a.i, b.r, c.i))};
}
__device__ __forceinline__ C2 crot(C2 z, C2 t) {
  const uint32_t r = hfma2(t.r, z.i, z.r), i = hfma2(t.i, r, z.i);
  return C2{hfma2(t.r, i, r), i};
}
__device__ __forceinline__ C2 cget(const uint32_t (&e)[8], int j, int b) { return C2{e[4 * j + b], e[4 * j + 2 + b]}; }
template <int N> __device__ __forceinline__ void fence_regs(uint32_t (&d)[N]) {
#pragma unroll
  for (int i = 0; i < N; i++) asm volatile("" : "+r"(d[i])::"memory");
}
__device__ __forceinline__ void ldsm4(uint32_t (&r)[4], uint32_t a) {
  asm volatile("ldmatrix.sync.aligned.m8n8.x4.shared.b16 {%0,%1,%2,%3}, [%4];\n"
               : "=r"(r[0]), "=r"(r[1]), "=r"(r[2]), "=r"(r[3]) : "r"(a) : "memory");
}

__device__ __forceinline__ uint32_t movm(uint32_t a) {
  uint32_t r;
  asm volatile("movmatrix.sync.aligned.m8n8.trans.b16 %0, %1;\n" : "=r"(r) : "r"(a));
  return r;
}
template <int C0, int H, bool T> __device__ __forceinline__ void attn_pack(const float (&acc)[96], uint32_t (&d)[8]) {
#pragma unroll
  for (int c = 0; c < 8; c++) {
    asm volatile("cvt.rn.bf16x2.f32 %0, %1, %2;\n" : "=r"(d[c]) : "f"(acc[4 * (C0 + c) + 2 * H + 1]), "f"(acc[4 * (C0 + c) + 2 * H]));
    if (T) d[c] = movm(d[c]);
  }
}
__device__ __forceinline__ void attn_qk(float (&s)[4], const uint32_t (&qlo)[8], const uint32_t (&qhi)[8],
                                        const uint32_t (&k)[8], int c) {
  mma16816_z(s, qlo[c], qhi[c], qlo[c + 1], qhi[c + 1], k[c], k[c + 1]);
  mma16816(s, qlo[c + 2], qhi[c + 2], qlo[c + 3], qhi[c + 3], k[c + 2], k[c + 3]);
}
template <int N> __device__ __forceinline__ void quad_softmax(float (&x)[N][2], uint32_t (&pp)[N]) {
  const float c2 = 1.4426950408889634f;
  uint32_t q[N], mx[N / 2];
#pragma unroll
  for (int n = 0; n < N; n++) {
    const uint32_t r = pack_bf16(x[n][0], x[n][1]);
    q[n] = bfma2(r, 0x3e353e35u, bmul2(r, 0x379e379eu));
    x[n][0] = bf_lo(q[n]);
    x[n][1] = bf_hi(q[n]);
  }
#pragma unroll
  for (int n = 0; n < N / 2; n++)
    mx[n] = bmax2(__byte_perm(q[2 * n], q[2 * n + 1], 0x5410), __byte_perm(q[2 * n], q[2 * n + 1], 0x7632));
#pragma unroll
  for (int o = 1; o <= 2; o++) {
#pragma unroll
    for (int n = 0; n < N / 2; n++) mx[n] = bmax2(mx[n], __shfl_xor_sync(0xffffffffu, mx[n], o));
  }
  float m[N], t[N];
#pragma unroll
  for (int n = 0; n < N / 2; n++) {
    m[2 * n] = bf_lo(mx[n]);
    m[2 * n + 1] = bf_hi(mx[n]);
  }
#pragma unroll
  for (int n = 0; n < N; n++) {
    const float nm = -m[n] * c2;
    x[n][0] = ex2(fmaf(x[n][0], c2, nm));
    x[n][1] = ex2(fmaf(x[n][1], c2, nm));
  }
#pragma unroll
  for (int n = 0; n < N; n += 2) {
    float u0, u1;
    asm("mma.sync.aligned.m16n8k8.row.col.f32.tf32.tf32.f32 {%0,%1,%2,%3}, {%4,%5,%6,%7}, {%8,%8}, {%9,%9,%9,%9};\n"
        : "=f"(t[n]), "=f"(u0), "=f"(t[n + 1]), "=f"(u1)
        : "r"(__float_as_uint(x[n][0])), "r"(__float_as_uint(x[n + 1][0])), "r"(__float_as_uint(x[n][1])),
          "r"(__float_as_uint(x[n + 1][1])), "r"(0x3f800000u), "f"(0.f));
  }
#pragma unroll
  for (int n = 0; n < N; n++) {
    const float inv = rcp(t[n]);
    pp[n] = pack_bf16(x[n][0] * inv, x[n][1] * inv);
  }
}
__device__ __forceinline__ void attn_pv(uint32_t dst, const uint32_t (&vp)[8], const uint32_t (&vo)[8], int c, uint32_t pp,
                                        uint32_t maskLE) {
  const uint32_t b0 = pp & ~maskLE, b1 = pp & maskLE;
  float oa[4], ob[4];
  mma16816_z(oa, vp[c], vp[c + 1], vo[c], vo[c + 1], b0, b1);
  mma16816_z(ob, vp[c + 2], vp[c + 3], vo[c + 2], vo[c + 3], b0, b1);
  stsm4t(dst, pack_bf16(oa[0], oa[1]), pack_bf16(oa[2], oa[3]), pack_bf16(ob[0], ob[1]), pack_bf16(ob[2], ob[3]));
}

template <int MODE>
__global__ void __cluster_dims__(2, 1, 1) __launch_bounds__(NTHREADS, 1)
fused_kernel(const Params p, const __grid_constant__ CUtensorMap tmX, const __grid_constant__ CUtensorMap tmW,
             const __grid_constant__ CUtensorMap tmWo, const __grid_constant__ CUtensorMap tmWp,
             const __grid_constant__ CUtensorMap tmQ,
             const __grid_constant__ CUtensorMap tmOb,
             const __grid_constant__ CUtensorMap tmXh, const __grid_constant__ CUtensorMap tmWh) {
  extern __shared__ __align__(1024) uint8_t smem[];
  if (threadIdx.x < 32) {
    const uint32_t i = (blockIdx.x & 127) * 16 + (threadIdx.x & 15);
    prefetch_l2(threadIdx.x & 16 ? (const char*)p.w + i * 128 : (const char*)p.x + i * 2048);
  }
  const uint32_t sb = smem_u32(smem);
  const uint32_t bars = sb + OFF_BAR;
  const int tid = threadIdx.x, lane = tid & 31, warp = __shfl_sync(0xffffffffu, tid >> 5, 0);
  const int rank = blockIdx.x & 1;
  const bool halo_cta = blockIdx.x < 4;
  if (halo_cta && MODE != 0) return;
  int grp, mem;
  {
    const int t = (blockIdx.x >> 1) - 4, u = t - 32;
    const int q7 = (u * 37) >> 8;
    const bool lo = (unsigned)t < 32u, mid = (unsigned)u < 28u;
    grp = lo ? (t & 7) : (mid ? 1 + u - 7 * q7 : 0);
    mem = lo ? (t >> 3) : (mid ? 4 + q7 : (t < 0 ? t + 6 : t - 54));
  }
  const int rg = (grp >> 2) * 4 + (mem >> 1), hp = (grp & 3) * 4 + (mem & 1) * 2 + rank;
  const int rb2 = (grp >> 2) * 8 + mem, cb2 = (grp & 3) * 2 + rank;
  const int chb = grp * 16 + mem * 2 + rank;
  const int cta = rg * 16 + hp;
  const int hsel = rb2 & 1;
  const int par = rg >> 2, gidx = rg & 3;

  if (tid < 256 && !halo_cta && MODE != 2) {
    const int r = tid >> 3, c = tid & 7;
    const uint32_t so = r * 128 + ((c ^ (r & 7)) << 4);
    const __nv_bfloat16* wg0 = p.w + (size_t)r * (3 * DM) + hp * 64 + c * 8;
    const __nv_bfloat16* xg0 = p.x + (size_t)(2 * (gidx * 256 + r) + par) * DM + c * 8;
#pragma unroll
    for (int j = 0; j < 3; j++) cp_async16n(sb + OFF_1B + j * 4096 + so, wg0 + j * DM);
#pragma unroll
    for (int i = 0; i < 8; i++) cp_async16n(sb + i * 4096 + so, xg0 + (size_t)i * 64 * DM);
    asm volatile("cp.async.commit_group;\n" ::: "memory");
  }
  auto halo_issue = [&](int kb, int s) {
    const uint32_t fb = bars + 8 * (BAR_FULLB + s), st = sb + s * STGH;
    mbar_expect_tx(fb, STGH - 2048);
    tma_load_3d(st + 8192, &tmWh, fb, 0, kb * 64, 16 + blockIdx.x * 4);
    tma_load_3d(st + 8192 + 32768, &tmWh, fb, 0, kb * 64, 32 + blockIdx.x * 4);
    tma_load_4d(st, &tmXh, fb, kb * 64, 248, 0, 0);
  };
  if (tid == 256) {
    prefetch_tmap(halo_cta ? &tmXh : &tmX);
#pragma unroll
    for (int i = 0; i < NS1B; i++) mbar_init(bars + 8 * (BAR_FULLB + i), 1);
#pragma unroll
    for (int i = 0; i < NS1A; i++) mbar_init(bars + 8 * (BAR_FULLA + i), 1);
    asm volatile("fence.mbarrier_init.release.cluster;\n" ::: "memory");
    if (!halo_cta && MODE != 2) {
      mbar_expect_tx(bars + 8 * (BAR_FULLB + 1), STG1B);
      tma_load_3d(sb + OFF_1B + 1 * STG1B, &tmW, bars + 8 * (BAR_FULLB + 1), hp * 64, 32, 0);
      mbar_expect_tx(bars + 8 * (BAR_FULLB + 2), STG1B);
      tma_load_3d(sb + OFF_1B + 2 * STG1B, &tmW, bars + 8 * (BAR_FULLB + 2), hp * 64, 64, 0);
    } else if (halo_cta) {
      halo_issue(0, 0);
    }
  } else if (tid == 288) {
#pragma unroll
    for (int i = 0; i < NS1A; i++) mbar_init(bars + 8 * (BAR_EMPTYA + i), 4);
#pragma unroll
    for (int i = 0; i < NS1B; i++) mbar_init(bars + 8 * (BAR_EMPTYB + i), 2);
    mbar_init(bars + 8 * BAR_X, 4);
    mbar_init(bars + 8 * BAR_TAB, 16);
    mbar_init(bars + 8 * BAR_U, 1);
    mbar_init(bars + 8 * BAR_H, 1);
    mbar_init(bars + 8 * BAR_STG, 8);
    mbar_init(bars + 8 * BAR_HALO, 1);
    mbar_init(bars + 8 * BAR_Q, 1);
    mbar_init(bars + 8 * BAR_LAND, 5);
    mbar_init(bars + 8 * (BAR_LAND + 1), 5);
    asm volatile("fence.mbarrier_init.release.cluster;\n" ::: "memory");
  } else if (tid == 320) {
#pragma unroll
    for (int i = 0; i < NS2; i++) {
      mbar_init(bars + 8 * (BAR_FULL2 + i), 1);
      mbar_init(bars + 8 * (BAR_EMPTY2 + i), 2);
      mbar_init(bars + 8 * (BAR_EMPTY2B + i), 2);
    }
    asm volatile("fence.mbarrier_init.release.cluster;\n" ::: "memory");
  } else if (tid == 352) {
#pragma unroll
    for (int i = 0; i < 4; i++) mbar_init(bars + 8 * (BAR_Y + i), i < 2 ? 4 : 8);
    mbar_init(bars + 8 * BAR_XFREE, 2);
    mbar_init(bars + 8 * (BAR_XFREE + 1), 2);
    asm volatile("fence.mbarrier_init.release.cluster;\n" ::: "memory");
  }
  cluster_sync_all();
  if (warp == 8) PROF2(24);

  if (warp >= 8) {
    const int hw = warp - 8;
    const int lr = lane & 7, lm = lane >> 3;
    auto g1_issue_a = [&](int j, int s) {
      const uint32_t fb = bars + 8 * (BAR_FULLA + s);
      mbar_expect_tx(fb, STG1A);
      tma_load_3d_mc(sb + s * STG1A + rank * 16384, &tmX, fb, j * 64, par, gidx * 256 + rank * 128);
    };
    auto g1_issue_b = [&](int kb, int s) {
      const uint32_t fb = bars + 8 * (BAR_FULLB + s);
      mbar_expect_tx(fb, STG1B);
      tma_load_3d(sb + OFF_1B + s * STG1B, &tmW, fb, hp * 64, kb * 32, 0);
    };
    auto g2_k = [&](int kb) { return (kb < 2 ? hp : kb < 4 ? hp & 14 : hp & 12) ^ kb; };
    auto g2_issue_b = [&](uint32_t fb, uint32_t bytes, uint32_t dst, int k0, bool whole) {
      if (whole) {
        tma_load_3d(dst, &tmWo, fb, 0, k0, cb2 * 2);
      } else {
#pragma unroll
        for (int i = 0; i < 4; i++)
          tma_load_3d(dst + (i & 1) * XT + (i >> 1) * 4 * XT, &tmWp, fb, 0, k0 + (i >> 1) * 32, cb2 * 2 + (i & 1));
      }
      mbar_expect_tx(fb, bytes);
    };
    auto send_y = [&](uint32_t o, uint32_t step, int half) {
      const uint32_t peer = mapa(sb, rank ^ 1);
      o += OFF_X + (rank ^ 1) * 4096 + half * 2048 + lane * 16;
      uint4 a[8];
#pragma unroll
      for (int i = 0; i < 8; i++) a[i] = lds128(sb + o + (i >> 2) * step + (i & 2) * (XT / 2) + (i & 1) * 512);
#pragma unroll
      for (int i = 0; i < 8; i++)
        st_async128(peer + o + 1024 + (i >> 2) * step + (i & 2) * (XT / 2) + (i & 1) * 512,
                    peer + OFF_BAR + 8 * (BAR_LAND + half), a[i].x, a[i].y, a[i].z, a[i].w);
    };
    asm volatile("setmaxnreg.dec.sync.aligned.u32 %0;\n" :: "n"(REG_HELP));

    if (halo_cta) {
      if (hw == 0) {
        int s = 1, ph = 1;
#pragma unroll 1
        for (int kb = 1; kb < 16; kb++) {
          mbar_wait(bars + 8 * (BAR_EMPTYB + s), ph);
          if (elect_one()) halo_issue(kb, s);
          if (++s == 3) { s = 0; ph ^= 1; }
        }
      }
      __syncwarp();
    } else if (hw == 0) {
      uint32_t epoch = 0;
      if (MODE == 2) {
        if (lane < NS2) mbar_arrive_cluster_n(mapa(bars, rank) + 8 * (BAR_EMPTY2 + lane), 2);
      } else {
      if (lane == 0) {
        mbar_expect_tx(bars + 8 * BAR_U, 32768);
        mbar_expect_tx(bars + 8 * BAR_LAND, 8192);
        mbar_expect_tx(bars + 8 * (BAR_LAND + 1), 8192);
        mbar_expect_tx(bars + 8 * BAR_Q, 32768);
        prefetch_tmap(&tmQ);
      }
      {
        int sa = 1, pha = 1, sbb = 2, phb = 1;
#pragma unroll 1
        for (int kb = 2; kb < 32; kb++) {
          if (!(kb & 1)) {
            mbar_wait(bars + 8 * (BAR_EMPTYA + sa), pha);
            if (elect_one()) g1_issue_a(kb >> 1, sa);
            if (++sa == NS1A) { sa = 0; pha ^= 1; }
          }
          mbar_wait(bars + 8 * (BAR_EMPTYB + sbb), phb);
          if (kb > 2 && elect_one()) g1_issue_b(kb, sbb);
          __syncwarp();
          if (kb == 4) epoch = ld_relaxed(g_flag_o + cta);
          if (kb == 4) PROF2(27);
          if (kb == 1) PROF2(38);
          if (kb == 2) PROF2(39);
          if (++sbb == NS1B) { sbb = 0; phb ^= 1; }
        }
      }
      auto q_issue = [&](int i) {
        mbar_wait(bars + 8 * (i ? BAR_EMPTYB + 3 : BAR_EMPTYA + 1), i);
        if (elect_one())
          asm volatile(
              "cp.async.bulk.tensor.5d.shared::cluster.global.mbarrier::complete_tx::bytes [%0], [%1, {%3, %4, %4, %4, %5}], [%2];\n"
              ::"r"(sb + (i ? OFF_Q1 : OFF_Q0)), "l"(&tmQ), "r"(bars + 8 * BAR_Q), "r"((chb & ~1) * 8), "r"(0), "r"(rank * 32 + i * 64)
              : "memory");
        __syncwarp();
      };
      if (QORD < 2) q_issue(0);
      else mbar_wait(bars + 8 * (BAR_EMPTYA + 1), 0);
      if (QORD < 1) q_issue(1);
      epoch++;
      if (lane == 0) {
        prefetch_tmap(&tmWo);
        prefetch_tmap(&tmWp);
        prefetch_tmap(&tmOb);
        if (gidx != 0) wait_flag(g_flag_h + (hp >> 2), epoch);
      }
      __syncwarp();
      {
        uint4 hk0 = make_uint4(0, 0, 0, 0), hk1 = hk0, hv0 = hk0, hv1 = hk0;
        if (gidx != 0) {
          const uint4* src = g_halo + cta * 128 + lane;
          hk0 = __ldcg(src); hk1 = __ldcg(src + 32); hv0 = __ldcg(src + 64); hv1 = __ldcg(src + 96);
        }
        if (gidx != 0) PROF(18);
        sts128(sb + OFF_KH + lane * 16, hk0.x, hk0.y, hk0.z, hk0.w);
        sts128(sb + OFF_KH + 512 + lane * 16, hk1.x, hk1.y, hk1.z, hk1.w);
        sts64(sb + OFF_KH + 1024 + lane * 8, movm(hv0.x), movm(hv0.y));
        sts64(sb + OFF_KH + 1280 + lane * 8, movm(hv0.z), movm(hv0.w));
        sts64(sb + OFF_KH + 1536 + lane * 8, movm(hv1.x), movm(hv1.y));
        sts64(sb + OFF_KH + 1792 + lane * 8, movm(hv1.z), movm(hv1.w));
        __syncwarp();
        if (lane == 0) mbar_arrive(bars + 8 * BAR_HALO);
      }
      if (QORD == 2) q_issue(0);
      if (QORD >= 1) q_issue(1);
      const uint32_t rb = mapa(bars, lane & 1);
      nb_sync(NB_OREADY, 288);
      if (lane == 0) {
        asm volatile("cp.async.bulk.global.shared::cta.bulk_group [%0], [%1], %2;\n" ::"l"(g_o + (size_t)cta * 16384),
                     "r"(sb + OFF_OP), "r"(32768) : "memory");
        bulk_commit();
      }
      if (lane < 2) {
#pragma unroll
        for (int i = 0; i < 4; i++) mbar_arrive_cluster(rb + 8 * (BAR_EMPTY2 + i + i / 2));
      }
      if (lane == 0) {
        bulk_wait0();
        st_release(g_flag_o + cta, epoch);
      }
      __syncwarp();
      PROF2(17);
      if (lane < 2) mbar_arrive_cluster(rb + 8 * (BAR_EMPTY2 + 2));
      }
      if (MODE != 1) {
        const __nv_bfloat16* osrc = g_o + (size_t)(rb2 >> 1) * 16 * 16384 + hsel * 8192;
        mbar_wait(bars + 8 * (BAR_EMPTY2 + 1), 0);
        if (elect_one()) {
          if (MODE == 0) {
            asm volatile("cp.async.bulk.shared::cluster.shared::cta.mbarrier::complete_tx::bytes [%0], [%1], %2, [%3];\n"
                         ::"r"(mapa(sb + g2_a(1, hsel), rank ^ 1)), "r"(sb + g2_a(0, hsel)), "r"(16384),
                         "r"(mapa(bars + 8 * (BAR_FULL2 + 1), rank ^ 1)) : "memory");
          } else {
            bulk_load(sb + g2_a(0, hsel), osrc + hp * 16384, 16384, bars + 8 * BAR_FULL2);
            bulk_load(sb + g2_a(1, hsel), osrc + (hp ^ 1) * 16384, 16384, bars + 8 * (BAR_FULL2 + 1));
          }
        }
        __syncwarp();
        unsigned long long seq = G2_SEQ >> 12;
        uint32_t wbar = bars + 8 * BAR_XFREE, fb = bars + 8 * (BAR_FULL2 + 3), dst = sb + g2_b(3, rank), ph = MODE ? 1 : 0;
        int k0 = g2_k(3) * 64;
        bool whole = false;
#pragma unroll 1
        for (int kb = 4; kb <= 16; kb++) {
          mbar_wait(wbar, ph);
          if (elect_one()) g2_issue_b(fb, STG2, dst, k0, whole);
          __syncwarp();
          seq >>= 4;
          const int s = seq & 7;
          wbar = bars + 8 * (kb == G2_KB4 ? BAR_XFREE + 1 : BAR_EMPTY2B + s);
          ph = ((uint32_t)seq >> 3 & 1) ^ (kb == G2_KB4 && MODE == 0 ? 0 : 1);
          fb = bars + 8 * (BAR_FULL2 + s);
          dst = sb + g2_b(s, rank);
          k0 = ((hp & 12) ^ kb) * 64;
          whole = s < 3;
        }
      }
      __syncwarp();
    } else {
      if (MODE != 2) {
      const float dall = __bfloat162float(p.ssm_D[chb * 8 + lr]);
      {
        const int g = lane >> 2, t = lane & 3;
        uint32_t w[2][4];
#pragma unroll
        for (int h = 0; h < 2; h++) {
          const uint2 x = __ldg(reinterpret_cast<const uint2*>(p.shift_k + ((chb & ~1) * 8 + h * 8 + g) * 4));
          w[h][0] = __byte_perm(x.x, x.x, 0x1010);
          w[h][1] = __byte_perm(x.x, x.x, 0x3232);
          w[h][2] = __byte_perm(x.y, x.y, 0x1010);
          w[h][3] = __byte_perm(x.y, x.y, 0x3232);
        }
        auto swz = [](int r) { return (((r & 29) | ((r ^ (r >> 2)) & 2)) << 5) | (r & 16); };
        const uint32_t kring = sb + OFF_X + 4096 + (hw - 1) * 2 * XT, vring = kring + XT;
        const int s0 = rank * 32 + (hw - 1) * 11, s1 = hw == 3 ? rank * 32 + 32 : s0 + 11;
        const size_t goff = (size_t)(lane >> 1) * DM + (chb & ~1) * 8 + (lane & 1) * 8;
        const __nv_bfloat16* kg = p.k + goff;
        const __nv_bfloat16* vg = p.v + goff;
        const uint32_t d0 = swz(lane >> 1) ^ ((lane & 1) << 4), d1 = swz(16 + (lane >> 1)) ^ ((lane & 1) << 4);
        auto issue = [&](int st) {
          const uint32_t so = (st & 3) << 10;
          cp_async16(kring + so + d0, kg + (size_t)st * 32 * DM, 16);
          cp_async16(kring + so + d1, kg + (size_t)(st * 32 + 16) * DM, 16);
          cp_async16(vring + so + d0, vg + (size_t)st * 32 * DM, 16);
          cp_async16(vring + so + d1, vg + (size_t)(st * 32 + 16) * DM, 16);
        };
        const int xa = 8 * (lr >> 1) + 2 * lm + (lr & 1), xb = 8 * (lr >> 1) - 4 + 2 * (lm & 1) + (lr & 1);
        const uint32_t la = swz(xa), lb = swz(xb & 31);
        const int backb = xb < 0 ? 1 : 0;
        const uint32_t ud[2] = {mapa(sb + OFF_X + g * XT + t * 16, 0), mapa(sb + OFF_X + g * XT + t * 16, 1)};
        const uint32_t ub[2] = {mapa(bars + 8 * BAR_U, 0), mapa(bars + 8 * BAR_U, 1)};
        if (tid == 320) prefetch_l2(g_tab + (chb & 63) * 32);
        if (lane == 0) mbar_wait(bars + 8 * (BAR_FULLB + NS1B - 1), 0);
        __syncwarp();
        if (lane >= 24) cp_async16(kring + (((s0 - 1) & 3) << 10) + d1, s0 > 0 ? kg + (size_t)(s0 * 32 - 16) * DM : kg, s0 > 0 ? 16 : 0);
        issue(s0);
        asm volatile("cp.async.commit_group;\n" ::: "memory");
        issue(s0 + 1);
        asm volatile("cp.async.commit_group;\n" ::: "memory");
        uint32_t tn = (uint32_t)clock();
#pragma unroll 1
        for (int st = s0; st < s1; st++) {
          tn += PSTEP;
          while ((int)((uint32_t)clock() - tn) < 0) __nanosleep(100);
          if (st + 2 < s1) issue(st + 2);
          if (hw == 1 && (unsigned)(st - s0 - HPF0) < 8u) prefetch_l2(p.ssm_k + (size_t)(chb * 8 + st - s0 - HPF0) * SEQ + lane * 64);
          asm volatile("cp.async.commit_group;\n" ::: "memory");
          asm volatile("cp.async.wait_group 2;\n" ::: "memory");
          __syncwarp();
#pragma unroll
          for (int h = 0; h < 2; h++) {
            uint32_t e[6], vv[4], e4[4];
            ldsm4t(e4, kring + ((st & 3) << 10) + (la ^ (h << 4)));
            ldsm2t(e[0], e[1], kring + (((st - backb) & 3) << 10) + (lb ^ (h << 4)));
            ldsm4t(vv, vring + ((st & 3) << 10) + (la ^ (h << 4)));
            e[2] = e4[0]; e[3] = e4[1]; e[4] = e4[2]; e[5] = e4[3];
            uint32_t o[5];
#pragma unroll
            for (int i = 0; i < 5; i++) o[i] = __byte_perm(e[i], e[i + 1], 0x5432);
#pragma unroll
            for (int i = 0; i < 4; i++) {
              uint32_t a = bmul2(o[i], w[h][3]);
              a = bfma2(e[i + 1], w[h][2], a);
              a = bfma2(o[i + 1], w[h][1], a);
              a = bfma2(e[i + 2], w[h][0], a);
              vv[i] = bmul2(a, vv[i]);
            }
            st_async128(ud[h] + (st ^ (g & 1)) * 64, ub[h], vv[0], vv[1], vv[2], vv[3]);
          }
          __syncwarp();
        }
        fence_async_smem();
        PROF(16);
      }
      nb_sync(NB_HELP3, 96);
      if (hw == 1 && elect_one()) {
        mbar_expect_tx(bars + 8 * BAR_H, 8 * 4096);
#pragma unroll 1
        for (int c = 0; c < 8; c++)
          bulk_load(sb + OFF_X + c * XT + 4096, p.ssm_k + (size_t)(chb * 8 + c) * SEQ, 4096, bars + 8 * BAR_H);
        mbar_expect_tx(bars + 8 * BAR_X, 6144);
        bulk_load(sb + OFF_T16, g_tab, 2048, bars + 8 * BAR_X);
        bulk_load(sb + OFF_T32, g_tab + 512, 4096, bars + 8 * BAR_X);
      }
      __syncwarp();
      {
        const int ck = 16 * (lane >> 4) + 2 * lr + (((lane >> 3) ^ (lane >> 2)) & 1);
        const uint32_t xo = (ck >> 1) * 64, xs = ((ck & 1) ^ (lr >> 1)) << 4;
#pragma unroll 1
        for (int job = hw - 1; job < 16; job += 3) {
          const int c = job & 7;
          uint4 a[8];
          float dv = __shfl_sync(0xffffffffu, dall, c);
          if (job < 8 || lane) dv = 0.f;
          if (job >= PF0 && job < PF1) prefetch_l2((job < 8 ? p.q + (size_t)chb * 16384 : p.wo + (size_t)chb * 8192) + c * 2048 + lane * 64);
          const uint32_t xt = sb + OFF_X + c * XT + (job >> 3) * 4096;
          mbar_wait(bars + 8 * (job < 8 ? BAR_U : BAR_H), 0);
#pragma unroll
          for (int i = 0; i < 8; i++) a[i] = lds128(xt + i * 512 + ((ck ^ (job < 8 ? (c & 1) << 2 : 0)) << 4));
          dv += bf_lo(a[0].x);
          uint32_t m[2] = {bmaxabs2(pack_bf16(dv, 0.f), bmaxabs2(a[0].x, a[0].y)), bmaxabs2(a[0].z, a[0].w)};
#pragma unroll
          for (int i = 1; i < 8; i++) {
            m[0] = bmaxabs2(bmaxabs2(m[0], a[i].x), a[i].y);
            m[1] = bmaxabs2(bmaxabs2(m[1], a[i].z), a[i].w);
          }
          m[0] = bmaxabs2(m[0], m[1]);
          const int f = max(252 - (int)(__reduce_max_sync(0xffffffffu, max(m[0] & 0x7fffu, (m[0] >> 16) & 0x7fffu)) >> 7), 1);
          if (lane == 0) asm volatile("st.shared.u32 [%0], %1;\n" ::"r"(sb + OFF_EX + job * 4), "r"(f) : "memory");
          if (f < 113) {
#pragma unroll
            for (int i = 0; i < 8; i++)
              a[i] = make_uint4(bmul2(a[i].x, f * 0x00800080u), bmul2(a[i].y, f * 0x00800080u), bmul2(a[i].z, f * 0x00800080u),
                                bmul2(a[i].w, f * 0x00800080u));
          }
          const uint32_t mul = (f < 113 ? 15 : f - 112) * 0x00800080u;
          auto cv = [&](uint32_t x) {
            x = bmul2(x, mul);
            return (x & 0x0fff0fffu) * 7 + x;
          };
          const uint32_t dst = xt + xo;
#pragma unroll
          for (int i = 0; i < 8; i++)
            sts128(dst + (i >> 2) * 2048 + (i & 1) * 1024 + (xs ^ ((i & 2) << 4)),
                   i ? cv(a[i].x) : __byte_perm(pack_f16(dv * __uint_as_float(f << 23), 0.f), cv(a[i].x), 0x7610), cv(a[i].y),
                   cv(a[i].z), cv(a[i].w));
        }
        fence_async_smem();
        __syncwarp();
        if (lane == 0) mbar_arrive(bars + 8 * BAR_X);
        PROF(19);
      }
      if (hw < 3) {
#pragma unroll 1
        for (int n = 0; n < SPIN_LIMIT && !mbar_try(bars + 8 * (BAR_Y + hw - 1), 0); n++) __nanosleep(100);
        send_y((hw - 1) * 4 * XT, 2 * XT, 0);
        __syncwarp();
        if (lane == 0) mbar_arrive(bars + 8 * (BAR_XFREE + 2 - hw));
        bool sent = false;
        auto send2 = [&]() {
          send_y((hw - 1) * 2 * XT, 4 * XT, 1);
          fence_async_smem();
          __syncwarp();
          if (lane == 0) mbar_arrive(bars + 8 * (BAR_XFREE + hw - 1));
          sent = true;
        };
        PROF(32);
        const int c8 = 2 * lm + (lr & 1), src = (lr >> 1) & 1;
        uint32_t fa = sb + OFF_X + c8 * XT + rank * 4096 + (src == rank ? 0 : 1024) + (hw - 1) * 512;
        const uint32_t fx = ((lr >> 2) ^ ((lr & 3) << 1)) << 4;
        uint32_t qa = sb + OFF_Q0 + (hw - 1) * 8192 + (lane >> 3) * 128 + (lane & 2) * 32 + (lane & 4) * 8 + (lane & 1) * 16;
        uint4* og = reinterpret_cast<uint4*>(p.out + (size_t)(rank * 512 + (hw - 1) * 256 + (lane & 2) * 4 + (lane >> 2)) * (2 * DM) +
                                             (chb & ~1) * 8 + (lane & 1) * 8);
        mbar_wait(bars + 8 * BAR_Q, 0);
        uint32_t tn = 0;
#pragma unroll 1
        for (int j = 0; j < 16; j++) {
          if (!sent && (j == 8 || mbar_test(bars + 8 * (BAR_Y + 1 + hw), 0))) {
            mbar_wait(bars + 8 * (BAR_Y + 1 + hw), 0);
            send2();
          }
          if (!(j & 7)) {
            mbar_wait(bars + 8 * (BAR_LAND + (j >> 3)), 0);
            tn = (uint32_t)clock() + (hw - 1) * (FPACE / 2);
            PROF2(33 + (j >> 1));
          }
#pragma unroll
          for (int i = 0; i < 2; i++) {
            uint32_t y[4];
            const uint4 q = lds128(qa + i * 512);
            ldsm4t(y, fa + (j & 6) * 64 + (fx ^ (i << 5) ^ ((j & 1) << 6) ^ ((j & 2) << 3)));
            while ((int)((uint32_t)clock() - tn) < 0) __nanosleep(FSL);
            tn += FPACE;
            og[i * 16 * (2 * DM / 8)] = make_uint4(bmul2(q.x, y[0]), bmul2(q.y, y[1]), bmul2(q.z, y[2]), bmul2(q.w, y[3]));
          }
          qa += j == 7 ? OFF_Q1 - OFF_Q0 - 7168 : 1024;
          if (j == 7) fa += 2048;
          og += (j == 7 ? 1024 - 224 : 32) * (2 * DM / 8);
        }
        PROF(22);
      }
      }
      if (MODE != 1 && hw == 3) {
        const uint32_t epoch = ld_relaxed(g_flag_o + cta) + 1;
        if (MODE == 0) nb_sync(NB_G1END, 288);
        if (BDEL) __nanosleep(BDEL);
        if (elect_one()) {
#pragma unroll
          for (int kb = 0; kb < 3; kb++)
            g2_issue_b(bars + 8 * (BAR_FULL2 + kb), kb || MODE ? STG2 : STG2 / 2, sb + g2_b(kb, 0), g2_k(kb) * 64, true);
        }
        __syncwarp();
        const __nv_bfloat16* osrc = g_o + (size_t)(rb2 >> 1) * 16 * 16384 + hsel * 8192;
        if (MODE == 0) __nanosleep(POLL0);
        const uint32_t* flag = g_flag_o + (rb2 >> 1) * 16 + g2_k(lane & 15);
        uint32_t ready = MODE == 0 ? 0u : ~0u;
        unsigned long long seq = G2_SEQ >> 8;
#pragma unroll 1
        for (int kb = 2; kb < 16; kb++, seq >>= 4) {
          uint32_t so = bars + (seq & 7) * 8, dst = sb + g2_a(seq & 7, hsel) + rank * 8192;
          const uint32_t ph = (uint32_t)seq >> 3 & 1;
          const __nv_bfloat16* src = osrc + rank * 4096 + (uint32_t)g2_k(kb) * 16384;
          asm volatile("" : "+r"(so), "+r"(dst), "+l"(src));
          if (!(ready >> kb & 1)) {
#pragma unroll 1
            for (int n = 0; n < SPIN_LIMIT && !(ready >> kb & 1); n++)
              ready = __ballot_sync(0xffffffffu, ld_acquire(flag) == epoch);
            fence_async_all();
          }
          if (kb == 2) PROF(21);
          if (MODE == 0 && kb == G2_KB4 && rank == 1) mbar_wait(bars + 8 * BAR_TAB, 0);
          mbar_wait(so + 8 * BAR_EMPTY2, ph);
          if (elect_one()) {
            asm volatile(
                "cp.async.bulk.shared::cluster.global.mbarrier::complete_tx::bytes.multicast::cluster [%0], [%1], %2, [%3], %4;\n"
                ::"r"(dst), "l"(src), "r"(8192), "r"(so + 8 * BAR_FULL2), "h"((uint16_t)3) : "memory");
          }
          __syncwarp();
        }
      }
    }
    cluster_sync_all();
    PROF_DUMP();
  } else {
    asm volatile("setmaxnreg.inc.sync.aligned.u32 %0;\n" :: "n"(REG_MATH));
    if (warp == 0) PROF2(26);
    const int wg = warp >> 2;
    const int wtid = tid & 127;
    const bool signaller = (wtid == 0) || (wtid == 32);
    const uint32_t rbars = mapa(bars, wtid >> 5 & 1);

    if (halo_cta) {
      const uint32_t epoch = ld_relaxed(g_flag_h + blockIdx.x) + 1;
      float acc0[64], acc1[64];
      int s = 0, ph = 0;
#pragma unroll 1
      for (int kb = 0; kb < 16; kb++) {
        mbar_wait(bars + 8 * (BAR_FULLB + s), ph);
        const uint32_t st = sb + s * STGH;
        const uint64_t da = mkdesc(st, 16, 1024, 1);
        const uint64_t db = mkdesc(st + 8192 + wg * 32768, 8192, 1024, 1);
        wg_fence();
#pragma unroll
        for (int kk = 0; kk < 4; kk++) {
          wgmma_n128(acc0, da + 2 * kk, db + 128 * kk, kb + kk);
          wgmma_n128(acc1, da + 2 * kk, db + 1024 + 128 * kk, kb + kk);
        }
        wg_commit();
        wg_wait<0>();
        if (kb == 15) PROF(37);
        if (wtid == 0) mbar_arrive(bars + 8 * (BAR_EMPTYB + s));
        if (++s == 3) { s = 0; ph ^= 1; }
      }
      fence_regs(acc0);
      fence_regs(acc1);
      if ((warp & 3) != 3) {
#pragma unroll
        for (int hh = 0; hh < 2; hh++) {
          uint4* dst = g_halo + ((hh * 4 + (warp & 3) + 1) * 16 + blockIdx.x * 4) * 128 + wg * 64 + lane;
#pragma unroll
          for (int j = 0; j < 4; j++) {
            const int o = 16 * j + 2 * hh;
            dst[(j >> 1) * 128 + (j & 1) * 32] =
                make_uint4(pack_bf16(acc0[o], acc0[o + 1]), pack_bf16(acc0[o + 4], acc0[o + 5]),
                           pack_bf16(acc0[o + 8], acc0[o + 9]), pack_bf16(acc0[o + 12], acc0[o + 13]));
            dst[(2 + (j >> 1)) * 128 + (j & 1) * 32] =
                make_uint4(pack_bf16(acc1[o], acc1[o + 1]), pack_bf16(acc1[o + 4], acc1[o + 5]),
                           pack_bf16(acc1[o + 8], acc1[o + 9]), pack_bf16(acc1[o + 12], acc1[o + 13]));
          }
        }
      }
      nb_sync(NB_G1DONE, 256);
      if (tid == 0) st_release(g_flag_h + blockIdx.x, epoch);
      PROF(36);
      cluster_sync_all();
      return;
    }

    float acc[64];
    const uint32_t g2rel = wtid ? mapa(bars, rank) + 8 * BAR_EMPTY2B : mapa(bars, wg) + 8 * BAR_EMPTY2;
    uint32_t g2a = (uint32_t)mkdesc(sb + wg * 8192, 16, 0, 0), g2b = (uint32_t)mkdesc(sb, 8192, 0, 0);
    auto g2_block = [&](bool first, int s, int ph) {
      mbar_wait(bars + 8 * (BAR_FULL2 + s), ph);
      const uint32_t da = g2a + (g2_a(s, hsel) >> 4), db = g2b + (g2_b(s, rank) >> 4), dc = db + (g2_bk(s) >> 4);
      wg_fence();
      if (first) wgmma_n128z(acc, da, db);
      else wgmma_n128a(acc, da, db);
      wgmma_n128a(acc, da + 2, db + 128);
      wgmma_n128a(acc, da + 4, dc);
      wgmma_n128a(acc, da + 6, dc + 128);
      wg_commit();
    };
    if (MODE != 2) {
    uint32_t a1[2][4], sc[2];
    C2 t[2];
    {
      float acc0[96], acc1[96];
      int sa = 0, pha = 0, sbb = 0, phb = 0;
      asm volatile("cp.async.wait_group 0;\n" ::: "memory");
      fence_async_smem();
      nb_sync(NB_FIRST, 256);
      if (tid == 0) {
        mbar_arrive(bars + 8 * BAR_FULLA);
        mbar_arrive(bars + 8 * BAR_FULLB);
      }
      PROF(0 + wg);
#pragma unroll 1
      for (int kb = 0; kb < 30; kb++) {
        if (!(kb & 1)) mbar_wait(bars + 8 * (BAR_FULLA + sa), pha);
        mbar_wait(bars + 8 * (BAR_FULLB + sbb), phb);
        if (kb == 0) PROF2(0 + wg);
        if (kb == 4 && wg == 0) PROF2(28);
        if (kb == 8 && wg == 0) PROF2(29);
        if (kb == 16 && wg == 0) PROF2(30);
        const uint64_t da = mkdesc(sb + sa * STG1A + wg * 16384 + (kb & 1) * 64, 16, 2048, 1);
        const uint64_t db = mkdesc(sb + OFF_1B + sbb * STG1B, 4096, 1024, 1);
        wg_fence();
        wgmma_n192(acc0, da + 64, db, kb);
        wgmma_n192(acc1, da, db, kb);
        wgmma_n192(acc0, da + 66, db + 128, 1);
        wgmma_n192(acc1, da + 2, db + 128, 1);
        wg_commit();
        wg_wait<1>();
        if (kb > 0) {
          if (wtid == 64) mbar_arrive(bars + 8 * (BAR_EMPTYB + (sbb == 0 ? NS1B - 1 : sbb - 1)));
          if (!(kb & 1) && signaller) mbar_arrive_cluster(rbars + 8 * (BAR_EMPTYA + (sa == 0 ? NS1A - 1 : sa - 1)));
        }
        if (++sbb == NS1B) { sbb = 0; phb ^= 1; }
        if ((kb & 1) && ++sa == NS1A) { sa = 0; pha ^= 1; }
      }
      const int lr = lane & 7, lm = lane >> 3;
      const bool le0 = 2 * (lane & 3) <= (lane >> 2), le1 = 2 * (lane & 3) + 1 <= (lane >> 2);
      const uint32_t maskLE = (le0 ? 0x0000FFFFu : 0u) | (le1 ? 0xFFFF0000u : 0u);
      uint32_t q[4][8], k[5][8], vt[5][8];
      {
        static_assert(15 % NS1A == 0 && 30 % NS1B == 0, "slots of the last k blocks");
        asm volatile("ld.volatile.global.v4.u32 {%0,%1,%2,%3}, [%4];\n"
                     : "=r"(t[0].r), "=r"(t[1].r), "=r"(t[0].i), "=r"(t[1].i) : "l"(g_tab + 1536 + wtid * 4) : "memory");
        mbar_wait(bars + 8 * BAR_FULLA, 1);
        mbar_wait(bars + 8 * BAR_FULLB, 0);
        mbar_wait(bars + 8 * (BAR_FULLB + 1), 0);
        mbar_wait(bars + 8 * (BAR_EMPTYA + 1), 0);
        const uint64_t da = mkdesc(sb + wg * 16384, 16, 2048, 1);
        const uint64_t db = mkdesc(sb + OFF_1B, 4096, 1024, 1);
        wg_fence();
#pragma unroll
        for (int i = 0; i < 4; i++) wgmma_n192(acc0, da + 64 + 2 * i, db + (i >> 1) * (STG1B >> 4) + (i & 1) * 128, 1);
        wg_commit();
#pragma unroll
        for (int i = 0; i < 2; i++) wgmma_n192(acc1, da + 2 * i, db + (i >> 1) * (STG1B >> 4) + (i & 1) * 128, 1);
        wg_commit();
        wg_wait<1>();
        fence_regs(acc0);
        PROFA(45, 0);
        attn_pack<8, 1, false>(acc0, k[4]);
        attn_pack<16, 1, true>(acc0, vt[4]);
        const uint32_t kh = sb + (warp == 7 ? OFF_OP + 7 * 4096 : OFF_KH + (warp + 1) * 2048) + lane * 16;
        sts128(kh, k[4][0], k[4][1], k[4][2], k[4][3]);
        sts128(kh + 512, k[4][4], k[4][5], k[4][6], k[4][7]);
#pragma unroll
        for (int i = 0; i < 4; i++) sts64(kh - lane * 8 + 1024 + 256 * i, vt[4][2 * i], vt[4][2 * i + 1]);
#pragma unroll
        for (int i = 2; i < 4; i++) wgmma_n192(acc1, da + 2 * i, db + (i >> 1) * (STG1B >> 4) + (i & 1) * 128, 1);
        wg_commit();
        attn_pack<0, 0, false>(acc0, q[1]);
        attn_pack<0, 1, false>(acc0, q[3]);
        attn_pack<8, 0, false>(acc0, k[2]);
        attn_pack<16, 0, true>(acc0, vt[2]);
        uint32_t z = p.zero;
#pragma unroll
        for (int i = 0; i < 8; i++) z &= q[1][i] & q[3][i];
#pragma unroll
        for (int i = 0; i < 8; i += 2) z &= k[2][i] & k[2][i + 1];
        __syncwarp();
        if (lane == 0) mbar_arrive(bars + 8 * BAR_STG + z);
        wg_wait<0>();
        fence_regs(acc1);
        if (MODE == 0) nb_arrive(NB_G1END, 288);
      }
      PROF(2 + wg);
      mbar_wait(bars + 8 * (warp == 0 ? BAR_HALO : BAR_STG), 0);
      {
        const uint32_t kh = sb + OFF_KH + warp * 2048 + lane * 16;
#pragma unroll
        for (int i = 0; i < 2; i++) {
          const uint4 t = lds128(kh + 512 * i);
          k[0][4 * i] = t.x; k[0][4 * i + 1] = t.y; k[0][4 * i + 2] = t.z; k[0][4 * i + 3] = t.w;
        }
#pragma unroll
        for (int i = 0; i < 4; i++) {
          const uint2 t = lds64(kh - lane * 8 + 1024 + 256 * i);
          vt[0][2 * i] = t.x; vt[0][2 * i + 1] = t.y;
        }
      }
      attn_pack<0, 0, false>(acc1, q[0]);
      attn_pack<0, 1, false>(acc1, q[2]);
      attn_pack<8, 0, false>(acc1, k[1]);
      attn_pack<8, 1, false>(acc1, k[3]);
      {
        float x[8][2];
        uint32_t pp[8];
        const bool first = warp == 0 && gidx == 0;
#pragma unroll
        for (int hd = 0; hd < 2; hd++) {
#pragma unroll
          for (int j = 0; j < 4; j += 2) {
            float s0[4], s1[4], s2[4];
            attn_qk(s2, q[j], q[j + 1], k[j + 2], 4 * hd);
            attn_qk(s1, q[j], q[j + 1], k[j + 1], 4 * hd);
            attn_qk(s0, q[j], q[j + 1], k[j], 4 * hd);
            if (j == 0 && first) s0[0] = s0[1] = -1e9f / 0.17677669529663687f;
            x[2 * j + hd][0] = le0 ? s1[0] : s0[0];
            x[2 * j + hd][1] = le1 ? s1[1] : s0[1];
            x[2 * j + 2 + hd][0] = le0 ? s2[2] : s1[2];
            x[2 * j + 2 + hd][1] = le1 ? s2[3] : s1[3];
          }
        }
        PROFA(40, __float_as_uint(x[1][0] + x[7][1]));
        attn_pack<16, 0, true>(acc1, vt[1]);
        attn_pack<16, 1, true>(acc1, vt[3]);
        quad_softmax<8>(x, pp);
        PROFA(41, pp[1] + pp[7]);
        mbar_wait(bars + 8 * BAR_X, 0);
        ldsm4(a1[0], sb + OFF_T32 + (warp & 3) * 1024 + lane * 16);
        ldsm4(a1[1], sb + OFF_T32 + 512 + (warp & 3) * 1024 + lane * 16);
        {
          const uint32_t ex = sb + OFF_EX + wg * 16 + (warp & 2) * 2;
#pragma unroll
          for (int i = 0; i < 2; i++) sc[i] = min(max(381 - (int)lds32(ex + 8 * i) - (int)lds32(ex + 32 + 8 * i), 1), 254) * 0x00800080u;
        }
        const uint32_t obase = sb + OFF_OP + (warp * 32 + lr) * 128;
#pragma unroll
        for (int n = 0; n < 8; n++) {
          attn_pv(obase + (n >> 1) * 1024 + (((4 * (n & 1) + lm) ^ lr) << 4), vt[n >> 1], vt[(n >> 1) + 1], 4 * (n & 1), pp[n],
                  maskLE);
        }
      }
      PROFA(42, 0);
    }

    {
      const int w = warp & 3;
      const int lr = lane & 7, lm = lane >> 3;
      const uint32_t xb = sb + OFF_X + wg * 4 * XT;
      auto uo = [](int c) { return (c & 1) * 2 * XT + (c >> 1) * 2048; };
      const uint64_t dc2 = mkdesc(sb + OFF_T16, 512, 128, 0), dc3 = mkdesc(sb + OFF_T16, 128, 512, 0);
      const uint64_t dc4 = mkdesc(sb + OFF_T32, 128, 256, 0);
      const uint64_t dx = mkdesc(xb, 4096, 512, 2), dz = mkdesc(xb, 4096, 256, 3);
      const uint32_t zs = xb + (w * 16 + (lm & 1) * 8 + lr) * 32 + (((lm >> 1) ^ (lr >> 2)) << 4);
      const uint32_t ys = xb + w * 4096 + (lm >> 1) * 256 + ((lr * 32 + (((lm & 1) ^ (lr >> 2)) << 4)) ^ (rank << 6) ^ ((w & 2) << 4));
      const bool own = (w & 1) == rank;
      const uint32_t ybar = mapa(bars, own ? rank ^ 1 : rank) + 8 * BAR_Y;
      uint32_t d[2][32], pa[2][4][2][4], e[4][4][8], ya[2][2][2][4], v[2][2][8];
      C2 s1[2][2][2];
      float o[2][16];
      auto rows = [&](int c) {
        fft_rows(d[c & 1], a1, dx + (uo(c) >> 4));
        wg_commit();
      };
      auto cols = [&](int c) {
        const int s = c & 1;
        fence_regs(d[s]);
#pragma unroll
        for (int i = 0; i < 16; i++) {
          const C2 z = crot(C2{d[s][2 * i], d[s][2 * i + 1]}, t[i & 1]);
          pa[s][i >> 2][i & 1][(i >> 1) & 1] = z.r;
          pa[s][i >> 2][i & 1][2 + ((i >> 1) & 1)] = z.i;
        }
        wg_fence();
#pragma unroll
        for (int i = 0; i < 4; i++) fft_cols<0>(e[c][i], pa[s][i], dc2);
        wg_commit();
      };
      auto prod = [&](int c, int n) {
        const int s = c & 1;
        fence_regs(e[c][2 * n]);
        fence_regs(e[c][2 * n + 1]);
#pragma unroll
        for (int j = 0; j < 2; j++) {
          const C2 u0 = cget(e[s][2 * n], j, 0), u1 = cget(e[s][2 * n], j, 1);
          const C2 h0 = cget(e[s][2 * n + 1], j, 0), h1 = cget(e[s][2 * n + 1], j, 1);
          C2 y0, y1;
          if (c < 2) {
            y0 = cmul(h0, u0);
            s1[s][n][j] = cfma(h0, u1, cmul(h1, u0));
            y1 = C2{hadd2(s1[s][n][j].r, y0.i), hadd2(s1[s][n][j].i, hneg2(y0.r))};
          } else {
            const C2 u2 = cget(e[c][2 * n], j, 0), u3 = cget(e[c][2 * n], j, 1);
            const C2 h2 = cget(e[c][2 * n + 1], j, 0), h3 = cget(e[c][2 * n + 1], j, 1);
            const C2 s2 = cfma(h0, u2, cfma(h2, u0, cmul(h1, u1)));
            y0 = C2{hadd2(s2.r, s1[s][n][j].i), hadd2(s2.i, hneg2(s1[s][n][j].r))};
            y1 = cfma(h0, u3, cfma(h1, u2, cfma(h2, u1, cfma(h3, u0, C2{s2.i, hneg2(s2.r)}))));
          }
          ya[s][n][j][0] = y0.r;
          ya[s][n][j][1] = y1.r;
          ya[s][n][j][2] = y0.i;
          ya[s][n][j][3] = y1.i;
        }
      };
      auto icols = [&](int c) {
        wg_fence();
        fft_cols<1>(v[c & 1][0], ya[c & 1][0], dc3);
        fft_cols<1>(v[c & 1][1], ya[c & 1][1], dc3);
        wg_commit();
      };
      auto stage = [&](int c) {
        const int s = c & 1;
        fence_regs(v[s][0]);
        fence_regs(v[s][1]);
#pragma unroll
        for (int b = 0; b < 4; b++) {
          const C2 x0 = cget(v[s][b >> 1], 0, b & 1), x1 = cget(v[s][b >> 1], 1, b & 1);
          const C2 z0 = crot(C2{x0.i, x0.r}, t[0]), z1 = crot(C2{x1.i, x1.r}, t[1]);
          stsm4(zs + uo(c) + b * 4096, z0.i, z0.r, z1.i, z1.r);
        }
      };
      auto back = [&](int c) {
        fft_back(o[c & 1], dz + (uo(c) >> 4), dc4);
        wg_commit();
      };
      auto out = [&](int c) {
        float (&r)[16] = o[c & 1];
        fence_regs(r);
#pragma unroll
        for (int i = 0; i < 16; i += 8)
          stsm4t(ys + uo(c) + 64 * i, bmul2(pack_bf16(r[i], r[i + 1]), sc[c & 1]), bmul2(pack_bf16(r[i + 2], r[i + 3]), sc[c & 1]),
                 bmul2(pack_bf16(r[i + 4], r[i + 5]), sc[c & 1]), bmul2(pack_bf16(r[i + 6], r[i + 7]), sc[c & 1]));
      };
      auto signal = [&](int yb, int land) {
        __syncwarp();
        if (lane == 0) {
          mbar_arrive_cluster(ybar + 8 * yb);
          if (own && land >= 0) mbar_arrive(bars + 8 * (BAR_LAND + land));
        }
      };
      wg_fence();
      rows(0);
      rows(1);
      fence_async_smem();
      nb_arrive(NB_OREADY, 288);
      PROF(34 + wg);
      wg_wait<1>();
      cols(0);
      wg_wait<1>();
      cols(1);
      rows(2);
      nb_sync(NB_CONV + wg, 128);
      wg_wait<2>();
      prod(0, 0);
      prod(0, 1);
      icols(0);
      wg_wait<2>();
      prod(1, 0);
      prod(1, 1);
      icols(1);
      PROF3(40 + 10 * wg);
      wg_wait<1>();
      stage(0);
      wg_wait<0>();
      stage(1);
      fence_async_smem();
      cols(2);
      PROF3(41 + 10 * wg);
      nb_sync(NB_CONV + wg, 128);
      back(0);
      back(1);
      wg_wait<2>();
      wg_fence();
      rows(3);
      prod(2, 0);
      wg_wait<1>();
      out(0);
      out(1);
      signal(wg, 0);
      PROF3(42 + 10 * wg);
      prod(2, 1);
      icols(2);
      wg_wait<1>();
      cols(3);
      PROF3(43 + 10 * wg);
      wg_wait<1>();
      stage(2);
      fence_async_smem();
      wg_wait<0>();
      prod(3, 0);
      nb_sync(NB_CONV + wg, 128);
      wg_fence();
      back(2);
      prod(3, 1);
      icols(3);
      PROF3(44 + 10 * wg);
      wg_wait<1>();
      out(2);
      signal(2, -1);
      wg_wait<0>();
      stage(3);
      PROF3(45 + 10 * wg);
      fence_async_smem();
      nb_sync(NB_CONV + wg, 128);
      wg_fence();
      back(3);
      constexpr int G = MODE == 0 && EARLY;
      if (MODE == 0) mbar_wait(bars + 8 * (BAR_EMPTY2 + 4), 0);
      if (G) g2_block(true, 0, 0);
      wg_wait<G>();
      if (lane == 0) mbar_arrive_cluster(mapa(bars, 1) + 8 * BAR_TAB);
      out(3);
      signal(3, 1);
      PROF(6 + wg);
    }
    }

    if (MODE != 1) {
      if (MODE == 2 || !EARLY) g2_block(true, 0, 0);
      const int lr = lane & 7, lm = lane >> 3;
      const uint32_t wb = sb + g2_a(1, 0) + warp * 2048;
      const int orow = (rb2 & 7) * 128 + warp * 16;
      uint4* og = reinterpret_cast<uint4*>(p.out + (size_t)(2 * (orow + lm) + (rb2 >> 3)) * (2 * DM) + DM + cb2 * 128 + lr * 8);
      uint32_t wst = wb + (lr + 8 * (lm & 1)) * 128, wsx = ((lm >> 1) ^ lr) << 4, wld = wb + lm * 128, wlx = (lr ^ lm) << 4;
      asm volatile("" : "+l"(og), "+r"(wst), "+r"(wsx), "+r"(wld), "+r"(wlx));
      static_assert(ENDG == NS2 && (G2SEQ >> 4 & 0xfffff) == (G2SEQ >> 24 & 0xfffff) && (G2SEQ >> 4 & 0xfffff) == G2SEQ >> 44, "rounds");
#pragma unroll 1
      for (int r = 0; r < 3; r++) {
        const bool hold = r == 2 && wg != LEADWG;
        const uint32_t rel0 = g2rel + (r ? 8 * (G2SEQ >> 20 & 7) : 0);
        if (hold) {
          wg_wait<0>();
          if (signaller) mbar_arrive_cluster(rel0);
          nb_sync(NB_LEAD, 256);
        }
#pragma unroll
        for (int i = 1; i <= NS2; i++) {
          const int s = G2SEQ >> (4 * i) & 7;
          g2_block(false, s, (r & 1) ^ (s == 0));
          if (warp == LEADWG * 4) PROF2(40 + 5 * r + i);
          if (i == 1 ? !hold : r < 2) {
            wg_wait<1>();
            if (signaller) mbar_arrive_cluster(i == 1 ? rel0 : g2rel + 8 * (G2SEQ >> (4 * i - 4) & 7));
          }
        }
        if (r == 0) PROF(8 + wg);
        g2a += p.zero;
        g2b += p.zero;
      }
      if (wg == LEADWG) nb_arrive(NB_LEAD, 256);
      wg_wait<0>();
      fence_regs(acc);
      PROF(10 + wg);
#pragma unroll
      for (int h = 0; h < 2; h++) {
        const uint32_t b = h * (g2_a(3, 0) - g2_a(1, 0));
#pragma unroll
        for (int j = 8 * h; j < 8 * h + 8; j += 2)
          stsm4(wst + b + (wsx ^ ((j & 7) << 4)), pack_bf16(acc[4 * j], acc[4 * j + 1]),
                pack_bf16(acc[4 * j + 2], acc[4 * j + 3]), pack_bf16(acc[4 * j + 4], acc[4 * j + 5]),
                pack_bf16(acc[4 * j + 6], acc[4 * j + 7]));
        if (OTMA == 2 || (OTMA == 1 && wg == LEADWG)) {
          fence_async_smem();
          __syncwarp();
          if (elect_one()) {
            tma_store_3d(&tmOb, wb + b, DM + cb2 * 128 + h * 64, rb2 >> 3, orow);
            bulk_commit();
          }
        } else {
          __syncwarp();
          uint4 v[4];
#pragma unroll
          for (int i = 0; i < 4; i++) v[i] = lds128(wld + b + i * 512 + (wlx ^ ((i & 1) << 6)));
#pragma unroll
          for (int i = 0; i < 4; i++) og[(size_t)i * 8 * (2 * DM / 8) + h * 8] = v[i];
        }
      }
      PROF(12 + wg);
      if (OTMA) bulk_wait0();
    }
    cluster_sync_all();
  }
}

typedef CUresult (*EncodeFn)(CUtensorMap*, CUtensorMapDataType, cuuint32_t, void*, const cuuint64_t*, const cuuint64_t*,
                             const cuuint32_t*, const cuuint32_t*, CUtensorMapInterleave, CUtensorMapSwizzle,
                             CUtensorMapL2promotion, CUtensorMapFloatOOBfill);

void make_map(EncodeFn enc, CUtensorMap* tm, const void* base, int rank, const cuuint64_t* dims, const cuuint64_t* strides,
              const cuuint32_t* box, CUtensorMapSwizzle swz) {
  cuuint32_t es[5] = {1, 1, 1, 1, 1};
  enc(tm, CU_TENSOR_MAP_DATA_TYPE_BFLOAT16, rank, const_cast<void*>(base), dims, strides, box, es,
      CU_TENSOR_MAP_INTERLEAVE_NONE, swz, CU_TENSOR_MAP_L2_PROMOTION_L2_256B, CU_TENSOR_MAP_FLOAT_OOB_FILL_NONE);
}

}

extern "C" void kernel_launch(void* const* d_in, const int* in_sizes, int n_in, void* d_out, int out_size) {
  static EncodeFn enc = nullptr;
  static bool coresident = true;
  if (!enc) {
    void* fn = nullptr;
    cudaDriverEntryPointQueryResult qr;
    cudaGetDriverEntryPoint("cuTensorMapEncodeTiled", &fn, cudaEnableDefault, &qr);
    enc = (EncodeFn)fn;
    cudaFuncSetAttribute(fused_kernel<0>, cudaFuncAttributeMaxDynamicSharedMemorySize, SMEM_BYTES);
    cudaFuncSetAttribute(fused_kernel<1>, cudaFuncAttributeMaxDynamicSharedMemorySize, SMEM_BYTES);
    cudaFuncSetAttribute(fused_kernel<2>, cudaFuncAttributeMaxDynamicSharedMemorySize, SMEM_BYTES);
    cudaLaunchConfig_t cfg = {};
    cfg.gridDim = dim3(NCTA);
    cfg.blockDim = dim3(NTHREADS);
    cfg.dynamicSmemBytes = SMEM_BYTES;
    cudaLaunchAttribute at;
    at.id = cudaLaunchAttributeClusterDimension;
    at.val.clusterDim.x = 2;
    at.val.clusterDim.y = 1;
    at.val.clusterDim.z = 1;
    cfg.attrs = &at;
    cfg.numAttrs = 1;
    int nclusters = 0;
    if (cudaOccupancyMaxActiveClusters(&nclusters, fused_kernel<0>, &cfg) == cudaSuccess) coresident = nclusters >= NCTA / 2;
    (void)cudaGetLastError();
  }
  CUtensorMap tmX, tmW, tmWo, tmWp, tmQ, tmOb, tmXh, tmWh;
  {
    cuuint64_t dims[3] = {1024, 2, 1024};
    cuuint64_t str[2] = {2048, 4096};
    cuuint32_t box[3] = {64, 1, 128};
    make_map(enc, &tmX, d_in[6], 3, dims, str, box, CU_TENSOR_MAP_SWIZZLE_128B);
  }
  {
    cuuint64_t dims[3] = {1024, 1024, 3};
    cuuint64_t str[2] = {6144, 2048};
    cuuint32_t box[3] = {64, 32, 3};
    make_map(enc, &tmW, d_in[7], 3, dims, str, box, CU_TENSOR_MAP_SWIZZLE_128B);
  }
  {
    cuuint64_t dims[3] = {64, 1024, 16};
    cuuint64_t str[2] = {2048, 128};
    cuuint32_t box[3] = {64, 64, 2};
    cuuint32_t piece[3] = {64, 32, 1};
    make_map(enc, &tmWo, d_in[8], 3, dims, str, box, CU_TENSOR_MAP_SWIZZLE_128B);
    make_map(enc, &tmWp, d_in[8], 3, dims, str, piece, CU_TENSOR_MAP_SWIZZLE_128B);
  }
  {
    cuuint64_t dims[5] = {1024, 2, 2, 4, 128};
    cuuint64_t str[4] = {2048, 8 * 2048, 2 * 2048, 16 * 2048};
    cuuint32_t box[5] = {16, 2, 2, 4, 32};
    make_map(enc, &tmQ, d_in[0], 5, dims, str, box, CU_TENSOR_MAP_SWIZZLE_NONE);
  }
  {
    cuuint64_t dims[3] = {2048, 2, 1024};
    cuuint64_t str[2] = {4096, 8192};
    cuuint32_t box[3] = {64, 1, 16};
    make_map(enc, &tmOb, d_out, 3, dims, str, box, CU_TENSOR_MAP_SWIZZLE_128B);
  }
  {
    cuuint64_t dims[4] = {1024, 256, 2, 4};
    cuuint64_t str[3] = {4096, 2048, 256 * 4096};
    cuuint32_t box[4] = {64, 8, 2, 3};
    make_map(enc, &tmXh, d_in[6], 4, dims, str, box, CU_TENSOR_MAP_SWIZZLE_128B);
  }
  {
    cuuint64_t dims[3] = {64, 1024, 48};
    cuuint64_t str[2] = {6144, 128};
    cuuint32_t box[3] = {64, 64, 4};
    make_map(enc, &tmWh, d_in[7], 3, dims, str, box, CU_TENSOR_MAP_SWIZZLE_128B);
  }
  Params p;
  p.q = (const __nv_bfloat16*)d_in[0];
  p.k = (const __nv_bfloat16*)d_in[1];
  p.v = (const __nv_bfloat16*)d_in[2];
  p.shift_k = (const __nv_bfloat16*)d_in[3];
  p.ssm_k = (const __nv_bfloat16*)d_in[4];
  p.ssm_D = (const __nv_bfloat16*)d_in[5];
  p.x = (const __nv_bfloat16*)d_in[6];
  p.w = (const __nv_bfloat16*)d_in[7];
  p.wo = (const __nv_bfloat16*)d_in[8];
  p.out = (__nv_bfloat16*)d_out;
  p.zero = 0;
  if (coresident) {
    fused_kernel<0><<<NCTA, NTHREADS, SMEM_BYTES>>>(p, tmX, tmW, tmWo, tmWp, tmQ, tmOb, tmXh, tmWh);
  } else {
    fused_kernel<0><<<4, NTHREADS, SMEM_BYTES>>>(p, tmX, tmW, tmWo, tmWp, tmQ, tmOb, tmXh, tmWh);
    fused_kernel<1><<<NCTA, NTHREADS, SMEM_BYTES>>>(p, tmX, tmW, tmWo, tmWp, tmQ, tmOb, tmXh, tmWh);
    fused_kernel<2><<<NCTA, NTHREADS, SMEM_BYTES>>>(p, tmX, tmW, tmWo, tmWp, tmQ, tmOb, tmXh, tmWh);
  }
}
```

```cpp
#include <cuda_runtime.h>
#include <cuda.h>
#include <cuda_bf16.h>
#include <stdint.h>

namespace {

constexpr int SEQ = 2048;
constexpr int DM = 1024;
constexpr int NCTA = 132;
constexpr int NTHREADS = 384;

constexpr int STG1A = 32768;
constexpr int NS1A = 3;
constexpr int STG1B = 12288;
constexpr int NS1B = 5;
constexpr int OFF_1B = NS1A * STG1A;
constexpr int STG2 = 32768;
constexpr int NS2 = 5;
#define G2SEQ 0x0432104321043210ull
constexpr unsigned long long g2_seq() {
  unsigned long long r = G2SEQ;
  for (int kb = 0; kb < 16; kb++)
    for (int j = 0; j < kb; j++)
      if (((G2SEQ >> (4 * j)) & 7) == ((G2SEQ >> (4 * kb)) & 7)) r ^= 8ull << (4 * kb);
  return r;
}
constexpr unsigned long long G2_SEQ = g2_seq();
constexpr int g2_first4() {
  int kb = 0;
  while (((G2SEQ >> (4 * kb)) & 7) != 4) kb++;
  return kb;
}
constexpr int G2_KB4 = g2_first4();
#define POLL0 1500
#define QORD 1
#define BDEL 0
#define XPF 0
#define HPF0 3
#define PF0 8
#define PF1 12
#define PSTEP 1150
#define FPACE 260
#define LEADWG 1
#define OTMA 1
#define EARLY 1
#define R3 0
#define FSL 50
#define JS 1
#define FPACE2 230
#define ENDG 5
__device__ __forceinline__ uint32_t g2_a(int s, int hsel) { return (((0x97524 >> (4 * s)) & 15) ^ (s & 5 ? 0 : hsel)) << 14; }
constexpr int OFF_Q0 = 3 << 14, OFF_Q1 = 8 << 14;
constexpr int STGH = 73728;
constexpr int OFF_KH = 1 * STG2;
constexpr int OFF_OP = 2 * STG2;
constexpr int OFF_T32 = 5 * STG2 - 4096;
constexpr int OFF_X = 5 * STG2;
constexpr int XT = 8192;
__device__ __forceinline__ uint32_t g2_b(int s, int rank) {
  return s < 3 ? (s == 2 ? 6 : s) << 14 : OFF_X + (s - 3) * 2 * XT + (rank ^ 1) * 4096;
}
__device__ __forceinline__ uint32_t g2_bk(int s) { return s < 3 ? 4096 : 4 * XT; }
constexpr int OFF_BAR = OFF_X + 8 * XT;
constexpr int OFF_EX = OFF_BAR + 448;
constexpr int OFF_T16 = 230400;
constexpr int SMEM_BYTES = OFF_T16 + 2048;
static_assert(OFF_1B + NS1B * STG1B <= OFF_T32 && OFF_X % 1024 == 0, "layout");
static_assert(3 * STGH <= OFF_BAR && OFF_EX + 64 <= OFF_T16 && SMEM_BYTES <= 232448, "smem");

constexpr int BAR_FULLA = 0;
constexpr int BAR_EMPTYA = 3;
constexpr int BAR_FULLB = 6;
constexpr int BAR_EMPTYB = 11;
constexpr int BAR_FULL2 = 16;
constexpr int BAR_EMPTY2 = 21;
constexpr int BAR_EMPTY2B = 44;
constexpr int BAR_X = 26;
constexpr int BAR_LAND = 42;
constexpr int BAR_TAB = 28;
constexpr int BAR_U = 29;
constexpr int BAR_H = 30;
constexpr int BAR_STG = 31;
constexpr int BAR_Y = 32;
constexpr int BAR_XFREE = 38;
constexpr int BAR_HALO = 40;
constexpr int BAR_Q = 41;

constexpr int NB_G1DONE = 1;
constexpr int NB_LEAD = 2;
constexpr int NB_G1END = 3;
constexpr int NB_OREADY = 4;
constexpr int NB_CONV = 5;
constexpr int NB_HELP3 = 11;
constexpr int NB_FIRST = 13;

#define REG_MATH 224
#define REG_HELP 56
constexpr int SPIN_LIMIT = 1 << 20;

__device__ __align__(1024) __nv_bfloat16 g_o[SEQ * DM];
__device__ uint32_t g_flag_o[128];
__device__ uint32_t g_flag_h[4];
__device__ uint4 g_halo[128 * 128];
__device__ __align__(128) const uint32_t g_tab[2048] = {
  0x2fd93000,0x2ea72f64,0x2c722da8,0x263e2a1f,0x2ea73000,0xa63e2a1f,0xafd9ada8,0xac72af64,0x2c723000,0xafd9aa1f,0x263eada8,0x2ea72f64,
  0x263e3000,0xac72af64,0x2ea72da8,0xafd9aa1f,0xa63e3000,0x2c72af64,0xaea72da8,0x2fd9aa1f,0xac723000,0x2fd9aa1f,0xa63eada8,0xaea72f64,
  0xaea73000,0x263e2a1f,0x2fd9ada8,0x2c72af64,0xafd93000,0xaea72f64,0xac722da8,0xa63e2a1f,0x263e0000,0x2c722a1f,0x2ea72da8,0x2fd92f64,
  0x2c720000,0x2fd92f64,0x263e2da8,0xaea7aa1f,0x2ea70000,0x263e2f64,0xafd9ada8,0x2c72aa1f,0x2fd90000,0xaea72a1f,0x2c72ada8,0xa63e2f64,
  0x2fd90000,0xaea7aa1f,0x2c722da8,0xa63eaf64,0x2ea70000,0x263eaf64,0xafd92da8,0x2c722a1f,0x2c720000,0x2fd9af64,0x263eada8,0xaea72a1f,
  0x263e0000,0x2c72aa1f,0x2ea7ada8,0x2fd9af64,0xafd93000,0xaea72f64,0xac722da8,0xa63e2a1f,0xaea73000,0x263e2a1f,0x2fd9ada8,0x2c72af64,
  0xac723000,0x2fd9aa1f,0xa63eada8,0xaea72f64,0xa63e3000,0x2c72af64,0xaea72da8,0x2fd9aa1f,0x263e3000,0xac72af64,0x2ea72da8,0xafd9aa1f,
  0x2c723000,0xafd9aa1f,0x263eada8,0x2ea72f64,0x2ea73000,0xa63e2a1f,0xafd9ada8,0xac72af64,0x2fd93000,0x2ea72f64,0x2c722da8,0x263e2a1f,
  0xa63e0000,0xac722a1f,0xaea72da8,0xafd92f64,0xac720000,0xafd92f64,0xa63e2da8,0x2ea7aa1f,0xaea70000,0xa63e2f64,0x2fd9ada8,0xac72aa1f,
  0xafd90000,0x2ea72a1f,0xac72ada8,0x263e2f64,0xafd90000,0x2ea7aa1f,0xac722da8,0x263eaf64,0xaea70000,0xa63eaf64,0x2fd92da8,0xac722a1f,
  0xac720000,0xafd9af64,0xa63eada8,0x2ea72a1f,0xa63e0000,0xac72aa1f,0xaea7ada8,0xafd9af64,0xa63e0000,0xac72aa1f,0xaea7ada8,0xafd9af64,
  0xac720000,0xafd9af64,0xa63eada8,0x2ea72a1f,0xaea70000,0xa63eaf64,0x2fd92da8,0xac722a1f,0xafd90000,0x2ea7aa1f,0xac722da8,0x263eaf64,
  0xafd90000,0x2ea72a1f,0xac72ada8,0x263e2f64,0xaea70000,0xa63e2f64,0x2fd9ada8,0xac72aa1f,0xac720000,0xafd92f64,0xa63e2da8,0x2ea7aa1f,
  0xa63e0000,0xac722a1f,0xaea72da8,0xafd92f64,0x2fd93000,0x2ea72f64,0x2c722da8,0x263e2a1f,0x2ea73000,0xa63e2a1f,0xafd9ada8,0xac72af64,
  0x2c723000,0xafd9aa1f,0x263eada8,0x2ea72f64,0x263e3000,0xac72af64,0x2ea72da8,0xafd9aa1f,0xa63e3000,0x2c72af64,0xaea72da8,0x2fd9aa1f,
  0xac723000,0x2fd9aa1f,0xa63eada8,0xaea72f64,0xaea73000,0x263e2a1f,0x2fd9ada8,0x2c72af64,0xafd93000,0xaea72f64,0xac722da8,0xa63e2a1f,
  0x263e0000,0x2c72aa1f,0x2ea7ada8,0x2fd9af64,0x2c720000,0x2fd9af64,0x263eada8,0xaea72a1f,0x2ea70000,0x263eaf64,0xafd92da8,0x2c722a1f,
  0x2fd90000,0xaea7aa1f,0x2c722da8,0xa63eaf64,0x2fd90000,0xaea72a1f,0x2c72ada8,0xa63e2f64,0x2ea70000,0x263e2f64,0xafd9ada8,0x2c72aa1f,
  0x2c720000,0x2fd92f64,0x263e2da8,0xaea7aa1f,0x263e0000,0x2c722a1f,0x2ea72da8,0x2fd92f64,0xafd93000,0xaea72f64,0xac722da8,0xa63e2a1f,
  0xaea73000,0x263e2a1f,0x2fd9ada8,0x2c72af64,0xac723000,0x2fd9aa1f,0xa63eada8,0xaea72f64,0xa63e3000,0x2c72af64,0xaea72da8,0x2fd9aa1f,
  0x263e3000,0xac72af64,0x2ea72da8,0xafd9aa1f,0x2c723000,0xafd9aa1f,0x263eada8,0x2ea72f64,0x2ea73000,0xa63e2a1f,0xafd9ada8,0xac72af64,
  0x2fd93000,0x2ea72f64,0x2c722da8,0x263e2a1f,0xa63e0000,0xac72aa1f,0xaea7ada8,0xafd9af64,0x2c720000,0x2fd92f64,0x263e2da8,0xaea7aa1f,
  0xaea70000,0xa63eaf64,0x2fd92da8,0xac722a1f,0x2fd90000,0xaea72a1f,0x2c72ada8,0xa63e2f64,0xafd90000,0x2ea72a1f,0xac72ada8,0x263e2f64,
  0x2ea70000,0x263eaf64,0xafd92da8,0x2c722a1f,0xac720000,0xafd92f64,0xa63e2da8,0x2ea7aa1f,0x263e0000,0x2c72aa1f,0x2ea7ada8,0x2fd9af64,
  0x2fd93000,0x2ea72f64,0x2c722da8,0x263e2a1f,0xaea7b000,0x263eaa1f,0x2fd92da8,0x2c722f64,0x2c723000,0xafd9aa1f,0x263eada8,0x2ea72f64,
  0xa63eb000,0x2c722f64,0xaea7ada8,0x2fd92a1f,0xa63e3000,0x2c72af64,0xaea72da8,0x2fd9aa1f,0x2c72b000,0xafd92a1f,0x263e2da8,0x2ea7af64,
  0xaea73000,0x263e2a1f,0x2fd9ada8,0x2c72af64,0x2fd9b000,0x2ea7af64,0x2c72ada8,0x263eaa1f,0x263e0000,0x2c72aa1f,0x2ea7ada8,0x2fd9af64,
  0xac720000,0xafd92f64,0xa63e2da8,0x2ea7aa1f,0x2ea70000,0x263eaf64,0xafd92da8,0x2c722a1f,0xafd90000,0x2ea72a1f,0xac72ada8,0x263e2f64,
  0x2fd90000,0xaea72a1f,0x2c72ada8,0xa63e2f64,0xaea70000,0xa63eaf64,0x2fd92da8,0xac722a1f,0x2c720000,0x2fd92f64,0x263e2da8,0xaea7aa1f,
  0xa63e0000,0xac72aa1f,0xaea7ada8,0xafd9af64,0xafd93000,0xaea72f64,0xac722da8,0xa63e2a1f,0x2ea7b000,0xa63eaa1f,0xafd92da8,0xac722f64,
  0xac723000,0x2fd9aa1f,0xa63eada8,0xaea72f64,0x263eb000,0xac722f64,0x2ea7ada8,0xafd92a1f,0x263e3000,0xac72af64,0x2ea72da8,0xafd9aa1f,
  0xac72b000,0x2fd92a1f,0xa63e2da8,0xaea7af64,0x2ea73000,0xa63e2a1f,0xafd9ada8,0xac72af64,0xafd9b000,0xaea7af64,0xac72ada8,0xa63eaa1f,
  0xafd9b000,0xaea7af64,0xac72ada8,0xa63eaa1f,0x2ea73000,0xa63e2a1f,0xafd9ada8,0xac72af64,0xac72b000,0x2fd92a1f,0xa63e2da8,0xaea7af64,
  0x263e3000,0xac72af64,0x2ea72da8,0xafd9aa1f,0x263eb000,0xac722f64,0x2ea7ada8,0xafd92a1f,0xac723000,0x2fd9aa1f,0xa63eada8,0xaea72f64,
  0x2ea7b000,0xa63eaa1f,0xafd92da8,0xac722f64,0xafd93000,0xaea72f64,0xac722da8,0xa63e2a1f,0xa63e0000,0xac72aa1f,0xaea7ada8,0xafd9af64,
  0x2c720000,0x2fd92f64,0x263e2da8,0xaea7aa1f,0xaea70000,0xa63eaf64,0x2fd92da8,0xac722a1f,0x2fd90000,0xaea72a1f,0x2c72ada8,0xa63e2f64,
  0xafd90000,0x2ea72a1f,0xac72ada8,0x263e2f64,0x2ea70000,0x263eaf64,0xafd92da8,0x2c722a1f,0xac720000,0xafd92f64,0xa63e2da8,0x2ea7aa1f,
  0x263e0000,0x2c72aa1f,0x2ea7ada8,0x2fd9af64,0x2fd9b000,0x2ea7af64,0x2c72ada8,0x263eaa1f,0xaea73000,0x263e2a1f,0x2fd9ada8,0x2c72af64,
  0x2c72b000,0xafd92a1f,0x263e2da8,0x2ea7af64,0xa63e3000,0x2c72af64,0xaea72da8,0x2fd9aa1f,0xa63eb000,0x2c722f64,0xaea7ada8,0x2fd92a1f,
  0x2c723000,0xafd9aa1f,0x263eada8,0x2ea72f64,0xaea7b000,0x263eaa1f,0x2fd92da8,0x2c722f64,0x2fd93000,0x2ea72f64,0x2c722da8,0x263e2a1f,
  0x263e0000,0x2c72aa1f,0x2ea7ada8,0x2fd9af64,0xac720000,0xafd92f64,0xa63e2da8,0x2ea7aa1f,0x2ea70000,0x263eaf64,0xafd92da8,0x2c722a1f,
  0xafd90000,0x2ea72a1f,0xac72ada8,0x263e2f64,0x2fd90000,0xaea72a1f,0x2c72ada8,0xa63e2f64,0xaea70000,0xa63eaf64,0x2fd92da8,0xac722a1f,
  0x2c720000,0x2fd92f64,0x263e2da8,0xaea7aa1f,0xa63e0000,0xac72aa1f,0xaea7ada8,0xafd9af64,0x316c2fbd,0x343e32f7,0x35bc34ff,0x372c3676,
  0x371532c6,0x3a81392e,0x3bef3b71,0x3b7c3bf2,0x397034cf,0x3bfc3b6c,0x38b23b04,0xb40e31e8,0x3ae13631,0x39e73bf5,0xb6e83219,0xbbe8bb13,
  0x3bc23785,0x30be3aa9,0xbbfdb911,0x2a16b9aa,0x3bfe3865,0xb80f37a6,0xb82abc00,0x3bfd376f,0x3b9238fd,0xbb7f2311,0x3805b929,0x31223bde,
  0x3a85398b,0xbb96b742,0x3bff319e,0xbbb82f8b,0xbbe2bbf1,0xbbb7bbcf,0xbb78bb9a,0xbb27bb52,0xbb2cbbd2,0xb8a8ba19,0xb029b5df,0x35a52f59,
  0xb9dfbba1,0x2ba7b5f7,0x3a7a37b2,0x3bbd3bdd,0xb815bb60,0x39662e91,0x3b373bda,0xb0d7377a,0xb3d3bb10,0x3be9386f,0x2a7a3a31,0xbbfeb9a6,
  0x294dbab0,0x3ae53b07,0xbad51fdb,0xab43bb16,0x352fba41,0x35993c00,0xbaebba1d,0x3be531cf,0x38a3b9c5,0xb5173b21,0x2776bbe0,0x34323bf2,
  0x384537dd,0x38ea3899,0x39823937,0x3a0d39c9,0x39463a93,0x3340374e,0xb426a452,0xb979b7c8,0xbb45b924,0xbb32bc00,0xb371b902,0x38d63294,
  0xb08db9a1,0x3b3f379b,0x39583bd7,0xb8252dfb,0x3bea3a2d,0xb3ba3874,0xbb89bb0d,0x36d2b625,0xb6bb387f,0xb8d1bbf5,0x3be73602,0xb546391f,
  0xba00bb01,0x3bff35eb,0xba5c34db,0x3359bab6,0x3ac7b66b,0xb9413933,0x368dbabd,0xb0103bb3,0xbac4baf7,0xba50ba8c,0xb9cdba11,0xb93cb986,
  0x3a04388e,0x3bcb3b1e,0x3bba3c00,0x39d63afe,0x36af3a21,0xb6ffa17f,0xbbc8ba3d,0xba60bbd4,0xbbebb9af,0xb6c6bb0a,0x39f43263,0x3ad83bf7,
  0x30a6b916,0x3bc33aa5,0xb55e3790,0xbb3dbb63,0x3b423a9e,0xba642ec3,0xb0f0bb6a,0x3b8e3a25,0xb94a37bd,0x2884bb6f,0x38db3b9f,0xbbc9b85a,
  0xb840bb54,0x3a093a15,0xbb4cb850,0x3bef3457,0x3a893a4d,0x3af43ac1,0x3b4f3b24,0x3b983b76,0xbb94baba,0xbbe4bbf9,0xba58bb57,0xb699b8f8,
  0x3bfe3b18,0x394f3b5c,0xb109347b,0xbae8b884,0xbbc0bb68,0xa9b1b90c,0x3b8b387a,0x38bc3ba5,0x3ade3ba7,0xb8c1324b,0xb9f0bbf6,0x39eb9648,
  0xb96bbbd6,0x3bbf3487,0xb38939b3,0xb9f8bba3,0x370a3bf3,0xbb47b994,0x3bbc2d65,0xb8ad3889,0xb153bc00,0x37213b9c,0xb97dba90,0x3af138f3,
  0xb89eb8ee,0xb7e8b84a,0xb682b737,0xb50bb5c8,0x35233855,0xb13b2d33,0xb8e0b65f,0xbb4aba45,0xa8e8b764,0x39fc3648,0x3be63bae,0x380a3a9b,
  0xb3eb360e,0xbbfeba35,0xb552baa2,0x3a7334b7,0x381ab4ab,0x3a6f3bd8,0xb95d2e5f,0xb962bc00,0xb9e3327c,0xb402bbac,0x3bc6399d,0xb95434c3,
  0x3b2faf27,0xb6a439bc,0xb41abbf9,0x3a7e3a97,0xbbe3251b,0x3b2ab4f3,0xb9d23894,0x37f3ba49,0x3bce3bb5,0x3bf03be1,0x3bff3bfa,0x3bfb3bff,
  0x2c38b1b6,0x383a34e7,0x3aee39c0,0x3bff3bb2,0xbb81bbf8,0xb53ab999,0x38302ef5,0x3bed3ab3,0xb8cc9cb6,0xbb85bbab,0x2adeb86a,0x3bc5391b,
  0x38c73bf6,0xbadbb232,0xb6ddbba9,0x3b87361a,0x3b833201,0xb0743a39,0xba76bb5e,0x3b352dc9,0xac06bbb0,0x39743b59,0xbbeeb759,0x3aceb2ad,
  0xbbccb5d4,0x3bfb2d00,0xbb7a32de,0x3a54b7d2,0xb30fb44b,0xafefb185,0xa6adacce,0x2c9c25e4,0xbbfcbbdf,0xbacbbb9e,0xb7feb990,0xa81fb463,
  0xb58d2d97,0xbb90b9b8,0xbad1bbf4,0xb05bb85f,0x3a673c00,0xb5763493,0xbbfdbaac,0xb3a2ba29,0x3a6b2e2d,0x38203bd9,0xbb3ab49f,0xb56abb65,
  0xb581bbdc,0x3bec3907,0xb8b7363c,0xb6f4bbf8,0xbbfcb46f,0x39dab654,0xb0423b1b,0xb835bbd3,0xb3283b73,0xac6abbfa,0x35b13bd0,0xb8e5bafb,
  0x38ee3a0d,0xb84aba89,0x37373af4,0xb5c8bb4f,0x35df3a81,0x2f59bbef,0xb88e3b7c,0x3b1eb946,0x2d973ae8,0x39b8bb81,0xbbf4353a,0x385f3830,
  0xb2633b3f,0x3bf7b958,0xb60eb825,0xba353bc0,0xb7853b87,0x3aa9b3d3,0x3911bbe9,0xb9aa2a7a,0xb99d3bbf,0x34c33389,0x3bdcb9f8,0x3907bb83,
  0xbb013be5,0xb5eb394a,0x34db2884,0x3ab6b8db,0xbbd03bfb,0xbafb3b7a,0xb98b3a54,0xb74238a3,0x3a4db93c,0xbac1389e,0x3b24b7e8,0xbb763682,
  0x3b71b8a8,0xbbf23029,0x3a9335a5,0xb74eba04,0x3bf8b80a,0xb999b58d,0xaef53b90,0x3ab3bad1,0x3bd7b6c6,0xadfbb9f4,0xbb683ad8,0x390c33eb,
  0x3b10b56a,0x386fbbc2,0xba3130be,0xb9a63bfd,0x39b3b402,0x3ba3bbc6,0x3201b954,0xba393581,0x37bdb122,0x3b6fba00,0x3b9fbbff,0x385aba5c,
  0x32deac6a,0x37d2b5b1,0x39c5b8e5,0x3b21ba85,0x344b3b98,0xb185bbce,0x2cce3bf0,0x25e4bbff,0xbc003340,0x3afe3426,0xb855b979,0x2d333b94,
  0x34cfbbed,0xbb6c39df,0x3b042ba7,0xb1e8ba7a,0x3aa2a9b1,0x34b7bb8b,0xbc0038bc,0x349338cc,0xba2d3bfe,0x387430a6,0x3b0dbbc3,0xb625b55e,
  0xb63cb074,0xbbf83a76,0xb8653b35,0x37a6294d,0x3bf3bbc9,0x3994bb2f,0x2d65b6a4,0xb889341a,0xb19e3517,0x2f8b2776,0x366bb432,0x3933b840,
  0x3bb5b50b,0xbbe1330f,0x3bfaafef,0xbbff26ad,0xa4523bcb,0x37c8bbba,0xbaba39d6,0x3bf9b523,0xbba1305b,0x35f73970,0x37b2bbfc,0xbbdd38b2,
  0x387abbfe,0xbba53552,0x9cb63a73,0x3babba67,0x39162a16,0x3aa5bbea,0xb790b3ba,0xbb633b89,0xbb5e3bec,0xadc938b7,0x3ab0b6f4,0x3b07bbfe,
  0xaf27b359,0xb9bc370a,0xbbf93b47,0xba973bbc,0x3be0bb96,0x3bf2bbff,0x3b54bbb8,0x3a15bac7,0xafbd3bfb,0x32f7bbe2,0xb4ff3bb7,0x3676bb78,
  0x365fbbe4,0xba453a58,0x3bdfb699,0xbb9eac38,0xb9243bbd,0x3c00b6af,0xb902b6ff,0xb2943bc8,0x3aacbb85,0xba29aade,0xb6313bc5,0x3bf5b815,
  0xbba73b3d,0x324b381a,0x3bf6ba6f,0x9648b95d,0x3c00bae5,0x376fbad5,0xb87f2b43,0xbbf53b42,0xbbb03a7e,0xbb593bfc,0xb75939da,0x32ad3042,
  0x3abdba09,0x3bb3bb4c,0x3c00bbef,0x3b9cbbe3,0x3bf12c9c,0xbbcfb16c,0x3b9a343e,0xbb52b5bc,0xbb57b13b,0x38f838e0,0xb1b6bb4a,0xb4e73bfc,
  0x3a21340e,0x217fbb45,0xba3d3b32,0x3bd4b371,0xb86ab576,0xb91b3bfd,0x3b60b3a2,0x2e91bae1,0x34ab36d2,0x3bd8bade,0xae5fb8c1,0xbc0039f0,
  0x9fdbb80f,0xbb16382a,0xba9e3bfd,0x2ec336bb,0xb46f38ad,0x3654ac06,0x3b1bb974,0x3bd3bbee,0x3850b941,0x3457b68d,0xa51bb010,0xb4f33153,
  0xb7dd3b27,0x3899bac4,0xb9373a50,0x39c9b9cd,0x3990383a,0xb463baee,0xb2c63bff,0x392ebb2c,0x3b18ba60,0xbb5c28e8,0x347b39fc,0x3884bbe6,
  0xb219b966,0xbb133b37,0x39a130d7,0x379bbbeb,0xbbf63962,0xb2323a6b,0x3ba9b820,0x361abb3a,0xb6023a64,0x391fb0f0,0x3bd6bb8e,0x3487b9e3,
  0x3a41b835,0x3c00bb92,0x3a1dbb7f,0x31cfb805,0x3a90bb2a,0x38f3b9d2,0x35d4b7f3,0x2d00b328,0x3af7372c,0xba8cb845,0x3a1138ea,0xb986b982,
  0x39c0bacb,0xbbb237fe,0x3bd2a81f,0xba19b715,0xb764b8d6,0xb6483bfe,0x3baeb94f,0xba9bb109,0xbbda39e7,0x377a36e8,0x39afbbe8,0xbb0a308d,
  0xae2d39eb,0x3bd9b8c7,0x349fbadb,0xbb6536dd,0x3b6ab8d1,0x3a25bbe7,0xb27cb546,0xbbac396b,0x38fdbace,0xa311b52f,0xb9293599,0xbbde3aeb,
  0xb8943721,0xba49397d,0xbb733af1,0xbbfa3bcc,0xbbfb3bff,0xbbe23bf1,0xbbb73bcf,0xbb783b9a,0xbb7c3bf2,0xb9463a93,0xb340374e,0x3426a452,
  0xba603bd4,0xa8e83764,0x39fcb648,0x3be6bbae,0xb8bc3ba5,0x38cc9cb6,0x3b85bbab,0xaadeb86a,0xb56a3b65,0x3bc2b785,0x30bebaa9,0xbbfd3911,
  0xab433b16,0x3b42ba9e,0xba64aec3,0xb0f03b6a,0x33593ab6,0x370abbf3,0xbb473994,0x3bbcad65,0x37f33a49,0xb328bb73,0xac6a3bfa,0x35b1bbd0,
  0xac9c25e4,0xb16c2fbd,0xb43e32f7,0xb5bc34ff,0xb5a52f59,0xba04388e,0xbbcb3b1e,0xbbba3c00,0xb8d63294,0xbbfe3b18,0xb94f3b5c,0x3109347b,
  0xba7334b7,0xba673c00,0x35763493,0x3bfdbaac,0xbb87361a,0xb3d33b10,0x3be9b86f,0x2a7aba31,0xbbfd376f,0x36bb387f,0x38d1bbf5,0xbbe73602,
  0xbbc9385a,0x3b2f2f27,0xb6a4b9bc,0xb41a3bf9,0xbaf138f3,0x3bccb5d4,0xbbfb2d00,0x3b7a32de,0xbb273b52,0xbac43af7,0xba503a8c,0xb9cd3a11,
  0x3979b7c8,0x3b94baba,0x3be4bbf9,0x3a58bb57,0x380aba9b,0xb58dad97,0xbb9039b8,0xbad13bf4,0xbbc5391b,0xb8153b60,0x3966ae91,0x3b37bbda,
  0x2a1639aa,0x3beaba2d,0xb3bab874,0xbb893b0d,0x3b8eba25,0xb9e3b27c,0xb4023bac,0x3bc6b99d,0xb8adb889,0xac063bb0,0x3974bb59,0xbbee3759,
  0xb8e53afb,0x3a85b98b,0xbb963742,0x3bffb19e,0xb72c3676,0xb84537dd,0xb8ea3899,0xb9823937,0xb9d63afe,0xb5233855,0x313b2d33,0x38e0b65f,
  0x3ae8b884,0x3b81bbf8,0x353ab999,0xb8302ef5,0x33a2ba29,0xbae13631,0xb9e73bf5,0x36e83219,0xbbfe39a6,0x30a63916,0x3bc3baa5,0xb55eb790,
  0x3546391f,0x396bbbd6,0xbbbf3487,0x338939b3,0x3a7eba97,0xbbfc346f,0x39da3654,0xb042bb1b,0xba54b7d2,0x38a339c5,0xb517bb21,0x27763be0,
  0xb93c3986,0xb89e38ee,0xb7e8384a,0xb6823737,0x3699b8f8,0xac38b1b6,0xb83a34e7,0xbaee39c0,0xb05b385f,0x3970b4cf,0x3bfcbb6c,0x38b2bb04,
  0xb0d7b77a,0xbbeb39af,0xb6c63b0a,0x39f4b263,0x36d23625,0x3adebba7,0xb8c1b24b,0xb9f03bf6,0xb954b4c3,0xb5813bdc,0x3becb907,0xb8b7b63c,
  0x3ace32ad,0xb52fba41,0xb5993c00,0x3aebba1d,0xbbb8af8b,0x3ac7366b,0xb941b933,0x368d3abd,0xba0d39c9,0xba893a4d,0xbaf43ac1,0xbb4f3b24,
  0x3b4aba45,0x3bfcbbdf,0x3acbbb9e,0x37feb990,0xbbed3ab3,0xb9df3ba1,0x2ba735f7,0x3a7ab7b2,0x3be8bb13,0x308db9a1,0xbb3f379b,0xb9583bd7,
  0xbb3d3b63,0x381a34ab,0x3a6fbbd8,0xb95dae5f,0x39f8bba3,0xbb833201,0x30743a39,0x3a76bb5e,0xb8353bd3,0x3b92b8fd,0xbb7fa311,0x38053929,
  0x3432bbf2,0xb8403b54,0x3a09ba15,0xbb4c3850,0xb50b35c8,0xb30f344b,0xafef3185,0xa6ad2cce,0xbbff3bb2,0xbb2c3bd2,0xb8a83a19,0xb02935df,
  0xb40eb1e8,0xbb453924,0xbb323c00,0xb3713902,0x3ad8bbf7,0xb3ebb60e,0xbbfe3a35,0xb5523aa2,0x39eb1648,0x38c7bbf6,0xbadb3232,0xb6dd3ba9,
  0xb6f43bf8,0x3bfeb865,0xb80fb7a6,0xb82a3c00,0xbbe531cf,0x394a37bd,0xa884bb6f,0xb8db3b9f,0xb010bbb3,0xb1533c00,0x3721bb9c,0xb97d3a90,
  0xbb983b76,0xbbce3bb5,0xbbf03be1,0xbbff3bfa,0x281fb463,0xb71532c6,0xba81392e,0xbbef3b71,0x3bbdbbdd,0x36afba21,0xb6ff217f,0xbbc83a3d,
  0x38252dfb,0x3bc0bb68,0x29b1b90c,0xbb8b387a,0xb9623c00,0x3a6bae2d,0x3820bbd9,0xbb3a349f,0xbb352dc9,0x294d3ab0,0x3ae5bb07,0xbad59fdb,
  0x3122bbde,0xba003b01,0x3bffb5eb,0xba5cb4db,0x3befb457,0xbbe3a51b,0x3b2a34f3,0xb9d2b894,0x39c939cd,0xba4db93c,0x3ac1389e,0xbb24b7e8,
  0x3b1e3946,0xbc00b340,0x3afeb426,0xb8553979,0x3bdd38b2,0xba21340e,0xa17fbb45,0x3a3d3b32,0x3bf53815,0xb2193966,0xbb13bb37,0x39a1b0d7,
  0x3b6536dd,0x37853b87,0xbaa9b3d3,0xb911bbe9,0x3a393581,0x3b5e3bec,0x2dc938b7,0xbab0b6f4,0x3889341a,0x3bb03a7e,0x3b593bfc,0x375939da,
  0x34f33153,0x38943721,0x3a49397d,0x3b733af1,0xb9863982,0x38eeba0d,0xb84a3a89,0x3737baf4,0xb74e3a04,0xa452bbcb,0x37c83bba,0xbabab9d6,
  0xb1e83a7a,0xb924bbbd,0x3c0036af,0xb90236ff,0x2e913ae1,0xbbdab9e7,0x377ab6e8,0x39af3be8,0x361a3b3a,0xbb10b56a,0xb86fbbc2,0x3a3130be,
  0x39073b83,0xb63c3074,0xbbf8ba76,0xb865bb35,0x3a973bbc,0x346f38ad,0xb654ac06,0xbb1bb974,0x3b9c3be3,0x3a903b2a,0x38f339d2,0x35d437f3,
  0x3b763682,0xbbb5b50b,0x3be1330f,0xbbfaafef,0x2d33bb94,0x365f3be4,0xba45ba58,0x3bdf3699,0xbbd4b371,0x3764b8d6,0x36483bfe,0xbbaeb94f,
  0x379b3beb,0xbbd7b6c6,0x2dfbb9f4,0x3b683ad8,0x39aa2a7a,0x3a2d3bfe,0xb87430a6,0xbb0dbbc3,0xbb07bbfe,0x1fdbb80f,0x3b16382a,0x3a9e3bfd,
  0xb2ad3042,0xba41b835,0xbc00bb92,0xba1dbb7f,0x3bfa3bcc,0x3bd03bfb,0x3afb3b7a,0x398b3a54,0xb5c83b4f,0x344bbb98,0xb1853bce,0x2ccebbf0,
  0x3bf93523,0xbb57313b,0x38f8b8e0,0xb1b63b4a,0xb294bbc8,0x3b183a60,0xbb5ca8e8,0x347bb9fc,0xbb0ab08d,0xb263bb3f,0x3bf73958,0xb60e3825,
  0x39a63bfd,0xb9162a16,0xbaa5bbea,0x3790b3ba,0x37a6a94d,0x3c003ae5,0x376f3ad5,0xb87fab43,0xbbd3bbee,0xb8fdbace,0x2311b52f,0x39293599,
  0x2d003328,0xb2deac6a,0xb7d2b5b1,0xb9c5b8e5,0x3bff26ad,0xbbf12c9c,0x3bcfb16c,0xbb9a343e,0xbb9e2c38,0x3990b83a,0xb4633aee,0xb2c6bbff,
  0x3a9bb109,0xad973ae8,0xb9b8bb81,0x3bf4353a,0xb90c33eb,0xb87abbfe,0x3ba53552,0x1cb63a73,0x3625b55e,0x3ba73b3d,0xb24b381a,0xbbf6ba6f,
  0xaec336bb,0xbb6ab8d1,0xba25bbe7,0x327cb546,0xb1cfb805,0x37bd3122,0x3b6f3a00,0x3b9f3bff,0x374238a3,0x319e3517,0xaf8b2776,0xb66bb432,
  0x25e43bff,0xafbdbbfb,0x32f73be2,0xb4ffbbb7,0xb4e7bbfc,0x39c03acb,0xbbb2b7fe,0x3bd2281f,0x38843be6,0xbbf8b80a,0x3999b58d,0x2ef53b90,
  0xba35bbc0,0x3aa229b1,0x34b73b8b,0xbc00b8bc,0x3b633b89,0xb4ab36d2,0xbbd8bade,0x2e5fb8c1,0xbbf5bb42,0xb602ba64,0x391f30f0,0x3bd63b8e,
  0x3bde3aeb,0x3b013be5,0x35eb394a,0xb4db2884,0xbb21ba85,0xbbe0bb96,0xbbf2bbff,0xbb54bbb8,0x3b52b5bc,0xbaf7372c,0x3a8cb845,0xba1138ea,
  0x392e3b2c,0xbb71b8a8,0x3bf23029,0xba9335a5,0xb85f3830,0xb4cfbbed,0x3b6c39df,0xbb042ba7,0xbbabba67,0x386ab576,0x391b3bfd,0xbb60b3a2,
  0x1648b95d,0x3bf63962,0x32323a6b,0xbba9b820,0x3bac396b,0x399d3bbf,0xb4c33389,0xbbdcb9f8,0x385a3a5c,0xaf273359,0xb9bcb70a,0xbbf9bb47,
  0xb933b840,0xbabdba09,0xbbb3bb4c,0xbc00bbef,0x36763b78,0xb7ddbb27,0x38993ac4,0xb937ba50,0xba193715,0x35dfba81,0x2f593bef,0xb88ebb7c,
  0xbab3bad1,0x3ba1305b,0xb5f73970,0xb7b2bbfc,0x3493b8cc,0x3aac3b85,0xba292ade,0xb631bbc5,0x3c0039f0,0x2e2d39eb,0xbbd9b8c7,0xb49fbadb,
  0x348739e3,0xb9b3b402,0xbba3bbc6,0xb201b954,0xbab6b8db,0xbbf3bbc9,0xb994bb2f,0xad65b6a4,0xba15bac7,0xb850b941,0xb457b68d,0x251bb010,
  0xb9cfbb16,0x30ac2a31,0x3b9c3bf1,0xb493ae2d,0xb76fb8b4,0x35a133e3,0x3a1d3afe,0xb902b76f,0xb3e3b5a1,0x38b4376f,0x376f3902,0xbafeba1d,
  0xaa31b0ac,0x3b1639cf,0x2e2d3493,0xbbf1bb9c,0xb956ba74,0x305f29cc,0x3b633bd2,0xb44badc9,0xb6e7b859,0x353f335e,0x39d23ab6,0xb8bcb6ff,
  0xb35eb53f,0x385936e7,0x36ff38bc,0xbab6b9d2,0xa9ccb05f,0x3a743956,0x2dc9344b,0xbbd2bb63,0xb8e3b9de,0x30122967,0x3b1e3ba1,0xb402ad65,
  0xb662b801,0x34de32da,0x39823a67,0xb874b68d,0xb2dab4de,0x38013662,0x368d3874,0xba67b982,0xa967b012,0x39de38e3,0x2d653402,0xbba1bb1e,
  0xb876b952,0x2f8c2902,0x3ace3b60,0xb371ad00,0xb5e1b758,0x347e3257,0x392e3a11,0xb82ab61a,0xb257b47e,0x375835e1,0x361a382a,0xba11b92e,
  0xa902af8c,0x39523876,0x2d003371,0xbb60bace,0xb80db8ce,0x2ef3289e,0x3a733b10,0xb2deac9c,0xb562b6b3,0x342031d5,0x38d639b3,0xb7bdb5a5,
  0xb1d5b420,0x36b33562,0x35a537bd,0xb9b3b8d6,0xa89eaef3,0x38ce380d,0x2c9c32de,0xbb10ba73,0xb750b851,0x2e5a2839,0x3a0d3ab0,0xb24bac38,
  0xb4e5b613,0x33863153,0x387a394f,0xb721b52f,0xb153b386,0x361334e5,0x352f3721,0xb94fb87a,0xa839ae5a,0x38513750,0x2c38324b,0xbab0ba0d,
  0xb68eb7b4,0x2dc227a9,0x399d3a41,0xb1b6aba7,0xb46ab577,0x32cd30d2,0x381a38e5,0xb682b4b7,0xb0d2b2cd,0x3577346a,0x34b73682,0xb8e5b81a,
  0xa7a9adc2,0x37b4368e,0x2ba731b6,0xba41b99d,0xb5d2b6d1,0x2d2a26e0,0x392439c5,0xb122aade,0xb3e3b4de,0x32163052,0x376f3874,0xb5dfb43e,
  0xb052b216,0x34de33e3,0x343e35df,0xb874b76f,0xa6e0ad2a,0x36d135d2,0x2ade3122,0xb9c5b924,0xb51cb5f6,0x2c932617,0x38a3393c,0xb08daa16,
  0xb2f4b448,0x31602fa5,0x36a437fe,0xb53ab389,0xafa5b160,0x344832f4,0x3389353a,0xb7feb6a4,0xa617ac93,0x35f6351c,0x2a16308d,0xb93cb8a3,
  0xb46ab523,0x2bf6254d,0x381a38a8,0xafefa94d,0xb209b36b,0x30ac2ea7,0x35d4370a,0xb493b294,0xaea7b0ac,0x336b3209,0x32943493,0xb70ab5d4,
  0xa54dabf6,0x3523346a,0x294d2fef,0xb8a8b81a,0xb378b456,0x2ac82484,0x3715380a,0xaec3a884,0xb120b24a,0x2ff22da9,0x34ff360e,0xb3d3b19e,
  0xada9aff2,0x324a3120,0x319e33d3,0xb60eb4ff,0xa484aac8,0x34563378,0x28842ec3,0xb80ab715,0xb223b31c,0x29992376,0x35eb36c6,0xad97a776,
  0xb039b12d,0x2e8d2cac,0x3426350b,0xb27cb0a6,0xacacae8d,0x312d3039,0x30a6327c,0xb50bb426,0xa376a999,0x331c3223,0x27762d97,0xb6c6b5eb,
  0xb0d2b194,0x286b21e4,0x34b7356a,0xac6aa5e4,0xaea7b012,0x2d2a2b5f,0x32943402,0xb122af59,0xab5fad2a,0x30122ea7,0x2f593122,0xb402b294,
  0xa1e4a86b,0x319430d2,0x25e42c6a,0xb56ab4b7,0xaf0cb012,0x267b2052,0x32f73402,0xaa7aa452,0xacdeadf5,0x2b912967,0x30d731e8,0xaf8bad65,
  0xa967ab91,0x2df52cde,0x2d652f8b,0xb1e8b0d7,0xa052a67b,0x30122f0c,0x24522a7a,0xb402b2f7,0xac79ad2a,0x24201d7f,0x30743122,0xa81fa17f,
  0xaa31ab91,0x28d026e0,0x2e2d2f8b,0xacceaade,0xa6e0a8d0,0x2b912a31,0x2ade2cce,0xaf8bae2d,0x9d7fa420,0x2d2a2c79,0x217f281f,0xb122b074,
  0xa7a9a86b,0x1f1218b6,0x2ba72c6a,0xa3119cb6,0xa54da67b,0x242021e4,0x294d2a7a,0xa81fa5e4,0xa1e4a420,0x267b254d,0x25e4281f,0xaa7aa94d,
  0x98b69f12,0x286b27a9,0x1cb62311,0xac6aaba7,0x211b21e4,0x98b69248,0xa51ba5e4,0x1cb61648,0x1f122052,0x9d7f9bdb,0xa311a452,0x217f1fdb,
  0x1bdb1d7f,0xa0529f12,0x9fdba17f,0x24522311,0x124818b6,0xa1e4a11b,0x96489cb6,0x25e4251b,0x2a632b5f,0xa1e49bdb,0xae5faf59,0x25e41fdb,
  0x286b2967,0xa6e0a4e9,0xac6aad65,0x2ade28e8,0x24e926e0,0xa967a86b,0xa8e8aade,0x2d652c6a,0x1bdb21e4,0xab5faa63,0x9fdba5e4,0x2f592e5f,
  0x2dc22ea7,0xa54d9f12,0xb1b6b294,0x294d2311,0x2bf62cde,0xaa31a86b,0xafefb0d7,0x2e2d2c6a,0x286b2a31,0xacdeabf6,0xac6aae2d,0x30d72fef,
  0x1f12254d,0xaea7adc2,0xa311a94d,0x329431b6,0x302c30d2,0xa7a9a11b,0xb41ab4b7,0x2ba7251b,0x2dc22f0c,0xac79aa63,0xb1b6b2f7,0x30742e5f,
  0x2a632c79,0xaf0cadc2,0xae5fb074,0x32f731b6,0x211b27a9,0xb0d2b02c,0xa51baba7,0x34b7341a,0x317a3257,0xa902a2ad,0xb552b61a,0x2d0026ad,
  0x2f8c309f,0xaddcac2e,0xb371b487,0x31cf3029,0x2c2e2ddc,0xb09faf8c,0xb029b1cf,0x34873371,0x22ad2902,0xb257b17a,0xa6adad00,0x361a3552,
  0x32cd33e3,0xaa31a420,0xb682b76f,0x2e2d281f,0x30ac31bb,0xaf3fad2a,0xb493b58d,0x33283122,0x2d2a2f3f,0xb1bbb0ac,0xb122b328,0x358d3493,
  0x24202a31,0xb3e3b2cd,0xa81fae2d,0x376f3682,0x341334bc,0xab5fa4e9,0xb7a6b85a,0x2f5928e8,0x319432da,0xb052ae28,0xb56ab68d,0x343e3219,
  0x2e283052,0xb2dab194,0xb219b43e,0x368d356a,0x24e92b5f,0xb4bcb413,0xa8e8af59,0x385a37a6,0x34c3358c,0xac47a5b2,0xb85fb8f3,0x304229b1,
  0x327e33fd,0xb106af26,0xb63cb785,0x34e7330f,0x2f263106,0xb3fdb27e,0xb30fb4e7,0x3785363c,0x25b22c47,0xb58cb4c3,0xa9b1b042,0x38f3385f,
  0x35773662,0xacdea67b,0xb8e5b982,0x30d72a7a,0x336b3493,0xb1bbb012,0xb70ab83a,0x358d3402,0x301231bb,0xb493b36b,0xb402b58d,0x383a370a,
  0x267b2cde,0xb662b577,0xaa7ab0d7,0x398238e5,0x36303741,0xad76a744,0xb962ba04,0x316c2b43,0x342e352a,0xb271b092,0xb7d2b8ad,0x3631347b,
  0x30923271,0xb52ab42e,0xb47bb631,0x38ad37d2,0x27442d76,0xb741b630,0xab43b16c,0x3a043962,0x36ee3815,0xae0ea807,0xb9d6ba7a,0x32012c06,
  0x34a735c4,0xb329b113,0xb84ab91b,0x36d234f3,0x31133329,0xb5c4b4a7,0xb4f3b6d2,0x391b384a,0x28072e0e,0xb815b6ee,0xac06b201,0x3a7a39d6,
  0x37b4388e,0xaea7a86b,0xba41bae1,0x32942c6a,0x35233662,0xb3e3b194,0xb8a8b982,0x376f356a,0x319433e3,0xb662b523,0xb56ab76f,0x398238a8,
  0x286b2ea7,0xb88eb7b4,0xac6ab294,0x3ae13a41,0x3841390f,0xaf3fa8d0,0xbaa2bb3a,0x33282cce,0x35a13705,0xb44fb216,0xb902b9e3,0x380535df,
  0x3216344f,0xb705b5a1,0xb5dfb805,0x39e33902,0x28d02f3f,0xb90fb841,0xacceb328,0x3b3a3aa2,0x38ac3997,0xafd8a935,0xbaf7bb83,0x33ba2d33,
  0x362137ac,0xb4aeb298,0xb958ba3d,0x38503654,0x329834ae,0xb7acb621,0xb654b850,0x3a3d3958,0x29352fd8,0xb997b8ac,0xad33b3ba,0x3b833af7,
  0x391c3a28,0xb039a999,0xbb42bbbc,0x34262d97,0x36a4382d,0xb50eb31c,0xb9aaba90,0x389936c6,0x331c350e,0xb82db6a4,0xb6c6b899,0x3a9039aa,
  0x29993039,0xba28b91c,0xad97b426,0x3bbc3b42,0x39923ac3,0xb085a9fe,0xbb81bbe3,0x346f2dfb,0x372a3886,0xb570b3a0,0xb9f8badb,0x38e03737,
  0x33a03570,0xb886b72a,0xb737b8e0,0x3adb39f8,0x29fe3085,0xbac3b992,0xadfbb46f,0x3be33b81,
};

#define PROF(slot) do {} while (0)
#define PROF_DUMP() do {} while (0)
#define PROFA(slot, dep) do {} while (0)
#define PROF3(slot) do {} while (0)
#define PROF2(slot) do {} while (0)

__device__ __forceinline__ uint32_t smem_u32(const void* p) { return (uint32_t)__cvta_generic_to_shared(p); }

__device__ __forceinline__ void mbar_init(uint32_t a, uint32_t c) {
  asm volatile("mbarrier.init.shared::cta.b64 [%0], %1;\n" ::"r"(a), "r"(c) : "memory");
}
__device__ __forceinline__ void mbar_expect_tx(uint32_t a, uint32_t bytes) {
  asm volatile("mbarrier.arrive.expect_tx.shared::cta.b64 _, [%0], %1;\n" ::"r"(a), "r"(bytes) : "memory");
}
__device__ __forceinline__ void mbar_arrive_cluster(uint32_t cluster_addr) {
  asm volatile("mbarrier.arrive.shared::cluster.b64 _, [%0];\n" ::"r"(cluster_addr) : "memory");
}
__device__ __forceinline__ void mbar_arrive_cluster_n(uint32_t cluster_addr, uint32_t n) {
  asm volatile("mbarrier.arrive.shared::cluster.b64 _, [%0], %1;\n" ::"r"(cluster_addr), "r"(n) : "memory");
}
__device__ __forceinline__ bool mbar_try(uint32_t a, uint32_t parity) {
  uint32_t ok;
  asm volatile("{\n.reg .pred p;\nmbarrier.try_wait.parity.shared::cta.b64 p, [%1], %2;\nselp.u32 %0, 1, 0, p;\n}\n"
               : "=r"(ok) : "r"(a), "r"(parity) : "memory");
  return ok;
}
__device__ __forceinline__ void mbar_wait(uint32_t a, uint32_t parity) {
  if (mbar_try(a, parity)) return;
#pragma unroll 1
  for (int n = 0; n < SPIN_LIMIT; n++)
    if (mbar_try(a, parity)) break;
}
__device__ __forceinline__ bool elect_one() {
  uint32_t p;
  asm volatile("{\n.reg .pred P;\nelect.sync _|P, 0xffffffff;\nselp.u32 %0, 1, 0, P;\n}\n" : "=r"(p));
  return p;
}
__device__ __forceinline__ uint32_t mapa(uint32_t a, uint32_t rank) {
  uint32_t r;
  asm volatile("mapa.shared::cluster.u32 %0, %1, %2;\n" : "=r"(r) : "r"(a), "r"(rank));
  return r;
}
__device__ __forceinline__ void nb_sync(int id, int n) { asm volatile("bar.sync %0, %1;\n" ::"r"(id), "r"(n) : "memory"); }
__device__ __forceinline__ void nb_arrive(int id, int n) { asm volatile("bar.arrive %0, %1;\n" ::"r"(id), "r"(n) : "memory"); }
__device__ __forceinline__ void cluster_sync_all() {
  asm volatile("barrier.cluster.arrive.relaxed.aligned;\nbarrier.cluster.wait.aligned;\n" ::: "memory");
}
__device__ __forceinline__ void fence_async_smem() { asm volatile("fence.proxy.async.shared::cta;\n" ::: "memory"); }
__device__ __forceinline__ void fence_async_all() { asm volatile("fence.proxy.async.global;\n" ::: "memory"); }

__device__ __forceinline__ void tma_load_3d(uint32_t dst, const CUtensorMap* tm, uint32_t bar, int c0, int c1, int c2) {
  asm volatile(
      "cp.async.bulk.tensor.3d.shared::cluster.global.mbarrier::complete_tx::bytes [%0], [%1, {%3, %4, %5}], [%2];\n"
      ::"r"(dst), "l"(tm), "r"(bar), "r"(c0), "r"(c1), "r"(c2) : "memory");
}
__device__ __forceinline__ void tma_load_4d(uint32_t dst, const CUtensorMap* tm, uint32_t bar, int c0, int c1, int c2, int c3) {
  asm volatile(
      "cp.async.bulk.tensor.4d.shared::cluster.global.mbarrier::complete_tx::bytes [%0], [%1, {%3, %4, %5, %6}], [%2];\n"
      ::"r"(dst), "l"(tm), "r"(bar), "r"(c0), "r"(c1), "r"(c2), "r"(c3) : "memory");
}
__device__ __forceinline__ void tma_load_3d_mc(uint32_t dst, const CUtensorMap* tm, uint32_t bar, int c0, int c1, int c2) {
  asm volatile(
      "cp.async.bulk.tensor.3d.shared::cluster.global.mbarrier::complete_tx::bytes.multicast::cluster [%0], [%1, {%3, %4, %5}], [%2], %6;\n"
      ::"r"(dst), "l"(tm), "r"(bar), "r"(c0), "r"(c1), "r"(c2), "h"((uint16_t)3) : "memory");
}
__device__ __forceinline__ void bulk_load(uint32_t dst, const void* src, uint32_t bytes, uint32_t bar) {
  asm volatile("cp.async.bulk.shared::cluster.global.mbarrier::complete_tx::bytes [%0], [%1], %2, [%3];\n"
               ::"r"(dst), "l"(src), "r"(bytes), "r"(bar) : "memory");
}
__device__ __forceinline__ void tma_store_3d(const CUtensorMap* tm, uint32_t src, int c0, int c1, int c2) {
  asm volatile("cp.async.bulk.tensor.3d.global.shared::cta.bulk_group [%0, {%2, %3, %4}], [%1];\n"
               ::"l"(tm), "r"(src), "r"(c0), "r"(c1), "r"(c2) : "memory");
}
__device__ __forceinline__ void bulk_commit() { asm volatile("cp.async.bulk.commit_group;\n" ::: "memory"); }
__device__ __forceinline__ void bulk_wait0() { asm volatile("cp.async.bulk.wait_group 0;\n" ::: "memory"); }
__device__ __forceinline__ void prefetch_tmap(const CUtensorMap* tm) {
  asm volatile("prefetch.tensormap [%0];\n" ::"l"(tm) : "memory");
}

__device__ __forceinline__ void wg_fence() { asm volatile("wgmma.fence.sync.aligned;\n" ::: "memory"); }
__device__ __forceinline__ void wg_commit() { asm volatile("wgmma.commit_group.sync.aligned;\n" ::: "memory"); }
template <int N> __device__ __forceinline__ void wg_wait() {
  asm volatile("wgmma.wait_group.sync.aligned %0;\n" ::"n"(N) : "memory");
}
__device__ __forceinline__ uint64_t mkdesc(uint32_t addr, uint32_t lbo, uint32_t sbo, uint32_t swz) {
  return (uint64_t)((addr & 0x3FFFF) >> 4) | ((uint64_t)(lbo >> 4) << 16) | ((uint64_t)(sbo >> 4) << 32) |
         ((uint64_t)swz << 62);
}

#define R4(d, o) "+f"(d[o + 0]), "+f"(d[o + 1]), "+f"(d[o + 2]), "+f"(d[o + 3])
#define R8(d, o) R4(d, o), R4(d, o + 4)
#define R16(d, o) R8(d, o), R8(d, o + 8)
#define R32(d, o) R16(d, o), R16(d, o + 16)
#define R64(d, o) R32(d, o), R32(d, o + 32)

__device__ __forceinline__ void wgmma_n192(float (&d)[96], uint64_t da, uint64_t db, uint32_t acc) {
  asm volatile(
      "{\n.reg .pred p;\nsetp.ne.u32 p, %98, 0;\n"
      "wgmma.mma_async.sync.aligned.m64n192k16.f32.bf16.bf16 "
      "{%0,%1,%2,%3,%4,%5,%6,%7,%8,%9,%10,%11,%12,%13,%14,%15,%16,%17,%18,%19,%20,%21,%22,%23,%24,%25,%26,%27,%28,%29,%30,%31,"
      "%32,%33,%34,%35,%36,%37,%38,%39,%40,%41,%42,%43,%44,%45,%46,%47,%48,%49,%50,%51,%52,%53,%54,%55,%56,%57,%58,%59,%60,%61,%62,%63,"
      "%64,%65,%66,%67,%68,%69,%70,%71,%72,%73,%74,%75,%76,%77,%78,%79,%80,%81,%82,%83,%84,%85,%86,%87,%88,%89,%90,%91,%92,%93,%94,%95}, "
      "%96, %97, p, 1, 1, 0, 1;\n}\n"
      : R64(d, 0), R32(d, 64)
      : "l"(da), "l"(db), "r"(acc));
}
__device__ __forceinline__ void wgmma_n128(float (&d)[64], uint64_t da, uint64_t db, uint32_t acc) {
  asm volatile(
      "{\n.reg .pred p;\nsetp.ne.u32 p, %66, 0;\n"
      "wgmma.mma_async.sync.aligned.m64n128k16.f32.bf16.bf16 "
      "{%0,%1,%2,%3,%4,%5,%6,%7,%8,%9,%10,%11,%12,%13,%14,%15,%16,%17,%18,%19,%20,%21,%22,%23,%24,%25,%26,%27,%28,%29,%30,%31,"
      "%32,%33,%34,%35,%36,%37,%38,%39,%40,%41,%42,%43,%44,%45,%46,%47,%48,%49,%50,%51,%52,%53,%54,%55,%56,%57,%58,%59,%60,%61,%62,%63}, "
      "%64, %65, p, 1, 1, 0, 1;\n}\n"
      : R64(d, 0)
      : "l"(da), "l"(db), "r"(acc));
}
#define WG128(C, ACC)                                                                                                      \
  asm volatile(                                                                                                            \
      "{\n.reg .b64 a, b;\nmov.b64 a, {%64, %66};\nmov.b64 b, {%65, %66};\n"                                               \
      "wgmma.mma_async.sync.aligned.m64n128k16.f32.bf16.bf16 "                                                             \
      "{%0,%1,%2,%3,%4,%5,%6,%7,%8,%9,%10,%11,%12,%13,%14,%15,%16,%17,%18,%19,%20,%21,%22,%23,%24,%25,%26,%27,%28,%29,%30,%31," \
      "%32,%33,%34,%35,%36,%37,%38,%39,%40,%41,%42,%43,%44,%45,%46,%47,%48,%49,%50,%51,%52,%53,%54,%55,%56,%57,%58,%59,%60,%61," \
      "%62,%63}, a, b, " ACC ", 1, 1, 0, 1;\n}\n"                                                                          \
      : Z16(C, d, 0), Z16(C, d, 16), Z16(C, d, 32), Z16(C, d, 48)                                                          \
      : "r"(da), "r"(db), "r"(0x40000040))
#define Z4(C, d, o) C(d[o + 0]), C(d[o + 1]), C(d[o + 2]), C(d[o + 3])
#define Z16(C, d, o) Z4(C, d, o), Z4(C, d, o + 4), Z4(C, d, o + 8), Z4(C, d, o + 12)
__device__ __forceinline__ void wgmma_n128z(float (&d)[64], uint32_t da, uint32_t db) { WG128("=f", "0"); }
__device__ __forceinline__ void wgmma_n128a(float (&d)[64], uint32_t da, uint32_t db) { WG128("+f", "1"); }
template <int N> __device__ __forceinline__ void fence_regs(float (&d)[N]) {
#pragma unroll
  for (int i = 0; i < N; i++) asm volatile("" : "+f"(d[i])::"memory");
}

__device__ __forceinline__ void mma16816(float (&d)[4], uint32_t a0, uint32_t a1, uint32_t a2, uint32_t a3, uint32_t b0,
                                         uint32_t b1) {
  asm("mma.sync.aligned.m16n8k16.row.col.f32.bf16.bf16.f32 {%0,%1,%2,%3}, {%4,%5,%6,%7}, {%8,%9}, {%0,%1,%2,%3};\n"
      : "+f"(d[0]), "+f"(d[1]), "+f"(d[2]), "+f"(d[3])
      : "r"(a0), "r"(a1), "r"(a2), "r"(a3), "r"(b0), "r"(b1));
}
__device__ __forceinline__ void mma16816_z(float (&d)[4], uint32_t a0, uint32_t a1, uint32_t a2, uint32_t a3, uint32_t b0,
                                           uint32_t b1) {
  asm("mma.sync.aligned.m16n8k16.row.col.f32.bf16.bf16.f32 {%0,%1,%2,%3}, {%4,%5,%6,%7}, {%8,%9}, {%10,%10,%10,%10};\n"
      : "=f"(d[0]), "=f"(d[1]), "=f"(d[2]), "=f"(d[3])
      : "r"(a0), "r"(a1), "r"(a2), "r"(a3), "r"(b0), "r"(b1), "f"(0.f));
}
__device__ __forceinline__ void ldsm4t(uint32_t (&r)[4], uint32_t a) {
  asm volatile("ldmatrix.sync.aligned.m8n8.x4.trans.shared.b16 {%0,%1,%2,%3}, [%4];\n"
               : "=r"(r[0]), "=r"(r[1]), "=r"(r[2]), "=r"(r[3]) : "r"(a) : "memory");
}
__device__ __forceinline__ void ldsm2t(uint32_t& r0, uint32_t& r1, uint32_t a) {
  asm volatile("ldmatrix.sync.aligned.m8n8.x2.trans.shared.b16 {%0,%1}, [%2];\n" : "=r"(r0), "=r"(r1) : "r"(a) : "memory");
}
__device__ __forceinline__ void st_async128(uint32_t a, uint32_t bar, uint32_t x, uint32_t y, uint32_t z, uint32_t w) {
  asm volatile("st.async.weak.shared::cluster.mbarrier::complete_tx::bytes.v4.b32 [%0], {%2,%3,%4,%5}, [%1];\n"
               ::"r"(a), "r"(bar), "r"(x), "r"(y), "r"(z), "r"(w) : "memory");
}
__device__ __forceinline__ void mbar_arrive(uint32_t a) {
  asm volatile("mbarrier.arrive.shared::cta.b64 _, [%0];\n" ::"r"(a) : "memory");
}
__device__ __forceinline__ void stsm4(uint32_t a, uint32_t r0, uint32_t r1, uint32_t r2, uint32_t r3) {
  asm volatile("stmatrix.sync.aligned.m8n8.x4.shared.b16 [%0], {%1,%2,%3,%4};\n"
               ::"r"(a), "r"(r0), "r"(r1), "r"(r2), "r"(r3) : "memory");
}
__device__ __forceinline__ void stsm4t(uint32_t a, uint32_t r0, uint32_t r1, uint32_t r2, uint32_t r3) {
  asm volatile("stmatrix.sync.aligned.m8n8.x4.trans.shared.b16 [%0], {%1,%2,%3,%4};\n"
               ::"r"(a), "r"(r0), "r"(r1), "r"(r2), "r"(r3) : "memory");
}
__device__ __forceinline__ uint2 lds64(uint32_t a) {
  uint2 v;
  asm volatile("ld.shared.v2.u32 {%0,%1}, [%2];\n" : "=r"(v.x), "=r"(v.y) : "r"(a));
  return v;
}
__device__ __forceinline__ uint4 lds128(uint32_t a) {
  uint4 v;
  asm volatile("ld.shared.v4.u32 {%0,%1,%2,%3}, [%4];\n" : "=r"(v.x), "=r"(v.y), "=r"(v.z), "=r"(v.w) : "r"(a) : "memory");
  return v;
}
__device__ __forceinline__ void sts128(uint32_t a, uint32_t x, uint32_t y, uint32_t z, uint32_t w) {
  asm volatile("st.shared.v4.u32 [%0], {%1,%2,%3,%4};\n" ::"r"(a), "r"(x), "r"(y), "r"(z), "r"(w) : "memory");
}
__device__ __forceinline__ void sts64(uint32_t a, uint32_t x, uint32_t y) {
  asm volatile("st.shared.v2.u32 [%0], {%1,%2};\n" ::"r"(a), "r"(x), "r"(y) : "memory");
}
__device__ __forceinline__ uint32_t pack_bf16(float lo, float hi) {
  uint32_t r;
  asm("cvt.rn.bf16x2.f32 %0, %1, %2;\n" : "=r"(r) : "f"(hi), "f"(lo));
  return r;
}
__device__ __forceinline__ uint32_t bmul2(uint32_t a, uint32_t b) {
  uint32_t r;
  asm("mul.rn.bf16x2 %0, %1, %2;\n" : "=r"(r) : "r"(a), "r"(b));
  return r;
}
__device__ __forceinline__ uint32_t bmax2(uint32_t a, uint32_t b) {
  uint32_t r;
  asm("max.bf16x2 %0, %1, %2;\n" : "=r"(r) : "r"(a), "r"(b));
  return r;
}
__device__ __forceinline__ uint32_t bfma2(uint32_t a, uint32_t b, uint32_t c) {
  uint32_t r;
  asm("fma.rn.bf16x2 %0, %1, %2, %3;\n" : "=r"(r) : "r"(a), "r"(b), "r"(c));
  return r;
}
__device__ __forceinline__ uint32_t badd2(uint32_t a, uint32_t b) {
  uint32_t r;
  asm("add.rn.bf16x2 %0, %1, %2;\n" : "=r"(r) : "r"(a), "r"(b));
  return r;
}
__device__ __forceinline__ void prefetch_l2(const void* p) { asm volatile("prefetch.global.L2 [%0];\n" ::"l"(p)); }
__device__ __forceinline__ void cp_async16n(uint32_t dst, const void* src) {
  asm volatile("cp.async.cg.shared.global [%0], [%1], 16;\n" ::"r"(dst), "l"(src) : "memory");
}
__device__ __forceinline__ void cp_async16(uint32_t dst, const void* src, uint32_t srcbytes) {
  asm volatile("cp.async.cg.shared.global.L2::256B [%0], [%1], 16, %2;\n" ::"r"(dst), "l"(src), "r"(srcbytes) : "memory");
}
__device__ __forceinline__ uint32_t ld_acquire(const uint32_t* p) {
  uint32_t v;
  asm volatile("ld.acquire.gpu.global.u32 %0, [%1];\n" : "=r"(v) : "l"(p) : "memory");
  return v;
}
__device__ __forceinline__ uint32_t ld_relaxed(const uint32_t* p) {
  uint32_t v;
  asm volatile("ld.relaxed.gpu.global.u32 %0, [%1];\n" : "=r"(v) : "l"(p) : "memory");
  return v;
}
__device__ __forceinline__ void st_release(uint32_t* p, uint32_t v) {
  asm volatile("st.release.gpu.global.u32 [%0], %1;\n" ::"l"(p), "r"(v) : "memory");
}
__device__ __forceinline__ void wait_flag(const uint32_t* p, uint32_t want) {
  int n = 0;
  while (ld_acquire(p) != want && ++n < SPIN_LIMIT) {}
}

struct Params {
  const __nv_bfloat16* x;
  const __nv_bfloat16* w;
  const __nv_bfloat16* q;
  const __nv_bfloat16* k;
  const __nv_bfloat16* v;
  const __nv_bfloat16* shift_k;
  const __nv_bfloat16* ssm_k;
  const __nv_bfloat16* ssm_D;
  const __nv_bfloat16* wo;
  __nv_bfloat16* out;
  uint32_t zero;
};

__device__ __forceinline__ uint32_t lds32(uint32_t a) {
  uint32_t v;
  asm volatile("ld.shared.u32 %0, [%1];\n" : "=r"(v) : "r"(a));
  return v;
}
__device__ __forceinline__ float bf_lo(uint32_t v) {
  uint32_t r;
  asm("prmt.b32 %0, %1, 0, 0x1044;\n" : "=r"(r) : "r"(v));
  return __uint_as_float(r);
}
__device__ __forceinline__ float bf_hi(uint32_t v) { return __uint_as_float(v & 0xffff0000u); }
__device__ __forceinline__ float ex2(float x) {
  float r;
  asm("ex2.approx.ftz.f32 %0, %1;\n" : "=f"(r) : "f"(x));
  return r;
}
__device__ __forceinline__ float rcp(float x) {
  float r;
  asm("rcp.approx.ftz.f32 %0, %1;\n" : "=f"(r) : "f"(x));
  return r;
}

#define Q4(c, d, o) c(d[o + 0]), c(d[o + 1]), c(d[o + 2]), c(d[o + 3])
#define Q8(c, d, o) Q4(c, d, o), Q4(c, d, o + 4)
#define Q16(c, d, o) Q8(c, d, o), Q8(c, d, o + 8)
#define Q32(c, d) Q16(c, d, 0), Q16(c, d, 16)
#define L8 "{%0,%1,%2,%3,%4,%5,%6,%7}"
#define L16 "{%0,%1,%2,%3,%4,%5,%6,%7,%8,%9,%10,%11,%12,%13,%14,%15}"
#define L32 "{%0,%1,%2,%3,%4,%5,%6,%7,%8,%9,%10,%11,%12,%13,%14,%15,%16,%17,%18,%19,%20,%21,%22,%23,%24,%25,%26,%27,%28,%29,%30,%31}"
__device__ __forceinline__ void fft_rows(uint32_t (&d)[32], const uint32_t (&a)[2][4], uint64_t db) {
  asm volatile("wgmma.mma_async.sync.aligned.m64n128k16.f16.f16.f16 " L32 ", {%32,%33,%34,%35}, %36, 0, 1, 1, 1;\n"
               : Q32("=r", d) : "r"(a[0][0]), "r"(a[0][1]), "r"(a[0][2]), "r"(a[0][3]), "l"(db));
  asm volatile("wgmma.mma_async.sync.aligned.m64n128k16.f16.f16.f16 " L32 ", {%32,%33,%34,%35}, %36, 1, 1, 1, 1;\n"
               : Q32("+r", d) : "r"(a[1][0]), "r"(a[1][1]), "r"(a[1][2]), "r"(a[1][3]), "l"(db + 64));
}
template <int INV> __device__ __forceinline__ void fft_cols(uint32_t (&d)[8], const uint32_t (&a)[2][4], uint64_t db) {
  asm volatile("wgmma.mma_async.sync.aligned.m64n32k16.f16.f16.f16 " L8 ", {%8,%9,%10,%11}, %12, 0, 1, 1, %13;\n"
               : Q8("=r", d, 0) : "r"(a[0][0]), "r"(a[0][1]), "r"(a[0][2]), "r"(a[0][3]), "l"(db), "n"(INV));
  asm volatile("wgmma.mma_async.sync.aligned.m64n32k16.f16.f16.f16 " L8 ", {%8,%9,%10,%11}, %12, 1, 1, 1, %13;\n"
               : Q8("+r", d, 0) : "r"(a[1][0]), "r"(a[1][1]), "r"(a[1][2]), "r"(a[1][3]), "l"(db + (INV ? 16 : 64)), "n"(INV));
}
__device__ __forceinline__ void fft_back(float (&d)[16], uint64_t da, uint64_t db) {
  asm volatile("wgmma.mma_async.sync.aligned.m64n32k16.f32.f16.f16 " L16 ", %16, %17, 0, 1, 1, 1, 1;\n"
               : Q16("=f", d, 0) : "l"(da), "l"(db));
#pragma unroll
  for (int i = 1; i < 4; i++)
    asm volatile("wgmma.mma_async.sync.aligned.m64n32k16.f32.f16.f16 " L16 ", %16, %17, 1, 1, 1, 1, 1;\n"
                 : Q16("+f", d, 0) : "l"(da + 32 * i), "l"(db + 64 * i));
}
__device__ __forceinline__ uint32_t hmul2(uint32_t a, uint32_t b) {
  uint32_t r;
  asm("mul.rn.f16x2 %0, %1, %2;\n" : "=r"(r) : "r"(a), "r"(b));
  return r;
}
__device__ __forceinline__ uint32_t hadd2(uint32_t a, uint32_t b) {
  uint32_t r;
  asm("add.rn.f16x2 %0, %1, %2;\n" : "=r"(r) : "r"(a), "r"(b));
  return r;
}
__device__ __forceinline__ uint32_t hneg2(uint32_t a) {
  uint32_t r;
  asm("neg.f16x2 %0, %1;\n" : "=r"(r) : "r"(a));
  return r;
}
__device__ __forceinline__ uint32_t hfma2(uint32_t a, uint32_t b, uint32_t c) {
  uint32_t r;
  asm("fma.rn.f16x2 %0, %1, %2, %3;\n" : "=r"(r) : "r"(a), "r"(b), "r"(c));
  return r;
}
__device__ __forceinline__ uint32_t pack_f16(float lo, float hi) {
  uint32_t r;
  asm("cvt.rn.f16x2.f32 %0, %1, %2;\n" : "=r"(r) : "f"(hi), "f"(lo));
  return r;
}
__device__ __forceinline__ uint32_t bmaxabs2(uint32_t a, uint32_t b) {
  uint32_t r;
  asm("max.xorsign.abs.bf16x2 %0, %1, %2;\n" : "=r"(r) : "r"(a), "r"(b));
  return r;
}
struct C2 { uint32_t r, i; };
__device__ __forceinline__ C2 cmul(C2 a, C2 b) {
  return C2{hfma2(a.r, b.r, hneg2(hmul2(a.i, b.i))), hfma2(a.r, b.i, hmul2(a.i, b.r))};
}
__device__ __forceinline__ C2 cfma(C2 a, C2 b, C2 c) {
  return C2{hfma2(a.r, b.r, hfma2(hneg2(a.i), b.i, c.r)), hfma2(a.r, b.i, hfma2(a.i, b.r, c.i))};
}
__device__ __forceinline__ C2 crot(C2 z, C2 t) {
  const uint32_t r = hfma2(t.r, z.i, z.r), i = hfma2(t.i, r, z.i);
  return C2{hfma2(t.r, i, r), i};
}
__device__ __forceinline__ C2 cget(const uint32_t (&e)[8], int j, int b) { return C2{e[4 * j + b], e[4 * j + 2 + b]}; }
template <int N> __device__ __forceinline__ void fence_regs(uint32_t (&d)[N]) {
#pragma unroll
  for (int i = 0; i < N; i++) asm volatile("" : "+r"(d[i])::"memory");
}
__device__ __forceinline__ void ldsm4(uint32_t (&r)[4], uint32_t a) {
  asm volatile("ldmatrix.sync.aligned.m8n8.x4.shared.b16 {%0,%1,%2,%3}, [%4];\n"
               : "=r"(r[0]), "=r"(r[1]), "=r"(r[2]), "=r"(r[3]) : "r"(a) : "memory");
}

__device__ __forceinline__ uint32_t movm(uint32_t a) {
  uint32_t r;
  asm volatile("movmatrix.sync.aligned.m8n8.trans.b16 %0, %1;\n" : "=r"(r) : "r"(a));
  return r;
}
template <int C0, int H, bool T> __device__ __forceinline__ void attn_pack(const float (&acc)[96], uint32_t (&d)[8]) {
#pragma unroll
  for (int c = 0; c < 8; c++) {
    asm volatile("cvt.rn.bf16x2.f32 %0, %1, %2;\n" : "=r"(d[c]) : "f"(acc[4 * (C0 + c) + 2 * H + 1]), "f"(acc[4 * (C0 + c) + 2 * H]));
    if (T) d[c] = movm(d[c]);
  }
}
__device__ __forceinline__ void attn_qk(float (&s)[4], const uint32_t (&qlo)[8], const uint32_t (&qhi)[8],
                                        const uint32_t (&k)[8], int c) {
  mma16816_z(s, qlo[c], qhi[c], qlo[c + 1], qhi[c + 1], k[c], k[c + 1]);
  mma16816(s, qlo[c + 2], qhi[c + 2], qlo[c + 3], qhi[c + 3], k[c + 2], k[c + 3]);
}
template <int N> __device__ __forceinline__ void quad_softmax(float (&x)[N][2], uint32_t (&pp)[N]) {
  const float c2 = 1.4426950408889634f;
  uint32_t q[N], mx[N / 2];
#pragma unroll
  for (int n = 0; n < N; n++) {
    const uint32_t r = pack_bf16(x[n][0], x[n][1]);
    q[n] = bfma2(r, 0x3e353e35u, bmul2(r, 0x379e379eu));
    x[n][0] = bf_lo(q[n]);
    x[n][1] = bf_hi(q[n]);
  }
#pragma unroll
  for (int n = 0; n < N / 2; n++)
    mx[n] = bmax2(__byte_perm(q[2 * n], q[2 * n + 1], 0x5410), __byte_perm(q[2 * n], q[2 * n + 1], 0x7632));
#pragma unroll
  for (int o = 1; o <= 2; o++) {
#pragma unroll
    for (int n = 0; n < N / 2; n++) mx[n] = bmax2(mx[n], __shfl_xor_sync(0xffffffffu, mx[n], o));
  }
  float m[N], t[N];
#pragma unroll
  for (int n = 0; n < N / 2; n++) {
    m[2 * n] = bf_lo(mx[n]);
    m[2 * n + 1] = bf_hi(mx[n]);
  }
#pragma unroll
  for (int n = 0; n < N; n++) {
    const float nm = -m[n] * c2;
    x[n][0] = ex2(fmaf(x[n][0], c2, nm));
    x[n][1] = ex2(fmaf(x[n][1], c2, nm));
  }
#pragma unroll
  for (int n = 0; n < N; n += 2) {
    float u0, u1;
    asm("mma.sync.aligned.m16n8k8.row.col.f32.tf32.tf32.f32 {%0,%1,%2,%3}, {%4,%5,%6,%7}, {%8,%8}, {%9,%9,%9,%9};\n"
        : "=f"(t[n]), "=f"(u0), "=f"(t[n + 1]), "=f"(u1)
        : "r"(__float_as_uint(x[n][0])), "r"(__float_as_uint(x[n + 1][0])), "r"(__float_as_uint(x[n][1])),
          "r"(__float_as_uint(x[n + 1][1])), "r"(0x3f800000u), "f"(0.f));
  }
#pragma unroll
  for (int n = 0; n < N; n++) {
    const float inv = rcp(t[n]);
    pp[n] = pack_bf16(x[n][0] * inv, x[n][1] * inv);
  }
}
__device__ __forceinline__ void attn_pv(uint32_t dst, const uint32_t (&vp)[8], const uint32_t (&vo)[8], int c, uint32_t pp,
                                        uint32_t maskLE) {
  const uint32_t b0 = pp & ~maskLE, b1 = pp & maskLE;
  float oa[4], ob[4];
  mma16816_z(oa, vp[c], vp[c + 1], vo[c], vo[c + 1], b0, b1);
  mma16816_z(ob, vp[c + 2], vp[c + 3], vo[c + 2], vo[c + 3], b0, b1);
  stsm4t(dst, pack_bf16(oa[0], oa[1]), pack_bf16(oa[2], oa[3]), pack_bf16(ob[0], ob[1]), pack_bf16(ob[2], ob[3]));
}

template <int MODE>
__global__ void __cluster_dims__(2, 1, 1) __launch_bounds__(NTHREADS, 1)
fused_kernel(const Params p, const __grid_constant__ CUtensorMap tmX, const __grid_constant__ CUtensorMap tmW,
             const __grid_constant__ CUtensorMap tmWo, const __grid_constant__ CUtensorMap tmWp,
             const __grid_constant__ CUtensorMap tmQ,
             const __grid_constant__ CUtensorMap tmOb,
             const __grid_constant__ CUtensorMap tmXh, const __grid_constant__ CUtensorMap tmWh) {
  extern __shared__ __align__(1024) uint8_t smem[];
  if (threadIdx.x < 32) {
    const uint32_t i = (blockIdx.x & 127) * 16 + (threadIdx.x & 15);
    prefetch_l2(threadIdx.x & 16 ? (const char*)p.w + i * 128 : (const char*)p.x + i * 2048);
  }
  const uint32_t sb = smem_u32(smem);
  const uint32_t bars = sb + OFF_BAR;
  const int tid = threadIdx.x, lane = tid & 31, warp = __shfl_sync(0xffffffffu, tid >> 5, 0);
  const int rank = blockIdx.x & 1;
  const bool halo_cta = blockIdx.x < 4;
  if (halo_cta && MODE != 0) return;
  int grp, mem;
  {
    const int t = (blockIdx.x >> 1) - 4, u = t - 32;
    const int q7 = (u * 37) >> 8;
    const bool lo = (unsigned)t < 32u, mid = (unsigned)u < 28u;
    grp = lo ? (t & 7) : (mid ? 1 + u - 7 * q7 : 0);
    mem = lo ? (t >> 3) : (mid ? 4 + q7 : (t < 0 ? t + 6 : t - 54));
  }
  const int rg = (grp >> 2) * 4 + (mem >> 1), hp = (grp & 3) * 4 + (mem & 1) * 2 + rank;
  const int rb2 = (grp >> 2) * 8 + mem, cb2 = (grp & 3) * 2 + rank;
  const int chb = grp * 16 + mem * 2 + rank;
  const int cta = rg * 16 + hp;
  const int hsel = rb2 & 1;
  const int par = rg >> 2, gidx = rg & 3;

  if (tid < 256 && !halo_cta && MODE != 2) {
    const int r = tid >> 3, c = tid & 7;
    const uint32_t so = r * 128 + ((c ^ (r & 7)) << 4);
    const __nv_bfloat16* wg0 = p.w + (size_t)r * (3 * DM) + hp * 64 + c * 8;
    const __nv_bfloat16* xg0 = p.x + (size_t)(2 * (gidx * 256 + r) + par) * DM + c * 8;
#pragma unroll
    for (int j = 0; j < 3; j++) cp_async16n(sb + OFF_1B + j * 4096 + so, wg0 + j * DM);
#pragma unroll
    for (int i = 0; i < 8; i++) cp_async16n(sb + i * 4096 + so, xg0 + (size_t)i * 64 * DM);
    asm volatile("cp.async.commit_group;\n" ::: "memory");
  }
  auto halo_issue = [&](int kb, int s) {
    const uint32_t fb = bars + 8 * (BAR_FULLB + s), st = sb + s * STGH;
    mbar_expect_tx(fb, STGH - 2048);
    tma_load_3d(st + 8192, &tmWh, fb, 0, kb * 64, 16 + blockIdx.x * 4);
    tma_load_3d(st + 8192 + 32768, &tmWh, fb, 0, kb * 64, 32 + blockIdx.x * 4);
    tma_load_4d(st, &tmXh, fb, kb * 64, 248, 0, 0);
  };
  if (tid == 256) {
    prefetch_tmap(halo_cta ? &tmXh : &tmX);
#pragma unroll
    for (int i = 0; i < NS1B; i++) mbar_init(bars + 8 * (BAR_FULLB + i), 1);
#pragma unroll
    for (int i = 0; i < NS1A; i++) mbar_init(bars + 8 * (BAR_FULLA + i), 1);
    asm volatile("fence.mbarrier_init.release.cluster;\n" ::: "memory");
    if (!halo_cta && MODE != 2) {
      mbar_expect_tx(bars + 8 * (BAR_FULLB + 1), STG1B);
      tma_load_3d(sb + OFF_1B + 1 * STG1B, &tmW, bars + 8 * (BAR_FULLB + 1), hp * 64, 32, 0);
      mbar_expect_tx(bars + 8 * (BAR_FULLB + 2), STG1B);
      tma_load_3d(sb + OFF_1B + 2 * STG1B, &tmW, bars + 8 * (BAR_FULLB + 2), hp * 64, 64, 0);
    } else if (halo_cta) {
      halo_issue(0, 0);
    }
  } else if (tid == 288) {
#pragma unroll
    for (int i = 0; i < NS1A; i++) mbar_init(bars + 8 * (BAR_EMPTYA + i), 4);
#pragma unroll
    for (int i = 0; i < NS1B; i++) mbar_init(bars + 8 * (BAR_EMPTYB + i), 2);
    mbar_init(bars + 8 * BAR_X, 4);
    mbar_init(bars + 8 * BAR_TAB, 16);
    mbar_init(bars + 8 * BAR_U, 1);
    mbar_init(bars + 8 * BAR_H, 1);
    mbar_init(bars + 8 * BAR_STG, 8);
    mbar_init(bars + 8 * BAR_HALO, 1);
    mbar_init(bars + 8 * BAR_Q, 1);
    mbar_init(bars + 8 * BAR_LAND, 5);
    mbar_init(bars + 8 * (BAR_LAND + 1), 5);
    asm volatile("fence.mbarrier_init.release.cluster;\n" ::: "memory");
  } else if (tid == 320) {
#pragma unroll
    for (int i = 0; i < NS2; i++) {
      mbar_init(bars + 8 * (BAR_FULL2 + i), 1);
      mbar_init(bars + 8 * (BAR_EMPTY2 + i), 2);
      mbar_init(bars + 8 * (BAR_EMPTY2B + i), 2);
    }
    asm volatile("fence.mbarrier_init.release.cluster;\n" ::: "memory");
  } else if (tid == 352) {
#pragma unroll
    for (int i = 0; i < 4; i++) mbar_init(bars + 8 * (BAR_Y + i), i < 2 ? 4 : i == 2 ? 10 : 8);
    mbar_init(bars + 8 * BAR_XFREE, 1);
    asm volatile("fence.mbarrier_init.release.cluster;\n" ::: "memory");
  }
  cluster_sync_all();
  if (warp == 8) PROF2(24);

  if (warp >= 8) {
    const int hw = warp - 8;
    const int lr = lane & 7, lm = lane >> 3;
    auto g1_issue_a = [&](int j, int s) {
      const uint32_t fb = bars + 8 * (BAR_FULLA + s);
      mbar_expect_tx(fb, STG1A);
      tma_load_3d_mc(sb + s * STG1A + rank * 16384, &tmX, fb, j * 64, par, gidx * 256 + rank * 128);
    };
    auto g1_issue_b = [&](int kb, int s) {
      const uint32_t fb = bars + 8 * (BAR_FULLB + s);
      mbar_expect_tx(fb, STG1B);
      tma_load_3d(sb + OFF_1B + s * STG1B, &tmW, fb, hp * 64, kb * 32, 0);
    };
    auto g2_k = [&](int kb) { return (kb < 2 ? hp : kb < 4 ? hp & 14 : hp & 12) ^ kb; };
    auto g2_issue_b = [&](uint32_t fb, uint32_t bytes, uint32_t dst, int k0, bool whole) {
      if (whole) {
        tma_load_3d(dst, &tmWo, fb, 0, k0, cb2 * 2);
      } else {
#pragma unroll
        for (int i = 0; i < 4; i++)
          tma_load_3d(dst + (i & 1) * XT + (i >> 1) * 4 * XT, &tmWp, fb, 0, k0 + (i >> 1) * 32, cb2 * 2 + (i & 1));
      }
      mbar_expect_tx(fb, bytes);
    };
    auto send_y = [&](uint32_t o, uint32_t step, int half) {
      const uint32_t peer = mapa(sb, rank ^ 1);
      o += OFF_X + (rank ^ 1) * 4096 + half * 2048 + lane * 16;
      uint4 a[8];
#pragma unroll
      for (int i = 0; i < 8; i++) a[i] = lds128(sb + o + (i >> 2) * step + (i & 2) * (XT / 2) + (i & 1) * 512);
#pragma unroll
      for (int i = 0; i < 8; i++)
        st_async128(peer + o + 1024 + (i >> 2) * step + (i & 2) * (XT / 2) + (i & 1) * 512,
                    peer + OFF_BAR + 8 * (BAR_LAND + half), a[i].x, a[i].y, a[i].z, a[i].w);
    };
    asm volatile("setmaxnreg.dec.sync.aligned.u32 %0;\n" :: "n"(REG_HELP));

    if (halo_cta) {
      if (hw == 0) {
        int s = 1, ph = 1;
#pragma unroll 1
        for (int kb = 1; kb < 16; kb++) {
          mbar_wait(bars + 8 * (BAR_EMPTYB + s), ph);
          if (elect_one()) halo_issue(kb, s);
          if (++s == 3) { s = 0; ph ^= 1; }
        }
      }
      __syncwarp();
    } else if (hw == 0) {
      uint32_t epoch = 0;
      if (MODE == 2) {
        if (lane < NS2) mbar_arrive_cluster_n(mapa(bars, rank) + 8 * (BAR_EMPTY2 + lane), 2);
      } else {
      if (lane == 0) {
        mbar_expect_tx(bars + 8 * BAR_U, 32768);
        mbar_expect_tx(bars + 8 * BAR_LAND, 8192);
        mbar_expect_tx(bars + 8 * (BAR_LAND + 1), 8192);
        mbar_expect_tx(bars + 8 * BAR_Q, 32768);
        prefetch_tmap(&tmQ);
      }
      {
        int sa = 1, pha = 1, sbb = 2, phb = 1;
#pragma unroll 1
        for (int kb = 2; kb < 32; kb++) {
          if (!(kb & 1)) {
            mbar_wait(bars + 8 * (BAR_EMPTYA + sa), pha);
            if (elect_one()) g1_issue_a(kb >> 1, sa);
            if (++sa == NS1A) { sa = 0; pha ^= 1; }
          }
          mbar_wait(bars + 8 * (BAR_EMPTYB + sbb), phb);
          if (kb > 2 && elect_one()) g1_issue_b(kb, sbb);
          __syncwarp();
          if (kb == 4) epoch = ld_relaxed(g_flag_o + cta);
          if (kb == 4) PROF2(27);
          if (kb == 1) PROF2(38);
          if (kb == 2) PROF2(39);
          if (++sbb == NS1B) { sbb = 0; phb ^= 1; }
        }
      }
      auto q_issue = [&](int i) {
        mbar_wait(bars + 8 * (i ? BAR_EMPTYB + 3 : BAR_EMPTYA + 1), i);
        if (elect_one())
          asm volatile(
              "cp.async.bulk.tensor.5d.shared::cluster.global.mbarrier::complete_tx::bytes [%0], [%1, {%3, %4, %4, %4, %5}], [%2];\n"
              ::"r"(sb + (i ? OFF_Q1 : OFF_Q0)), "l"(&tmQ), "r"(bars + 8 * BAR_Q), "r"((chb & ~1) * 8), "r"(0), "r"(rank * 32 + i * 64)
              : "memory");
        __syncwarp();
      };
      if (QORD < 2) q_issue(0);
      else mbar_wait(bars + 8 * (BAR_EMPTYA + 1), 0);
      if (QORD < 1) q_issue(1);
      epoch++;
      if (lane == 0) {
        prefetch_tmap(&tmWo);
        prefetch_tmap(&tmWp);
        prefetch_tmap(&tmOb);
        if (gidx != 0) wait_flag(g_flag_h + (hp >> 2), epoch);
      }
      __syncwarp();
      {
        uint4 hk0 = make_uint4(0, 0, 0, 0), hk1 = hk0, hv0 = hk0, hv1 = hk0;
        if (gidx != 0) {
          const uint4* src = g_halo + cta * 128 + lane;
          hk0 = __ldcg(src); hk1 = __ldcg(src + 32); hv0 = __ldcg(src + 64); hv1 = __ldcg(src + 96);
        }
        if (gidx != 0) PROF(18);
        sts128(sb + OFF_KH + lane * 16, hk0.x, hk0.y, hk0.z, hk0.w);
        sts128(sb + OFF_KH + 512 + lane * 16, hk1.x, hk1.y, hk1.z, hk1.w);
        sts64(sb + OFF_KH + 1024 + lane * 8, movm(hv0.x), movm(hv0.y));
        sts64(sb + OFF_KH + 1280 + lane * 8, movm(hv0.z), movm(hv0.w));
        sts64(sb + OFF_KH + 1536 + lane * 8, movm(hv1.x), movm(hv1.y));
        sts64(sb + OFF_KH + 1792 + lane * 8, movm(hv1.z), movm(hv1.w));
        __syncwarp();
        if (lane == 0) mbar_arrive(bars + 8 * BAR_HALO);
      }
      if (QORD == 2) q_issue(0);
      if (QORD >= 1) q_issue(1);
      const uint32_t rb = mapa(bars, lane & 1);
      nb_sync(NB_OREADY, 288);
      if (lane == 0) {
        asm volatile("cp.async.bulk.global.shared::cta.bulk_group [%0], [%1], %2;\n" ::"l"(g_o + (size_t)cta * 16384),
                     "r"(sb + OFF_OP), "r"(32768) : "memory");
        bulk_commit();
      }
      if (lane < 2) {
#pragma unroll
        for (int i = 0; i < 4; i++) mbar_arrive_cluster(rb + 8 * (BAR_EMPTY2 + i + i / 2));
      }
      if (lane == 0) {
        bulk_wait0();
        st_release(g_flag_o + cta, epoch);
      }
      __syncwarp();
      PROF2(17);
      if (lane < 2) mbar_arrive_cluster(rb + 8 * (BAR_EMPTY2 + 2));
      }
      if (MODE != 1) {
        const __nv_bfloat16* osrc = g_o + (size_t)(rb2 >> 1) * 16 * 16384 + hsel * 8192;
        mbar_wait(bars + 8 * (BAR_EMPTY2 + 1), 0);
        if (elect_one()) {
          if (MODE == 0) {
            asm volatile("cp.async.bulk.shared::cluster.shared::cta.mbarrier::complete_tx::bytes [%0], [%1], %2, [%3];\n"
                         ::"r"(mapa(sb + g2_a(1, hsel), rank ^ 1)), "r"(sb + g2_a(0, hsel)), "r"(16384),
                         "r"(mapa(bars + 8 * (BAR_FULL2 + 1), rank ^ 1)) : "memory");
          } else {
            bulk_load(sb + g2_a(0, hsel), osrc + hp * 16384, 16384, bars + 8 * BAR_FULL2);
            bulk_load(sb + g2_a(1, hsel), osrc + (hp ^ 1) * 16384, 16384, bars + 8 * (BAR_FULL2 + 1));
          }
        }
        __syncwarp();
      }
      if (MODE != 2) {
        mbar_wait(bars + 8 * (BAR_Y + 2), 0);
        send_y(0, 4 * XT, 1);
        fence_async_smem();
        __syncwarp();
      }
      if (MODE != 1) {
        unsigned long long seq = G2_SEQ >> 12;
        uint32_t wbar = bars + 8 * (BAR_Y + 2), fb = bars + 8 * (BAR_FULL2 + 3), dst = sb + g2_b(3, rank), ph = MODE ? 1 : 0;
        int k0 = g2_k(3) * 64;
        bool whole = false;
#pragma unroll 1
        for (int kb = 4; kb <= 16; kb++) {
          mbar_wait(wbar, ph);
          if (elect_one()) g2_issue_b(fb, STG2, dst, k0, whole);
          __syncwarp();
          seq >>= 4;
          const int s = seq & 7;
          wbar = bars + 8 * (kb == G2_KB4 ? BAR_XFREE : BAR_EMPTY2B + s);
          ph = ((uint32_t)seq >> 3 & 1) ^ (kb == G2_KB4 && MODE == 0 ? 0 : 1);
          fb = bars + 8 * (BAR_FULL2 + s);
          dst = sb + g2_b(s, rank);
          k0 = ((hp & 12) ^ kb) * 64;
          whole = s < 3;
        }
      }
      __syncwarp();
    } else {
      if (MODE != 2) {
      const float dall = __bfloat162float(p.ssm_D[chb * 8 + lr]);
      {
        const int g = lane >> 2, t = lane & 3;
        uint32_t w[2][4];
#pragma unroll
        for (int h = 0; h < 2; h++) {
          const uint2 x = __ldg(reinterpret_cast<const uint2*>(p.shift_k + ((chb & ~1) * 8 + h * 8 + g) * 4));
          w[h][0] = __byte_perm(x.x, x.x, 0x1010);
          w[h][1] = __byte_perm(x.x, x.x, 0x3232);
          w[h][2] = __byte_perm(x.y, x.y, 0x1010);
          w[h][3] = __byte_perm(x.y, x.y, 0x3232);
        }
        auto swz = [](int r) { return (((r & 29) | ((r ^ (r >> 2)) & 2)) << 5) | (r & 16); };
        const uint32_t kring = sb + OFF_X + 4096 + (hw - 1) * 2 * XT, vring = kring + XT;
        const int s0 = rank * 32 + (hw - 1) * 11, s1 = hw == 3 ? rank * 32 + 32 : s0 + 11;
        const size_t goff = (size_t)(lane >> 1) * DM + (chb & ~1) * 8 + (lane & 1) * 8;
        const __nv_bfloat16* kg = p.k + goff;
        const __nv_bfloat16* vg = p.v + goff;
        const uint32_t d0 = swz(lane >> 1) ^ ((lane & 1) << 4), d1 = swz(16 + (lane >> 1)) ^ ((lane & 1) << 4);
        auto issue = [&](int st) {
          const uint32_t so = (st & 3) << 10;
          cp_async16(kring + so + d0, kg + (size_t)st * 32 * DM, 16);
          cp_async16(kring + so + d1, kg + (size_t)(st * 32 + 16) * DM, 16);
          cp_async16(vring + so + d0, vg + (size_t)st * 32 * DM, 16);
          cp_async16(vring + so + d1, vg + (size_t)(st * 32 + 16) * DM, 16);
        };
        const int xa = 8 * (lr >> 1) + 2 * lm + (lr & 1), xb = 8 * (lr >> 1) - 4 + 2 * (lm & 1) + (lr & 1);
        const uint32_t la = swz(xa), lb = swz(xb & 31);
        const int backb = xb < 0 ? 1 : 0;
        const uint32_t ud[2] = {mapa(sb + OFF_X + g * XT + t * 16, 0), mapa(sb + OFF_X + g * XT + t * 16, 1)};
        const uint32_t ub[2] = {mapa(bars + 8 * BAR_U, 0), mapa(bars + 8 * BAR_U, 1)};
        if (tid == 320) prefetch_l2(g_tab + (chb & 63) * 32);
        if (lane == 0) mbar_wait(bars + 8 * (BAR_FULLB + NS1B - 1), 0);
        __syncwarp();
        if (lane >= 24) cp_async16(kring + (((s0 - 1) & 3) << 10) + d1, s0 > 0 ? kg + (size_t)(s0 * 32 - 16) * DM : kg, s0 > 0 ? 16 : 0);
        issue(s0);
        asm volatile("cp.async.commit_group;\n" ::: "memory");
        issue(s0 + 1);
        asm volatile("cp.async.commit_group;\n" ::: "memory");
        uint32_t tn = (uint32_t)clock();
#pragma unroll 1
        for (int st = s0; st < s1; st++) {
          tn += PSTEP;
          while ((int)((uint32_t)clock() - tn) < 0) __nanosleep(100);
          if (st + 2 < s1) issue(st + 2);
          if (hw == 1 && (unsigned)(st - s0 - HPF0) < 8u) prefetch_l2(p.ssm_k + (size_t)(chb * 8 + st - s0 - HPF0) * SEQ + lane * 64);
          asm volatile("cp.async.commit_group;\n" ::: "memory");
          asm volatile("cp.async.wait_group 2;\n" ::: "memory");
          __syncwarp();
#pragma unroll
          for (int h = 0; h < 2; h++) {
            uint32_t e[6], vv[4], e4[4];
            ldsm4t(e4, kring + ((st & 3) << 10) + (la ^ (h << 4)));
            ldsm2t(e[0], e[1], kring + (((st - backb) & 3) << 10) + (lb ^ (h << 4)));
            ldsm4t(vv, vring + ((st & 3) << 10) + (la ^ (h << 4)));
            e[2] = e4[0]; e[3] = e4[1]; e[4] = e4[2]; e[5] = e4[3];
            uint32_t o[5];
#pragma unroll
            for (int i = 0; i < 5; i++) o[i] = __byte_perm(e[i], e[i + 1], 0x5432);
#pragma unroll
            for (int i = 0; i < 4; i++) {
              uint32_t a = bmul2(o[i], w[h][3]);
              a = bfma2(e[i + 1], w[h][2], a);
              a = bfma2(o[i + 1], w[h][1], a);
              a = bfma2(e[i + 2], w[h][0], a);
              vv[i] = bmul2(a, vv[i]);
            }
            st_async128(ud[h] + (st ^ (g & 1)) * 64, ub[h], vv[0], vv[1], vv[2], vv[3]);
          }
          __syncwarp();
        }
        fence_async_smem();
        PROF(16);
      }
      nb_sync(NB_HELP3, 96);
      if (hw == 1 && elect_one()) {
        mbar_expect_tx(bars + 8 * BAR_H, 8 * 4096);
#pragma unroll 1
        for (int c = 0; c < 8; c++)
          bulk_load(sb + OFF_X + c * XT + 4096, p.ssm_k + (size_t)(chb * 8 + c) * SEQ, 4096, bars + 8 * BAR_H);
        mbar_expect_tx(bars + 8 * BAR_X, 6144);
        bulk_load(sb + OFF_T16, g_tab, 2048, bars + 8 * BAR_X);
        bulk_load(sb + OFF_T32, g_tab + 512, 4096, bars + 8 * BAR_X);
      }
      __syncwarp();
      {
        const int ck = 16 * (lane >> 4) + 2 * lr + (((lane >> 3) ^ (lane >> 2)) & 1);
        const uint32_t xo = (ck >> 1) * 64, xs = ((ck & 1) ^ (lr >> 1)) << 4;
#pragma unroll 1
        for (int job = hw - 1; job < 16; job += 3) {
          const int c = job & 7;
          uint4 a[8];
          float dv = __shfl_sync(0xffffffffu, dall, c);
          if (job < 8 || lane) dv = 0.f;
          if (job >= PF0 && job < PF1) prefetch_l2((job < 8 ? p.q + (size_t)chb * 16384 : p.wo + (size_t)chb * 8192) + c * 2048 + lane * 64);
          const uint32_t xt = sb + OFF_X + c * XT + (job >> 3) * 4096;
          mbar_wait(bars + 8 * (job < 8 ? BAR_U : BAR_H), 0);
#pragma unroll
          for (int i = 0; i < 8; i++) a[i] = lds128(xt + i * 512 + ((ck ^ (job < 8 ? (c & 1) << 2 : 0)) << 4));
          dv += bf_lo(a[0].x);
          uint32_t m[2] = {bmaxabs2(pack_bf16(dv, 0.f), bmaxabs2(a[0].x, a[0].y)), bmaxabs2(a[0].z, a[0].w)};
#pragma unroll
          for (int i = 1; i < 8; i++) {
            m[0] = bmaxabs2(bmaxabs2(m[0], a[i].x), a[i].y);
            m[1] = bmaxabs2(bmaxabs2(m[1], a[i].z), a[i].w);
          }
          m[0] = bmaxabs2(m[0], m[1]);
          const int f = max(252 - (int)(__reduce_max_sync(0xffffffffu, max(m[0] & 0x7fffu, (m[0] >> 16) & 0x7fffu)) >> 7), 1);
          if (lane == 0) asm volatile("st.shared.u32 [%0], %1;\n" ::"r"(sb + OFF_EX + job * 4), "r"(f) : "memory");
          if (f < 113) {
#pragma unroll
            for (int i = 0; i < 8; i++)
              a[i] = make_uint4(bmul2(a[i].x, f * 0x00800080u), bmul2(a[i].y, f * 0x00800080u), bmul2(a[i].z, f * 0x00800080u),
                                bmul2(a[i].w, f * 0x00800080u));
          }
          const uint32_t mul = (f < 113 ? 15 : f - 112) * 0x00800080u;
          auto cv = [&](uint32_t x) {
            x = bmul2(x, mul);
            return (x & 0x0fff0fffu) * 7 + x;
          };
          const uint32_t dst = xt + xo;
#pragma unroll
          for (int i = 0; i < 8; i++)
            sts128(dst + (i >> 2) * 2048 + (i & 1) * 1024 + (xs ^ ((i & 2) << 4)),
                   i ? cv(a[i].x) : __byte_perm(pack_f16(dv * __uint_as_float(f << 23), 0.f), cv(a[i].x), 0x7610), cv(a[i].y),
                   cv(a[i].z), cv(a[i].w));
        }
        fence_async_smem();
        __syncwarp();
        if (lane == 0) mbar_arrive(bars + 8 * BAR_X);
        PROF(19);
      }
      if (hw < 3) {
#pragma unroll 1
        for (int n = 0; n < SPIN_LIMIT && !mbar_try(bars + 8 * (BAR_Y + hw - 1), 0); n++) __nanosleep(100);
        send_y((hw - 1) * 4 * XT, 2 * XT, 0);
        __syncwarp();
        if (lane == 0) mbar_arrive(bars + 8 * (BAR_Y + 2));
        PROF(32);
        const int c8 = 2 * lm + (lr & 1), src = (lr >> 1) & 1;
        uint32_t fa = sb + OFF_X + c8 * XT + rank * 4096 + (src == rank ? 0 : 1024) + (hw - 1) * 512;
        const uint32_t fx = ((lr >> 2) ^ ((lr & 3) << 1)) << 4;
        uint32_t qa = sb + OFF_Q0 + (hw - 1) * 8192 + (lane >> 3) * 128 + (lane & 2) * 32 + (lane & 4) * 8 + (lane & 1) * 16;
        uint4* og = reinterpret_cast<uint4*>(p.out + (size_t)(rank * 512 + (hw - 1) * 256 + (lane & 2) * 4 + (lane >> 2)) * (2 * DM) +
                                             (chb & ~1) * 8 + (lane & 1) * 8);
        mbar_wait(bars + 8 * BAR_Q, 0);
        uint32_t tn = 0;
#pragma unroll 1
        for (int j = 0; j < 16; j++) {
          if (j == JS && hw == 2) {
            mbar_wait(bars + 8 * (BAR_Y + 3), 0);
            send_y(2 * XT, 4 * XT, 1);
            fence_async_smem();
            __syncwarp();
            if (lane == 0) mbar_arrive(bars + 8 * BAR_XFREE);
            tn = (uint32_t)clock();
          }
          if (!(j & 7)) {
            mbar_wait(bars + 8 * (BAR_LAND + (j >> 3)), 0);
            tn = (uint32_t)clock() + (hw - 1) * (FPACE / 2);
            PROF2(33 + (j >> 1));
          }
#pragma unroll
          for (int i = 0; i < 2; i++) {
            uint32_t y[4];
            const uint4 q = lds128(qa + i * 512);
            ldsm4t(y, fa + (j & 6) * 64 + (fx ^ (i << 5) ^ ((j & 1) << 6) ^ ((j & 2) << 3)));
            while ((int)((uint32_t)clock() - tn) < 0) __nanosleep(FSL);
            tn += hw == 2 ? FPACE2 : FPACE;
            og[i * 16 * (2 * DM / 8)] = make_uint4(bmul2(q.x, y[0]), bmul2(q.y, y[1]), bmul2(q.z, y[2]), bmul2(q.w, y[3]));
          }
          qa += j == 7 ? OFF_Q1 - OFF_Q0 - 7168 : 1024;
          if (j == 7) fa += 2048;
          og += (j == 7 ? 1024 - 224 : 32) * (2 * DM / 8);
        }
        PROF(22);
      }
      }
      if (MODE != 1 && hw == 3) {
        const uint32_t epoch = ld_relaxed(g_flag_o + cta) + 1;
        if (MODE == 0) nb_sync(NB_G1END, 288);
        if (BDEL) __nanosleep(BDEL);
        if (elect_one()) {
#pragma unroll
          for (int kb = 0; kb < 3; kb++)
            g2_issue_b(bars + 8 * (BAR_FULL2 + kb), kb || MODE ? STG2 : STG2 / 2, sb + g2_b(kb, 0), g2_k(kb) * 64, true);
        }
        __syncwarp();
        const __nv_bfloat16* osrc = g_o + (size_t)(rb2 >> 1) * 16 * 16384 + hsel * 8192;
        if (MODE == 0) __nanosleep(POLL0);
        const uint32_t* flag = g_flag_o + (rb2 >> 1) * 16 + g2_k(lane & 15);
        uint32_t ready = MODE == 0 ? 0u : ~0u;
        unsigned long long seq = G2_SEQ >> 8;
#pragma unroll 1
        for (int kb = 2; kb < 16; kb++, seq >>= 4) {
          uint32_t so = bars + (seq & 7) * 8, dst = sb + g2_a(seq & 7, hsel) + rank * 8192;
          const uint32_t ph = (uint32_t)seq >> 3 & 1;
          const __nv_bfloat16* src = osrc + rank * 4096 + (uint32_t)g2_k(kb) * 16384;
          asm volatile("" : "+r"(so), "+r"(dst), "+l"(src));
          if (!(ready >> kb & 1)) {
#pragma unroll 1
            for (int n = 0; n < SPIN_LIMIT && !(ready >> kb & 1); n++)
              ready = __ballot_sync(0xffffffffu, ld_acquire(flag) == epoch);
            fence_async_all();
          }
          if (kb == 2) PROF(21);
          if (MODE == 0 && kb == G2_KB4 && rank == 1) mbar_wait(bars + 8 * BAR_TAB, 0);
          mbar_wait(so + 8 * BAR_EMPTY2, ph);
          if (elect_one()) {
            asm volatile(
                "cp.async.bulk.shared::cluster.global.mbarrier::complete_tx::bytes.multicast::cluster [%0], [%1], %2, [%3], %4;\n"
                ::"r"(dst), "l"(src), "r"(8192), "r"(so + 8 * BAR_FULL2), "h"((uint16_t)3) : "memory");
          }
          __syncwarp();
        }
      }
    }
    cluster_sync_all();
    PROF_DUMP();
  } else {
    asm volatile("setmaxnreg.inc.sync.aligned.u32 %0;\n" :: "n"(REG_MATH));
    if (warp == 0) PROF2(26);
    const int wg = warp >> 2;
    const int wtid = tid & 127;
    const bool signaller = (wtid == 0) || (wtid == 32);
    const uint32_t rbars = mapa(bars, wtid >> 5 & 1);

    if (halo_cta) {
      const uint32_t epoch = ld_relaxed(g_flag_h + blockIdx.x) + 1;
      float acc0[64], acc1[64];
      int s = 0, ph = 0;
#pragma unroll 1
      for (int kb = 0; kb < 16; kb++) {
        mbar_wait(bars + 8 * (BAR_FULLB + s), ph);
        const uint32_t st = sb + s * STGH;
        const uint64_t da = mkdesc(st, 16, 1024, 1);
        const uint64_t db = mkdesc(st + 8192 + wg * 32768, 8192, 1024, 1);
        wg_fence();
#pragma unroll
        for (int kk = 0; kk < 4; kk++) {
          wgmma_n128(acc0, da + 2 * kk, db + 128 * kk, kb + kk);
          wgmma_n128(acc1, da + 2 * kk, db + 1024 + 128 * kk, kb + kk);
        }
        wg_commit();
        wg_wait<0>();
        if (kb == 15) PROF(37);
        if (wtid == 0) mbar_arrive(bars + 8 * (BAR_EMPTYB + s));
        if (++s == 3) { s = 0; ph ^= 1; }
      }
      fence_regs(acc0);
      fence_regs(acc1);
      if ((warp & 3) != 3) {
#pragma unroll
        for (int hh = 0; hh < 2; hh++) {
          uint4* dst = g_halo + ((hh * 4 + (warp & 3) + 1) * 16 + blockIdx.x * 4) * 128 + wg * 64 + lane;
#pragma unroll
          for (int j = 0; j < 4; j++) {
            const int o = 16 * j + 2 * hh;
            dst[(j >> 1) * 128 + (j & 1) * 32] =
                make_uint4(pack_bf16(acc0[o], acc0[o + 1]), pack_bf16(acc0[o + 4], acc0[o + 5]),
                           pack_bf16(acc0[o + 8], acc0[o + 9]), pack_bf16(acc0[o + 12], acc0[o + 13]));
            dst[(2 + (j >> 1)) * 128 + (j & 1) * 32] =
                make_uint4(pack_bf16(acc1[o], acc1[o + 1]), pack_bf16(acc1[o + 4], acc1[o + 5]),
                           pack_bf16(acc1[o + 8], acc1[o + 9]), pack_bf16(acc1[o + 12], acc1[o + 13]));
          }
        }
      }
      nb_sync(NB_G1DONE, 256);
      if (tid == 0) st_release(g_flag_h + blockIdx.x, epoch);
      PROF(36);
      cluster_sync_all();
      return;
    }

    float acc[64];
    const uint32_t g2rel = wtid ? mapa(bars, rank) + 8 * BAR_EMPTY2B : mapa(bars, wg) + 8 * BAR_EMPTY2;
    uint32_t g2a = (uint32_t)mkdesc(sb + wg * 8192, 16, 0, 0), g2b = (uint32_t)mkdesc(sb, 8192, 0, 0);
    auto g2_block = [&](bool first, int s, int ph) {
      mbar_wait(bars + 8 * (BAR_FULL2 + s), ph);
      const uint32_t da = g2a + (g2_a(s, hsel) >> 4), db = g2b + (g2_b(s, rank) >> 4), dc = db + (g2_bk(s) >> 4);
      wg_fence();
      if (first) wgmma_n128z(acc, da, db);
      else wgmma_n128a(acc, da, db);
      wgmma_n128a(acc, da + 2, db + 128);
      wgmma_n128a(acc, da + 4, dc);
      wgmma_n128a(acc, da + 6, dc + 128);
      wg_commit();
    };
    if (MODE != 2) {
    uint32_t a1[2][4], sc[2];
    C2 t[2];
    {
      float acc0[96], acc1[96];
      int sa = 0, pha = 0, sbb = 0, phb = 0;
      asm volatile("cp.async.wait_group 0;\n" ::: "memory");
      fence_async_smem();
      nb_sync(NB_FIRST, 256);
      if (tid == 0) {
        mbar_arrive(bars + 8 * BAR_FULLA);
        mbar_arrive(bars + 8 * BAR_FULLB);
      }
      PROF(0 + wg);
#pragma unroll 1
      for (int kb = 0; kb < 30; kb++) {
        if (!(kb & 1)) mbar_wait(bars + 8 * (BAR_FULLA + sa), pha);
        mbar_wait(bars + 8 * (BAR_FULLB + sbb), phb);
        if (kb == 0) PROF2(0 + wg);
        if (kb == 4 && wg == 0) PROF2(28);
        if (kb == 8 && wg == 0) PROF2(29);
        if (kb == 16 && wg == 0) PROF2(30);
        const uint64_t da = mkdesc(sb + sa * STG1A + wg * 16384 + (kb & 1) * 64, 16, 2048, 1);
        const uint64_t db = mkdesc(sb + OFF_1B + sbb * STG1B, 4096, 1024, 1);
        wg_fence();
        wgmma_n192(acc0, da + 64, db, kb);
        wgmma_n192(acc1, da, db, kb);
        wgmma_n192(acc0, da + 66, db + 128, 1);
        wgmma_n192(acc1, da + 2, db + 128, 1);
        wg_commit();
        wg_wait<1>();
        if (kb > 0) {
          if (wtid == 64) mbar_arrive(bars + 8 * (BAR_EMPTYB + (sbb == 0 ? NS1B - 1 : sbb - 1)));
          if (!(kb & 1) && signaller) mbar_arrive_cluster(rbars + 8 * (BAR_EMPTYA + (sa == 0 ? NS1A - 1 : sa - 1)));
        }
        if (++sbb == NS1B) { sbb = 0; phb ^= 1; }
        if ((kb & 1) && ++sa == NS1A) { sa = 0; pha ^= 1; }
      }
      const int lr = lane & 7, lm = lane >> 3;
      const bool le0 = 2 * (lane & 3) <= (lane >> 2), le1 = 2 * (lane & 3) + 1 <= (lane >> 2);
      const uint32_t maskLE = (le0 ? 0x0000FFFFu : 0u) | (le1 ? 0xFFFF0000u : 0u);
      uint32_t q[4][8], k[5][8], vt[5][8];
      {
        static_assert(15 % NS1A == 0 && 30 % NS1B == 0, "slots of the last k blocks");
        asm volatile("ld.volatile.global.v4.u32 {%0,%1,%2,%3}, [%4];\n"
                     : "=r"(t[0].r), "=r"(t[1].r), "=r"(t[0].i), "=r"(t[1].i) : "l"(g_tab + 1536 + wtid * 4) : "memory");
        mbar_wait(bars + 8 * BAR_FULLA, 1);
        mbar_wait(bars + 8 * BAR_FULLB, 0);
        mbar_wait(bars + 8 * (BAR_FULLB + 1), 0);
        mbar_wait(bars + 8 * (BAR_EMPTYA + 1), 0);
        const uint64_t da = mkdesc(sb + wg * 16384, 16, 2048, 1);
        const uint64_t db = mkdesc(sb + OFF_1B, 4096, 1024, 1);
        wg_fence();
#pragma unroll
        for (int i = 0; i < 4; i++) wgmma_n192(acc0, da + 64 + 2 * i, db + (i >> 1) * (STG1B >> 4) + (i & 1) * 128, 1);
        wg_commit();
#pragma unroll
        for (int i = 0; i < 2; i++) wgmma_n192(acc1, da + 2 * i, db + (i >> 1) * (STG1B >> 4) + (i & 1) * 128, 1);
        wg_commit();
        wg_wait<1>();
        fence_regs(acc0);
        PROFA(45, 0);
        attn_pack<8, 1, false>(acc0, k[4]);
        attn_pack<16, 1, true>(acc0, vt[4]);
        const uint32_t kh = sb + (warp == 7 ? OFF_OP + 7 * 4096 : OFF_KH + (warp + 1) * 2048) + lane * 16;
        sts128(kh, k[4][0], k[4][1], k[4][2], k[4][3]);
        sts128(kh + 512, k[4][4], k[4][5], k[4][6], k[4][7]);
#pragma unroll
        for (int i = 0; i < 4; i++) sts64(kh - lane * 8 + 1024 + 256 * i, vt[4][2 * i], vt[4][2 * i + 1]);
#pragma unroll
        for (int i = 2; i < 4; i++) wgmma_n192(acc1, da + 2 * i, db + (i >> 1) * (STG1B >> 4) + (i & 1) * 128, 1);
        wg_commit();
        attn_pack<0, 0, false>(acc0, q[1]);
        attn_pack<0, 1, false>(acc0, q[3]);
        attn_pack<8, 0, false>(acc0, k[2]);
        attn_pack<16, 0, true>(acc0, vt[2]);
        uint32_t z = p.zero;
#pragma unroll
        for (int i = 0; i < 8; i++) z &= q[1][i] & q[3][i];
#pragma unroll
        for (int i = 0; i < 8; i += 2) z &= k[2][i] & k[2][i + 1];
        __syncwarp();
        if (lane == 0) mbar_arrive(bars + 8 * BAR_STG + z);
        wg_wait<0>();
        fence_regs(acc1);
        if (MODE == 0) nb_arrive(NB_G1END, 288);
      }
      PROF(2 + wg);
      mbar_wait(bars + 8 * (warp == 0 ? BAR_HALO : BAR_STG), 0);
      {
        const uint32_t kh = sb + OFF_KH + warp * 2048 + lane * 16;
#pragma unroll
        for (int i = 0; i < 2; i++) {
          const uint4 t = lds128(kh + 512 * i);
          k[0][4 * i] = t.x; k[0][4 * i + 1] = t.y; k[0][4 * i + 2] = t.z; k[0][4 * i + 3] = t.w;
        }
#pragma unroll
        for (int i = 0; i < 4; i++) {
          const uint2 t = lds64(kh - lane * 8 + 1024 + 256 * i);
          vt[0][2 * i] = t.x; vt[0][2 * i + 1] = t.y;
        }
      }
      attn_pack<0, 0, false>(acc1, q[0]);
      attn_pack<0, 1, false>(acc1, q[2]);
      attn_pack<8, 0, false>(acc1, k[1]);
      attn_pack<8, 1, false>(acc1, k[3]);
      {
        float x[8][2];
        uint32_t pp[8];
        const bool first = warp == 0 && gidx == 0;
#pragma unroll
        for (int hd = 0; hd < 2; hd++) {
#pragma unroll
          for (int j = 0; j < 4; j += 2) {
            float s0[4], s1[4], s2[4];
            attn_qk(s2, q[j], q[j + 1], k[j + 2], 4 * hd);
            attn_qk(s1, q[j], q[j + 1], k[j + 1], 4 * hd);
            attn_qk(s0, q[j], q[j + 1], k[j], 4 * hd);
            if (j == 0 && first) s0[0] = s0[1] = -1e9f / 0.17677669529663687f;
            x[2 * j + hd][0] = le0 ? s1[0] : s0[0];
            x[2 * j + hd][1] = le1 ? s1[1] : s0[1];
            x[2 * j + 2 + hd][0] = le0 ? s2[2] : s1[2];
            x[2 * j + 2 + hd][1] = le1 ? s2[3] : s1[3];
          }
        }
        PROFA(40, __float_as_uint(x[1][0] + x[7][1]));
        attn_pack<16, 0, true>(acc1, vt[1]);
        attn_pack<16, 1, true>(acc1, vt[3]);
        quad_softmax<8>(x, pp);
        PROFA(41, pp[1] + pp[7]);
        mbar_wait(bars + 8 * BAR_X, 0);
        ldsm4(a1[0], sb + OFF_T32 + (warp & 3) * 1024 + lane * 16);
        ldsm4(a1[1], sb + OFF_T32 + 512 + (warp & 3) * 1024 + lane * 16);
        {
          const uint32_t ex = sb + OFF_EX + wg * 16 + (warp & 2) * 2;
#pragma unroll
          for (int i = 0; i < 2; i++) sc[i] = min(max(381 - (int)lds32(ex + 8 * i) - (int)lds32(ex + 32 + 8 * i), 1), 254) * 0x00800080u;
        }
        const uint32_t obase = sb + OFF_OP + (warp * 32 + lr) * 128;
#pragma unroll
        for (int n = 0; n < 8; n++) {
          attn_pv(obase + (n >> 1) * 1024 + (((4 * (n & 1) + lm) ^ lr) << 4), vt[n >> 1], vt[(n >> 1) + 1], 4 * (n & 1), pp[n],
                  maskLE);
        }
      }
      PROFA(42, 0);
    }

    {
      const int w = warp & 3;
      const int lr = lane & 7, lm = lane >> 3;
      const uint32_t xb = sb + OFF_X + wg * 4 * XT;
      auto uo = [](int c) { return (c & 1) * 2 * XT + (c >> 1) * 2048; };
      const uint64_t dc2 = mkdesc(sb + OFF_T16, 512, 128, 0), dc3 = mkdesc(sb + OFF_T16, 128, 512, 0);
      const uint64_t dc4 = mkdesc(sb + OFF_T32, 128, 256, 0);
      const uint64_t dx = mkdesc(xb, 4096, 512, 2), dz = mkdesc(xb, 4096, 256, 3);
      const uint32_t zs = xb + (w * 16 + (lm & 1) * 8 + lr) * 32 + (((lm >> 1) ^ (lr >> 2)) << 4);
      const uint32_t ys = xb + w * 4096 + (lm >> 1) * 256 + ((lr * 32 + (((lm & 1) ^ (lr >> 2)) << 4)) ^ (rank << 6) ^ ((w & 2) << 4));
      const bool own = (w & 1) == rank;
      const uint32_t ybar = mapa(bars, own ? rank ^ 1 : rank) + 8 * BAR_Y;
      uint32_t d[2][32], pa[2][4][2][4], e[4][4][8], ya[2][2][2][4], v[2][2][8];
      C2 s1[2][2][2];
      float o[2][16];
      auto rows = [&](int c) {
        fft_rows(d[c & 1], a1, dx + (uo(c) >> 4));
        wg_commit();
      };
      auto cols = [&](int c) {
        const int s = c & 1;
        fence_regs(d[s]);
#pragma unroll
        for (int i = 0; i < 16; i++) {
          const C2 z = crot(C2{d[s][2 * i], d[s][2 * i + 1]}, t[i & 1]);
          pa[s][i >> 2][i & 1][(i >> 1) & 1] = z.r;
          pa[s][i >> 2][i & 1][2 + ((i >> 1) & 1)] = z.i;
        }
        wg_fence();
#pragma unroll
        for (int i = 0; i < 4; i++) fft_cols<0>(e[c][i], pa[s][i], dc2);
        wg_commit();
      };
      auto prod = [&](int c, int n) {
        const int s = c & 1;
        fence_regs(e[c][2 * n]);
        fence_regs(e[c][2 * n + 1]);
#pragma unroll
        for (int j = 0; j < 2; j++) {
          const C2 u0 = cget(e[s][2 * n], j, 0), u1 = cget(e[s][2 * n], j, 1);
          const C2 h0 = cget(e[s][2 * n + 1], j, 0), h1 = cget(e[s][2 * n + 1], j, 1);
          C2 y0, y1;
          if (c < 2) {
            y0 = cmul(h0, u0);
            s1[s][n][j] = cfma(h0, u1, cmul(h1, u0));
            y1 = C2{hadd2(s1[s][n][j].r, y0.i), hadd2(s1[s][n][j].i, hneg2(y0.r))};
          } else {
            const C2 u2 = cget(e[c][2 * n], j, 0), u3 = cget(e[c][2 * n], j, 1);
            const C2 h2 = cget(e[c][2 * n + 1], j, 0), h3 = cget(e[c][2 * n + 1], j, 1);
            const C2 s2 = cfma(h0, u2, cfma(h2, u0, cmul(h1, u1)));
            y0 = C2{hadd2(s2.r, s1[s][n][j].i), hadd2(s2.i, hneg2(s1[s][n][j].r))};
            y1 = cfma(h0, u3, cfma(h1, u2, cfma(h2, u1, cfma(h3, u0, C2{s2.i, hneg2(s2.r)}))));
          }
          ya[s][n][j][0] = y0.r;
          ya[s][n][j][1] = y1.r;
          ya[s][n][j][2] = y0.i;
          ya[s][n][j][3] = y1.i;
        }
      };
      auto icols = [&](int c) {
        wg_fence();
        fft_cols<1>(v[c & 1][0], ya[c & 1][0], dc3);
        fft_cols<1>(v[c & 1][1], ya[c & 1][1], dc3);
        wg_commit();
      };
      auto stage = [&](int c) {
        const int s = c & 1;
        fence_regs(v[s][0]);
        fence_regs(v[s][1]);
#pragma unroll
        for (int b = 0; b < 4; b++) {
          const C2 x0 = cget(v[s][b >> 1], 0, b & 1), x1 = cget(v[s][b >> 1], 1, b & 1);
          const C2 z0 = crot(C2{x0.i, x0.r}, t[0]), z1 = crot(C2{x1.i, x1.r}, t[1]);
          stsm4(zs + uo(c) + b * 4096, z0.i, z0.r, z1.i, z1.r);
        }
      };
      auto back = [&](int c) {
        fft_back(o[c & 1], dz + (uo(c) >> 4), dc4);
        wg_commit();
      };
      auto out = [&](int c) {
        float (&r)[16] = o[c & 1];
        fence_regs(r);
#pragma unroll
        for (int i = 0; i < 16; i += 8)
          stsm4t(ys + uo(c) + 64 * i, bmul2(pack_bf16(r[i], r[i + 1]), sc[c & 1]), bmul2(pack_bf16(r[i + 2], r[i + 3]), sc[c & 1]),
                 bmul2(pack_bf16(r[i + 4], r[i + 5]), sc[c & 1]), bmul2(pack_bf16(r[i + 6], r[i + 7]), sc[c & 1]));
      };
      auto signal = [&](int yb, int land) {
        __syncwarp();
        if (lane == 0) {
          mbar_arrive_cluster(ybar + 8 * yb);
          if (own && land >= 0) mbar_arrive(bars + 8 * (BAR_LAND + land));
        }
      };
      wg_fence();
      rows(0);
      rows(1);
      fence_async_smem();
      nb_arrive(NB_OREADY, 288);
      PROF(34 + wg);
      wg_wait<1>();
      cols(0);
      wg_wait<1>();
      cols(1);
      rows(2);
      nb_sync(NB_CONV + wg, 128);
      wg_wait<2>();
      prod(0, 0);
      prod(0, 1);
      icols(0);
      wg_wait<2>();
      prod(1, 0);
      prod(1, 1);
      icols(1);
      PROF3(40 + 10 * wg);
      wg_wait<1>();
      stage(0);
      wg_wait<0>();
      stage(1);
      fence_async_smem();
      cols(2);
      PROF3(41 + 10 * wg);
      nb_sync(NB_CONV + wg, 128);
      back(0);
      back(1);
      wg_wait<2>();
      wg_fence();
      rows(3);
      prod(2, 0);
      wg_wait<1>();
      out(0);
      out(1);
      signal(wg, 0);
      PROF3(42 + 10 * wg);
      prod(2, 1);
      icols(2);
      wg_wait<1>();
      cols(3);
      PROF3(43 + 10 * wg);
      wg_wait<1>();
      stage(2);
      fence_async_smem();
      wg_wait<0>();
      prod(3, 0);
      nb_sync(NB_CONV + wg, 128);
      wg_fence();
      back(2);
      prod(3, 1);
      icols(3);
      PROF3(44 + 10 * wg);
      wg_wait<1>();
      out(2);
      signal(2, -1);
      wg_wait<0>();
      stage(3);
      PROF3(45 + 10 * wg);
      fence_async_smem();
      nb_sync(NB_CONV + wg, 128);
      wg_fence();
      back(3);
      constexpr int G = MODE == 0 && EARLY;
      if (MODE == 0) mbar_wait(bars + 8 * (BAR_EMPTY2 + 4), 0);
      if (G) g2_block(true, 0, 0);
      wg_wait<G>();
      if (lane == 0) mbar_arrive_cluster(mapa(bars, 1) + 8 * BAR_TAB);
      out(3);
      signal(3, 1);
      PROF(6 + wg);
    }
    }

    if (MODE != 1) {
      if (MODE == 2 || !EARLY) g2_block(true, 0, 0);
      const int lr = lane & 7, lm = lane >> 3;
      const uint32_t wb = sb + g2_a(1, 0) + warp * 2048;
      const int orow = (rb2 & 7) * 128 + warp * 16;
      uint4* og = reinterpret_cast<uint4*>(p.out + (size_t)(2 * (orow + lm) + (rb2 >> 3)) * (2 * DM) + DM + cb2 * 128 + lr * 8);
      uint32_t wst = wb + (lr + 8 * (lm & 1)) * 128, wsx = ((lm >> 1) ^ lr) << 4, wld = wb + lm * 128, wlx = (lr ^ lm) << 4;
      asm volatile("" : "+l"(og), "+r"(wst), "+r"(wsx), "+r"(wld), "+r"(wlx));
      static_assert(ENDG == NS2 && (G2SEQ >> 4 & 0xfffff) == (G2SEQ >> 24 & 0xfffff) && (G2SEQ >> 4 & 0xfffff) == G2SEQ >> 44, "rounds");
#pragma unroll 1
      for (int r = 0; r < 3; r++) {
        const bool hold = r == 2 && wg != LEADWG;
        const uint32_t rel0 = g2rel + (r ? 8 * (G2SEQ >> 20 & 7) : 0);
        if (hold) {
          wg_wait<0>();
          if (signaller) mbar_arrive_cluster(rel0);
          nb_sync(NB_LEAD, 256);
        }
#pragma unroll
        for (int i = 1; i <= NS2; i++) {
          const int s = G2SEQ >> (4 * i) & 7;
          g2_block(false, s, (r & 1) ^ (s == 0));
          if (warp == LEADWG * 4) PROF2(40 + 5 * r + i);
          if (i == 1 ? !hold : r < 2) {
            wg_wait<1>();
            if (signaller) mbar_arrive_cluster(i == 1 ? rel0 : g2rel + 8 * (G2SEQ >> (4 * i - 4) & 7));
          }
        }
        if (r == 0) PROF(8 + wg);
        g2a += p.zero;
        g2b += p.zero;
      }
      if (wg == LEADWG) nb_arrive(NB_LEAD, 256);
      wg_wait<0>();
      fence_regs(acc);
      PROF(10 + wg);
#pragma unroll
      for (int h = 0; h < 2; h++) {
        const uint32_t b = h * (g2_a(3, 0) - g2_a(1, 0));
#pragma unroll
        for (int j = 8 * h; j < 8 * h + 8; j += 2)
          stsm4(wst + b + (wsx ^ ((j & 7) << 4)), pack_bf16(acc[4 * j], acc[4 * j + 1]),
                pack_bf16(acc[4 * j + 2], acc[4 * j + 3]), pack_bf16(acc[4 * j + 4], acc[4 * j + 5]),
                pack_bf16(acc[4 * j + 6], acc[4 * j + 7]));
        if (OTMA == 2 || (OTMA == 1 && wg == LEADWG)) {
          fence_async_smem();
          __syncwarp();
          if (elect_one()) {
            tma_store_3d(&tmOb, wb + b, DM + cb2 * 128 + h * 64, rb2 >> 3, orow);
            bulk_commit();
          }
        } else {
          __syncwarp();
          uint4 v[4];
#pragma unroll
          for (int i = 0; i < 4; i++) v[i] = lds128(wld + b + i * 512 + (wlx ^ ((i & 1) << 6)));
#pragma unroll
          for (int i = 0; i < 4; i++) og[(size_t)i * 8 * (2 * DM / 8) + h * 8] = v[i];
        }
      }
      PROF(12 + wg);
      if (OTMA) bulk_wait0();
    }
    cluster_sync_all();
  }
}

typedef CUresult (*EncodeFn)(CUtensorMap*, CUtensorMapDataType, cuuint32_t, void*, const cuuint64_t*, const cuuint64_t*,
                             const cuuint32_t*, const cuuint32_t*, CUtensorMapInterleave, CUtensorMapSwizzle,
                             CUtensorMapL2promotion, CUtensorMapFloatOOBfill);

void make_map(EncodeFn enc, CUtensorMap* tm, const void* base, int rank, const cuuint64_t* dims, const cuuint64_t* strides,
              const cuuint32_t* box, CUtensorMapSwizzle swz) {
  cuuint32_t es[5] = {1, 1, 1, 1, 1};
  enc(tm, CU_TENSOR_MAP_DATA_TYPE_BFLOAT16, rank, const_cast<void*>(base), dims, strides, box, es,
      CU_TENSOR_MAP_INTERLEAVE_NONE, swz, CU_TENSOR_MAP_L2_PROMOTION_L2_256B, CU_TENSOR_MAP_FLOAT_OOB_FILL_NONE);
}

}

extern "C" void kernel_launch(void* const* d_in, const int* in_sizes, int n_in, void* d_out, int out_size) {
  static EncodeFn enc = nullptr;
  static bool coresident = true;
  if (!enc) {
    void* fn = nullptr;
    cudaDriverEntryPointQueryResult qr;
    cudaGetDriverEntryPoint("cuTensorMapEncodeTiled", &fn, cudaEnableDefault, &qr);
    enc = (EncodeFn)fn;
    cudaFuncSetAttribute(fused_kernel<0>, cudaFuncAttributeMaxDynamicSharedMemorySize, SMEM_BYTES);
    cudaFuncSetAttribute(fused_kernel<1>, cudaFuncAttributeMaxDynamicSharedMemorySize, SMEM_BYTES);
    cudaFuncSetAttribute(fused_kernel<2>, cudaFuncAttributeMaxDynamicSharedMemorySize, SMEM_BYTES);
    cudaLaunchConfig_t cfg = {};
    cfg.gridDim = dim3(NCTA);
    cfg.blockDim = dim3(NTHREADS);
    cfg.dynamicSmemBytes = SMEM_BYTES;
    cudaLaunchAttribute at;
    at.id = cudaLaunchAttributeClusterDimension;
    at.val.clusterDim.x = 2;
    at.val.clusterDim.y = 1;
    at.val.clusterDim.z = 1;
    cfg.attrs = &at;
    cfg.numAttrs = 1;
    int nclusters = 0;
    if (cudaOccupancyMaxActiveClusters(&nclusters, fused_kernel<0>, &cfg) == cudaSuccess) coresident = nclusters >= NCTA / 2;
    (void)cudaGetLastError();
  }
  CUtensorMap tmX, tmW, tmWo, tmWp, tmQ, tmOb, tmXh, tmWh;
  {
    cuuint64_t dims[3] = {1024, 2, 1024};
    cuuint64_t str[2] = {2048, 4096};
    cuuint32_t box[3] = {64, 1, 128};
    make_map(enc, &tmX, d_in[6], 3, dims, str, box, CU_TENSOR_MAP_SWIZZLE_128B);
  }
  {
    cuuint64_t dims[3] = {1024, 1024, 3};
    cuuint64_t str[2] = {6144, 2048};
    cuuint32_t box[3] = {64, 32, 3};
    make_map(enc, &tmW, d_in[7], 3, dims, str, box, CU_TENSOR_MAP_SWIZZLE_128B);
  }
  {
    cuuint64_t dims[3] = {64, 1024, 16};
    cuuint64_t str[2] = {2048, 128};
    cuuint32_t box[3] = {64, 64, 2};
    cuuint32_t piece[3] = {64, 32, 1};
    make_map(enc, &tmWo, d_in[8], 3, dims, str, box, CU_TENSOR_MAP_SWIZZLE_128B);
    make_map(enc, &tmWp, d_in[8], 3, dims, str, piece, CU_TENSOR_MAP_SWIZZLE_128B);
  }
  {
    cuuint64_t dims[5] = {1024, 2, 2, 4, 128};
    cuuint64_t str[4] = {2048, 8 * 2048, 2 * 2048, 16 * 2048};
    cuuint32_t box[5] = {16, 2, 2, 4, 32};
    make_map(enc, &tmQ, d_in[0], 5, dims, str, box, CU_TENSOR_MAP_SWIZZLE_NONE);
  }
  {
    cuuint64_t dims[3] = {2048, 2, 1024};
    cuuint64_t str[2] = {4096, 8192};
    cuuint32_t box[3] = {64, 1, 16};
    make_map(enc, &tmOb, d_out, 3, dims, str, box, CU_TENSOR_MAP_SWIZZLE_128B);
  }
  {
    cuuint64_t dims[4] = {1024, 256, 2, 4};
    cuuint64_t str[3] = {4096, 2048, 256 * 4096};
    cuuint32_t box[4] = {64, 8, 2, 3};
    make_map(enc, &tmXh, d_in[6], 4, dims, str, box, CU_TENSOR_MAP_SWIZZLE_128B);
  }
  {
    cuuint64_t dims[3] = {64, 1024, 48};
    cuuint64_t str[2] = {6144, 128};
    cuuint32_t box[3] = {64, 64, 4};
    make_map(enc, &tmWh, d_in[7], 3, dims, str, box, CU_TENSOR_MAP_SWIZZLE_128B);
  }
  Params p;
  p.q = (const __nv_bfloat16*)d_in[0];
  p.k = (const __nv_bfloat16*)d_in[1];
  p.v = (const __nv_bfloat16*)d_in[2];
  p.shift_k = (const __nv_bfloat16*)d_in[3];
  p.ssm_k = (const __nv_bfloat16*)d_in[4];
  p.ssm_D = (const __nv_bfloat16*)d_in[5];
  p.x = (const __nv_bfloat16*)d_in[6];
  p.w = (const __nv_bfloat16*)d_in[7];
  p.wo = (const __nv_bfloat16*)d_in[8];
  p.out = (__nv_bfloat16*)d_out;
  p.zero = 0;
  if (coresident) {
    fused_kernel<0><<<NCTA, NTHREADS, SMEM_BYTES>>>(p, tmX, tmW, tmWo, tmWp, tmQ, tmOb, tmXh, tmWh);
  } else {
    fused_kernel<0><<<4, NTHREADS, SMEM_BYTES>>>(p, tmX, tmW, tmWo, tmWp, tmQ, tmOb, tmXh, tmWh);
    fused_kernel<1><<<NCTA, NTHREADS, SMEM_BYTES>>>(p, tmX, tmW, tmWo, tmWp, tmQ, tmOb, tmXh, tmWh);
    fused_kernel<2><<<NCTA, NTHREADS, SMEM_BYTES>>>(p, tmX, tmW, tmWo, tmWp, tmQ, tmOb, tmXh, tmWh);
  }
}
```

```cpp
#include <cuda_runtime.h>
#include <cuda.h>
#include <cuda_bf16.h>
#include <stdint.h>

namespace {

constexpr int SEQ = 2048;
constexpr int DM = 1024;
constexpr int NCTA = 132;
constexpr int NTHREADS = 384;

constexpr int STG1A = 32768;
constexpr int NS1A = 3;
constexpr int STG1B = 12288;
constexpr int NS1B = 5;
constexpr int OFF_1B = NS1A * STG1A;
constexpr int STG2 = 32768;
constexpr int NS2 = 5;
#define G2SEQ 0x0432104321043210ull
constexpr unsigned long long g2_seq() {
  unsigned long long r = G2SEQ;
  for (int kb = 0; kb < 16; kb++)
    for (int j = 0; j < kb; j++)
      if (((G2SEQ >> (4 * j)) & 7) == ((G2SEQ >> (4 * kb)) & 7)) r ^= 8ull << (4 * kb);
  return r;
}
constexpr unsigned long long G2_SEQ = g2_seq();
constexpr int g2_first4() {
  int kb = 0;
  while (((G2SEQ >> (4 * kb)) & 7) != 4) kb++;
  return kb;
}
constexpr int G2_KB4 = g2_first4();
#define POLL0 1500
#define QORD 1
#define BDEL 0
#define XPF 0
#define HPF0 3
#define PF0 8
#define PF1 12
#define PSTEP 1150
#define FPACE 260
#define LEADWG 1
#define OTMA 1
#define EARLY 1
#define R3 0
#define FSL 50
#define JS 1
#define FPACE2 230
#define PFR 1
#define ENDG 5
__device__ __forceinline__ uint32_t g2_a(int s, int hsel) { return (((0x97524 >> (4 * s)) & 15) ^ (s & 5 ? 0 : hsel)) << 14; }
constexpr int OFF_Q0 = 3 << 14, OFF_Q1 = 8 << 14;
constexpr int STGH = 73728;
constexpr int OFF_KH = 1 * STG2;
constexpr int OFF_OP = 2 * STG2;
constexpr int OFF_T32 = 5 * STG2 - 4096;
constexpr int OFF_X = 5 * STG2;
constexpr int XT = 8192;
__device__ __forceinline__ uint32_t g2_b(int s, int rank) {
  return s < 3 ? (s == 2 ? 6 : s) << 14 : OFF_X + (s - 3) * 2 * XT + (rank ^ 1) * 4096;
}
__device__ __forceinline__ uint32_t g2_bk(int s) { return s < 3 ? 4096 : 4 * XT; }
constexpr int OFF_BAR = OFF_X + 8 * XT;
constexpr int OFF_EX = OFF_BAR + 448;
constexpr int OFF_T16 = 230400;
constexpr int SMEM_BYTES = OFF_T16 + 2048;
static_assert(OFF_1B + NS1B * STG1B <= OFF_T32 && OFF_X % 1024 == 0, "layout");
static_assert(3 * STGH <= OFF_BAR && OFF_EX + 64 <= OFF_T16 && SMEM_BYTES <= 232448, "smem");

constexpr int BAR_FULLA = 0;
constexpr int BAR_EMPTYA = 3;
constexpr int BAR_FULLB = 6;
constexpr int BAR_EMPTYB = 11;
constexpr int BAR_FULL2 = 16;
constexpr int BAR_EMPTY2 = 21;
constexpr int BAR_EMPTY2B = 44;
constexpr int BAR_X = 26;
constexpr int BAR_LAND = 42;
constexpr int BAR_TAB = 28;
constexpr int BAR_U = 29;
constexpr int BAR_H = 30;
constexpr int BAR_STG = 31;
constexpr int BAR_Y = 32;
constexpr int BAR_XFREE = 38;
constexpr int BAR_HALO = 40;
constexpr int BAR_Q = 41;

constexpr int NB_G1DONE = 1;
constexpr int NB_LEAD = 2;
constexpr int NB_G1END = 3;
constexpr int NB_OREADY = 4;
constexpr int NB_CONV = 5;
constexpr int NB_HELP3 = 11;
constexpr int NB_FIRST = 13;

#define REG_MATH 224
#define REG_HELP 56
constexpr int SPIN_LIMIT = 1 << 20;

__device__ __align__(1024) __nv_bfloat16 g_o[SEQ * DM];
__device__ uint32_t g_flag_o[128];
__device__ uint32_t g_flag_h[4];
__device__ uint4 g_halo[128 * 128];
__device__ __align__(128) const uint32_t g_tab[2048] = {
  0x2fd93000,0x2ea72f64,0x2c722da8,0x263e2a1f,0x2ea73000,0xa63e2a1f,0xafd9ada8,0xac72af64,0x2c723000,0xafd9aa1f,0x263eada8,0x2ea72f64,
  0x263e3000,0xac72af64,0x2ea72da8,0xafd9aa1f,0xa63e3000,0x2c72af64,0xaea72da8,0x2fd9aa1f,0xac723000,0x2fd9aa1f,0xa63eada8,0xaea72f64,
  0xaea73000,0x263e2a1f,0x2fd9ada8,0x2c72af64,0xafd93000,0xaea72f64,0xac722da8,0xa63e2a1f,0x263e0000,0x2c722a1f,0x2ea72da8,0x2fd92f64,
  0x2c720000,0x2fd92f64,0x263e2da8,0xaea7aa1f,0x2ea70000,0x263e2f64,0xafd9ada8,0x2c72aa1f,0x2fd90000,0xaea72a1f,0x2c72ada8,0xa63e2f64,
  0x2fd90000,0xaea7aa1f,0x2c722da8,0xa63eaf64,0x2ea70000,0x263eaf64,0xafd92da8,0x2c722a1f,0x2c720000,0x2fd9af64,0x263eada8,0xaea72a1f,
  0x263e0000,0x2c72aa1f,0x2ea7ada8,0x2fd9af64,0xafd93000,0xaea72f64,0xac722da8,0xa63e2a1f,0xaea73000,0x263e2a1f,0x2fd9ada8,0x2c72af64,
  0xac723000,0x2fd9aa1f,0xa63eada8,0xaea72f64,0xa63e3000,0x2c72af64,0xaea72da8,0x2fd9aa1f,0x263e3000,0xac72af64,0x2ea72da8,0xafd9aa1f,
  0x2c723000,0xafd9aa1f,0x263eada8,0x2ea72f64,0x2ea73000,0xa63e2a1f,0xafd9ada8,0xac72af64,0x2fd93000,0x2ea72f64,0x2c722da8,0x263e2a1f,
  0xa63e0000,0xac722a1f,0xaea72da8,0xafd92f64,0xac720000,0xafd92f64,0xa63e2da8,0x2ea7aa1f,0xaea70000,0xa63e2f64,0x2fd9ada8,0xac72aa1f,
  0xafd90000,0x2ea72a1f,0xac72ada8,0x263e2f64,0xafd90000,0x2ea7aa1f,0xac722da8,0x263eaf64,0xaea70000,0xa63eaf64,0x2fd92da8,0xac722a1f,
  0xac720000,0xafd9af64,0xa63eada8,0x2ea72a1f,0xa63e0000,0xac72aa1f,0xaea7ada8,0xafd9af64,0xa63e0000,0xac72aa1f,0xaea7ada8,0xafd9af64,
  0xac720000,0xafd9af64,0xa63eada8,0x2ea72a1f,0xaea70000,0xa63eaf64,0x2fd92da8,0xac722a1f,0xafd90000,0x2ea7aa1f,0xac722da8,0x263eaf64,
  0xafd90000,0x2ea72a1f,0xac72ada8,0x263e2f64,0xaea70000,0xa63e2f64,0x2fd9ada8,0xac72aa1f,0xac720000,0xafd92f64,0xa63e2da8,0x2ea7aa1f,
  0xa63e0000,0xac722a1f,0xaea72da8,0xafd92f64,0x2fd93000,0x2ea72f64,0x2c722da8,0x263e2a1f,0x2ea73000,0xa63e2a1f,0xafd9ada8,0xac72af64,
  0x2c723000,0xafd9aa1f,0x263eada8,0x2ea72f64,0x263e3000,0xac72af64,0x2ea72da8,0xafd9aa1f,0xa63e3000,0x2c72af64,0xaea72da8,0x2fd9aa1f,
  0xac723000,0x2fd9aa1f,0xa63eada8,0xaea72f64,0xaea73000,0x263e2a1f,0x2fd9ada8,0x2c72af64,0xafd93000,0xaea72f64,0xac722da8,0xa63e2a1f,
  0x263e0000,0x2c72aa1f,0x2ea7ada8,0x2fd9af64,0x2c720000,0x2fd9af64,0x263eada8,0xaea72a1f,0x2ea70000,0x263eaf64,0xafd92da8,0x2c722a1f,
  0x2fd90000,0xaea7aa1f,0x2c722da8,0xa63eaf64,0x2fd90000,0xaea72a1f,0x2c72ada8,0xa63e2f64,0x2ea70000,0x263e2f64,0xafd9ada8,0x2c72aa1f,
  0x2c720000,0x2fd92f64,0x263e2da8,0xaea7aa1f,0x263e0000,0x2c722a1f,0x2ea72da8,0x2fd92f64,0xafd93000,0xaea72f64,0xac722da8,0xa63e2a1f,
  0xaea73000,0x263e2a1f,0x2fd9ada8,0x2c72af64,0xac723000,0x2fd9aa1f,0xa63eada8,0xaea72f64,0xa63e3000,0x2c72af64,0xaea72da8,0x2fd9aa1f,
  0x263e3000,0xac72af64,0x2ea72da8,0xafd9aa1f,0x2c723000,0xafd9aa1f,0x263eada8,0x2ea72f64,0x2ea73000,0xa63e2a1f,0xafd9ada8,0xac72af64,
  0x2fd93000,0x2ea72f64,0x2c722da8,0x263e2a1f,0xa63e0000,0xac72aa1f,0xaea7ada8,0xafd9af64,0x2c720000,0x2fd92f64,0x263e2da8,0xaea7aa1f,
  0xaea70000,0xa63eaf64,0x2fd92da8,0xac722a1f,0x2fd90000,0xaea72a1f,0x2c72ada8,0xa63e2f64,0xafd90000,0x2ea72a1f,0xac72ada8,0x263e2f64,
  0x2ea70000,0x263eaf64,0xafd92da8,0x2c722a1f,0xac720000,0xafd92f64,0xa63e2da8,0x2ea7aa1f,0x263e0000,0x2c72aa1f,0x2ea7ada8,0x2fd9af64,
  0x2fd93000,0x2ea72f64,0x2c722da8,0x263e2a1f,0xaea7b000,0x263eaa1f,0x2fd92da8,0x2c722f64,0x2c723000,0xafd9aa1f,0x263eada8,0x2ea72f64,
  0xa63eb000,0x2c722f64,0xaea7ada8,0x2fd92a1f,0xa63e3000,0x2c72af64,0xaea72da8,0x2fd9aa1f,0x2c72b000,0xafd92a1f,0x263e2da8,0x2ea7af64,
  0xaea73000,0x263e2a1f,0x2fd9ada8,0x2c72af64,0x2fd9b000,0x2ea7af64,0x2c72ada8,0x263eaa1f,0x263e0000,0x2c72aa1f,0x2ea7ada8,0x2fd9af64,
  0xac720000,0xafd92f64,0xa63e2da8,0x2ea7aa1f,0x2ea70000,0x263eaf64,0xafd92da8,0x2c722a1f,0xafd90000,0x2ea72a1f,0xac72ada8,0x263e2f64,
  0x2fd90000,0xaea72a1f,0x2c72ada8,0xa63e2f64,0xaea70000,0xa63eaf64,0x2fd92da8,0xac722a1f,0x2c720000,0x2fd92f64,0x263e2da8,0xaea7aa1f,
  0xa63e0000,0xac72aa1f,0xaea7ada8,0xafd9af64,0xafd93000,0xaea72f64,0xac722da8,0xa63e2a1f,0x2ea7b000,0xa63eaa1f,0xafd92da8,0xac722f64,
  0xac723000,0x2fd9aa1f,0xa63eada8,0xaea72f64,0x263eb000,0xac722f64,0x2ea7ada8,0xafd92a1f,0x263e3000,0xac72af64,0x2ea72da8,0xafd9aa1f,
  0xac72b000,0x2fd92a1f,0xa63e2da8,0xaea7af64,0x2ea73000,0xa63e2a1f,0xafd9ada8,0xac72af64,0xafd9b000,0xaea7af64,0xac72ada8,0xa63eaa1f,
  0xafd9b000,0xaea7af64,0xac72ada8,0xa63eaa1f,0x2ea73000,0xa63e2a1f,0xafd9ada8,0xac72af64,0xac72b000,0x2fd92a1f,0xa63e2da8,0xaea7af64,
  0x263e3000,0xac72af64,0x2ea72da8,0xafd9aa1f,0x263eb000,0xac722f64,0x2ea7ada8,0xafd92a1f,0xac723000,0x2fd9aa1f,0xa63eada8,0xaea72f64,
  0x2ea7b000,0xa63eaa1f,0xafd92da8,0xac722f64,0xafd93000,0xaea72f64,0xac722da8,0xa63e2a1f,0xa63e0000,0xac72aa1f,0xaea7ada8,0xafd9af64,
  0x2c720000,0x2fd92f64,0x263e2da8,0xaea7aa1f,0xaea70000,0xa63eaf64,0x2fd92da8,0xac722a1f,0x2fd90000,0xaea72a1f,0x2c72ada8,0xa63e2f64,
  0xafd90000,0x2ea72a1f,0xac72ada8,0x263e2f64,0x2ea70000,0x263eaf64,0xafd92da8,0x2c722a1f,0xac720000,0xafd92f64,0xa63e2da8,0x2ea7aa1f,
  0x263e0000,0x2c72aa1f,0x2ea7ada8,0x2fd9af64,0x2fd9b000,0x2ea7af64,0x2c72ada8,0x263eaa1f,0xaea73000,0x263e2a1f,0x2fd9ada8,0x2c72af64,
  0x2c72b000,0xafd92a1f,0x263e2da8,0x2ea7af64,0xa63e3000,0x2c72af64,0xaea72da8,0x2fd9aa1f,0xa63eb000,0x2c722f64,0xaea7ada8,0x2fd92a1f,
  0x2c723000,0xafd9aa1f,0x263eada8,0x2ea72f64,0xaea7b000,0x263eaa1f,0x2fd92da8,0x2c722f64,0x2fd93000,0x2ea72f64,0x2c722da8,0x263e2a1f,
  0x263e0000,0x2c72aa1f,0x2ea7ada8,0x2fd9af64,0xac720000,0xafd92f64,0xa63e2da8,0x2ea7aa1f,0x2ea70000,0x263eaf64,0xafd92da8,0x2c722a1f,
  0xafd90000,0x2ea72a1f,0xac72ada8,0x263e2f64,0x2fd90000,0xaea72a1f,0x2c72ada8,0xa63e2f64,0xaea70000,0xa63eaf64,0x2fd92da8,0xac722a1f,
  0x2c720000,0x2fd92f64,0x263e2da8,0xaea7aa1f,0xa63e0000,0xac72aa1f,0xaea7ada8,0xafd9af64,0x316c2fbd,0x343e32f7,0x35bc34ff,0x372c3676,
  0x371532c6,0x3a81392e,0x3bef3b71,0x3b7c3bf2,0x397034cf,0x3bfc3b6c,0x38b23b04,0xb40e31e8,0x3ae13631,0x39e73bf5,0xb6e83219,0xbbe8bb13,
  0x3bc23785,0x30be3aa9,0xbbfdb911,0x2a16b9aa,0x3bfe3865,0xb80f37a6,0xb82abc00,0x3bfd376f,0x3b9238fd,0xbb7f2311,0x3805b929,0x31223bde,
  0x3a85398b,0xbb96b742,0x3bff319e,0xbbb82f8b,0xbbe2bbf1,0xbbb7bbcf,0xbb78bb9a,0xbb27bb52,0xbb2cbbd2,0xb8a8ba19,0xb029b5df,0x35a52f59,
  0xb9dfbba1,0x2ba7b5f7,0x3a7a37b2,0x3bbd3bdd,0xb815bb60,0x39662e91,0x3b373bda,0xb0d7377a,0xb3d3bb10,0x3be9386f,0x2a7a3a31,0xbbfeb9a6,
  0x294dbab0,0x3ae53b07,0xbad51fdb,0xab43bb16,0x352fba41,0x35993c00,0xbaebba1d,0x3be531cf,0x38a3b9c5,0xb5173b21,0x2776bbe0,0x34323bf2,
  0x384537dd,0x38ea3899,0x39823937,0x3a0d39c9,0x39463a93,0x3340374e,0xb426a452,0xb979b7c8,0xbb45b924,0xbb32bc00,0xb371b902,0x38d63294,
  0xb08db9a1,0x3b3f379b,0x39583bd7,0xb8252dfb,0x3bea3a2d,0xb3ba3874,0xbb89bb0d,0x36d2b625,0xb6bb387f,0xb8d1bbf5,0x3be73602,0xb546391f,
  0xba00bb01,0x3bff35eb,0xba5c34db,0x3359bab6,0x3ac7b66b,0xb9413933,0x368dbabd,0xb0103bb3,0xbac4baf7,0xba50ba8c,0xb9cdba11,0xb93cb986,
  0x3a04388e,0x3bcb3b1e,0x3bba3c00,0x39d63afe,0x36af3a21,0xb6ffa17f,0xbbc8ba3d,0xba60bbd4,0xbbebb9af,0xb6c6bb0a,0x39f43263,0x3ad83bf7,
  0x30a6b916,0x3bc33aa5,0xb55e3790,0xbb3dbb63,0x3b423a9e,0xba642ec3,0xb0f0bb6a,0x3b8e3a25,0xb94a37bd,0x2884bb6f,0x38db3b9f,0xbbc9b85a,
  0xb840bb54,0x3a093a15,0xbb4cb850,0x3bef3457,0x3a893a4d,0x3af43ac1,0x3b4f3b24,0x3b983b76,0xbb94baba,0xbbe4bbf9,0xba58bb57,0xb699b8f8,
  0x3bfe3b18,0x394f3b5c,0xb109347b,0xbae8b884,0xbbc0bb68,0xa9b1b90c,0x3b8b387a,0x38bc3ba5,0x3ade3ba7,0xb8c1324b,0xb9f0bbf6,0x39eb9648,
  0xb96bbbd6,0x3bbf3487,0xb38939b3,0xb9f8bba3,0x370a3bf3,0xbb47b994,0x3bbc2d65,0xb8ad3889,0xb153bc00,0x37213b9c,0xb97dba90,0x3af138f3,
  0xb89eb8ee,0xb7e8b84a,0xb682b737,0xb50bb5c8,0x35233855,0xb13b2d33,0xb8e0b65f,0xbb4aba45,0xa8e8b764,0x39fc3648,0x3be63bae,0x380a3a9b,
  0xb3eb360e,0xbbfeba35,0xb552baa2,0x3a7334b7,0x381ab4ab,0x3a6f3bd8,0xb95d2e5f,0xb962bc00,0xb9e3327c,0xb402bbac,0x3bc6399d,0xb95434c3,
  0x3b2faf27,0xb6a439bc,0xb41abbf9,0x3a7e3a97,0xbbe3251b,0x3b2ab4f3,0xb9d23894,0x37f3ba49,0x3bce3bb5,0x3bf03be1,0x3bff3bfa,0x3bfb3bff,
  0x2c38b1b6,0x383a34e7,0x3aee39c0,0x3bff3bb2,0xbb81bbf8,0xb53ab999,0x38302ef5,0x3bed3ab3,0xb8cc9cb6,0xbb85bbab,0x2adeb86a,0x3bc5391b,
  0x38c73bf6,0xbadbb232,0xb6ddbba9,0x3b87361a,0x3b833201,0xb0743a39,0xba76bb5e,0x3b352dc9,0xac06bbb0,0x39743b59,0xbbeeb759,0x3aceb2ad,
  0xbbccb5d4,0x3bfb2d00,0xbb7a32de,0x3a54b7d2,0xb30fb44b,0xafefb185,0xa6adacce,0x2c9c25e4,0xbbfcbbdf,0xbacbbb9e,0xb7feb990,0xa81fb463,
  0xb58d2d97,0xbb90b9b8,0xbad1bbf4,0xb05bb85f,0x3a673c00,0xb5763493,0xbbfdbaac,0xb3a2ba29,0x3a6b2e2d,0x38203bd9,0xbb3ab49f,0xb56abb65,
  0xb581bbdc,0x3bec3907,0xb8b7363c,0xb6f4bbf8,0xbbfcb46f,0x39dab654,0xb0423b1b,0xb835bbd3,0xb3283b73,0xac6abbfa,0x35b13bd0,0xb8e5bafb,
  0x38ee3a0d,0xb84aba89,0x37373af4,0xb5c8bb4f,0x35df3a81,0x2f59bbef,0xb88e3b7c,0x3b1eb946,0x2d973ae8,0x39b8bb81,0xbbf4353a,0x385f3830,
  0xb2633b3f,0x3bf7b958,0xb60eb825,0xba353bc0,0xb7853b87,0x3aa9b3d3,0x3911bbe9,0xb9aa2a7a,0xb99d3bbf,0x34c33389,0x3bdcb9f8,0x3907bb83,
  0xbb013be5,0xb5eb394a,0x34db2884,0x3ab6b8db,0xbbd03bfb,0xbafb3b7a,0xb98b3a54,0xb74238a3,0x3a4db93c,0xbac1389e,0x3b24b7e8,0xbb763682,
  0x3b71b8a8,0xbbf23029,0x3a9335a5,0xb74eba04,0x3bf8b80a,0xb999b58d,0xaef53b90,0x3ab3bad1,0x3bd7b6c6,0xadfbb9f4,0xbb683ad8,0x390c33eb,
  0x3b10b56a,0x386fbbc2,0xba3130be,0xb9a63bfd,0x39b3b402,0x3ba3bbc6,0x3201b954,0xba393581,0x37bdb122,0x3b6fba00,0x3b9fbbff,0x385aba5c,
  0x32deac6a,0x37d2b5b1,0x39c5b8e5,0x3b21ba85,0x344b3b98,0xb185bbce,0x2cce3bf0,0x25e4bbff,0xbc003340,0x3afe3426,0xb855b979,0x2d333b94,
  0x34cfbbed,0xbb6c39df,0x3b042ba7,0xb1e8ba7a,0x3aa2a9b1,0x34b7bb8b,0xbc0038bc,0x349338cc,0xba2d3bfe,0x387430a6,0x3b0dbbc3,0xb625b55e,
  0xb63cb074,0xbbf83a76,0xb8653b35,0x37a6294d,0x3bf3bbc9,0x3994bb2f,0x2d65b6a4,0xb889341a,0xb19e3517,0x2f8b2776,0x366bb432,0x3933b840,
  0x3bb5b50b,0xbbe1330f,0x3bfaafef,0xbbff26ad,0xa4523bcb,0x37c8bbba,0xbaba39d6,0x3bf9b523,0xbba1305b,0x35f73970,0x37b2bbfc,0xbbdd38b2,
  0x387abbfe,0xbba53552,0x9cb63a73,0x3babba67,0x39162a16,0x3aa5bbea,0xb790b3ba,0xbb633b89,0xbb5e3bec,0xadc938b7,0x3ab0b6f4,0x3b07bbfe,
  0xaf27b359,0xb9bc370a,0xbbf93b47,0xba973bbc,0x3be0bb96,0x3bf2bbff,0x3b54bbb8,0x3a15bac7,0xafbd3bfb,0x32f7bbe2,0xb4ff3bb7,0x3676bb78,
  0x365fbbe4,0xba453a58,0x3bdfb699,0xbb9eac38,0xb9243bbd,0x3c00b6af,0xb902b6ff,0xb2943bc8,0x3aacbb85,0xba29aade,0xb6313bc5,0x3bf5b815,
  0xbba73b3d,0x324b381a,0x3bf6ba6f,0x9648b95d,0x3c00bae5,0x376fbad5,0xb87f2b43,0xbbf53b42,0xbbb03a7e,0xbb593bfc,0xb75939da,0x32ad3042,
  0x3abdba09,0x3bb3bb4c,0x3c00bbef,0x3b9cbbe3,0x3bf12c9c,0xbbcfb16c,0x3b9a343e,0xbb52b5bc,0xbb57b13b,0x38f838e0,0xb1b6bb4a,0xb4e73bfc,
  0x3a21340e,0x217fbb45,0xba3d3b32,0x3bd4b371,0xb86ab576,0xb91b3bfd,0x3b60b3a2,0x2e91bae1,0x34ab36d2,0x3bd8bade,0xae5fb8c1,0xbc0039f0,
  0x9fdbb80f,0xbb16382a,0xba9e3bfd,0x2ec336bb,0xb46f38ad,0x3654ac06,0x3b1bb974,0x3bd3bbee,0x3850b941,0x3457b68d,0xa51bb010,0xb4f33153,
  0xb7dd3b27,0x3899bac4,0xb9373a50,0x39c9b9cd,0x3990383a,0xb463baee,0xb2c63bff,0x392ebb2c,0x3b18ba60,0xbb5c28e8,0x347b39fc,0x3884bbe6,
  0xb219b966,0xbb133b37,0x39a130d7,0x379bbbeb,0xbbf63962,0xb2323a6b,0x3ba9b820,0x361abb3a,0xb6023a64,0x391fb0f0,0x3bd6bb8e,0x3487b9e3,
  0x3a41b835,0x3c00bb92,0x3a1dbb7f,0x31cfb805,0x3a90bb2a,0x38f3b9d2,0x35d4b7f3,0x2d00b328,0x3af7372c,0xba8cb845,0x3a1138ea,0xb986b982,
  0x39c0bacb,0xbbb237fe,0x3bd2a81f,0xba19b715,0xb764b8d6,0xb6483bfe,0x3baeb94f,0xba9bb109,0xbbda39e7,0x377a36e8,0x39afbbe8,0xbb0a308d,
  0xae2d39eb,0x3bd9b8c7,0x349fbadb,0xbb6536dd,0x3b6ab8d1,0x3a25bbe7,0xb27cb546,0xbbac396b,0x38fdbace,0xa311b52f,0xb9293599,0xbbde3aeb,
  0xb8943721,0xba49397d,0xbb733af1,0xbbfa3bcc,0xbbfb3bff,0xbbe23bf1,0xbbb73bcf,0xbb783b9a,0xbb7c3bf2,0xb9463a93,0xb340374e,0x3426a452,
  0xba603bd4,0xa8e83764,0x39fcb648,0x3be6bbae,0xb8bc3ba5,0x38cc9cb6,0x3b85bbab,0xaadeb86a,0xb56a3b65,0x3bc2b785,0x30bebaa9,0xbbfd3911,
  0xab433b16,0x3b42ba9e,0xba64aec3,0xb0f03b6a,0x33593ab6,0x370abbf3,0xbb473994,0x3bbcad65,0x37f33a49,0xb328bb73,0xac6a3bfa,0x35b1bbd0,
  0xac9c25e4,0xb16c2fbd,0xb43e32f7,0xb5bc34ff,0xb5a52f59,0xba04388e,0xbbcb3b1e,0xbbba3c00,0xb8d63294,0xbbfe3b18,0xb94f3b5c,0x3109347b,
  0xba7334b7,0xba673c00,0x35763493,0x3bfdbaac,0xbb87361a,0xb3d33b10,0x3be9b86f,0x2a7aba31,0xbbfd376f,0x36bb387f,0x38d1bbf5,0xbbe73602,
  0xbbc9385a,0x3b2f2f27,0xb6a4b9bc,0xb41a3bf9,0xbaf138f3,0x3bccb5d4,0xbbfb2d00,0x3b7a32de,0xbb273b52,0xbac43af7,0xba503a8c,0xb9cd3a11,
  0x3979b7c8,0x3b94baba,0x3be4bbf9,0x3a58bb57,0x380aba9b,0xb58dad97,0xbb9039b8,0xbad13bf4,0xbbc5391b,0xb8153b60,0x3966ae91,0x3b37bbda,
  0x2a1639aa,0x3beaba2d,0xb3bab874,0xbb893b0d,0x3b8eba25,0xb9e3b27c,0xb4023bac,0x3bc6b99d,0xb8adb889,0xac063bb0,0x3974bb59,0xbbee3759,
  0xb8e53afb,0x3a85b98b,0xbb963742,0x3bffb19e,0xb72c3676,0xb84537dd,0xb8ea3899,0xb9823937,0xb9d63afe,0xb5233855,0x313b2d33,0x38e0b65f,
  0x3ae8b884,0x3b81bbf8,0x353ab999,0xb8302ef5,0x33a2ba29,0xbae13631,0xb9e73bf5,0x36e83219,0xbbfe39a6,0x30a63916,0x3bc3baa5,0xb55eb790,
  0x3546391f,0x396bbbd6,0xbbbf3487,0x338939b3,0x3a7eba97,0xbbfc346f,0x39da3654,0xb042bb1b,0xba54b7d2,0x38a339c5,0xb517bb21,0x27763be0,
  0xb93c3986,0xb89e38ee,0xb7e8384a,0xb6823737,0x3699b8f8,0xac38b1b6,0xb83a34e7,0xbaee39c0,0xb05b385f,0x3970b4cf,0x3bfcbb6c,0x38b2bb04,
  0xb0d7b77a,0xbbeb39af,0xb6c63b0a,0x39f4b263,0x36d23625,0x3adebba7,0xb8c1b24b,0xb9f03bf6,0xb954b4c3,0xb5813bdc,0x3becb907,0xb8b7b63c,
  0x3ace32ad,0xb52fba41,0xb5993c00,0x3aebba1d,0xbbb8af8b,0x3ac7366b,0xb941b933,0x368d3abd,0xba0d39c9,0xba893a4d,0xbaf43ac1,0xbb4f3b24,
  0x3b4aba45,0x3bfcbbdf,0x3acbbb9e,0x37feb990,0xbbed3ab3,0xb9df3ba1,0x2ba735f7,0x3a7ab7b2,0x3be8bb13,0x308db9a1,0xbb3f379b,0xb9583bd7,
  0xbb3d3b63,0x381a34ab,0x3a6fbbd8,0xb95dae5f,0x39f8bba3,0xbb833201,0x30743a39,0x3a76bb5e,0xb8353bd3,0x3b92b8fd,0xbb7fa311,0x38053929,
  0x3432bbf2,0xb8403b54,0x3a09ba15,0xbb4c3850,0xb50b35c8,0xb30f344b,0xafef3185,0xa6ad2cce,0xbbff3bb2,0xbb2c3bd2,0xb8a83a19,0xb02935df,
  0xb40eb1e8,0xbb453924,0xbb323c00,0xb3713902,0x3ad8bbf7,0xb3ebb60e,0xbbfe3a35,0xb5523aa2,0x39eb1648,0x38c7bbf6,0xbadb3232,0xb6dd3ba9,
  0xb6f43bf8,0x3bfeb865,0xb80fb7a6,0xb82a3c00,0xbbe531cf,0x394a37bd,0xa884bb6f,0xb8db3b9f,0xb010bbb3,0xb1533c00,0x3721bb9c,0xb97d3a90,
  0xbb983b76,0xbbce3bb5,0xbbf03be1,0xbbff3bfa,0x281fb463,0xb71532c6,0xba81392e,0xbbef3b71,0x3bbdbbdd,0x36afba21,0xb6ff217f,0xbbc83a3d,
  0x38252dfb,0x3bc0bb68,0x29b1b90c,0xbb8b387a,0xb9623c00,0x3a6bae2d,0x3820bbd9,0xbb3a349f,0xbb352dc9,0x294d3ab0,0x3ae5bb07,0xbad59fdb,
  0x3122bbde,0xba003b01,0x3bffb5eb,0xba5cb4db,0x3befb457,0xbbe3a51b,0x3b2a34f3,0xb9d2b894,0x39c939cd,0xba4db93c,0x3ac1389e,0xbb24b7e8,
  0x3b1e3946,0xbc00b340,0x3afeb426,0xb8553979,0x3bdd38b2,0xba21340e,0xa17fbb45,0x3a3d3b32,0x3bf53815,0xb2193966,0xbb13bb37,0x39a1b0d7,
  0x3b6536dd,0x37853b87,0xbaa9b3d3,0xb911bbe9,0x3a393581,0x3b5e3bec,0x2dc938b7,0xbab0b6f4,0x3889341a,0x3bb03a7e,0x3b593bfc,0x375939da,
  0x34f33153,0x38943721,0x3a49397d,0x3b733af1,0xb9863982,0x38eeba0d,0xb84a3a89,0x3737baf4,0xb74e3a04,0xa452bbcb,0x37c83bba,0xbabab9d6,
  0xb1e83a7a,0xb924bbbd,0x3c0036af,0xb90236ff,0x2e913ae1,0xbbdab9e7,0x377ab6e8,0x39af3be8,0x361a3b3a,0xbb10b56a,0xb86fbbc2,0x3a3130be,
  0x39073b83,0xb63c3074,0xbbf8ba76,0xb865bb35,0x3a973bbc,0x346f38ad,0xb654ac06,0xbb1bb974,0x3b9c3be3,0x3a903b2a,0x38f339d2,0x35d437f3,
  0x3b763682,0xbbb5b50b,0x3be1330f,0xbbfaafef,0x2d33bb94,0x365f3be4,0xba45ba58,0x3bdf3699,0xbbd4b371,0x3764b8d6,0x36483bfe,0xbbaeb94f,
  0x379b3beb,0xbbd7b6c6,0x2dfbb9f4,0x3b683ad8,0x39aa2a7a,0x3a2d3bfe,0xb87430a6,0xbb0dbbc3,0xbb07bbfe,0x1fdbb80f,0x3b16382a,0x3a9e3bfd,
  0xb2ad3042,0xba41b835,0xbc00bb92,0xba1dbb7f,0x3bfa3bcc,0x3bd03bfb,0x3afb3b7a,0x398b3a54,0xb5c83b4f,0x344bbb98,0xb1853bce,0x2ccebbf0,
  0x3bf93523,0xbb57313b,0x38f8b8e0,0xb1b63b4a,0xb294bbc8,0x3b183a60,0xbb5ca8e8,0x347bb9fc,0xbb0ab08d,0xb263bb3f,0x3bf73958,0xb60e3825,
  0x39a63bfd,0xb9162a16,0xbaa5bbea,0x3790b3ba,0x37a6a94d,0x3c003ae5,0x376f3ad5,0xb87fab43,0xbbd3bbee,0xb8fdbace,0x2311b52f,0x39293599,
  0x2d003328,0xb2deac6a,0xb7d2b5b1,0xb9c5b8e5,0x3bff26ad,0xbbf12c9c,0x3bcfb16c,0xbb9a343e,0xbb9e2c38,0x3990b83a,0xb4633aee,0xb2c6bbff,
  0x3a9bb109,0xad973ae8,0xb9b8bb81,0x3bf4353a,0xb90c33eb,0xb87abbfe,0x3ba53552,0x1cb63a73,0x3625b55e,0x3ba73b3d,0xb24b381a,0xbbf6ba6f,
  0xaec336bb,0xbb6ab8d1,0xba25bbe7,0x327cb546,0xb1cfb805,0x37bd3122,0x3b6f3a00,0x3b9f3bff,0x374238a3,0x319e3517,0xaf8b2776,0xb66bb432,
  0x25e43bff,0xafbdbbfb,0x32f73be2,0xb4ffbbb7,0xb4e7bbfc,0x39c03acb,0xbbb2b7fe,0x3bd2281f,0x38843be6,0xbbf8b80a,0x3999b58d,0x2ef53b90,
  0xba35bbc0,0x3aa229b1,0x34b73b8b,0xbc00b8bc,0x3b633b89,0xb4ab36d2,0xbbd8bade,0x2e5fb8c1,0xbbf5bb42,0xb602ba64,0x391f30f0,0x3bd63b8e,
  0x3bde3aeb,0x3b013be5,0x35eb394a,0xb4db2884,0xbb21ba85,0xbbe0bb96,0xbbf2bbff,0xbb54bbb8,0x3b52b5bc,0xbaf7372c,0x3a8cb845,0xba1138ea,
  0x392e3b2c,0xbb71b8a8,0x3bf23029,0xba9335a5,0xb85f3830,0xb4cfbbed,0x3b6c39df,0xbb042ba7,0xbbabba67,0x386ab576,0x391b3bfd,0xbb60b3a2,
  0x1648b95d,0x3bf63962,0x32323a6b,0xbba9b820,0x3bac396b,0x399d3bbf,0xb4c33389,0xbbdcb9f8,0x385a3a5c,0xaf273359,0xb9bcb70a,0xbbf9bb47,
  0xb933b840,0xbabdba09,0xbbb3bb4c,0xbc00bbef,0x36763b78,0xb7ddbb27,0x38993ac4,0xb937ba50,0xba193715,0x35dfba81,0x2f593bef,0xb88ebb7c,
  0xbab3bad1,0x3ba1305b,0xb5f73970,0xb7b2bbfc,0x3493b8cc,0x3aac3b85,0xba292ade,0xb631bbc5,0x3c0039f0,0x2e2d39eb,0xbbd9b8c7,0xb49fbadb,
  0x348739e3,0xb9b3b402,0xbba3bbc6,0xb201b954,0xbab6b8db,0xbbf3bbc9,0xb994bb2f,0xad65b6a4,0xba15bac7,0xb850b941,0xb457b68d,0x251bb010,
  0xb9cfbb16,0x30ac2a31,0x3b9c3bf1,0xb493ae2d,0xb76fb8b4,0x35a133e3,0x3a1d3afe,0xb902b76f,0xb3e3b5a1,0x38b4376f,0x376f3902,0xbafeba1d,
  0xaa31b0ac,0x3b1639cf,0x2e2d3493,0xbbf1bb9c,0xb956ba74,0x305f29cc,0x3b633bd2,0xb44badc9,0xb6e7b859,0x353f335e,0x39d23ab6,0xb8bcb6ff,
  0xb35eb53f,0x385936e7,0x36ff38bc,0xbab6b9d2,0xa9ccb05f,0x3a743956,0x2dc9344b,0xbbd2bb63,0xb8e3b9de,0x30122967,0x3b1e3ba1,0xb402ad65,
  0xb662b801,0x34de32da,0x39823a67,0xb874b68d,0xb2dab4de,0x38013662,0x368d3874,0xba67b982,0xa967b012,0x39de38e3,0x2d653402,0xbba1bb1e,
  0xb876b952,0x2f8c2902,0x3ace3b60,0xb371ad00,0xb5e1b758,0x347e3257,0x392e3a11,0xb82ab61a,0xb257b47e,0x375835e1,0x361a382a,0xba11b92e,
  0xa902af8c,0x39523876,0x2d003371,0xbb60bace,0xb80db8ce,0x2ef3289e,0x3a733b10,0xb2deac9c,0xb562b6b3,0x342031d5,0x38d639b3,0xb7bdb5a5,
  0xb1d5b420,0x36b33562,0x35a537bd,0xb9b3b8d6,0xa89eaef3,0x38ce380d,0x2c9c32de,0xbb10ba73,0xb750b851,0x2e5a2839,0x3a0d3ab0,0xb24bac38,
  0xb4e5b613,0x33863153,0x387a394f,0xb721b52f,0xb153b386,0x361334e5,0x352f3721,0xb94fb87a,0xa839ae5a,0x38513750,0x2c38324b,0xbab0ba0d,
  0xb68eb7b4,0x2dc227a9,0x399d3a41,0xb1b6aba7,0xb46ab577,0x32cd30d2,0x381a38e5,0xb682b4b7,0xb0d2b2cd,0x3577346a,0x34b73682,0xb8e5b81a,
  0xa7a9adc2,0x37b4368e,0x2ba731b6,0xba41b99d,0xb5d2b6d1,0x2d2a26e0,0x392439c5,0xb122aade,0xb3e3b4de,0x32163052,0x376f3874,0xb5dfb43e,
  0xb052b216,0x34de33e3,0x343e35df,0xb874b76f,0xa6e0ad2a,0x36d135d2,0x2ade3122,0xb9c5b924,0xb51cb5f6,0x2c932617,0x38a3393c,0xb08daa16,
  0xb2f4b448,0x31602fa5,0x36a437fe,0xb53ab389,0xafa5b160,0x344832f4,0x3389353a,0xb7feb6a4,0xa617ac93,0x35f6351c,0x2a16308d,0xb93cb8a3,
  0xb46ab523,0x2bf6254d,0x381a38a8,0xafefa94d,0xb209b36b,0x30ac2ea7,0x35d4370a,0xb493b294,0xaea7b0ac,0x336b3209,0x32943493,0xb70ab5d4,
  0xa54dabf6,0x3523346a,0x294d2fef,0xb8a8b81a,0xb378b456,0x2ac82484,0x3715380a,0xaec3a884,0xb120b24a,0x2ff22da9,0x34ff360e,0xb3d3b19e,
  0xada9aff2,0x324a3120,0x319e33d3,0xb60eb4ff,0xa484aac8,0x34563378,0x28842ec3,0xb80ab715,0xb223b31c,0x29992376,0x35eb36c6,0xad97a776,
  0xb039b12d,0x2e8d2cac,0x3426350b,0xb27cb0a6,0xacacae8d,0x312d3039,0x30a6327c,0xb50bb426,0xa376a999,0x331c3223,0x27762d97,0xb6c6b5eb,
  0xb0d2b194,0x286b21e4,0x34b7356a,0xac6aa5e4,0xaea7b012,0x2d2a2b5f,0x32943402,0xb122af59,0xab5fad2a,0x30122ea7,0x2f593122,0xb402b294,
  0xa1e4a86b,0x319430d2,0x25e42c6a,0xb56ab4b7,0xaf0cb012,0x267b2052,0x32f73402,0xaa7aa452,0xacdeadf5,0x2b912967,0x30d731e8,0xaf8bad65,
  0xa967ab91,0x2df52cde,0x2d652f8b,0xb1e8b0d7,0xa052a67b,0x30122f0c,0x24522a7a,0xb402b2f7,0xac79ad2a,0x24201d7f,0x30743122,0xa81fa17f,
  0xaa31ab91,0x28d026e0,0x2e2d2f8b,0xacceaade,0xa6e0a8d0,0x2b912a31,0x2ade2cce,0xaf8bae2d,0x9d7fa420,0x2d2a2c79,0x217f281f,0xb122b074,
  0xa7a9a86b,0x1f1218b6,0x2ba72c6a,0xa3119cb6,0xa54da67b,0x242021e4,0x294d2a7a,0xa81fa5e4,0xa1e4a420,0x267b254d,0x25e4281f,0xaa7aa94d,
  0x98b69f12,0x286b27a9,0x1cb62311,0xac6aaba7,0x211b21e4,0x98b69248,0xa51ba5e4,0x1cb61648,0x1f122052,0x9d7f9bdb,0xa311a452,0x217f1fdb,
  0x1bdb1d7f,0xa0529f12,0x9fdba17f,0x24522311,0x124818b6,0xa1e4a11b,0x96489cb6,0x25e4251b,0x2a632b5f,0xa1e49bdb,0xae5faf59,0x25e41fdb,
  0x286b2967,0xa6e0a4e9,0xac6aad65,0x2ade28e8,0x24e926e0,0xa967a86b,0xa8e8aade,0x2d652c6a,0x1bdb21e4,0xab5faa63,0x9fdba5e4,0x2f592e5f,
  0x2dc22ea7,0xa54d9f12,0xb1b6b294,0x294d2311,0x2bf62cde,0xaa31a86b,0xafefb0d7,0x2e2d2c6a,0x286b2a31,0xacdeabf6,0xac6aae2d,0x30d72fef,
  0x1f12254d,0xaea7adc2,0xa311a94d,0x329431b6,0x302c30d2,0xa7a9a11b,0xb41ab4b7,0x2ba7251b,0x2dc22f0c,0xac79aa63,0xb1b6b2f7,0x30742e5f,
  0x2a632c79,0xaf0cadc2,0xae5fb074,0x32f731b6,0x211b27a9,0xb0d2b02c,0xa51baba7,0x34b7341a,0x317a3257,0xa902a2ad,0xb552b61a,0x2d0026ad,
  0x2f8c309f,0xaddcac2e,0xb371b487,0x31cf3029,0x2c2e2ddc,0xb09faf8c,0xb029b1cf,0x34873371,0x22ad2902,0xb257b17a,0xa6adad00,0x361a3552,
  0x32cd33e3,0xaa31a420,0xb682b76f,0x2e2d281f,0x30ac31bb,0xaf3fad2a,0xb493b58d,0x33283122,0x2d2a2f3f,0xb1bbb0ac,0xb122b328,0x358d3493,
  0x24202a31,0xb3e3b2cd,0xa81fae2d,0x376f3682,0x341334bc,0xab5fa4e9,0xb7a6b85a,0x2f5928e8,0x319432da,0xb052ae28,0xb56ab68d,0x343e3219,
  0x2e283052,0xb2dab194,0xb219b43e,0x368d356a,0x24e92b5f,0xb4bcb413,0xa8e8af59,0x385a37a6,0x34c3358c,0xac47a5b2,0xb85fb8f3,0x304229b1,
  0x327e33fd,0xb106af26,0xb63cb785,0x34e7330f,0x2f263106,0xb3fdb27e,0xb30fb4e7,0x3785363c,0x25b22c47,0xb58cb4c3,0xa9b1b042,0x38f3385f,
  0x35773662,0xacdea67b,0xb8e5b982,0x30d72a7a,0x336b3493,0xb1bbb012,0xb70ab83a,0x358d3402,0x301231bb,0xb493b36b,0xb402b58d,0x383a370a,
  0x267b2cde,0xb662b577,0xaa7ab0d7,0x398238e5,0x36303741,0xad76a744,0xb962ba04,0x316c2b43,0x342e352a,0xb271b092,0xb7d2b8ad,0x3631347b,
  0x30923271,0xb52ab42e,0xb47bb631,0x38ad37d2,0x27442d76,0xb741b630,0xab43b16c,0x3a043962,0x36ee3815,0xae0ea807,0xb9d6ba7a,0x32012c06,
  0x34a735c4,0xb329b113,0xb84ab91b,0x36d234f3,0x31133329,0xb5c4b4a7,0xb4f3b6d2,0x391b384a,0x28072e0e,0xb815b6ee,0xac06b201,0x3a7a39d6,
  0x37b4388e,0xaea7a86b,0xba41bae1,0x32942c6a,0x35233662,0xb3e3b194,0xb8a8b982,0x376f356a,0x319433e3,0xb662b523,0xb56ab76f,0x398238a8,
  0x286b2ea7,0xb88eb7b4,0xac6ab294,0x3ae13a41,0x3841390f,0xaf3fa8d0,0xbaa2bb3a,0x33282cce,0x35a13705,0xb44fb216,0xb902b9e3,0x380535df,
  0x3216344f,0xb705b5a1,0xb5dfb805,0x39e33902,0x28d02f3f,0xb90fb841,0xacceb328,0x3b3a3aa2,0x38ac3997,0xafd8a935,0xbaf7bb83,0x33ba2d33,
  0x362137ac,0xb4aeb298,0xb958ba3d,0x38503654,0x329834ae,0xb7acb621,0xb654b850,0x3a3d3958,0x29352fd8,0xb997b8ac,0xad33b3ba,0x3b833af7,
  0x391c3a28,0xb039a999,0xbb42bbbc,0x34262d97,0x36a4382d,0xb50eb31c,0xb9aaba90,0x389936c6,0x331c350e,0xb82db6a4,0xb6c6b899,0x3a9039aa,
  0x29993039,0xba28b91c,0xad97b426,0x3bbc3b42,0x39923ac3,0xb085a9fe,0xbb81bbe3,0x346f2dfb,0x372a3886,0xb570b3a0,0xb9f8badb,0x38e03737,
  0x33a03570,0xb886b72a,0xb737b8e0,0x3adb39f8,0x29fe3085,0xbac3b992,0xadfbb46f,0x3be33b81,
};

#define PROF(slot) do {} while (0)
#define PROF_DUMP() do {} while (0)
#define PROFA(slot, dep) do {} while (0)
#define PROF3(slot) do {} while (0)
#define PROF2(slot) do {} while (0)

__device__ __forceinline__ uint32_t smem_u32(const void* p) { return (uint32_t)__cvta_generic_to_shared(p); }

__device__ __forceinline__ void mbar_init(uint32_t a, uint32_t c) {
  asm volatile("mbarrier.init.shared::cta.b64 [%0], %1;\n" ::"r"(a), "r"(c) : "memory");
}
__device__ __forceinline__ void mbar_expect_tx(uint32_t a, uint32_t bytes) {
  asm volatile("mbarrier.arrive.expect_tx.shared::cta.b64 _, [%0], %1;\n" ::"r"(a), "r"(bytes) : "memory");
}
__device__ __forceinline__ void mbar_arrive_cluster(uint32_t cluster_addr) {
  asm volatile("mbarrier.arrive.shared::cluster.b64 _, [%0];\n" ::"r"(cluster_addr) : "memory");
}
__device__ __forceinline__ void mbar_arrive_cluster_n(uint32_t cluster_addr, uint32_t n) {
  asm volatile("mbarrier.arrive.shared::cluster.b64 _, [%0], %1;\n" ::"r"(cluster_addr), "r"(n) : "memory");
}
__device__ __forceinline__ bool mbar_try(uint32_t a, uint32_t parity) {
  uint32_t ok;
  asm volatile("{\n.reg .pred p;\nmbarrier.try_wait.parity.shared::cta.b64 p, [%1], %2;\nselp.u32 %0, 1, 0, p;\n}\n"
               : "=r"(ok) : "r"(a), "r"(parity) : "memory");
  return ok;
}
__device__ __forceinline__ void mbar_wait(uint32_t a, uint32_t parity) {
  if (mbar_try(a, parity)) return;
#pragma unroll 1
  for (int n = 0; n < SPIN_LIMIT; n++)
    if (mbar_try(a, parity)) break;
}
__device__ __forceinline__ bool elect_one() {
  uint32_t p;
  asm volatile("{\n.reg .pred P;\nelect.sync _|P, 0xffffffff;\nselp.u32 %0, 1, 0, P;\n}\n" : "=r"(p));
  return p;
}
__device__ __forceinline__ uint32_t mapa(uint32_t a, uint32_t rank) {
  uint32_t r;
  asm volatile("mapa.shared::cluster.u32 %0, %1, %2;\n" : "=r"(r) : "r"(a), "r"(rank));
  return r;
}
__device__ __forceinline__ void nb_sync(int id, int n) { asm volatile("bar.sync %0, %1;\n" ::"r"(id), "r"(n) : "memory"); }
__device__ __forceinline__ void nb_arrive(int id, int n) { asm volatile("bar.arrive %0, %1;\n" ::"r"(id), "r"(n) : "memory"); }
__device__ __forceinline__ void cluster_sync_all() {
  asm volatile("barrier.cluster.arrive.relaxed.aligned;\nbarrier.cluster.wait.aligned;\n" ::: "memory");
}
__device__ __forceinline__ void fence_async_smem() { asm volatile("fence.proxy.async.shared::cta;\n" ::: "memory"); }
__device__ __forceinline__ void fence_async_all() { asm volatile("fence.proxy.async.global;\n" ::: "memory"); }

__device__ __forceinline__ void tma_load_3d(uint32_t dst, const CUtensorMap* tm, uint32_t bar, int c0, int c1, int c2) {
  asm volatile(
      "cp.async.bulk.tensor.3d.shared::cluster.global.mbarrier::complete_tx::bytes [%0], [%1, {%3, %4, %5}], [%2];\n"
      ::"r"(dst), "l"(tm), "r"(bar), "r"(c0), "r"(c1), "r"(c2) : "memory");
}
__device__ __forceinline__ void tma_load_4d(uint32_t dst, const CUtensorMap* tm, uint32_t bar, int c0, int c1, int c2, int c3) {
  asm volatile(
      "cp.async.bulk.tensor.4d.shared::cluster.global.mbarrier::complete_tx::bytes [%0], [%1, {%3, %4, %5, %6}], [%2];\n"
      ::"r"(dst), "l"(tm), "r"(bar), "r"(c0), "r"(c1), "r"(c2), "r"(c3) : "memory");
}
__device__ __forceinline__ void tma_load_3d_mc(uint32_t dst, const CUtensorMap* tm, uint32_t bar, int c0, int c1, int c2) {
  asm volatile(
      "cp.async.bulk.tensor.3d.shared::cluster.global.mbarrier::complete_tx::bytes.multicast::cluster [%0], [%1, {%3, %4, %5}], [%2], %6;\n"
      ::"r"(dst), "l"(tm), "r"(bar), "r"(c0), "r"(c1), "r"(c2), "h"((uint16_t)3) : "memory");
}
__device__ __forceinline__ void bulk_load(uint32_t dst, const void* src, uint32_t bytes, uint32_t bar) {
  asm volatile("cp.async.bulk.shared::cluster.global.mbarrier::complete_tx::bytes [%0], [%1], %2, [%3];\n"
               ::"r"(dst), "l"(src), "r"(bytes), "r"(bar) : "memory");
}
__device__ __forceinline__ void tma_store_3d(const CUtensorMap* tm, uint32_t src, int c0, int c1, int c2) {
  asm volatile("cp.async.bulk.tensor.3d.global.shared::cta.bulk_group [%0, {%2, %3, %4}], [%1];\n"
               ::"l"(tm), "r"(src), "r"(c0), "r"(c1), "r"(c2) : "memory");
}
__device__ __forceinline__ void bulk_commit() { asm volatile("cp.async.bulk.commit_group;\n" ::: "memory"); }
__device__ __forceinline__ void bulk_wait0() { asm volatile("cp.async.bulk.wait_group 0;\n" ::: "memory"); }
__device__ __forceinline__ void prefetch_tmap(const CUtensorMap* tm) {
  asm volatile("prefetch.tensormap [%0];\n" ::"l"(tm) : "memory");
}

__device__ __forceinline__ void wg_fence() { asm volatile("wgmma.fence.sync.aligned;\n" ::: "memory"); }
__device__ __forceinline__ void wg_commit() { asm volatile("wgmma.commit_group.sync.aligned;\n" ::: "memory"); }
template <int N> __device__ __forceinline__ void wg_wait() {
  asm volatile("wgmma.wait_group.sync.aligned %0;\n" ::"n"(N) : "memory");
}
__device__ __forceinline__ uint64_t mkdesc(uint32_t addr, uint32_t lbo, uint32_t sbo, uint32_t swz) {
  return (uint64_t)((addr & 0x3FFFF) >> 4) | ((uint64_t)(lbo >> 4) << 16) | ((uint64_t)(sbo >> 4) << 32) |
         ((uint64_t)swz << 62);
}

#define R4(d, o) "+f"(d[o + 0]), "+f"(d[o + 1]), "+f"(d[o + 2]), "+f"(d[o + 3])
#define R8(d, o) R4(d, o), R4(d, o + 4)
#define R16(d, o) R8(d, o), R8(d, o + 8)
#define R32(d, o) R16(d, o), R16(d, o + 16)
#define R64(d, o) R32(d, o), R32(d, o + 32)

__device__ __forceinline__ void wgmma_n192(float (&d)[96], uint64_t da, uint64_t db, uint32_t acc) {
  asm volatile(
      "{\n.reg .pred p;\nsetp.ne.u32 p, %98, 0;\n"
      "wgmma.mma_async.sync.aligned.m64n192k16.f32.bf16.bf16 "
      "{%0,%1,%2,%3,%4,%5,%6,%7,%8,%9,%10,%11,%12,%13,%14,%15,%16,%17,%18,%19,%20,%21,%22,%23,%24,%25,%26,%27,%28,%29,%30,%31,"
      "%32,%33,%34,%35,%36,%37,%38,%39,%40,%41,%42,%43,%44,%45,%46,%47,%48,%49,%50,%51,%52,%53,%54,%55,%56,%57,%58,%59,%60,%61,%62,%63,"
      "%64,%65,%66,%67,%68,%69,%70,%71,%72,%73,%74,%75,%76,%77,%78,%79,%80,%81,%82,%83,%84,%85,%86,%87,%88,%89,%90,%91,%92,%93,%94,%95}, "
      "%96, %97, p, 1, 1, 0, 1;\n}\n"
      : R64(d, 0), R32(d, 64)
      : "l"(da), "l"(db), "r"(acc));
}
__device__ __forceinline__ void wgmma_n128(float (&d)[64], uint64_t da, uint64_t db, uint32_t acc) {
  asm volatile(
      "{\n.reg .pred p;\nsetp.ne.u32 p, %66, 0;\n"
      "wgmma.mma_async.sync.aligned.m64n128k16.f32.bf16.bf16 "
      "{%0,%1,%2,%3,%4,%5,%6,%7,%8,%9,%10,%11,%12,%13,%14,%15,%16,%17,%18,%19,%20,%21,%22,%23,%24,%25,%26,%27,%28,%29,%30,%31,"
      "%32,%33,%34,%35,%36,%37,%38,%39,%40,%41,%42,%43,%44,%45,%46,%47,%48,%49,%50,%51,%52,%53,%54,%55,%56,%57,%58,%59,%60,%61,%62,%63}, "
      "%64, %65, p, 1, 1, 0, 1;\n}\n"
      : R64(d, 0)
      : "l"(da), "l"(db), "r"(acc));
}
#define WG128(C, ACC)                                                                                                      \
  asm volatile(                                                                                                            \
      "{\n.reg .b64 a, b;\nmov.b64 a, {%64, %66};\nmov.b64 b, {%65, %66};\n"                                               \
      "wgmma.mma_async.sync.aligned.m64n128k16.f32.bf16.bf16 "                                                             \
      "{%0,%1,%2,%3,%4,%5,%6,%7,%8,%9,%10,%11,%12,%13,%14,%15,%16,%17,%18,%19,%20,%21,%22,%23,%24,%25,%26,%27,%28,%29,%30,%31," \
      "%32,%33,%34,%35,%36,%37,%38,%39,%40,%41,%42,%43,%44,%45,%46,%47,%48,%49,%50,%51,%52,%53,%54,%55,%56,%57,%58,%59,%60,%61," \
      "%62,%63}, a, b, " ACC ", 1, 1, 0, 1;\n}\n"                                                                          \
      : Z16(C, d, 0), Z16(C, d, 16), Z16(C, d, 32), Z16(C, d, 48)                                                          \
      : "r"(da), "r"(db), "r"(0x40000040))
#define Z4(C, d, o) C(d[o + 0]), C(d[o + 1]), C(d[o + 2]), C(d[o + 3])
#define Z16(C, d, o) Z4(C, d, o), Z4(C, d, o + 4), Z4(C, d, o + 8), Z4(C, d, o + 12)
__device__ __forceinline__ void wgmma_n128z(float (&d)[64], uint32_t da, uint32_t db) { WG128("=f", "0"); }
__device__ __forceinline__ void wgmma_n128a(float (&d)[64], uint32_t da, uint32_t db) { WG128("+f", "1"); }
template <int N> __device__ __forceinline__ void fence_regs(float (&d)[N]) {
#pragma unroll
  for (int i = 0; i < N; i++) asm volatile("" : "+f"(d[i])::"memory");
}

__device__ __forceinline__ void mma16816(float (&d)[4], uint32_t a0, uint32_t a1, uint32_t a2, uint32_t a3, uint32_t b0,
                                         uint32_t b1) {
  asm("mma.sync.aligned.m16n8k16.row.col.f32.bf16.bf16.f32 {%0,%1,%2,%3}, {%4,%5,%6,%7}, {%8,%9}, {%0,%1,%2,%3};\n"
      : "+f"(d[0]), "+f"(d[1]), "+f"(d[2]), "+f"(d[3])
      : "r"(a0), "r"(a1), "r"(a2), "r"(a3), "r"(b0), "r"(b1));
}
__device__ __forceinline__ void mma16816_z(float (&d)[4], uint32_t a0, uint32_t a1, uint32_t a2, uint32_t a3, uint32_t b0,
                                           uint32_t b1) {
  asm("mma.sync.aligned.m16n8k16.row.col.f32.bf16.bf16.f32 {%0,%1,%2,%3}, {%4,%5,%6,%7}, {%8,%9}, {%10,%10,%10,%10};\n"
      : "=f"(d[0]), "=f"(d[1]), "=f"(d[2]), "=f"(d[3])
      : "r"(a0), "r"(a1), "r"(a2), "r"(a3), "r"(b0), "r"(b1), "f"(0.f));
}
__device__ __forceinline__ void ldsm4t(uint32_t (&r)[4], uint32_t a) {
  asm volatile("ldmatrix.sync.aligned.m8n8.x4.trans.shared.b16 {%0,%1,%2,%3}, [%4];\n"
               : "=r"(r[0]), "=r"(r[1]), "=r"(r[2]), "=r"(r[3]) : "r"(a) : "memory");
}
__device__ __forceinline__ void ldsm2t(uint32_t& r0, uint32_t& r1, uint32_t a) {
  asm volatile("ldmatrix.sync.aligned.m8n8.x2.trans.shared.b16 {%0,%1}, [%2];\n" : "=r"(r0), "=r"(r1) : "r"(a) : "memory");
}
__device__ __forceinline__ void st_async128(uint32_t a, uint32_t bar, uint32_t x, uint32_t y, uint32_t z, uint32_t w) {
  asm volatile("st.async.weak.shared::cluster.mbarrier::complete_tx::bytes.v4.b32 [%0], {%2,%3,%4,%5}, [%1];\n"
               ::"r"(a), "r"(bar), "r"(x), "r"(y), "r"(z), "r"(w) : "memory");
}
__device__ __forceinline__ void mbar_arrive(uint32_t a) {
  asm volatile("mbarrier.arrive.shared::cta.b64 _, [%0];\n" ::"r"(a) : "memory");
}
__device__ __forceinline__ void stsm4(uint32_t a, uint32_t r0, uint32_t r1, uint32_t r2, uint32_t r3) {
  asm volatile("stmatrix.sync.aligned.m8n8.x4.shared.b16 [%0], {%1,%2,%3,%4};\n"
               ::"r"(a), "r"(r0), "r"(r1), "r"(r2), "r"(r3) : "memory");
}
__device__ __forceinline__ void stsm4t(uint32_t a, uint32_t r0, uint32_t r1, uint32_t r2, uint32_t r3) {
  asm volatile("stmatrix.sync.aligned.m8n8.x4.trans.shared.b16 [%0], {%1,%2,%3,%4};\n"
               ::"r"(a), "r"(r0), "r"(r1), "r"(r2), "r"(r3) : "memory");
}
__device__ __forceinline__ uint2 lds64(uint32_t a) {
  uint2 v;
  asm volatile("ld.shared.v2.u32 {%0,%1}, [%2];\n" : "=r"(v.x), "=r"(v.y) : "r"(a));
  return v;
}
__device__ __forceinline__ uint4 lds128(uint32_t a) {
  uint4 v;
  asm volatile("ld.shared.v4.u32 {%0,%1,%2,%3}, [%4];\n" : "=r"(v.x), "=r"(v.y), "=r"(v.z), "=r"(v.w) : "r"(a) : "memory");
  return v;
}
__device__ __forceinline__ void sts128(uint32_t a, uint32_t x, uint32_t y, uint32_t z, uint32_t w) {
  asm volatile("st.shared.v4.u32 [%0], {%1,%2,%3,%4};\n" ::"r"(a), "r"(x), "r"(y), "r"(z), "r"(w) : "memory");
}
__device__ __forceinline__ void sts64(uint32_t a, uint32_t x, uint32_t y) {
  asm volatile("st.shared.v2.u32 [%0], {%1,%2};\n" ::"r"(a), "r"(x), "r"(y) : "memory");
}
__device__ __forceinline__ uint32_t pack_bf16(float lo, float hi) {
  uint32_t r;
  asm("cvt.rn.bf16x2.f32 %0, %1, %2;\n" : "=r"(r) : "f"(hi), "f"(lo));
  return r;
}
__device__ __forceinline__ uint32_t bmul2(uint32_t a, uint32_t b) {
  uint32_t r;
  asm("mul.rn.bf16x2 %0, %1, %2;\n" : "=r"(r) : "r"(a), "r"(b));
  return r;
}
__device__ __forceinline__ uint32_t bmax2(uint32_t a, uint32_t b) {
  uint32_t r;
  asm("max.bf16x2 %0, %1, %2;\n" : "=r"(r) : "r"(a), "r"(b));
  return r;
}
__device__ __forceinline__ uint32_t bfma2(uint32_t a, uint32_t b, uint32_t c) {
  uint32_t r;
  asm("fma.rn.bf16x2 %0, %1, %2, %3;\n" : "=r"(r) : "r"(a), "r"(b), "r"(c));
  return r;
}
__device__ __forceinline__ uint32_t badd2(uint32_t a, uint32_t b) {
  uint32_t r;
  asm("add.rn.bf16x2 %0, %1, %2;\n" : "=r"(r) : "r"(a), "r"(b));
  return r;
}
__device__ __forceinline__ void prefetch_l2(const void* p) { asm volatile("prefetch.global.L2 [%0];\n" ::"l"(p)); }
__device__ __forceinline__ void cp_async16n(uint32_t dst, const void* src) {
  asm volatile("cp.async.cg.shared.global [%0], [%1], 16;\n" ::"r"(dst), "l"(src) : "memory");
}
__device__ __forceinline__ void cp_async16(uint32_t dst, const void* src, uint32_t srcbytes) {
  asm volatile("cp.async.cg.shared.global.L2::256B [%0], [%1], 16, %2;\n" ::"r"(dst), "l"(src), "r"(srcbytes) : "memory");
}
__device__ __forceinline__ uint32_t ld_acquire(const uint32_t* p) {
  uint32_t v;
  asm volatile("ld.acquire.gpu.global.u32 %0, [%1];\n" : "=r"(v) : "l"(p) : "memory");
  return v;
}
__device__ __forceinline__ uint32_t ld_relaxed(const uint32_t* p) {
  uint32_t v;
  asm volatile("ld.relaxed.gpu.global.u32 %0, [%1];\n" : "=r"(v) : "l"(p) : "memory");
  return v;
}
__device__ __forceinline__ void st_release(uint32_t* p, uint32_t v) {
  asm volatile("st.release.gpu.global.u32 [%0], %1;\n" ::"l"(p), "r"(v) : "memory");
}
__device__ __forceinline__ void wait_flag(const uint32_t* p, uint32_t want) {
  int n = 0;
  while (ld_acquire(p) != want && ++n < SPIN_LIMIT) {}
}

struct Params {
  const __nv_bfloat16* x;
  const __nv_bfloat16* w;
  const __nv_bfloat16* q;
  const __nv_bfloat16* k;
  const __nv_bfloat16* v;
  const __nv_bfloat16* shift_k;
  const __nv_bfloat16* ssm_k;
  const __nv_bfloat16* ssm_D;
  const __nv_bfloat16* wo;
  __nv_bfloat16* out;
  uint32_t zero;
};

__device__ __forceinline__ uint32_t lds32(uint32_t a) {
  uint32_t v;
  asm volatile("ld.shared.u32 %0, [%1];\n" : "=r"(v) : "r"(a));
  return v;
}
__device__ __forceinline__ float bf_lo(uint32_t v) {
  uint32_t r;
  asm("prmt.b32 %0, %1, 0, 0x1044;\n" : "=r"(r) : "r"(v));
  return __uint_as_float(r);
}
__device__ __forceinline__ float bf_hi(uint32_t v) { return __uint_as_float(v & 0xffff0000u); }
__device__ __forceinline__ float ex2(float x) {
  float r;
  asm("ex2.approx.ftz.f32 %0, %1;\n" : "=f"(r) : "f"(x));
  return r;
}
__device__ __forceinline__ float rcp(float x) {
  float r;
  asm("rcp.approx.ftz.f32 %0, %1;\n" : "=f"(r) : "f"(x));
  return r;
}

#define Q4(c, d, o) c(d[o + 0]), c(d[o + 1]), c(d[o + 2]), c(d[o + 3])
#define Q8(c, d, o) Q4(c, d, o), Q4(c, d, o + 4)
#define Q16(c, d, o) Q8(c, d, o), Q8(c, d, o + 8)
#define Q32(c, d) Q16(c, d, 0), Q16(c, d, 16)
#define L8 "{%0,%1,%2,%3,%4,%5,%6,%7}"
#define L16 "{%0,%1,%2,%3,%4,%5,%6,%7,%8,%9,%10,%11,%12,%13,%14,%15}"
#define L32 "{%0,%1,%2,%3,%4,%5,%6,%7,%8,%9,%10,%11,%12,%13,%14,%15,%16,%17,%18,%19,%20,%21,%22,%23,%24,%25,%26,%27,%28,%29,%30,%31}"
__device__ __forceinline__ void fft_rows(uint32_t (&d)[32], const uint32_t (&a)[2][4], uint64_t db) {
  asm volatile("wgmma.mma_async.sync.aligned.m64n128k16.f16.f16.f16 " L32 ", {%32,%33,%34,%35}, %36, 0, 1, 1, 1;\n"
               : Q32("=r", d) : "r"(a[0][0]), "r"(a[0][1]), "r"(a[0][2]), "r"(a[0][3]), "l"(db));
  asm volatile("wgmma.mma_async.sync.aligned.m64n128k16.f16.f16.f16 " L32 ", {%32,%33,%34,%35}, %36, 1, 1, 1, 1;\n"
               : Q32("+r", d) : "r"(a[1][0]), "r"(a[1][1]), "r"(a[1][2]), "r"(a[1][3]), "l"(db + 64));
}
template <int INV> __device__ __forceinline__ void fft_cols(uint32_t (&d)[8], const uint32_t (&a)[2][4], uint64_t db) {
  asm volatile("wgmma.mma_async.sync.aligned.m64n32k16.f16.f16.f16 " L8 ", {%8,%9,%10,%11}, %12, 0, 1, 1, %13;\n"
               : Q8("=r", d, 0) : "r"(a[0][0]), "r"(a[0][1]), "r"(a[0][2]), "r"(a[0][3]), "l"(db), "n"(INV));
  asm volatile("wgmma.mma_async.sync.aligned.m64n32k16.f16.f16.f16 " L8 ", {%8,%9,%10,%11}, %12, 1, 1, 1, %13;\n"
               : Q8("+r", d, 0) : "r"(a[1][0]), "r"(a[1][1]), "r"(a[1][2]), "r"(a[1][3]), "l"(db + (INV ? 16 : 64)), "n"(INV));
}
__device__ __forceinline__ void fft_back(float (&d)[16], uint64_t da, uint64_t db) {
  asm volatile("wgmma.mma_async.sync.aligned.m64n32k16.f32.f16.f16 " L16 ", %16, %17, 0, 1, 1, 1, 1;\n"
               : Q16("=f", d, 0) : "l"(da), "l"(db));
#pragma unroll
  for (int i = 1; i < 4; i++)
    asm volatile("wgmma.mma_async.sync.aligned.m64n32k16.f32.f16.f16 " L16 ", %16, %17, 1, 1, 1, 1, 1;\n"
                 : Q16("+f", d, 0) : "l"(da + 32 * i), "l"(db + 64 * i));
}
__device__ __forceinline__ uint32_t hmul2(uint32_t a, uint32_t b) {
  uint32_t r;
  asm("mul.rn.f16x2 %0, %1, %2;\n" : "=r"(r) : "r"(a), "r"(b));
  return r;
}
__device__ __forceinline__ uint32_t hadd2(uint32_t a, uint32_t b) {
  uint32_t r;
  asm("add.rn.f16x2 %0, %1, %2;\n" : "=r"(r) : "r"(a), "r"(b));
  return r;
}
__device__ __forceinline__ uint32_t hneg2(uint32_t a) {
  uint32_t r;
  asm("neg.f16x2 %0, %1;\n" : "=r"(r) : "r"(a));
  return r;
}
__device__ __forceinline__ uint32_t hfma2(uint32_t a, uint32_t b, uint32_t c) {
  uint32_t r;
  asm("fma.rn.f16x2 %0, %1, %2, %3;\n" : "=r"(r) : "r"(a), "r"(b), "r"(c));
  return r;
}
__device__ __forceinline__ uint32_t pack_f16(float lo, float hi) {
  uint32_t r;
  asm("cvt.rn.f16x2.f32 %0, %1, %2;\n" : "=r"(r) : "f"(hi), "f"(lo));
  return r;
}
__device__ __forceinline__ uint32_t bmaxabs2(uint32_t a, uint32_t b) {
  uint32_t r;
  asm("max.xorsign.abs.bf16x2 %0, %1, %2;\n" : "=r"(r) : "r"(a), "r"(b));
  return r;
}
struct C2 { uint32_t r, i; };
__device__ __forceinline__ C2 cmul(C2 a, C2 b) {
  return C2{hfma2(a.r, b.r, hneg2(hmul2(a.i, b.i))), hfma2(a.r, b.i, hmul2(a.i, b.r))};
}
__device__ __forceinline__ C2 cfma(C2 a, C2 b, C2 c) {
  return C2{hfma2(a.r, b.r, hfma2(hneg2(a.i), b.i, c.r)), hfma2(a.r, b.i, hfma2(a.i, b.r, c.i))};
}
__device__ __forceinline__ C2 crot(C2 z, C2 t) {
  const uint32_t r = hfma2(t.r, z.i, z.r), i = hfma2(t.i, r, z.i);
  return C2{hfma2(t.r, i, r), i};
}
__device__ __forceinline__ C2 cget(const uint32_t (&e)[8], int j, int b) { return C2{e[4 * j + b], e[4 * j + 2 + b]}; }
template <int N> __device__ __forceinline__ void fence_regs(uint32_t (&d)[N]) {
#pragma unroll
  for (int i = 0; i < N; i++) asm volatile("" : "+r"(d[i])::"memory");
}
__device__ __forceinline__ void ldsm4(uint32_t (&r)[4], uint32_t a) {
  asm volatile("ldmatrix.sync.aligned.m8n8.x4.shared.b16 {%0,%1,%2,%3}, [%4];\n"
               : "=r"(r[0]), "=r"(r[1]), "=r"(r[2]), "=r"(r[3]) : "r"(a) : "memory");
}

__device__ __forceinline__ uint32_t movm(uint32_t a) {
  uint32_t r;
  asm volatile("movmatrix.sync.aligned.m8n8.trans.b16 %0, %1;\n" : "=r"(r) : "r"(a));
  return r;
}
template <int C0, int H, bool T> __device__ __forceinline__ void attn_pack(const float (&acc)[96], uint32_t (&d)[8]) {
#pragma unroll
  for (int c = 0; c < 8; c++) {
    asm volatile("cvt.rn.bf16x2.f32 %0, %1, %2;\n" : "=r"(d[c]) : "f"(acc[4 * (C0 + c) + 2 * H + 1]), "f"(acc[4 * (C0 + c) + 2 * H]));
    if (T) d[c] = movm(d[c]);
  }
}
__device__ __forceinline__ void attn_qk(float (&s)[4], const uint32_t (&qlo)[8], const uint32_t (&qhi)[8],
                                        const uint32_t (&k)[8], int c) {
  mma16816_z(s, qlo[c], qhi[c], qlo[c + 1], qhi[c + 1], k[c], k[c + 1]);
  mma16816(s, qlo[c + 2], qhi[c + 2], qlo[c + 3], qhi[c + 3], k[c + 2], k[c + 3]);
}
template <int N> __device__ __forceinline__ void quad_softmax(float (&x)[N][2], uint32_t (&pp)[N]) {
  const float c2 = 1.4426950408889634f;
  uint32_t q[N], mx[N / 2];
#pragma unroll
  for (int n = 0; n < N; n++) {
    const uint32_t r = pack_bf16(x[n][0], x[n][1]);
    q[n] = bfma2(r, 0x3e353e35u, bmul2(r, 0x379e379eu));
    x[n][0] = bf_lo(q[n]);
    x[n][1] = bf_hi(q[n]);
  }
#pragma unroll
  for (int n = 0; n < N / 2; n++)
    mx[n] = bmax2(__byte_perm(q[2 * n], q[2 * n + 1], 0x5410), __byte_perm(q[2 * n], q[2 * n + 1], 0x7632));
#pragma unroll
  for (int o = 1; o <= 2; o++) {
#pragma unroll
    for (int n = 0; n < N / 2; n++) mx[n] = bmax2(mx[n], __shfl_xor_sync(0xffffffffu, mx[n], o));
  }
  float m[N], t[N];
#pragma unroll
  for (int n = 0; n < N / 2; n++) {
    m[2 * n] = bf_lo(mx[n]);
    m[2 * n + 1] = bf_hi(mx[n]);
  }
#pragma unroll
  for (int n = 0; n < N; n++) {
    const float nm = -m[n] * c2;
    x[n][0] = ex2(fmaf(x[n][0], c2, nm));
    x[n][1] = ex2(fmaf(x[n][1], c2, nm));
  }
#pragma unroll
  for (int n = 0; n < N; n += 2) {
    float u0, u1;
    asm("mma.sync.aligned.m16n8k8.row.col.f32.tf32.tf32.f32 {%0,%1,%2,%3}, {%4,%5,%6,%7}, {%8,%8}, {%9,%9,%9,%9};\n"
        : "=f"(t[n]), "=f"(u0), "=f"(t[n + 1]), "=f"(u1)
        : "r"(__float_as_uint(x[n][0])), "r"(__float_as_uint(x[n + 1][0])), "r"(__float_as_uint(x[n][1])),
          "r"(__float_as_uint(x[n + 1][1])), "r"(0x3f800000u), "f"(0.f));
  }
#pragma unroll
  for (int n = 0; n < N; n++) {
    const float inv = rcp(t[n]);
    pp[n] = pack_bf16(x[n][0] * inv, x[n][1] * inv);
  }
}
__device__ __forceinline__ void attn_pv(uint32_t dst, const uint32_t (&vp)[8], const uint32_t (&vo)[8], int c, uint32_t pp,
                                        uint32_t maskLE) {
  const uint32_t b0 = pp & ~maskLE, b1 = pp & maskLE;
  float oa[4], ob[4];
  mma16816_z(oa, vp[c], vp[c + 1], vo[c], vo[c + 1], b0, b1);
  mma16816_z(ob, vp[c + 2], vp[c + 3], vo[c + 2], vo[c + 3], b0, b1);
  stsm4t(dst, pack_bf16(oa[0], oa[1]), pack_bf16(oa[2], oa[3]), pack_bf16(ob[0], ob[1]), pack_bf16(ob[2], ob[3]));
}

template <int MODE>
__global__ void __cluster_dims__(2, 1, 1) __launch_bounds__(NTHREADS, 1)
fused_kernel(const Params p, const __grid_constant__ CUtensorMap tmX, const __grid_constant__ CUtensorMap tmW,
             const __grid_constant__ CUtensorMap tmWo, const __grid_constant__ CUtensorMap tmWp,
             const __grid_constant__ CUtensorMap tmQ,
             const __grid_constant__ CUtensorMap tmOb,
             const __grid_constant__ CUtensorMap tmXh, const __grid_constant__ CUtensorMap tmWh) {
  extern __shared__ __align__(1024) uint8_t smem[];
  if (threadIdx.x < 32 * PFR) {
    const uint32_t i = ((blockIdx.x + (threadIdx.x >> 5) * (128 / PFR)) & 127) * 16 + (threadIdx.x & 15);
    prefetch_l2(threadIdx.x & 16 ? (const char*)p.w + i * 128 : (const char*)p.x + i * 2048);
  }
  const uint32_t sb = smem_u32(smem);
  const uint32_t bars = sb + OFF_BAR;
  const int tid = threadIdx.x, lane = tid & 31, warp = __shfl_sync(0xffffffffu, tid >> 5, 0);
  const int rank = blockIdx.x & 1;
  const bool halo_cta = blockIdx.x < 4;
  if (halo_cta && MODE != 0) return;
  int grp, mem;
  {
    const int t = (blockIdx.x >> 1) - 4, u = t - 32;
    const int q7 = (u * 37) >> 8;
    const bool lo = (unsigned)t < 32u, mid = (unsigned)u < 28u;
    grp = lo ? (t & 7) : (mid ? 1 + u - 7 * q7 : 0);
    mem = lo ? (t >> 3) : (mid ? 4 + q7 : (t < 0 ? t + 6 : t - 54));
  }
  const int rg = (grp >> 2) * 4 + (mem >> 1), hp = (grp & 3) * 4 + (mem & 1) * 2 + rank;
  const int rb2 = (grp >> 2) * 8 + mem, cb2 = (grp & 3) * 2 + rank;
  const int chb = grp * 16 + mem * 2 + rank;
  const int cta = rg * 16 + hp;
  const int hsel = rb2 & 1;
  const int par = rg >> 2, gidx = rg & 3;

  if (tid < 256 && !halo_cta && MODE != 2) {
    const int r = tid >> 3, c = tid & 7;
    const uint32_t so = r * 128 + ((c ^ (r & 7)) << 4);
    const __nv_bfloat16* wg0 = p.w + (size_t)r * (3 * DM) + hp * 64 + c * 8;
    const __nv_bfloat16* xg0 = p.x + (size_t)(2 * (gidx * 256 + r) + par) * DM + c * 8;
#pragma unroll
    for (int j = 0; j < 3; j++) cp_async16n(sb + OFF_1B + j * 4096 + so, wg0 + j * DM);
#pragma unroll
    for (int i = 0; i < 8; i++) cp_async16n(sb + i * 4096 + so, xg0 + (size_t)i * 64 * DM);
    asm volatile("cp.async.commit_group;\n" ::: "memory");
  }
  auto halo_issue = [&](int kb, int s) {
    const uint32_t fb = bars + 8 * (BAR_FULLB + s), st = sb + s * STGH;
    mbar_expect_tx(fb, STGH - 2048);
    tma_load_3d(st + 8192, &tmWh, fb, 0, kb * 64, 16 + blockIdx.x * 4);
    tma_load_3d(st + 8192 + 32768, &tmWh, fb, 0, kb * 64, 32 + blockIdx.x * 4);
    tma_load_4d(st, &tmXh, fb, kb * 64, 248, 0, 0);
  };
  if (tid == 256) {
    prefetch_tmap(halo_cta ? &tmXh : &tmX);
#pragma unroll
    for (int i = 0; i < NS1B; i++) mbar_init(bars + 8 * (BAR_FULLB + i), 1);
#pragma unroll
    for (int i = 0; i < NS1A; i++) mbar_init(bars + 8 * (BAR_FULLA + i), 1);
    asm volatile("fence.mbarrier_init.release.cluster;\n" ::: "memory");
    if (!halo_cta && MODE != 2) {
      mbar_expect_tx(bars + 8 * (BAR_FULLB + 1), STG1B);
      tma_load_3d(sb + OFF_1B + 1 * STG1B, &tmW, bars + 8 * (BAR_FULLB + 1), hp * 64, 32, 0);
      mbar_expect_tx(bars + 8 * (BAR_FULLB + 2), STG1B);
      tma_load_3d(sb + OFF_1B + 2 * STG1B, &tmW, bars + 8 * (BAR_FULLB + 2), hp * 64, 64, 0);
    } else if (halo_cta) {
      halo_issue(0, 0);
    }
  } else if (tid == 288) {
#pragma unroll
    for (int i = 0; i < NS1A; i++) mbar_init(bars + 8 * (BAR_EMPTYA + i), 4);
#pragma unroll
    for (int i = 0; i < NS1B; i++) mbar_init(bars + 8 * (BAR_EMPTYB + i), 2);
    mbar_init(bars + 8 * BAR_X, 4);
    mbar_init(bars + 8 * BAR_TAB, 16);
    mbar_init(bars + 8 * BAR_U, 1);
    mbar_init(bars + 8 * BAR_H, 1);
    mbar_init(bars + 8 * BAR_STG, 8);
    mbar_init(bars + 8 * BAR_HALO, 1);
    mbar_init(bars + 8 * BAR_Q, 1);
    mbar_init(bars + 8 * BAR_LAND, 5);
    mbar_init(bars + 8 * (BAR_LAND + 1), 5);
    asm volatile("fence.mbarrier_init.release.cluster;\n" ::: "memory");
  } else if (tid == 320) {
#pragma unroll
    for (int i = 0; i < NS2; i++) {
      mbar_init(bars + 8 * (BAR_FULL2 + i), 1);
      mbar_init(bars + 8 * (BAR_EMPTY2 + i), 2);
      mbar_init(bars + 8 * (BAR_EMPTY2B + i), 2);
    }
    asm volatile("fence.mbarrier_init.release.cluster;\n" ::: "memory");
  } else if (tid == 352) {
#pragma unroll
    for (int i = 0; i < 4; i++) mbar_init(bars + 8 * (BAR_Y + i), i < 2 ? 4 : i == 2 ? 10 : 8);
    mbar_init(bars + 8 * BAR_XFREE, 1);
    asm volatile("fence.mbarrier_init.release.cluster;\n" ::: "memory");
  }
  cluster_sync_all();
  if (warp == 8) PROF2(24);

  if (warp >= 8) {
    const int hw = warp - 8;
    const int lr = lane & 7, lm = lane >> 3;
    auto g1_issue_a = [&](int j, int s) {
      const uint32_t fb = bars + 8 * (BAR_FULLA + s);
      mbar_expect_tx(fb, STG1A);
      tma_load_3d_mc(sb + s * STG1A + rank * 16384, &tmX, fb, j * 64, par, gidx * 256 + rank * 128);
    };
    auto g1_issue_b = [&](int kb, int s) {
      const uint32_t fb = bars + 8 * (BAR_FULLB + s);
      mbar_expect_tx(fb, STG1B);
      tma_load_3d(sb + OFF_1B + s * STG1B, &tmW, fb, hp * 64, kb * 32, 0);
    };
    auto g2_k = [&](int kb) { return (kb < 2 ? hp : kb < 4 ? hp & 14 : hp & 12) ^ kb; };
    auto g2_issue_b = [&](uint32_t fb, uint32_t bytes, uint32_t dst, int k0, bool whole) {
      if (whole) {
        tma_load_3d(dst, &tmWo, fb, 0, k0, cb2 * 2);
      } else {
#pragma unroll
        for (int i = 0; i < 4; i++)
          tma_load_3d(dst + (i & 1) * XT + (i >> 1) * 4 * XT, &tmWp, fb, 0, k0 + (i >> 1) * 32, cb2 * 2 + (i & 1));
      }
      mbar_expect_tx(fb, bytes);
    };
    auto send_y = [&](uint32_t o, uint32_t step, int half) {
      const uint32_t peer = mapa(sb, rank ^ 1);
      o += OFF_X + (rank ^ 1) * 4096 + half * 2048 + lane * 16;
      uint4 a[8];
#pragma unroll
      for (int i = 0; i < 8; i++) a[i] = lds128(sb + o + (i >> 2) * step + (i & 2) * (XT / 2) + (i & 1) * 512);
#pragma unroll
      for (int i = 0; i < 8; i++)
        st_async128(peer + o + 1024 + (i >> 2) * step + (i & 2) * (XT / 2) + (i & 1) * 512,
                    peer + OFF_BAR + 8 * (BAR_LAND + half), a[i].x, a[i].y, a[i].z, a[i].w);
    };
    asm volatile("setmaxnreg.dec.sync.aligned.u32 %0;\n" :: "n"(REG_HELP));

    if (halo_cta) {
      if (hw == 0) {
        int s = 1, ph = 1;
#pragma unroll 1
        for (int kb = 1; kb < 16; kb++) {
          mbar_wait(bars + 8 * (BAR_EMPTYB + s), ph);
          if (elect_one()) halo_issue(kb, s);
          if (++s == 3) { s = 0; ph ^= 1; }
        }
      }
      __syncwarp();
    } else if (hw == 0) {
      uint32_t epoch = 0;
      if (MODE == 2) {
        if (lane < NS2) mbar_arrive_cluster_n(mapa(bars, rank) + 8 * (BAR_EMPTY2 + lane), 2);
      } else {
      if (lane == 0) {
        mbar_expect_tx(bars + 8 * BAR_U, 32768);
        mbar_expect_tx(bars + 8 * BAR_LAND, 8192);
        mbar_expect_tx(bars + 8 * (BAR_LAND + 1), 8192);
        mbar_expect_tx(bars + 8 * BAR_Q, 32768);
        prefetch_tmap(&tmQ);
      }
      {
        int sa = 1, pha = 1, sbb = 2, phb = 1;
#pragma unroll 1
        for (int kb = 2; kb < 32; kb++) {
          if (!(kb & 1)) {
            mbar_wait(bars + 8 * (BAR_EMPTYA + sa), pha);
            if (elect_one()) g1_issue_a(kb >> 1, sa);
            if (++sa == NS1A) { sa = 0; pha ^= 1; }
          }
          mbar_wait(bars + 8 * (BAR_EMPTYB + sbb), phb);
          if (kb > 2 && elect_one()) g1_issue_b(kb, sbb);
          __syncwarp();
          if (kb == 4) epoch = ld_relaxed(g_flag_o + cta);
          if (kb == 4) PROF2(27);
          if (kb == 1) PROF2(38);
          if (kb == 2) PROF2(39);
          if (++sbb == NS1B) { sbb = 0; phb ^= 1; }
        }
      }
      auto q_issue = [&](int i) {
        mbar_wait(bars + 8 * (i ? BAR_EMPTYB + 3 : BAR_EMPTYA + 1), i);
        if (elect_one())
          asm volatile(
              "cp.async.bulk.tensor.5d.shared::cluster.global.mbarrier::complete_tx::bytes [%0], [%1, {%3, %4, %4, %4, %5}], [%2];\n"
              ::"r"(sb + (i ? OFF_Q1 : OFF_Q0)), "l"(&tmQ), "r"(bars + 8 * BAR_Q), "r"((chb & ~1) * 8), "r"(0), "r"(rank * 32 + i * 64)
              : "memory");
        __syncwarp();
      };
      if (QORD < 2) q_issue(0);
      else mbar_wait(bars + 8 * (BAR_EMPTYA + 1), 0);
      if (QORD < 1) q_issue(1);
      epoch++;
      if (lane == 0) {
        prefetch_tmap(&tmWo);
        prefetch_tmap(&tmWp);
        prefetch_tmap(&tmOb);
        if (gidx != 0) wait_flag(g_flag_h + (hp >> 2), epoch);
      }
      __syncwarp();
      {
        uint4 hk0 = make_uint4(0, 0, 0, 0), hk1 = hk0, hv0 = hk0, hv1 = hk0;
        if (gidx != 0) {
          const uint4* src = g_halo + cta * 128 + lane;
          hk0 = __ldcg(src); hk1 = __ldcg(src + 32); hv0 = __ldcg(src + 64); hv1 = __ldcg(src + 96);
        }
        if (gidx != 0) PROF(18);
        sts128(sb + OFF_KH + lane * 16, hk0.x, hk0.y, hk0.z, hk0.w);
        sts128(sb + OFF_KH + 512 + lane * 16, hk1.x, hk1.y, hk1.z, hk1.w);
        sts64(sb + OFF_KH + 1024 + lane * 8, movm(hv0.x), movm(hv0.y));
        sts64(sb + OFF_KH + 1280 + lane * 8, movm(hv0.z), movm(hv0.w));
        sts64(sb + OFF_KH + 1536 + lane * 8, movm(hv1.x), movm(hv1.y));
        sts64(sb + OFF_KH + 1792 + lane * 8, movm(hv1.z), movm(hv1.w));
        __syncwarp();
        if (lane == 0) mbar_arrive(bars + 8 * BAR_HALO);
      }
      if (QORD == 2) q_issue(0);
      if (QORD >= 1) q_issue(1);
      const uint32_t rb = mapa(bars, lane & 1);
      nb_sync(NB_OREADY, 288);
      if (lane == 0) {
        asm volatile("cp.async.bulk.global.shared::cta.bulk_group [%0], [%1], %2;\n" ::"l"(g_o + (size_t)cta * 16384),
                     "r"(sb + OFF_OP), "r"(32768) : "memory");
        bulk_commit();
      }
      if (lane < 2) {
#pragma unroll
        for (int i = 0; i < 4; i++) mbar_arrive_cluster(rb + 8 * (BAR_EMPTY2 + i + i / 2));
      }
      if (lane == 0) {
        bulk_wait0();
        st_release(g_flag_o + cta, epoch);
      }
      __syncwarp();
      PROF2(17);
      if (lane < 2) mbar_arrive_cluster(rb + 8 * (BAR_EMPTY2 + 2));
      }
      if (MODE != 1) {
        const __nv_bfloat16* osrc = g_o + (size_t)(rb2 >> 1) * 16 * 16384 + hsel * 8192;
        mbar_wait(bars + 8 * (BAR_EMPTY2 + 1), 0);
        if (elect_one()) {
          if (MODE == 0) {
            asm volatile("cp.async.bulk.shared::cluster.shared::cta.mbarrier::complete_tx::bytes [%0], [%1], %2, [%3];\n"
                         ::"r"(mapa(sb + g2_a(1, hsel), rank ^ 1)), "r"(sb + g2_a(0, hsel)), "r"(16384),
                         "r"(mapa(bars + 8 * (BAR_FULL2 + 1), rank ^ 1)) : "memory");
          } else {
            bulk_load(sb + g2_a(0, hsel), osrc + hp * 16384, 16384, bars + 8 * BAR_FULL2);
            bulk_load(sb + g2_a(1, hsel), osrc + (hp ^ 1) * 16384, 16384, bars + 8 * (BAR_FULL2 + 1));
          }
        }
        __syncwarp();
      }
      if (MODE != 2) {
        mbar_wait(bars + 8 * (BAR_Y + 2), 0);
        send_y(0, 4 * XT, 1);
        fence_async_smem();
        __syncwarp();
      }
      if (MODE != 1) {
        unsigned long long seq = G2_SEQ >> 12;
        uint32_t wbar = bars + 8 * (BAR_Y + 2), fb = bars + 8 * (BAR_FULL2 + 3), dst = sb + g2_b(3, rank), ph = MODE ? 1 : 0;
        int k0 = g2_k(3) * 64;
        bool whole = false;
#pragma unroll 1
        for (int kb = 4; kb <= 16; kb++) {
          mbar_wait(wbar, ph);
          if (elect_one()) g2_issue_b(fb, STG2, dst, k0, whole);
          __syncwarp();
          seq >>= 4;
          const int s = seq & 7;
          wbar = bars + 8 * (kb == G2_KB4 ? BAR_XFREE : BAR_EMPTY2B + s);
          ph = ((uint32_t)seq >> 3 & 1) ^ (kb == G2_KB4 && MODE == 0 ? 0 : 1);
          fb = bars + 8 * (BAR_FULL2 + s);
          dst = sb + g2_b(s, rank);
          k0 = ((hp & 12) ^ kb) * 64;
          whole = s < 3;
        }
      }
      __syncwarp();
    } else {
      if (MODE != 2) {
      const float dall = __bfloat162float(p.ssm_D[chb * 8 + lr]);
      {
        const int g = lane >> 2, t = lane & 3;
        uint32_t w[2][4];
#pragma unroll
        for (int h = 0; h < 2; h++) {
          const uint2 x = __ldg(reinterpret_cast<const uint2*>(p.shift_k + ((chb & ~1) * 8 + h * 8 + g) * 4));
          w[h][0] = __byte_perm(x.x, x.x, 0x1010);
          w[h][1] = __byte_perm(x.x, x.x, 0x3232);
          w[h][2] = __byte_perm(x.y, x.y, 0x1010);
          w[h][3] = __byte_perm(x.y, x.y, 0x3232);
        }
        auto swz = [](int r) { return (((r & 29) | ((r ^ (r >> 2)) & 2)) << 5) | (r & 16); };
        const uint32_t kring = sb + OFF_X + 4096 + (hw - 1) * 2 * XT, vring = kring + XT;
        const int s0 = rank * 32 + (hw - 1) * 11, s1 = hw == 3 ? rank * 32 + 32 : s0 + 11;
        const size_t goff = (size_t)(lane >> 1) * DM + (chb & ~1) * 8 + (lane & 1) * 8;
        const __nv_bfloat16* kg = p.k + goff;
        const __nv_bfloat16* vg = p.v + goff;
        const uint32_t d0 = swz(lane >> 1) ^ ((lane & 1) << 4), d1 = swz(16 + (lane >> 1)) ^ ((lane & 1) << 4);
        auto issue = [&](int st) {
          const uint32_t so = (st & 3) << 10;
          cp_async16(kring + so + d0, kg + (size_t)st * 32 * DM, 16);
          cp_async16(kring + so + d1, kg + (size_t)(st * 32 + 16) * DM, 16);
          cp_async16(vring + so + d0, vg + (size_t)st * 32 * DM, 16);
          cp_async16(vring + so + d1, vg + (size_t)(st * 32 + 16) * DM, 16);
        };
        const int xa = 8 * (lr >> 1) + 2 * lm + (lr & 1), xb = 8 * (lr >> 1) - 4 + 2 * (lm & 1) + (lr & 1);
        const uint32_t la = swz(xa), lb = swz(xb & 31);
        const int backb = xb < 0 ? 1 : 0;
        const uint32_t ud[2] = {mapa(sb + OFF_X + g * XT + t * 16, 0), mapa(sb + OFF_X + g * XT + t * 16, 1)};
        const uint32_t ub[2] = {mapa(bars + 8 * BAR_U, 0), mapa(bars + 8 * BAR_U, 1)};
        if (tid == 320) prefetch_l2(g_tab + (chb & 63) * 32);
        if (lane == 0) mbar_wait(bars + 8 * (BAR_FULLB + NS1B - 1), 0);
        __syncwarp();
        if (lane >= 24) cp_async16(kring + (((s0 - 1) & 3) << 10) + d1, s0 > 0 ? kg + (size_t)(s0 * 32 - 16) * DM : kg, s0 > 0 ? 16 : 0);
        issue(s0);
        asm volatile("cp.async.commit_group;\n" ::: "memory");
        issue(s0 + 1);
        asm volatile("cp.async.commit_group;\n" ::: "memory");
        uint32_t tn = (uint32_t)clock();
#pragma unroll 1
        for (int st = s0; st < s1; st++) {
          tn += PSTEP;
          while ((int)((uint32_t)clock() - tn) < 0) __nanosleep(100);
          if (st + 2 < s1) issue(st + 2);
          if (hw == 1 && (unsigned)(st - s0 - HPF0) < 8u) prefetch_l2(p.ssm_k + (size_t)(chb * 8 + st - s0 - HPF0) * SEQ + lane * 64);
          asm volatile("cp.async.commit_group;\n" ::: "memory");
          asm volatile("cp.async.wait_group 2;\n" ::: "memory");
          __syncwarp();
#pragma unroll
          for (int h = 0; h < 2; h++) {
            uint32_t e[6], vv[4], e4[4];
            ldsm4t(e4, kring + ((st & 3) << 10) + (la ^ (h << 4)));
            ldsm2t(e[0], e[1], kring + (((st - backb) & 3) << 10) + (lb ^ (h << 4)));
            ldsm4t(vv, vring + ((st & 3) << 10) + (la ^ (h << 4)));
            e[2] = e4[0]; e[3] = e4[1]; e[4] = e4[2]; e[5] = e4[3];
            uint32_t o[5];
#pragma unroll
            for (int i = 0; i < 5; i++) o[i] = __byte_perm(e[i], e[i + 1], 0x5432);
#pragma unroll
            for (int i = 0; i < 4; i++) {
              uint32_t a = bmul2(o[i], w[h][3]);
              a = bfma2(e[i + 1], w[h][2], a);
              a = bfma2(o[i + 1], w[h][1], a);
              a = bfma2(e[i + 2], w[h][0], a);
              vv[i] = bmul2(a, vv[i]);
            }
            st_async128(ud[h] + (st ^ (g & 1)) * 64, ub[h], vv[0], vv[1], vv[2], vv[3]);
          }
          __syncwarp();
        }
        fence_async_smem();
        PROF(16);
      }
      nb_sync(NB_HELP3, 96);
      if (hw == 1 && elect_one()) {
        mbar_expect_tx(bars + 8 * BAR_H, 8 * 4096);
#pragma unroll 1
        for (int c = 0; c < 8; c++)
          bulk_load(sb + OFF_X + c * XT + 4096, p.ssm_k + (size_t)(chb * 8 + c) * SEQ, 4096, bars + 8 * BAR_H);
        mbar_expect_tx(bars + 8 * BAR_X, 6144);
        bulk_load(sb + OFF_T16, g_tab, 2048, bars + 8 * BAR_X);
        bulk_load(sb + OFF_T32, g_tab + 512, 4096, bars + 8 * BAR_X);
      }
      __syncwarp();
      {
        const int ck = 16 * (lane >> 4) + 2 * lr + (((lane >> 3) ^ (lane >> 2)) & 1);
        const uint32_t xo = (ck >> 1) * 64, xs = ((ck & 1) ^ (lr >> 1)) << 4;
#pragma unroll 1
        for (int job = hw - 1; job < 16; job += 3) {
          const int c = job & 7;
          uint4 a[8];
          float dv = __shfl_sync(0xffffffffu, dall, c);
          if (job < 8 || lane) dv = 0.f;
          if (job >= PF0 && job < PF1) prefetch_l2((job < 8 ? p.q + (size_t)chb * 16384 : p.wo + (size_t)chb * 8192) + c * 2048 + lane * 64);
          const uint32_t xt = sb + OFF_X + c * XT + (job >> 3) * 4096;
          mbar_wait(bars + 8 * (job < 8 ? BAR_U : BAR_H), 0);
#pragma unroll
          for (int i = 0; i < 8; i++) a[i] = lds128(xt + i * 512 + ((ck ^ (job < 8 ? (c & 1) << 2 : 0)) << 4));
          dv += bf_lo(a[0].x);
          uint32_t m[2] = {bmaxabs2(pack_bf16(dv, 0.f), bmaxabs2(a[0].x, a[0].y)), bmaxabs2(a[0].z, a[0].w)};
#pragma unroll
          for (int i = 1; i < 8; i++) {
            m[0] = bmaxabs2(bmaxabs2(m[0], a[i].x), a[i].y);
            m[1] = bmaxabs2(bmaxabs2(m[1], a[i].z), a[i].w);
          }
          m[0] = bmaxabs2(m[0], m[1]);
          const int f = max(252 - (int)(__reduce_max_sync(0xffffffffu, max(m[0] & 0x7fffu, (m[0] >> 16) & 0x7fffu)) >> 7), 1);
          if (lane == 0) asm volatile("st.shared.u32 [%0], %1;\n" ::"r"(sb + OFF_EX + job * 4), "r"(f) : "memory");
          if (f < 113) {
#pragma unroll
            for (int i = 0; i < 8; i++)
              a[i] = make_uint4(bmul2(a[i].x, f * 0x00800080u), bmul2(a[i].y, f * 0x00800080u), bmul2(a[i].z, f * 0x00800080u),
                                bmul2(a[i].w, f * 0x00800080u));
          }
          const uint32_t mul = (f < 113 ? 15 : f - 112) * 0x00800080u;
          auto cv = [&](uint32_t x) {
            x = bmul2(x, mul);
            return (x & 0x0fff0fffu) * 7 + x;
          };
          const uint32_t dst = xt + xo;
#pragma unroll
          for (int i = 0; i < 8; i++)
            sts128(dst + (i >> 2) * 2048 + (i & 1) * 1024 + (xs ^ ((i & 2) << 4)),
                   i ? cv(a[i].x) : __byte_perm(pack_f16(dv * __uint_as_float(f << 23), 0.f), cv(a[i].x), 0x7610), cv(a[i].y),
                   cv(a[i].z), cv(a[i].w));
        }
        fence_async_smem();
        __syncwarp();
        if (lane == 0) mbar_arrive(bars + 8 * BAR_X);
        PROF(19);
      }
      if (hw < 3) {
#pragma unroll 1
        for (int n = 0; n < SPIN_LIMIT && !mbar_try(bars + 8 * (BAR_Y + hw - 1), 0); n++) __nanosleep(100);
        send_y((hw - 1) * 4 * XT, 2 * XT, 0);
        __syncwarp();
        if (lane == 0) mbar_arrive(bars + 8 * (BAR_Y + 2));
        PROF(32);
        const int c8 = 2 * lm + (lr & 1), src = (lr >> 1) & 1;
        uint32_t fa = sb + OFF_X + c8 * XT + rank * 4096 + (src == rank ? 0 : 1024) + (hw - 1) * 512;
        const uint32_t fx = ((lr >> 2) ^ ((lr & 3) << 1)) << 4;
        uint32_t qa = sb + OFF_Q0 + (hw - 1) * 8192 + (lane >> 3) * 128 + (lane & 2) * 32 + (lane & 4) * 8 + (lane & 1) * 16;
        uint4* og = reinterpret_cast<uint4*>(p.out + (size_t)(rank * 512 + (hw - 1) * 256 + (lane & 2) * 4 + (lane >> 2)) * (2 * DM) +
                                             (chb & ~1) * 8 + (lane & 1) * 8);
        mbar_wait(bars + 8 * BAR_Q, 0);
        uint32_t tn = 0;
#pragma unroll 1
        for (int j = 0; j < 16; j++) {
          if (j == JS && hw == 2) {
            mbar_wait(bars + 8 * (BAR_Y + 3), 0);
            send_y(2 * XT, 4 * XT, 1);
            fence_async_smem();
            __syncwarp();
            if (lane == 0) mbar_arrive(bars + 8 * BAR_XFREE);
            tn = (uint32_t)clock();
          }
          if (!(j & 7)) {
            mbar_wait(bars + 8 * (BAR_LAND + (j >> 3)), 0);
            tn = (uint32_t)clock() + (hw - 1) * (FPACE / 2);
            PROF2(33 + (j >> 1));
          }
#pragma unroll
          for (int i = 0; i < 2; i++) {
            uint32_t y[4];
            const uint4 q = lds128(qa + i * 512);
            ldsm4t(y, fa + (j & 6) * 64 + (fx ^ (i << 5) ^ ((j & 1) << 6) ^ ((j & 2) << 3)));
            while ((int)((uint32_t)clock() - tn) < 0) __nanosleep(FSL);
            tn += hw == 2 ? FPACE2 : FPACE;
            og[i * 16 * (2 * DM / 8)] = make_uint4(bmul2(q.x, y[0]), bmul2(q.y, y[1]), bmul2(q.z, y[2]), bmul2(q.w, y[3]));
          }
          qa += j == 7 ? OFF_Q1 - OFF_Q0 - 7168 : 1024;
          if (j == 7) fa += 2048;
          og += (j == 7 ? 1024 - 224 : 32) * (2 * DM / 8);
        }
        PROF(22);
      }
      }
      if (MODE != 1 && hw == 3) {
        const uint32_t epoch = ld_relaxed(g_flag_o + cta) + 1;
        if (MODE == 0) nb_sync(NB_G1END, 288);
        if (BDEL) __nanosleep(BDEL);
        if (elect_one()) {
#pragma unroll
          for (int kb = 0; kb < 3; kb++)
            g2_issue_b(bars + 8 * (BAR_FULL2 + kb), kb || MODE ? STG2 : STG2 / 2, sb + g2_b(kb, 0), g2_k(kb) * 64, true);
        }
        __syncwarp();
        const __nv_bfloat16* osrc = g_o + (size_t)(rb2 >> 1) * 16 * 16384 + hsel * 8192;
        if (MODE == 0) __nanosleep(POLL0);
        const uint32_t* flag = g_flag_o + (rb2 >> 1) * 16 + g2_k(lane & 15);
        uint32_t ready = MODE == 0 ? 0u : ~0u;
        unsigned long long seq = G2_SEQ >> 8;
#pragma unroll 1
        for (int kb = 2; kb < 16; kb++, seq >>= 4) {
          uint32_t so = bars + (seq & 7) * 8, dst = sb + g2_a(seq & 7, hsel) + rank * 8192;
          const uint32_t ph = (uint32_t)seq >> 3 & 1;
          const __nv_bfloat16* src = osrc + rank * 4096 + (uint32_t)g2_k(kb) * 16384;
          asm volatile("" : "+r"(so), "+r"(dst), "+l"(src));
          if (!(ready >> kb & 1)) {
#pragma unroll 1
            for (int n = 0; n < SPIN_LIMIT && !(ready >> kb & 1); n++)
              ready = __ballot_sync(0xffffffffu, ld_acquire(flag) == epoch);
            fence_async_all();
          }
          if (kb == 2) PROF(21);
          if (MODE == 0 && kb == G2_KB4 && rank == 1) mbar_wait(bars + 8 * BAR_TAB, 0);
          mbar_wait(so + 8 * BAR_EMPTY2, ph);
          if (elect_one()) {
            asm volatile(
                "cp.async.bulk.shared::cluster.global.mbarrier::complete_tx::bytes.multicast::cluster [%0], [%1], %2, [%3], %4;\n"
                ::"r"(dst), "l"(src), "r"(8192), "r"(so + 8 * BAR_FULL2), "h"((uint16_t)3) : "memory");
          }
          __syncwarp();
        }
      }
    }
    cluster_sync_all();
    PROF_DUMP();
  } else {
    asm volatile("setmaxnreg.inc.sync.aligned.u32 %0;\n" :: "n"(REG_MATH));
    if (warp == 0) PROF2(26);
    const int wg = warp >> 2;
    const int wtid = tid & 127;
    const bool signaller = (wtid == 0) || (wtid == 32);
    const uint32_t rbars = mapa(bars, wtid >> 5 & 1);

    if (halo_cta) {
      const uint32_t epoch = ld_relaxed(g_flag_h + blockIdx.x) + 1;
      float acc0[64], acc1[64];
      int s = 0, ph = 0;
#pragma unroll 1
      for (int kb = 0; kb < 16; kb++) {
        mbar_wait(bars + 8 * (BAR_FULLB + s), ph);
        const uint32_t st = sb + s * STGH;
        const uint64_t da = mkdesc(st, 16, 1024, 1);
        const uint64_t db = mkdesc(st + 8192 + wg * 32768, 8192, 1024, 1);
        wg_fence();
#pragma unroll
        for (int kk = 0; kk < 4; kk++) {
          wgmma_n128(acc0, da + 2 * kk, db + 128 * kk, kb + kk);
          wgmma_n128(acc1, da + 2 * kk, db + 1024 + 128 * kk, kb + kk);
        }
        wg_commit();
        wg_wait<0>();
        if (kb == 15) PROF(37);
        if (wtid == 0) mbar_arrive(bars + 8 * (BAR_EMPTYB + s));
        if (++s == 3) { s = 0; ph ^= 1; }
      }
      fence_regs(acc0);
      fence_regs(acc1);
      if ((warp & 3) != 3) {
#pragma unroll
        for (int hh = 0; hh < 2; hh++) {
          uint4* dst = g_halo + ((hh * 4 + (warp & 3) + 1) * 16 + blockIdx.x * 4) * 128 + wg * 64 + lane;
#pragma unroll
          for (int j = 0; j < 4; j++) {
            const int o = 16 * j + 2 * hh;
            dst[(j >> 1) * 128 + (j & 1) * 32] =
                make_uint4(pack_bf16(acc0[o], acc0[o + 1]), pack_bf16(acc0[o + 4], acc0[o + 5]),
                           pack_bf16(acc0[o + 8], acc0[o + 9]), pack_bf16(acc0[o + 12], acc0[o + 13]));
            dst[(2 + (j >> 1)) * 128 + (j & 1) * 32] =
                make_uint4(pack_bf16(acc1[o], acc1[o + 1]), pack_bf16(acc1[o + 4], acc1[o + 5]),
                           pack_bf16(acc1[o + 8], acc1[o + 9]), pack_bf16(acc1[o + 12], acc1[o + 13]));
          }
        }
      }
      nb_sync(NB_G1DONE, 256);
      if (tid == 0) st_release(g_flag_h + blockIdx.x, epoch);
      PROF(36);
      cluster_sync_all();
      return;
    }

    float acc[64];
    const uint32_t g2rel = wtid ? mapa(bars, rank) + 8 * BAR_EMPTY2B : mapa(bars, wg) + 8 * BAR_EMPTY2;
    uint32_t g2a = (uint32_t)mkdesc(sb + wg * 8192, 16, 0, 0), g2b = (uint32_t)mkdesc(sb, 8192, 0, 0);
    auto g2_block = [&](bool first, int s, int ph) {
      mbar_wait(bars + 8 * (BAR_FULL2 + s), ph);
      const uint32_t da = g2a + (g2_a(s, hsel) >> 4), db = g2b + (g2_b(s, rank) >> 4), dc = db + (g2_bk(s) >> 4);
      wg_fence();
      if (first) wgmma_n128z(acc, da, db);
      else wgmma_n128a(acc, da, db);
      wgmma_n128a(acc, da + 2, db + 128);
      wgmma_n128a(acc, da + 4, dc);
      wgmma_n128a(acc, da + 6, dc + 128);
      wg_commit();
    };
    if (MODE != 2) {
    uint32_t a1[2][4], sc[2];
    C2 t[2];
    {
      float acc0[96], acc1[96];
      int sa = 0, pha = 0, sbb = 0, phb = 0;
      if (tid == 0) {
        mbar_arrive(bars + 8 * BAR_FULLA);
        mbar_arrive(bars + 8 * BAR_FULLB);
      }
#pragma unroll 1
      for (int kb = 0; kb < 30; kb++) {
        uint64_t da = mkdesc(sb + sa * STG1A + wg * 16384 + (kb & 1) * 64, 16, 2048, 1);
        uint64_t db = mkdesc(sb + OFF_1B + sbb * STG1B, 4096, 1024, 1);
        asm volatile("" : "+l"(da), "+l"(db));
        if (kb) {
          if (!(kb & 1)) mbar_wait(bars + 8 * (BAR_FULLA + sa), pha);
          mbar_wait(bars + 8 * (BAR_FULLB + sbb), phb);
        } else {
          asm volatile("cp.async.wait_group 0;\n" ::: "memory");
          fence_async_smem();
          nb_sync(NB_FIRST, 256);
          PROF(0 + wg);
        }
        if (kb == 4 && wg == 0) PROF2(28);
        if (kb == 8 && wg == 0) PROF2(29);
        if (kb == 16 && wg == 0) PROF2(30);
        wg_fence();
        wgmma_n192(acc0, da + 64, db, kb);
        wgmma_n192(acc1, da, db, kb);
        wgmma_n192(acc0, da + 66, db + 128, 1);
        wgmma_n192(acc1, da + 2, db + 128, 1);
        wg_commit();
        wg_wait<1>();
        if (kb > 0) {
          if (wtid == 64) mbar_arrive(bars + 8 * (BAR_EMPTYB + (sbb == 0 ? NS1B - 1 : sbb - 1)));
          if (!(kb & 1) && signaller) mbar_arrive_cluster(rbars + 8 * (BAR_EMPTYA + (sa == 0 ? NS1A - 1 : sa - 1)));
        }
        if (++sbb == NS1B) { sbb = 0; phb ^= 1; }
        if ((kb & 1) && ++sa == NS1A) { sa = 0; pha ^= 1; }
      }
      const int lr = lane & 7, lm = lane >> 3;
      const bool le0 = 2 * (lane & 3) <= (lane >> 2), le1 = 2 * (lane & 3) + 1 <= (lane >> 2);
      const uint32_t maskLE = (le0 ? 0x0000FFFFu : 0u) | (le1 ? 0xFFFF0000u : 0u);
      uint32_t q[4][8], k[5][8], vt[5][8];
      {
        static_assert(15 % NS1A == 0 && 30 % NS1B == 0, "slots of the last k blocks");
        asm volatile("ld.volatile.global.v4.u32 {%0,%1,%2,%3}, [%4];\n"
                     : "=r"(t[0].r), "=r"(t[1].r), "=r"(t[0].i), "=r"(t[1].i) : "l"(g_tab + 1536 + wtid * 4) : "memory");
        mbar_wait(bars + 8 * BAR_FULLA, 1);
        mbar_wait(bars + 8 * BAR_FULLB, 0);
        mbar_wait(bars + 8 * (BAR_FULLB + 1), 0);
        mbar_wait(bars + 8 * (BAR_EMPTYA + 1), 0);
        const uint64_t da = mkdesc(sb + wg * 16384, 16, 2048, 1);
        const uint64_t db = mkdesc(sb + OFF_1B, 4096, 1024, 1);
        wg_fence();
#pragma unroll
        for (int i = 0; i < 4; i++) wgmma_n192(acc0, da + 64 + 2 * i, db + (i >> 1) * (STG1B >> 4) + (i & 1) * 128, 1);
        wg_commit();
#pragma unroll
        for (int i = 0; i < 2; i++) wgmma_n192(acc1, da + 2 * i, db + (i >> 1) * (STG1B >> 4) + (i & 1) * 128, 1);
        wg_commit();
        wg_wait<1>();
        fence_regs(acc0);
        PROFA(45, 0);
        attn_pack<8, 1, false>(acc0, k[4]);
        attn_pack<16, 1, true>(acc0, vt[4]);
        const uint32_t kh = sb + (warp == 7 ? OFF_OP + 7 * 4096 : OFF_KH + (warp + 1) * 2048) + lane * 16;
        sts128(kh, k[4][0], k[4][1], k[4][2], k[4][3]);
        sts128(kh + 512, k[4][4], k[4][5], k[4][6], k[4][7]);
#pragma unroll
        for (int i = 0; i < 4; i++) sts64(kh - lane * 8 + 1024 + 256 * i, vt[4][2 * i], vt[4][2 * i + 1]);
#pragma unroll
        for (int i = 2; i < 4; i++) wgmma_n192(acc1, da + 2 * i, db + (i >> 1) * (STG1B >> 4) + (i & 1) * 128, 1);
        wg_commit();
        attn_pack<0, 0, false>(acc0, q[1]);
        attn_pack<0, 1, false>(acc0, q[3]);
        attn_pack<8, 0, false>(acc0, k[2]);
        attn_pack<16, 0, true>(acc0, vt[2]);
        uint32_t z = p.zero;
#pragma unroll
        for (int i = 0; i < 8; i++) z &= q[1][i] & q[3][i];
#pragma unroll
        for (int i = 0; i < 8; i += 2) z &= k[2][i] & k[2][i + 1];
        __syncwarp();
        if (lane == 0) mbar_arrive(bars + 8 * BAR_STG + z);
        wg_wait<0>();
        fence_regs(acc1);
        if (MODE == 0) nb_arrive(NB_G1END, 288);
      }
      PROF(2 + wg);
      mbar_wait(bars + 8 * (warp == 0 ? BAR_HALO : BAR_STG), 0);
      {
        const uint32_t kh = sb + OFF_KH + warp * 2048 + lane * 16;
#pragma unroll
        for (int i = 0; i < 2; i++) {
          const uint4 t = lds128(kh + 512 * i);
          k[0][4 * i] = t.x; k[0][4 * i + 1] = t.y; k[0][4 * i + 2] = t.z; k[0][4 * i + 3] = t.w;
        }
#pragma unroll
        for (int i = 0; i < 4; i++) {
          const uint2 t = lds64(kh - lane * 8 + 1024 + 256 * i);
          vt[0][2 * i] = t.x; vt[0][2 * i + 1] = t.y;
        }
      }
      attn_pack<0, 0, false>(acc1, q[0]);
      attn_pack<0, 1, false>(acc1, q[2]);
      attn_pack<8, 0, false>(acc1, k[1]);
      attn_pack<8, 1, false>(acc1, k[3]);
      {
        float x[8][2];
        uint32_t pp[8];
        const bool first = warp == 0 && gidx == 0;
#pragma unroll
        for (int hd = 0; hd < 2; hd++) {
#pragma unroll
          for (int j = 0; j < 4; j += 2) {
            float s0[4], s1[4], s2[4];
            attn_qk(s2, q[j], q[j + 1], k[j + 2], 4 * hd);
            attn_qk(s1, q[j], q[j + 1], k[j + 1], 4 * hd);
            attn_qk(s0, q[j], q[j + 1], k[j], 4 * hd);
            if (j == 0 && first) s0[0] = s0[1] = -1e9f / 0.17677669529663687f;
            x[2 * j + hd][0] = le0 ? s1[0] : s0[0];
            x[2 * j + hd][1] = le1 ? s1[1] : s0[1];
            x[2 * j + 2 + hd][0] = le0 ? s2[2] : s1[2];
            x[2 * j + 2 + hd][1] = le1 ? s2[3] : s1[3];
          }
        }
        PROFA(40, __float_as_uint(x[1][0] + x[7][1]));
        attn_pack<16, 0, true>(acc1, vt[1]);
        attn_pack<16, 1, true>(acc1, vt[3]);
        quad_softmax<8>(x, pp);
        PROFA(41, pp[1] + pp[7]);
        mbar_wait(bars + 8 * BAR_X, 0);
        ldsm4(a1[0], sb + OFF_T32 + (warp & 3) * 1024 + lane * 16);
        ldsm4(a1[1], sb + OFF_T32 + 512 + (warp & 3) * 1024 + lane * 16);
        {
          const uint32_t ex = sb + OFF_EX + wg * 16 + (warp & 2) * 2;
#pragma unroll
          for (int i = 0; i < 2; i++) sc[i] = min(max(381 - (int)lds32(ex + 8 * i) - (int)lds32(ex + 32 + 8 * i), 1), 254) * 0x00800080u;
        }
        const uint32_t obase = sb + OFF_OP + (warp * 32 + lr) * 128;
#pragma unroll
        for (int n = 0; n < 8; n++) {
          attn_pv(obase + (n >> 1) * 1024 + (((4 * (n & 1) + lm) ^ lr) << 4), vt[n >> 1], vt[(n >> 1) + 1], 4 * (n & 1), pp[n],
                  maskLE);
        }
      }
      PROFA(42, 0);
    }

    {
      const int w = warp & 3;
      const int lr = lane & 7, lm = lane >> 3;
      const uint32_t xb = sb + OFF_X + wg * 4 * XT;
      auto uo = [](int c) { return (c & 1) * 2 * XT + (c >> 1) * 2048; };
      const uint64_t dc2 = mkdesc(sb + OFF_T16, 512, 128, 0), dc3 = mkdesc(sb + OFF_T16, 128, 512, 0);
      const uint64_t dc4 = mkdesc(sb + OFF_T32, 128, 256, 0);
      const uint64_t dx = mkdesc(xb, 4096, 512, 2), dz = mkdesc(xb, 4096, 256, 3);
      const uint32_t zs = xb + (w * 16 + (lm & 1) * 8 + lr) * 32 + (((lm >> 1) ^ (lr >> 2)) << 4);
      const uint32_t ys = xb + w * 4096 + (lm >> 1) * 256 + ((lr * 32 + (((lm & 1) ^ (lr >> 2)) << 4)) ^ (rank << 6) ^ ((w & 2) << 4));
      const bool own = (w & 1) == rank;
      const uint32_t ybar = mapa(bars, own ? rank ^ 1 : rank) + 8 * BAR_Y;
      uint32_t d[2][32], pa[2][4][2][4], e[4][4][8], ya[2][2][2][4], v[2][2][8];
      C2 s1[2][2][2];
      float o[2][16];
      auto rows = [&](int c) {
        fft_rows(d[c & 1], a1, dx + (uo(c) >> 4));
        wg_commit();
      };
      auto cols = [&](int c) {
        const int s = c & 1;
        fence_regs(d[s]);
#pragma unroll
        for (int i = 0; i < 16; i++) {
          const C2 z = crot(C2{d[s][2 * i], d[s][2 * i + 1]}, t[i & 1]);
          pa[s][i >> 2][i & 1][(i >> 1) & 1] = z.r;
          pa[s][i >> 2][i & 1][2 + ((i >> 1) & 1)] = z.i;
        }
        wg_fence();
#pragma unroll
        for (int i = 0; i < 4; i++) fft_cols<0>(e[c][i], pa[s][i], dc2);
        wg_commit();
      };
      auto prod = [&](int c, int n) {
        const int s = c & 1;
        fence_regs(e[c][2 * n]);
        fence_regs(e[c][2 * n + 1]);
#pragma unroll
        for (int j = 0; j < 2; j++) {
          const C2 u0 = cget(e[s][2 * n], j, 0), u1 = cget(e[s][2 * n], j, 1);
          const C2 h0 = cget(e[s][2 * n + 1], j, 0), h1 = cget(e[s][2 * n + 1], j, 1);
          C2 y0, y1;
          if (c < 2) {
            y0 = cmul(h0, u0);
            s1[s][n][j] = cfma(h0, u1, cmul(h1, u0));
            y1 = C2{hadd2(s1[s][n][j].r, y0.i), hadd2(s1[s][n][j].i, hneg2(y0.r))};
          } else {
            const C2 u2 = cget(e[c][2 * n], j, 0), u3 = cget(e[c][2 * n], j, 1);
            const C2 h2 = cget(e[c][2 * n + 1], j, 0), h3 = cget(e[c][2 * n + 1], j, 1);
            const C2 s2 = cfma(h0, u2, cfma(h2, u0, cmul(h1, u1)));
            y0 = C2{hadd2(s2.r, s1[s][n][j].i), hadd2(s2.i, hneg2(s1[s][n][j].r))};
            y1 = cfma(h0, u3, cfma(h1, u2, cfma(h2, u1, cfma(h3, u0, C2{s2.i, hneg2(s2.r)}))));
          }
          ya[s][n][j][0] = y0.r;
          ya[s][n][j][1] = y1.r;
          ya[s][n][j][2] = y0.i;
          ya[s][n][j][3] = y1.i;
        }
      };
      auto icols = [&](int c) {
        wg_fence();
        fft_cols<1>(v[c & 1][0], ya[c & 1][0], dc3);
        fft_cols<1>(v[c & 1][1], ya[c & 1][1], dc3);
        wg_commit();
      };
      auto stage = [&](int c) {
        const int s = c & 1;
        fence_regs(v[s][0]);
        fence_regs(v[s][1]);
#pragma unroll
        for (int b = 0; b < 4; b++) {
          const C2 x0 = cget(v[s][b >> 1], 0, b & 1), x1 = cget(v[s][b >> 1], 1, b & 1);
          const C2 z0 = crot(C2{x0.i, x0.r}, t[0]), z1 = crot(C2{x1.i, x1.r}, t[1]);
          stsm4(zs + uo(c) + b * 4096, z0.i, z0.r, z1.i, z1.r);
        }
      };
      auto back = [&](int c) {
        fft_back(o[c & 1], dz + (uo(c) >> 4), dc4);
        wg_commit();
      };
      auto out = [&](int c) {
        float (&r)[16] = o[c & 1];
        fence_regs(r);
#pragma unroll
        for (int i = 0; i < 16; i += 8)
          stsm4t(ys + uo(c) + 64 * i, bmul2(pack_bf16(r[i], r[i + 1]), sc[c & 1]), bmul2(pack_bf16(r[i + 2], r[i + 3]), sc[c & 1]),
                 bmul2(pack_bf16(r[i + 4], r[i + 5]), sc[c & 1]), bmul2(pack_bf16(r[i + 6], r[i + 7]), sc[c & 1]));
      };
      auto signal = [&](int yb, int land) {
        __syncwarp();
        if (lane == 0) {
          mbar_arrive_cluster(ybar + 8 * yb);
          if (own && land >= 0) mbar_arrive(bars + 8 * (BAR_LAND + land));
        }
      };
      wg_fence();
      rows(0);
      rows(1);
      fence_async_smem();
      nb_arrive(NB_OREADY, 288);
      PROF(34 + wg);
      wg_wait<1>();
      cols(0);
      wg_wait<1>();
      cols(1);
      rows(2);
      nb_sync(NB_CONV + wg, 128);
      wg_wait<2>();
      prod(0, 0);
      prod(0, 1);
      icols(0);
      wg_wait<2>();
      prod(1, 0);
      prod(1, 1);
      icols(1);
      PROF3(40 + 10 * wg);
      wg_wait<1>();
      stage(0);
      wg_wait<0>();
      stage(1);
      fence_async_smem();
      cols(2);
      PROF3(41 + 10 * wg);
      nb_sync(NB_CONV + wg, 128);
      back(0);
      back(1);
      wg_wait<2>();
      wg_fence();
      rows(3);
      prod(2, 0);
      wg_wait<1>();
      out(0);
      out(1);
      signal(wg, 0);
      PROF3(42 + 10 * wg);
      prod(2, 1);
      icols(2);
      wg_wait<1>();
      cols(3);
      PROF3(43 + 10 * wg);
      wg_wait<1>();
      stage(2);
      fence_async_smem();
      wg_wait<0>();
      prod(3, 0);
      nb_sync(NB_CONV + wg, 128);
      wg_fence();
      back(2);
      prod(3, 1);
      icols(3);
      PROF3(44 + 10 * wg);
      wg_wait<1>();
      out(2);
      signal(2, -1);
      wg_wait<0>();
      stage(3);
      PROF3(45 + 10 * wg);
      fence_async_smem();
      nb_sync(NB_CONV + wg, 128);
      wg_fence();
      back(3);
      constexpr int G = MODE == 0 && EARLY;
      if (MODE == 0) mbar_wait(bars + 8 * (BAR_EMPTY2 + 4), 0);
      if (G) g2_block(true, 0, 0);
      wg_wait<G>();
      if (lane == 0) mbar_arrive_cluster(mapa(bars, 1) + 8 * BAR_TAB);
      out(3);
      signal(3, 1);
      PROF(6 + wg);
    }
    }

    if (MODE != 1) {
      if (MODE == 2 || !EARLY) g2_block(true, 0, 0);
      const int lr = lane & 7, lm = lane >> 3;
      const uint32_t wb = sb + g2_a(1, 0) + warp * 2048;
      const int orow = (rb2 & 7) * 128 + warp * 16;
      uint4* og = reinterpret_cast<uint4*>(p.out + (size_t)(2 * (orow + lm) + (rb2 >> 3)) * (2 * DM) + DM + cb2 * 128 + lr * 8);
      uint32_t wst = wb + (lr + 8 * (lm & 1)) * 128, wsx = ((lm >> 1) ^ lr) << 4, wld = wb + lm * 128, wlx = (lr ^ lm) << 4;
      asm volatile("" : "+l"(og), "+r"(wst), "+r"(wsx), "+r"(wld), "+r"(wlx));
      static_assert(ENDG == NS2 && (G2SEQ >> 4 & 0xfffff) == (G2SEQ >> 24 & 0xfffff) && (G2SEQ >> 4 & 0xfffff) == G2SEQ >> 44, "rounds");
#pragma unroll 1
      for (int r = 0; r < 3; r++) {
        const bool hold = r == 2 && wg != LEADWG;
        const uint32_t rel0 = g2rel + (r ? 8 * (G2SEQ >> 20 & 7) : 0);
        if (hold) {
          wg_wait<0>();
          if (signaller) mbar_arrive_cluster(rel0);
          nb_sync(NB_LEAD, 256);
        }
#pragma unroll
        for (int i = 1; i <= NS2; i++) {
          const int s = G2SEQ >> (4 * i) & 7;
          g2_block(false, s, (r & 1) ^ (s == 0));
          if (warp == LEADWG * 4) PROF2(40 + 5 * r + i);
          if (i == 1 ? !hold : r < 2) {
            wg_wait<1>();
            if (signaller) mbar_arrive_cluster(i == 1 ? rel0 : g2rel + 8 * (G2SEQ >> (4 * i - 4) & 7));
          }
        }
        if (r == 0) PROF(8 + wg);
        g2a += p.zero;
        g2b += p.zero;
      }
      if (wg == LEADWG) nb_arrive(NB_LEAD, 256);
      wg_wait<0>();
      fence_regs(acc);
      PROF(10 + wg);
#pragma unroll
      for (int h = 0; h < 2; h++) {
        const uint32_t b = h * (g2_a(3, 0) - g2_a(1, 0));
#pragma unroll
        for (int j = 8 * h; j < 8 * h + 8; j += 2)
          stsm4(wst + b + (wsx ^ ((j & 7) << 4)), pack_bf16(acc[4 * j], acc[4 * j + 1]),
                pack_bf16(acc[4 * j + 2], acc[4 * j + 3]), pack_bf16(acc[4 * j + 4], acc[4 * j + 5]),
                pack_bf16(acc[4 * j + 6], acc[4 * j + 7]));
        if (OTMA == 2 || (OTMA == 1 && wg == LEADWG)) {
          fence_async_smem();
          __syncwarp();
          if (elect_one()) {
            tma_store_3d(&tmOb, wb + b, DM + cb2 * 128 + h * 64, rb2 >> 3, orow);
            bulk_commit();
          }
        } else {
          __syncwarp();
          uint4 v[4];
#pragma unroll
          for (int i = 0; i < 4; i++) v[i] = lds128(wld + b + i * 512 + (wlx ^ ((i & 1) << 6)));
#pragma unroll
          for (int i = 0; i < 4; i++) og[(size_t)i * 8 * (2 * DM / 8) + h * 8] = v[i];
        }
      }
      PROF(12 + wg);
      if (OTMA) bulk_wait0();
    }
    cluster_sync_all();
  }
}

typedef CUresult (*EncodeFn)(CUtensorMap*, CUtensorMapDataType, cuuint32_t, void*, const cuuint64_t*, const cuuint64_t*,
                             const cuuint32_t*, const cuuint32_t*, CUtensorMapInterleave, CUtensorMapSwizzle,
                             CUtensorMapL2promotion, CUtensorMapFloatOOBfill);

void make_map(EncodeFn enc, CUtensorMap* tm, const void* base, int rank, const cuuint64_t* dims, const cuuint64_t* strides,
              const cuuint32_t* box, CUtensorMapSwizzle swz) {
  cuuint32_t es[5] = {1, 1, 1, 1, 1};
  enc(tm, CU_TENSOR_MAP_DATA_TYPE_BFLOAT16, rank, const_cast<void*>(base), dims, strides, box, es,
      CU_TENSOR_MAP_INTERLEAVE_NONE, swz, CU_TENSOR_MAP_L2_PROMOTION_L2_256B, CU_TENSOR_MAP_FLOAT_OOB_FILL_NONE);
}

}

extern "C" void kernel_launch(void* const* d_in, const int* in_sizes, int n_in, void* d_out, int out_size) {
  static EncodeFn enc = nullptr;
  static bool coresident = true;
  if (!enc) {
    void* fn = nullptr;
    cudaDriverEntryPointQueryResult qr;
    cudaGetDriverEntryPoint("cuTensorMapEncodeTiled", &fn, cudaEnableDefault, &qr);
    enc = (EncodeFn)fn;
    cudaFuncSetAttribute(fused_kernel<0>, cudaFuncAttributeMaxDynamicSharedMemorySize, SMEM_BYTES);
    cudaFuncSetAttribute(fused_kernel<1>, cudaFuncAttributeMaxDynamicSharedMemorySize, SMEM_BYTES);
    cudaFuncSetAttribute(fused_kernel<2>, cudaFuncAttributeMaxDynamicSharedMemorySize, SMEM_BYTES);
    cudaLaunchConfig_t cfg = {};
    cfg.gridDim = dim3(NCTA);
    cfg.blockDim = dim3(NTHREADS);
    cfg.dynamicSmemBytes = SMEM_BYTES;
    cudaLaunchAttribute at;
    at.id = cudaLaunchAttributeClusterDimension;
    at.val.clusterDim.x = 2;
    at.val.clusterDim.y = 1;
    at.val.clusterDim.z = 1;
    cfg.attrs = &at;
    cfg.numAttrs = 1;
    int nclusters = 0;
    if (cudaOccupancyMaxActiveClusters(&nclusters, fused_kernel<0>, &cfg) == cudaSuccess) coresident = nclusters >= NCTA / 2;
    (void)cudaGetLastError();
  }
  CUtensorMap tmX, tmW, tmWo, tmWp, tmQ, tmOb, tmXh, tmWh;
  {
    cuuint64_t dims[3] = {1024, 2, 1024};
    cuuint64_t str[2] = {2048, 4096};
    cuuint32_t box[3] = {64, 1, 128};
    make_map(enc, &tmX, d_in[6], 3, dims, str, box, CU_TENSOR_MAP_SWIZZLE_128B);
  }
  {
    cuuint64_t dims[3] = {1024, 1024, 3};
    cuuint64_t str[2] = {6144, 2048};
    cuuint32_t box[3] = {64, 32, 3};
    make_map(enc, &tmW, d_in[7], 3, dims, str, box, CU_TENSOR_MAP_SWIZZLE_128B);
  }
  {
    cuuint64_t dims[3] = {64, 1024, 16};
    cuuint64_t str[2] = {2048, 128};
    cuuint32_t box[3] = {64, 64, 2};
    cuuint32_t piece[3] = {64, 32, 1};
    make_map(enc, &tmWo, d_in[8], 3, dims, str, box, CU_TENSOR_MAP_SWIZZLE_128B);
    make_map(enc, &tmWp, d_in[8], 3, dims, str, piece, CU_TENSOR_MAP_SWIZZLE_128B);
  }
  {
    cuuint64_t dims[5] = {1024, 2, 2, 4, 128};
    cuuint64_t str[4] = {2048, 8 * 2048, 2 * 2048, 16 * 2048};
    cuuint32_t box[5] = {16, 2, 2, 4, 32};
    make_map(enc, &tmQ, d_in[0], 5, dims, str, box, CU_TENSOR_MAP_SWIZZLE_NONE);
  }
  {
    cuuint64_t dims[3] = {2048, 2, 1024};
    cuuint64_t str[2] = {4096, 8192};
    cuuint32_t box[3] = {64, 1, 16};
    make_map(enc, &tmOb, d_out, 3, dims, str, box, CU_TENSOR_MAP_SWIZZLE_128B);
  }
  {
    cuuint64_t dims[4] = {1024, 256, 2, 4};
    cuuint64_t str[3] = {4096, 2048, 256 * 4096};
    cuuint32_t box[4] = {64, 8, 2, 3};
    make_map(enc, &tmXh, d_in[6], 4, dims, str, box, CU_TENSOR_MAP_SWIZZLE_128B);
  }
  {
    cuuint64_t dims[3] = {64, 1024, 48};
    cuuint64_t str[2] = {6144, 128};
    cuuint32_t box[3] = {64, 64, 4};
    make_map(enc, &tmWh, d_in[7], 3, dims, str, box, CU_TENSOR_MAP_SWIZZLE_128B);
  }
  Params p;
  p.q = (const __nv_bfloat16*)d_in[0];
  p.k = (const __nv_bfloat16*)d_in[1];
  p.v = (const __nv_bfloat16*)d_in[2];
  p.shift_k = (const __nv_bfloat16*)d_in[3];
  p.ssm_k = (const __nv_bfloat16*)d_in[4];
  p.ssm_D = (const __nv_bfloat16*)d_in[5];
  p.x = (const __nv_bfloat16*)d_in[6];
  p.w = (const __nv_bfloat16*)d_in[7];
  p.wo = (const __nv_bfloat16*)d_in[8];
  p.out = (__nv_bfloat16*)d_out;
  p.zero = 0;
  if (coresident) {
    fused_kernel<0><<<NCTA, NTHREADS, SMEM_BYTES>>>(p, tmX, tmW, tmWo, tmWp, tmQ, tmOb, tmXh, tmWh);
  } else {
    fused_kernel<0><<<4, NTHREADS, SMEM_BYTES>>>(p, tmX, tmW, tmWo, tmWp, tmQ, tmOb, tmXh, tmWh);
    fused_kernel<1><<<NCTA, NTHREADS, SMEM_BYTES>>>(p, tmX, tmW, tmWo, tmWp, tmQ, tmOb, tmXh, tmWh);
    fused_kernel<2><<<NCTA, NTHREADS, SMEM_BYTES>>>(p, tmX, tmW, tmWo, tmWp, tmQ, tmOb, tmXh, tmWh);
  }
}
```

```cpp
#include <cuda_runtime.h>
#include <cuda.h>
#include <cuda_bf16.h>
#include <stdint.h>

namespace {

constexpr int SEQ = 2048;
constexpr int DM = 1024;
constexpr int NCTA = 132;
constexpr int NTHREADS = 384;

constexpr int STG1A = 32768;
constexpr int NS1A = 3;
constexpr int STG1B = 12288;
constexpr int NS1B = 5;
constexpr int OFF_1B = NS1A * STG1A;
constexpr int STG2 = 32768;
constexpr int NS2 = 5;
#define G2SEQ 0x0432104321043210ull
constexpr unsigned long long g2_seq() {
  unsigned long long r = G2SEQ;
  for (int kb = 0; kb < 16; kb++)
    for (int j = 0; j < kb; j++)
      if (((G2SEQ >> (4 * j)) & 7) == ((G2SEQ >> (4 * kb)) & 7)) r ^= 8ull << (4 * kb);
  return r;
}
constexpr unsigned long long G2_SEQ = g2_seq();
constexpr int g2_first4() {
  int kb = 0;
  while (((G2SEQ >> (4 * kb)) & 7) != 4) kb++;
  return kb;
}
constexpr int G2_KB4 = g2_first4();
#define POLL0 1500
#define QORD 1
#define BDEL 0
#define XPF 0
#define HPF0 3
#define PF0 8
#define PF1 12
#define PSTEP 1150
#define FPACE 260
#define LEADWG 1
#define OTMA 1
#define EARLY 1
#define R3 0
#define FSL 50
#define JS 1
#define FPACE2 230
#define PFR 1
#define PF2 2
#define PF2X 1
#define STAG 0
#define XW 0
#define ENDG 5
__device__ __forceinline__ uint32_t g2_a(int s, int hsel) { return (((0x97524 >> (4 * s)) & 15) ^ (s & 5 ? 0 : hsel)) << 14; }
constexpr int OFF_Q0 = 3 << 14, OFF_Q1 = 8 << 14;
constexpr int STGH = 73728;
constexpr int OFF_KH = 1 * STG2;
constexpr int OFF_OP = 2 * STG2;
constexpr int OFF_T32 = 5 * STG2 - 4096;
constexpr int OFF_X = 5 * STG2;
constexpr int XT = 8192;
__device__ __forceinline__ uint32_t g2_b(int s, int rank) {
  return s < 3 ? (s == 2 ? 6 : s) << 14 : OFF_X + (s - 3) * 2 * XT + (rank ^ 1) * 4096;
}
__device__ __forceinline__ uint32_t g2_bk(int s) { return s < 3 ? 4096 : 4 * XT; }
constexpr int OFF_BAR = OFF_X + 8 * XT;
constexpr int OFF_EX = OFF_BAR + 448;
constexpr int OFF_T16 = 230400;
constexpr int SMEM_BYTES = OFF_T16 + 2048;
static_assert(OFF_1B + NS1B * STG1B <= OFF_T32 && OFF_X % 1024 == 0, "layout");
static_assert(3 * STGH <= OFF_BAR && OFF_EX + 64 <= OFF_T16 && SMEM_BYTES <= 232448, "smem");

constexpr int BAR_FULLA = 0;
constexpr int BAR_EMPTYA = 3;
constexpr int BAR_FULLB = 6;
constexpr int BAR_EMPTYB = 11;
constexpr int BAR_FULL2 = 16;
constexpr int BAR_EMPTY2 = 21;
constexpr int BAR_EMPTY2B = 44;
constexpr int BAR_X = 26;
constexpr int BAR_LAND = 42;
constexpr int BAR_TAB = 28;
constexpr int BAR_U = 29;
constexpr int BAR_H = 30;
constexpr int BAR_STG = 31;
constexpr int BAR_Y = 32;
constexpr int BAR_XFREE = 38;
constexpr int BAR_HALO = 40;
constexpr int BAR_Q = 41;

constexpr int NB_G1DONE = 1;
constexpr int NB_LEAD = 2;
constexpr int NB_G1END = 3;
constexpr int NB_OREADY = 4;
constexpr int NB_CONV = 5;
constexpr int NB_HELP3 = 11;
constexpr int NB_FIRST = 13;

#define REG_MATH 224
#define REG_HELP 56
constexpr int SPIN_LIMIT = 1 << 20;

__device__ __align__(1024) __nv_bfloat16 g_o[SEQ * DM];
__device__ uint32_t g_flag_o[128];
__device__ uint32_t g_flag_h[4];
__device__ uint4 g_halo[128 * 128];
__device__ __align__(128) const uint32_t g_tab[2048] = {
  0x2fd93000,0x2ea72f64,0x2c722da8,0x263e2a1f,0x2ea73000,0xa63e2a1f,0xafd9ada8,0xac72af64,0x2c723000,0xafd9aa1f,0x263eada8,0x2ea72f64,
  0x263e3000,0xac72af64,0x2ea72da8,0xafd9aa1f,0xa63e3000,0x2c72af64,0xaea72da8,0x2fd9aa1f,0xac723000,0x2fd9aa1f,0xa63eada8,0xaea72f64,
  0xaea73000,0x263e2a1f,0x2fd9ada8,0x2c72af64,0xafd93000,0xaea72f64,0xac722da8,0xa63e2a1f,0x263e0000,0x2c722a1f,0x2ea72da8,0x2fd92f64,
  0x2c720000,0x2fd92f64,0x263e2da8,0xaea7aa1f,0x2ea70000,0x263e2f64,0xafd9ada8,0x2c72aa1f,0x2fd90000,0xaea72a1f,0x2c72ada8,0xa63e2f64,
  0x2fd90000,0xaea7aa1f,0x2c722da8,0xa63eaf64,0x2ea70000,0x263eaf64,0xafd92da8,0x2c722a1f,0x2c720000,0x2fd9af64,0x263eada8,0xaea72a1f,
  0x263e0000,0x2c72aa1f,0x2ea7ada8,0x2fd9af64,0xafd93000,0xaea72f64,0xac722da8,0xa63e2a1f,0xaea73000,0x263e2a1f,0x2fd9ada8,0x2c72af64,
  0xac723000,0x2fd9aa1f,0xa63eada8,0xaea72f64,0xa63e3000,0x2c72af64,0xaea72da8,0x2fd9aa1f,0x263e3000,0xac72af64,0x2ea72da8,0xafd9aa1f,
  0x2c723000,0xafd9aa1f,0x263eada8,0x2ea72f64,0x2ea73000,0xa63e2a1f,0xafd9ada8,0xac72af64,0x2fd93000,0x2ea72f64,0x2c722da8,0x263e2a1f,
  0xa63e0000,0xac722a1f,0xaea72da8,0xafd92f64,0xac720000,0xafd92f64,0xa63e2da8,0x2ea7aa1f,0xaea70000,0xa63e2f64,0x2fd9ada8,0xac72aa1f,
  0xafd90000,0x2ea72a1f,0xac72ada8,0x263e2f64,0xafd90000,0x2ea7aa1f,0xac722da8,0x263eaf64,0xaea70000,0xa63eaf64,0x2fd92da8,0xac722a1f,
  0xac720000,0xafd9af64,0xa63eada8,0x2ea72a1f,0xa63e0000,0xac72aa1f,0xaea7ada8,0xafd9af64,0xa63e0000,0xac72aa1f,0xaea7ada8,0xafd9af64,
  0xac720000,0xafd9af64,0xa63eada8,0x2ea72a1f,0xaea70000,0xa63eaf64,0x2fd92da8,0xac722a1f,0xafd90000,0x2ea7aa1f,0xac722da8,0x263eaf64,
  0xafd90000,0x2ea72a1f,0xac72ada8,0x263e2f64,0xaea70000,0xa63e2f64,0x2fd9ada8,0xac72aa1f,0xac720000,0xafd92f64,0xa63e2da8,0x2ea7aa1f,
  0xa63e0000,0xac722a1f,0xaea72da8,0xafd92f64,0x2fd93000,0x2ea72f64,0x2c722da8,0x263e2a1f,0x2ea73000,0xa63e2a1f,0xafd9ada8,0xac72af64,
  0x2c723000,0xafd9aa1f,0x263eada8,0x2ea72f64,0x263e3000,0xac72af64,0x2ea72da8,0xafd9aa1f,0xa63e3000,0x2c72af64,0xaea72da8,0x2fd9aa1f,
  0xac723000,0x2fd9aa1f,0xa63eada8,0xaea72f64,0xaea73000,0x263e2a1f,0x2fd9ada8,0x2c72af64,0xafd93000,0xaea72f64,0xac722da8,0xa63e2a1f,
  0x263e0000,0x2c72aa1f,0x2ea7ada8,0x2fd9af64,0x2c720000,0x2fd9af64,0x263eada8,0xaea72a1f,0x2ea70000,0x263eaf64,0xafd92da8,0x2c722a1f,
  0x2fd90000,0xaea7aa1f,0x2c722da8,0xa63eaf64,0x2fd90000,0xaea72a1f,0x2c72ada8,0xa63e2f64,0x2ea70000,0x263e2f64,0xafd9ada8,0x2c72aa1f,
  0x2c720000,0x2fd92f64,0x263e2da8,0xaea7aa1f,0x263e0000,0x2c722a1f,0x2ea72da8,0x2fd92f64,0xafd93000,0xaea72f64,0xac722da8,0xa63e2a1f,
  0xaea73000,0x263e2a1f,0x2fd9ada8,0x2c72af64,0xac723000,0x2fd9aa1f,0xa63eada8,0xaea72f64,0xa63e3000,0x2c72af64,0xaea72da8,0x2fd9aa1f,
  0x263e3000,0xac72af64,0x2ea72da8,0xafd9aa1f,0x2c723000,0xafd9aa1f,0x263eada8,0x2ea72f64,0x2ea73000,0xa63e2a1f,0xafd9ada8,0xac72af64,
  0x2fd93000,0x2ea72f64,0x2c722da8,0x263e2a1f,0xa63e0000,0xac72aa1f,0xaea7ada8,0xafd9af64,0x2c720000,0x2fd92f64,0x263e2da8,0xaea7aa1f,
  0xaea70000,0xa63eaf64,0x2fd92da8,0xac722a1f,0x2fd90000,0xaea72a1f,0x2c72ada8,0xa63e2f64,0xafd90000,0x2ea72a1f,0xac72ada8,0x263e2f64,
  0x2ea70000,0x263eaf64,0xafd92da8,0x2c722a1f,0xac720000,0xafd92f64,0xa63e2da8,0x2ea7aa1f,0x263e0000,0x2c72aa1f,0x2ea7ada8,0x2fd9af64,
  0x2fd93000,0x2ea72f64,0x2c722da8,0x263e2a1f,0xaea7b000,0x263eaa1f,0x2fd92da8,0x2c722f64,0x2c723000,0xafd9aa1f,0x263eada8,0x2ea72f64,
  0xa63eb000,0x2c722f64,0xaea7ada8,0x2fd92a1f,0xa63e3000,0x2c72af64,0xaea72da8,0x2fd9aa1f,0x2c72b000,0xafd92a1f,0x263e2da8,0x2ea7af64,
  0xaea73000,0x263e2a1f,0x2fd9ada8,0x2c72af64,0x2fd9b000,0x2ea7af64,0x2c72ada8,0x263eaa1f,0x263e0000,0x2c72aa1f,0x2ea7ada8,0x2fd9af64,
  0xac720000,0xafd92f64,0xa63e2da8,0x2ea7aa1f,0x2ea70000,0x263eaf64,0xafd92da8,0x2c722a1f,0xafd90000,0x2ea72a1f,0xac72ada8,0x263e2f64,
  0x2fd90000,0xaea72a1f,0x2c72ada8,0xa63e2f64,0xaea70000,0xa63eaf64,0x2fd92da8,0xac722a1f,0x2c720000,0x2fd92f64,0x263e2da8,0xaea7aa1f,
  0xa63e0000,0xac72aa1f,0xaea7ada8,0xafd9af64,0xafd93000,0xaea72f64,0xac722da8,0xa63e2a1f,0x2ea7b000,0xa63eaa1f,0xafd92da8,0xac722f64,
  0xac723000,0x2fd9aa1f,0xa63eada8,0xaea72f64,0x263eb000,0xac722f64,0x2ea7ada8,0xafd92a1f,0x263e3000,0xac72af64,0x2ea72da8,0xafd9aa1f,
  0xac72b000,0x2fd92a1f,0xa63e2da8,0xaea7af64,0x2ea73000,0xa63e2a1f,0xafd9ada8,0xac72af64,0xafd9b000,0xaea7af64,0xac72ada8,0xa63eaa1f,
  0xafd9b000,0xaea7af64,0xac72ada8,0xa63eaa1f,0x2ea73000,0xa63e2a1f,0xafd9ada8,0xac72af64,0xac72b000,0x2fd92a1f,0xa63e2da8,0xaea7af64,
  0x263e3000,0xac72af64,0x2ea72da8,0xafd9aa1f,0x263eb000,0xac722f64,0x2ea7ada8,0xafd92a1f,0xac723000,0x2fd9aa1f,0xa63eada8,0xaea72f64,
  0x2ea7b000,0xa63eaa1f,0xafd92da8,0xac722f64,0xafd93000,0xaea72f64,0xac722da8,0xa63e2a1f,0xa63e0000,0xac72aa1f,0xaea7ada8,0xafd9af64,
  0x2c720000,0x2fd92f64,0x263e2da8,0xaea7aa1f,0xaea70000,0xa63eaf64,0x2fd92da8,0xac722a1f,0x2fd90000,0xaea72a1f,0x2c72ada8,0xa63e2f64,
  0xafd90000,0x2ea72a1f,0xac72ada8,0x263e2f64,0x2ea70000,0x263eaf64,0xafd92da8,0x2c722a1f,0xac720000,0xafd92f64,0xa63e2da8,0x2ea7aa1f,
  0x263e0000,0x2c72aa1f,0x2ea7ada8,0x2fd9af64,0x2fd9b000,0x2ea7af64,0x2c72ada8,0x263eaa1f,0xaea73000,0x263e2a1f,0x2fd9ada8,0x2c72af64,
  0x2c72b000,0xafd92a1f,0x263e2da8,0x2ea7af64,0xa63e3000,0x2c72af64,0xaea72da8,0x2fd9aa1f,0xa63eb000,0x2c722f64,0xaea7ada8,0x2fd92a1f,
  0x2c723000,0xafd9aa1f,0x263eada8,0x2ea72f64,0xaea7b000,0x263eaa1f,0x2fd92da8,0x2c722f64,0x2fd93000,0x2ea72f64,0x2c722da8,0x263e2a1f,
  0x263e0000,0x2c72aa1f,0x2ea7ada8,0x2fd9af64,0xac720000,0xafd92f64,0xa63e2da8,0x2ea7aa1f,0x2ea70000,0x263eaf64,0xafd92da8,0x2c722a1f,
  0xafd90000,0x2ea72a1f,0xac72ada8,0x263e2f64,0x2fd90000,0xaea72a1f,0x2c72ada8,0xa63e2f64,0xaea70000,0xa63eaf64,0x2fd92da8,0xac722a1f,
  0x2c720000,0x2fd92f64,0x263e2da8,0xaea7aa1f,0xa63e0000,0xac72aa1f,0xaea7ada8,0xafd9af64,0x316c2fbd,0x343e32f7,0x35bc34ff,0x372c3676,
  0x371532c6,0x3a81392e,0x3bef3b71,0x3b7c3bf2,0x397034cf,0x3bfc3b6c,0x38b23b04,0xb40e31e8,0x3ae13631,0x39e73bf5,0xb6e83219,0xbbe8bb13,
  0x3bc23785,0x30be3aa9,0xbbfdb911,0x2a16b9aa,0x3bfe3865,0xb80f37a6,0xb82abc00,0x3bfd376f,0x3b9238fd,0xbb7f2311,0x3805b929,0x31223bde,
  0x3a85398b,0xbb96b742,0x3bff319e,0xbbb82f8b,0xbbe2bbf1,0xbbb7bbcf,0xbb78bb9a,0xbb27bb52,0xbb2cbbd2,0xb8a8ba19,0xb029b5df,0x35a52f59,
  0xb9dfbba1,0x2ba7b5f7,0x3a7a37b2,0x3bbd3bdd,0xb815bb60,0x39662e91,0x3b373bda,0xb0d7377a,0xb3d3bb10,0x3be9386f,0x2a7a3a31,0xbbfeb9a6,
  0x294dbab0,0x3ae53b07,0xbad51fdb,0xab43bb16,0x352fba41,0x35993c00,0xbaebba1d,0x3be531cf,0x38a3b9c5,0xb5173b21,0x2776bbe0,0x34323bf2,
  0x384537dd,0x38ea3899,0x39823937,0x3a0d39c9,0x39463a93,0x3340374e,0xb426a452,0xb979b7c8,0xbb45b924,0xbb32bc00,0xb371b902,0x38d63294,
  0xb08db9a1,0x3b3f379b,0x39583bd7,0xb8252dfb,0x3bea3a2d,0xb3ba3874,0xbb89bb0d,0x36d2b625,0xb6bb387f,0xb8d1bbf5,0x3be73602,0xb546391f,
  0xba00bb01,0x3bff35eb,0xba5c34db,0x3359bab6,0x3ac7b66b,0xb9413933,0x368dbabd,0xb0103bb3,0xbac4baf7,0xba50ba8c,0xb9cdba11,0xb93cb986,
  0x3a04388e,0x3bcb3b1e,0x3bba3c00,0x39d63afe,0x36af3a21,0xb6ffa17f,0xbbc8ba3d,0xba60bbd4,0xbbebb9af,0xb6c6bb0a,0x39f43263,0x3ad83bf7,
  0x30a6b916,0x3bc33aa5,0xb55e3790,0xbb3dbb63,0x3b423a9e,0xba642ec3,0xb0f0bb6a,0x3b8e3a25,0xb94a37bd,0x2884bb6f,0x38db3b9f,0xbbc9b85a,
  0xb840bb54,0x3a093a15,0xbb4cb850,0x3bef3457,0x3a893a4d,0x3af43ac1,0x3b4f3b24,0x3b983b76,0xbb94baba,0xbbe4bbf9,0xba58bb57,0xb699b8f8,
  0x3bfe3b18,0x394f3b5c,0xb109347b,0xbae8b884,0xbbc0bb68,0xa9b1b90c,0x3b8b387a,0x38bc3ba5,0x3ade3ba7,0xb8c1324b,0xb9f0bbf6,0x39eb9648,
  0xb96bbbd6,0x3bbf3487,0xb38939b3,0xb9f8bba3,0x370a3bf3,0xbb47b994,0x3bbc2d65,0xb8ad3889,0xb153bc00,0x37213b9c,0xb97dba90,0x3af138f3,
  0xb89eb8ee,0xb7e8b84a,0xb682b737,0xb50bb5c8,0x35233855,0xb13b2d33,0xb8e0b65f,0xbb4aba45,0xa8e8b764,0x39fc3648,0x3be63bae,0x380a3a9b,
  0xb3eb360e,0xbbfeba35,0xb552baa2,0x3a7334b7,0x381ab4ab,0x3a6f3bd8,0xb95d2e5f,0xb962bc00,0xb9e3327c,0xb402bbac,0x3bc6399d,0xb95434c3,
  0x3b2faf27,0xb6a439bc,0xb41abbf9,0x3a7e3a97,0xbbe3251b,0x3b2ab4f3,0xb9d23894,0x37f3ba49,0x3bce3bb5,0x3bf03be1,0x3bff3bfa,0x3bfb3bff,
  0x2c38b1b6,0x383a34e7,0x3aee39c0,0x3bff3bb2,0xbb81bbf8,0xb53ab999,0x38302ef5,0x3bed3ab3,0xb8cc9cb6,0xbb85bbab,0x2adeb86a,0x3bc5391b,
  0x38c73bf6,0xbadbb232,0xb6ddbba9,0x3b87361a,0x3b833201,0xb0743a39,0xba76bb5e,0x3b352dc9,0xac06bbb0,0x39743b59,0xbbeeb759,0x3aceb2ad,
  0xbbccb5d4,0x3bfb2d00,0xbb7a32de,0x3a54b7d2,0xb30fb44b,0xafefb185,0xa6adacce,0x2c9c25e4,0xbbfcbbdf,0xbacbbb9e,0xb7feb990,0xa81fb463,
  0xb58d2d97,0xbb90b9b8,0xbad1bbf4,0xb05bb85f,0x3a673c00,0xb5763493,0xbbfdbaac,0xb3a2ba29,0x3a6b2e2d,0x38203bd9,0xbb3ab49f,0xb56abb65,
  0xb581bbdc,0x3bec3907,0xb8b7363c,0xb6f4bbf8,0xbbfcb46f,0x39dab654,0xb0423b1b,0xb835bbd3,0xb3283b73,0xac6abbfa,0x35b13bd0,0xb8e5bafb,
  0x38ee3a0d,0xb84aba89,0x37373af4,0xb5c8bb4f,0x35df3a81,0x2f59bbef,0xb88e3b7c,0x3b1eb946,0x2d973ae8,0x39b8bb81,0xbbf4353a,0x385f3830,
  0xb2633b3f,0x3bf7b958,0xb60eb825,0xba353bc0,0xb7853b87,0x3aa9b3d3,0x3911bbe9,0xb9aa2a7a,0xb99d3bbf,0x34c33389,0x3bdcb9f8,0x3907bb83,
  0xbb013be5,0xb5eb394a,0x34db2884,0x3ab6b8db,0xbbd03bfb,0xbafb3b7a,0xb98b3a54,0xb74238a3,0x3a4db93c,0xbac1389e,0x3b24b7e8,0xbb763682,
  0x3b71b8a8,0xbbf23029,0x3a9335a5,0xb74eba04,0x3bf8b80a,0xb999b58d,0xaef53b90,0x3ab3bad1,0x3bd7b6c6,0xadfbb9f4,0xbb683ad8,0x390c33eb,
  0x3b10b56a,0x386fbbc2,0xba3130be,0xb9a63bfd,0x39b3b402,0x3ba3bbc6,0x3201b954,0xba393581,0x37bdb122,0x3b6fba00,0x3b9fbbff,0x385aba5c,
  0x32deac6a,0x37d2b5b1,0x39c5b8e5,0x3b21ba85,0x344b3b98,0xb185bbce,0x2cce3bf0,0x25e4bbff,0xbc003340,0x3afe3426,0xb855b979,0x2d333b94,
  0x34cfbbed,0xbb6c39df,0x3b042ba7,0xb1e8ba7a,0x3aa2a9b1,0x34b7bb8b,0xbc0038bc,0x349338cc,0xba2d3bfe,0x387430a6,0x3b0dbbc3,0xb625b55e,
  0xb63cb074,0xbbf83a76,0xb8653b35,0x37a6294d,0x3bf3bbc9,0x3994bb2f,0x2d65b6a4,0xb889341a,0xb19e3517,0x2f8b2776,0x366bb432,0x3933b840,
  0x3bb5b50b,0xbbe1330f,0x3bfaafef,0xbbff26ad,0xa4523bcb,0x37c8bbba,0xbaba39d6,0x3bf9b523,0xbba1305b,0x35f73970,0x37b2bbfc,0xbbdd38b2,
  0x387abbfe,0xbba53552,0x9cb63a73,0x3babba67,0x39162a16,0x3aa5bbea,0xb790b3ba,0xbb633b89,0xbb5e3bec,0xadc938b7,0x3ab0b6f4,0x3b07bbfe,
  0xaf27b359,0xb9bc370a,0xbbf93b47,0xba973bbc,0x3be0bb96,0x3bf2bbff,0x3b54bbb8,0x3a15bac7,0xafbd3bfb,0x32f7bbe2,0xb4ff3bb7,0x3676bb78,
  0x365fbbe4,0xba453a58,0x3bdfb699,0xbb9eac38,0xb9243bbd,0x3c00b6af,0xb902b6ff,0xb2943bc8,0x3aacbb85,0xba29aade,0xb6313bc5,0x3bf5b815,
  0xbba73b3d,0x324b381a,0x3bf6ba6f,0x9648b95d,0x3c00bae5,0x376fbad5,0xb87f2b43,0xbbf53b42,0xbbb03a7e,0xbb593bfc,0xb75939da,0x32ad3042,
  0x3abdba09,0x3bb3bb4c,0x3c00bbef,0x3b9cbbe3,0x3bf12c9c,0xbbcfb16c,0x3b9a343e,0xbb52b5bc,0xbb57b13b,0x38f838e0,0xb1b6bb4a,0xb4e73bfc,
  0x3a21340e,0x217fbb45,0xba3d3b32,0x3bd4b371,0xb86ab576,0xb91b3bfd,0x3b60b3a2,0x2e91bae1,0x34ab36d2,0x3bd8bade,0xae5fb8c1,0xbc0039f0,
  0x9fdbb80f,0xbb16382a,0xba9e3bfd,0x2ec336bb,0xb46f38ad,0x3654ac06,0x3b1bb974,0x3bd3bbee,0x3850b941,0x3457b68d,0xa51bb010,0xb4f33153,
  0xb7dd3b27,0x3899bac4,0xb9373a50,0x39c9b9cd,0x3990383a,0xb463baee,0xb2c63bff,0x392ebb2c,0x3b18ba60,0xbb5c28e8,0x347b39fc,0x3884bbe6,
  0xb219b966,0xbb133b37,0x39a130d7,0x379bbbeb,0xbbf63962,0xb2323a6b,0x3ba9b820,0x361abb3a,0xb6023a64,0x391fb0f0,0x3bd6bb8e,0x3487b9e3,
  0x3a41b835,0x3c00bb92,0x3a1dbb7f,0x31cfb805,0x3a90bb2a,0x38f3b9d2,0x35d4b7f3,0x2d00b328,0x3af7372c,0xba8cb845,0x3a1138ea,0xb986b982,
  0x39c0bacb,0xbbb237fe,0x3bd2a81f,0xba19b715,0xb764b8d6,0xb6483bfe,0x3baeb94f,0xba9bb109,0xbbda39e7,0x377a36e8,0x39afbbe8,0xbb0a308d,
  0xae2d39eb,0x3bd9b8c7,0x349fbadb,0xbb6536dd,0x3b6ab8d1,0x3a25bbe7,0xb27cb546,0xbbac396b,0x38fdbace,0xa311b52f,0xb9293599,0xbbde3aeb,
  0xb8943721,0xba49397d,0xbb733af1,0xbbfa3bcc,0xbbfb3bff,0xbbe23bf1,0xbbb73bcf,0xbb783b9a,0xbb7c3bf2,0xb9463a93,0xb340374e,0x3426a452,
  0xba603bd4,0xa8e83764,0x39fcb648,0x3be6bbae,0xb8bc3ba5,0x38cc9cb6,0x3b85bbab,0xaadeb86a,0xb56a3b65,0x3bc2b785,0x30bebaa9,0xbbfd3911,
  0xab433b16,0x3b42ba9e,0xba64aec3,0xb0f03b6a,0x33593ab6,0x370abbf3,0xbb473994,0x3bbcad65,0x37f33a49,0xb328bb73,0xac6a3bfa,0x35b1bbd0,
  0xac9c25e4,0xb16c2fbd,0xb43e32f7,0xb5bc34ff,0xb5a52f59,0xba04388e,0xbbcb3b1e,0xbbba3c00,0xb8d63294,0xbbfe3b18,0xb94f3b5c,0x3109347b,
  0xba7334b7,0xba673c00,0x35763493,0x3bfdbaac,0xbb87361a,0xb3d33b10,0x3be9b86f,0x2a7aba31,0xbbfd376f,0x36bb387f,0x38d1bbf5,0xbbe73602,
  0xbbc9385a,0x3b2f2f27,0xb6a4b9bc,0xb41a3bf9,0xbaf138f3,0x3bccb5d4,0xbbfb2d00,0x3b7a32de,0xbb273b52,0xbac43af7,0xba503a8c,0xb9cd3a11,
  0x3979b7c8,0x3b94baba,0x3be4bbf9,0x3a58bb57,0x380aba9b,0xb58dad97,0xbb9039b8,0xbad13bf4,0xbbc5391b,0xb8153b60,0x3966ae91,0x3b37bbda,
  0x2a1639aa,0x3beaba2d,0xb3bab874,0xbb893b0d,0x3b8eba25,0xb9e3b27c,0xb4023bac,0x3bc6b99d,0xb8adb889,0xac063bb0,0x3974bb59,0xbbee3759,
  0xb8e53afb,0x3a85b98b,0xbb963742,0x3bffb19e,0xb72c3676,0xb84537dd,0xb8ea3899,0xb9823937,0xb9d63afe,0xb5233855,0x313b2d33,0x38e0b65f,
  0x3ae8b884,0x3b81bbf8,0x353ab999,0xb8302ef5,0x33a2ba29,0xbae13631,0xb9e73bf5,0x36e83219,0xbbfe39a6,0x30a63916,0x3bc3baa5,0xb55eb790,
  0x3546391f,0x396bbbd6,0xbbbf3487,0x338939b3,0x3a7eba97,0xbbfc346f,0x39da3654,0xb042bb1b,0xba54b7d2,0x38a339c5,0xb517bb21,0x27763be0,
  0xb93c3986,0xb89e38ee,0xb7e8384a,0xb6823737,0x3699b8f8,0xac38b1b6,0xb83a34e7,0xbaee39c0,0xb05b385f,0x3970b4cf,0x3bfcbb6c,0x38b2bb04,
  0xb0d7b77a,0xbbeb39af,0xb6c63b0a,0x39f4b263,0x36d23625,0x3adebba7,0xb8c1b24b,0xb9f03bf6,0xb954b4c3,0xb5813bdc,0x3becb907,0xb8b7b63c,
  0x3ace32ad,0xb52fba41,0xb5993c00,0x3aebba1d,0xbbb8af8b,0x3ac7366b,0xb941b933,0x368d3abd,0xba0d39c9,0xba893a4d,0xbaf43ac1,0xbb4f3b24,
  0x3b4aba45,0x3bfcbbdf,0x3acbbb9e,0x37feb990,0xbbed3ab3,0xb9df3ba1,0x2ba735f7,0x3a7ab7b2,0x3be8bb13,0x308db9a1,0xbb3f379b,0xb9583bd7,
  0xbb3d3b63,0x381a34ab,0x3a6fbbd8,0xb95dae5f,0x39f8bba3,0xbb833201,0x30743a39,0x3a76bb5e,0xb8353bd3,0x3b92b8fd,0xbb7fa311,0x38053929,
  0x3432bbf2,0xb8403b54,0x3a09ba15,0xbb4c3850,0xb50b35c8,0xb30f344b,0xafef3185,0xa6ad2cce,0xbbff3bb2,0xbb2c3bd2,0xb8a83a19,0xb02935df,
  0xb40eb1e8,0xbb453924,0xbb323c00,0xb3713902,0x3ad8bbf7,0xb3ebb60e,0xbbfe3a35,0xb5523aa2,0x39eb1648,0x38c7bbf6,0xbadb3232,0xb6dd3ba9,
  0xb6f43bf8,0x3bfeb865,0xb80fb7a6,0xb82a3c00,0xbbe531cf,0x394a37bd,0xa884bb6f,0xb8db3b9f,0xb010bbb3,0xb1533c00,0x3721bb9c,0xb97d3a90,
  0xbb983b76,0xbbce3bb5,0xbbf03be1,0xbbff3bfa,0x281fb463,0xb71532c6,0xba81392e,0xbbef3b71,0x3bbdbbdd,0x36afba21,0xb6ff217f,0xbbc83a3d,
  0x38252dfb,0x3bc0bb68,0x29b1b90c,0xbb8b387a,0xb9623c00,0x3a6bae2d,0x3820bbd9,0xbb3a349f,0xbb352dc9,0x294d3ab0,0x3ae5bb07,0xbad59fdb,
  0x3122bbde,0xba003b01,0x3bffb5eb,0xba5cb4db,0x3befb457,0xbbe3a51b,0x3b2a34f3,0xb9d2b894,0x39c939cd,0xba4db93c,0x3ac1389e,0xbb24b7e8,
  0x3b1e3946,0xbc00b340,0x3afeb426,0xb8553979,0x3bdd38b2,0xba21340e,0xa17fbb45,0x3a3d3b32,0x3bf53815,0xb2193966,0xbb13bb37,0x39a1b0d7,
  0x3b6536dd,0x37853b87,0xbaa9b3d3,0xb911bbe9,0x3a393581,0x3b5e3bec,0x2dc938b7,0xbab0b6f4,0x3889341a,0x3bb03a7e,0x3b593bfc,0x375939da,
  0x34f33153,0x38943721,0x3a49397d,0x3b733af1,0xb9863982,0x38eeba0d,0xb84a3a89,0x3737baf4,0xb74e3a04,0xa452bbcb,0x37c83bba,0xbabab9d6,
  0xb1e83a7a,0xb924bbbd,0x3c0036af,0xb90236ff,0x2e913ae1,0xbbdab9e7,0x377ab6e8,0x39af3be8,0x361a3b3a,0xbb10b56a,0xb86fbbc2,0x3a3130be,
  0x39073b83,0xb63c3074,0xbbf8ba76,0xb865bb35,0x3a973bbc,0x346f38ad,0xb654ac06,0xbb1bb974,0x3b9c3be3,0x3a903b2a,0x38f339d2,0x35d437f3,
  0x3b763682,0xbbb5b50b,0x3be1330f,0xbbfaafef,0x2d33bb94,0x365f3be4,0xba45ba58,0x3bdf3699,0xbbd4b371,0x3764b8d6,0x36483bfe,0xbbaeb94f,
  0x379b3beb,0xbbd7b6c6,0x2dfbb9f4,0x3b683ad8,0x39aa2a7a,0x3a2d3bfe,0xb87430a6,0xbb0dbbc3,0xbb07bbfe,0x1fdbb80f,0x3b16382a,0x3a9e3bfd,
  0xb2ad3042,0xba41b835,0xbc00bb92,0xba1dbb7f,0x3bfa3bcc,0x3bd03bfb,0x3afb3b7a,0x398b3a54,0xb5c83b4f,0x344bbb98,0xb1853bce,0x2ccebbf0,
  0x3bf93523,0xbb57313b,0x38f8b8e0,0xb1b63b4a,0xb294bbc8,0x3b183a60,0xbb5ca8e8,0x347bb9fc,0xbb0ab08d,0xb263bb3f,0x3bf73958,0xb60e3825,
  0x39a63bfd,0xb9162a16,0xbaa5bbea,0x3790b3ba,0x37a6a94d,0x3c003ae5,0x376f3ad5,0xb87fab43,0xbbd3bbee,0xb8fdbace,0x2311b52f,0x39293599,
  0x2d003328,0xb2deac6a,0xb7d2b5b1,0xb9c5b8e5,0x3bff26ad,0xbbf12c9c,0x3bcfb16c,0xbb9a343e,0xbb9e2c38,0x3990b83a,0xb4633aee,0xb2c6bbff,
  0x3a9bb109,0xad973ae8,0xb9b8bb81,0x3bf4353a,0xb90c33eb,0xb87abbfe,0x3ba53552,0x1cb63a73,0x3625b55e,0x3ba73b3d,0xb24b381a,0xbbf6ba6f,
  0xaec336bb,0xbb6ab8d1,0xba25bbe7,0x327cb546,0xb1cfb805,0x37bd3122,0x3b6f3a00,0x3b9f3bff,0x374238a3,0x319e3517,0xaf8b2776,0xb66bb432,
  0x25e43bff,0xafbdbbfb,0x32f73be2,0xb4ffbbb7,0xb4e7bbfc,0x39c03acb,0xbbb2b7fe,0x3bd2281f,0x38843be6,0xbbf8b80a,0x3999b58d,0x2ef53b90,
  0xba35bbc0,0x3aa229b1,0x34b73b8b,0xbc00b8bc,0x3b633b89,0xb4ab36d2,0xbbd8bade,0x2e5fb8c1,0xbbf5bb42,0xb602ba64,0x391f30f0,0x3bd63b8e,
  0x3bde3aeb,0x3b013be5,0x35eb394a,0xb4db2884,0xbb21ba85,0xbbe0bb96,0xbbf2bbff,0xbb54bbb8,0x3b52b5bc,0xbaf7372c,0x3a8cb845,0xba1138ea,
  0x392e3b2c,0xbb71b8a8,0x3bf23029,0xba9335a5,0xb85f3830,0xb4cfbbed,0x3b6c39df,0xbb042ba7,0xbbabba67,0x386ab576,0x391b3bfd,0xbb60b3a2,
  0x1648b95d,0x3bf63962,0x32323a6b,0xbba9b820,0x3bac396b,0x399d3bbf,0xb4c33389,0xbbdcb9f8,0x385a3a5c,0xaf273359,0xb9bcb70a,0xbbf9bb47,
  0xb933b840,0xbabdba09,0xbbb3bb4c,0xbc00bbef,0x36763b78,0xb7ddbb27,0x38993ac4,0xb937ba50,0xba193715,0x35dfba81,0x2f593bef,0xb88ebb7c,
  0xbab3bad1,0x3ba1305b,0xb5f73970,0xb7b2bbfc,0x3493b8cc,0x3aac3b85,0xba292ade,0xb631bbc5,0x3c0039f0,0x2e2d39eb,0xbbd9b8c7,0xb49fbadb,
  0x348739e3,0xb9b3b402,0xbba3bbc6,0xb201b954,0xbab6b8db,0xbbf3bbc9,0xb994bb2f,0xad65b6a4,0xba15bac7,0xb850b941,0xb457b68d,0x251bb010,
  0xb9cfbb16,0x30ac2a31,0x3b9c3bf1,0xb493ae2d,0xb76fb8b4,0x35a133e3,0x3a1d3afe,0xb902b76f,0xb3e3b5a1,0x38b4376f,0x376f3902,0xbafeba1d,
  0xaa31b0ac,0x3b1639cf,0x2e2d3493,0xbbf1bb9c,0xb956ba74,0x305f29cc,0x3b633bd2,0xb44badc9,0xb6e7b859,0x353f335e,0x39d23ab6,0xb8bcb6ff,
  0xb35eb53f,0x385936e7,0x36ff38bc,0xbab6b9d2,0xa9ccb05f,0x3a743956,0x2dc9344b,0xbbd2bb63,0xb8e3b9de,0x30122967,0x3b1e3ba1,0xb402ad65,
  0xb662b801,0x34de32da,0x39823a67,0xb874b68d,0xb2dab4de,0x38013662,0x368d3874,0xba67b982,0xa967b012,0x39de38e3,0x2d653402,0xbba1bb1e,
  0xb876b952,0x2f8c2902,0x3ace3b60,0xb371ad00,0xb5e1b758,0x347e3257,0x392e3a11,0xb82ab61a,0xb257b47e,0x375835e1,0x361a382a,0xba11b92e,
  0xa902af8c,0x39523876,0x2d003371,0xbb60bace,0xb80db8ce,0x2ef3289e,0x3a733b10,0xb2deac9c,0xb562b6b3,0x342031d5,0x38d639b3,0xb7bdb5a5,
  0xb1d5b420,0x36b33562,0x35a537bd,0xb9b3b8d6,0xa89eaef3,0x38ce380d,0x2c9c32de,0xbb10ba73,0xb750b851,0x2e5a2839,0x3a0d3ab0,0xb24bac38,
  0xb4e5b613,0x33863153,0x387a394f,0xb721b52f,0xb153b386,0x361334e5,0x352f3721,0xb94fb87a,0xa839ae5a,0x38513750,0x2c38324b,0xbab0ba0d,
  0xb68eb7b4,0x2dc227a9,0x399d3a41,0xb1b6aba7,0xb46ab577,0x32cd30d2,0x381a38e5,0xb682b4b7,0xb0d2b2cd,0x3577346a,0x34b73682,0xb8e5b81a,
  0xa7a9adc2,0x37b4368e,0x2ba731b6,0xba41b99d,0xb5d2b6d1,0x2d2a26e0,0x392439c5,0xb122aade,0xb3e3b4de,0x32163052,0x376f3874,0xb5dfb43e,
  0xb052b216,0x34de33e3,0x343e35df,0xb874b76f,0xa6e0ad2a,0x36d135d2,0x2ade3122,0xb9c5b924,0xb51cb5f6,0x2c932617,0x38a3393c,0xb08daa16,
  0xb2f4b448,0x31602fa5,0x36a437fe,0xb53ab389,0xafa5b160,0x344832f4,0x3389353a,0xb7feb6a4,0xa617ac93,0x35f6351c,0x2a16308d,0xb93cb8a3,
  0xb46ab523,0x2bf6254d,0x381a38a8,0xafefa94d,0xb209b36b,0x30ac2ea7,0x35d4370a,0xb493b294,0xaea7b0ac,0x336b3209,0x32943493,0xb70ab5d4,
  0xa54dabf6,0x3523346a,0x294d2fef,0xb8a8b81a,0xb378b456,0x2ac82484,0x3715380a,0xaec3a884,0xb120b24a,0x2ff22da9,0x34ff360e,0xb3d3b19e,
  0xada9aff2,0x324a3120,0x319e33d3,0xb60eb4ff,0xa484aac8,0x34563378,0x28842ec3,0xb80ab715,0xb223b31c,0x29992376,0x35eb36c6,0xad97a776,
  0xb039b12d,0x2e8d2cac,0x3426350b,0xb27cb0a6,0xacacae8d,0x312d3039,0x30a6327c,0xb50bb426,0xa376a999,0x331c3223,0x27762d97,0xb6c6b5eb,
  0xb0d2b194,0x286b21e4,0x34b7356a,0xac6aa5e4,0xaea7b012,0x2d2a2b5f,0x32943402,0xb122af59,0xab5fad2a,0x30122ea7,0x2f593122,0xb402b294,
  0xa1e4a86b,0x319430d2,0x25e42c6a,0xb56ab4b7,0xaf0cb012,0x267b2052,0x32f73402,0xaa7aa452,0xacdeadf5,0x2b912967,0x30d731e8,0xaf8bad65,
  0xa967ab91,0x2df52cde,0x2d652f8b,0xb1e8b0d7,0xa052a67b,0x30122f0c,0x24522a7a,0xb402b2f7,0xac79ad2a,0x24201d7f,0x30743122,0xa81fa17f,
  0xaa31ab91,0x28d026e0,0x2e2d2f8b,0xacceaade,0xa6e0a8d0,0x2b912a31,0x2ade2cce,0xaf8bae2d,0x9d7fa420,0x2d2a2c79,0x217f281f,0xb122b074,
  0xa7a9a86b,0x1f1218b6,0x2ba72c6a,0xa3119cb6,0xa54da67b,0x242021e4,0x294d2a7a,0xa81fa5e4,0xa1e4a420,0x267b254d,0x25e4281f,0xaa7aa94d,
  0x98b69f12,0x286b27a9,0x1cb62311,0xac6aaba7,0x211b21e4,0x98b69248,0xa51ba5e4,0x1cb61648,0x1f122052,0x9d7f9bdb,0xa311a452,0x217f1fdb,
  0x1bdb1d7f,0xa0529f12,0x9fdba17f,0x24522311,0x124818b6,0xa1e4a11b,0x96489cb6,0x25e4251b,0x2a632b5f,0xa1e49bdb,0xae5faf59,0x25e41fdb,
  0x286b2967,0xa6e0a4e9,0xac6aad65,0x2ade28e8,0x24e926e0,0xa967a86b,0xa8e8aade,0x2d652c6a,0x1bdb21e4,0xab5faa63,0x9fdba5e4,0x2f592e5f,
  0x2dc22ea7,0xa54d9f12,0xb1b6b294,0x294d2311,0x2bf62cde,0xaa31a86b,0xafefb0d7,0x2e2d2c6a,0x286b2a31,0xacdeabf6,0xac6aae2d,0x30d72fef,
  0x1f12254d,0xaea7adc2,0xa311a94d,0x329431b6,0x302c30d2,0xa7a9a11b,0xb41ab4b7,0x2ba7251b,0x2dc22f0c,0xac79aa63,0xb1b6b2f7,0x30742e5f,
  0x2a632c79,0xaf0cadc2,0xae5fb074,0x32f731b6,0x211b27a9,0xb0d2b02c,0xa51baba7,0x34b7341a,0x317a3257,0xa902a2ad,0xb552b61a,0x2d0026ad,
  0x2f8c309f,0xaddcac2e,0xb371b487,0x31cf3029,0x2c2e2ddc,0xb09faf8c,0xb029b1cf,0x34873371,0x22ad2902,0xb257b17a,0xa6adad00,0x361a3552,
  0x32cd33e3,0xaa31a420,0xb682b76f,0x2e2d281f,0x30ac31bb,0xaf3fad2a,0xb493b58d,0x33283122,0x2d2a2f3f,0xb1bbb0ac,0xb122b328,0x358d3493,
  0x24202a31,0xb3e3b2cd,0xa81fae2d,0x376f3682,0x341334bc,0xab5fa4e9,0xb7a6b85a,0x2f5928e8,0x319432da,0xb052ae28,0xb56ab68d,0x343e3219,
  0x2e283052,0xb2dab194,0xb219b43e,0x368d356a,0x24e92b5f,0xb4bcb413,0xa8e8af59,0x385a37a6,0x34c3358c,0xac47a5b2,0xb85fb8f3,0x304229b1,
  0x327e33fd,0xb106af26,0xb63cb785,0x34e7330f,0x2f263106,0xb3fdb27e,0xb30fb4e7,0x3785363c,0x25b22c47,0xb58cb4c3,0xa9b1b042,0x38f3385f,
  0x35773662,0xacdea67b,0xb8e5b982,0x30d72a7a,0x336b3493,0xb1bbb012,0xb70ab83a,0x358d3402,0x301231bb,0xb493b36b,0xb402b58d,0x383a370a,
  0x267b2cde,0xb662b577,0xaa7ab0d7,0x398238e5,0x36303741,0xad76a744,0xb962ba04,0x316c2b43,0x342e352a,0xb271b092,0xb7d2b8ad,0x3631347b,
  0x30923271,0xb52ab42e,0xb47bb631,0x38ad37d2,0x27442d76,0xb741b630,0xab43b16c,0x3a043962,0x36ee3815,0xae0ea807,0xb9d6ba7a,0x32012c06,
  0x34a735c4,0xb329b113,0xb84ab91b,0x36d234f3,0x31133329,0xb5c4b4a7,0xb4f3b6d2,0x391b384a,0x28072e0e,0xb815b6ee,0xac06b201,0x3a7a39d6,
  0x37b4388e,0xaea7a86b,0xba41bae1,0x32942c6a,0x35233662,0xb3e3b194,0xb8a8b982,0x376f356a,0x319433e3,0xb662b523,0xb56ab76f,0x398238a8,
  0x286b2ea7,0xb88eb7b4,0xac6ab294,0x3ae13a41,0x3841390f,0xaf3fa8d0,0xbaa2bb3a,0x33282cce,0x35a13705,0xb44fb216,0xb902b9e3,0x380535df,
  0x3216344f,0xb705b5a1,0xb5dfb805,0x39e33902,0x28d02f3f,0xb90fb841,0xacceb328,0x3b3a3aa2,0x38ac3997,0xafd8a935,0xbaf7bb83,0x33ba2d33,
  0x362137ac,0xb4aeb298,0xb958ba3d,0x38503654,0x329834ae,0xb7acb621,0xb654b850,0x3a3d3958,0x29352fd8,0xb997b8ac,0xad33b3ba,0x3b833af7,
  0x391c3a28,0xb039a999,0xbb42bbbc,0x34262d97,0x36a4382d,0xb50eb31c,0xb9aaba90,0x389936c6,0x331c350e,0xb82db6a4,0xb6c6b899,0x3a9039aa,
  0x29993039,0xba28b91c,0xad97b426,0x3bbc3b42,0x39923ac3,0xb085a9fe,0xbb81bbe3,0x346f2dfb,0x372a3886,0xb570b3a0,0xb9f8badb,0x38e03737,
  0x33a03570,0xb886b72a,0xb737b8e0,0x3adb39f8,0x29fe3085,0xbac3b992,0xadfbb46f,0x3be33b81,
};

#define PROF(slot) do {} while (0)
#define PROF_DUMP() do {} while (0)
#define PROFA(slot, dep) do {} while (0)
#define PROF3(slot) do {} while (0)
#define PROF2(slot) do {} while (0)

__device__ __forceinline__ uint32_t smem_u32(const void* p) { return (uint32_t)__cvta_generic_to_shared(p); }

__device__ __forceinline__ void mbar_init(uint32_t a, uint32_t c) {
  asm volatile("mbarrier.init.shared::cta.b64 [%0], %1;\n" ::"r"(a), "r"(c) : "memory");
}
__device__ __forceinline__ void mbar_expect_tx(uint32_t a, uint32_t bytes) {
  asm volatile("mbarrier.arrive.expect_tx.shared::cta.b64 _, [%0], %1;\n" ::"r"(a), "r"(bytes) : "memory");
}
__device__ __forceinline__ void mbar_arrive_cluster(uint32_t cluster_addr) {
  asm volatile("mbarrier.arrive.shared::cluster.b64 _, [%0];\n" ::"r"(cluster_addr) : "memory");
}
__device__ __forceinline__ void mbar_arrive_cluster_n(uint32_t cluster_addr, uint32_t n) {
  asm volatile("mbarrier.arrive.shared::cluster.b64 _, [%0], %1;\n" ::"r"(cluster_addr), "r"(n) : "memory");
}
__device__ __forceinline__ bool mbar_try(uint32_t a, uint32_t parity) {
  uint32_t ok;
  asm volatile("{\n.reg .pred p;\nmbarrier.try_wait.parity.shared::cta.b64 p, [%1], %2;\nselp.u32 %0, 1, 0, p;\n}\n"
               : "=r"(ok) : "r"(a), "r"(parity) : "memory");
  return ok;
}
__device__ __forceinline__ void mbar_wait(uint32_t a, uint32_t parity) {
  if (mbar_try(a, parity)) return;
#pragma unroll 1
  for (int n = 0; n < SPIN_LIMIT; n++)
    if (mbar_try(a, parity)) break;
}
__device__ __forceinline__ bool elect_one() {
  uint32_t p;
  asm volatile("{\n.reg .pred P;\nelect.sync _|P, 0xffffffff;\nselp.u32 %0, 1, 0, P;\n}\n" : "=r"(p));
  return p;
}
__device__ __forceinline__ uint32_t mapa(uint32_t a, uint32_t rank) {
  uint32_t r;
  asm volatile("mapa.shared::cluster.u32 %0, %1, %2;\n" : "=r"(r) : "r"(a), "r"(rank));
  return r;
}
__device__ __forceinline__ void nb_sync(int id, int n) { asm volatile("bar.sync %0, %1;\n" ::"r"(id), "r"(n) : "memory"); }
__device__ __forceinline__ void nb_arrive(int id, int n) { asm volatile("bar.arrive %0, %1;\n" ::"r"(id), "r"(n) : "memory"); }
__device__ __forceinline__ void cluster_sync_all() {
  asm volatile("barrier.cluster.arrive.relaxed.aligned;\nbarrier.cluster.wait.aligned;\n" ::: "memory");
}
__device__ __forceinline__ void fence_async_smem() { asm volatile("fence.proxy.async.shared::cta;\n" ::: "memory"); }
__device__ __forceinline__ void fence_async_all() { asm volatile("fence.proxy.async.global;\n" ::: "memory"); }

__device__ __forceinline__ void tma_load_3d(uint32_t dst, const CUtensorMap* tm, uint32_t bar, int c0, int c1, int c2) {
  asm volatile(
      "cp.async.bulk.tensor.3d.shared::cluster.global.mbarrier::complete_tx::bytes [%0], [%1, {%3, %4, %5}], [%2];\n"
      ::"r"(dst), "l"(tm), "r"(bar), "r"(c0), "r"(c1), "r"(c2) : "memory");
}
__device__ __forceinline__ void tma_load_4d(uint32_t dst, const CUtensorMap* tm, uint32_t bar, int c0, int c1, int c2, int c3) {
  asm volatile(
      "cp.async.bulk.tensor.4d.shared::cluster.global.mbarrier::complete_tx::bytes [%0], [%1, {%3, %4, %5, %6}], [%2];\n"
      ::"r"(dst), "l"(tm), "r"(bar), "r"(c0), "r"(c1), "r"(c2), "r"(c3) : "memory");
}
__device__ __forceinline__ void tma_load_3d_mc(uint32_t dst, const CUtensorMap* tm, uint32_t bar, int c0, int c1, int c2) {
  asm volatile(
      "cp.async.bulk.tensor.3d.shared::cluster.global.mbarrier::complete_tx::bytes.multicast::cluster [%0], [%1, {%3, %4, %5}], [%2], %6;\n"
      ::"r"(dst), "l"(tm), "r"(bar), "r"(c0), "r"(c1), "r"(c2), "h"((uint16_t)3) : "memory");
}
__device__ __forceinline__ void bulk_load(uint32_t dst, const void* src, uint32_t bytes, uint32_t bar) {
  asm volatile("cp.async.bulk.shared::cluster.global.mbarrier::complete_tx::bytes [%0], [%1], %2, [%3];\n"
               ::"r"(dst), "l"(src), "r"(bytes), "r"(bar) : "memory");
}
__device__ __forceinline__ void tma_store_3d(const CUtensorMap* tm, uint32_t src, int c0, int c1, int c2) {
  asm volatile("cp.async.bulk.tensor.3d.global.shared::cta.bulk_group [%0, {%2, %3, %4}], [%1];\n"
               ::"l"(tm), "r"(src), "r"(c0), "r"(c1), "r"(c2) : "memory");
}
__device__ __forceinline__ void bulk_commit() { asm volatile("cp.async.bulk.commit_group;\n" ::: "memory"); }
__device__ __forceinline__ void bulk_wait0() { asm volatile("cp.async.bulk.wait_group 0;\n" ::: "memory"); }
__device__ __forceinline__ void prefetch_tmap(const CUtensorMap* tm) {
  asm volatile("prefetch.tensormap [%0];\n" ::"l"(tm) : "memory");
}

__device__ __forceinline__ void wg_fence() { asm volatile("wgmma.fence.sync.aligned;\n" ::: "memory"); }
__device__ __forceinline__ void wg_commit() { asm volatile("wgmma.commit_group.sync.aligned;\n" ::: "memory"); }
template <int N> __device__ __forceinline__ void wg_wait() {
  asm volatile("wgmma.wait_group.sync.aligned %0;\n" ::"n"(N) : "memory");
}
__device__ __forceinline__ uint64_t mkdesc(uint32_t addr, uint32_t lbo, uint32_t sbo, uint32_t swz) {
  return (uint64_t)((addr & 0x3FFFF) >> 4) | ((uint64_t)(lbo >> 4) << 16) | ((uint64_t)(sbo >> 4) << 32) |
         ((uint64_t)swz << 62);
}

#define R4(d, o) "+f"(d[o + 0]), "+f"(d[o + 1]), "+f"(d[o + 2]), "+f"(d[o + 3])
#define R8(d, o) R4(d, o), R4(d, o + 4)
#define R16(d, o) R8(d, o), R8(d, o + 8)
#define R32(d, o) R16(d, o), R16(d, o + 16)
#define R64(d, o) R32(d, o), R32(d, o + 32)

__device__ __forceinline__ void wgmma_n192(float (&d)[96], uint64_t da, uint64_t db, uint32_t acc) {
  asm volatile(
      "{\n.reg .pred p;\nsetp.ne.u32 p, %98, 0;\n"
      "wgmma.mma_async.sync.aligned.m64n192k16.f32.bf16.bf16 "
      "{%0,%1,%2,%3,%4,%5,%6,%7,%8,%9,%10,%11,%12,%13,%14,%15,%16,%17,%18,%19,%20,%21,%22,%23,%24,%25,%26,%27,%28,%29,%30,%31,"
      "%32,%33,%34,%35,%36,%37,%38,%39,%40,%41,%42,%43,%44,%45,%46,%47,%48,%49,%50,%51,%52,%53,%54,%55,%56,%57,%58,%59,%60,%61,%62,%63,"
      "%64,%65,%66,%67,%68,%69,%70,%71,%72,%73,%74,%75,%76,%77,%78,%79,%80,%81,%82,%83,%84,%85,%86,%87,%88,%89,%90,%91,%92,%93,%94,%95}, "
      "%96, %97, p, 1, 1, 0, 1;\n}\n"
      : R64(d, 0), R32(d, 64)
      : "l"(da), "l"(db), "r"(acc));
}
__device__ __forceinline__ void wgmma_n128(float (&d)[64], uint64_t da, uint64_t db, uint32_t acc) {
  asm volatile(
      "{\n.reg .pred p;\nsetp.ne.u32 p, %66, 0;\n"
      "wgmma.mma_async.sync.aligned.m64n128k16.f32.bf16.bf16 "
      "{%0,%1,%2,%3,%4,%5,%6,%7,%8,%9,%10,%11,%12,%13,%14,%15,%16,%17,%18,%19,%20,%21,%22,%23,%24,%25,%26,%27,%28,%29,%30,%31,"
      "%32,%33,%34,%35,%36,%37,%38,%39,%40,%41,%42,%43,%44,%45,%46,%47,%48,%49,%50,%51,%52,%53,%54,%55,%56,%57,%58,%59,%60,%61,%62,%63}, "
      "%64, %65, p, 1, 1, 0, 1;\n}\n"
      : R64(d, 0)
      : "l"(da), "l"(db), "r"(acc));
}
#define WG128(C, ACC)                                                                                                      \
  asm volatile(                                                                                                            \
      "{\n.reg .b64 a, b;\nmov.b64 a, {%64, %66};\nmov.b64 b, {%65, %66};\n"                                               \
      "wgmma.mma_async.sync.aligned.m64n128k16.f32.bf16.bf16 "                                                             \
      "{%0,%1,%2,%3,%4,%5,%6,%7,%8,%9,%10,%11,%12,%13,%14,%15,%16,%17,%18,%19,%20,%21,%22,%23,%24,%25,%26,%27,%28,%29,%30,%31," \
      "%32,%33,%34,%35,%36,%37,%38,%39,%40,%41,%42,%43,%44,%45,%46,%47,%48,%49,%50,%51,%52,%53,%54,%55,%56,%57,%58,%59,%60,%61," \
      "%62,%63}, a, b, " ACC ", 1, 1, 0, 1;\n}\n"                                                                          \
      : Z16(C, d, 0), Z16(C, d, 16), Z16(C, d, 32), Z16(C, d, 48)                                                          \
      : "r"(da), "r"(db), "r"(0x40000040))
#define Z4(C, d, o) C(d[o + 0]), C(d[o + 1]), C(d[o + 2]), C(d[o + 3])
#define Z16(C, d, o) Z4(C, d, o), Z4(C, d, o + 4), Z4(C, d, o + 8), Z4(C, d, o + 12)
__device__ __forceinline__ void wgmma_n128z(float (&d)[64], uint32_t da, uint32_t db) { WG128("=f", "0"); }
__device__ __forceinline__ void wgmma_n128a(float (&d)[64], uint32_t da, uint32_t db) { WG128("+f", "1"); }
template <int N> __device__ __forceinline__ void fence_regs(float (&d)[N]) {
#pragma unroll
  for (int i = 0; i < N; i++) asm volatile("" : "+f"(d[i])::"memory");
}

__device__ __forceinline__ void mma16816(float (&d)[4], uint32_t a0, uint32_t a1, uint32_t a2, uint32_t a3, uint32_t b0,
                                         uint32_t b1) {
  asm("mma.sync.aligned.m16n8k16.row.col.f32.bf16.bf16.f32 {%0,%1,%2,%3}, {%4,%5,%6,%7}, {%8,%9}, {%0,%1,%2,%3};\n"
      : "+f"(d[0]), "+f"(d[1]), "+f"(d[2]), "+f"(d[3])
      : "r"(a0), "r"(a1), "r"(a2), "r"(a3), "r"(b0), "r"(b1));
}
__device__ __forceinline__ void mma16816_z(float (&d)[4], uint32_t a0, uint32_t a1, uint32_t a2, uint32_t a3, uint32_t b0,
                                           uint32_t b1) {
  asm("mma.sync.aligned.m16n8k16.row.col.f32.bf16.bf16.f32 {%0,%1,%2,%3}, {%4,%5,%6,%7}, {%8,%9}, {%10,%10,%10,%10};\n"
      : "=f"(d[0]), "=f"(d[1]), "=f"(d[2]), "=f"(d[3])
      : "r"(a0), "r"(a1), "r"(a2), "r"(a3), "r"(b0), "r"(b1), "f"(0.f));
}
__device__ __forceinline__ void ldsm4t(uint32_t (&r)[4], uint32_t a) {
  asm volatile("ldmatrix.sync.aligned.m8n8.x4.trans.shared.b16 {%0,%1,%2,%3}, [%4];\n"
               : "=r"(r[0]), "=r"(r[1]), "=r"(r[2]), "=r"(r[3]) : "r"(a) : "memory");
}
__device__ __forceinline__ void ldsm2t(uint32_t& r0, uint32_t& r1, uint32_t a) {
  asm volatile("ldmatrix.sync.aligned.m8n8.x2.trans.shared.b16 {%0,%1}, [%2];\n" : "=r"(r0), "=r"(r1) : "r"(a) : "memory");
}
__device__ __forceinline__ void st_async128(uint32_t a, uint32_t bar, uint32_t x, uint32_t y, uint32_t z, uint32_t w) {
  asm volatile("st.async.weak.shared::cluster.mbarrier::complete_tx::bytes.v4.b32 [%0], {%2,%3,%4,%5}, [%1];\n"
               ::"r"(a), "r"(bar), "r"(x), "r"(y), "r"(z), "r"(w) : "memory");
}
__device__ __forceinline__ void mbar_arrive(uint32_t a) {
  asm volatile("mbarrier.arrive.shared::cta.b64 _, [%0];\n" ::"r"(a) : "memory");
}
__device__ __forceinline__ void stsm4(uint32_t a, uint32_t r0, uint32_t r1, uint32_t r2, uint32_t r3) {
  asm volatile("stmatrix.sync.aligned.m8n8.x4.shared.b16 [%0], {%1,%2,%3,%4};\n"
               ::"r"(a), "r"(r0), "r"(r1), "r"(r2), "r"(r3) : "memory");
}
__device__ __forceinline__ void stsm4t(uint32_t a, uint32_t r0, uint32_t r1, uint32_t r2, uint32_t r3) {
  asm volatile("stmatrix.sync.aligned.m8n8.x4.trans.shared.b16 [%0], {%1,%2,%3,%4};\n"
               ::"r"(a), "r"(r0), "r"(r1), "r"(r2), "r"(r3) : "memory");
}
__device__ __forceinline__ uint2 lds64(uint32_t a) {
  uint2 v;
  asm volatile("ld.shared.v2.u32 {%0,%1}, [%2];\n" : "=r"(v.x), "=r"(v.y) : "r"(a));
  return v;
}
__device__ __forceinline__ uint4 lds128(uint32_t a) {
  uint4 v;
  asm volatile("ld.shared.v4.u32 {%0,%1,%2,%3}, [%4];\n" : "=r"(v.x), "=r"(v.y), "=r"(v.z), "=r"(v.w) : "r"(a) : "memory");
  return v;
}
__device__ __forceinline__ void sts128(uint32_t a, uint32_t x, uint32_t y, uint32_t z, uint32_t w) {
  asm volatile("st.shared.v4.u32 [%0], {%1,%2,%3,%4};\n" ::"r"(a), "r"(x), "r"(y), "r"(z), "r"(w) : "memory");
}
__device__ __forceinline__ void sts64(uint32_t a, uint32_t x, uint32_t y) {
  asm volatile("st.shared.v2.u32 [%0], {%1,%2};\n" ::"r"(a), "r"(x), "r"(y) : "memory");
}
__device__ __forceinline__ uint32_t pack_bf16(float lo, float hi) {
  uint32_t r;
  asm("cvt.rn.bf16x2.f32 %0, %1, %2;\n" : "=r"(r) : "f"(hi), "f"(lo));
  return r;
}
__device__ __forceinline__ uint32_t bmul2(uint32_t a, uint32_t b) {
  uint32_t r;
  asm("mul.rn.bf16x2 %0, %1, %2;\n" : "=r"(r) : "r"(a), "r"(b));
  return r;
}
__device__ __forceinline__ uint32_t bmax2(uint32_t a, uint32_t b) {
  uint32_t r;
  asm("max.bf16x2 %0, %1, %2;\n" : "=r"(r) : "r"(a), "r"(b));
  return r;
}
__device__ __forceinline__ uint32_t bfma2(uint32_t a, uint32_t b, uint32_t c) {
  uint32_t r;
  asm("fma.rn.bf16x2 %0, %1, %2, %3;\n" : "=r"(r) : "r"(a), "r"(b), "r"(c));
  return r;
}
__device__ __forceinline__ uint32_t badd2(uint32_t a, uint32_t b) {
  uint32_t r;
  asm("add.rn.bf16x2 %0, %1, %2;\n" : "=r"(r) : "r"(a), "r"(b));
  return r;
}
__device__ __forceinline__ void prefetch_l2(const void* p) { asm volatile("prefetch.global.L2 [%0];\n" ::"l"(p)); }
__device__ __forceinline__ void cp_async16n(uint32_t dst, const void* src) {
  asm volatile("cp.async.cg.shared.global [%0], [%1], 16;\n" ::"r"(dst), "l"(src) : "memory");
}
__device__ __forceinline__ void cp_async16(uint32_t dst, const void* src, uint32_t srcbytes) {
  asm volatile("cp.async.cg.shared.global.L2::256B [%0], [%1], 16, %2;\n" ::"r"(dst), "l"(src), "r"(srcbytes) : "memory");
}
__device__ __forceinline__ uint32_t ld_acquire(const uint32_t* p) {
  uint32_t v;
  asm volatile("ld.acquire.gpu.global.u32 %0, [%1];\n" : "=r"(v) : "l"(p) : "memory");
  return v;
}
__device__ __forceinline__ uint32_t ld_relaxed(const uint32_t* p) {
  uint32_t v;
  asm volatile("ld.relaxed.gpu.global.u32 %0, [%1];\n" : "=r"(v) : "l"(p) : "memory");
  return v;
}
__device__ __forceinline__ void st_release(uint32_t* p, uint32_t v) {
  asm volatile("st.release.gpu.global.u32 [%0], %1;\n" ::"l"(p), "r"(v) : "memory");
}
__device__ __forceinline__ void wait_flag(const uint32_t* p, uint32_t want) {
  int n = 0;
  while (ld_acquire(p) != want && ++n < SPIN_LIMIT) {}
}

struct Params {
  const __nv_bfloat16* x;
  const __nv_bfloat16* w;
  const __nv_bfloat16* q;
  const __nv_bfloat16* k;
  const __nv_bfloat16* v;
  const __nv_bfloat16* shift_k;
  const __nv_bfloat16* ssm_k;
  const __nv_bfloat16* ssm_D;
  const __nv_bfloat16* wo;
  __nv_bfloat16* out;
  uint32_t zero;
};

__device__ __forceinline__ uint32_t lds32(uint32_t a) {
  uint32_t v;
  asm volatile("ld.shared.u32 %0, [%1];\n" : "=r"(v) : "r"(a));
  return v;
}
__device__ __forceinline__ float bf_lo(uint32_t v) {
  uint32_t r;
  asm("prmt.b32 %0, %1, 0, 0x1044;\n" : "=r"(r) : "r"(v));
  return __uint_as_float(r);
}
__device__ __forceinline__ float bf_hi(uint32_t v) { return __uint_as_float(v & 0xffff0000u); }
__device__ __forceinline__ float ex2(float x) {
  float r;
  asm("ex2.approx.ftz.f32 %0, %1;\n" : "=f"(r) : "f"(x));
  return r;
}
__device__ __forceinline__ float rcp(float x) {
  float r;
  asm("rcp.approx.ftz.f32 %0, %1;\n" : "=f"(r) : "f"(x));
  return r;
}

#define Q4(c, d, o) c(d[o + 0]), c(d[o + 1]), c(d[o + 2]), c(d[o + 3])
#define Q8(c, d, o) Q4(c, d, o), Q4(c, d, o + 4)
#define Q16(c, d, o) Q8(c, d, o), Q8(c, d, o + 8)
#define Q32(c, d) Q16(c, d, 0), Q16(c, d, 16)
#define L8 "{%0,%1,%2,%3,%4,%5,%6,%7}"
#define L16 "{%0,%1,%2,%3,%4,%5,%6,%7,%8,%9,%10,%11,%12,%13,%14,%15}"
#define L32 "{%0,%1,%2,%3,%4,%5,%6,%7,%8,%9,%10,%11,%12,%13,%14,%15,%16,%17,%18,%19,%20,%21,%22,%23,%24,%25,%26,%27,%28,%29,%30,%31}"
__device__ __forceinline__ void fft_rows(uint32_t (&d)[32], const uint32_t (&a)[2][4], uint64_t db) {
  asm volatile("wgmma.mma_async.sync.aligned.m64n128k16.f16.f16.f16 " L32 ", {%32,%33,%34,%35}, %36, 0, 1, 1, 1;\n"
               : Q32("=r", d) : "r"(a[0][0]), "r"(a[0][1]), "r"(a[0][2]), "r"(a[0][3]), "l"(db));
  asm volatile("wgmma.mma_async.sync.aligned.m64n128k16.f16.f16.f16 " L32 ", {%32,%33,%34,%35}, %36, 1, 1, 1, 1;\n"
               : Q32("+r", d) : "r"(a[1][0]), "r"(a[1][1]), "r"(a[1][2]), "r"(a[1][3]), "l"(db + 64));
}
template <int INV> __device__ __forceinline__ void fft_cols(uint32_t (&d)[8], const uint32_t (&a)[2][4], uint64_t db) {
  asm volatile("wgmma.mma_async.sync.aligned.m64n32k16.f16.f16.f16 " L8 ", {%8,%9,%10,%11}, %12, 0, 1, 1, %13;\n"
               : Q8("=r", d, 0) : "r"(a[0][0]), "r"(a[0][1]), "r"(a[0][2]), "r"(a[0][3]), "l"(db), "n"(INV));
  asm volatile("wgmma.mma_async.sync.aligned.m64n32k16.f16.f16.f16 " L8 ", {%8,%9,%10,%11}, %12, 1, 1, 1, %13;\n"
               : Q8("+r", d, 0) : "r"(a[1][0]), "r"(a[1][1]), "r"(a[1][2]), "r"(a[1][3]), "l"(db + (INV ? 16 : 64)), "n"(INV));
}
__device__ __forceinline__ void fft_back(float (&d)[16], uint64_t da, uint64_t db) {
  asm volatile("wgmma.mma_async.sync.aligned.m64n32k16.f32.f16.f16 " L16 ", %16, %17, 0, 1, 1, 1, 1;\n"
               : Q16("=f", d, 0) : "l"(da), "l"(db));
#pragma unroll
  for (int i = 1; i < 4; i++)
    asm volatile("wgmma.mma_async.sync.aligned.m64n32k16.f32.f16.f16 " L16 ", %16, %17, 1, 1, 1, 1, 1;\n"
                 : Q16("+f", d, 0) : "l"(da + 32 * i), "l"(db + 64 * i));
}
__device__ __forceinline__ uint32_t hmul2(uint32_t a, uint32_t b) {
  uint32_t r;
  asm("mul.rn.f16x2 %0, %1, %2;\n" : "=r"(r) : "r"(a), "r"(b));
  return r;
}
__device__ __forceinline__ uint32_t hadd2(uint32_t a, uint32_t b) {
  uint32_t r;
  asm("add.rn.f16x2 %0, %1, %2;\n" : "=r"(r) : "r"(a), "r"(b));
  return r;
}
__device__ __forceinline__ uint32_t hneg2(uint32_t a) {
  uint32_t r;
  asm("neg.f16x2 %0, %1;\n" : "=r"(r) : "r"(a));
  return r;
}
__device__ __forceinline__ uint32_t hfma2(uint32_t a, uint32_t b, uint32_t c) {
  uint32_t r;
  asm("fma.rn.f16x2 %0, %1, %2, %3;\n" : "=r"(r) : "r"(a), "r"(b), "r"(c));
  return r;
}
__device__ __forceinline__ uint32_t pack_f16(float lo, float hi) {
  uint32_t r;
  asm("cvt.rn.f16x2.f32 %0, %1, %2;\n" : "=r"(r) : "f"(hi), "f"(lo));
  return r;
}
__device__ __forceinline__ uint32_t bmaxabs2(uint32_t a, uint32_t b) {
  uint32_t r;
  asm("max.xorsign.abs.bf16x2 %0, %1, %2;\n" : "=r"(r) : "r"(a), "r"(b));
  return r;
}
struct C2 { uint32_t r, i; };
__device__ __forceinline__ C2 cmul(C2 a, C2 b) {
  return C2{hfma2(a.r, b.r, hneg2(hmul2(a.i, b.i))), hfma2(a.r, b.i, hmul2(a.i, b.r))};
}
__device__ __forceinline__ C2 cfma(C2 a, C2 b, C2 c) {
  return C2{hfma2(a.r, b.r, hfma2(hneg2(a.i), b.i, c.r)), hfma2(a.r, b.i, hfma2(a.i, b.r, c.i))};
}
__device__ __forceinline__ C2 crot(C2 z, C2 t) {
  const uint32_t r = hfma2(t.r, z.i, z.r), i = hfma2(t.i, r, z.i);
  return C2{hfma2(t.r, i, r), i};
}
__device__ __forceinline__ C2 cget(const uint32_t (&e)[8], int j, int b) { return C2{e[4 * j + b], e[4 * j + 2 + b]}; }
template <int N> __device__ __forceinline__ void fence_regs(uint32_t (&d)[N]) {
#pragma unroll
  for (int i = 0; i < N; i++) asm volatile("" : "+r"(d[i])::"memory");
}
__device__ __forceinline__ void ldsm4(uint32_t (&r)[4], uint32_t a) {
  asm volatile("ldmatrix.sync.aligned.m8n8.x4.shared.b16 {%0,%1,%2,%3}, [%4];\n"
               : "=r"(r[0]), "=r"(r[1]), "=r"(r[2]), "=r"(r[3]) : "r"(a) : "memory");
}

__device__ __forceinline__ uint32_t movm(uint32_t a) {
  uint32_t r;
  asm volatile("movmatrix.sync.aligned.m8n8.trans.b16 %0, %1;\n" : "=r"(r) : "r"(a));
  return r;
}
template <int C0, int H, bool T> __device__ __forceinline__ void attn_pack(const float (&acc)[96], uint32_t (&d)[8]) {
#pragma unroll
  for (int c = 0; c < 8; c++) {
    asm volatile("cvt.rn.bf16x2.f32 %0, %1, %2;\n" : "=r"(d[c]) : "f"(acc[4 * (C0 + c) + 2 * H + 1]), "f"(acc[4 * (C0 + c) + 2 * H]));
    if (T) d[c] = movm(d[c]);
  }
}
__device__ __forceinline__ void attn_qk(float (&s)[4], const uint32_t (&qlo)[8], const uint32_t (&qhi)[8],
                                        const uint32_t (&k)[8], int c) {
  mma16816_z(s, qlo[c], qhi[c], qlo[c + 1], qhi[c + 1], k[c], k[c + 1]);
  mma16816(s, qlo[c + 2], qhi[c + 2], qlo[c + 3], qhi[c + 3], k[c + 2], k[c + 3]);
}
template <int N> __device__ __forceinline__ void quad_softmax(float (&x)[N][2], uint32_t (&pp)[N]) {
  const float c2 = 1.4426950408889634f;
  uint32_t q[N], mx[N / 2];
#pragma unroll
  for (int n = 0; n < N; n++) {
    const uint32_t r = pack_bf16(x[n][0], x[n][1]);
    q[n] = bfma2(r, 0x3e353e35u, bmul2(r, 0x379e379eu));
    x[n][0] = bf_lo(q[n]);
    x[n][1] = bf_hi(q[n]);
  }
#pragma unroll
  for (int n = 0; n < N / 2; n++)
    mx[n] = bmax2(__byte_perm(q[2 * n], q[2 * n + 1], 0x5410), __byte_perm(q[2 * n], q[2 * n + 1], 0x7632));
#pragma unroll
  for (int o = 1; o <= 2; o++) {
#pragma unroll
    for (int n = 0; n < N / 2; n++) mx[n] = bmax2(mx[n], __shfl_xor_sync(0xffffffffu, mx[n], o));
  }
  float m[N], t[N];
#pragma unroll
  for (int n = 0; n < N / 2; n++) {
    m[2 * n] = bf_lo(mx[n]);
    m[2 * n + 1] = bf_hi(mx[n]);
  }
#pragma unroll
  for (int n = 0; n < N; n++) {
    const float nm = -m[n] * c2;
    x[n][0] = ex2(fmaf(x[n][0], c2, nm));
    x[n][1] = ex2(fmaf(x[n][1], c2, nm));
  }
#pragma unroll
  for (int n = 0; n < N; n += 2) {
    float u0, u1;
    asm("mma.sync.aligned.m16n8k8.row.col.f32.tf32.tf32.f32 {%0,%1,%2,%3}, {%4,%5,%6,%7}, {%8,%8}, {%9,%9,%9,%9};\n"
        : "=f"(t[n]), "=f"(u0), "=f"(t[n + 1]), "=f"(u1)
        : "r"(__float_as_uint(x[n][0])), "r"(__float_as_uint(x[n + 1][0])), "r"(__float_as_uint(x[n][1])),
          "r"(__float_as_uint(x[n + 1][1])), "r"(0x3f800000u), "f"(0.f));
  }
#pragma unroll
  for (int n = 0; n < N; n++) {
    const float inv = rcp(t[n]);
    pp[n] = pack_bf16(x[n][0] * inv, x[n][1] * inv);
  }
}
__device__ __forceinline__ void attn_pv(uint32_t dst, const uint32_t (&vp)[8], const uint32_t (&vo)[8], int c, uint32_t pp,
                                        uint32_t maskLE) {
  const uint32_t b0 = pp & ~maskLE, b1 = pp & maskLE;
  float oa[4], ob[4];
  mma16816_z(oa, vp[c], vp[c + 1], vo[c], vo[c + 1], b0, b1);
  mma16816_z(ob, vp[c + 2], vp[c + 3], vo[c + 2], vo[c + 3], b0, b1);
  stsm4t(dst, pack_bf16(oa[0], oa[1]), pack_bf16(oa[2], oa[3]), pack_bf16(ob[0], ob[1]), pack_bf16(ob[2], ob[3]));
}

template <int MODE>
__global__ void __cluster_dims__(2, 1, 1) __launch_bounds__(NTHREADS, 1)
fused_kernel(const Params p, const __grid_constant__ CUtensorMap tmX, const __grid_constant__ CUtensorMap tmW,
             const __grid_constant__ CUtensorMap tmWo, const __grid_constant__ CUtensorMap tmWp,
             const __grid_constant__ CUtensorMap tmQ,
             const __grid_constant__ CUtensorMap tmOb,
             const __grid_constant__ CUtensorMap tmXh, const __grid_constant__ CUtensorMap tmWh) {
  extern __shared__ __align__(1024) uint8_t smem[];
  if (threadIdx.x < 32 * PFR) {
    const uint32_t i = ((blockIdx.x + (threadIdx.x >> 5) * (128 / PFR)) & 127) * 16 + (threadIdx.x & 15);
    prefetch_l2(threadIdx.x & 16 ? (const char*)p.w + i * 128 : (const char*)p.x + i * 2048);
  }
  const uint32_t sb = smem_u32(smem);
  const uint32_t bars = sb + OFF_BAR;
  const int tid = threadIdx.x, lane = tid & 31, warp = __shfl_sync(0xffffffffu, tid >> 5, 0);
  const int rank = blockIdx.x & 1;
  const bool halo_cta = blockIdx.x < 4;
  if (halo_cta && MODE != 0) return;
  int grp, mem;
  {
    const int t = (blockIdx.x >> 1) - 4, u = t - 32;
    const int q7 = (u * 37) >> 8;
    const bool lo = (unsigned)t < 32u, mid = (unsigned)u < 28u;
    grp = lo ? (t & 7) : (mid ? 1 + u - 7 * q7 : 0);
    mem = lo ? (t >> 3) : (mid ? 4 + q7 : (t < 0 ? t + 6 : t - 54));
  }
  const int rg = (grp >> 2) * 4 + (mem >> 1), hp = (grp & 3) * 4 + (mem & 1) * 2 + rank;
  const int rb2 = (grp >> 2) * 8 + mem, cb2 = (grp & 3) * 2 + rank;
  const int chb = grp * 16 + mem * 2 + rank;
  const int cta = rg * 16 + hp;
  const int hsel = rb2 & 1;
  const int par = rg >> 2, gidx = rg & 3;

  if (tid < 256 && !halo_cta && MODE != 2) {
    const int r = tid >> 3, c = tid & 7;
    const uint32_t so = r * 128 + ((c ^ (r & 7)) << 4);
    const __nv_bfloat16* wg0 = p.w + (size_t)r * (3 * DM) + hp * 64 + c * 8;
    const __nv_bfloat16* xg0 = p.x + (size_t)(2 * (gidx * 256 + r) + par) * DM + c * 8;
#pragma unroll
    for (int j = 0; j < 3; j++) cp_async16n(sb + OFF_1B + j * 4096 + so, wg0 + j * DM);
#pragma unroll
    for (int i = 0; i < 8; i++) cp_async16n(sb + i * 4096 + so, xg0 + (size_t)i * 64 * DM);
    asm volatile("cp.async.commit_group;\n" ::: "memory");
    if (PF2 >= 1 && tid < 16 * PF2X) prefetch_l2((const char*)p.x + (chb * 16 + (tid & 15)) * 2048 + 128 + (tid >> 4) * 128);
    if (PF2 >= 2 && warp == 2) prefetch_l2((const char*)p.w + (2048 + chb * 32 + lane) * 128);
  }

  if (warp >= 8) {
    asm volatile("setmaxnreg.dec.sync.aligned.u32 %0;\n" :: "n"(REG_HELP));
    auto halo_issue = [&](int kb, int s) {
      const uint32_t fb = bars + 8 * (BAR_FULLB + s), st = sb + s * STGH;
      mbar_expect_tx(fb, STGH - 2048);
      tma_load_3d(st + 8192, &tmWh, fb, 0, kb * 64, 16 + blockIdx.x * 4);
      tma_load_3d(st + 8192 + 32768, &tmWh, fb, 0, kb * 64, 32 + blockIdx.x * 4);
      tma_load_4d(st, &tmXh, fb, kb * 64, 248, 0, 0);
    };
    if (tid == 256) {
      prefetch_tmap(halo_cta ? &tmXh : &tmX);
#pragma unroll
      for (int i = 0; i < NS1B; i++) mbar_init(bars + 8 * (BAR_FULLB + i), 1);
#pragma unroll
      for (int i = 0; i < NS1A; i++) mbar_init(bars + 8 * (BAR_FULLA + i), 1);
      asm volatile("fence.mbarrier_init.release.cluster;\n" ::: "memory");
      if (!halo_cta && MODE != 2) {
        mbar_expect_tx(bars + 8 * (BAR_FULLB + 1), STG1B);
        tma_load_3d(sb + OFF_1B + 1 * STG1B, &tmW, bars + 8 * (BAR_FULLB + 1), hp * 64, 32, 0);
        mbar_expect_tx(bars + 8 * (BAR_FULLB + 2), STG1B);
        tma_load_3d(sb + OFF_1B + 2 * STG1B, &tmW, bars + 8 * (BAR_FULLB + 2), hp * 64, 64, 0);
        mbar_arrive(bars + 8 * BAR_FULLA);
        mbar_arrive(bars + 8 * BAR_FULLB);
      } else if (halo_cta) {
        halo_issue(0, 0);
      }
    } else if (tid == 288) {
#pragma unroll
      for (int i = 0; i < NS1A; i++) mbar_init(bars + 8 * (BAR_EMPTYA + i), 4);
#pragma unroll
      for (int i = 0; i < NS1B; i++) mbar_init(bars + 8 * (BAR_EMPTYB + i), 2);
      mbar_init(bars + 8 * BAR_X, 4);
      mbar_init(bars + 8 * BAR_TAB, 16);
      mbar_init(bars + 8 * BAR_U, 1);
      mbar_init(bars + 8 * BAR_H, 1);
      mbar_init(bars + 8 * BAR_STG, 8);
      mbar_init(bars + 8 * BAR_HALO, 1);
      mbar_init(bars + 8 * BAR_Q, 1);
      mbar_init(bars + 8 * BAR_LAND, 5);
      mbar_init(bars + 8 * (BAR_LAND + 1), 5);
      asm volatile("fence.mbarrier_init.release.cluster;\n" ::: "memory");
    } else if (tid == 320) {
#pragma unroll
      for (int i = 0; i < NS2; i++) {
        mbar_init(bars + 8 * (BAR_FULL2 + i), 1);
        mbar_init(bars + 8 * (BAR_EMPTY2 + i), 2);
        mbar_init(bars + 8 * (BAR_EMPTY2B + i), 2);
      }
      asm volatile("fence.mbarrier_init.release.cluster;\n" ::: "memory");
    } else if (tid == 352) {
#pragma unroll
      for (int i = 0; i < 4; i++) mbar_init(bars + 8 * (BAR_Y + i), i < 2 ? 4 : i == 2 ? 10 : 8);
      mbar_init(bars + 8 * BAR_XFREE, 1);
      asm volatile("fence.mbarrier_init.release.cluster;\n" ::: "memory");
    }
    __syncwarp();
    cluster_sync_all();
    if (warp == 8) PROF2(24);
    const int hw = warp - 8;
    const int lr = lane & 7, lm = lane >> 3;
    auto g1_issue_a = [&](int j, int s) {
      const uint32_t fb = bars + 8 * (BAR_FULLA + s);
      mbar_expect_tx(fb, STG1A);
      tma_load_3d_mc(sb + s * STG1A + rank * 16384, &tmX, fb, j * 64, par, gidx * 256 + rank * 128);
    };
    auto g1_issue_b = [&](int kb, int s) {
      const uint32_t fb = bars + 8 * (BAR_FULLB + s);
      mbar_expect_tx(fb, STG1B);
      tma_load_3d(sb + OFF_1B + s * STG1B, &tmW, fb, hp * 64, kb * 32, 0);
    };
    auto g2_k = [&](int kb) { return (kb < 2 ? hp : kb < 4 ? hp & 14 : hp & 12) ^ kb; };
    auto g2_issue_b = [&](uint32_t fb, uint32_t bytes, uint32_t dst, int k0, bool whole) {
      if (whole) {
        tma_load_3d(dst, &tmWo, fb, 0, k0, cb2 * 2);
      } else {
#pragma unroll
        for (int i = 0; i < 4; i++)
          tma_load_3d(dst + (i & 1) * XT + (i >> 1) * 4 * XT, &tmWp, fb, 0, k0 + (i >> 1) * 32, cb2 * 2 + (i & 1));
      }
      mbar_expect_tx(fb, bytes);
    };
    auto send_y = [&](uint32_t o, uint32_t step, int half) {
      const uint32_t peer = mapa(sb, rank ^ 1);
      o += OFF_X + (rank ^ 1) * 4096 + half * 2048 + lane * 16;
      uint4 a[8];
#pragma unroll
      for (int i = 0; i < 8; i++) a[i] = lds128(sb + o + (i >> 2) * step + (i & 2) * (XT / 2) + (i & 1) * 512);
#pragma unroll
      for (int i = 0; i < 8; i++)
        st_async128(peer + o + 1024 + (i >> 2) * step + (i & 2) * (XT / 2) + (i & 1) * 512,
                    peer + OFF_BAR + 8 * (BAR_LAND + half), a[i].x, a[i].y, a[i].z, a[i].w);
    };

    if (halo_cta) {
      if (hw == 0) {
        int s = 1, ph = 1;
#pragma unroll 1
        for (int kb = 1; kb < 16; kb++) {
          mbar_wait(bars + 8 * (BAR_EMPTYB + s), ph);
          if (elect_one()) halo_issue(kb, s);
          if (++s == 3) { s = 0; ph ^= 1; }
        }
      }
      __syncwarp();
    } else if (hw == 0) {
      uint32_t epoch = 0;
      if (MODE == 2) {
        if (lane < NS2) mbar_arrive_cluster_n(mapa(bars, rank) + 8 * (BAR_EMPTY2 + lane), 2);
      } else {
      if (lane == 0) {
        mbar_expect_tx(bars + 8 * BAR_U, 32768);
        mbar_expect_tx(bars + 8 * BAR_LAND, 8192);
        mbar_expect_tx(bars + 8 * (BAR_LAND + 1), 8192);
        mbar_expect_tx(bars + 8 * BAR_Q, 32768);
        prefetch_tmap(&tmQ);
      }
      {
        int sa = 1, pha = 1, sbb = 2, phb = 1;
#pragma unroll 1
        for (int kb = 2; kb < 32; kb++) {
          if (!(kb & 1)) {
            mbar_wait(bars + 8 * (BAR_EMPTYA + sa), pha);
            if (elect_one()) g1_issue_a(kb >> 1, sa);
            if (++sa == NS1A) { sa = 0; pha ^= 1; }
          }
          mbar_wait(bars + 8 * (BAR_EMPTYB + sbb), phb);
          if (kb > 2 && elect_one()) g1_issue_b(kb, sbb);
          __syncwarp();
          if (kb == 4) epoch = ld_relaxed(g_flag_o + cta);
          if (kb == 4) PROF2(27);
          if (kb == 1) PROF2(38);
          if (kb == 2) PROF2(39);
          if (++sbb == NS1B) { sbb = 0; phb ^= 1; }
        }
      }
      auto q_issue = [&](int i) {
        mbar_wait(bars + 8 * (i ? BAR_EMPTYB + 3 : BAR_EMPTYA + 1), i);
        if (elect_one())
          asm volatile(
              "cp.async.bulk.tensor.5d.shared::cluster.global.mbarrier::complete_tx::bytes [%0], [%1, {%3, %4, %4, %4, %5}], [%2];\n"
              ::"r"(sb + (i ? OFF_Q1 : OFF_Q0)), "l"(&tmQ), "r"(bars + 8 * BAR_Q), "r"((chb & ~1) * 8), "r"(0), "r"(rank * 32 + i * 64)
              : "memory");
        __syncwarp();
      };
      if (QORD < 2) q_issue(0);
      else mbar_wait(bars + 8 * (BAR_EMPTYA + 1), 0);
      if (QORD < 1) q_issue(1);
      epoch++;
      if (lane == 0) {
        prefetch_tmap(&tmWo);
        prefetch_tmap(&tmWp);
        prefetch_tmap(&tmOb);
        if (gidx != 0) wait_flag(g_flag_h + (hp >> 2), epoch);
      }
      __syncwarp();
      {
        uint4 hk0 = make_uint4(0, 0, 0, 0), hk1 = hk0, hv0 = hk0, hv1 = hk0;
        if (gidx != 0) {
          const uint4* src = g_halo + cta * 128 + lane;
          hk0 = __ldcg(src); hk1 = __ldcg(src + 32); hv0 = __ldcg(src + 64); hv1 = __ldcg(src + 96);
        }
        if (gidx != 0) PROF(18);
        sts128(sb + OFF_KH + lane * 16, hk0.x, hk0.y, hk0.z, hk0.w);
        sts128(sb + OFF_KH + 512 + lane * 16, hk1.x, hk1.y, hk1.z, hk1.w);
        sts64(sb + OFF_KH + 1024 + lane * 8, movm(hv0.x), movm(hv0.y));
        sts64(sb + OFF_KH + 1280 + lane * 8, movm(hv0.z), movm(hv0.w));
        sts64(sb + OFF_KH + 1536 + lane * 8, movm(hv1.x), movm(hv1.y));
        sts64(sb + OFF_KH + 1792 + lane * 8, movm(hv1.z), movm(hv1.w));
        __syncwarp();
        if (lane == 0) mbar_arrive(bars + 8 * BAR_HALO);
      }
      if (QORD == 2) q_issue(0);
      if (QORD >= 1) q_issue(1);
      const uint32_t rb = mapa(bars, lane & 1);
      nb_sync(NB_OREADY, 288);
      if (lane == 0) {
        asm volatile("cp.async.bulk.global.shared::cta.bulk_group [%0], [%1], %2;\n" ::"l"(g_o + (size_t)cta * 16384),
                     "r"(sb + OFF_OP), "r"(32768) : "memory");
        bulk_commit();
      }
      if (lane < 2) {
#pragma unroll
        for (int i = 0; i < 4; i++) mbar_arrive_cluster(rb + 8 * (BAR_EMPTY2 + i + i / 2));
      }
      if (lane == 0) {
        bulk_wait0();
        st_release(g_flag_o + cta, epoch);
      }
      __syncwarp();
      PROF2(17);
      if (lane < 2) mbar_arrive_cluster(rb + 8 * (BAR_EMPTY2 + 2));
      }
      if (MODE != 1) {
        const __nv_bfloat16* osrc = g_o + (size_t)(rb2 >> 1) * 16 * 16384 + hsel * 8192;
        mbar_wait(bars + 8 * (BAR_EMPTY2 + 1), 0);
        if (elect_one()) {
          if (MODE == 0) {
            asm volatile("cp.async.bulk.shared::cluster.shared::cta.mbarrier::complete_tx::bytes [%0], [%1], %2, [%3];\n"
                         ::"r"(mapa(sb + g2_a(1, hsel), rank ^ 1)), "r"(sb + g2_a(0, hsel)), "r"(16384),
                         "r"(mapa(bars + 8 * (BAR_FULL2 + 1), rank ^ 1)) : "memory");
          } else {
            bulk_load(sb + g2_a(0, hsel), osrc + hp * 16384, 16384, bars + 8 * BAR_FULL2);
            bulk_load(sb + g2_a(1, hsel), osrc + (hp ^ 1) * 16384, 16384, bars + 8 * (BAR_FULL2 + 1));
          }
        }
        __syncwarp();
      }
      if (MODE != 2) {
        mbar_wait(bars + 8 * (BAR_Y + 2), 0);
        send_y(0, 4 * XT, 1);
        fence_async_smem();
        __syncwarp();
      }
      if (MODE != 1) {
        unsigned long long seq = G2_SEQ >> 12;
        uint32_t wbar = bars + 8 * (BAR_Y + 2), fb = bars + 8 * (BAR_FULL2 + 3), dst = sb + g2_b(3, rank), ph = MODE ? 1 : 0;
        int k0 = g2_k(3) * 64;
        bool whole = false;
#pragma unroll 1
        for (int kb = 4; kb <= 16; kb++) {
          mbar_wait(wbar, ph);
          if (elect_one()) g2_issue_b(fb, STG2, dst, k0, whole);
          __syncwarp();
          seq >>= 4;
          const int s = seq & 7;
          wbar = bars + 8 * (kb == G2_KB4 ? BAR_XFREE : BAR_EMPTY2B + s);
          ph = ((uint32_t)seq >> 3 & 1) ^ (kb == G2_KB4 && MODE == 0 ? 0 : 1);
          fb = bars + 8 * (BAR_FULL2 + s);
          dst = sb + g2_b(s, rank);
          k0 = ((hp & 12) ^ kb) * 64;
          whole = s < 3;
        }
      }
      __syncwarp();
    } else {
      if (MODE != 2) {
      const float dall = __bfloat162float(p.ssm_D[chb * 8 + lr]);
      {
        const int g = lane >> 2, t = lane & 3;
        uint32_t w[2][4];
#pragma unroll
        for (int h = 0; h < 2; h++) {
          const uint2 x = __ldg(reinterpret_cast<const uint2*>(p.shift_k + ((chb & ~1) * 8 + h * 8 + g) * 4));
          w[h][0] = __byte_perm(x.x, x.x, 0x1010);
          w[h][1] = __byte_perm(x.x, x.x, 0x3232);
          w[h][2] = __byte_perm(x.y, x.y, 0x1010);
          w[h][3] = __byte_perm(x.y, x.y, 0x3232);
        }
        auto swz = [](int r) { return (((r & 29) | ((r ^ (r >> 2)) & 2)) << 5) | (r & 16); };
        const uint32_t kring = sb + OFF_X + 4096 + (hw - 1) * 2 * XT, vring = kring + XT;
        const int s0 = rank * 32 + (hw - 1) * 11, s1 = hw == 3 ? rank * 32 + 32 : s0 + 11;
        const size_t goff = (size_t)(lane >> 1) * DM + (chb & ~1) * 8 + (lane & 1) * 8;
        const __nv_bfloat16* kg = p.k + goff;
        const __nv_bfloat16* vg = p.v + goff;
        const uint32_t d0 = swz(lane >> 1) ^ ((lane & 1) << 4), d1 = swz(16 + (lane >> 1)) ^ ((lane & 1) << 4);
        auto issue = [&](int st) {
          const uint32_t so = (st & 3) << 10;
          cp_async16(kring + so + d0, kg + (size_t)st * 32 * DM, 16);
          cp_async16(kring + so + d1, kg + (size_t)(st * 32 + 16) * DM, 16);
          cp_async16(vring + so + d0, vg + (size_t)st * 32 * DM, 16);
          cp_async16(vring + so + d1, vg + (size_t)(st * 32 + 16) * DM, 16);
        };
        const int xa = 8 * (lr >> 1) + 2 * lm + (lr & 1), xb = 8 * (lr >> 1) - 4 + 2 * (lm & 1) + (lr & 1);
        const uint32_t la = swz(xa), lb = swz(xb & 31);
        const int backb = xb < 0 ? 1 : 0;
        const uint32_t ud[2] = {mapa(sb + OFF_X + g * XT + t * 16, 0), mapa(sb + OFF_X + g * XT + t * 16, 1)};
        const uint32_t ub[2] = {mapa(bars + 8 * BAR_U, 0), mapa(bars + 8 * BAR_U, 1)};
        if (tid == 320) prefetch_l2(g_tab + (chb & 63) * 32);
        if (lane == 0) mbar_wait(bars + 8 * (BAR_FULLB + NS1B - 1), 0);
        __syncwarp();
        if (lane >= 24) cp_async16(kring + (((s0 - 1) & 3) << 10) + d1, s0 > 0 ? kg + (size_t)(s0 * 32 - 16) * DM : kg, s0 > 0 ? 16 : 0);
        issue(s0);
        asm volatile("cp.async.commit_group;\n" ::: "memory");
        issue(s0 + 1);
        asm volatile("cp.async.commit_group;\n" ::: "memory");
        uint32_t tn = (uint32_t)clock() + STAG * ((hw - 1) * 2 + rank - 3) * (PSTEP / 6);
#pragma unroll 1
        for (int st = s0; st < s1; st++) {
          tn += PSTEP;
          while ((int)((uint32_t)clock() - tn) < 0) __nanosleep(100);
          if (st + 2 < s1) issue(st + 2);
          if (hw == 1 && (unsigned)(st - s0 - HPF0) < 8u) prefetch_l2(p.ssm_k + (size_t)(chb * 8 + st - s0 - HPF0) * SEQ + lane * 64);
          asm volatile("cp.async.commit_group;\n" ::: "memory");
          asm volatile("cp.async.wait_group 2;\n" ::: "memory");
          __syncwarp();
#pragma unroll
          for (int h = 0; h < 2; h++) {
            uint32_t e[6], vv[4], e4[4];
            ldsm4t(e4, kring + ((st & 3) << 10) + (la ^ (h << 4)));
            ldsm2t(e[0], e[1], kring + (((st - backb) & 3) << 10) + (lb ^ (h << 4)));
            ldsm4t(vv, vring + ((st & 3) << 10) + (la ^ (h << 4)));
            e[2] = e4[0]; e[3] = e4[1]; e[4] = e4[2]; e[5] = e4[3];
            uint32_t o[5];
#pragma unroll
            for (int i = 0; i < 5; i++) o[i] = __byte_perm(e[i], e[i + 1], 0x5432);
#pragma unroll
            for (int i = 0; i < 4; i++) {
              uint32_t a = bmul2(o[i], w[h][3]);
              a = bfma2(e[i + 1], w[h][2], a);
              a = bfma2(o[i + 1], w[h][1], a);
              a = bfma2(e[i + 2], w[h][0], a);
              vv[i] = bmul2(a, vv[i]);
            }
            st_async128(ud[h] + (st ^ (g & 1)) * 64, ub[h], vv[0], vv[1], vv[2], vv[3]);
          }
          __syncwarp();
        }
        fence_async_smem();
        PROF(16);
      }
      nb_sync(NB_HELP3, 96);
      if (hw == 1 && elect_one()) {
        mbar_expect_tx(bars + 8 * BAR_H, 8 * 4096);
#pragma unroll 1
        for (int c = 0; c < 8; c++)
          bulk_load(sb + OFF_X + c * XT + 4096, p.ssm_k + (size_t)(chb * 8 + c) * SEQ, 4096, bars + 8 * BAR_H);
        mbar_expect_tx(bars + 8 * BAR_X, 6144);
        bulk_load(sb + OFF_T16, g_tab, 2048, bars + 8 * BAR_X);
        bulk_load(sb + OFF_T32, g_tab + 512, 4096, bars + 8 * BAR_X);
      }
      __syncwarp();
      {
        const int ck = 16 * (lane >> 4) + 2 * lr + (((lane >> 3) ^ (lane >> 2)) & 1);
        const uint32_t xo = (ck >> 1) * 64, xs = ((ck & 1) ^ (lr >> 1)) << 4;
#pragma unroll 1
        for (int job = hw - 1; job < 16; job += 3) {
          const int c = job & 7;
          uint4 a[8];
          float dv = __shfl_sync(0xffffffffu, dall, c);
          if (job < 8 || lane) dv = 0.f;
          if (job >= PF0 && job < PF1) prefetch_l2((job < 8 ? p.q + (size_t)chb * 16384 : p.wo + (size_t)chb * 8192) + c * 2048 + lane * 64);
          const uint32_t xt = sb + OFF_X + c * XT + (job >> 3) * 4096;
          mbar_wait(bars + 8 * (job < 8 ? BAR_U : BAR_H), 0);
#pragma unroll
          for (int i = 0; i < 8; i++) a[i] = lds128(xt + i * 512 + ((ck ^ (job < 8 ? (c & 1) << 2 : 0)) << 4));
          dv += bf_lo(a[0].x);
          uint32_t m[2] = {bmaxabs2(pack_bf16(dv, 0.f), bmaxabs2(a[0].x, a[0].y)), bmaxabs2(a[0].z, a[0].w)};
#pragma unroll
          for (int i = 1; i < 8; i++) {
            m[0] = bmaxabs2(bmaxabs2(m[0], a[i].x), a[i].y);
            m[1] = bmaxabs2(bmaxabs2(m[1], a[i].z), a[i].w);
          }
          m[0] = bmaxabs2(m[0], m[1]);
          const int f = max(252 - (int)(__reduce_max_sync(0xffffffffu, max(m[0] & 0x7fffu, (m[0] >> 16) & 0x7fffu)) >> 7), 1);
          if (lane == 0) asm volatile("st.shared.u32 [%0], %1;\n" ::"r"(sb + OFF_EX + job * 4), "r"(f) : "memory");
          if (f < 113) {
#pragma unroll
            for (int i = 0; i < 8; i++)
              a[i] = make_uint4(bmul2(a[i].x, f * 0x00800080u), bmul2(a[i].y, f * 0x00800080u), bmul2(a[i].z, f * 0x00800080u),
                                bmul2(a[i].w, f * 0x00800080u));
          }
          const uint32_t mul = (f < 113 ? 15 : f - 112) * 0x00800080u;
          auto cv = [&](uint32_t x) {
            x = bmul2(x, mul);
            return (x & 0x0fff0fffu) * 7 + x;
          };
          const uint32_t dst = xt + xo;
#pragma unroll
          for (int i = 0; i < 8; i++)
            sts128(dst + (i >> 2) * 2048 + (i & 1) * 1024 + (xs ^ ((i & 2) << 4)),
                   i ? cv(a[i].x) : __byte_perm(pack_f16(dv * __uint_as_float(f << 23), 0.f), cv(a[i].x), 0x7610), cv(a[i].y),
                   cv(a[i].z), cv(a[i].w));
        }
        fence_async_smem();
        __syncwarp();
        if (lane == 0) mbar_arrive(bars + 8 * BAR_X);
        PROF(19);
      }
      if (hw < 3) {
#pragma unroll 1
        for (int n = 0; n < SPIN_LIMIT && !mbar_try(bars + 8 * (BAR_Y + hw - 1), 0); n++) __nanosleep(100);
        send_y((hw - 1) * 4 * XT, 2 * XT, 0);
        __syncwarp();
        if (lane == 0) mbar_arrive(bars + 8 * (BAR_Y + 2));
        PROF(32);
        const int c8 = 2 * lm + (lr & 1), src = (lr >> 1) & 1;
        uint32_t fa = sb + OFF_X + c8 * XT + rank * 4096 + (src == rank ? 0 : 1024) + (hw - 1) * 512;
        const uint32_t fx = ((lr >> 2) ^ ((lr & 3) << 1)) << 4;
        uint32_t qa = sb + OFF_Q0 + (hw - 1) * 8192 + (lane >> 3) * 128 + (lane & 2) * 32 + (lane & 4) * 8 + (lane & 1) * 16;
        uint4* og = reinterpret_cast<uint4*>(p.out + (size_t)(rank * 512 + (hw - 1) * 256 + (lane & 2) * 4 + (lane >> 2)) * (2 * DM) +
                                             (chb & ~1) * 8 + (lane & 1) * 8);
        mbar_wait(bars + 8 * BAR_Q, 0);
        uint32_t tn = 0;
#pragma unroll 1
        for (int j = 0; j < 16; j++) {
          if (j == JS && hw == 2) {
            mbar_wait(bars + 8 * (BAR_Y + 3), 0);
            send_y(2 * XT, 4 * XT, 1);
            fence_async_smem();
            __syncwarp();
            if (lane == 0) mbar_arrive(bars + 8 * BAR_XFREE);
            tn = (uint32_t)clock();
          }
          if (!(j & 7)) {
            mbar_wait(bars + 8 * (BAR_LAND + (j >> 3)), 0);
            tn = (uint32_t)clock() + (hw - 1) * (FPACE / 2);
            PROF2(33 + (j >> 1));
          }
#pragma unroll
          for (int i = 0; i < 2; i++) {
            uint32_t y[4];
            const uint4 q = lds128(qa + i * 512);
            ldsm4t(y, fa + (j & 6) * 64 + (fx ^ (i << 5) ^ ((j & 1) << 6) ^ ((j & 2) << 3)));
            while ((int)((uint32_t)clock() - tn) < 0) __nanosleep(FSL);
            tn += hw == 2 ? FPACE2 : FPACE;
            og[i * 16 * (2 * DM / 8)] = make_uint4(bmul2(q.x, y[0]), bmul2(q.y, y[1]), bmul2(q.z, y[2]), bmul2(q.w, y[3]));
          }
          qa += j == 7 ? OFF_Q1 - OFF_Q0 - 7168 : 1024;
          if (j == 7) fa += 2048;
          og += (j == 7 ? 1024 - 224 : 32) * (2 * DM / 8);
        }
        PROF(22);
      }
      }
      if (MODE != 1 && hw == 3) {
        const uint32_t epoch = ld_relaxed(g_flag_o + cta) + 1;
        if (MODE == 0) nb_sync(NB_G1END, 288);
        if (BDEL) __nanosleep(BDEL);
        if (elect_one()) {
#pragma unroll
          for (int kb = 0; kb < 3; kb++)
            g2_issue_b(bars + 8 * (BAR_FULL2 + kb), kb || MODE ? STG2 : STG2 / 2, sb + g2_b(kb, 0), g2_k(kb) * 64, true);
        }
        __syncwarp();
        const __nv_bfloat16* osrc = g_o + (size_t)(rb2 >> 1) * 16 * 16384 + hsel * 8192;
        if (MODE == 0) __nanosleep(POLL0);
        const uint32_t* flag = g_flag_o + (rb2 >> 1) * 16 + g2_k(lane & 15);
        uint32_t ready = MODE == 0 ? 0u : ~0u;
        unsigned long long seq = G2_SEQ >> 8;
#pragma unroll 1
        for (int kb = 2; kb < 16; kb++, seq >>= 4) {
          uint32_t so = bars + (seq & 7) * 8, dst = sb + g2_a(seq & 7, hsel) + rank * 8192;
          const uint32_t ph = (uint32_t)seq >> 3 & 1;
          const __nv_bfloat16* src = osrc + rank * 4096 + (uint32_t)g2_k(kb) * 16384;
          asm volatile("" : "+r"(so), "+r"(dst), "+l"(src));
          if (!(ready >> kb & 1)) {
#pragma unroll 1
            for (int n = 0; n < SPIN_LIMIT && !(ready >> kb & 1); n++)
              ready = __ballot_sync(0xffffffffu, ld_acquire(flag) == epoch);
            fence_async_all();
          }
          if (kb == 2) PROF(21);
          if (MODE == 0 && kb == G2_KB4 && rank == 1) mbar_wait(bars + 8 * BAR_TAB, 0);
          mbar_wait(so + 8 * BAR_EMPTY2, ph);
          if (elect_one()) {
            asm volatile(
                "cp.async.bulk.shared::cluster.global.mbarrier::complete_tx::bytes.multicast::cluster [%0], [%1], %2, [%3], %4;\n"
                ::"r"(dst), "l"(src), "r"(8192), "r"(so + 8 * BAR_FULL2), "h"((uint16_t)3) : "memory");
          }
          __syncwarp();
        }
      }
    }
    cluster_sync_all();
    PROF_DUMP();
  } else {
    asm volatile("barrier.cluster.arrive.relaxed.aligned;\n" ::: "memory");
    asm volatile("setmaxnreg.inc.sync.aligned.u32 %0;\n" :: "n"(REG_MATH));
    if (halo_cta || MODE == 2) asm volatile("barrier.cluster.wait.aligned;\n" ::: "memory");
    if (warp == 0) PROF2(26);
    const int wg = warp >> 2;
    const int wtid = tid & 127;
    const bool signaller = (wtid == 0) || (wtid == 32);
    const uint32_t rbars = mapa(bars, wtid >> 5 & 1);

    if (halo_cta) {
      const uint32_t epoch = ld_relaxed(g_flag_h + blockIdx.x) + 1;
      float acc0[64], acc1[64];
      int s = 0, ph = 0;
#pragma unroll 1
      for (int kb = 0; kb < 16; kb++) {
        mbar_wait(bars + 8 * (BAR_FULLB + s), ph);
        const uint32_t st = sb + s * STGH;
        const uint64_t da = mkdesc(st, 16, 1024, 1);
        const uint64_t db = mkdesc(st + 8192 + wg * 32768, 8192, 1024, 1);
        wg_fence();
#pragma unroll
        for (int kk = 0; kk < 4; kk++) {
          wgmma_n128(acc0, da + 2 * kk, db + 128 * kk, kb + kk);
          wgmma_n128(acc1, da + 2 * kk, db + 1024 + 128 * kk, kb + kk);
        }
        wg_commit();
        wg_wait<0>();
        if (kb == 15) PROF(37);
        if (wtid == 0) mbar_arrive(bars + 8 * (BAR_EMPTYB + s));
        if (++s == 3) { s = 0; ph ^= 1; }
      }
      fence_regs(acc0);
      fence_regs(acc1);
      if ((warp & 3) != 3) {
#pragma unroll
        for (int hh = 0; hh < 2; hh++) {
          uint4* dst = g_halo + ((hh * 4 + (warp & 3) + 1) * 16 + blockIdx.x * 4) * 128 + wg * 64 + lane;
#pragma unroll
          for (int j = 0; j < 4; j++) {
            const int o = 16 * j + 2 * hh;
            dst[(j >> 1) * 128 + (j & 1) * 32] =
                make_uint4(pack_bf16(acc0[o], acc0[o + 1]), pack_bf16(acc0[o + 4], acc0[o + 5]),
                           pack_bf16(acc0[o + 8], acc0[o + 9]), pack_bf16(acc0[o + 12], acc0[o + 13]));
            dst[(2 + (j >> 1)) * 128 + (j & 1) * 32] =
                make_uint4(pack_bf16(acc1[o], acc1[o + 1]), pack_bf16(acc1[o + 4], acc1[o + 5]),
                           pack_bf16(acc1[o + 8], acc1[o + 9]), pack_bf16(acc1[o + 12], acc1[o + 13]));
          }
        }
      }
      nb_sync(NB_G1DONE, 256);
      if (tid == 0) st_release(g_flag_h + blockIdx.x, epoch);
      PROF(36);
      cluster_sync_all();
      return;
    }

    float acc[64];
    const uint32_t g2rel = wtid ? mapa(bars, rank) + 8 * BAR_EMPTY2B : mapa(bars, wg) + 8 * BAR_EMPTY2;
    uint32_t g2a = (uint32_t)mkdesc(sb + wg * 8192, 16, 0, 0), g2b = (uint32_t)mkdesc(sb, 8192, 0, 0);
    auto g2_block = [&](bool first, int s, int ph) {
      mbar_wait(bars + 8 * (BAR_FULL2 + s), ph);
      const uint32_t da = g2a + (g2_a(s, hsel) >> 4), db = g2b + (g2_b(s, rank) >> 4), dc = db + (g2_bk(s) >> 4);
      wg_fence();
      if (first) wgmma_n128z(acc, da, db);
      else wgmma_n128a(acc, da, db);
      wgmma_n128a(acc, da + 2, db + 128);
      wgmma_n128a(acc, da + 4, dc);
      wgmma_n128a(acc, da + 6, dc + 128);
      wg_commit();
    };
    if (MODE != 2) {
    uint32_t a1[2][4], sc[2];
    C2 t[2];
    {
      float acc0[96], acc1[96];
      int sa = 0, pha = 0;
      uint64_t db0 = mkdesc(sb + OFF_1B, 4096, 1024, 1);
      const uint64_t da0 = mkdesc(sb + wg * 16384, 16, 2048, 1);
      const bool sigb = wtid == 64;
      uint32_t rela = 0;
#pragma unroll 1
      for (int r = 0; r < 3; r++) {
#pragma unroll
        for (int i = 0; i < 2 * NS1B; i++) {
          const uint64_t da = da0 + sa * (STG1A >> 4) + (i & 1) * 4, db = db0 + (i % NS1B) * (STG1B >> 4);
          if (i || r) {
            if (!(i & 1)) mbar_wait(bars + 8 * (BAR_FULLA + sa), pha);
            mbar_wait(bars + 8 * (BAR_FULLB + i % NS1B), i / NS1B);
          } else {
            asm volatile("cp.async.wait_group 0;\n" ::: "memory");
            fence_async_smem();
            nb_sync(NB_FIRST, 256);
            PROF(0 + wg);
          }
          wg_fence();
          wgmma_n192(acc0, da + 64, db, i ? 1 : r);
          wgmma_n192(acc1, da, db, i ? 1 : r);
          wgmma_n192(acc0, da + 66, db + 128, 1);
          wgmma_n192(acc1, da + 2, db + 128, 1);
          wg_commit();
          wg_wait<1>();
          if (i || r) {
            if (sigb) mbar_arrive(bars + 8 * (BAR_EMPTYB + (i + NS1B - 1) % NS1B));
            if (!(i & 1) && signaller) mbar_arrive_cluster(rela);
          } else {
            asm volatile("barrier.cluster.wait.aligned;\n" ::: "memory");
          }
          if (i & 1) {
            rela = rbars + 8 * (BAR_EMPTYA + sa);
            if (++sa == NS1A) { sa = 0; pha ^= 1; }
          }
        }
        db0 += p.zero;
      }
      const int lr = lane & 7, lm = lane >> 3;
      const bool le0 = 2 * (lane & 3) <= (lane >> 2), le1 = 2 * (lane & 3) + 1 <= (lane >> 2);
      const uint32_t maskLE = (le0 ? 0x0000FFFFu : 0u) | (le1 ? 0xFFFF0000u : 0u);
      uint32_t q[4][8], k[5][8], vt[5][8];
      {
        static_assert(15 % NS1A == 0 && 30 % NS1B == 0, "slots of the last k blocks");
        asm volatile("ld.volatile.global.v4.u32 {%0,%1,%2,%3}, [%4];\n"
                     : "=r"(t[0].r), "=r"(t[1].r), "=r"(t[0].i), "=r"(t[1].i) : "l"(g_tab + 1536 + wtid * 4) : "memory");
        mbar_wait(bars + 8 * BAR_FULLA, 1);
        mbar_wait(bars + 8 * BAR_FULLB, 0);
        mbar_wait(bars + 8 * (BAR_FULLB + 1), 0);
        mbar_wait(bars + 8 * (BAR_EMPTYA + 1), 0);
        const uint64_t da = mkdesc(sb + wg * 16384, 16, 2048, 1);
        const uint64_t db = mkdesc(sb + OFF_1B, 4096, 1024, 1);
        wg_fence();
#pragma unroll
        for (int i = 0; i < 4; i++) wgmma_n192(acc0, da + 64 + 2 * i, db + (i >> 1) * (STG1B >> 4) + (i & 1) * 128, 1);
        wg_commit();
#pragma unroll
        for (int i = 0; i < 2; i++) wgmma_n192(acc1, da + 2 * i, db + (i >> 1) * (STG1B >> 4) + (i & 1) * 128, 1);
        wg_commit();
        wg_wait<1>();
        fence_regs(acc0);
        PROFA(45, 0);
        attn_pack<8, 1, false>(acc0, k[4]);
        attn_pack<16, 1, true>(acc0, vt[4]);
        const uint32_t kh = sb + (warp == 7 ? OFF_OP + 7 * 4096 : OFF_KH + (warp + 1) * 2048) + lane * 16;
        sts128(kh, k[4][0], k[4][1], k[4][2], k[4][3]);
        sts128(kh + 512, k[4][4], k[4][5], k[4][6], k[4][7]);
#pragma unroll
        for (int i = 0; i < 4; i++) sts64(kh - lane * 8 + 1024 + 256 * i, vt[4][2 * i], vt[4][2 * i + 1]);
#pragma unroll
        for (int i = 2; i < 4; i++) wgmma_n192(acc1, da + 2 * i, db + (i >> 1) * (STG1B >> 4) + (i & 1) * 128, 1);
        wg_commit();
        attn_pack<0, 0, false>(acc0, q[1]);
        attn_pack<0, 1, false>(acc0, q[3]);
        attn_pack<8, 0, false>(acc0, k[2]);
        attn_pack<16, 0, true>(acc0, vt[2]);
        uint32_t z = p.zero;
#pragma unroll
        for (int i = 0; i < 8; i++) z &= q[1][i] & q[3][i];
#pragma unroll
        for (int i = 0; i < 8; i += 2) z &= k[2][i] & k[2][i + 1];
        __syncwarp();
        if (lane == 0) mbar_arrive(bars + 8 * BAR_STG + z);
        wg_wait<0>();
        fence_regs(acc1);
        if (MODE == 0) nb_arrive(NB_G1END, 288);
      }
      PROF(2 + wg);
      mbar_wait(bars + 8 * (warp == 0 ? BAR_HALO : BAR_STG), 0);
      {
        const uint32_t kh = sb + OFF_KH + warp * 2048 + lane * 16;
#pragma unroll
        for (int i = 0; i < 2; i++) {
          const uint4 t = lds128(kh + 512 * i);
          k[0][4 * i] = t.x; k[0][4 * i + 1] = t.y; k[0][4 * i + 2] = t.z; k[0][4 * i + 3] = t.w;
        }
#pragma unroll
        for (int i = 0; i < 4; i++) {
          const uint2 t = lds64(kh - lane * 8 + 1024 + 256 * i);
          vt[0][2 * i] = t.x; vt[0][2 * i + 1] = t.y;
        }
      }
      attn_pack<0, 0, false>(acc1, q[0]);
      attn_pack<0, 1, false>(acc1, q[2]);
      attn_pack<8, 0, false>(acc1, k[1]);
      attn_pack<8, 1, false>(acc1, k[3]);
      {
        float x[8][2];
        uint32_t pp[8];
        const bool first = warp == 0 && gidx == 0;
#pragma unroll
        for (int hd = 0; hd < 2; hd++) {
#pragma unroll
          for (int j = 0; j < 4; j += 2) {
            float s0[4], s1[4], s2[4];
            attn_qk(s2, q[j], q[j + 1], k[j + 2], 4 * hd);
            attn_qk(s1, q[j], q[j + 1], k[j + 1], 4 * hd);
            attn_qk(s0, q[j], q[j + 1], k[j], 4 * hd);
            if (j == 0 && first) s0[0] = s0[1] = -1e9f / 0.17677669529663687f;
            x[2 * j + hd][0] = le0 ? s1[0] : s0[0];
            x[2 * j + hd][1] = le1 ? s1[1] : s0[1];
            x[2 * j + 2 + hd][0] = le0 ? s2[2] : s1[2];
            x[2 * j + 2 + hd][1] = le1 ? s2[3] : s1[3];
          }
        }
        PROFA(40, __float_as_uint(x[1][0] + x[7][1]));
        attn_pack<16, 0, true>(acc1, vt[1]);
        attn_pack<16, 1, true>(acc1, vt[3]);
        quad_softmax<8>(x, pp);
        PROFA(41, pp[1] + pp[7]);
        mbar_wait(bars + 8 * BAR_X, 0);
        ldsm4(a1[0], sb + OFF_T32 + (warp & 3) * 1024 + lane * 16);
        ldsm4(a1[1], sb + OFF_T32 + 512 + (warp & 3) * 1024 + lane * 16);
        {
          const uint32_t ex = sb + OFF_EX + wg * 16 + (warp & 2) * 2;
#pragma unroll
          for (int i = 0; i < 2; i++) sc[i] = min(max(381 - (int)lds32(ex + 8 * i) - (int)lds32(ex + 32 + 8 * i), 1), 254) * 0x00800080u;
        }
        const uint32_t obase = sb + OFF_OP + (warp * 32 + lr) * 128;
#pragma unroll
        for (int n = 0; n < 8; n++) {
          attn_pv(obase + (n >> 1) * 1024 + (((4 * (n & 1) + lm) ^ lr) << 4), vt[n >> 1], vt[(n >> 1) + 1], 4 * (n & 1), pp[n],
                  maskLE);
        }
      }
      PROFA(42, 0);
    }

    {
      const int w = warp & 3;
      const int lr = lane & 7, lm = lane >> 3;
      const uint32_t xb = sb + OFF_X + wg * 4 * XT;
      auto uo = [](int c) { return (c & 1) * 2 * XT + (c >> 1) * 2048; };
      const uint64_t dc2 = mkdesc(sb + OFF_T16, 512, 128, 0), dc3 = mkdesc(sb + OFF_T16, 128, 512, 0);
      const uint64_t dc4 = mkdesc(sb + OFF_T32, 128, 256, 0);
      const uint64_t dx = mkdesc(xb, 4096, 512, 2), dz = mkdesc(xb, 4096, 256, 3);
      const uint32_t zs = xb + (w * 16 + (lm & 1) * 8 + lr) * 32 + (((lm >> 1) ^ (lr >> 2)) << 4);
      const uint32_t ys = xb + w * 4096 + (lm >> 1) * 256 + ((lr * 32 + (((lm & 1) ^ (lr >> 2)) << 4)) ^ (rank << 6) ^ ((w & 2) << 4));
      const bool own = (w & 1) == rank;
      const uint32_t ybar = mapa(bars, own ? rank ^ 1 : rank) + 8 * BAR_Y;
      uint32_t d[2][32], pa[2][4][2][4], e[4][4][8], ya[2][2][2][4], v[2][2][8];
      C2 s1[2][2][2];
      float o[2][16];
      auto rows = [&](int c) {
        fft_rows(d[c & 1], a1, dx + (uo(c) >> 4));
        wg_commit();
      };
      auto cols = [&](int c) {
        const int s = c & 1;
        fence_regs(d[s]);
#pragma unroll
        for (int i = 0; i < 16; i++) {
          const C2 z = crot(C2{d[s][2 * i], d[s][2 * i + 1]}, t[i & 1]);
          pa[s][i >> 2][i & 1][(i >> 1) & 1] = z.r;
          pa[s][i >> 2][i & 1][2 + ((i >> 1) & 1)] = z.i;
        }
        wg_fence();
#pragma unroll
        for (int i = 0; i < 4; i++) fft_cols<0>(e[c][i], pa[s][i], dc2);
        wg_commit();
      };
      auto prod = [&](int c, int n) {
        const int s = c & 1;
        fence_regs(e[c][2 * n]);
        fence_regs(e[c][2 * n + 1]);
#pragma unroll
        for (int j = 0; j < 2; j++) {
          const C2 u0 = cget(e[s][2 * n], j, 0), u1 = cget(e[s][2 * n], j, 1);
          const C2 h0 = cget(e[s][2 * n + 1], j, 0), h1 = cget(e[s][2 * n + 1], j, 1);
          C2 y0, y1;
          if (c < 2) {
            y0 = cmul(h0, u0);
            s1[s][n][j] = cfma(h0, u1, cmul(h1, u0));
            y1 = C2{hadd2(s1[s][n][j].r, y0.i), hadd2(s1[s][n][j].i, hneg2(y0.r))};
          } else {
            const C2 u2 = cget(e[c][2 * n], j, 0), u3 = cget(e[c][2 * n], j, 1);
            const C2 h2 = cget(e[c][2 * n + 1], j, 0), h3 = cget(e[c][2 * n + 1], j, 1);
            const C2 s2 = cfma(h0, u2, cfma(h2, u0, cmul(h1, u1)));
            y0 = C2{hadd2(s2.r, s1[s][n][j].i), hadd2(s2.i, hneg2(s1[s][n][j].r))};
            y1 = cfma(h0, u3, cfma(h1, u2, cfma(h2, u1, cfma(h3, u0, C2{s2.i, hneg2(s2.r)}))));
          }
          ya[s][n][j][0] = y0.r;
          ya[s][n][j][1] = y1.r;
          ya[s][n][j][2] = y0.i;
          ya[s][n][j][3] = y1.i;
        }
      };
      auto icols = [&](int c) {
        wg_fence();
        fft_cols<1>(v[c & 1][0], ya[c & 1][0], dc3);
        fft_cols<1>(v[c & 1][1], ya[c & 1][1], dc3);
        wg_commit();
      };
      auto stage = [&](int c) {
        const int s = c & 1;
        fence_regs(v[s][0]);
        fence_regs(v[s][1]);
#pragma unroll
        for (int b = 0; b < 4; b++) {
          const C2 x0 = cget(v[s][b >> 1], 0, b & 1), x1 = cget(v[s][b >> 1], 1, b & 1);
          const C2 z0 = crot(C2{x0.i, x0.r}, t[0]), z1 = crot(C2{x1.i, x1.r}, t[1]);
          stsm4(zs + uo(c) + b * 4096, z0.i, z0.r, z1.i, z1.r);
        }
      };
      auto back = [&](int c) {
        fft_back(o[c & 1], dz + (uo(c) >> 4), dc4);
        wg_commit();
      };
      auto out = [&](int c) {
        float (&r)[16] = o[c & 1];
        fence_regs(r);
#pragma unroll
        for (int i = 0; i < 16; i += 8)
          stsm4t(ys + uo(c) + 64 * i, bmul2(pack_bf16(r[i], r[i + 1]), sc[c & 1]), bmul2(pack_bf16(r[i + 2], r[i + 3]), sc[c & 1]),
                 bmul2(pack_bf16(r[i + 4], r[i + 5]), sc[c & 1]), bmul2(pack_bf16(r[i + 6], r[i + 7]), sc[c & 1]));
      };
      auto signal = [&](int yb, int land) {
        __syncwarp();
        if (lane == 0) {
          mbar_arrive_cluster(ybar + 8 * yb);
          if (own && land >= 0) mbar_arrive(bars + 8 * (BAR_LAND + land));
        }
      };
      wg_fence();
      rows(0);
      rows(1);
      fence_async_smem();
      nb_arrive(NB_OREADY, 288);
      PROF(34 + wg);
      wg_wait<1>();
      cols(0);
      wg_wait<1>();
      cols(1);
      rows(2);
      nb_sync(NB_CONV + wg, 128);
      wg_wait<2>();
      prod(0, 0);
      prod(0, 1);
      icols(0);
      wg_wait<2>();
      prod(1, 0);
      prod(1, 1);
      icols(1);
      PROF3(40 + 10 * wg);
      wg_wait<1>();
      stage(0);
      wg_wait<0>();
      stage(1);
      fence_async_smem();
      cols(2);
      PROF3(41 + 10 * wg);
      nb_sync(NB_CONV + wg, 128);
      back(0);
      back(1);
      wg_wait<2>();
      wg_fence();
      rows(3);
      prod(2, 0);
      wg_wait<1>();
      out(0);
      out(1);
      signal(wg, 0);
      PROF3(42 + 10 * wg);
      prod(2, 1);
      icols(2);
      wg_wait<1>();
      cols(3);
      PROF3(43 + 10 * wg);
      wg_wait<1>();
      stage(2);
      fence_async_smem();
      wg_wait<0>();
      prod(3, 0);
      nb_sync(NB_CONV + wg, 128);
      wg_fence();
      back(2);
      prod(3, 1);
      icols(3);
      PROF3(44 + 10 * wg);
      wg_wait<1>();
      out(2);
      signal(2, -1);
      wg_wait<0>();
      stage(3);
      PROF3(45 + 10 * wg);
      fence_async_smem();
      nb_sync(NB_CONV + wg, 128);
      wg_fence();
      back(3);
      constexpr int G = MODE == 0 && EARLY;
      if (MODE == 0) mbar_wait(bars + 8 * (BAR_EMPTY2 + 4), 0);
      if (G) g2_block(true, 0, 0);
      wg_wait<G>();
      if (lane == 0) mbar_arrive_cluster(mapa(bars, 1) + 8 * BAR_TAB);
      out(3);
      signal(3, 1);
      PROF(6 + wg);
    }
    }

    if (MODE != 1) {
      if (MODE == 2 || !EARLY) g2_block(true, 0, 0);
      const int lr = lane & 7, lm = lane >> 3;
      const uint32_t wb = sb + g2_a(1, 0) + warp * 2048;
      const int orow = (rb2 & 7) * 128 + warp * 16;
      uint4* og = reinterpret_cast<uint4*>(p.out + (size_t)(2 * (orow + lm) + (rb2 >> 3)) * (2 * DM) + DM + cb2 * 128 + lr * 8);
      uint32_t wst = wb + (lr + 8 * (lm & 1)) * 128, wsx = ((lm >> 1) ^ lr) << 4, wld = wb + lm * 128, wlx = (lr ^ lm) << 4;
      asm volatile("" : "+l"(og), "+r"(wst), "+r"(wsx), "+r"(wld), "+r"(wlx));
      static_assert(ENDG == NS2 && (G2SEQ >> 4 & 0xfffff) == (G2SEQ >> 24 & 0xfffff) && (G2SEQ >> 4 & 0xfffff) == G2SEQ >> 44, "rounds");
#pragma unroll 1
      for (int r = 0; r < 3; r++) {
        const bool hold = r == 2 && wg != LEADWG;
        const uint32_t rel0 = g2rel + (r ? 8 * (G2SEQ >> 20 & 7) : 0);
        if (hold) {
          wg_wait<0>();
          if (signaller) mbar_arrive_cluster(rel0);
          nb_sync(NB_LEAD, 256);
        }
#pragma unroll
        for (int i = 1; i <= NS2; i++) {
          const int s = G2SEQ >> (4 * i) & 7;
          g2_block(false, s, (r & 1) ^ (s == 0));
          if (warp == LEADWG * 4) PROF2(40 + 5 * r + i);
          if (i == 1 ? !hold : r < 2) {
            wg_wait<1>();
            if (signaller) mbar_arrive_cluster(i == 1 ? rel0 : g2rel + 8 * (G2SEQ >> (4 * i - 4) & 7));
          }
        }
        if (r == 0) PROF(8 + wg);
        g2a += p.zero;
        g2b += p.zero;
      }
      if (wg == LEADWG) nb_arrive(NB_LEAD, 256);
      wg_wait<0>();
      fence_regs(acc);
      PROF(10 + wg);
#pragma unroll
      for (int h = 0; h < 2; h++) {
        const uint32_t b = h * (g2_a(3, 0) - g2_a(1, 0));
#pragma unroll
        for (int j = 8 * h; j < 8 * h + 8; j += 2)
          stsm4(wst + b + (wsx ^ ((j & 7) << 4)), pack_bf16(acc[4 * j], acc[4 * j + 1]),
                pack_bf16(acc[4 * j + 2], acc[4 * j + 3]), pack_bf16(acc[4 * j + 4], acc[4 * j + 5]),
                pack_bf16(acc[4 * j + 6], acc[4 * j + 7]));
        if (OTMA == 2 || (OTMA == 1 && wg == LEADWG)) {
          fence_async_smem();
          __syncwarp();
          if (elect_one()) {
            tma_store_3d(&tmOb, wb + b, DM + cb2 * 128 + h * 64, rb2 >> 3, orow);
            bulk_commit();
          }
        } else {
          __syncwarp();
          uint4 v[4];
#pragma unroll
          for (int i = 0; i < 4; i++) v[i] = lds128(wld + b + i * 512 + (wlx ^ ((i & 1) << 6)));
#pragma unroll
          for (int i = 0; i < 4; i++) og[(size_t)i * 8 * (2 * DM / 8) + h * 8] = v[i];
        }
      }
      PROF(12 + wg);
      if (OTMA) bulk_wait0();
    }
    cluster_sync_all();
  }
}

typedef CUresult (*EncodeFn)(CUtensorMap*, CUtensorMapDataType, cuuint32_t, void*, const cuuint64_t*, const cuuint64_t*,
                             const cuuint32_t*, const cuuint32_t*, CUtensorMapInterleave, CUtensorMapSwizzle,
                             CUtensorMapL2promotion, CUtensorMapFloatOOBfill);

void make_map(EncodeFn enc, CUtensorMap* tm, const void* base, int rank, const cuuint64_t* dims, const cuuint64_t* strides,
              const cuuint32_t* box, CUtensorMapSwizzle swz) {
  cuuint32_t es[5] = {1, 1, 1, 1, 1};
  enc(tm, CU_TENSOR_MAP_DATA_TYPE_BFLOAT16, rank, const_cast<void*>(base), dims, strides, box, es,
      CU_TENSOR_MAP_INTERLEAVE_NONE, swz, CU_TENSOR_MAP_L2_PROMOTION_L2_256B, CU_TENSOR_MAP_FLOAT_OOB_FILL_NONE);
}

}

extern "C" void kernel_launch(void* const* d_in, const int* in_sizes, int n_in, void* d_out, int out_size) {
  static EncodeFn enc = nullptr;
  static bool coresident = true;
  if (!enc) {
    void* fn = nullptr;
    cudaDriverEntryPointQueryResult qr;
    cudaGetDriverEntryPoint("cuTensorMapEncodeTiled", &fn, cudaEnableDefault, &qr);
    enc = (EncodeFn)fn;
    cudaFuncSetAttribute(fused_kernel<0>, cudaFuncAttributeMaxDynamicSharedMemorySize, SMEM_BYTES);
    cudaFuncSetAttribute(fused_kernel<1>, cudaFuncAttributeMaxDynamicSharedMemorySize, SMEM_BYTES);
    cudaFuncSetAttribute(fused_kernel<2>, cudaFuncAttributeMaxDynamicSharedMemorySize, SMEM_BYTES);
    cudaLaunchConfig_t cfg = {};
    cfg.gridDim = dim3(NCTA);
    cfg.blockDim = dim3(NTHREADS);
    cfg.dynamicSmemBytes = SMEM_BYTES;
    cudaLaunchAttribute at;
    at.id = cudaLaunchAttributeClusterDimension;
    at.val.clusterDim.x = 2;
    at.val.clusterDim.y = 1;
    at.val.clusterDim.z = 1;
    cfg.attrs = &at;
    cfg.numAttrs = 1;
    int nclusters = 0;
    if (cudaOccupancyMaxActiveClusters(&nclusters, fused_kernel<0>, &cfg) == cudaSuccess) coresident = nclusters >= NCTA / 2;
    (void)cudaGetLastError();
  }
  CUtensorMap tmX, tmW, tmWo, tmWp, tmQ, tmOb, tmXh, tmWh;
  {
    cuuint64_t dims[3] = {1024, 2, 1024};
    cuuint64_t str[2] = {2048, 4096};
    cuuint32_t box[3] = {64, 1, 128};
    make_map(enc, &tmX, d_in[6], 3, dims, str, box, CU_TENSOR_MAP_SWIZZLE_128B);
  }
  {
    cuuint64_t dims[3] = {1024, 1024, 3};
    cuuint64_t str[2] = {6144, 2048};
    cuuint32_t box[3] = {64, 32, 3};
    make_map(enc, &tmW, d_in[7], 3, dims, str, box, CU_TENSOR_MAP_SWIZZLE_128B);
  }
  {
    cuuint64_t dims[3] = {64, 1024, 16};
    cuuint64_t str[2] = {2048, 128};
    cuuint32_t box[3] = {64, 64, 2};
    cuuint32_t piece[3] = {64, 32, 1};
    make_map(enc, &tmWo, d_in[8], 3, dims, str, box, CU_TENSOR_MAP_SWIZZLE_128B);
    make_map(enc, &tmWp, d_in[8], 3, dims, str, piece, CU_TENSOR_MAP_SWIZZLE_128B);
  }
  {
    cuuint64_t dims[5] = {1024, 2, 2, 4, 128};
    cuuint64_t str[4] = {2048, 8 * 2048, 2 * 2048, 16 * 2048};
    cuuint32_t box[5] = {16, 2, 2, 4, 32};
    make_map(enc, &tmQ, d_in[0], 5, dims, str, box, CU_TENSOR_MAP_SWIZZLE_NONE);
  }
  {
    cuuint64_t dims[3] = {2048, 2, 1024};
    cuuint64_t str[2] = {4096, 8192};
    cuuint32_t box[3] = {64, 1, 16};
    make_map(enc, &tmOb, d_out, 3, dims, str, box, CU_TENSOR_MAP_SWIZZLE_128B);
  }
  {
    cuuint64_t dims[4] = {1024, 256, 2, 4};
    cuuint64_t str[3] = {4096, 2048, 256 * 4096};
    cuuint32_t box[4] = {64, 8, 2, 3};
    make_map(enc, &tmXh, d_in[6], 4, dims, str, box, CU_TENSOR_MAP_SWIZZLE_128B);
  }
  {
    cuuint64_t dims[3] = {64, 1024, 48};
    cuuint64_t str[2] = {6144, 128};
    cuuint32_t box[3] = {64, 64, 4};
    make_map(enc, &tmWh, d_in[7], 3, dims, str, box, CU_TENSOR_MAP_SWIZZLE_128B);
  }
  Params p;
  p.q = (const __nv_bfloat16*)d_in[0];
  p.k = (const __nv_bfloat16*)d_in[1];
  p.v = (const __nv_bfloat16*)d_in[2];
  p.shift_k = (const __nv_bfloat16*)d_in[3];
  p.ssm_k = (const __nv_bfloat16*)d_in[4];
  p.ssm_D = (const __nv_bfloat16*)d_in[5];
  p.x = (const __nv_bfloat16*)d_in[6];
  p.w = (const __nv_bfloat16*)d_in[7];
  p.wo = (const __nv_bfloat16*)d_in[8];
  p.out = (__nv_bfloat16*)d_out;
  p.zero = 0;
  if (coresident) {
    fused_kernel<0><<<NCTA, NTHREADS, SMEM_BYTES>>>(p, tmX, tmW, tmWo, tmWp, tmQ, tmOb, tmXh, tmWh);
  } else {
    fused_kernel<0><<<4, NTHREADS, SMEM_BYTES>>>(p, tmX, tmW, tmWo, tmWp, tmQ, tmOb, tmXh, tmWh);
    fused_kernel<1><<<NCTA, NTHREADS, SMEM_BYTES>>>(p, tmX, tmW, tmWo, tmWp, tmQ, tmOb, tmXh, tmWh);
    fused_kernel<2><<<NCTA, NTHREADS, SMEM_BYTES>>>(p, tmX, tmW, tmWo, tmWp, tmQ, tmOb, tmXh, tmWh);
  }
}
```

```cpp
#include <cuda_runtime.h>
#include <cuda.h>
#include <cuda_bf16.h>
#include <stdint.h>

namespace {

constexpr int SEQ = 2048;
constexpr int DM = 1024;
constexpr int NCTA = 132;
constexpr int NTHREADS = 384;

constexpr int STG1A = 32768;
constexpr int NS1A = 3;
constexpr int STG1B = 12288;
constexpr int NS1B = 5;
constexpr int OFF_1B = NS1A * STG1A;
constexpr int STG2 = 32768;
constexpr int NS2 = 5;
#define G2SEQ 0x0432104321043210ull
constexpr unsigned long long g2_seq() {
  unsigned long long r = G2SEQ;
  for (int kb = 0; kb < 16; kb++)
    for (int j = 0; j < kb; j++)
      if (((G2SEQ >> (4 * j)) & 7) == ((G2SEQ >> (4 * kb)) & 7)) r ^= 8ull << (4 * kb);
  return r;
}
constexpr unsigned long long G2_SEQ = g2_seq();
constexpr int g2_first4() {
  int kb = 0;
  while (((G2SEQ >> (4 * kb)) & 7) != 4) kb++;
  return kb;
}
constexpr int G2_KB4 = g2_first4();
#define POLL0 1500
#define QORD 1
#define BDEL 0
#define HPF0 0
#define PF0 8
#define PF1 12
#define PSTEP 1250
#define FPACE 260
#define LEADWG 1
#define OTMA 1
#define EARLY 1
#define R3 0
#define FSL 50
#define JS 1
#define FPACE2 230
#define PFR 1
#define PF2 2
#define PF2X 1
#define ENDG 5
__device__ __forceinline__ uint32_t g2_a(int s, int hsel) { return (((0x97524 >> (4 * s)) & 15) ^ (s & 5 ? 0 : hsel)) << 14; }
constexpr int OFF_Q0 = 3 << 14, OFF_Q1 = 8 << 14;
constexpr int STGH = 73728;
constexpr int OFF_KH = 1 * STG2;
constexpr int OFF_OP = 2 * STG2;
constexpr int OFF_T32 = 5 * STG2 - 4096;
constexpr int OFF_X = 5 * STG2;
constexpr int XT = 8192;
__device__ __forceinline__ uint32_t g2_b(int s, int rank) {
  return s < 3 ? (s == 2 ? 6 : s) << 14 : OFF_X + (s - 3) * 2 * XT + (rank ^ 1) * 4096;
}
__device__ __forceinline__ uint32_t g2_bk(int s) { return s < 3 ? 4096 : 4 * XT; }
constexpr int OFF_BAR = OFF_X + 8 * XT;
constexpr int OFF_EX = OFF_BAR + 448;
constexpr int OFF_T16 = 230400;
constexpr int SMEM_BYTES = OFF_T16 + 2048;
static_assert(OFF_1B + NS1B * STG1B <= OFF_T32 && OFF_X % 1024 == 0, "layout");
static_assert(3 * STGH <= OFF_BAR && OFF_EX + 64 <= OFF_T16 && SMEM_BYTES <= 232448, "smem");

constexpr int BAR_FULLA = 0;
constexpr int BAR_EMPTYA = 3;
constexpr int BAR_FULLB = 6;
constexpr int BAR_EMPTYB = 11;
constexpr int BAR_FULL2 = 16;
constexpr int BAR_EMPTY2 = 21;
constexpr int BAR_EMPTY2B = 44;
constexpr int BAR_X = 26;
constexpr int BAR_LAND = 42;
constexpr int BAR_TAB = 28;
constexpr int BAR_U = 29;
constexpr int BAR_H = 30;
constexpr int BAR_STG = 31;
constexpr int BAR_Y = 32;
constexpr int BAR_XFREE = 38;
constexpr int BAR_HALO = 40;
constexpr int BAR_Q = 41;

constexpr int NB_G1DONE = 1;
constexpr int NB_LEAD = 2;
constexpr int NB_G1END = 3;
constexpr int NB_OREADY = 4;
constexpr int NB_CONV = 5;
constexpr int NB_HELP3 = 11;
constexpr int NB_FIRST = 13;

#define REG_MATH 224
#define REG_HELP 56
constexpr int SPIN_LIMIT = 1 << 20;

__device__ __align__(1024) __nv_bfloat16 g_o[SEQ * DM];
__device__ uint32_t g_flag_o[128];
__device__ uint32_t g_flag_h[4];
__device__ uint4 g_halo[128 * 128];
__device__ __align__(128) const uint32_t g_tab[2048] = {
  0x2fd93000,0x2ea72f64,0x2c722da8,0x263e2a1f,0x2ea73000,0xa63e2a1f,0xafd9ada8,0xac72af64,0x2c723000,0xafd9aa1f,0x263eada8,0x2ea72f64,
  0x263e3000,0xac72af64,0x2ea72da8,0xafd9aa1f,0xa63e3000,0x2c72af64,0xaea72da8,0x2fd9aa1f,0xac723000,0x2fd9aa1f,0xa63eada8,0xaea72f64,
  0xaea73000,0x263e2a1f,0x2fd9ada8,0x2c72af64,0xafd93000,0xaea72f64,0xac722da8,0xa63e2a1f,0x263e0000,0x2c722a1f,0x2ea72da8,0x2fd92f64,
  0x2c720000,0x2fd92f64,0x263e2da8,0xaea7aa1f,0x2ea70000,0x263e2f64,0xafd9ada8,0x2c72aa1f,0x2fd90000,0xaea72a1f,0x2c72ada8,0xa63e2f64,
  0x2fd90000,0xaea7aa1f,0x2c722da8,0xa63eaf64,0x2ea70000,0x263eaf64,0xafd92da8,0x2c722a1f,0x2c720000,0x2fd9af64,0x263eada8,0xaea72a1f,
  0x263e0000,0x2c72aa1f,0x2ea7ada8,0x2fd9af64,0xafd93000,0xaea72f64,0xac722da8,0xa63e2a1f,0xaea73000,0x263e2a1f,0x2fd9ada8,0x2c72af64,
  0xac723000,0x2fd9aa1f,0xa63eada8,0xaea72f64,0xa63e3000,0x2c72af64,0xaea72da8,0x2fd9aa1f,0x263e3000,0xac72af64,0x2ea72da8,0xafd9aa1f,
  0x2c723000,0xafd9aa1f,0x263eada8,0x2ea72f64,0x2ea73000,0xa63e2a1f,0xafd9ada8,0xac72af64,0x2fd93000,0x2ea72f64,0x2c722da8,0x263e2a1f,
  0xa63e0000,0xac722a1f,0xaea72da8,0xafd92f64,0xac720000,0xafd92f64,0xa63e2da8,0x2ea7aa1f,0xaea70000,0xa63e2f64,0x2fd9ada8,0xac72aa1f,
  0xafd90000,0x2ea72a1f,0xac72ada8,0x263e2f64,0xafd90000,0x2ea7aa1f,0xac722da8,0x263eaf64,0xaea70000,0xa63eaf64,0x2fd92da8,0xac722a1f,
  0xac720000,0xafd9af64,0xa63eada8,0x2ea72a1f,0xa63e0000,0xac72aa1f,0xaea7ada8,0xafd9af64,0xa63e0000,0xac72aa1f,0xaea7ada8,0xafd9af64,
  0xac720000,0xafd9af64,0xa63eada8,0x2ea72a1f,0xaea70000,0xa63eaf64,0x2fd92da8,0xac722a1f,0xafd90000,0x2ea7aa1f,0xac722da8,0x263eaf64,
  0xafd90000,0x2ea72a1f,0xac72ada8,0x263e2f64,0xaea70000,0xa63e2f64,0x2fd9ada8,0xac72aa1f,0xac720000,0xafd92f64,0xa63e2da8,0x2ea7aa1f,
  0xa63e0000,0xac722a1f,0xaea72da8,0xafd92f64,0x2fd93000,0x2ea72f64,0x2c722da8,0x263e2a1f,0x2ea73000,0xa63e2a1f,0xafd9ada8,0xac72af64,
  0x2c723000,0xafd9aa1f,0x263eada8,0x2ea72f64,0x263e3000,0xac72af64,0x2ea72da8,0xafd9aa1f,0xa63e3000,0x2c72af64,0xaea72da8,0x2fd9aa1f,
  0xac723000,0x2fd9aa1f,0xa63eada8,0xaea72f64,0xaea73000,0x263e2a1f,0x2fd9ada8,0x2c72af64,0xafd93000,0xaea72f64,0xac722da8,0xa63e2a1f,
  0x263e0000,0x2c72aa1f,0x2ea7ada8,0x2fd9af64,0x2c720000,0x2fd9af64,0x263eada8,0xaea72a1f,0x2ea70000,0x263eaf64,0xafd92da8,0x2c722a1f,
  0x2fd90000,0xaea7aa1f,0x2c722da8,0xa63eaf64,0x2fd90000,0xaea72a1f,0x2c72ada8,0xa63e2f64,0x2ea70000,0x263e2f64,0xafd9ada8,0x2c72aa1f,
  0x2c720000,0x2fd92f64,0x263e2da8,0xaea7aa1f,0x263e0000,0x2c722a1f,0x2ea72da8,0x2fd92f64,0xafd93000,0xaea72f64,0xac722da8,0xa63e2a1f,
  0xaea73000,0x263e2a1f,0x2fd9ada8,0x2c72af64,0xac723000,0x2fd9aa1f,0xa63eada8,0xaea72f64,0xa63e3000,0x2c72af64,0xaea72da8,0x2fd9aa1f,
  0x263e3000,0xac72af64,0x2ea72da8,0xafd9aa1f,0x2c723000,0xafd9aa1f,0x263eada8,0x2ea72f64,0x2ea73000,0xa63e2a1f,0xafd9ada8,0xac72af64,
  0x2fd93000,0x2ea72f64,0x2c722da8,0x263e2a1f,0xa63e0000,0xac72aa1f,0xaea7ada8,0xafd9af64,0x2c720000,0x2fd92f64,0x263e2da8,0xaea7aa1f,
  0xaea70000,0xa63eaf64,0x2fd92da8,0xac722a1f,0x2fd90000,0xaea72a1f,0x2c72ada8,0xa63e2f64,0xafd90000,0x2ea72a1f,0xac72ada8,0x263e2f64,
  0x2ea70000,0x263eaf64,0xafd92da8,0x2c722a1f,0xac720000,0xafd92f64,0xa63e2da8,0x2ea7aa1f,0x263e0000,0x2c72aa1f,0x2ea7ada8,0x2fd9af64,
  0x2fd93000,0x2ea72f64,0x2c722da8,0x263e2a1f,0xaea7b000,0x263eaa1f,0x2fd92da8,0x2c722f64,0x2c723000,0xafd9aa1f,0x263eada8,0x2ea72f64,
  0xa63eb000,0x2c722f64,0xaea7ada8,0x2fd92a1f,0xa63e3000,0x2c72af64,0xaea72da8,0x2fd9aa1f,0x2c72b000,0xafd92a1f,0x263e2da8,0x2ea7af64,
  0xaea73000,0x263e2a1f,0x2fd9ada8,0x2c72af64,0x2fd9b000,0x2ea7af64,0x2c72ada8,0x263eaa1f,0x263e0000,0x2c72aa1f,0x2ea7ada8,0x2fd9af64,
  0xac720000,0xafd92f64,0xa63e2da8,0x2ea7aa1f,0x2ea70000,0x263eaf64,0xafd92da8,0x2c722a1f,0xafd90000,0x2ea72a1f,0xac72ada8,0x263e2f64,
  0x2fd90000,0xaea72a1f,0x2c72ada8,0xa63e2f64,0xaea70000,0xa63eaf64,0x2fd92da8,0xac722a1f,0x2c720000,0x2fd92f64,0x263e2da8,0xaea7aa1f,
  0xa63e0000,0xac72aa1f,0xaea7ada8,0xafd9af64,0xafd93000,0xaea72f64,0xac722da8,0xa63e2a1f,0x2ea7b000,0xa63eaa1f,0xafd92da8,0xac722f64,
  0xac723000,0x2fd9aa1f,0xa63eada8,0xaea72f64,0x263eb000,0xac722f64,0x2ea7ada8,0xafd92a1f,0x263e3000,0xac72af64,0x2ea72da8,0xafd9aa1f,
  0xac72b000,0x2fd92a1f,0xa63e2da8,0xaea7af64,0x2ea73000,0xa63e2a1f,0xafd9ada8,0xac72af64,0xafd9b000,0xaea7af64,0xac72ada8,0xa63eaa1f,
  0xafd9b000,0xaea7af64,0xac72ada8,0xa63eaa1f,0x2ea73000,0xa63e2a1f,0xafd9ada8,0xac72af64,0xac72b000,0x2fd92a1f,0xa63e2da8,0xaea7af64,
  0x263e3000,0xac72af64,0x2ea72da8,0xafd9aa1f,0x263eb000,0xac722f64,0x2ea7ada8,0xafd92a1f,0xac723000,0x2fd9aa1f,0xa63eada8,0xaea72f64,
  0x2ea7b000,0xa63eaa1f,0xafd92da8,0xac722f64,0xafd93000,0xaea72f64,0xac722da8,0xa63e2a1f,0xa63e0000,0xac72aa1f,0xaea7ada8,0xafd9af64,
  0x2c720000,0x2fd92f64,0x263e2da8,0xaea7aa1f,0xaea70000,0xa63eaf64,0x2fd92da8,0xac722a1f,0x2fd90000,0xaea72a1f,0x2c72ada8,0xa63e2f64,
  0xafd90000,0x2ea72a1f,0xac72ada8,0x263e2f64,0x2ea70000,0x263eaf64,0xafd92da8,0x2c722a1f,0xac720000,0xafd92f64,0xa63e2da8,0x2ea7aa1f,
  0x263e0000,0x2c72aa1f,0x2ea7ada8,0x2fd9af64,0x2fd9b000,0x2ea7af64,0x2c72ada8,0x263eaa1f,0xaea73000,0x263e2a1f,0x2fd9ada8,0x2c72af64,
  0x2c72b000,0xafd92a1f,0x263e2da8,0x2ea7af64,0xa63e3000,0x2c72af64,0xaea72da8,0x2fd9aa1f,0xa63eb000,0x2c722f64,0xaea7ada8,0x2fd92a1f,
  0x2c723000,0xafd9aa1f,0x263eada8,0x2ea72f64,0xaea7b000,0x263eaa1f,0x2fd92da8,0x2c722f64,0x2fd93000,0x2ea72f64,0x2c722da8,0x263e2a1f,
  0x263e0000,0x2c72aa1f,0x2ea7ada8,0x2fd9af64,0xac720000,0xafd92f64,0xa63e2da8,0x2ea7aa1f,0x2ea70000,0x263eaf64,0xafd92da8,0x2c722a1f,
  0xafd90000,0x2ea72a1f,0xac72ada8,0x263e2f64,0x2fd90000,0xaea72a1f,0x2c72ada8,0xa63e2f64,0xaea70000,0xa63eaf64,0x2fd92da8,0xac722a1f,
  0x2c720000,0x2fd92f64,0x263e2da8,0xaea7aa1f,0xa63e0000,0xac72aa1f,0xaea7ada8,0xafd9af64,0x316c2fbd,0x343e32f7,0x35bc34ff,0x372c3676,
  0x371532c6,0x3a81392e,0x3bef3b71,0x3b7c3bf2,0x397034cf,0x3bfc3b6c,0x38b23b04,0xb40e31e8,0x3ae13631,0x39e73bf5,0xb6e83219,0xbbe8bb13,
  0x3bc23785,0x30be3aa9,0xbbfdb911,0x2a16b9aa,0x3bfe3865,0xb80f37a6,0xb82abc00,0x3bfd376f,0x3b9238fd,0xbb7f2311,0x3805b929,0x31223bde,
  0x3a85398b,0xbb96b742,0x3bff319e,0xbbb82f8b,0xbbe2bbf1,0xbbb7bbcf,0xbb78bb9a,0xbb27bb52,0xbb2cbbd2,0xb8a8ba19,0xb029b5df,0x35a52f59,
  0xb9dfbba1,0x2ba7b5f7,0x3a7a37b2,0x3bbd3bdd,0xb815bb60,0x39662e91,0x3b373bda,0xb0d7377a,0xb3d3bb10,0x3be9386f,0x2a7a3a31,0xbbfeb9a6,
  0x294dbab0,0x3ae53b07,0xbad51fdb,0xab43bb16,0x352fba41,0x35993c00,0xbaebba1d,0x3be531cf,0x38a3b9c5,0xb5173b21,0x2776bbe0,0x34323bf2,
  0x384537dd,0x38ea3899,0x39823937,0x3a0d39c9,0x39463a93,0x3340374e,0xb426a452,0xb979b7c8,0xbb45b924,0xbb32bc00,0xb371b902,0x38d63294,
  0xb08db9a1,0x3b3f379b,0x39583bd7,0xb8252dfb,0x3bea3a2d,0xb3ba3874,0xbb89bb0d,0x36d2b625,0xb6bb387f,0xb8d1bbf5,0x3be73602,0xb546391f,
  0xba00bb01,0x3bff35eb,0xba5c34db,0x3359bab6,0x3ac7b66b,0xb9413933,0x368dbabd,0xb0103bb3,0xbac4baf7,0xba50ba8c,0xb9cdba11,0xb93cb986,
  0x3a04388e,0x3bcb3b1e,0x3bba3c00,0x39d63afe,0x36af3a21,0xb6ffa17f,0xbbc8ba3d,0xba60bbd4,0xbbebb9af,0xb6c6bb0a,0x39f43263,0x3ad83bf7,
  0x30a6b916,0x3bc33aa5,0xb55e3790,0xbb3dbb63,0x3b423a9e,0xba642ec3,0xb0f0bb6a,0x3b8e3a25,0xb94a37bd,0x2884bb6f,0x38db3b9f,0xbbc9b85a,
  0xb840bb54,0x3a093a15,0xbb4cb850,0x3bef3457,0x3a893a4d,0x3af43ac1,0x3b4f3b24,0x3b983b76,0xbb94baba,0xbbe4bbf9,0xba58bb57,0xb699b8f8,
  0x3bfe3b18,0x394f3b5c,0xb109347b,0xbae8b884,0xbbc0bb68,0xa9b1b90c,0x3b8b387a,0x38bc3ba5,0x3ade3ba7,0xb8c1324b,0xb9f0bbf6,0x39eb9648,
  0xb96bbbd6,0x3bbf3487,0xb38939b3,0xb9f8bba3,0x370a3bf3,0xbb47b994,0x3bbc2d65,0xb8ad3889,0xb153bc00,0x37213b9c,0xb97dba90,0x3af138f3,
  0xb89eb8ee,0xb7e8b84a,0xb682b737,0xb50bb5c8,0x35233855,0xb13b2d33,0xb8e0b65f,0xbb4aba45,0xa8e8b764,0x39fc3648,0x3be63bae,0x380a3a9b,
  0xb3eb360e,0xbbfeba35,0xb552baa2,0x3a7334b7,0x381ab4ab,0x3a6f3bd8,0xb95d2e5f,0xb962bc00,0xb9e3327c,0xb402bbac,0x3bc6399d,0xb95434c3,
  0x3b2faf27,0xb6a439bc,0xb41abbf9,0x3a7e3a97,0xbbe3251b,0x3b2ab4f3,0xb9d23894,0x37f3ba49,0x3bce3bb5,0x3bf03be1,0x3bff3bfa,0x3bfb3bff,
  0x2c38b1b6,0x383a34e7,0x3aee39c0,0x3bff3bb2,0xbb81bbf8,0xb53ab999,0x38302ef5,0x3bed3ab3,0xb8cc9cb6,0xbb85bbab,0x2adeb86a,0x3bc5391b,
  0x38c73bf6,0xbadbb232,0xb6ddbba9,0x3b87361a,0x3b833201,0xb0743a39,0xba76bb5e,0x3b352dc9,0xac06bbb0,0x39743b59,0xbbeeb759,0x3aceb2ad,
  0xbbccb5d4,0x3bfb2d00,0xbb7a32de,0x3a54b7d2,0xb30fb44b,0xafefb185,0xa6adacce,0x2c9c25e4,0xbbfcbbdf,0xbacbbb9e,0xb7feb990,0xa81fb463,
  0xb58d2d97,0xbb90b9b8,0xbad1bbf4,0xb05bb85f,0x3a673c00,0xb5763493,0xbbfdbaac,0xb3a2ba29,0x3a6b2e2d,0x38203bd9,0xbb3ab49f,0xb56abb65,
  0xb581bbdc,0x3bec3907,0xb8b7363c,0xb6f4bbf8,0xbbfcb46f,0x39dab654,0xb0423b1b,0xb835bbd3,0xb3283b73,0xac6abbfa,0x35b13bd0,0xb8e5bafb,
  0x38ee3a0d,0xb84aba89,0x37373af4,0xb5c8bb4f,0x35df3a81,0x2f59bbef,0xb88e3b7c,0x3b1eb946,0x2d973ae8,0x39b8bb81,0xbbf4353a,0x385f3830,
  0xb2633b3f,0x3bf7b958,0xb60eb825,0xba353bc0,0xb7853b87,0x3aa9b3d3,0x3911bbe9,0xb9aa2a7a,0xb99d3bbf,0x34c33389,0x3bdcb9f8,0x3907bb83,
  0xbb013be5,0xb5eb394a,0x34db2884,0x3ab6b8db,0xbbd03bfb,0xbafb3b7a,0xb98b3a54,0xb74238a3,0x3a4db93c,0xbac1389e,0x3b24b7e8,0xbb763682,
  0x3b71b8a8,0xbbf23029,0x3a9335a5,0xb74eba04,0x3bf8b80a,0xb999b58d,0xaef53b90,0x3ab3bad1,0x3bd7b6c6,0xadfbb9f4,0xbb683ad8,0x390c33eb,
  0x3b10b56a,0x386fbbc2,0xba3130be,0xb9a63bfd,0x39b3b402,0x3ba3bbc6,0x3201b954,0xba393581,0x37bdb122,0x3b6fba00,0x3b9fbbff,0x385aba5c,
  0x32deac6a,0x37d2b5b1,0x39c5b8e5,0x3b21ba85,0x344b3b98,0xb185bbce,0x2cce3bf0,0x25e4bbff,0xbc003340,0x3afe3426,0xb855b979,0x2d333b94,
  0x34cfbbed,0xbb6c39df,0x3b042ba7,0xb1e8ba7a,0x3aa2a9b1,0x34b7bb8b,0xbc0038bc,0x349338cc,0xba2d3bfe,0x387430a6,0x3b0dbbc3,0xb625b55e,
  0xb63cb074,0xbbf83a76,0xb8653b35,0x37a6294d,0x3bf3bbc9,0x3994bb2f,0x2d65b6a4,0xb889341a,0xb19e3517,0x2f8b2776,0x366bb432,0x3933b840,
  0x3bb5b50b,0xbbe1330f,0x3bfaafef,0xbbff26ad,0xa4523bcb,0x37c8bbba,0xbaba39d6,0x3bf9b523,0xbba1305b,0x35f73970,0x37b2bbfc,0xbbdd38b2,
  0x387abbfe,0xbba53552,0x9cb63a73,0x3babba67,0x39162a16,0x3aa5bbea,0xb790b3ba,0xbb633b89,0xbb5e3bec,0xadc938b7,0x3ab0b6f4,0x3b07bbfe,
  0xaf27b359,0xb9bc370a,0xbbf93b47,0xba973bbc,0x3be0bb96,0x3bf2bbff,0x3b54bbb8,0x3a15bac7,0xafbd3bfb,0x32f7bbe2,0xb4ff3bb7,0x3676bb78,
  0x365fbbe4,0xba453a58,0x3bdfb699,0xbb9eac38,0xb9243bbd,0x3c00b6af,0xb902b6ff,0xb2943bc8,0x3aacbb85,0xba29aade,0xb6313bc5,0x3bf5b815,
  0xbba73b3d,0x324b381a,0x3bf6ba6f,0x9648b95d,0x3c00bae5,0x376fbad5,0xb87f2b43,0xbbf53b42,0xbbb03a7e,0xbb593bfc,0xb75939da,0x32ad3042,
  0x3abdba09,0x3bb3bb4c,0x3c00bbef,0x3b9cbbe3,0x3bf12c9c,0xbbcfb16c,0x3b9a343e,0xbb52b5bc,0xbb57b13b,0x38f838e0,0xb1b6bb4a,0xb4e73bfc,
  0x3a21340e,0x217fbb45,0xba3d3b32,0x3bd4b371,0xb86ab576,0xb91b3bfd,0x3b60b3a2,0x2e91bae1,0x34ab36d2,0x3bd8bade,0xae5fb8c1,0xbc0039f0,
  0x9fdbb80f,0xbb16382a,0xba9e3bfd,0x2ec336bb,0xb46f38ad,0x3654ac06,0x3b1bb974,0x3bd3bbee,0x3850b941,0x3457b68d,0xa51bb010,0xb4f33153,
  0xb7dd3b27,0x3899bac4,0xb9373a50,0x39c9b9cd,0x3990383a,0xb463baee,0xb2c63bff,0x392ebb2c,0x3b18ba60,0xbb5c28e8,0x347b39fc,0x3884bbe6,
  0xb219b966,0xbb133b37,0x39a130d7,0x379bbbeb,0xbbf63962,0xb2323a6b,0x3ba9b820,0x361abb3a,0xb6023a64,0x391fb0f0,0x3bd6bb8e,0x3487b9e3,
  0x3a41b835,0x3c00bb92,0x3a1dbb7f,0x31cfb805,0x3a90bb2a,0x38f3b9d2,0x35d4b7f3,0x2d00b328,0x3af7372c,0xba8cb845,0x3a1138ea,0xb986b982,
  0x39c0bacb,0xbbb237fe,0x3bd2a81f,0xba19b715,0xb764b8d6,0xb6483bfe,0x3baeb94f,0xba9bb109,0xbbda39e7,0x377a36e8,0x39afbbe8,0xbb0a308d,
  0xae2d39eb,0x3bd9b8c7,0x349fbadb,0xbb6536dd,0x3b6ab8d1,0x3a25bbe7,0xb27cb546,0xbbac396b,0x38fdbace,0xa311b52f,0xb9293599,0xbbde3aeb,
  0xb8943721,0xba49397d,0xbb733af1,0xbbfa3bcc,0xbbfb3bff,0xbbe23bf1,0xbbb73bcf,0xbb783b9a,0xbb7c3bf2,0xb9463a93,0xb340374e,0x3426a452,
  0xba603bd4,0xa8e83764,0x39fcb648,0x3be6bbae,0xb8bc3ba5,0x38cc9cb6,0x3b85bbab,0xaadeb86a,0xb56a3b65,0x3bc2b785,0x30bebaa9,0xbbfd3911,
  0xab433b16,0x3b42ba9e,0xba64aec3,0xb0f03b6a,0x33593ab6,0x370abbf3,0xbb473994,0x3bbcad65,0x37f33a49,0xb328bb73,0xac6a3bfa,0x35b1bbd0,
  0xac9c25e4,0xb16c2fbd,0xb43e32f7,0xb5bc34ff,0xb5a52f59,0xba04388e,0xbbcb3b1e,0xbbba3c00,0xb8d63294,0xbbfe3b18,0xb94f3b5c,0x3109347b,
  0xba7334b7,0xba673c00,0x35763493,0x3bfdbaac,0xbb87361a,0xb3d33b10,0x3be9b86f,0x2a7aba31,0xbbfd376f,0x36bb387f,0x38d1bbf5,0xbbe73602,
  0xbbc9385a,0x3b2f2f27,0xb6a4b9bc,0xb41a3bf9,0xbaf138f3,0x3bccb5d4,0xbbfb2d00,0x3b7a32de,0xbb273b52,0xbac43af7,0xba503a8c,0xb9cd3a11,
  0x3979b7c8,0x3b94baba,0x3be4bbf9,0x3a58bb57,0x380aba9b,0xb58dad97,0xbb9039b8,0xbad13bf4,0xbbc5391b,0xb8153b60,0x3966ae91,0x3b37bbda,
  0x2a1639aa,0x3beaba2d,0xb3bab874,0xbb893b0d,0x3b8eba25,0xb9e3b27c,0xb4023bac,0x3bc6b99d,0xb8adb889,0xac063bb0,0x3974bb59,0xbbee3759,
  0xb8e53afb,0x3a85b98b,0xbb963742,0x3bffb19e,0xb72c3676,0xb84537dd,0xb8ea3899,0xb9823937,0xb9d63afe,0xb5233855,0x313b2d33,0x38e0b65f,
  0x3ae8b884,0x3b81bbf8,0x353ab999,0xb8302ef5,0x33a2ba29,0xbae13631,0xb9e73bf5,0x36e83219,0xbbfe39a6,0x30a63916,0x3bc3baa5,0xb55eb790,
  0x3546391f,0x396bbbd6,0xbbbf3487,0x338939b3,0x3a7eba97,0xbbfc346f,0x39da3654,0xb042bb1b,0xba54b7d2,0x38a339c5,0xb517bb21,0x27763be0,
  0xb93c3986,0xb89e38ee,0xb7e8384a,0xb6823737,0x3699b8f8,0xac38b1b6,0xb83a34e7,0xbaee39c0,0xb05b385f,0x3970b4cf,0x3bfcbb6c,0x38b2bb04,
  0xb0d7b77a,0xbbeb39af,0xb6c63b0a,0x39f4b263,0x36d23625,0x3adebba7,0xb8c1b24b,0xb9f03bf6,0xb954b4c3,0xb5813bdc,0x3becb907,0xb8b7b63c,
  0x3ace32ad,0xb52fba41,0xb5993c00,0x3aebba1d,0xbbb8af8b,0x3ac7366b,0xb941b933,0x368d3abd,0xba0d39c9,0xba893a4d,0xbaf43ac1,0xbb4f3b24,
  0x3b4aba45,0x3bfcbbdf,0x3acbbb9e,0x37feb990,0xbbed3ab3,0xb9df3ba1,0x2ba735f7,0x3a7ab7b2,0x3be8bb13,0x308db9a1,0xbb3f379b,0xb9583bd7,
  0xbb3d3b63,0x381a34ab,0x3a6fbbd8,0xb95dae5f,0x39f8bba3,0xbb833201,0x30743a39,0x3a76bb5e,0xb8353bd3,0x3b92b8fd,0xbb7fa311,0x38053929,
  0x3432bbf2,0xb8403b54,0x3a09ba15,0xbb4c3850,0xb50b35c8,0xb30f344b,0xafef3185,0xa6ad2cce,0xbbff3bb2,0xbb2c3bd2,0xb8a83a19,0xb02935df,
  0xb40eb1e8,0xbb453924,0xbb323c00,0xb3713902,0x3ad8bbf7,0xb3ebb60e,0xbbfe3a35,0xb5523aa2,0x39eb1648,0x38c7bbf6,0xbadb3232,0xb6dd3ba9,
  0xb6f43bf8,0x3bfeb865,0xb80fb7a6,0xb82a3c00,0xbbe531cf,0x394a37bd,0xa884bb6f,0xb8db3b9f,0xb010bbb3,0xb1533c00,0x3721bb9c,0xb97d3a90,
  0xbb983b76,0xbbce3bb5,0xbbf03be1,0xbbff3bfa,0x281fb463,0xb71532c6,0xba81392e,0xbbef3b71,0x3bbdbbdd,0x36afba21,0xb6ff217f,0xbbc83a3d,
  0x38252dfb,0x3bc0bb68,0x29b1b90c,0xbb8b387a,0xb9623c00,0x3a6bae2d,0x3820bbd9,0xbb3a349f,0xbb352dc9,0x294d3ab0,0x3ae5bb07,0xbad59fdb,
  0x3122bbde,0xba003b01,0x3bffb5eb,0xba5cb4db,0x3befb457,0xbbe3a51b,0x3b2a34f3,0xb9d2b894,0x39c939cd,0xba4db93c,0x3ac1389e,0xbb24b7e8,
  0x3b1e3946,0xbc00b340,0x3afeb426,0xb8553979,0x3bdd38b2,0xba21340e,0xa17fbb45,0x3a3d3b32,0x3bf53815,0xb2193966,0xbb13bb37,0x39a1b0d7,
  0x3b6536dd,0x37853b87,0xbaa9b3d3,0xb911bbe9,0x3a393581,0x3b5e3bec,0x2dc938b7,0xbab0b6f4,0x3889341a,0x3bb03a7e,0x3b593bfc,0x375939da,
  0x34f33153,0x38943721,0x3a49397d,0x3b733af1,0xb9863982,0x38eeba0d,0xb84a3a89,0x3737baf4,0xb74e3a04,0xa452bbcb,0x37c83bba,0xbabab9d6,
  0xb1e83a7a,0xb924bbbd,0x3c0036af,0xb90236ff,0x2e913ae1,0xbbdab9e7,0x377ab6e8,0x39af3be8,0x361a3b3a,0xbb10b56a,0xb86fbbc2,0x3a3130be,
  0x39073b83,0xb63c3074,0xbbf8ba76,0xb865bb35,0x3a973bbc,0x346f38ad,0xb654ac06,0xbb1bb974,0x3b9c3be3,0x3a903b2a,0x38f339d2,0x35d437f3,
  0x3b763682,0xbbb5b50b,0x3be1330f,0xbbfaafef,0x2d33bb94,0x365f3be4,0xba45ba58,0x3bdf3699,0xbbd4b371,0x3764b8d6,0x36483bfe,0xbbaeb94f,
  0x379b3beb,0xbbd7b6c6,0x2dfbb9f4,0x3b683ad8,0x39aa2a7a,0x3a2d3bfe,0xb87430a6,0xbb0dbbc3,0xbb07bbfe,0x1fdbb80f,0x3b16382a,0x3a9e3bfd,
  0xb2ad3042,0xba41b835,0xbc00bb92,0xba1dbb7f,0x3bfa3bcc,0x3bd03bfb,0x3afb3b7a,0x398b3a54,0xb5c83b4f,0x344bbb98,0xb1853bce,0x2ccebbf0,
  0x3bf93523,0xbb57313b,0x38f8b8e0,0xb1b63b4a,0xb294bbc8,0x3b183a60,0xbb5ca8e8,0x347bb9fc,0xbb0ab08d,0xb263bb3f,0x3bf73958,0xb60e3825,
  0x39a63bfd,0xb9162a16,0xbaa5bbea,0x3790b3ba,0x37a6a94d,0x3c003ae5,0x376f3ad5,0xb87fab43,0xbbd3bbee,0xb8fdbace,0x2311b52f,0x39293599,
  0x2d003328,0xb2deac6a,0xb7d2b5b1,0xb9c5b8e5,0x3bff26ad,0xbbf12c9c,0x3bcfb16c,0xbb9a343e,0xbb9e2c38,0x3990b83a,0xb4633aee,0xb2c6bbff,
  0x3a9bb109,0xad973ae8,0xb9b8bb81,0x3bf4353a,0xb90c33eb,0xb87abbfe,0x3ba53552,0x1cb63a73,0x3625b55e,0x3ba73b3d,0xb24b381a,0xbbf6ba6f,
  0xaec336bb,0xbb6ab8d1,0xba25bbe7,0x327cb546,0xb1cfb805,0x37bd3122,0x3b6f3a00,0x3b9f3bff,0x374238a3,0x319e3517,0xaf8b2776,0xb66bb432,
  0x25e43bff,0xafbdbbfb,0x32f73be2,0xb4ffbbb7,0xb4e7bbfc,0x39c03acb,0xbbb2b7fe,0x3bd2281f,0x38843be6,0xbbf8b80a,0x3999b58d,0x2ef53b90,
  0xba35bbc0,0x3aa229b1,0x34b73b8b,0xbc00b8bc,0x3b633b89,0xb4ab36d2,0xbbd8bade,0x2e5fb8c1,0xbbf5bb42,0xb602ba64,0x391f30f0,0x3bd63b8e,
  0x3bde3aeb,0x3b013be5,0x35eb394a,0xb4db2884,0xbb21ba85,0xbbe0bb96,0xbbf2bbff,0xbb54bbb8,0x3b52b5bc,0xbaf7372c,0x3a8cb845,0xba1138ea,
  0x392e3b2c,0xbb71b8a8,0x3bf23029,0xba9335a5,0xb85f3830,0xb4cfbbed,0x3b6c39df,0xbb042ba7,0xbbabba67,0x386ab576,0x391b3bfd,0xbb60b3a2,
  0x1648b95d,0x3bf63962,0x32323a6b,0xbba9b820,0x3bac396b,0x399d3bbf,0xb4c33389,0xbbdcb9f8,0x385a3a5c,0xaf273359,0xb9bcb70a,0xbbf9bb47,
  0xb933b840,0xbabdba09,0xbbb3bb4c,0xbc00bbef,0x36763b78,0xb7ddbb27,0x38993ac4,0xb937ba50,0xba193715,0x35dfba81,0x2f593bef,0xb88ebb7c,
  0xbab3bad1,0x3ba1305b,0xb5f73970,0xb7b2bbfc,0x3493b8cc,0x3aac3b85,0xba292ade,0xb631bbc5,0x3c0039f0,0x2e2d39eb,0xbbd9b8c7,0xb49fbadb,
  0x348739e3,0xb9b3b402,0xbba3bbc6,0xb201b954,0xbab6b8db,0xbbf3bbc9,0xb994bb2f,0xad65b6a4,0xba15bac7,0xb850b941,0xb457b68d,0x251bb010,
  0xb9cfbb16,0x30ac2a31,0x3b9c3bf1,0xb493ae2d,0xb76fb8b4,0x35a133e3,0x3a1d3afe,0xb902b76f,0xb3e3b5a1,0x38b4376f,0x376f3902,0xbafeba1d,
  0xaa31b0ac,0x3b1639cf,0x2e2d3493,0xbbf1bb9c,0xb956ba74,0x305f29cc,0x3b633bd2,0xb44badc9,0xb6e7b859,0x353f335e,0x39d23ab6,0xb8bcb6ff,
  0xb35eb53f,0x385936e7,0x36ff38bc,0xbab6b9d2,0xa9ccb05f,0x3a743956,0x2dc9344b,0xbbd2bb63,0xb8e3b9de,0x30122967,0x3b1e3ba1,0xb402ad65,
  0xb662b801,0x34de32da,0x39823a67,0xb874b68d,0xb2dab4de,0x38013662,0x368d3874,0xba67b982,0xa967b012,0x39de38e3,0x2d653402,0xbba1bb1e,
  0xb876b952,0x2f8c2902,0x3ace3b60,0xb371ad00,0xb5e1b758,0x347e3257,0x392e3a11,0xb82ab61a,0xb257b47e,0x375835e1,0x361a382a,0xba11b92e,
  0xa902af8c,0x39523876,0x2d003371,0xbb60bace,0xb80db8ce,0x2ef3289e,0x3a733b10,0xb2deac9c,0xb562b6b3,0x342031d5,0x38d639b3,0xb7bdb5a5,
  0xb1d5b420,0x36b33562,0x35a537bd,0xb9b3b8d6,0xa89eaef3,0x38ce380d,0x2c9c32de,0xbb10ba73,0xb750b851,0x2e5a2839,0x3a0d3ab0,0xb24bac38,
  0xb4e5b613,0x33863153,0x387a394f,0xb721b52f,0xb153b386,0x361334e5,0x352f3721,0xb94fb87a,0xa839ae5a,0x38513750,0x2c38324b,0xbab0ba0d,
  0xb68eb7b4,0x2dc227a9,0x399d3a41,0xb1b6aba7,0xb46ab577,0x32cd30d2,0x381a38e5,0xb682b4b7,0xb0d2b2cd,0x3577346a,0x34b73682,0xb8e5b81a,
  0xa7a9adc2,0x37b4368e,0x2ba731b6,0xba41b99d,0xb5d2b6d1,0x2d2a26e0,0x392439c5,0xb122aade,0xb3e3b4de,0x32163052,0x376f3874,0xb5dfb43e,
  0xb052b216,0x34de33e3,0x343e35df,0xb874b76f,0xa6e0ad2a,0x36d135d2,0x2ade3122,0xb9c5b924,0xb51cb5f6,0x2c932617,0x38a3393c,0xb08daa16,
  0xb2f4b448,0x31602fa5,0x36a437fe,0xb53ab389,0xafa5b160,0x344832f4,0x3389353a,0xb7feb6a4,0xa617ac93,0x35f6351c,0x2a16308d,0xb93cb8a3,
  0xb46ab523,0x2bf6254d,0x381a38a8,0xafefa94d,0xb209b36b,0x30ac2ea7,0x35d4370a,0xb493b294,0xaea7b0ac,0x336b3209,0x32943493,0xb70ab5d4,
  0xa54dabf6,0x3523346a,0x294d2fef,0xb8a8b81a,0xb378b456,0x2ac82484,0x3715380a,0xaec3a884,0xb120b24a,0x2ff22da9,0x34ff360e,0xb3d3b19e,
  0xada9aff2,0x324a3120,0x319e33d3,0xb60eb4ff,0xa484aac8,0x34563378,0x28842ec3,0xb80ab715,0xb223b31c,0x29992376,0x35eb36c6,0xad97a776,
  0xb039b12d,0x2e8d2cac,0x3426350b,0xb27cb0a6,0xacacae8d,0x312d3039,0x30a6327c,0xb50bb426,0xa376a999,0x331c3223,0x27762d97,0xb6c6b5eb,
  0xb0d2b194,0x286b21e4,0x34b7356a,0xac6aa5e4,0xaea7b012,0x2d2a2b5f,0x32943402,0xb122af59,0xab5fad2a,0x30122ea7,0x2f593122,0xb402b294,
  0xa1e4a86b,0x319430d2,0x25e42c6a,0xb56ab4b7,0xaf0cb012,0x267b2052,0x32f73402,0xaa7aa452,0xacdeadf5,0x2b912967,0x30d731e8,0xaf8bad65,
  0xa967ab91,0x2df52cde,0x2d652f8b,0xb1e8b0d7,0xa052a67b,0x30122f0c,0x24522a7a,0xb402b2f7,0xac79ad2a,0x24201d7f,0x30743122,0xa81fa17f,
  0xaa31ab91,0x28d026e0,0x2e2d2f8b,0xacceaade,0xa6e0a8d0,0x2b912a31,0x2ade2cce,0xaf8bae2d,0x9d7fa420,0x2d2a2c79,0x217f281f,0xb122b074,
  0xa7a9a86b,0x1f1218b6,0x2ba72c6a,0xa3119cb6,0xa54da67b,0x242021e4,0x294d2a7a,0xa81fa5e4,0xa1e4a420,0x267b254d,0x25e4281f,0xaa7aa94d,
  0x98b69f12,0x286b27a9,0x1cb62311,0xac6aaba7,0x211b21e4,0x98b69248,0xa51ba5e4,0x1cb61648,0x1f122052,0x9d7f9bdb,0xa311a452,0x217f1fdb,
  0x1bdb1d7f,0xa0529f12,0x9fdba17f,0x24522311,0x124818b6,0xa1e4a11b,0x96489cb6,0x25e4251b,0x2a632b5f,0xa1e49bdb,0xae5faf59,0x25e41fdb,
  0x286b2967,0xa6e0a4e9,0xac6aad65,0x2ade28e8,0x24e926e0,0xa967a86b,0xa8e8aade,0x2d652c6a,0x1bdb21e4,0xab5faa63,0x9fdba5e4,0x2f592e5f,
  0x2dc22ea7,0xa54d9f12,0xb1b6b294,0x294d2311,0x2bf62cde,0xaa31a86b,0xafefb0d7,0x2e2d2c6a,0x286b2a31,0xacdeabf6,0xac6aae2d,0x30d72fef,
  0x1f12254d,0xaea7adc2,0xa311a94d,0x329431b6,0x302c30d2,0xa7a9a11b,0xb41ab4b7,0x2ba7251b,0x2dc22f0c,0xac79aa63,0xb1b6b2f7,0x30742e5f,
  0x2a632c79,0xaf0cadc2,0xae5fb074,0x32f731b6,0x211b27a9,0xb0d2b02c,0xa51baba7,0x34b7341a,0x317a3257,0xa902a2ad,0xb552b61a,0x2d0026ad,
  0x2f8c309f,0xaddcac2e,0xb371b487,0x31cf3029,0x2c2e2ddc,0xb09faf8c,0xb029b1cf,0x34873371,0x22ad2902,0xb257b17a,0xa6adad00,0x361a3552,
  0x32cd33e3,0xaa31a420,0xb682b76f,0x2e2d281f,0x30ac31bb,0xaf3fad2a,0xb493b58d,0x33283122,0x2d2a2f3f,0xb1bbb0ac,0xb122b328,0x358d3493,
  0x24202a31,0xb3e3b2cd,0xa81fae2d,0x376f3682,0x341334bc,0xab5fa4e9,0xb7a6b85a,0x2f5928e8,0x319432da,0xb052ae28,0xb56ab68d,0x343e3219,
  0x2e283052,0xb2dab194,0xb219b43e,0x368d356a,0x24e92b5f,0xb4bcb413,0xa8e8af59,0x385a37a6,0x34c3358c,0xac47a5b2,0xb85fb8f3,0x304229b1,
  0x327e33fd,0xb106af26,0xb63cb785,0x34e7330f,0x2f263106,0xb3fdb27e,0xb30fb4e7,0x3785363c,0x25b22c47,0xb58cb4c3,0xa9b1b042,0x38f3385f,
  0x35773662,0xacdea67b,0xb8e5b982,0x30d72a7a,0x336b3493,0xb1bbb012,0xb70ab83a,0x358d3402,0x301231bb,0xb493b36b,0xb402b58d,0x383a370a,
  0x267b2cde,0xb662b577,0xaa7ab0d7,0x398238e5,0x36303741,0xad76a744,0xb962ba04,0x316c2b43,0x342e352a,0xb271b092,0xb7d2b8ad,0x3631347b,
  0x30923271,0xb52ab42e,0xb47bb631,0x38ad37d2,0x27442d76,0xb741b630,0xab43b16c,0x3a043962,0x36ee3815,0xae0ea807,0xb9d6ba7a,0x32012c06,
  0x34a735c4,0xb329b113,0xb84ab91b,0x36d234f3,0x31133329,0xb5c4b4a7,0xb4f3b6d2,0x391b384a,0x28072e0e,0xb815b6ee,0xac06b201,0x3a7a39d6,
  0x37b4388e,0xaea7a86b,0xba41bae1,0x32942c6a,0x35233662,0xb3e3b194,0xb8a8b982,0x376f356a,0x319433e3,0xb662b523,0xb56ab76f,0x398238a8,
  0x286b2ea7,0xb88eb7b4,0xac6ab294,0x3ae13a41,0x3841390f,0xaf3fa8d0,0xbaa2bb3a,0x33282cce,0x35a13705,0xb44fb216,0xb902b9e3,0x380535df,
  0x3216344f,0xb705b5a1,0xb5dfb805,0x39e33902,0x28d02f3f,0xb90fb841,0xacceb328,0x3b3a3aa2,0x38ac3997,0xafd8a935,0xbaf7bb83,0x33ba2d33,
  0x362137ac,0xb4aeb298,0xb958ba3d,0x38503654,0x329834ae,0xb7acb621,0xb654b850,0x3a3d3958,0x29352fd8,0xb997b8ac,0xad33b3ba,0x3b833af7,
  0x391c3a28,0xb039a999,0xbb42bbbc,0x34262d97,0x36a4382d,0xb50eb31c,0xb9aaba90,0x389936c6,0x331c350e,0xb82db6a4,0xb6c6b899,0x3a9039aa,
  0x29993039,0xba28b91c,0xad97b426,0x3bbc3b42,0x39923ac3,0xb085a9fe,0xbb81bbe3,0x346f2dfb,0x372a3886,0xb570b3a0,0xb9f8badb,0x38e03737,
  0x33a03570,0xb886b72a,0xb737b8e0,0x3adb39f8,0x29fe3085,0xbac3b992,0xadfbb46f,0x3be33b81,
};

#define PROF(slot) do {} while (0)
#define PROF_DUMP() do {} while (0)
#define PROFA(slot, dep) do {} while (0)
#define PROF3(slot) do {} while (0)
#define PROF2(slot) do {} while (0)

__device__ __forceinline__ uint32_t smem_u32(const void* p) { return (uint32_t)__cvta_generic_to_shared(p); }

__device__ __forceinline__ void mbar_init(uint32_t a, uint32_t c) {
  asm volatile("mbarrier.init.shared::cta.b64 [%0], %1;\n" ::"r"(a), "r"(c) : "memory");
}
__device__ __forceinline__ void mbar_expect_tx(uint32_t a, uint32_t bytes) {
  asm volatile("mbarrier.arrive.expect_tx.shared::cta.b64 _, [%0], %1;\n" ::"r"(a), "r"(bytes) : "memory");
}
__device__ __forceinline__ void mbar_arrive_cluster(uint32_t cluster_addr) {
  asm volatile("mbarrier.arrive.shared::cluster.b64 _, [%0];\n" ::"r"(cluster_addr) : "memory");
}
__device__ __forceinline__ void mbar_arrive_cluster_n(uint32_t cluster_addr, uint32_t n) {
  asm volatile("mbarrier.arrive.shared::cluster.b64 _, [%0], %1;\n" ::"r"(cluster_addr), "r"(n) : "memory");
}
__device__ __forceinline__ bool mbar_try(uint32_t a, uint32_t parity) {
  uint32_t ok;
  asm volatile("{\n.reg .pred p;\nmbarrier.try_wait.parity.shared::cta.b64 p, [%1], %2;\nselp.u32 %0, 1, 0, p;\n}\n"
               : "=r"(ok) : "r"(a), "r"(parity) : "memory");
  return ok;
}
__device__ __forceinline__ void mbar_wait(uint32_t a, uint32_t parity) {
  if (mbar_try(a, parity)) return;
#pragma unroll 1
  for (int n = 0; n < SPIN_LIMIT; n++)
    if (mbar_try(a, parity)) break;
}
__device__ __forceinline__ bool elect_one() {
  uint32_t p;
  asm volatile("{\n.reg .pred P;\nelect.sync _|P, 0xffffffff;\nselp.u32 %0, 1, 0, P;\n}\n" : "=r"(p));
  return p;
}
__device__ __forceinline__ uint32_t mapa(uint32_t a, uint32_t rank) {
  uint32_t r;
  asm volatile("mapa.shared::cluster.u32 %0, %1, %2;\n" : "=r"(r) : "r"(a), "r"(rank));
  return r;
}
__device__ __forceinline__ void nb_sync(int id, int n) { asm volatile("bar.sync %0, %1;\n" ::"r"(id), "r"(n) : "memory"); }
__device__ __forceinline__ void nb_arrive(int id, int n) { asm volatile("bar.arrive %0, %1;\n" ::"r"(id), "r"(n) : "memory"); }
__device__ __forceinline__ void cluster_sync_all() {
  asm volatile("barrier.cluster.arrive.relaxed.aligned;\nbarrier.cluster.wait.aligned;\n" ::: "memory");
}
__device__ __forceinline__ void fence_async_smem() { asm volatile("fence.proxy.async.shared::cta;\n" ::: "memory"); }
__device__ __forceinline__ void fence_async_all() { asm volatile("fence.proxy.async.global;\n" ::: "memory"); }

__device__ __forceinline__ void tma_load_3d(uint32_t dst, const CUtensorMap* tm, uint32_t bar, int c0, int c1, int c2) {
  asm volatile(
      "cp.async.bulk.tensor.3d.shared::cluster.global.mbarrier::complete_tx::bytes [%0], [%1, {%3, %4, %5}], [%2];\n"
      ::"r"(dst), "l"(tm), "r"(bar), "r"(c0), "r"(c1), "r"(c2) : "memory");
}
__device__ __forceinline__ void tma_load_4d(uint32_t dst, const CUtensorMap* tm, uint32_t bar, int c0, int c1, int c2, int c3) {
  asm volatile(
      "cp.async.bulk.tensor.4d.shared::cluster.global.mbarrier::complete_tx::bytes [%0], [%1, {%3, %4, %5, %6}], [%2];\n"
      ::"r"(dst), "l"(tm), "r"(bar), "r"(c0), "r"(c1), "r"(c2), "r"(c3) : "memory");
}
__device__ __forceinline__ void tma_load_3d_mc(uint32_t dst, const CUtensorMap* tm, uint32_t bar, int c0, int c1, int c2) {
  asm volatile(
      "cp.async.bulk.tensor.3d.shared::cluster.global.mbarrier::complete_tx::bytes.multicast::cluster [%0], [%1, {%3, %4, %5}], [%2], %6;\n"
      ::"r"(dst), "l"(tm), "r"(bar), "r"(c0), "r"(c1), "r"(c2), "h"((uint16_t)3) : "memory");
}
__device__ __forceinline__ void bulk_load(uint32_t dst, const void* src, uint32_t bytes, uint32_t bar) {
  asm volatile("cp.async.bulk.shared::cluster.global.mbarrier::complete_tx::bytes [%0], [%1], %2, [%3];\n"
               ::"r"(dst), "l"(src), "r"(bytes), "r"(bar) : "memory");
}
__device__ __forceinline__ void tma_store_3d(const CUtensorMap* tm, uint32_t src, int c0, int c1, int c2) {
  asm volatile("cp.async.bulk.tensor.3d.global.shared::cta.bulk_group [%0, {%2, %3, %4}], [%1];\n"
               ::"l"(tm), "r"(src), "r"(c0), "r"(c1), "r"(c2) : "memory");
}
__device__ __forceinline__ void bulk_commit() { asm volatile("cp.async.bulk.commit_group;\n" ::: "memory"); }
__device__ __forceinline__ void bulk_wait0() { asm volatile("cp.async.bulk.wait_group 0;\n" ::: "memory"); }
__device__ __forceinline__ void prefetch_tmap(const CUtensorMap* tm) {
  asm volatile("prefetch.tensormap [%0];\n" ::"l"(tm) : "memory");
}

__device__ __forceinline__ void wg_fence() { asm volatile("wgmma.fence.sync.aligned;\n" ::: "memory"); }
__device__ __forceinline__ void wg_commit() { asm volatile("wgmma.commit_group.sync.aligned;\n" ::: "memory"); }
template <int N> __device__ __forceinline__ void wg_wait() {
  asm volatile("wgmma.wait_group.sync.aligned %0;\n" ::"n"(N) : "memory");
}
__device__ __forceinline__ uint64_t mkdesc(uint32_t addr, uint32_t lbo, uint32_t sbo, uint32_t swz) {
  return (uint64_t)((addr & 0x3FFFF) >> 4) | ((uint64_t)(lbo >> 4) << 16) | ((uint64_t)(sbo >> 4) << 32) |
         ((uint64_t)swz << 62);
}

#define R4(d, o) "+f"(d[o + 0]), "+f"(d[o + 1]), "+f"(d[o + 2]), "+f"(d[o + 3])
#define R8(d, o) R4(d, o), R4(d, o + 4)
#define R16(d, o) R8(d, o), R8(d, o + 8)
#define R32(d, o) R16(d, o), R16(d, o + 16)
#define R64(d, o) R32(d, o), R32(d, o + 32)

__device__ __forceinline__ void wgmma_n192(float (&d)[96], uint64_t da, uint64_t db, uint32_t acc) {
  asm volatile(
      "{\n.reg .pred p;\nsetp.ne.u32 p, %98, 0;\n"
      "wgmma.mma_async.sync.aligned.m64n192k16.f32.bf16.bf16 "
      "{%0,%1,%2,%3,%4,%5,%6,%7,%8,%9,%10,%11,%12,%13,%14,%15,%16,%17,%18,%19,%20,%21,%22,%23,%24,%25,%26,%27,%28,%29,%30,%31,"
      "%32,%33,%34,%35,%36,%37,%38,%39,%40,%41,%42,%43,%44,%45,%46,%47,%48,%49,%50,%51,%52,%53,%54,%55,%56,%57,%58,%59,%60,%61,%62,%63,"
      "%64,%65,%66,%67,%68,%69,%70,%71,%72,%73,%74,%75,%76,%77,%78,%79,%80,%81,%82,%83,%84,%85,%86,%87,%88,%89,%90,%91,%92,%93,%94,%95}, "
      "%96, %97, p, 1, 1, 0, 1;\n}\n"
      : R64(d, 0), R32(d, 64)
      : "l"(da), "l"(db), "r"(acc));
}
__device__ __forceinline__ void wgmma_n128(float (&d)[64], uint64_t da, uint64_t db, uint32_t acc) {
  asm volatile(
      "{\n.reg .pred p;\nsetp.ne.u32 p, %66, 0;\n"
      "wgmma.mma_async.sync.aligned.m64n128k16.f32.bf16.bf16 "
      "{%0,%1,%2,%3,%4,%5,%6,%7,%8,%9,%10,%11,%12,%13,%14,%15,%16,%17,%18,%19,%20,%21,%22,%23,%24,%25,%26,%27,%28,%29,%30,%31,"
      "%32,%33,%34,%35,%36,%37,%38,%39,%40,%41,%42,%43,%44,%45,%46,%47,%48,%49,%50,%51,%52,%53,%54,%55,%56,%57,%58,%59,%60,%61,%62,%63}, "
      "%64, %65, p, 1, 1, 0, 1;\n}\n"
      : R64(d, 0)
      : "l"(da), "l"(db), "r"(acc));
}
#define WG128(C, ACC)                                                                                                      \
  asm volatile(                                                                                                            \
      "{\n.reg .b64 a, b;\nmov.b64 a, {%64, %66};\nmov.b64 b, {%65, %66};\n"                                               \
      "wgmma.mma_async.sync.aligned.m64n128k16.f32.bf16.bf16 "                                                             \
      "{%0,%1,%2,%3,%4,%5,%6,%7,%8,%9,%10,%11,%12,%13,%14,%15,%16,%17,%18,%19,%20,%21,%22,%23,%24,%25,%26,%27,%28,%29,%30,%31," \
      "%32,%33,%34,%35,%36,%37,%38,%39,%40,%41,%42,%43,%44,%45,%46,%47,%48,%49,%50,%51,%52,%53,%54,%55,%56,%57,%58,%59,%60,%61," \
      "%62,%63}, a, b, " ACC ", 1, 1, 0, 1;\n}\n"                                                                          \
      : Z16(C, d, 0), Z16(C, d, 16), Z16(C, d, 32), Z16(C, d, 48)                                                          \
      : "r"(da), "r"(db), "r"(0x40000040))
#define Z4(C, d, o) C(d[o + 0]), C(d[o + 1]), C(d[o + 2]), C(d[o + 3])
#define Z16(C, d, o) Z4(C, d, o), Z4(C, d, o + 4), Z4(C, d, o + 8), Z4(C, d, o + 12)
__device__ __forceinline__ void wgmma_n128z(float (&d)[64], uint32_t da, uint32_t db) { WG128("=f", "0"); }
__device__ __forceinline__ void wgmma_n128a(float (&d)[64], uint32_t da, uint32_t db) { WG128("+f", "1"); }
template <int N> __device__ __forceinline__ void fence_regs(float (&d)[N]) {
#pragma unroll
  for (int i = 0; i < N; i++) asm volatile("" : "+f"(d[i])::"memory");
}

__device__ __forceinline__ void mma16816(float (&d)[4], uint32_t a0, uint32_t a1, uint32_t a2, uint32_t a3, uint32_t b0,
                                         uint32_t b1) {
  asm("mma.sync.aligned.m16n8k16.row.col.f32.bf16.bf16.f32 {%0,%1,%2,%3}, {%4,%5,%6,%7}, {%8,%9}, {%0,%1,%2,%3};\n"
      : "+f"(d[0]), "+f"(d[1]), "+f"(d[2]), "+f"(d[3])
      : "r"(a0), "r"(a1), "r"(a2), "r"(a3), "r"(b0), "r"(b1));
}
__device__ __forceinline__ void mma16816_z(float (&d)[4], uint32_t a0, uint32_t a1, uint32_t a2, uint32_t a3, uint32_t b0,
                                           uint32_t b1) {
  asm("mma.sync.aligned.m16n8k16.row.col.f32.bf16.bf16.f32 {%0,%1,%2,%3}, {%4,%5,%6,%7}, {%8,%9}, {%10,%10,%10,%10};\n"
      : "=f"(d[0]), "=f"(d[1]), "=f"(d[2]), "=f"(d[3])
      : "r"(a0), "r"(a1), "r"(a2), "r"(a3), "r"(b0), "r"(b1), "f"(0.f));
}
__device__ __forceinline__ void ldsm4t(uint32_t (&r)[4], uint32_t a) {
  asm volatile("ldmatrix.sync.aligned.m8n8.x4.trans.shared.b16 {%0,%1,%2,%3}, [%4];\n"
               : "=r"(r[0]), "=r"(r[1]), "=r"(r[2]), "=r"(r[3]) : "r"(a) : "memory");
}
__device__ __forceinline__ void ldsm2t(uint32_t& r0, uint32_t& r1, uint32_t a) {
  asm volatile("ldmatrix.sync.aligned.m8n8.x2.trans.shared.b16 {%0,%1}, [%2];\n" : "=r"(r0), "=r"(r1) : "r"(a) : "memory");
}
__device__ __forceinline__ void st_async128(uint32_t a, uint32_t bar, uint32_t x, uint32_t y, uint32_t z, uint32_t w) {
  asm volatile("st.async.weak.shared::cluster.mbarrier::complete_tx::bytes.v4.b32 [%0], {%2,%3,%4,%5}, [%1];\n"
               ::"r"(a), "r"(bar), "r"(x), "r"(y), "r"(z), "r"(w) : "memory");
}
__device__ __forceinline__ void mbar_arrive(uint32_t a) {
  asm volatile("mbarrier.arrive.shared::cta.b64 _, [%0];\n" ::"r"(a) : "memory");
}
__device__ __forceinline__ void stsm4(uint32_t a, uint32_t r0, uint32_t r1, uint32_t r2, uint32_t r3) {
  asm volatile("stmatrix.sync.aligned.m8n8.x4.shared.b16 [%0], {%1,%2,%3,%4};\n"
               ::"r"(a), "r"(r0), "r"(r1), "r"(r2), "r"(r3) : "memory");
}
__device__ __forceinline__ void stsm4t(uint32_t a, uint32_t r0, uint32_t r1, uint32_t r2, uint32_t r3) {
  asm volatile("stmatrix.sync.aligned.m8n8.x4.trans.shared.b16 [%0], {%1,%2,%3,%4};\n"
               ::"r"(a), "r"(r0), "r"(r1), "r"(r2), "r"(r3) : "memory");
}
__device__ __forceinline__ uint2 lds64(uint32_t a) {
  uint2 v;
  asm volatile("ld.shared.v2.u32 {%0,%1}, [%2];\n" : "=r"(v.x), "=r"(v.y) : "r"(a));
  return v;
}
__device__ __forceinline__ uint4 lds128(uint32_t a) {
  uint4 v;
  asm volatile("ld.shared.v4.u32 {%0,%1,%2,%3}, [%4];\n" : "=r"(v.x), "=r"(v.y), "=r"(v.z), "=r"(v.w) : "r"(a) : "memory");
  return v;
}
__device__ __forceinline__ void sts128(uint32_t a, uint32_t x, uint32_t y, uint32_t z, uint32_t w) {
  asm volatile("st.shared.v4.u32 [%0], {%1,%2,%3,%4};\n" ::"r"(a), "r"(x), "r"(y), "r"(z), "r"(w) : "memory");
}
__device__ __forceinline__ void sts64(uint32_t a, uint32_t x, uint32_t y) {
  asm volatile("st.shared.v2.u32 [%0], {%1,%2};\n" ::"r"(a), "r"(x), "r"(y) : "memory");
}
__device__ __forceinline__ uint32_t pack_bf16(float lo, float hi) {
  uint32_t r;
  asm("cvt.rn.bf16x2.f32 %0, %1, %2;\n" : "=r"(r) : "f"(hi), "f"(lo));
  return r;
}
__device__ __forceinline__ uint32_t bmul2(uint32_t a, uint32_t b) {
  uint32_t r;
  asm("mul.rn.bf16x2 %0, %1, %2;\n" : "=r"(r) : "r"(a), "r"(b));
  return r;
}
__device__ __forceinline__ uint32_t bmax2(uint32_t a, uint32_t b) {
  uint32_t r;
  asm("max.bf16x2 %0, %1, %2;\n" : "=r"(r) : "r"(a), "r"(b));
  return r;
}
__device__ __forceinline__ uint32_t bfma2(uint32_t a, uint32_t b, uint32_t c) {
  uint32_t r;
  asm("fma.rn.bf16x2 %0, %1, %2, %3;\n" : "=r"(r) : "r"(a), "r"(b), "r"(c));
  return r;
}
__device__ __forceinline__ uint32_t badd2(uint32_t a, uint32_t b) {
  uint32_t r;
  asm("add.rn.bf16x2 %0, %1, %2;\n" : "=r"(r) : "r"(a), "r"(b));
  return r;
}
__device__ __forceinline__ void prefetch_l2(const void* p) { asm volatile("prefetch.global.L2 [%0];\n" ::"l"(p)); }
__device__ __forceinline__ void cp_async16n(uint32_t dst, const void* src) {
  asm volatile("cp.async.cg.shared.global [%0], [%1], 16;\n" ::"r"(dst), "l"(src) : "memory");
}
__device__ __forceinline__ void cp_async16(uint32_t dst, const void* src, uint32_t srcbytes) {
  asm volatile("cp.async.cg.shared.global.L2::256B [%0], [%1], 16, %2;\n" ::"r"(dst), "l"(src), "r"(srcbytes) : "memory");
}
__device__ __forceinline__ uint32_t ld_acquire(const uint32_t* p) {
  uint32_t v;
  asm volatile("ld.acquire.gpu.global.u32 %0, [%1];\n" : "=r"(v) : "l"(p) : "memory");
  return v;
}
__device__ __forceinline__ uint32_t ld_relaxed(const uint32_t* p) {
  uint32_t v;
  asm volatile("ld.relaxed.gpu.global.u32 %0, [%1];\n" : "=r"(v) : "l"(p) : "memory");
  return v;
}
__device__ __forceinline__ void st_release(uint32_t* p, uint32_t v) {
  asm volatile("st.release.gpu.global.u32 [%0], %1;\n" ::"l"(p), "r"(v) : "memory");
}
__device__ __forceinline__ void wait_flag(const uint32_t* p, uint32_t want) {
  int n = 0;
  while (ld_acquire(p) != want && ++n < SPIN_LIMIT) {}
}

struct Params {
  const __nv_bfloat16* x;
  const __nv_bfloat16* w;
  const __nv_bfloat16* q;
  const __nv_bfloat16* k;
  const __nv_bfloat16* v;
  const __nv_bfloat16* shift_k;
  const __nv_bfloat16* ssm_k;
  const __nv_bfloat16* ssm_D;
  const __nv_bfloat16* wo;
  __nv_bfloat16* out;
  uint32_t zero;
};

__device__ __forceinline__ uint32_t lds32(uint32_t a) {
  uint32_t v;
  asm volatile("ld.shared.u32 %0, [%1];\n" : "=r"(v) : "r"(a));
  return v;
}
__device__ __forceinline__ float bf_lo(uint32_t v) {
  uint32_t r;
  asm("prmt.b32 %0, %1, 0, 0x1044;\n" : "=r"(r) : "r"(v));
  return __uint_as_float(r);
}
__device__ __forceinline__ float bf_hi(uint32_t v) { return __uint_as_float(v & 0xffff0000u); }
__device__ __forceinline__ float ex2(float x) {
  float r;
  asm("ex2.approx.ftz.f32 %0, %1;\n" : "=f"(r) : "f"(x));
  return r;
}
__device__ __forceinline__ float rcp(float x) {
  float r;
  asm("rcp.approx.ftz.f32 %0, %1;\n" : "=f"(r) : "f"(x));
  return r;
}

#define Q4(c, d, o) c(d[o + 0]), c(d[o + 1]), c(d[o + 2]), c(d[o + 3])
#define Q8(c, d, o) Q4(c, d, o), Q4(c, d, o + 4)
#define Q16(c, d, o) Q8(c, d, o), Q8(c, d, o + 8)
#define Q32(c, d) Q16(c, d, 0), Q16(c, d, 16)
#define L8 "{%0,%1,%2,%3,%4,%5,%6,%7}"
#define L16 "{%0,%1,%2,%3,%4,%5,%6,%7,%8,%9,%10,%11,%12,%13,%14,%15}"
#define L32 "{%0,%1,%2,%3,%4,%5,%6,%7,%8,%9,%10,%11,%12,%13,%14,%15,%16,%17,%18,%19,%20,%21,%22,%23,%24,%25,%26,%27,%28,%29,%30,%31}"
__device__ __forceinline__ void fft_rows(uint32_t (&d)[32], const uint32_t (&a)[2][4], uint64_t db) {
  asm volatile("wgmma.mma_async.sync.aligned.m64n128k16.f16.f16.f16 " L32 ", {%32,%33,%34,%35}, %36, 0, 1, 1, 1;\n"
               : Q32("=r", d) : "r"(a[0][0]), "r"(a[0][1]), "r"(a[0][2]), "r"(a[0][3]), "l"(db));
  asm volatile("wgmma.mma_async.sync.aligned.m64n128k16.f16.f16.f16 " L32 ", {%32,%33,%34,%35}, %36, 1, 1, 1, 1;\n"
               : Q32("+r", d) : "r"(a[1][0]), "r"(a[1][1]), "r"(a[1][2]), "r"(a[1][3]), "l"(db + 64));
}
template <int INV> __device__ __forceinline__ void fft_cols(uint32_t (&d)[8], const uint32_t (&a)[2][4], uint64_t db) {
  asm volatile("wgmma.mma_async.sync.aligned.m64n32k16.f16.f16.f16 " L8 ", {%8,%9,%10,%11}, %12, 0, 1, 1, %13;\n"
               : Q8("=r", d, 0) : "r"(a[0][0]), "r"(a[0][1]), "r"(a[0][2]), "r"(a[0][3]), "l"(db), "n"(INV));
  asm volatile("wgmma.mma_async.sync.aligned.m64n32k16.f16.f16.f16 " L8 ", {%8,%9,%10,%11}, %12, 1, 1, 1, %13;\n"
               : Q8("+r", d, 0) : "r"(a[1][0]), "r"(a[1][1]), "r"(a[1][2]), "r"(a[1][3]), "l"(db + (INV ? 16 : 64)), "n"(INV));
}
__device__ __forceinline__ void fft_back(float (&d)[16], uint64_t da, uint64_t db) {
  asm volatile("wgmma.mma_async.sync.aligned.m64n32k16.f32.f16.f16 " L16 ", %16, %17, 0, 1, 1, 1, 1;\n"
               : Q16("=f", d, 0) : "l"(da), "l"(db));
#pragma unroll
  for (int i = 1; i < 4; i++)
    asm volatile("wgmma.mma_async.sync.aligned.m64n32k16.f32.f16.f16 " L16 ", %16, %17, 1, 1, 1, 1, 1;\n"
                 : Q16("+f", d, 0) : "l"(da + 32 * i), "l"(db + 64 * i));
}
__device__ __forceinline__ uint32_t hmul2(uint32_t a, uint32_t b) {
  uint32_t r;
  asm("mul.rn.f16x2 %0, %1, %2;\n" : "=r"(r) : "r"(a), "r"(b));
  return r;
}
__device__ __forceinline__ uint32_t hadd2(uint32_t a, uint32_t b) {
  uint32_t r;
  asm("add.rn.f16x2 %0, %1, %2;\n" : "=r"(r) : "r"(a), "r"(b));
  return r;
}
__device__ __forceinline__ uint32_t hneg2(uint32_t a) {
  uint32_t r;
  asm("neg.f16x2 %0, %1;\n" : "=r"(r) : "r"(a));
  return r;
}
__device__ __forceinline__ uint32_t hfma2(uint32_t a, uint32_t b, uint32_t c) {
  uint32_t r;
  asm("fma.rn.f16x2 %0, %1, %2, %3;\n" : "=r"(r) : "r"(a), "r"(b), "r"(c));
  return r;
}
__device__ __forceinline__ uint32_t pack_f16(float lo, float hi) {
  uint32_t r;
  asm("cvt.rn.f16x2.f32 %0, %1, %2;\n" : "=r"(r) : "f"(hi), "f"(lo));
  return r;
}
__device__ __forceinline__ uint32_t bmaxabs2(uint32_t a, uint32_t b) {
  uint32_t r;
  asm("max.xorsign.abs.bf16x2 %0, %1, %2;\n" : "=r"(r) : "r"(a), "r"(b));
  return r;
}
struct C2 { uint32_t r, i; };
__device__ __forceinline__ C2 cmul(C2 a, C2 b) {
  return C2{hfma2(a.r, b.r, hneg2(hmul2(a.i, b.i))), hfma2(a.r, b.i, hmul2(a.i, b.r))};
}
__device__ __forceinline__ C2 cfma(C2 a, C2 b, C2 c) {
  return C2{hfma2(a.r, b.r, hfma2(hneg2(a.i), b.i, c.r)), hfma2(a.r, b.i, hfma2(a.i, b.r, c.i))};
}
__device__ __forceinline__ C2 crot(C2 z, C2 t) {
  const uint32_t r = hfma2(t.r, z.i, z.r), i = hfma2(t.i, r, z.i);
  return C2{hfma2(t.r, i, r), i};
}
__device__ __forceinline__ C2 cget(const uint32_t (&e)[8], int j, int b) { return C2{e[4 * j + b], e[4 * j + 2 + b]}; }
template <int N> __device__ __forceinline__ void fence_regs(uint32_t (&d)[N]) {
#pragma unroll
  for (int i = 0; i < N; i++) asm volatile("" : "+r"(d[i])::"memory");
}
__device__ __forceinline__ void ldsm4(uint32_t (&r)[4], uint32_t a) {
  asm volatile("ldmatrix.sync.aligned.m8n8.x4.shared.b16 {%0,%1,%2,%3}, [%4];\n"
               : "=r"(r[0]), "=r"(r[1]), "=r"(r[2]), "=r"(r[3]) : "r"(a) : "memory");
}

__device__ __forceinline__ uint32_t movm(uint32_t a) {
  uint32_t r;
  asm volatile("movmatrix.sync.aligned.m8n8.trans.b16 %0, %1;\n" : "=r"(r) : "r"(a));
  return r;
}
template <int C0, int H, bool T> __device__ __forceinline__ void attn_pack(const float (&acc)[96], uint32_t (&d)[8]) {
#pragma unroll
  for (int c = 0; c < 8; c++) {
    asm volatile("cvt.rn.bf16x2.f32 %0, %1, %2;\n" : "=r"(d[c]) : "f"(acc[4 * (C0 + c) + 2 * H + 1]), "f"(acc[4 * (C0 + c) + 2 * H]));
    if (T) d[c] = movm(d[c]);
  }
}
__device__ __forceinline__ void attn_qk(float (&s)[4], const uint32_t (&qlo)[8], const uint32_t (&qhi)[8],
                                        const uint32_t (&k)[8], int c) {
  mma16816_z(s, qlo[c], qhi[c], qlo[c + 1], qhi[c + 1], k[c], k[c + 1]);
  mma16816(s, qlo[c + 2], qhi[c + 2], qlo[c + 3], qhi[c + 3], k[c + 2], k[c + 3]);
}
template <int N> __device__ __forceinline__ void quad_softmax(float (&x)[N][2], uint32_t (&pp)[N]) {
  const float c2 = 1.4426950408889634f;
  uint32_t q[N], mx[N / 2];
#pragma unroll
  for (int n = 0; n < N; n++) {
    const uint32_t r = pack_bf16(x[n][0], x[n][1]);
    q[n] = bfma2(r, 0x3e353e35u, bmul2(r, 0x379e379eu));
    x[n][0] = bf_lo(q[n]);
    x[n][1] = bf_hi(q[n]);
  }
#pragma unroll
  for (int n = 0; n < N / 2; n++)
    mx[n] = bmax2(__byte_perm(q[2 * n], q[2 * n + 1], 0x5410), __byte_perm(q[2 * n], q[2 * n + 1], 0x7632));
#pragma unroll
  for (int o = 1; o <= 2; o++) {
#pragma unroll
    for (int n = 0; n < N / 2; n++) mx[n] = bmax2(mx[n], __shfl_xor_sync(0xffffffffu, mx[n], o));
  }
  float m[N], t[N];
#pragma unroll
  for (int n = 0; n < N / 2; n++) {
    m[2 * n] = bf_lo(mx[n]);
    m[2 * n + 1] = bf_hi(mx[n]);
  }
#pragma unroll
  for (int n = 0; n < N; n++) {
    const float nm = -m[n] * c2;
    x[n][0] = ex2(fmaf(x[n][0], c2, nm));
    x[n][1] = ex2(fmaf(x[n][1], c2, nm));
  }
#pragma unroll
  for (int n = 0; n < N; n += 2) {
    float u0, u1;
    asm("mma.sync.aligned.m16n8k8.row.col.f32.tf32.tf32.f32 {%0,%1,%2,%3}, {%4,%5,%6,%7}, {%8,%8}, {%9,%9,%9,%9};\n"
        : "=f"(t[n]), "=f"(u0), "=f"(t[n + 1]), "=f"(u1)
        : "r"(__float_as_uint(x[n][0])), "r"(__float_as_uint(x[n + 1][0])), "r"(__float_as_uint(x[n][1])),
          "r"(__float_as_uint(x[n + 1][1])), "r"(0x3f800000u), "f"(0.f));
  }
#pragma unroll
  for (int n = 0; n < N; n++) {
    const float inv = rcp(t[n]);
    pp[n] = pack_bf16(x[n][0] * inv, x[n][1] * inv);
  }
}
__device__ __forceinline__ void attn_pv(uint32_t dst, const uint32_t (&vp)[8], const uint32_t (&vo)[8], int c, uint32_t pp,
                                        uint32_t maskLE) {
  const uint32_t b0 = pp & ~maskLE, b1 = pp & maskLE;
  float oa[4], ob[4];
  mma16816_z(oa, vp[c], vp[c + 1], vo[c], vo[c + 1], b0, b1);
  mma16816_z(ob, vp[c + 2], vp[c + 3], vo[c + 2], vo[c + 3], b0, b1);
  stsm4t(dst, pack_bf16(oa[0], oa[1]), pack_bf16(oa[2], oa[3]), pack_bf16(ob[0], ob[1]), pack_bf16(ob[2], ob[3]));
}

template <int MODE>
__global__ void __cluster_dims__(2, 1, 1) __launch_bounds__(NTHREADS, 1)
fused_kernel(const Params p, const __grid_constant__ CUtensorMap tmX, const __grid_constant__ CUtensorMap tmW,
             const __grid_constant__ CUtensorMap tmWo, const __grid_constant__ CUtensorMap tmWp,
             const __grid_constant__ CUtensorMap tmQ,
             const __grid_constant__ CUtensorMap tmOb,
             const __grid_constant__ CUtensorMap tmXh, const __grid_constant__ CUtensorMap tmWh) {
  extern __shared__ __align__(1024) uint8_t smem[];
  if (threadIdx.x < 32 * PFR) {
    const uint32_t i = ((blockIdx.x + (threadIdx.x >> 5) * (128 / PFR)) & 127) * 16 + (threadIdx.x & 15);
    prefetch_l2(threadIdx.x & 16 ? (const char*)p.w + i * 128 : (const char*)p.x + i * 2048);
  }
  const uint32_t sb = smem_u32(smem);
  const uint32_t bars = sb + OFF_BAR;
  const int tid = threadIdx.x, lane = tid & 31, warp = __shfl_sync(0xffffffffu, tid >> 5, 0);
  const int rank = blockIdx.x & 1;
  const bool halo_cta = blockIdx.x < 4;
  if (halo_cta && MODE != 0) return;
  int grp, mem;
  {
    const int t = (blockIdx.x >> 1) - 4, u = t - 32;
    const int q7 = (u * 37) >> 8;
    const bool lo = (unsigned)t < 32u, mid = (unsigned)u < 28u;
    grp = lo ? (t & 7) : (mid ? 1 + u - 7 * q7 : 0);
    mem = lo ? (t >> 3) : (mid ? 4 + q7 : (t < 0 ? t + 6 : t - 54));
  }
  const int rg = (grp >> 2) * 4 + (mem >> 1), hp = (grp & 3) * 4 + (mem & 1) * 2 + rank;
  const int rb2 = (grp >> 2) * 8 + mem, cb2 = (grp & 3) * 2 + rank;
  const int chb = grp * 16 + mem * 2 + rank;
  const int cta = rg * 16 + hp;
  const int hsel = rb2 & 1;
  const int par = rg >> 2, gidx = rg & 3;

  if (tid < 256 && !halo_cta && MODE != 2) {
    const int r = tid >> 3, c = tid & 7;
    const uint32_t so = r * 128 + ((c ^ (r & 7)) << 4);
    const __nv_bfloat16* wg0 = p.w + (size_t)r * (3 * DM) + hp * 64 + c * 8;
    const __nv_bfloat16* xg0 = p.x + (size_t)(2 * (gidx * 256 + r) + par) * DM + c * 8;
#pragma unroll
    for (int j = 0; j < 3; j++) cp_async16n(sb + OFF_1B + j * 4096 + so, wg0 + j * DM);
#pragma unroll
    for (int i = 0; i < 8; i++) cp_async16n(sb + i * 4096 + so, xg0 + (size_t)i * 64 * DM);
    asm volatile("cp.async.commit_group;\n" ::: "memory");
    if (PF2 >= 1 && tid < 16 * PF2X) prefetch_l2((const char*)p.x + (chb * 16 + (tid & 15)) * 2048 + 128 + (tid >> 4) * 128);
    if (PF2 >= 2 && warp == 2) prefetch_l2((const char*)p.w + (2048 + chb * 32 + lane) * 128);
  }

  if (warp >= 8) {
    asm volatile("setmaxnreg.dec.sync.aligned.u32 %0;\n" :: "n"(REG_HELP));
    auto halo_issue = [&](int kb, int s) {
      const uint32_t fb = bars + 8 * (BAR_FULLB + s), st = sb + s * STGH;
      mbar_expect_tx(fb, STGH - 2048);
      tma_load_3d(st + 8192, &tmWh, fb, 0, kb * 64, 16 + blockIdx.x * 4);
      tma_load_3d(st + 8192 + 32768, &tmWh, fb, 0, kb * 64, 32 + blockIdx.x * 4);
      tma_load_4d(st, &tmXh, fb, kb * 64, 248, 0, 0);
    };
    if (tid == 256) {
      prefetch_tmap(halo_cta ? &tmXh : &tmX);
#pragma unroll
      for (int i = 0; i < NS1B; i++) mbar_init(bars + 8 * (BAR_FULLB + i), 1);
#pragma unroll
      for (int i = 0; i < NS1A; i++) mbar_init(bars + 8 * (BAR_FULLA + i), 1);
      asm volatile("fence.mbarrier_init.release.cluster;\n" ::: "memory");
      if (!halo_cta && MODE != 2) {
        mbar_expect_tx(bars + 8 * (BAR_FULLB + 1), STG1B);
        tma_load_3d(sb + OFF_1B + 1 * STG1B, &tmW, bars + 8 * (BAR_FULLB + 1), hp * 64, 32, 0);
        mbar_expect_tx(bars + 8 * (BAR_FULLB + 2), STG1B);
        tma_load_3d(sb + OFF_1B + 2 * STG1B, &tmW, bars + 8 * (BAR_FULLB + 2), hp * 64, 64, 0);
        mbar_arrive(bars + 8 * BAR_FULLA);
        mbar_arrive(bars + 8 * BAR_FULLB);
      } else if (halo_cta) {
        halo_issue(0, 0);
      }
    } else if (tid == 288) {
#pragma unroll
      for (int i = 0; i < NS1A; i++) mbar_init(bars + 8 * (BAR_EMPTYA + i), 4);
#pragma unroll
      for (int i = 0; i < NS1B; i++) mbar_init(bars + 8 * (BAR_EMPTYB + i), 2);
      mbar_init(bars + 8 * BAR_X, 4);
      mbar_init(bars + 8 * BAR_TAB, 16);
      mbar_init(bars + 8 * BAR_U, 1);
      mbar_init(bars + 8 * BAR_H, 1);
      mbar_init(bars + 8 * BAR_STG, 8);
      mbar_init(bars + 8 * BAR_HALO, 1);
      mbar_init(bars + 8 * BAR_Q, 1);
      mbar_init(bars + 8 * BAR_LAND, 5);
      mbar_init(bars + 8 * (BAR_LAND + 1), 5);
      asm volatile("fence.mbarrier_init.release.cluster;\n" ::: "memory");
    } else if (tid == 320) {
#pragma unroll
      for (int i = 0; i < NS2; i++) {
        mbar_init(bars + 8 * (BAR_FULL2 + i), 1);
        mbar_init(bars + 8 * (BAR_EMPTY2 + i), 2);
        mbar_init(bars + 8 * (BAR_EMPTY2B + i), 2);
      }
      asm volatile("fence.mbarrier_init.release.cluster;\n" ::: "memory");
    } else if (tid == 352) {
#pragma unroll
      for (int i = 0; i < 4; i++) mbar_init(bars + 8 * (BAR_Y + i), i < 2 ? 4 : i == 2 ? 10 : 8);
      mbar_init(bars + 8 * BAR_XFREE, 1);
      asm volatile("fence.mbarrier_init.release.cluster;\n" ::: "memory");
    }
    __syncwarp();
    cluster_sync_all();
    if (warp == 8) PROF2(24);
    const int hw = warp - 8;
    const int lr = lane & 7, lm = lane >> 3;
    auto g1_issue_a = [&](int j, int s) {
      const uint32_t fb = bars + 8 * (BAR_FULLA + s);
      mbar_expect_tx(fb, STG1A);
      tma_load_3d_mc(sb + s * STG1A + rank * 16384, &tmX, fb, j * 64, par, gidx * 256 + rank * 128);
    };
    auto g1_issue_b = [&](int kb, int s) {
      const uint32_t fb = bars + 8 * (BAR_FULLB + s);
      mbar_expect_tx(fb, STG1B);
      tma_load_3d(sb + OFF_1B + s * STG1B, &tmW, fb, hp * 64, kb * 32, 0);
    };
    auto g2_k = [&](int kb) { return (kb < 2 ? hp : kb < 4 ? hp & 14 : hp & 12) ^ kb; };
    auto g2_issue_b = [&](uint32_t fb, uint32_t bytes, uint32_t dst, int k0, bool whole) {
      if (whole) {
        tma_load_3d(dst, &tmWo, fb, 0, k0, cb2 * 2);
      } else {
#pragma unroll
        for (int i = 0; i < 4; i++)
          tma_load_3d(dst + (i & 1) * XT + (i >> 1) * 4 * XT, &tmWp, fb, 0, k0 + (i >> 1) * 32, cb2 * 2 + (i & 1));
      }
      mbar_expect_tx(fb, bytes);
    };
    auto send_y = [&](uint32_t o, uint32_t step, int half) {
      const uint32_t peer = mapa(sb, rank ^ 1);
      o += OFF_X + (rank ^ 1) * 4096 + half * 2048 + lane * 16;
      uint4 a[8];
#pragma unroll
      for (int i = 0; i < 8; i++) a[i] = lds128(sb + o + (i >> 2) * step + (i & 2) * (XT / 2) + (i & 1) * 512);
#pragma unroll
      for (int i = 0; i < 8; i++)
        st_async128(peer + o + 1024 + (i >> 2) * step + (i & 2) * (XT / 2) + (i & 1) * 512,
                    peer + OFF_BAR + 8 * (BAR_LAND + half), a[i].x, a[i].y, a[i].z, a[i].w);
    };

    if (halo_cta) {
      if (hw == 0) {
        int s = 1, ph = 1;
#pragma unroll 1
        for (int kb = 1; kb < 16; kb++) {
          mbar_wait(bars + 8 * (BAR_EMPTYB + s), ph);
          if (elect_one()) halo_issue(kb, s);
          if (++s == 3) { s = 0; ph ^= 1; }
        }
      }
      __syncwarp();
    } else if (hw == 0) {
      uint32_t epoch = 0;
      if (MODE == 2) {
        if (lane < NS2) mbar_arrive_cluster_n(mapa(bars, rank) + 8 * (BAR_EMPTY2 + lane), 2);
      } else {
      if (lane == 0) {
        mbar_expect_tx(bars + 8 * BAR_U, 32768);
        mbar_expect_tx(bars + 8 * BAR_LAND, 8192);
        mbar_expect_tx(bars + 8 * (BAR_LAND + 1), 8192);
        mbar_expect_tx(bars + 8 * BAR_Q, 32768);
        prefetch_tmap(&tmQ);
      }
      {
        int sa = 1, pha = 1, sbb = 2, phb = 1;
#pragma unroll 1
        for (int kb = 2; kb < 32; kb++) {
          if (!(kb & 1)) {
            mbar_wait(bars + 8 * (BAR_EMPTYA + sa), pha);
            if (elect_one()) g1_issue_a(kb >> 1, sa);
            if (++sa == NS1A) { sa = 0; pha ^= 1; }
          }
          mbar_wait(bars + 8 * (BAR_EMPTYB + sbb), phb);
          if (kb > 2 && elect_one()) g1_issue_b(kb, sbb);
          __syncwarp();
          if (kb == 4) epoch = ld_relaxed(g_flag_o + cta);
          if (kb == 4) PROF2(27);
          if (kb == 1) PROF2(38);
          if (kb == 2) PROF2(39);
          if (++sbb == NS1B) { sbb = 0; phb ^= 1; }
        }
      }
      auto q_issue = [&](int i) {
        mbar_wait(bars + 8 * (i ? BAR_EMPTYB + 3 : BAR_EMPTYA + 1), i);
        if (elect_one())
          asm volatile(
              "cp.async.bulk.tensor.5d.shared::cluster.global.mbarrier::complete_tx::bytes [%0], [%1, {%3, %4, %4, %4, %5}], [%2];\n"
              ::"r"(sb + (i ? OFF_Q1 : OFF_Q0)), "l"(&tmQ), "r"(bars + 8 * BAR_Q), "r"((chb & ~1) * 8), "r"(0), "r"(rank * 32 + i * 64)
              : "memory");
        __syncwarp();
      };
      if (QORD < 2) q_issue(0);
      else mbar_wait(bars + 8 * (BAR_EMPTYA + 1), 0);
      if (QORD < 1) q_issue(1);
      epoch++;
      if (lane == 0) {
        prefetch_tmap(&tmWo);
        prefetch_tmap(&tmWp);
        prefetch_tmap(&tmOb);
        if (gidx != 0) wait_flag(g_flag_h + (hp >> 2), epoch);
      }
      __syncwarp();
      {
        uint4 hk0 = make_uint4(0, 0, 0, 0), hk1 = hk0, hv0 = hk0, hv1 = hk0;
        if (gidx != 0) {
          const uint4* src = g_halo + cta * 128 + lane;
          hk0 = __ldcg(src); hk1 = __ldcg(src + 32); hv0 = __ldcg(src + 64); hv1 = __ldcg(src + 96);
        }
        if (gidx != 0) PROF(18);
        sts128(sb + OFF_KH + lane * 16, hk0.x, hk0.y, hk0.z, hk0.w);
        sts128(sb + OFF_KH + 512 + lane * 16, hk1.x, hk1.y, hk1.z, hk1.w);
        sts64(sb + OFF_KH + 1024 + lane * 8, movm(hv0.x), movm(hv0.y));
        sts64(sb + OFF_KH + 1280 + lane * 8, movm(hv0.z), movm(hv0.w));
        sts64(sb + OFF_KH + 1536 + lane * 8, movm(hv1.x), movm(hv1.y));
        sts64(sb + OFF_KH + 1792 + lane * 8, movm(hv1.z), movm(hv1.w));
        __syncwarp();
        if (lane == 0) mbar_arrive(bars + 8 * BAR_HALO);
      }
      if (QORD == 2) q_issue(0);
      if (QORD >= 1) q_issue(1);
      const uint32_t rb = mapa(bars, lane & 1);
      nb_sync(NB_OREADY, 288);
      if (lane == 0) {
        asm volatile("cp.async.bulk.global.shared::cta.bulk_group [%0], [%1], %2;\n" ::"l"(g_o + (size_t)cta * 16384),
                     "r"(sb + OFF_OP), "r"(32768) : "memory");
        bulk_commit();
      }
      if (lane < 2) {
#pragma unroll
        for (int i = 0; i < 4; i++) mbar_arrive_cluster(rb + 8 * (BAR_EMPTY2 + i + i / 2));
      }
      if (lane == 0) {
        bulk_wait0();
        st_release(g_flag_o + cta, epoch);
      }
      __syncwarp();
      PROF2(17);
      if (lane < 2) mbar_arrive_cluster(rb + 8 * (BAR_EMPTY2 + 2));
      }
      if (MODE != 1) {
        const __nv_bfloat16* osrc = g_o + (size_t)(rb2 >> 1) * 16 * 16384 + hsel * 8192;
        mbar_wait(bars + 8 * (BAR_EMPTY2 + 1), 0);
        if (elect_one()) {
          if (MODE == 0) {
            asm volatile("cp.async.bulk.shared::cluster.shared::cta.mbarrier::complete_tx::bytes [%0], [%1], %2, [%3];\n"
                         ::"r"(mapa(sb + g2_a(1, hsel), rank ^ 1)), "r"(sb + g2_a(0, hsel)), "r"(16384),
                         "r"(mapa(bars + 8 * (BAR_FULL2 + 1), rank ^ 1)) : "memory");
          } else {
            bulk_load(sb + g2_a(0, hsel), osrc + hp * 16384, 16384, bars + 8 * BAR_FULL2);
            bulk_load(sb + g2_a(1, hsel), osrc + (hp ^ 1) * 16384, 16384, bars + 8 * (BAR_FULL2 + 1));
          }
        }
        __syncwarp();
      }
      if (MODE != 2) {
        mbar_wait(bars + 8 * (BAR_Y + 2), 0);
        send_y(0, 4 * XT, 1);
        fence_async_smem();
        __syncwarp();
      }
      if (MODE != 1) {
        unsigned long long seq = G2_SEQ >> 12;
        uint32_t wbar = bars + 8 * (BAR_Y + 2), fb = bars + 8 * (BAR_FULL2 + 3), dst = sb + g2_b(3, rank), ph = MODE ? 1 : 0;
        int k0 = g2_k(3) * 64;
        bool whole = false;
#pragma unroll 1
        for (int kb = 4; kb <= 16; kb++) {
          mbar_wait(wbar, ph);
          if (elect_one()) g2_issue_b(fb, STG2, dst, k0, whole);
          __syncwarp();
          seq >>= 4;
          const int s = seq & 7;
          wbar = bars + 8 * (kb == G2_KB4 ? BAR_XFREE : BAR_EMPTY2B + s);
          ph = ((uint32_t)seq >> 3 & 1) ^ (kb == G2_KB4 && MODE == 0 ? 0 : 1);
          fb = bars + 8 * (BAR_FULL2 + s);
          dst = sb + g2_b(s, rank);
          k0 = ((hp & 12) ^ kb) * 64;
          whole = s < 3;
        }
      }
      __syncwarp();
    } else {
      if (MODE != 2) {
      const float dall = __bfloat162float(p.ssm_D[chb * 8 + lr]);
      {
        const int g = lane >> 2, t = lane & 3;
        uint32_t w[2][4];
#pragma unroll
        for (int h = 0; h < 2; h++) {
          const uint2 x = __ldg(reinterpret_cast<const uint2*>(p.shift_k + ((chb & ~1) * 8 + h * 8 + g) * 4));
          w[h][0] = __byte_perm(x.x, x.x, 0x1010);
          w[h][1] = __byte_perm(x.x, x.x, 0x3232);
          w[h][2] = __byte_perm(x.y, x.y, 0x1010);
          w[h][3] = __byte_perm(x.y, x.y, 0x3232);
        }
        auto swz = [](int r) { return (((r & 29) | ((r ^ (r >> 2)) & 2)) << 5) | (r & 16); };
        const uint32_t kring = sb + OFF_X + 4096 + (hw - 1) * 2 * XT, vring = kring + XT;
        const int s0 = rank * 32 + (hw - 1) * 11, s1 = hw == 3 ? rank * 32 + 32 : s0 + 11;
        const size_t goff = (size_t)(s0 * 32 + (lane >> 1)) * DM + (chb & ~1) * 8 + (lane & 1) * 8;
        const __nv_bfloat16* kg = p.k + goff;
        const __nv_bfloat16* vg = p.v + goff;
        const uint32_t d0 = swz(lane >> 1) ^ ((lane & 1) << 4), d1 = swz(16 + (lane >> 1)) ^ ((lane & 1) << 4);
        auto issue = [&](int st) {
          const uint32_t a = kring + ((st & 3) << 10);
          asm volatile("cp.async.cg.shared.global.L2::256B [%0], [%2], 16;\n"
                       "cp.async.cg.shared.global.L2::256B [%1], [%2 + 32768], 16;\n"
                       "cp.async.cg.shared.global.L2::256B [%0 + 8192], [%3], 16;\n"
                       "cp.async.cg.shared.global.L2::256B [%1 + 8192], [%3 + 32768], 16;\n"
                       ::"r"(a + d0), "r"(a + d1), "l"(kg), "l"(vg) : "memory");
          kg += 32 * DM;
          vg += 32 * DM;
          asm volatile("" : "+l"(kg), "+l"(vg));
        };
        const int xa = 8 * (lr >> 1) + 2 * lm + (lr & 1), xb = 8 * (lr >> 1) - 4 + 2 * (lm & 1) + (lr & 1);
        const uint32_t la = swz(xa), lb = swz(xb & 31);
        const int backb = xb < 0 ? 1 : 0;
        const uint32_t ud[2] = {mapa(sb + OFF_X + g * XT + t * 16, 0), mapa(sb + OFF_X + g * XT + t * 16, 1)};
        const uint32_t ub[2] = {mapa(bars + 8 * BAR_U, 0), mapa(bars + 8 * BAR_U, 1)};
        if (tid == 320) prefetch_l2(g_tab + (chb & 63) * 32);
        if (lane == 0) mbar_wait(bars + 8 * (BAR_FULLB + NS1B - 1), 0);
        __syncwarp();
        if (lane >= 24) cp_async16(kring + (((s0 - 1) & 3) << 10) + d1, s0 > 0 ? kg - 16 * DM : kg, s0 > 0 ? 16 : 0);
        issue(s0);
        asm volatile("cp.async.commit_group;\n" ::: "memory");
        issue(s0 + 1);
        asm volatile("cp.async.commit_group;\n" ::: "memory");
        uint32_t tn = (uint32_t)clock();
#pragma unroll 1
        for (int st = s0; st < s1; st++) {
          tn += PSTEP;
          while ((int)((uint32_t)clock() - tn) < 0) __nanosleep(100);
          if (st + 2 < s1) issue(st + 2);
          if (hw == 1 && (unsigned)(st - s0 - HPF0) < 8u) prefetch_l2(p.ssm_k + (size_t)(chb * 8 + st - s0 - HPF0) * SEQ + lane * 64);
          asm volatile("cp.async.commit_group;\n" ::: "memory");
          asm volatile("cp.async.wait_group 2;\n" ::: "memory");
          __syncwarp();
#pragma unroll
          for (int h = 0; h < 2; h++) {
            uint32_t e[6], vv[4], e4[4];
            ldsm4t(e4, kring + ((st & 3) << 10) + (la ^ (h << 4)));
            ldsm2t(e[0], e[1], kring + (((st - backb) & 3) << 10) + (lb ^ (h << 4)));
            ldsm4t(vv, vring + ((st & 3) << 10) + (la ^ (h << 4)));
            e[2] = e4[0]; e[3] = e4[1]; e[4] = e4[2]; e[5] = e4[3];
            uint32_t o[5];
#pragma unroll
            for (int i = 0; i < 5; i++) o[i] = __byte_perm(e[i], e[i + 1], 0x5432);
#pragma unroll
            for (int i = 0; i < 4; i++) {
              uint32_t a = bmul2(o[i], w[h][3]);
              a = bfma2(e[i + 1], w[h][2], a);
              a = bfma2(o[i + 1], w[h][1], a);
              a = bfma2(e[i + 2], w[h][0], a);
              vv[i] = bmul2(a, vv[i]);
            }
            st_async128(ud[h] + (st ^ (g & 1)) * 64, ub[h], vv[0], vv[1], vv[2], vv[3]);
          }
          __syncwarp();
        }
        fence_async_smem();
        PROF(16);
      }
      nb_sync(NB_HELP3, 96);
      if (hw == 1 && elect_one()) {
        mbar_expect_tx(bars + 8 * BAR_H, 8 * 4096);
#pragma unroll 1
        for (int c = 0; c < 8; c++)
          bulk_load(sb + OFF_X + c * XT + 4096, p.ssm_k + (size_t)(chb * 8 + c) * SEQ, 4096, bars + 8 * BAR_H);
        mbar_expect_tx(bars + 8 * BAR_X, 6144);
        bulk_load(sb + OFF_T16, g_tab, 2048, bars + 8 * BAR_X);
        bulk_load(sb + OFF_T32, g_tab + 512, 4096, bars + 8 * BAR_X);
      }
      __syncwarp();
      {
        const int ck = 16 * (lane >> 4) + 2 * lr + (((lane >> 3) ^ (lane >> 2)) & 1);
        const uint32_t xo = (ck >> 1) * 64, xs = ((ck & 1) ^ (lr >> 1)) << 4;
#pragma unroll 1
        for (int job = hw - 1; job < 16; job += 3) {
          const int c = job & 7;
          uint4 a[8];
          float dv = __shfl_sync(0xffffffffu, dall, c);
          if (job < 8 || lane) dv = 0.f;
          if (job >= PF0 && job < PF1) prefetch_l2((job < 8 ? p.q + (size_t)chb * 16384 : p.wo + (size_t)chb * 8192) + c * 2048 + lane * 64);
          const uint32_t xt = sb + OFF_X + c * XT + (job >> 3) * 4096;
          mbar_wait(bars + 8 * (job < 8 ? BAR_U : BAR_H), 0);
#pragma unroll
          for (int i = 0; i < 8; i++) a[i] = lds128(xt + i * 512 + ((ck ^ (job < 8 ? (c & 1) << 2 : 0)) << 4));
          dv += bf_lo(a[0].x);
          uint32_t m[2] = {bmaxabs2(pack_bf16(dv, 0.f), bmaxabs2(a[0].x, a[0].y)), bmaxabs2(a[0].z, a[0].w)};
#pragma unroll
          for (int i = 1; i < 8; i++) {
            m[0] = bmaxabs2(bmaxabs2(m[0], a[i].x), a[i].y);
            m[1] = bmaxabs2(bmaxabs2(m[1], a[i].z), a[i].w);
          }
          m[0] = bmaxabs2(m[0], m[1]);
          const int f = max(252 - (int)(__reduce_max_sync(0xffffffffu, max(m[0] & 0x7fffu, (m[0] >> 16) & 0x7fffu)) >> 7), 1);
          if (lane == 0) asm volatile("st.shared.u32 [%0], %1;\n" ::"r"(sb + OFF_EX + job * 4), "r"(f) : "memory");
          if (f < 113) {
#pragma unroll
            for (int i = 0; i < 8; i++)
              a[i] = make_uint4(bmul2(a[i].x, f * 0x00800080u), bmul2(a[i].y, f * 0x00800080u), bmul2(a[i].z, f * 0x00800080u),
                                bmul2(a[i].w, f * 0x00800080u));
          }
          const uint32_t mul = (f < 113 ? 15 : f - 112) * 0x00800080u;
          auto cv = [&](uint32_t x) {
            x = bmul2(x, mul);
            return (x & 0x0fff0fffu) * 7 + x;
          };
          const uint32_t dst = xt + xo;
#pragma unroll
          for (int i = 0; i < 8; i++)
            sts128(dst + (i >> 2) * 2048 + (i & 1) * 1024 + (xs ^ ((i & 2) << 4)),
                   i ? cv(a[i].x) : __byte_perm(pack_f16(dv * __uint_as_float(f << 23), 0.f), cv(a[i].x), 0x7610), cv(a[i].y),
                   cv(a[i].z), cv(a[i].w));
        }
        fence_async_smem();
        __syncwarp();
        if (lane == 0) mbar_arrive(bars + 8 * BAR_X);
        PROF(19);
      }
      if (hw < 3) {
#pragma unroll 1
        for (int n = 0; n < SPIN_LIMIT && !mbar_try(bars + 8 * (BAR_Y + hw - 1), 0); n++) __nanosleep(100);
        send_y((hw - 1) * 4 * XT, 2 * XT, 0);
        __syncwarp();
        if (lane == 0) mbar_arrive(bars + 8 * (BAR_Y + 2));
        PROF(32);
        const int c8 = 2 * lm + (lr & 1), src = (lr >> 1) & 1;
        uint32_t fa = sb + OFF_X + c8 * XT + rank * 4096 + (src == rank ? 0 : 1024) + (hw - 1) * 512;
        const uint32_t fx = ((lr >> 2) ^ ((lr & 3) << 1)) << 4;
        uint32_t qa = sb + OFF_Q0 + (hw - 1) * 8192 + (lane >> 3) * 128 + (lane & 2) * 32 + (lane & 4) * 8 + (lane & 1) * 16;
        uint4* og = reinterpret_cast<uint4*>(p.out + (size_t)(rank * 512 + (hw - 1) * 256 + (lane & 2) * 4 + (lane >> 2)) * (2 * DM) +
                                             (chb & ~1) * 8 + (lane & 1) * 8);
        mbar_wait(bars + 8 * BAR_Q, 0);
        uint32_t tn = 0;
#pragma unroll 1
        for (int j = 0; j < 16; j++) {
          if (j == JS && hw == 2) {
            mbar_wait(bars + 8 * (BAR_Y + 3), 0);
            send_y(2 * XT, 4 * XT, 1);
            fence_async_smem();
            __syncwarp();
            if (lane == 0) mbar_arrive(bars + 8 * BAR_XFREE);
            tn = (uint32_t)clock();
          }
          if (!(j & 7)) {
            mbar_wait(bars + 8 * (BAR_LAND + (j >> 3)), 0);
            tn = (uint32_t)clock() + (hw - 1) * (FPACE / 2);
            PROF2(33 + (j >> 1));
          }
#pragma unroll
          for (int i = 0; i < 2; i++) {
            uint32_t y[4];
            const uint4 q = lds128(qa + i * 512);
            ldsm4t(y, fa + (j & 6) * 64 + (fx ^ (i << 5) ^ ((j & 1) << 6) ^ ((j & 2) << 3)));
            while ((int)((uint32_t)clock() - tn) < 0) __nanosleep(FSL);
            tn += hw == 2 ? FPACE2 : FPACE;
            og[i * 16 * (2 * DM / 8)] = make_uint4(bmul2(q.x, y[0]), bmul2(q.y, y[1]), bmul2(q.z, y[2]), bmul2(q.w, y[3]));
          }
          qa += j == 7 ? OFF_Q1 - OFF_Q0 - 7168 : 1024;
          if (j == 7) fa += 2048;
          og += (j == 7 ? 1024 - 224 : 32) * (2 * DM / 8);
        }
        PROF(22);
      }
      }
      if (MODE != 1 && hw == 3) {
        const uint32_t epoch = ld_relaxed(g_flag_o + cta) + 1;
        if (MODE == 0) nb_sync(NB_G1END, 288);
        if (BDEL) __nanosleep(BDEL);
        if (elect_one()) {
#pragma unroll
          for (int kb = 0; kb < 3; kb++)
            g2_issue_b(bars + 8 * (BAR_FULL2 + kb), kb || MODE ? STG2 : STG2 / 2, sb + g2_b(kb, 0), g2_k(kb) * 64, true);
        }
        __syncwarp();
        const __nv_bfloat16* osrc = g_o + (size_t)(rb2 >> 1) * 16 * 16384 + hsel * 8192;
        if (MODE == 0) __nanosleep(POLL0);
        const uint32_t* flag = g_flag_o + (rb2 >> 1) * 16 + g2_k(lane & 15);
        uint32_t ready = MODE == 0 ? 0u : ~0u;
        unsigned long long seq = G2_SEQ >> 8;
#pragma unroll 1
        for (int kb = 2; kb < 16; kb++, seq >>= 4) {
          uint32_t so = bars + (seq & 7) * 8, dst = sb + g2_a(seq & 7, hsel) + rank * 8192;
          const uint32_t ph = (uint32_t)seq >> 3 & 1;
          const __nv_bfloat16* src = osrc + rank * 4096 + (uint32_t)g2_k(kb) * 16384;
          asm volatile("" : "+r"(so), "+r"(dst), "+l"(src));
          if (!(ready >> kb & 1)) {
#pragma unroll 1
            for (int n = 0; n < SPIN_LIMIT && !(ready >> kb & 1); n++)
              ready = __ballot_sync(0xffffffffu, ld_acquire(flag) == epoch);
            fence_async_all();
          }
          if (kb == 2) PROF(21);
          if (MODE == 0 && kb == G2_KB4 && rank == 1) mbar_wait(bars + 8 * BAR_TAB, 0);
          mbar_wait(so + 8 * BAR_EMPTY2, ph);
          if (elect_one()) {
            asm volatile(
                "cp.async.bulk.shared::cluster.global.mbarrier::complete_tx::bytes.multicast::cluster [%0], [%1], %2, [%3], %4;\n"
                ::"r"(dst), "l"(src), "r"(8192), "r"(so + 8 * BAR_FULL2), "h"((uint16_t)3) : "memory");
          }
          __syncwarp();
        }
      }
    }
    cluster_sync_all();
    PROF_DUMP();
  } else {
    asm volatile("barrier.cluster.arrive.relaxed.aligned;\n" ::: "memory");
    asm volatile("setmaxnreg.inc.sync.aligned.u32 %0;\n" :: "n"(REG_MATH));
    if (halo_cta || MODE == 2) asm volatile("barrier.cluster.wait.aligned;\n" ::: "memory");
    if (warp == 0) PROF2(26);
    const int wg = warp >> 2;
    const int wtid = tid & 127;
    const bool signaller = (wtid == 0) || (wtid == 32);
    const uint32_t rbars = mapa(bars, wtid >> 5 & 1);

    if (halo_cta) {
      const uint32_t epoch = ld_relaxed(g_flag_h + blockIdx.x) + 1;
      float acc0[64], acc1[64];
      int s = 0, ph = 0;
#pragma unroll 1
      for (int kb = 0; kb < 16; kb++) {
        mbar_wait(bars + 8 * (BAR_FULLB + s), ph);
        const uint32_t st = sb + s * STGH;
        const uint64_t da = mkdesc(st, 16, 1024, 1);
        const uint64_t db = mkdesc(st + 8192 + wg * 32768, 8192, 1024, 1);
        wg_fence();
#pragma unroll
        for (int kk = 0; kk < 4; kk++) {
          wgmma_n128(acc0, da + 2 * kk, db + 128 * kk, kb + kk);
          wgmma_n128(acc1, da + 2 * kk, db + 1024 + 128 * kk, kb + kk);
        }
        wg_commit();
        wg_wait<0>();
        if (kb == 15) PROF(37);
        if (wtid == 0) mbar_arrive(bars + 8 * (BAR_EMPTYB + s));
        if (++s == 3) { s = 0; ph ^= 1; }
      }
      fence_regs(acc0);
      fence_regs(acc1);
      if ((warp & 3) != 3) {
#pragma unroll
        for (int hh = 0; hh < 2; hh++) {
          uint4* dst = g_halo + ((hh * 4 + (warp & 3) + 1) * 16 + blockIdx.x * 4) * 128 + wg * 64 + lane;
#pragma unroll
          for (int j = 0; j < 4; j++) {
            const int o = 16 * j + 2 * hh;
            dst[(j >> 1) * 128 + (j & 1) * 32] =
                make_uint4(pack_bf16(acc0[o], acc0[o + 1]), pack_bf16(acc0[o + 4], acc0[o + 5]),
                           pack_bf16(acc0[o + 8], acc0[o + 9]), pack_bf16(acc0[o + 12], acc0[o + 13]));
            dst[(2 + (j >> 1)) * 128 + (j & 1) * 32] =
                make_uint4(pack_bf16(acc1[o], acc1[o + 1]), pack_bf16(acc1[o + 4], acc1[o + 5]),
                           pack_bf16(acc1[o + 8], acc1[o + 9]), pack_bf16(acc1[o + 12], acc1[o + 13]));
          }
        }
      }
      nb_sync(NB_G1DONE, 256);
      if (tid == 0) st_release(g_flag_h + blockIdx.x, epoch);
      PROF(36);
      cluster_sync_all();
      return;
    }

    float acc[64];
    const uint32_t g2rel = wtid ? mapa(bars, rank) + 8 * BAR_EMPTY2B : mapa(bars, wg) + 8 * BAR_EMPTY2;
    uint32_t g2a = (uint32_t)mkdesc(sb + wg * 8192, 16, 0, 0), g2b = (uint32_t)mkdesc(sb, 8192, 0, 0);
    auto g2_block = [&](bool first, int s, int ph) {
      mbar_wait(bars + 8 * (BAR_FULL2 + s), ph);
      const uint32_t da = g2a + (g2_a(s, hsel) >> 4), db = g2b + (g2_b(s, rank) >> 4), dc = db + (g2_bk(s) >> 4);
      wg_fence();
      if (first) wgmma_n128z(acc, da, db);
      else wgmma_n128a(acc, da, db);
      wgmma_n128a(acc, da + 2, db + 128);
      wgmma_n128a(acc, da + 4, dc);
      wgmma_n128a(acc, da + 6, dc + 128);
      wg_commit();
    };
    if (MODE != 2) {
    uint32_t a1[2][4], sc[2];
    C2 t[2];
    {
      float acc0[96], acc1[96];
      int sa = 0, pha = 0;
      uint64_t db0 = mkdesc(sb + OFF_1B, 4096, 1024, 1);
      const uint64_t da0 = mkdesc(sb + wg * 16384, 16, 2048, 1);
      const bool sigb = wtid == 64;
      uint32_t rela = 0;
#pragma unroll 1
      for (int r = 0; r < 3; r++) {
#pragma unroll
        for (int i = 0; i < 2 * NS1B; i++) {
          const uint64_t da = da0 + sa * (STG1A >> 4) + (i & 1) * 4, db = db0 + (i % NS1B) * (STG1B >> 4);
          if (i || r) {
            if (!(i & 1)) mbar_wait(bars + 8 * (BAR_FULLA + sa), pha);
            mbar_wait(bars + 8 * (BAR_FULLB + i % NS1B), i / NS1B);
          } else {
            asm volatile("cp.async.wait_group 0;\n" ::: "memory");
            fence_async_smem();
            nb_sync(NB_FIRST, 256);
            PROF(0 + wg);
          }
          wg_fence();
          wgmma_n192(acc0, da + 64, db, i ? 1 : r);
          wgmma_n192(acc1, da, db, i ? 1 : r);
          wgmma_n192(acc0, da + 66, db + 128, 1);
          wgmma_n192(acc1, da + 2, db + 128, 1);
          wg_commit();
          wg_wait<1>();
          if (i || r) {
            if (sigb) mbar_arrive(bars + 8 * (BAR_EMPTYB + (i + NS1B - 1) % NS1B));
            if (!(i & 1) && signaller) mbar_arrive_cluster(rela);
          } else {
            asm volatile("barrier.cluster.wait.aligned;\n" ::: "memory");
          }
          if (i & 1) {
            rela = rbars + 8 * (BAR_EMPTYA + sa);
            if (++sa == NS1A) { sa = 0; pha ^= 1; }
          }
        }
        db0 += p.zero;
      }
      const int lr = lane & 7, lm = lane >> 3;
      const bool le0 = 2 * (lane & 3) <= (lane >> 2), le1 = 2 * (lane & 3) + 1 <= (lane >> 2);
      const uint32_t maskLE = (le0 ? 0x0000FFFFu : 0u) | (le1 ? 0xFFFF0000u : 0u);
      uint32_t q[4][8], k[5][8], vt[5][8];
      {
        static_assert(15 % NS1A == 0 && 30 % NS1B == 0, "slots of the last k blocks");
        asm volatile("ld.volatile.global.v4.u32 {%0,%1,%2,%3}, [%4];\n"
                     : "=r"(t[0].r), "=r"(t[1].r), "=r"(t[0].i), "=r"(t[1].i) : "l"(g_tab + 1536 + wtid * 4) : "memory");
        mbar_wait(bars + 8 * BAR_FULLA, 1);
        mbar_wait(bars + 8 * BAR_FULLB, 0);
        mbar_wait(bars + 8 * (BAR_FULLB + 1), 0);
        mbar_wait(bars + 8 * (BAR_EMPTYA + 1), 0);
        const uint64_t da = mkdesc(sb + wg * 16384, 16, 2048, 1);
        const uint64_t db = mkdesc(sb + OFF_1B, 4096, 1024, 1);
        wg_fence();
#pragma unroll
        for (int i = 0; i < 4; i++) wgmma_n192(acc0, da + 64 + 2 * i, db + (i >> 1) * (STG1B >> 4) + (i & 1) * 128, 1);
        wg_commit();
#pragma unroll
        for (int i = 0; i < 2; i++) wgmma_n192(acc1, da + 2 * i, db + (i >> 1) * (STG1B >> 4) + (i & 1) * 128, 1);
        wg_commit();
        wg_wait<1>();
        fence_regs(acc0);
        PROFA(45, 0);
        attn_pack<8, 1, false>(acc0, k[4]);
        attn_pack<16, 1, true>(acc0, vt[4]);
        const uint32_t kh = sb + (warp == 7 ? OFF_OP + 7 * 4096 : OFF_KH + (warp + 1) * 2048) + lane * 16;
        sts128(kh, k[4][0], k[4][1], k[4][2], k[4][3]);
        sts128(kh + 512, k[4][4], k[4][5], k[4][6], k[4][7]);
#pragma unroll
        for (int i = 0; i < 4; i++) sts64(kh - lane * 8 + 1024 + 256 * i, vt[4][2 * i], vt[4][2 * i + 1]);
#pragma unroll
        for (int i = 2; i < 4; i++) wgmma_n192(acc1, da + 2 * i, db + (i >> 1) * (STG1B >> 4) + (i & 1) * 128, 1);
        wg_commit();
        attn_pack<0, 0, false>(acc0, q[1]);
        attn_pack<0, 1, false>(acc0, q[3]);
        attn_pack<8, 0, false>(acc0, k[2]);
        attn_pack<16, 0, true>(acc0, vt[2]);
        uint32_t z = p.zero;
#pragma unroll
        for (int i = 0; i < 8; i++) z &= q[1][i] & q[3][i];
#pragma unroll
        for (int i = 0; i < 8; i += 2) z &= k[2][i] & k[2][i + 1];
        __syncwarp();
        if (lane == 0) mbar_arrive(bars + 8 * BAR_STG + z);
        wg_wait<0>();
        fence_regs(acc1);
        if (MODE == 0) nb_arrive(NB_G1END, 288);
      }
      PROF(2 + wg);
      mbar_wait(bars + 8 * (warp == 0 ? BAR_HALO : BAR_STG), 0);
      {
        const uint32_t kh = sb + OFF_KH + warp * 2048 + lane * 16;
#pragma unroll
        for (int i = 0; i < 2; i++) {
          const uint4 t = lds128(kh + 512 * i);
          k[0][4 * i] = t.x; k[0][4 * i + 1] = t.y; k[0][4 * i + 2] = t.z; k[0][4 * i + 3] = t.w;
        }
#pragma unroll
        for (int i = 0; i < 4; i++) {
          const uint2 t = lds64(kh - lane * 8 + 1024 + 256 * i);
          vt[0][2 * i] = t.x; vt[0][2 * i + 1] = t.y;
        }
      }
      attn_pack<0, 0, false>(acc1, q[0]);
      attn_pack<0, 1, false>(acc1, q[2]);
      attn_pack<8, 0, false>(acc1, k[1]);
      attn_pack<8, 1, false>(acc1, k[3]);
      {
        float x[8][2];
        uint32_t pp[8];
        const bool first = warp == 0 && gidx == 0;
#pragma unroll
        for (int hd = 0; hd < 2; hd++) {
#pragma unroll
          for (int j = 0; j < 4; j += 2) {
            float s0[4], s1[4], s2[4];
            attn_qk(s2, q[j], q[j + 1], k[j + 2], 4 * hd);
            attn_qk(s1, q[j], q[j + 1], k[j + 1], 4 * hd);
            attn_qk(s0, q[j], q[j + 1], k[j], 4 * hd);
            if (j == 0 && first) s0[0] = s0[1] = -1e9f / 0.17677669529663687f;
            x[2 * j + hd][0] = le0 ? s1[0] : s0[0];
            x[2 * j + hd][1] = le1 ? s1[1] : s0[1];
            x[2 * j + 2 + hd][0] = le0 ? s2[2] : s1[2];
            x[2 * j + 2 + hd][1] = le1 ? s2[3] : s1[3];
          }
        }
        PROFA(40, __float_as_uint(x[1][0] + x[7][1]));
        attn_pack<16, 0, true>(acc1, vt[1]);
        attn_pack<16, 1, true>(acc1, vt[3]);
        quad_softmax<8>(x, pp);
        PROFA(41, pp[1] + pp[7]);
        mbar_wait(bars + 8 * BAR_X, 0);
        ldsm4(a1[0], sb + OFF_T32 + (warp & 3) * 1024 + lane * 16);
        ldsm4(a1[1], sb + OFF_T32 + 512 + (warp & 3) * 1024 + lane * 16);
        {
          const uint32_t ex = sb + OFF_EX + wg * 16 + (warp & 2) * 2;
#pragma unroll
          for (int i = 0; i < 2; i++) sc[i] = min(max(381 - (int)lds32(ex + 8 * i) - (int)lds32(ex + 32 + 8 * i), 1), 254) * 0x00800080u;
        }
        const uint32_t obase = sb + OFF_OP + (warp * 32 + lr) * 128;
#pragma unroll
        for (int n = 0; n < 8; n++) {
          attn_pv(obase + (n >> 1) * 1024 + (((4 * (n & 1) + lm) ^ lr) << 4), vt[n >> 1], vt[(n >> 1) + 1], 4 * (n & 1), pp[n],
                  maskLE);
        }
      }
      PROFA(42, 0);
    }

    {
      const int w = warp & 3;
      const int lr = lane & 7, lm = lane >> 3;
      const uint32_t xb = sb + OFF_X + wg * 4 * XT;
      auto uo = [](int c) { return (c & 1) * 2 * XT + (c >> 1) * 2048; };
      const uint64_t dc2 = mkdesc(sb + OFF_T16, 512, 128, 0), dc3 = mkdesc(sb + OFF_T16, 128, 512, 0);
      const uint64_t dc4 = mkdesc(sb + OFF_T32, 128, 256, 0);
      const uint64_t dx = mkdesc(xb, 4096, 512, 2), dz = mkdesc(xb, 4096, 256, 3);
      const uint32_t zs = xb + (w * 16 + (lm & 1) * 8 + lr) * 32 + (((lm >> 1) ^ (lr >> 2)) << 4);
      const uint32_t ys = xb + w * 4096 + (lm >> 1) * 256 + ((lr * 32 + (((lm & 1) ^ (lr >> 2)) << 4)) ^ (rank << 6) ^ ((w & 2) << 4));
      const bool own = (w & 1) == rank;
      const uint32_t ybar = mapa(bars, own ? rank ^ 1 : rank) + 8 * BAR_Y;
      uint32_t d[2][32], pa[2][4][2][4], e[4][4][8], ya[2][2][2][4], v[2][2][8];
      C2 s1[2][2][2];
      float o[2][16];
      auto rows = [&](int c) {
        fft_rows(d[c & 1], a1, dx + (uo(c) >> 4));
        wg_commit();
      };
      auto cols = [&](int c) {
        const int s = c & 1;
        fence_regs(d[s]);
#pragma unroll
        for (int i = 0; i < 16; i++) {
          const C2 z = crot(C2{d[s][2 * i], d[s][2 * i + 1]}, t[i & 1]);
          pa[s][i >> 2][i & 1][(i >> 1) & 1] = z.r;
          pa[s][i >> 2][i & 1][2 + ((i >> 1) & 1)] = z.i;
        }
        wg_fence();
#pragma unroll
        for (int i = 0; i < 4; i++) fft_cols<0>(e[c][i], pa[s][i], dc2);
        wg_commit();
      };
      auto prod = [&](int c, int n) {
        const int s = c & 1;
        fence_regs(e[c][2 * n]);
        fence_regs(e[c][2 * n + 1]);
#pragma unroll
        for (int j = 0; j < 2; j++) {
          const C2 u0 = cget(e[s][2 * n], j, 0), u1 = cget(e[s][2 * n], j, 1);
          const C2 h0 = cget(e[s][2 * n + 1], j, 0), h1 = cget(e[s][2 * n + 1], j, 1);
          C2 y0, y1;
          if (c < 2) {
            y0 = cmul(h0, u0);
            s1[s][n][j] = cfma(h0, u1, cmul(h1, u0));
            y1 = C2{hadd2(s1[s][n][j].r, y0.i), hadd2(s1[s][n][j].i, hneg2(y0.r))};
          } else {
            const C2 u2 = cget(e[c][2 * n], j, 0), u3 = cget(e[c][2 * n], j, 1);
            const C2 h2 = cget(e[c][2 * n + 1], j, 0), h3 = cget(e[c][2 * n + 1], j, 1);
            const C2 s2 = cfma(h0, u2, cfma(h2, u0, cmul(h1, u1)));
            y0 = C2{hadd2(s2.r, s1[s][n][j].i), hadd2(s2.i, hneg2(s1[s][n][j].r))};
            y1 = cfma(h0, u3, cfma(h1, u2, cfma(h2, u1, cfma(h3, u0, C2{s2.i, hneg2(s2.r)}))));
          }
          ya[s][n][j][0] = y0.r;
          ya[s][n][j][1] = y1.r;
          ya[s][n][j][2] = y0.i;
          ya[s][n][j][3] = y1.i;
        }
      };
      auto icols = [&](int c) {
        wg_fence();
        fft_cols<1>(v[c & 1][0], ya[c & 1][0], dc3);
        fft_cols<1>(v[c & 1][1], ya[c & 1][1], dc3);
        wg_commit();
      };
      auto stage = [&](int c) {
        const int s = c & 1;
        fence_regs(v[s][0]);
        fence_regs(v[s][1]);
#pragma unroll
        for (int b = 0; b < 4; b++) {
          const C2 x0 = cget(v[s][b >> 1], 0, b & 1), x1 = cget(v[s][b >> 1], 1, b & 1);
          const C2 z0 = crot(C2{x0.i, x0.r}, t[0]), z1 = crot(C2{x1.i, x1.r}, t[1]);
          stsm4(zs + uo(c) + b * 4096, z0.i, z0.r, z1.i, z1.r);
        }
      };
      auto back = [&](int c) {
        fft_back(o[c & 1], dz + (uo(c) >> 4), dc4);
        wg_commit();
      };
      auto out = [&](int c) {
        float (&r)[16] = o[c & 1];
        fence_regs(r);
#pragma unroll
        for (int i = 0; i < 16; i += 8)
          stsm4t(ys + uo(c) + 64 * i, bmul2(pack_bf16(r[i], r[i + 1]), sc[c & 1]), bmul2(pack_bf16(r[i + 2], r[i + 3]), sc[c & 1]),
                 bmul2(pack_bf16(r[i + 4], r[i + 5]), sc[c & 1]), bmul2(pack_bf16(r[i + 6], r[i + 7]), sc[c & 1]));
      };
      auto signal = [&](int yb, int land) {
        __syncwarp();
        if (lane == 0) {
          mbar_arrive_cluster(ybar + 8 * yb);
          if (own && land >= 0) mbar_arrive(bars + 8 * (BAR_LAND + land));
        }
      };
      wg_fence();
      rows(0);
      rows(1);
      fence_async_smem();
      nb_arrive(NB_OREADY, 288);
      PROF(34 + wg);
      wg_wait<1>();
      cols(0);
      wg_wait<1>();
      cols(1);
      rows(2);
      nb_sync(NB_CONV + wg, 128);
      wg_wait<2>();
      prod(0, 0);
      prod(0, 1);
      icols(0);
      wg_wait<2>();
      prod(1, 0);
      prod(1, 1);
      icols(1);
      PROF3(40 + 10 * wg);
      wg_wait<1>();
      stage(0);
      wg_wait<0>();
      stage(1);
      fence_async_smem();
      cols(2);
      PROF3(41 + 10 * wg);
      nb_sync(NB_CONV + wg, 128);
      back(0);
      back(1);
      wg_wait<2>();
      wg_fence();
      rows(3);
      prod(2, 0);
      wg_wait<1>();
      out(0);
      out(1);
      signal(wg, 0);
      PROF3(42 + 10 * wg);
      prod(2, 1);
      icols(2);
      wg_wait<1>();
      cols(3);
      PROF3(43 + 10 * wg);
      wg_wait<1>();
      stage(2);
      fence_async_smem();
      wg_wait<0>();
      prod(3, 0);
      nb_sync(NB_CONV + wg, 128);
      wg_fence();
      back(2);
      prod(3, 1);
      icols(3);
      PROF3(44 + 10 * wg);
      wg_wait<1>();
      out(2);
      signal(2, -1);
      wg_wait<0>();
      stage(3);
      PROF3(45 + 10 * wg);
      fence_async_smem();
      nb_sync(NB_CONV + wg, 128);
      wg_fence();
      back(3);
      constexpr int G = MODE == 0 && EARLY;
      if (MODE == 0) mbar_wait(bars + 8 * (BAR_EMPTY2 + 4), 0);
      if (G) g2_block(true, 0, 0);
      wg_wait<G>();
      if (lane == 0) mbar_arrive_cluster(mapa(bars, 1) + 8 * BAR_TAB);
      out(3);
      signal(3, 1);
      PROF(6 + wg);
    }
    }

    if (MODE != 1) {
      if (MODE == 2 || !EARLY) g2_block(true, 0, 0);
      const int lr = lane & 7, lm = lane >> 3;
      const uint32_t wb = sb + g2_a(1, 0) + warp * 2048;
      const int orow = (rb2 & 7) * 128 + warp * 16;
      uint4* og = reinterpret_cast<uint4*>(p.out + (size_t)(2 * (orow + lm) + (rb2 >> 3)) * (2 * DM) + DM + cb2 * 128 + lr * 8);
      uint32_t wst = wb + (lr + 8 * (lm & 1)) * 128, wsx = ((lm >> 1) ^ lr) << 4, wld = wb + lm * 128, wlx = (lr ^ lm) << 4;
      asm volatile("" : "+l"(og), "+r"(wst), "+r"(wsx), "+r"(wld), "+r"(wlx));
      static_assert(ENDG == NS2 && (G2SEQ >> 4 & 0xfffff) == (G2SEQ >> 24 & 0xfffff) && (G2SEQ >> 4 & 0xfffff) == G2SEQ >> 44, "rounds");
#pragma unroll 1
      for (int r = 0; r < 3; r++) {
        const bool hold = r == 2 && wg != LEADWG;
        const uint32_t rel0 = g2rel + (r ? 8 * (G2SEQ >> 20 & 7) : 0);
        if (hold) {
          wg_wait<0>();
          if (signaller) mbar_arrive_cluster(rel0);
          nb_sync(NB_LEAD, 256);
        }
#pragma unroll
        for (int i = 1; i <= NS2; i++) {
          const int s = G2SEQ >> (4 * i) & 7;
          g2_block(false, s, (r & 1) ^ (s == 0));
          if (warp == LEADWG * 4) PROF2(40 + 5 * r + i);
          if (i == 1 ? !hold : r < 2) {
            wg_wait<1>();
            if (signaller) mbar_arrive_cluster(i == 1 ? rel0 : g2rel + 8 * (G2SEQ >> (4 * i - 4) & 7));
          }
        }
        if (r == 0) PROF(8 + wg);
        g2a += p.zero;
        g2b += p.zero;
      }
      if (wg == LEADWG) nb_arrive(NB_LEAD, 256);
      wg_wait<0>();
      fence_regs(acc);
      PROF(10 + wg);
#pragma unroll
      for (int h = 0; h < 2; h++) {
        const uint32_t b = h * (g2_a(3, 0) - g2_a(1, 0));
#pragma unroll
        for (int j = 8 * h; j < 8 * h + 8; j += 2)
          stsm4(wst + b + (wsx ^ ((j & 7) << 4)), pack_bf16(acc[4 * j], acc[4 * j + 1]),
                pack_bf16(acc[4 * j + 2], acc[4 * j + 3]), pack_bf16(acc[4 * j + 4], acc[4 * j + 5]),
                pack_bf16(acc[4 * j + 6], acc[4 * j + 7]));
        if (OTMA == 2 || (OTMA == 1 && wg == LEADWG)) {
          fence_async_smem();
          __syncwarp();
          if (elect_one()) {
            tma_store_3d(&tmOb, wb + b, DM + cb2 * 128 + h * 64, rb2 >> 3, orow);
            bulk_commit();
          }
        } else {
          __syncwarp();
          uint4 v[4];
#pragma unroll
          for (int i = 0; i < 4; i++) v[i] = lds128(wld + b + i * 512 + (wlx ^ ((i & 1) << 6)));
#pragma unroll
          for (int i = 0; i < 4; i++) og[(size_t)i * 8 * (2 * DM / 8) + h * 8] = v[i];
        }
      }
      PROF(12 + wg);
      if (OTMA) bulk_wait0();
    }
    cluster_sync_all();
  }
}

typedef CUresult (*EncodeFn)(CUtensorMap*, CUtensorMapDataType, cuuint32_t, void*, const cuuint64_t*, const cuuint64_t*,
                             const cuuint32_t*, const cuuint32_t*, CUtensorMapInterleave, CUtensorMapSwizzle,
                             CUtensorMapL2promotion, CUtensorMapFloatOOBfill);

void make_map(EncodeFn enc, CUtensorMap* tm, const void* base, int rank, const cuuint64_t* dims, const cuuint64_t* strides,
              const cuuint32_t* box, CUtensorMapSwizzle swz) {
  cuuint32_t es[5] = {1, 1, 1, 1, 1};
  enc(tm, CU_TENSOR_MAP_DATA_TYPE_BFLOAT16, rank, const_cast<void*>(base), dims, strides, box, es,
      CU_TENSOR_MAP_INTERLEAVE_NONE, swz, CU_TENSOR_MAP_L2_PROMOTION_L2_256B, CU_TENSOR_MAP_FLOAT_OOB_FILL_NONE);
}

}

extern "C" void kernel_launch(void* const* d_in, const int* in_sizes, int n_in, void* d_out, int out_size) {
  static EncodeFn enc = nullptr;
  static bool coresident = true;
  if (!enc) {
    void* fn = nullptr;
    cudaDriverEntryPointQueryResult qr;
    cudaGetDriverEntryPoint("cuTensorMapEncodeTiled", &fn, cudaEnableDefault, &qr);
    enc = (EncodeFn)fn;
    cudaFuncSetAttribute(fused_kernel<0>, cudaFuncAttributeMaxDynamicSharedMemorySize, SMEM_BYTES);
    cudaFuncSetAttribute(fused_kernel<1>, cudaFuncAttributeMaxDynamicSharedMemorySize, SMEM_BYTES);
    cudaFuncSetAttribute(fused_kernel<2>, cudaFuncAttributeMaxDynamicSharedMemorySize, SMEM_BYTES);
    cudaLaunchConfig_t cfg = {};
    cfg.gridDim = dim3(NCTA);
    cfg.blockDim = dim3(NTHREADS);
    cfg.dynamicSmemBytes = SMEM_BYTES;
    cudaLaunchAttribute at;
    at.id = cudaLaunchAttributeClusterDimension;
    at.val.clusterDim.x = 2;
    at.val.clusterDim.y = 1;
    at.val.clusterDim.z = 1;
    cfg.attrs = &at;
    cfg.numAttrs = 1;
    int nclusters = 0;
    if (cudaOccupancyMaxActiveClusters(&nclusters, fused_kernel<0>, &cfg) == cudaSuccess) coresident = nclusters >= NCTA / 2;
    (void)cudaGetLastError();
  }
  CUtensorMap tmX, tmW, tmWo, tmWp, tmQ, tmOb, tmXh, tmWh;
  {
    cuuint64_t dims[3] = {1024, 2, 1024};
    cuuint64_t str[2] = {2048, 4096};
    cuuint32_t box[3] = {64, 1, 128};
    make_map(enc, &tmX, d_in[6], 3, dims, str, box, CU_TENSOR_MAP_SWIZZLE_128B);
  }
  {
    cuuint64_t dims[3] = {1024, 1024, 3};
    cuuint64_t str[2] = {6144, 2048};
    cuuint32_t box[3] = {64, 32, 3};
    make_map(enc, &tmW, d_in[7], 3, dims, str, box, CU_TENSOR_MAP_SWIZZLE_128B);
  }
  {
    cuuint64_t dims[3] = {64, 1024, 16};
    cuuint64_t str[2] = {2048, 128};
    cuuint32_t box[3] = {64, 64, 2};
    cuuint32_t piece[3] = {64, 32, 1};
    make_map(enc, &tmWo, d_in[8], 3, dims, str, box, CU_TENSOR_MAP_SWIZZLE_128B);
    make_map(enc, &tmWp, d_in[8], 3, dims, str, piece, CU_TENSOR_MAP_SWIZZLE_128B);
  }
  {
    cuuint64_t dims[5] = {1024, 2, 2, 4, 128};
    cuuint64_t str[4] = {2048, 8 * 2048, 2 * 2048, 16 * 2048};
    cuuint32_t box[5] = {16, 2, 2, 4, 32};
    make_map(enc, &tmQ, d_in[0], 5, dims, str, box, CU_TENSOR_MAP_SWIZZLE_NONE);
  }
  {
    cuuint64_t dims[3] = {2048, 2, 1024};
    cuuint64_t str[2] = {4096, 8192};
    cuuint32_t box[3] = {64, 1, 16};
    make_map(enc, &tmOb, d_out, 3, dims, str, box, CU_TENSOR_MAP_SWIZZLE_128B);
  }
  {
    cuuint64_t dims[4] = {1024, 256, 2, 4};
    cuuint64_t str[3] = {4096, 2048, 256 * 4096};
    cuuint32_t box[4] = {64, 8, 2, 3};
    make_map(enc, &tmXh, d_in[6], 4, dims, str, box, CU_TENSOR_MAP_SWIZZLE_128B);
  }
  {
    cuuint64_t dims[3] = {64, 1024, 48};
    cuuint64_t str[2] = {6144, 128};
    cuuint32_t box[3] = {64, 64, 4};
    make_map(enc, &tmWh, d_in[7], 3, dims, str, box, CU_TENSOR_MAP_SWIZZLE_128B);
  }
  Params p;
  p.q = (const __nv_bfloat16*)d_in[0];
  p.k = (const __nv_bfloat16*)d_in[1];
  p.v = (const __nv_bfloat16*)d_in[2];
  p.shift_k = (const __nv_bfloat16*)d_in[3];
  p.ssm_k = (const __nv_bfloat16*)d_in[4];
  p.ssm_D = (const __nv_bfloat16*)d_in[5];
  p.x = (const __nv_bfloat16*)d_in[6];
  p.w = (const __nv_bfloat16*)d_in[7];
  p.wo = (const __nv_bfloat16*)d_in[8];
  p.out = (__nv_bfloat16*)d_out;
  p.zero = 0;
  if (coresident) {
    fused_kernel<0><<<NCTA, NTHREADS, SMEM_BYTES>>>(p, tmX, tmW, tmWo, tmWp, tmQ, tmOb, tmXh, tmWh);
  } else {
    fused_kernel<0><<<4, NTHREADS, SMEM_BYTES>>>(p, tmX, tmW, tmWo, tmWp, tmQ, tmOb, tmXh, tmWh);
    fused_kernel<1><<<NCTA, NTHREADS, SMEM_BYTES>>>(p, tmX, tmW, tmWo, tmWp, tmQ, tmOb, tmXh, tmWh);
    fused_kernel<2><<<NCTA, NTHREADS, SMEM_BYTES>>>(p, tmX, tmW, tmWo, tmWp, tmQ, tmOb, tmXh, tmWh);
  }
}
```

```cpp
#include <cuda_runtime.h>
#include <cuda.h>
#include <cuda_bf16.h>
#include <stdint.h>

namespace {

constexpr int SEQ = 2048;
constexpr int DM = 1024;
constexpr int NCTA = 132;
constexpr int NTHREADS = 384;

constexpr int STG1A = 32768;
constexpr int NS1A = 3;
constexpr int STG1B = 12288;
constexpr int NS1B = 5;
constexpr int OFF_1B = NS1A * STG1A;
constexpr int STG2 = 32768;
constexpr int NS2 = 5;
#define G2SEQ 0x0432104321043210ull
constexpr unsigned long long g2_seq() {
  unsigned long long r = G2SEQ;
  for (int kb = 0; kb < 16; kb++)
    for (int j = 0; j < kb; j++)
      if (((G2SEQ >> (4 * j)) & 7) == ((G2SEQ >> (4 * kb)) & 7)) r ^= 8ull << (4 * kb);
  return r;
}
constexpr unsigned long long G2_SEQ = g2_seq();
constexpr int g2_first4() {
  int kb = 0;
  while (((G2SEQ >> (4 * kb)) & 7) != 4) kb++;
  return kb;
}
constexpr int G2_KB4 = g2_first4();
#define POLL0 1500
#define QORD 1
#define BDEL 0
#define WOP 0
#define PSTEP 1250
#define FPACE 260
#define LEADWG 1
#define OTMA 1
#define EARLY 1
#define R3 0
#define FSL 50
#define JS 1
#define FPACE2 230
#define PFR 1
#define PF2 2
#define PF2X 1
#define ENDG 5
__device__ __forceinline__ uint32_t g2_a(int s, int hsel) { return (((0x97524 >> (4 * s)) & 15) ^ (s & 5 ? 0 : hsel)) << 14; }
constexpr int OFF_Q0 = 3 << 14, OFF_Q1 = 8 << 14;
constexpr int STGH = 73728;
constexpr int OFF_KH = 1 * STG2;
constexpr int OFF_OP = 2 * STG2;
constexpr int OFF_T32 = 5 * STG2 - 4096;
constexpr int OFF_X = 5 * STG2;
constexpr int XT = 8192;
__device__ __forceinline__ uint32_t g2_b(int s, int rank) {
  return s < 3 ? (s == 2 ? 6 : s) << 14 : OFF_X + (s - 3) * 2 * XT + (rank ^ 1) * 4096;
}
__device__ __forceinline__ uint32_t g2_bk(int s) { return s < 3 ? 4096 : 4 * XT; }
constexpr int OFF_BAR = OFF_X + 8 * XT;
constexpr int OFF_EX = OFF_BAR + 448;
constexpr int OFF_T16 = 230400;
constexpr int SMEM_BYTES = OFF_T16 + 2048;
static_assert(OFF_1B + NS1B * STG1B <= OFF_T32 && OFF_X % 1024 == 0, "layout");
static_assert(3 * STGH <= OFF_BAR && OFF_EX + 64 <= OFF_T16 && SMEM_BYTES <= 232448, "smem");

constexpr int BAR_FULLA = 0;
constexpr int BAR_EMPTYA = 3;
constexpr int BAR_FULLB = 6;
constexpr int BAR_EMPTYB = 11;
constexpr int BAR_FULL2 = 16;
constexpr int BAR_EMPTY2 = 21;
constexpr int BAR_EMPTY2B = 44;
constexpr int BAR_X = 26;
constexpr int BAR_LAND = 42;
constexpr int BAR_TAB = 28;
constexpr int BAR_U = 29;
constexpr int BAR_H = 30;
constexpr int BAR_STG = 31;
constexpr int BAR_Y = 32;
constexpr int BAR_XFREE = 38;
constexpr int BAR_HALO = 40;
constexpr int BAR_Q = 41;

constexpr int NB_G1DONE = 1;
constexpr int NB_LEAD = 2;
constexpr int NB_G1END = 3;
constexpr int NB_OREADY = 4;
constexpr int NB_CONV = 5;
constexpr int NB_HELP3 = 11;
constexpr int NB_FIRST = 13;

#define REG_MATH 224
#define REG_HELP 56
constexpr int SPIN_LIMIT = 1 << 20;

__device__ __align__(1024) __nv_bfloat16 g_o[SEQ * DM];
__device__ uint32_t g_flag_o[128];
__device__ uint32_t g_flag_h[4];
__device__ uint4 g_halo[128 * 128];
__device__ __align__(128) const uint32_t g_tab[2048] = {
  0x2fd93000,0x2ea72f64,0x2c722da8,0x263e2a1f,0x2ea73000,0xa63e2a1f,0xafd9ada8,0xac72af64,0x2c723000,0xafd9aa1f,0x263eada8,0x2ea72f64,
  0x263e3000,0xac72af64,0x2ea72da8,0xafd9aa1f,0xa63e3000,0x2c72af64,0xaea72da8,0x2fd9aa1f,0xac723000,0x2fd9aa1f,0xa63eada8,0xaea72f64,
  0xaea73000,0x263e2a1f,0x2fd9ada8,0x2c72af64,0xafd93000,0xaea72f64,0xac722da8,0xa63e2a1f,0x263e0000,0x2c722a1f,0x2ea72da8,0x2fd92f64,
  0x2c720000,0x2fd92f64,0x263e2da8,0xaea7aa1f,0x2ea70000,0x263e2f64,0xafd9ada8,0x2c72aa1f,0x2fd90000,0xaea72a1f,0x2c72ada8,0xa63e2f64,
  0x2fd90000,0xaea7aa1f,0x2c722da8,0xa63eaf64,0x2ea70000,0x263eaf64,0xafd92da8,0x2c722a1f,0x2c720000,0x2fd9af64,0x263eada8,0xaea72a1f,
  0x263e0000,0x2c72aa1f,0x2ea7ada8,0x2fd9af64,0xafd93000,0xaea72f64,0xac722da8,0xa63e2a1f,0xaea73000,0x263e2a1f,0x2fd9ada8,0x2c72af64,
  0xac723000,0x2fd9aa1f,0xa63eada8,0xaea72f64,0xa63e3000,0x2c72af64,0xaea72da8,0x2fd9aa1f,0x263e3000,0xac72af64,0x2ea72da8,0xafd9aa1f,
  0x2c723000,0xafd9aa1f,0x263eada8,0x2ea72f64,0x2ea73000,0xa63e2a1f,0xafd9ada8,0xac72af64,0x2fd93000,0x2ea72f64,0x2c722da8,0x263e2a1f,
  0xa63e0000,0xac722a1f,0xaea72da8,0xafd92f64,0xac720000,0xafd92f64,0xa63e2da8,0x2ea7aa1f,0xaea70000,0xa63e2f64,0x2fd9ada8,0xac72aa1f,
  0xafd90000,0x2ea72a1f,0xac72ada8,0x263e2f64,0xafd90000,0x2ea7aa1f,0xac722da8,0x263eaf64,0xaea70000,0xa63eaf64,0x2fd92da8,0xac722a1f,
  0xac720000,0xafd9af64,0xa63eada8,0x2ea72a1f,0xa63e0000,0xac72aa1f,0xaea7ada8,0xafd9af64,0xa63e0000,0xac72aa1f,0xaea7ada8,0xafd9af64,
  0xac720000,0xafd9af64,0xa63eada8,0x2ea72a1f,0xaea70000,0xa63eaf64,0x2fd92da8,0xac722a1f,0xafd90000,0x2ea7aa1f,0xac722da8,0x263eaf64,
  0xafd90000,0x2ea72a1f,0xac72ada8,0x263e2f64,0xaea70000,0xa63e2f64,0x2fd9ada8,0xac72aa1f,0xac720000,0xafd92f64,0xa63e2da8,0x2ea7aa1f,
  0xa63e0000,0xac722a1f,0xaea72da8,0xafd92f64,0x2fd93000,0x2ea72f64,0x2c722da8,0x263e2a1f,0x2ea73000,0xa63e2a1f,0xafd9ada8,0xac72af64,
  0x2c723000,0xafd9aa1f,0x263eada8,0x2ea72f64,0x263e3000,0xac72af64,0x2ea72da8,0xafd9aa1f,0xa63e3000,0x2c72af64,0xaea72da8,0x2fd9aa1f,
  0xac723000,0x2fd9aa1f,0xa63eada8,0xaea72f64,0xaea73000,0x263e2a1f,0x2fd9ada8,0x2c72af64,0xafd93000,0xaea72f64,0xac722da8,0xa63e2a1f,
  0x263e0000,0x2c72aa1f,0x2ea7ada8,0x2fd9af64,0x2c720000,0x2fd9af64,0x263eada8,0xaea72a1f,0x2ea70000,0x263eaf64,0xafd92da8,0x2c722a1f,
  0x2fd90000,0xaea7aa1f,0x2c722da8,0xa63eaf64,0x2fd90000,0xaea72a1f,0x2c72ada8,0xa63e2f64,0x2ea70000,0x263e2f64,0xafd9ada8,0x2c72aa1f,
  0x2c720000,0x2fd92f64,0x263e2da8,0xaea7aa1f,0x263e0000,0x2c722a1f,0x2ea72da8,0x2fd92f64,0xafd93000,0xaea72f64,0xac722da8,0xa63e2a1f,
  0xaea73000,0x263e2a1f,0x2fd9ada8,0x2c72af64,0xac723000,0x2fd9aa1f,0xa63eada8,0xaea72f64,0xa63e3000,0x2c72af64,0xaea72da8,0x2fd9aa1f,
  0x263e3000,0xac72af64,0x2ea72da8,0xafd9aa1f,0x2c723000,0xafd9aa1f,0x263eada8,0x2ea72f64,0x2ea73000,0xa63e2a1f,0xafd9ada8,0xac72af64,
  0x2fd93000,0x2ea72f64,0x2c722da8,0x263e2a1f,0xa63e0000,0xac72aa1f,0xaea7ada8,0xafd9af64,0x2c720000,0x2fd92f64,0x263e2da8,0xaea7aa1f,
  0xaea70000,0xa63eaf64,0x2fd92da8,0xac722a1f,0x2fd90000,0xaea72a1f,0x2c72ada8,0xa63e2f64,0xafd90000,0x2ea72a1f,0xac72ada8,0x263e2f64,
  0x2ea70000,0x263eaf64,0xafd92da8,0x2c722a1f,0xac720000,0xafd92f64,0xa63e2da8,0x2ea7aa1f,0x263e0000,0x2c72aa1f,0x2ea7ada8,0x2fd9af64,
  0x2fd93000,0x2ea72f64,0x2c722da8,0x263e2a1f,0xaea7b000,0x263eaa1f,0x2fd92da8,0x2c722f64,0x2c723000,0xafd9aa1f,0x263eada8,0x2ea72f64,
  0xa63eb000,0x2c722f64,0xaea7ada8,0x2fd92a1f,0xa63e3000,0x2c72af64,0xaea72da8,0x2fd9aa1f,0x2c72b000,0xafd92a1f,0x263e2da8,0x2ea7af64,
  0xaea73000,0x263e2a1f,0x2fd9ada8,0x2c72af64,0x2fd9b000,0x2ea7af64,0x2c72ada8,0x263eaa1f,0x263e0000,0x2c72aa1f,0x2ea7ada8,0x2fd9af64,
  0xac720000,0xafd92f64,0xa63e2da8,0x2ea7aa1f,0x2ea70000,0x263eaf64,0xafd92da8,0x2c722a1f,0xafd90000,0x2ea72a1f,0xac72ada8,0x263e2f64,
  0x2fd90000,0xaea72a1f,0x2c72ada8,0xa63e2f64,0xaea70000,0xa63eaf64,0x2fd92da8,0xac722a1f,0x2c720000,0x2fd92f64,0x263e2da8,0xaea7aa1f,
  0xa63e0000,0xac72aa1f,0xaea7ada8,0xafd9af64,0xafd93000,0xaea72f64,0xac722da8,0xa63e2a1f,0x2ea7b000,0xa63eaa1f,0xafd92da8,0xac722f64,
  0xac723000,0x2fd9aa1f,0xa63eada8,0xaea72f64,0x263eb000,0xac722f64,0x2ea7ada8,0xafd92a1f,0x263e3000,0xac72af64,0x2ea72da8,0xafd9aa1f,
  0xac72b000,0x2fd92a1f,0xa63e2da8,0xaea7af64,0x2ea73000,0xa63e2a1f,0xafd9ada8,0xac72af64,0xafd9b000,0xaea7af64,0xac72ada8,0xa63eaa1f,
  0xafd9b000,0xaea7af64,0xac72ada8,0xa63eaa1f,0x2ea73000,0xa63e2a1f,0xafd9ada8,0xac72af64,0xac72b000,0x2fd92a1f,0xa63e2da8,0xaea7af64,
  0x263e3000,0xac72af64,0x2ea72da8,0xafd9aa1f,0x263eb000,0xac722f64,0x2ea7ada8,0xafd92a1f,0xac723000,0x2fd9aa1f,0xa63eada8,0xaea72f64,
  0x2ea7b000,0xa63eaa1f,0xafd92da8,0xac722f64,0xafd93000,0xaea72f64,0xac722da8,0xa63e2a1f,0xa63e0000,0xac72aa1f,0xaea7ada8,0xafd9af64,
  0x2c720000,0x2fd92f64,0x263e2da8,0xaea7aa1f,0xaea70000,0xa63eaf64,0x2fd92da8,0xac722a1f,0x2fd90000,0xaea72a1f,0x2c72ada8,0xa63e2f64,
  0xafd90000,0x2ea72a1f,0xac72ada8,0x263e2f64,0x2ea70000,0x263eaf64,0xafd92da8,0x2c722a1f,0xac720000,0xafd92f64,0xa63e2da8,0x2ea7aa1f,
  0x263e0000,0x2c72aa1f,0x2ea7ada8,0x2fd9af64,0x2fd9b000,0x2ea7af64,0x2c72ada8,0x263eaa1f,0xaea73000,0x263e2a1f,0x2fd9ada8,0x2c72af64,
  0x2c72b000,0xafd92a1f,0x263e2da8,0x2ea7af64,0xa63e3000,0x2c72af64,0xaea72da8,0x2fd9aa1f,0xa63eb000,0x2c722f64,0xaea7ada8,0x2fd92a1f,
  0x2c723000,0xafd9aa1f,0x263eada8,0x2ea72f64,0xaea7b000,0x263eaa1f,0x2fd92da8,0x2c722f64,0x2fd93000,0x2ea72f64,0x2c722da8,0x263e2a1f,
  0x263e0000,0x2c72aa1f,0x2ea7ada8,0x2fd9af64,0xac720000,0xafd92f64,0xa63e2da8,0x2ea7aa1f,0x2ea70000,0x263eaf64,0xafd92da8,0x2c722a1f,
  0xafd90000,0x2ea72a1f,0xac72ada8,0x263e2f64,0x2fd90000,0xaea72a1f,0x2c72ada8,0xa63e2f64,0xaea70000,0xa63eaf64,0x2fd92da8,0xac722a1f,
  0x2c720000,0x2fd92f64,0x263e2da8,0xaea7aa1f,0xa63e0000,0xac72aa1f,0xaea7ada8,0xafd9af64,0x316c2fbd,0x343e32f7,0x35bc34ff,0x372c3676,
  0x371532c6,0x3a81392e,0x3bef3b71,0x3b7c3bf2,0x397034cf,0x3bfc3b6c,0x38b23b04,0xb40e31e8,0x3ae13631,0x39e73bf5,0xb6e83219,0xbbe8bb13,
  0x3bc23785,0x30be3aa9,0xbbfdb911,0x2a16b9aa,0x3bfe3865,0xb80f37a6,0xb82abc00,0x3bfd376f,0x3b9238fd,0xbb7f2311,0x3805b929,0x31223bde,
  0x3a85398b,0xbb96b742,0x3bff319e,0xbbb82f8b,0xbbe2bbf1,0xbbb7bbcf,0xbb78bb9a,0xbb27bb52,0xbb2cbbd2,0xb8a8ba19,0xb029b5df,0x35a52f59,
  0xb9dfbba1,0x2ba7b5f7,0x3a7a37b2,0x3bbd3bdd,0xb815bb60,0x39662e91,0x3b373bda,0xb0d7377a,0xb3d3bb10,0x3be9386f,0x2a7a3a31,0xbbfeb9a6,
  0x294dbab0,0x3ae53b07,0xbad51fdb,0xab43bb16,0x352fba41,0x35993c00,0xbaebba1d,0x3be531cf,0x38a3b9c5,0xb5173b21,0x2776bbe0,0x34323bf2,
  0x384537dd,0x38ea3899,0x39823937,0x3a0d39c9,0x39463a93,0x3340374e,0xb426a452,0xb979b7c8,0xbb45b924,0xbb32bc00,0xb371b902,0x38d63294,
  0xb08db9a1,0x3b3f379b,0x39583bd7,0xb8252dfb,0x3bea3a2d,0xb3ba3874,0xbb89bb0d,0x36d2b625,0xb6bb387f,0xb8d1bbf5,0x3be73602,0xb546391f,
  0xba00bb01,0x3bff35eb,0xba5c34db,0x3359bab6,0x3ac7b66b,0xb9413933,0x368dbabd,0xb0103bb3,0xbac4baf7,0xba50ba8c,0xb9cdba11,0xb93cb986,
  0x3a04388e,0x3bcb3b1e,0x3bba3c00,0x39d63afe,0x36af3a21,0xb6ffa17f,0xbbc8ba3d,0xba60bbd4,0xbbebb9af,0xb6c6bb0a,0x39f43263,0x3ad83bf7,
  0x30a6b916,0x3bc33aa5,0xb55e3790,0xbb3dbb63,0x3b423a9e,0xba642ec3,0xb0f0bb6a,0x3b8e3a25,0xb94a37bd,0x2884bb6f,0x38db3b9f,0xbbc9b85a,
  0xb840bb54,0x3a093a15,0xbb4cb850,0x3bef3457,0x3a893a4d,0x3af43ac1,0x3b4f3b24,0x3b983b76,0xbb94baba,0xbbe4bbf9,0xba58bb57,0xb699b8f8,
  0x3bfe3b18,0x394f3b5c,0xb109347b,0xbae8b884,0xbbc0bb68,0xa9b1b90c,0x3b8b387a,0x38bc3ba5,0x3ade3ba7,0xb8c1324b,0xb9f0bbf6,0x39eb9648,
  0xb96bbbd6,0x3bbf3487,0xb38939b3,0xb9f8bba3,0x370a3bf3,0xbb47b994,0x3bbc2d65,0xb8ad3889,0xb153bc00,0x37213b9c,0xb97dba90,0x3af138f3,
  0xb89eb8ee,0xb7e8b84a,0xb682b737,0xb50bb5c8,0x35233855,0xb13b2d33,0xb8e0b65f,0xbb4aba45,0xa8e8b764,0x39fc3648,0x3be63bae,0x380a3a9b,
  0xb3eb360e,0xbbfeba35,0xb552baa2,0x3a7334b7,0x381ab4ab,0x3a6f3bd8,0xb95d2e5f,0xb962bc00,0xb9e3327c,0xb402bbac,0x3bc6399d,0xb95434c3,
  0x3b2faf27,0xb6a439bc,0xb41abbf9,0x3a7e3a97,0xbbe3251b,0x3b2ab4f3,0xb9d23894,0x37f3ba49,0x3bce3bb5,0x3bf03be1,0x3bff3bfa,0x3bfb3bff,
  0x2c38b1b6,0x383a34e7,0x3aee39c0,0x3bff3bb2,0xbb81bbf8,0xb53ab999,0x38302ef5,0x3bed3ab3,0xb8cc9cb6,0xbb85bbab,0x2adeb86a,0x3bc5391b,
  0x38c73bf6,0xbadbb232,0xb6ddbba9,0x3b87361a,0x3b833201,0xb0743a39,0xba76bb5e,0x3b352dc9,0xac06bbb0,0x39743b59,0xbbeeb759,0x3aceb2ad,
  0xbbccb5d4,0x3bfb2d00,0xbb7a32de,0x3a54b7d2,0xb30fb44b,0xafefb185,0xa6adacce,0x2c9c25e4,0xbbfcbbdf,0xbacbbb9e,0xb7feb990,0xa81fb463,
  0xb58d2d97,0xbb90b9b8,0xbad1bbf4,0xb05bb85f,0x3a673c00,0xb5763493,0xbbfdbaac,0xb3a2ba29,0x3a6b2e2d,0x38203bd9,0xbb3ab49f,0xb56abb65,
  0xb581bbdc,0x3bec3907,0xb8b7363c,0xb6f4bbf8,0xbbfcb46f,0x39dab654,0xb0423b1b,0xb835bbd3,0xb3283b73,0xac6abbfa,0x35b13bd0,0xb8e5bafb,
  0x38ee3a0d,0xb84aba89,0x37373af4,0xb5c8bb4f,0x35df3a81,0x2f59bbef,0xb88e3b7c,0x3b1eb946,0x2d973ae8,0x39b8bb81,0xbbf4353a,0x385f3830,
  0xb2633b3f,0x3bf7b958,0xb60eb825,0xba353bc0,0xb7853b87,0x3aa9b3d3,0x3911bbe9,0xb9aa2a7a,0xb99d3bbf,0x34c33389,0x3bdcb9f8,0x3907bb83,
  0xbb013be5,0xb5eb394a,0x34db2884,0x3ab6b8db,0xbbd03bfb,0xbafb3b7a,0xb98b3a54,0xb74238a3,0x3a4db93c,0xbac1389e,0x3b24b7e8,0xbb763682,
  0x3b71b8a8,0xbbf23029,0x3a9335a5,0xb74eba04,0x3bf8b80a,0xb999b58d,0xaef53b90,0x3ab3bad1,0x3bd7b6c6,0xadfbb9f4,0xbb683ad8,0x390c33eb,
  0x3b10b56a,0x386fbbc2,0xba3130be,0xb9a63bfd,0x39b3b402,0x3ba3bbc6,0x3201b954,0xba393581,0x37bdb122,0x3b6fba00,0x3b9fbbff,0x385aba5c,
  0x32deac6a,0x37d2b5b1,0x39c5b8e5,0x3b21ba85,0x344b3b98,0xb185bbce,0x2cce3bf0,0x25e4bbff,0xbc003340,0x3afe3426,0xb855b979,0x2d333b94,
  0x34cfbbed,0xbb6c39df,0x3b042ba7,0xb1e8ba7a,0x3aa2a9b1,0x34b7bb8b,0xbc0038bc,0x349338cc,0xba2d3bfe,0x387430a6,0x3b0dbbc3,0xb625b55e,
  0xb63cb074,0xbbf83a76,0xb8653b35,0x37a6294d,0x3bf3bbc9,0x3994bb2f,0x2d65b6a4,0xb889341a,0xb19e3517,0x2f8b2776,0x366bb432,0x3933b840,
  0x3bb5b50b,0xbbe1330f,0x3bfaafef,0xbbff26ad,0xa4523bcb,0x37c8bbba,0xbaba39d6,0x3bf9b523,0xbba1305b,0x35f73970,0x37b2bbfc,0xbbdd38b2,
  0x387abbfe,0xbba53552,0x9cb63a73,0x3babba67,0x39162a16,0x3aa5bbea,0xb790b3ba,0xbb633b89,0xbb5e3bec,0xadc938b7,0x3ab0b6f4,0x3b07bbfe,
  0xaf27b359,0xb9bc370a,0xbbf93b47,0xba973bbc,0x3be0bb96,0x3bf2bbff,0x3b54bbb8,0x3a15bac7,0xafbd3bfb,0x32f7bbe2,0xb4ff3bb7,0x3676bb78,
  0x365fbbe4,0xba453a58,0x3bdfb699,0xbb9eac38,0xb9243bbd,0x3c00b6af,0xb902b6ff,0xb2943bc8,0x3aacbb85,0xba29aade,0xb6313bc5,0x3bf5b815,
  0xbba73b3d,0x324b381a,0x3bf6ba6f,0x9648b95d,0x3c00bae5,0x376fbad5,0xb87f2b43,0xbbf53b42,0xbbb03a7e,0xbb593bfc,0xb75939da,0x32ad3042,
  0x3abdba09,0x3bb3bb4c,0x3c00bbef,0x3b9cbbe3,0x3bf12c9c,0xbbcfb16c,0x3b9a343e,0xbb52b5bc,0xbb57b13b,0x38f838e0,0xb1b6bb4a,0xb4e73bfc,
  0x3a21340e,0x217fbb45,0xba3d3b32,0x3bd4b371,0xb86ab576,0xb91b3bfd,0x3b60b3a2,0x2e91bae1,0x34ab36d2,0x3bd8bade,0xae5fb8c1,0xbc0039f0,
  0x9fdbb80f,0xbb16382a,0xba9e3bfd,0x2ec336bb,0xb46f38ad,0x3654ac06,0x3b1bb974,0x3bd3bbee,0x3850b941,0x3457b68d,0xa51bb010,0xb4f33153,
  0xb7dd3b27,0x3899bac4,0xb9373a50,0x39c9b9cd,0x3990383a,0xb463baee,0xb2c63bff,0x392ebb2c,0x3b18ba60,0xbb5c28e8,0x347b39fc,0x3884bbe6,
  0xb219b966,0xbb133b37,0x39a130d7,0x379bbbeb,0xbbf63962,0xb2323a6b,0x3ba9b820,0x361abb3a,0xb6023a64,0x391fb0f0,0x3bd6bb8e,0x3487b9e3,
  0x3a41b835,0x3c00bb92,0x3a1dbb7f,0x31cfb805,0x3a90bb2a,0x38f3b9d2,0x35d4b7f3,0x2d00b328,0x3af7372c,0xba8cb845,0x3a1138ea,0xb986b982,
  0x39c0bacb,0xbbb237fe,0x3bd2a81f,0xba19b715,0xb764b8d6,0xb6483bfe,0x3baeb94f,0xba9bb109,0xbbda39e7,0x377a36e8,0x39afbbe8,0xbb0a308d,
  0xae2d39eb,0x3bd9b8c7,0x349fbadb,0xbb6536dd,0x3b6ab8d1,0x3a25bbe7,0xb27cb546,0xbbac396b,0x38fdbace,0xa311b52f,0xb9293599,0xbbde3aeb,
  0xb8943721,0xba49397d,0xbb733af1,0xbbfa3bcc,0xbbfb3bff,0xbbe23bf1,0xbbb73bcf,0xbb783b9a,0xbb7c3bf2,0xb9463a93,0xb340374e,0x3426a452,
  0xba603bd4,0xa8e83764,0x39fcb648,0x3be6bbae,0xb8bc3ba5,0x38cc9cb6,0x3b85bbab,0xaadeb86a,0xb56a3b65,0x3bc2b785,0x30bebaa9,0xbbfd3911,
  0xab433b16,0x3b42ba9e,0xba64aec3,0xb0f03b6a,0x33593ab6,0x370abbf3,0xbb473994,0x3bbcad65,0x37f33a49,0xb328bb73,0xac6a3bfa,0x35b1bbd0,
  0xac9c25e4,0xb16c2fbd,0xb43e32f7,0xb5bc34ff,0xb5a52f59,0xba04388e,0xbbcb3b1e,0xbbba3c00,0xb8d63294,0xbbfe3b18,0xb94f3b5c,0x3109347b,
  0xba7334b7,0xba673c00,0x35763493,0x3bfdbaac,0xbb87361a,0xb3d33b10,0x3be9b86f,0x2a7aba31,0xbbfd376f,0x36bb387f,0x38d1bbf5,0xbbe73602,
  0xbbc9385a,0x3b2f2f27,0xb6a4b9bc,0xb41a3bf9,0xbaf138f3,0x3bccb5d4,0xbbfb2d00,0x3b7a32de,0xbb273b52,0xbac43af7,0xba503a8c,0xb9cd3a11,
  0x3979b7c8,0x3b94baba,0x3be4bbf9,0x3a58bb57,0x380aba9b,0xb58dad97,0xbb9039b8,0xbad13bf4,0xbbc5391b,0xb8153b60,0x3966ae91,0x3b37bbda,
  0x2a1639aa,0x3beaba2d,0xb3bab874,0xbb893b0d,0x3b8eba25,0xb9e3b27c,0xb4023bac,0x3bc6b99d,0xb8adb889,0xac063bb0,0x3974bb59,0xbbee3759,
  0xb8e53afb,0x3a85b98b,0xbb963742,0x3bffb19e,0xb72c3676,0xb84537dd,0xb8ea3899,0xb9823937,0xb9d63afe,0xb5233855,0x313b2d33,0x38e0b65f,
  0x3ae8b884,0x3b81bbf8,0x353ab999,0xb8302ef5,0x33a2ba29,0xbae13631,0xb9e73bf5,0x36e83219,0xbbfe39a6,0x30a63916,0x3bc3baa5,0xb55eb790,
  0x3546391f,0x396bbbd6,0xbbbf3487,0x338939b3,0x3a7eba97,0xbbfc346f,0x39da3654,0xb042bb1b,0xba54b7d2,0x38a339c5,0xb517bb21,0x27763be0,
  0xb93c3986,0xb89e38ee,0xb7e8384a,0xb6823737,0x3699b8f8,0xac38b1b6,0xb83a34e7,0xbaee39c0,0xb05b385f,0x3970b4cf,0x3bfcbb6c,0x38b2bb04,
  0xb0d7b77a,0xbbeb39af,0xb6c63b0a,0x39f4b263,0x36d23625,0x3adebba7,0xb8c1b24b,0xb9f03bf6,0xb954b4c3,0xb5813bdc,0x3becb907,0xb8b7b63c,
  0x3ace32ad,0xb52fba41,0xb5993c00,0x3aebba1d,0xbbb8af8b,0x3ac7366b,0xb941b933,0x368d3abd,0xba0d39c9,0xba893a4d,0xbaf43ac1,0xbb4f3b24,
  0x3b4aba45,0x3bfcbbdf,0x3acbbb9e,0x37feb990,0xbbed3ab3,0xb9df3ba1,0x2ba735f7,0x3a7ab7b2,0x3be8bb13,0x308db9a1,0xbb3f379b,0xb9583bd7,
  0xbb3d3b63,0x381a34ab,0x3a6fbbd8,0xb95dae5f,0x39f8bba3,0xbb833201,0x30743a39,0x3a76bb5e,0xb8353bd3,0x3b92b8fd,0xbb7fa311,0x38053929,
  0x3432bbf2,0xb8403b54,0x3a09ba15,0xbb4c3850,0xb50b35c8,0xb30f344b,0xafef3185,0xa6ad2cce,0xbbff3bb2,0xbb2c3bd2,0xb8a83a19,0xb02935df,
  0xb40eb1e8,0xbb453924,0xbb323c00,0xb3713902,0x3ad8bbf7,0xb3ebb60e,0xbbfe3a35,0xb5523aa2,0x39eb1648,0x38c7bbf6,0xbadb3232,0xb6dd3ba9,
  0xb6f43bf8,0x3bfeb865,0xb80fb7a6,0xb82a3c00,0xbbe531cf,0x394a37bd,0xa884bb6f,0xb8db3b9f,0xb010bbb3,0xb1533c00,0x3721bb9c,0xb97d3a90,
  0xbb983b76,0xbbce3bb5,0xbbf03be1,0xbbff3bfa,0x281fb463,0xb71532c6,0xba81392e,0xbbef3b71,0x3bbdbbdd,0x36afba21,0xb6ff217f,0xbbc83a3d,
  0x38252dfb,0x3bc0bb68,0x29b1b90c,0xbb8b387a,0xb9623c00,0x3a6bae2d,0x3820bbd9,0xbb3a349f,0xbb352dc9,0x294d3ab0,0x3ae5bb07,0xbad59fdb,
  0x3122bbde,0xba003b01,0x3bffb5eb,0xba5cb4db,0x3befb457,0xbbe3a51b,0x3b2a34f3,0xb9d2b894,0x39c939cd,0xba4db93c,0x3ac1389e,0xbb24b7e8,
  0x3b1e3946,0xbc00b340,0x3afeb426,0xb8553979,0x3bdd38b2,0xba21340e,0xa17fbb45,0x3a3d3b32,0x3bf53815,0xb2193966,0xbb13bb37,0x39a1b0d7,
  0x3b6536dd,0x37853b87,0xbaa9b3d3,0xb911bbe9,0x3a393581,0x3b5e3bec,0x2dc938b7,0xbab0b6f4,0x3889341a,0x3bb03a7e,0x3b593bfc,0x375939da,
  0x34f33153,0x38943721,0x3a49397d,0x3b733af1,0xb9863982,0x38eeba0d,0xb84a3a89,0x3737baf4,0xb74e3a04,0xa452bbcb,0x37c83bba,0xbabab9d6,
  0xb1e83a7a,0xb924bbbd,0x3c0036af,0xb90236ff,0x2e913ae1,0xbbdab9e7,0x377ab6e8,0x39af3be8,0x361a3b3a,0xbb10b56a,0xb86fbbc2,0x3a3130be,
  0x39073b83,0xb63c3074,0xbbf8ba76,0xb865bb35,0x3a973bbc,0x346f38ad,0xb654ac06,0xbb1bb974,0x3b9c3be3,0x3a903b2a,0x38f339d2,0x35d437f3,
  0x3b763682,0xbbb5b50b,0x3be1330f,0xbbfaafef,0x2d33bb94,0x365f3be4,0xba45ba58,0x3bdf3699,0xbbd4b371,0x3764b8d6,0x36483bfe,0xbbaeb94f,
  0x379b3beb,0xbbd7b6c6,0x2dfbb9f4,0x3b683ad8,0x39aa2a7a,0x3a2d3bfe,0xb87430a6,0xbb0dbbc3,0xbb07bbfe,0x1fdbb80f,0x3b16382a,0x3a9e3bfd,
  0xb2ad3042,0xba41b835,0xbc00bb92,0xba1dbb7f,0x3bfa3bcc,0x3bd03bfb,0x3afb3b7a,0x398b3a54,0xb5c83b4f,0x344bbb98,0xb1853bce,0x2ccebbf0,
  0x3bf93523,0xbb57313b,0x38f8b8e0,0xb1b63b4a,0xb294bbc8,0x3b183a60,0xbb5ca8e8,0x347bb9fc,0xbb0ab08d,0xb263bb3f,0x3bf73958,0xb60e3825,
  0x39a63bfd,0xb9162a16,0xbaa5bbea,0x3790b3ba,0x37a6a94d,0x3c003ae5,0x376f3ad5,0xb87fab43,0xbbd3bbee,0xb8fdbace,0x2311b52f,0x39293599,
  0x2d003328,0xb2deac6a,0xb7d2b5b1,0xb9c5b8e5,0x3bff26ad,0xbbf12c9c,0x3bcfb16c,0xbb9a343e,0xbb9e2c38,0x3990b83a,0xb4633aee,0xb2c6bbff,
  0x3a9bb109,0xad973ae8,0xb9b8bb81,0x3bf4353a,0xb90c33eb,0xb87abbfe,0x3ba53552,0x1cb63a73,0x3625b55e,0x3ba73b3d,0xb24b381a,0xbbf6ba6f,
  0xaec336bb,0xbb6ab8d1,0xba25bbe7,0x327cb546,0xb1cfb805,0x37bd3122,0x3b6f3a00,0x3b9f3bff,0x374238a3,0x319e3517,0xaf8b2776,0xb66bb432,
  0x25e43bff,0xafbdbbfb,0x32f73be2,0xb4ffbbb7,0xb4e7bbfc,0x39c03acb,0xbbb2b7fe,0x3bd2281f,0x38843be6,0xbbf8b80a,0x3999b58d,0x2ef53b90,
  0xba35bbc0,0x3aa229b1,0x34b73b8b,0xbc00b8bc,0x3b633b89,0xb4ab36d2,0xbbd8bade,0x2e5fb8c1,0xbbf5bb42,0xb602ba64,0x391f30f0,0x3bd63b8e,
  0x3bde3aeb,0x3b013be5,0x35eb394a,0xb4db2884,0xbb21ba85,0xbbe0bb96,0xbbf2bbff,0xbb54bbb8,0x3b52b5bc,0xbaf7372c,0x3a8cb845,0xba1138ea,
  0x392e3b2c,0xbb71b8a8,0x3bf23029,0xba9335a5,0xb85f3830,0xb4cfbbed,0x3b6c39df,0xbb042ba7,0xbbabba67,0x386ab576,0x391b3bfd,0xbb60b3a2,
  0x1648b95d,0x3bf63962,0x32323a6b,0xbba9b820,0x3bac396b,0x399d3bbf,0xb4c33389,0xbbdcb9f8,0x385a3a5c,0xaf273359,0xb9bcb70a,0xbbf9bb47,
  0xb933b840,0xbabdba09,0xbbb3bb4c,0xbc00bbef,0x36763b78,0xb7ddbb27,0x38993ac4,0xb937ba50,0xba193715,0x35dfba81,0x2f593bef,0xb88ebb7c,
  0xbab3bad1,0x3ba1305b,0xb5f73970,0xb7b2bbfc,0x3493b8cc,0x3aac3b85,0xba292ade,0xb631bbc5,0x3c0039f0,0x2e2d39eb,0xbbd9b8c7,0xb49fbadb,
  0x348739e3,0xb9b3b402,0xbba3bbc6,0xb201b954,0xbab6b8db,0xbbf3bbc9,0xb994bb2f,0xad65b6a4,0xba15bac7,0xb850b941,0xb457b68d,0x251bb010,
  0xb9cfbb16,0x30ac2a31,0x3b9c3bf1,0xb493ae2d,0xb76fb8b4,0x35a133e3,0x3a1d3afe,0xb902b76f,0xb3e3b5a1,0x38b4376f,0x376f3902,0xbafeba1d,
  0xaa31b0ac,0x3b1639cf,0x2e2d3493,0xbbf1bb9c,0xb956ba74,0x305f29cc,0x3b633bd2,0xb44badc9,0xb6e7b859,0x353f335e,0x39d23ab6,0xb8bcb6ff,
  0xb35eb53f,0x385936e7,0x36ff38bc,0xbab6b9d2,0xa9ccb05f,0x3a743956,0x2dc9344b,0xbbd2bb63,0xb8e3b9de,0x30122967,0x3b1e3ba1,0xb402ad65,
  0xb662b801,0x34de32da,0x39823a67,0xb874b68d,0xb2dab4de,0x38013662,0x368d3874,0xba67b982,0xa967b012,0x39de38e3,0x2d653402,0xbba1bb1e,
  0xb876b952,0x2f8c2902,0x3ace3b60,0xb371ad00,0xb5e1b758,0x347e3257,0x392e3a11,0xb82ab61a,0xb257b47e,0x375835e1,0x361a382a,0xba11b92e,
  0xa902af8c,0x39523876,0x2d003371,0xbb60bace,0xb80db8ce,0x2ef3289e,0x3a733b10,0xb2deac9c,0xb562b6b3,0x342031d5,0x38d639b3,0xb7bdb5a5,
  0xb1d5b420,0x36b33562,0x35a537bd,0xb9b3b8d6,0xa89eaef3,0x38ce380d,0x2c9c32de,0xbb10ba73,0xb750b851,0x2e5a2839,0x3a0d3ab0,0xb24bac38,
  0xb4e5b613,0x33863153,0x387a394f,0xb721b52f,0xb153b386,0x361334e5,0x352f3721,0xb94fb87a,0xa839ae5a,0x38513750,0x2c38324b,0xbab0ba0d,
  0xb68eb7b4,0x2dc227a9,0x399d3a41,0xb1b6aba7,0xb46ab577,0x32cd30d2,0x381a38e5,0xb682b4b7,0xb0d2b2cd,0x3577346a,0x34b73682,0xb8e5b81a,
  0xa7a9adc2,0x37b4368e,0x2ba731b6,0xba41b99d,0xb5d2b6d1,0x2d2a26e0,0x392439c5,0xb122aade,0xb3e3b4de,0x32163052,0x376f3874,0xb5dfb43e,
  0xb052b216,0x34de33e3,0x343e35df,0xb874b76f,0xa6e0ad2a,0x36d135d2,0x2ade3122,0xb9c5b924,0xb51cb5f6,0x2c932617,0x38a3393c,0xb08daa16,
  0xb2f4b448,0x31602fa5,0x36a437fe,0xb53ab389,0xafa5b160,0x344832f4,0x3389353a,0xb7feb6a4,0xa617ac93,0x35f6351c,0x2a16308d,0xb93cb8a3,
  0xb46ab523,0x2bf6254d,0x381a38a8,0xafefa94d,0xb209b36b,0x30ac2ea7,0x35d4370a,0xb493b294,0xaea7b0ac,0x336b3209,0x32943493,0xb70ab5d4,
  0xa54dabf6,0x3523346a,0x294d2fef,0xb8a8b81a,0xb378b456,0x2ac82484,0x3715380a,0xaec3a884,0xb120b24a,0x2ff22da9,0x34ff360e,0xb3d3b19e,
  0xada9aff2,0x324a3120,0x319e33d3,0xb60eb4ff,0xa484aac8,0x34563378,0x28842ec3,0xb80ab715,0xb223b31c,0x29992376,0x35eb36c6,0xad97a776,
  0xb039b12d,0x2e8d2cac,0x3426350b,0xb27cb0a6,0xacacae8d,0x312d3039,0x30a6327c,0xb50bb426,0xa376a999,0x331c3223,0x27762d97,0xb6c6b5eb,
  0xb0d2b194,0x286b21e4,0x34b7356a,0xac6aa5e4,0xaea7b012,0x2d2a2b5f,0x32943402,0xb122af59,0xab5fad2a,0x30122ea7,0x2f593122,0xb402b294,
  0xa1e4a86b,0x319430d2,0x25e42c6a,0xb56ab4b7,0xaf0cb012,0x267b2052,0x32f73402,0xaa7aa452,0xacdeadf5,0x2b912967,0x30d731e8,0xaf8bad65,
  0xa967ab91,0x2df52cde,0x2d652f8b,0xb1e8b0d7,0xa052a67b,0x30122f0c,0x24522a7a,0xb402b2f7,0xac79ad2a,0x24201d7f,0x30743122,0xa81fa17f,
  0xaa31ab91,0x28d026e0,0x2e2d2f8b,0xacceaade,0xa6e0a8d0,0x2b912a31,0x2ade2cce,0xaf8bae2d,0x9d7fa420,0x2d2a2c79,0x217f281f,0xb122b074,
  0xa7a9a86b,0x1f1218b6,0x2ba72c6a,0xa3119cb6,0xa54da67b,0x242021e4,0x294d2a7a,0xa81fa5e4,0xa1e4a420,0x267b254d,0x25e4281f,0xaa7aa94d,
  0x98b69f12,0x286b27a9,0x1cb62311,0xac6aaba7,0x211b21e4,0x98b69248,0xa51ba5e4,0x1cb61648,0x1f122052,0x9d7f9bdb,0xa311a452,0x217f1fdb,
  0x1bdb1d7f,0xa0529f12,0x9fdba17f,0x24522311,0x124818b6,0xa1e4a11b,0x96489cb6,0x25e4251b,0x2a632b5f,0xa1e49bdb,0xae5faf59,0x25e41fdb,
  0x286b2967,0xa6e0a4e9,0xac6aad65,0x2ade28e8,0x24e926e0,0xa967a86b,0xa8e8aade,0x2d652c6a,0x1bdb21e4,0xab5faa63,0x9fdba5e4,0x2f592e5f,
  0x2dc22ea7,0xa54d9f12,0xb1b6b294,0x294d2311,0x2bf62cde,0xaa31a86b,0xafefb0d7,0x2e2d2c6a,0x286b2a31,0xacdeabf6,0xac6aae2d,0x30d72fef,
  0x1f12254d,0xaea7adc2,0xa311a94d,0x329431b6,0x302c30d2,0xa7a9a11b,0xb41ab4b7,0x2ba7251b,0x2dc22f0c,0xac79aa63,0xb1b6b2f7,0x30742e5f,
  0x2a632c79,0xaf0cadc2,0xae5fb074,0x32f731b6,0x211b27a9,0xb0d2b02c,0xa51baba7,0x34b7341a,0x317a3257,0xa902a2ad,0xb552b61a,0x2d0026ad,
  0x2f8c309f,0xaddcac2e,0xb371b487,0x31cf3029,0x2c2e2ddc,0xb09faf8c,0xb029b1cf,0x34873371,0x22ad2902,0xb257b17a,0xa6adad00,0x361a3552,
  0x32cd33e3,0xaa31a420,0xb682b76f,0x2e2d281f,0x30ac31bb,0xaf3fad2a,0xb493b58d,0x33283122,0x2d2a2f3f,0xb1bbb0ac,0xb122b328,0x358d3493,
  0x24202a31,0xb3e3b2cd,0xa81fae2d,0x376f3682,0x341334bc,0xab5fa4e9,0xb7a6b85a,0x2f5928e8,0x319432da,0xb052ae28,0xb56ab68d,0x343e3219,
  0x2e283052,0xb2dab194,0xb219b43e,0x368d356a,0x24e92b5f,0xb4bcb413,0xa8e8af59,0x385a37a6,0x34c3358c,0xac47a5b2,0xb85fb8f3,0x304229b1,
  0x327e33fd,0xb106af26,0xb63cb785,0x34e7330f,0x2f263106,0xb3fdb27e,0xb30fb4e7,0x3785363c,0x25b22c47,0xb58cb4c3,0xa9b1b042,0x38f3385f,
  0x35773662,0xacdea67b,0xb8e5b982,0x30d72a7a,0x336b3493,0xb1bbb012,0xb70ab83a,0x358d3402,0x301231bb,0xb493b36b,0xb402b58d,0x383a370a,
  0x267b2cde,0xb662b577,0xaa7ab0d7,0x398238e5,0x36303741,0xad76a744,0xb962ba04,0x316c2b43,0x342e352a,0xb271b092,0xb7d2b8ad,0x3631347b,
  0x30923271,0xb52ab42e,0xb47bb631,0x38ad37d2,0x27442d76,0xb741b630,0xab43b16c,0x3a043962,0x36ee3815,0xae0ea807,0xb9d6ba7a,0x32012c06,
  0x34a735c4,0xb329b113,0xb84ab91b,0x36d234f3,0x31133329,0xb5c4b4a7,0xb4f3b6d2,0x391b384a,0x28072e0e,0xb815b6ee,0xac06b201,0x3a7a39d6,
  0x37b4388e,0xaea7a86b,0xba41bae1,0x32942c6a,0x35233662,0xb3e3b194,0xb8a8b982,0x376f356a,0x319433e3,0xb662b523,0xb56ab76f,0x398238a8,
  0x286b2ea7,0xb88eb7b4,0xac6ab294,0x3ae13a41,0x3841390f,0xaf3fa8d0,0xbaa2bb3a,0x33282cce,0x35a13705,0xb44fb216,0xb902b9e3,0x380535df,
  0x3216344f,0xb705b5a1,0xb5dfb805,0x39e33902,0x28d02f3f,0xb90fb841,0xacceb328,0x3b3a3aa2,0x38ac3997,0xafd8a935,0xbaf7bb83,0x33ba2d33,
  0x362137ac,0xb4aeb298,0xb958ba3d,0x38503654,0x329834ae,0xb7acb621,0xb654b850,0x3a3d3958,0x29352fd8,0xb997b8ac,0xad33b3ba,0x3b833af7,
  0x391c3a28,0xb039a999,0xbb42bbbc,0x34262d97,0x36a4382d,0xb50eb31c,0xb9aaba90,0x389936c6,0x331c350e,0xb82db6a4,0xb6c6b899,0x3a9039aa,
  0x29993039,0xba28b91c,0xad97b426,0x3bbc3b42,0x39923ac3,0xb085a9fe,0xbb81bbe3,0x346f2dfb,0x372a3886,0xb570b3a0,0xb9f8badb,0x38e03737,
  0x33a03570,0xb886b72a,0xb737b8e0,0x3adb39f8,0x29fe3085,0xbac3b992,0xadfbb46f,0x3be33b81,
};

#define PROF(slot) do {} while (0)
#define PROF_DUMP() do {} while (0)
#define PROFA(slot, dep) do {} while (0)
#define PROF3(slot) do {} while (0)
#define PROF2(slot) do {} while (0)

__device__ __forceinline__ uint32_t smem_u32(const void* p) { return (uint32_t)__cvta_generic_to_shared(p); }

__device__ __forceinline__ void mbar_init(uint32_t a, uint32_t c) {
  asm volatile("mbarrier.init.shared::cta.b64 [%0], %1;\n" ::"r"(a), "r"(c) : "memory");
}
__device__ __forceinline__ void mbar_expect_tx(uint32_t a, uint32_t bytes) {
  asm volatile("mbarrier.arrive.expect_tx.shared::cta.b64 _, [%0], %1;\n" ::"r"(a), "r"(bytes) : "memory");
}
__device__ __forceinline__ void mbar_arrive_cluster(uint32_t cluster_addr) {
  asm volatile("mbarrier.arrive.shared::cluster.b64 _, [%0];\n" ::"r"(cluster_addr) : "memory");
}
__device__ __forceinline__ void mbar_arrive_cluster_n(uint32_t cluster_addr, uint32_t n) {
  asm volatile("mbarrier.arrive.shared::cluster.b64 _, [%0], %1;\n" ::"r"(cluster_addr), "r"(n) : "memory");
}
__device__ __forceinline__ bool mbar_try(uint32_t a, uint32_t parity) {
  uint32_t ok;
  asm volatile("{\n.reg .pred p;\nmbarrier.try_wait.parity.shared::cta.b64 p, [%1], %2;\nselp.u32 %0, 1, 0, p;\n}\n"
               : "=r"(ok) : "r"(a), "r"(parity) : "memory");
  return ok;
}
__device__ __forceinline__ void mbar_wait(uint32_t a, uint32_t parity) {
  if (mbar_try(a, parity)) return;
#pragma unroll 1
  for (int n = 0; n < SPIN_LIMIT; n++)
    if (mbar_try(a, parity)) break;
}
__device__ __forceinline__ bool elect_one() {
  uint32_t p;
  asm volatile("{\n.reg .pred P;\nelect.sync _|P, 0xffffffff;\nselp.u32 %0, 1, 0, P;\n}\n" : "=r"(p));
  return p;
}
__device__ __forceinline__ uint32_t mapa(uint32_t a, uint32_t rank) {
  uint32_t r;
  asm volatile("mapa.shared::cluster.u32 %0, %1, %2;\n" : "=r"(r) : "r"(a), "r"(rank));
  return r;
}
__device__ __forceinline__ void nb_sync(int id, int n) { asm volatile("bar.sync %0, %1;\n" ::"r"(id), "r"(n) : "memory"); }
__device__ __forceinline__ void nb_arrive(int id, int n) { asm volatile("bar.arrive %0, %1;\n" ::"r"(id), "r"(n) : "memory"); }
__device__ __forceinline__ void cluster_sync_all() {
  asm volatile("barrier.cluster.arrive.relaxed.aligned;\nbarrier.cluster.wait.aligned;\n" ::: "memory");
}
__device__ __forceinline__ void fence_async_smem() { asm volatile("fence.proxy.async.shared::cta;\n" ::: "memory"); }
__device__ __forceinline__ void fence_async_all() { asm volatile("fence.proxy.async.global;\n" ::: "memory"); }

__device__ __forceinline__ void tma_load_3d(uint32_t dst, const CUtensorMap* tm, uint32_t bar, int c0, int c1, int c2) {
  asm volatile(
      "cp.async.bulk.tensor.3d.shared::cluster.global.mbarrier::complete_tx::bytes [%0], [%1, {%3, %4, %5}], [%2];\n"
      ::"r"(dst), "l"(tm), "r"(bar), "r"(c0), "r"(c1), "r"(c2) : "memory");
}
__device__ __forceinline__ void tma_load_4d(uint32_t dst, const CUtensorMap* tm, uint32_t bar, int c0, int c1, int c2, int c3) {
  asm volatile(
      "cp.async.bulk.tensor.4d.shared::cluster.global.mbarrier::complete_tx::bytes [%0], [%1, {%3, %4, %5, %6}], [%2];\n"
      ::"r"(dst), "l"(tm), "r"(bar), "r"(c0), "r"(c1), "r"(c2), "r"(c3) : "memory");
}
__device__ __forceinline__ void tma_load_3d_mc(uint32_t dst, const CUtensorMap* tm, uint32_t bar, int c0, int c1, int c2) {
  asm volatile(
      "cp.async.bulk.tensor.3d.shared::cluster.global.mbarrier::complete_tx::bytes.multicast::cluster [%0], [%1, {%3, %4, %5}], [%2], %6;\n"
      ::"r"(dst), "l"(tm), "r"(bar), "r"(c0), "r"(c1), "r"(c2), "h"((uint16_t)3) : "memory");
}
__device__ __forceinline__ void bulk_load(uint32_t dst, const void* src, uint32_t bytes, uint32_t bar) {
  asm volatile("cp.async.bulk.shared::cluster.global.mbarrier::complete_tx::bytes [%0], [%1], %2, [%3];\n"
               ::"r"(dst), "l"(src), "r"(bytes), "r"(bar) : "memory");
}
__device__ __forceinline__ void tma_store_3d(const CUtensorMap* tm, uint32_t src, int c0, int c1, int c2) {
  asm volatile("cp.async.bulk.tensor.3d.global.shared::cta.bulk_group [%0, {%2, %3, %4}], [%1];\n"
               ::"l"(tm), "r"(src), "r"(c0), "r"(c1), "r"(c2) : "memory");
}
__device__ __forceinline__ void bulk_commit() { asm volatile("cp.async.bulk.commit_group;\n" ::: "memory"); }
__device__ __forceinline__ void bulk_wait0() { asm volatile("cp.async.bulk.wait_group 0;\n" ::: "memory"); }
__device__ __forceinline__ void prefetch_tmap(const CUtensorMap* tm) {
  asm volatile("prefetch.tensormap [%0];\n" ::"l"(tm) : "memory");
}

__device__ __forceinline__ void wg_fence() { asm volatile("wgmma.fence.sync.aligned;\n" ::: "memory"); }
__device__ __forceinline__ void wg_commit() { asm volatile("wgmma.commit_group.sync.aligned;\n" ::: "memory"); }
template <int N> __device__ __forceinline__ void wg_wait() {
  asm volatile("wgmma.wait_group.sync.aligned %0;\n" ::"n"(N) : "memory");
}
__device__ __forceinline__ uint64_t mkdesc(uint32_t addr, uint32_t lbo, uint32_t sbo, uint32_t swz) {
  return (uint64_t)((addr & 0x3FFFF) >> 4) | ((uint64_t)(lbo >> 4) << 16) | ((uint64_t)(sbo >> 4) << 32) |
         ((uint64_t)swz << 62);
}

#define R4(d, o) "+f"(d[o + 0]), "+f"(d[o + 1]), "+f"(d[o + 2]), "+f"(d[o + 3])
#define R8(d, o) R4(d, o), R4(d, o + 4)
#define R16(d, o) R8(d, o), R8(d, o + 8)
#define R32(d, o) R16(d, o), R16(d, o + 16)
#define R64(d, o) R32(d, o), R32(d, o + 32)

__device__ __forceinline__ void wgmma_n192(float (&d)[96], uint64_t da, uint64_t db, uint32_t acc) {
  asm volatile(
      "{\n.reg .pred p;\nsetp.ne.u32 p, %98, 0;\n"
      "wgmma.mma_async.sync.aligned.m64n192k16.f32.bf16.bf16 "
      "{%0,%1,%2,%3,%4,%5,%6,%7,%8,%9,%10,%11,%12,%13,%14,%15,%16,%17,%18,%19,%20,%21,%22,%23,%24,%25,%26,%27,%28,%29,%30,%31,"
      "%32,%33,%34,%35,%36,%37,%38,%39,%40,%41,%42,%43,%44,%45,%46,%47,%48,%49,%50,%51,%52,%53,%54,%55,%56,%57,%58,%59,%60,%61,%62,%63,"
      "%64,%65,%66,%67,%68,%69,%70,%71,%72,%73,%74,%75,%76,%77,%78,%79,%80,%81,%82,%83,%84,%85,%86,%87,%88,%89,%90,%91,%92,%93,%94,%95}, "
      "%96, %97, p, 1, 1, 0, 1;\n}\n"
      : R64(d, 0), R32(d, 64)
      : "l"(da), "l"(db), "r"(acc));
}
__device__ __forceinline__ void wgmma_n128(float (&d)[64], uint64_t da, uint64_t db, uint32_t acc) {
  asm volatile(
      "{\n.reg .pred p;\nsetp.ne.u32 p, %66, 0;\n"
      "wgmma.mma_async.sync.aligned.m64n128k16.f32.bf16.bf16 "
      "{%0,%1,%2,%3,%4,%5,%6,%7,%8,%9,%10,%11,%12,%13,%14,%15,%16,%17,%18,%19,%20,%21,%22,%23,%24,%25,%26,%27,%28,%29,%30,%31,"
      "%32,%33,%34,%35,%36,%37,%38,%39,%40,%41,%42,%43,%44,%45,%46,%47,%48,%49,%50,%51,%52,%53,%54,%55,%56,%57,%58,%59,%60,%61,%62,%63}, "
      "%64, %65, p, 1, 1, 0, 1;\n}\n"
      : R64(d, 0)
      : "l"(da), "l"(db), "r"(acc));
}
#define WG128(C, ACC)                                                                                                      \
  asm volatile(                                                                                                            \
      "{\n.reg .b64 a, b;\nmov.b64 a, {%64, %66};\nmov.b64 b, {%65, %66};\n"                                               \
      "wgmma.mma_async.sync.aligned.m64n128k16.f32.bf16.bf16 "                                                             \
      "{%0,%1,%2,%3,%4,%5,%6,%7,%8,%9,%10,%11,%12,%13,%14,%15,%16,%17,%18,%19,%20,%21,%22,%23,%24,%25,%26,%27,%28,%29,%30,%31," \
      "%32,%33,%34,%35,%36,%37,%38,%39,%40,%41,%42,%43,%44,%45,%46,%47,%48,%49,%50,%51,%52,%53,%54,%55,%56,%57,%58,%59,%60,%61," \
      "%62,%63}, a, b, " ACC ", 1, 1, 0, 1;\n}\n"                                                                          \
      : Z16(C, d, 0), Z16(C, d, 16), Z16(C, d, 32), Z16(C, d, 48)                                                          \
      : "r"(da), "r"(db), "r"(0x40000040))
#define Z4(C, d, o) C(d[o + 0]), C(d[o + 1]), C(d[o + 2]), C(d[o + 3])
#define Z16(C, d, o) Z4(C, d, o), Z4(C, d, o + 4), Z4(C, d, o + 8), Z4(C, d, o + 12)
__device__ __forceinline__ void wgmma_n128z(float (&d)[64], uint32_t da, uint32_t db) { WG128("=f", "0"); }
__device__ __forceinline__ void wgmma_n128a(float (&d)[64], uint32_t da, uint32_t db) { WG128("+f", "1"); }
template <int N> __device__ __forceinline__ void fence_regs(float (&d)[N]) {
#pragma unroll
  for (int i = 0; i < N; i++) asm volatile("" : "+f"(d[i])::"memory");
}

__device__ __forceinline__ void mma16816(float (&d)[4], uint32_t a0, uint32_t a1, uint32_t a2, uint32_t a3, uint32_t b0,
                                         uint32_t b1) {
  asm("mma.sync.aligned.m16n8k16.row.col.f32.bf16.bf16.f32 {%0,%1,%2,%3}, {%4,%5,%6,%7}, {%8,%9}, {%0,%1,%2,%3};\n"
      : "+f"(d[0]), "+f"(d[1]), "+f"(d[2]), "+f"(d[3])
      : "r"(a0), "r"(a1), "r"(a2), "r"(a3), "r"(b0), "r"(b1));
}
__device__ __forceinline__ void mma16816_z(float (&d)[4], uint32_t a0, uint32_t a1, uint32_t a2, uint32_t a3, uint32_t b0,
                                           uint32_t b1) {
  asm("mma.sync.aligned.m16n8k16.row.col.f32.bf16.bf16.f32 {%0,%1,%2,%3}, {%4,%5,%6,%7}, {%8,%9}, {%10,%10,%10,%10};\n"
      : "=f"(d[0]), "=f"(d[1]), "=f"(d[2]), "=f"(d[3])
      : "r"(a0), "r"(a1), "r"(a2), "r"(a3), "r"(b0), "r"(b1), "f"(0.f));
}
__device__ __forceinline__ void ldsm4t(uint32_t (&r)[4], uint32_t a) {
  asm volatile("ldmatrix.sync.aligned.m8n8.x4.trans.shared.b16 {%0,%1,%2,%3}, [%4];\n"
               : "=r"(r[0]), "=r"(r[1]), "=r"(r[2]), "=r"(r[3]) : "r"(a) : "memory");
}
__device__ __forceinline__ void ldsm2t(uint32_t& r0, uint32_t& r1, uint32_t a) {
  asm volatile("ldmatrix.sync.aligned.m8n8.x2.trans.shared.b16 {%0,%1}, [%2];\n" : "=r"(r0), "=r"(r1) : "r"(a) : "memory");
}
__device__ __forceinline__ void st_async128(uint32_t a, uint32_t bar, uint32_t x, uint32_t y, uint32_t z, uint32_t w) {
  asm volatile("st.async.weak.shared::cluster.mbarrier::complete_tx::bytes.v4.b32 [%0], {%2,%3,%4,%5}, [%1];\n"
               ::"r"(a), "r"(bar), "r"(x), "r"(y), "r"(z), "r"(w) : "memory");
}
__device__ __forceinline__ void mbar_arrive(uint32_t a) {
  asm volatile("mbarrier.arrive.shared::cta.b64 _, [%0];\n" ::"r"(a) : "memory");
}
__device__ __forceinline__ void stsm4(uint32_t a, uint32_t r0, uint32_t r1, uint32_t r2, uint32_t r3) {
  asm volatile("stmatrix.sync.aligned.m8n8.x4.shared.b16 [%0], {%1,%2,%3,%4};\n"
               ::"r"(a), "r"(r0), "r"(r1), "r"(r2), "r"(r3) : "memory");
}
__device__ __forceinline__ void stsm4t(uint32_t a, uint32_t r0, uint32_t r1, uint32_t r2, uint32_t r3) {
  asm volatile("stmatrix.sync.aligned.m8n8.x4.trans.shared.b16 [%0], {%1,%2,%3,%4};\n"
               ::"r"(a), "r"(r0), "r"(r1), "r"(r2), "r"(r3) : "memory");
}
__device__ __forceinline__ uint2 lds64(uint32_t a) {
  uint2 v;
  asm volatile("ld.shared.v2.u32 {%0,%1}, [%2];\n" : "=r"(v.x), "=r"(v.y) : "r"(a));
  return v;
}
__device__ __forceinline__ uint4 lds128(uint32_t a) {
  uint4 v;
  asm volatile("ld.shared.v4.u32 {%0,%1,%2,%3}, [%4];\n" : "=r"(v.x), "=r"(v.y), "=r"(v.z), "=r"(v.w) : "r"(a) : "memory");
  return v;
}
__device__ __forceinline__ void sts128(uint32_t a, uint32_t x, uint32_t y, uint32_t z, uint32_t w) {
  asm volatile("st.shared.v4.u32 [%0], {%1,%2,%3,%4};\n" ::"r"(a), "r"(x), "r"(y), "r"(z), "r"(w) : "memory");
}
__device__ __forceinline__ void sts64(uint32_t a, uint32_t x, uint32_t y) {
  asm volatile("st.shared.v2.u32 [%0], {%1,%2};\n" ::"r"(a), "r"(x), "r"(y) : "memory");
}
__device__ __forceinline__ uint32_t pack_bf16(float lo, float hi) {
  uint32_t r;
  asm("cvt.rn.bf16x2.f32 %0, %1, %2;\n" : "=r"(r) : "f"(hi), "f"(lo));
  return r;
}
__device__ __forceinline__ uint32_t bmul2(uint32_t a, uint32_t b) {
  uint32_t r;
  asm("mul.rn.bf16x2 %0, %1, %2;\n" : "=r"(r) : "r"(a), "r"(b));
  return r;
}
__device__ __forceinline__ uint32_t bmax2(uint32_t a, uint32_t b) {
  uint32_t r;
  asm("max.bf16x2 %0, %1, %2;\n" : "=r"(r) : "r"(a), "r"(b));
  return r;
}
__device__ __forceinline__ uint32_t bfma2(uint32_t a, uint32_t b, uint32_t c) {
  uint32_t r;
  asm("fma.rn.bf16x2 %0, %1, %2, %3;\n" : "=r"(r) : "r"(a), "r"(b), "r"(c));
  return r;
}
__device__ __forceinline__ uint32_t badd2(uint32_t a, uint32_t b) {
  uint32_t r;
  asm("add.rn.bf16x2 %0, %1, %2;\n" : "=r"(r) : "r"(a), "r"(b));
  return r;
}
__device__ __forceinline__ void prefetch_l2(const void* p) { asm volatile("prefetch.global.L2 [%0];\n" ::"l"(p)); }
__device__ __forceinline__ void cp_async16n(uint32_t dst, const void* src) {
  asm volatile("cp.async.cg.shared.global [%0], [%1], 16;\n" ::"r"(dst), "l"(src) : "memory");
}
__device__ __forceinline__ void cp_async16(uint32_t dst, const void* src, uint32_t srcbytes) {
  asm volatile("cp.async.cg.shared.global.L2::256B [%0], [%1], 16, %2;\n" ::"r"(dst), "l"(src), "r"(srcbytes) : "memory");
}
__device__ __forceinline__ uint32_t ld_acquire(const uint32_t* p) {
  uint32_t v;
  asm volatile("ld.acquire.gpu.global.u32 %0, [%1];\n" : "=r"(v) : "l"(p) : "memory");
  return v;
}
__device__ __forceinline__ uint32_t ld_relaxed(const uint32_t* p) {
  uint32_t v;
  asm volatile("ld.relaxed.gpu.global.u32 %0, [%1];\n" : "=r"(v) : "l"(p) : "memory");
  return v;
}
__device__ __forceinline__ void st_release(uint32_t* p, uint32_t v) {
  asm volatile("st.release.gpu.global.u32 [%0], %1;\n" ::"l"(p), "r"(v) : "memory");
}
__device__ __forceinline__ void wait_flag(const uint32_t* p, uint32_t want) {
  int n = 0;
  while (ld_acquire(p) != want && ++n < SPIN_LIMIT) {}
}

struct Params {
  const __nv_bfloat16* x;
  const __nv_bfloat16* w;
  const __nv_bfloat16* q;
  const __nv_bfloat16* k;
  const __nv_bfloat16* v;
  const __nv_bfloat16* shift_k;
  const __nv_bfloat16* ssm_k;
  const __nv_bfloat16* ssm_D;
  const __nv_bfloat16* wo;
  __nv_bfloat16* out;
  uint32_t zero;
};

__device__ __forceinline__ uint32_t lds32(uint32_t a) {
  uint32_t v;
  asm volatile("ld.shared.u32 %0, [%1];\n" : "=r"(v) : "r"(a));
  return v;
}
__device__ __forceinline__ float bf_lo(uint32_t v) {
  uint32_t r;
  asm("prmt.b32 %0, %1, 0, 0x1044;\n" : "=r"(r) : "r"(v));
  return __uint_as_float(r);
}
__device__ __forceinline__ float bf_hi(uint32_t v) { return __uint_as_float(v & 0xffff0000u); }
__device__ __forceinline__ float ex2(float x) {
  float r;
  asm("ex2.approx.ftz.f32 %0, %1;\n" : "=f"(r) : "f"(x));
  return r;
}
__device__ __forceinline__ float rcp(float x) {
  float r;
  asm("rcp.approx.ftz.f32 %0, %1;\n" : "=f"(r) : "f"(x));
  return r;
}

#define Q4(c, d, o) c(d[o + 0]), c(d[o + 1]), c(d[o + 2]), c(d[o + 3])
#define Q8(c, d, o) Q4(c, d, o), Q4(c, d, o + 4)
#define Q16(c, d, o) Q8(c, d, o), Q8(c, d, o + 8)
#define Q32(c, d) Q16(c, d, 0), Q16(c, d, 16)
#define L8 "{%0,%1,%2,%3,%4,%5,%6,%7}"
#define L16 "{%0,%1,%2,%3,%4,%5,%6,%7,%8,%9,%10,%11,%12,%13,%14,%15}"
#define L32 "{%0,%1,%2,%3,%4,%5,%6,%7,%8,%9,%10,%11,%12,%13,%14,%15,%16,%17,%18,%19,%20,%21,%22,%23,%24,%25,%26,%27,%28,%29,%30,%31}"
__device__ __forceinline__ void fft_rows(uint32_t (&d)[32], const uint32_t (&a)[2][4], uint64_t db) {
  asm volatile("wgmma.mma_async.sync.aligned.m64n128k16.f16.f16.f16 " L32 ", {%32,%33,%34,%35}, %36, 0, 1, 1, 1;\n"
               : Q32("=r", d) : "r"(a[0][0]), "r"(a[0][1]), "r"(a[0][2]), "r"(a[0][3]), "l"(db));
  asm volatile("wgmma.mma_async.sync.aligned.m64n128k16.f16.f16.f16 " L32 ", {%32,%33,%34,%35}, %36, 1, 1, 1, 1;\n"
               : Q32("+r", d) : "r"(a[1][0]), "r"(a[1][1]), "r"(a[1][2]), "r"(a[1][3]), "l"(db + 64));
}
template <int INV> __device__ __forceinline__ void fft_cols(uint32_t (&d)[8], const uint32_t (&a)[2][4], uint64_t db) {
  asm volatile("wgmma.mma_async.sync.aligned.m64n32k16.f16.f16.f16 " L8 ", {%8,%9,%10,%11}, %12, 0, 1, 1, %13;\n"
               : Q8("=r", d, 0) : "r"(a[0][0]), "r"(a[0][1]), "r"(a[0][2]), "r"(a[0][3]), "l"(db), "n"(INV));
  asm volatile("wgmma.mma_async.sync.aligned.m64n32k16.f16.f16.f16 " L8 ", {%8,%9,%10,%11}, %12, 1, 1, 1, %13;\n"
               : Q8("+r", d, 0) : "r"(a[1][0]), "r"(a[1][1]), "r"(a[1][2]), "r"(a[1][3]), "l"(db + (INV ? 16 : 64)), "n"(INV));
}
__device__ __forceinline__ void fft_back(float (&d)[16], uint64_t da, uint64_t db) {
  asm volatile("wgmma.mma_async.sync.aligned.m64n32k16.f32.f16.f16 " L16 ", %16, %17, 0, 1, 1, 1, 1;\n"
               : Q16("=f", d, 0) : "l"(da), "l"(db));
#pragma unroll
  for (int i = 1; i < 4; i++)
    asm volatile("wgmma.mma_async.sync.aligned.m64n32k16.f32.f16.f16 " L16 ", %16, %17, 1, 1, 1, 1, 1;\n"
                 : Q16("+f", d, 0) : "l"(da + 32 * i), "l"(db + 64 * i));
}
__device__ __forceinline__ uint32_t hmul2(uint32_t a, uint32_t b) {
  uint32_t r;
  asm("mul.rn.f16x2 %0, %1, %2;\n" : "=r"(r) : "r"(a), "r"(b));
  return r;
}
__device__ __forceinline__ uint32_t hadd2(uint32_t a, uint32_t b) {
  uint32_t r;
  asm("add.rn.f16x2 %0, %1, %2;\n" : "=r"(r) : "r"(a), "r"(b));
  return r;
}
__device__ __forceinline__ uint32_t hneg2(uint32_t a) {
  uint32_t r;
  asm("neg.f16x2 %0, %1;\n" : "=r"(r) : "r"(a));
  return r;
}
__device__ __forceinline__ uint32_t hfma2(uint32_t a, uint32_t b, uint32_t c) {
  uint32_t r;
  asm("fma.rn.f16x2 %0, %1, %2, %3;\n" : "=r"(r) : "r"(a), "r"(b), "r"(c));
  return r;
}
__device__ __forceinline__ uint32_t pack_f16(float lo, float hi) {
  uint32_t r;
  asm("cvt.rn.f16x2.f32 %0, %1, %2;\n" : "=r"(r) : "f"(hi), "f"(lo));
  return r;
}
__device__ __forceinline__ uint32_t bmaxabs2(uint32_t a, uint32_t b) {
  uint32_t r;
  asm("max.xorsign.abs.bf16x2 %0, %1, %2;\n" : "=r"(r) : "r"(a), "r"(b));
  return r;
}
struct C2 { uint32_t r, i; };
__device__ __forceinline__ C2 cmul(C2 a, C2 b) {
  return C2{hfma2(a.r, b.r, hneg2(hmul2(a.i, b.i))), hfma2(a.r, b.i, hmul2(a.i, b.r))};
}
__device__ __forceinline__ C2 cfma(C2 a, C2 b, C2 c) {
  return C2{hfma2(a.r, b.r, hfma2(hneg2(a.i), b.i, c.r)), hfma2(a.r, b.i, hfma2(a.i, b.r, c.i))};
}
__device__ __forceinline__ C2 crot(C2 z, C2 t) {
  const uint32_t r = hfma2(t.r, z.i, z.r), i = hfma2(t.i, r, z.i);
  return C2{hfma2(t.r, i, r), i};
}
__device__ __forceinline__ C2 cget(const uint32_t (&e)[8], int j, int b) { return C2{e[4 * j + b], e[4 * j + 2 + b]}; }
template <int N> __device__ __forceinline__ void fence_regs(uint32_t (&d)[N]) {
#pragma unroll
  for (int i = 0; i < N; i++) asm volatile("" : "+r"(d[i])::"memory");
}
__device__ __forceinline__ void ldsm4(uint32_t (&r)[4], uint32_t a) {
  asm volatile("ldmatrix.sync.aligned.m8n8.x4.shared.b16 {%0,%1,%2,%3}, [%4];\n"
               : "=r"(r[0]), "=r"(r[1]), "=r"(r[2]), "=r"(r[3]) : "r"(a) : "memory");
}

__device__ __forceinline__ uint32_t movm(uint32_t a) {
  uint32_t r;
  asm volatile("movmatrix.sync.aligned.m8n8.trans.b16 %0, %1;\n" : "=r"(r) : "r"(a));
  return r;
}
template <int C0, int H, bool T> __device__ __forceinline__ void attn_pack(const float (&acc)[96], uint32_t (&d)[8]) {
#pragma unroll
  for (int c = 0; c < 8; c++) {
    asm volatile("cvt.rn.bf16x2.f32 %0, %1, %2;\n" : "=r"(d[c]) : "f"(acc[4 * (C0 + c) + 2 * H + 1]), "f"(acc[4 * (C0 + c) + 2 * H]));
    if (T) d[c] = movm(d[c]);
  }
}
__device__ __forceinline__ void attn_qk(float (&s)[4], const uint32_t (&qlo)[8], const uint32_t (&qhi)[8],
                                        const uint32_t (&k)[8], int c) {
  mma16816_z(s, qlo[c], qhi[c], qlo[c + 1], qhi[c + 1], k[c], k[c + 1]);
  mma16816(s, qlo[c + 2], qhi[c + 2], qlo[c + 3], qhi[c + 3], k[c + 2], k[c + 3]);
}
template <int N> __device__ __forceinline__ void quad_softmax(float (&x)[N][2], uint32_t (&pp)[N]) {
  const float c2 = 1.4426950408889634f;
  uint32_t q[N], mx[N / 2];
#pragma unroll
  for (int n = 0; n < N; n++) {
    const uint32_t r = pack_bf16(x[n][0], x[n][1]);
    q[n] = bfma2(r, 0x3e353e35u, bmul2(r, 0x379e379eu));
    x[n][0] = bf_lo(q[n]);
    x[n][1] = bf_hi(q[n]);
  }
#pragma unroll
  for (int n = 0; n < N / 2; n++)
    mx[n] = bmax2(__byte_perm(q[2 * n], q[2 * n + 1], 0x5410), __byte_perm(q[2 * n], q[2 * n + 1], 0x7632));
#pragma unroll
  for (int o = 1; o <= 2; o++) {
#pragma unroll
    for (int n = 0; n < N / 2; n++) mx[n] = bmax2(mx[n], __shfl_xor_sync(0xffffffffu, mx[n], o));
  }
  float m[N], t[N];
#pragma unroll
  for (int n = 0; n < N / 2; n++) {
    m[2 * n] = bf_lo(mx[n]);
    m[2 * n + 1] = bf_hi(mx[n]);
  }
#pragma unroll
  for (int n = 0; n < N; n++) {
    const float nm = -m[n] * c2;
    x[n][0] = ex2(fmaf(x[n][0], c2, nm));
    x[n][1] = ex2(fmaf(x[n][1], c2, nm));
  }
#pragma unroll
  for (int n = 0; n < N; n += 2) {
    float u0, u1;
    asm("mma.sync.aligned.m16n8k8.row.col.f32.tf32.tf32.f32 {%0,%1,%2,%3}, {%4,%5,%6,%7}, {%8,%8}, {%9,%9,%9,%9};\n"
        : "=f"(t[n]), "=f"(u0), "=f"(t[n + 1]), "=f"(u1)
        : "r"(__float_as_uint(x[n][0])), "r"(__float_as_uint(x[n + 1][0])), "r"(__float_as_uint(x[n][1])),
          "r"(__float_as_uint(x[n + 1][1])), "r"(0x3f800000u), "f"(0.f));
  }
#pragma unroll
  for (int n = 0; n < N; n++) {
    const float inv = rcp(t[n]);
    pp[n] = pack_bf16(x[n][0] * inv, x[n][1] * inv);
  }
}
__device__ __forceinline__ void attn_pv(uint32_t dst, const uint32_t (&vp)[8], const uint32_t (&vo)[8], int c, uint32_t pp,
                                        uint32_t maskLE) {
  const uint32_t b0 = pp & ~maskLE, b1 = pp & maskLE;
  float oa[4], ob[4];
  mma16816_z(oa, vp[c], vp[c + 1], vo[c], vo[c + 1], b0, b1);
  mma16816_z(ob, vp[c + 2], vp[c + 3], vo[c + 2], vo[c + 3], b0, b1);
  stsm4t(dst, pack_bf16(oa[0], oa[1]), pack_bf16(oa[2], oa[3]), pack_bf16(ob[0], ob[1]), pack_bf16(ob[2], ob[3]));
}

template <int MODE>
__global__ void __cluster_dims__(2, 1, 1) __launch_bounds__(NTHREADS, 1)
fused_kernel(const Params p, const __grid_constant__ CUtensorMap tmX, const __grid_constant__ CUtensorMap tmW,
             const __grid_constant__ CUtensorMap tmWo, const __grid_constant__ CUtensorMap tmWp,
             const __grid_constant__ CUtensorMap tmQ,
             const __grid_constant__ CUtensorMap tmOb,
             const __grid_constant__ CUtensorMap tmXh, const __grid_constant__ CUtensorMap tmWh) {
  extern __shared__ __align__(1024) uint8_t smem[];
  if (threadIdx.x < 32 * PFR) {
    const uint32_t i = ((blockIdx.x + (threadIdx.x >> 5) * (128 / PFR)) & 127) * 16 + (threadIdx.x & 15);
    prefetch_l2(threadIdx.x & 16 ? (const char*)p.w + i * 128 : (const char*)p.x + i * 2048);
  }
  const uint32_t sb = smem_u32(smem);
  const uint32_t bars = sb + OFF_BAR;
  const int tid = threadIdx.x, lane = tid & 31, warp = __shfl_sync(0xffffffffu, tid >> 5, 0);
  const int rank = blockIdx.x & 1;
  const bool halo_cta = blockIdx.x < 4;
  if (halo_cta && MODE != 0) return;
  int grp, mem;
  {
    const int t = (blockIdx.x >> 1) - 4, u = t - 32;
    const int q7 = (u * 37) >> 8;
    const bool lo = (unsigned)t < 32u, mid = (unsigned)u < 28u;
    grp = lo ? (t & 7) : (mid ? 1 + u - 7 * q7 : 0);
    mem = lo ? (t >> 3) : (mid ? 4 + q7 : (t < 0 ? t + 6 : t - 54));
  }
  const int rg = (grp >> 2) * 4 + (mem >> 1), hp = (grp & 3) * 4 + (mem & 1) * 2 + rank;
  const int rb2 = (grp >> 2) * 8 + mem, cb2 = (grp & 3) * 2 + rank;
  const int chb = grp * 16 + mem * 2 + rank;
  const int cta = rg * 16 + hp;
  const int hsel = rb2 & 1;
  const int par = rg >> 2, gidx = rg & 3;

  if (tid < 256 && !halo_cta && MODE != 2) {
    const int r = tid >> 3, c = tid & 7;
    const uint32_t so = r * 128 + ((c ^ (r & 7)) << 4);
    const __nv_bfloat16* wg0 = p.w + (size_t)r * (3 * DM) + hp * 64 + c * 8;
    const __nv_bfloat16* xg0 = p.x + (size_t)(2 * (gidx * 256 + r) + par) * DM + c * 8;
#pragma unroll
    for (int j = 0; j < 3; j++) cp_async16n(sb + OFF_1B + j * 4096 + so, wg0 + j * DM);
#pragma unroll
    for (int i = 0; i < 8; i++) cp_async16n(sb + i * 4096 + so, xg0 + (size_t)i * 64 * DM);
    asm volatile("cp.async.commit_group;\n" ::: "memory");
    if (PF2 >= 1 && tid < 16 * PF2X) prefetch_l2((const char*)p.x + (chb * 16 + (tid & 15)) * 2048 + 128 + (tid >> 4) * 128);
    if (PF2 >= 2 && warp == 2) prefetch_l2((const char*)p.w + (2048 + chb * 32 + lane) * 128);
  }

  if (warp >= 8) {
    asm volatile("setmaxnreg.dec.sync.aligned.u32 %0;\n" :: "n"(REG_HELP));
    auto halo_issue = [&](int kb, int s) {
      const uint32_t fb = bars + 8 * (BAR_FULLB + s), st = sb + s * STGH;
      mbar_expect_tx(fb, STGH - 2048);
      tma_load_3d(st + 8192, &tmWh, fb, 0, kb * 64, 16 + blockIdx.x * 4);
      tma_load_3d(st + 8192 + 32768, &tmWh, fb, 0, kb * 64, 32 + blockIdx.x * 4);
      tma_load_4d(st, &tmXh, fb, kb * 64, 248, 0, 0);
    };
    if (tid == 256) {
      prefetch_tmap(halo_cta ? &tmXh : &tmX);
#pragma unroll
      for (int i = 0; i < NS1B; i++) mbar_init(bars + 8 * (BAR_FULLB + i), 1);
#pragma unroll
      for (int i = 0; i < NS1A; i++) mbar_init(bars + 8 * (BAR_FULLA + i), 1);
      asm volatile("fence.mbarrier_init.release.cluster;\n" ::: "memory");
      if (!halo_cta && MODE != 2) {
        mbar_expect_tx(bars + 8 * (BAR_FULLB + 1), STG1B);
        tma_load_3d(sb + OFF_1B + 1 * STG1B, &tmW, bars + 8 * (BAR_FULLB + 1), hp * 64, 32, 0);
        mbar_expect_tx(bars + 8 * (BAR_FULLB + 2), STG1B);
        tma_load_3d(sb + OFF_1B + 2 * STG1B, &tmW, bars + 8 * (BAR_FULLB + 2), hp * 64, 64, 0);
        mbar_arrive(bars + 8 * BAR_FULLA);
        mbar_arrive(bars + 8 * BAR_FULLB);
      } else if (halo_cta) {
        halo_issue(0, 0);
      }
    } else if (tid == 288) {
#pragma unroll
      for (int i = 0; i < NS1A; i++) mbar_init(bars + 8 * (BAR_EMPTYA + i), 4);
#pragma unroll
      for (int i = 0; i < NS1B; i++) mbar_init(bars + 8 * (BAR_EMPTYB + i), 2);
      mbar_init(bars + 8 * BAR_X, 4);
      mbar_init(bars + 8 * BAR_TAB, 16);
      mbar_init(bars + 8 * BAR_U, 1);
      mbar_init(bars + 8 * BAR_H, 1);
      mbar_init(bars + 8 * BAR_STG, 8);
      mbar_init(bars + 8 * BAR_HALO, 1);
      mbar_init(bars + 8 * BAR_Q, 1);
      mbar_init(bars + 8 * BAR_LAND, 5);
      mbar_init(bars + 8 * (BAR_LAND + 1), 5);
      asm volatile("fence.mbarrier_init.release.cluster;\n" ::: "memory");
    } else if (tid == 320) {
#pragma unroll
      for (int i = 0; i < NS2; i++) {
        mbar_init(bars + 8 * (BAR_FULL2 + i), 1);
        mbar_init(bars + 8 * (BAR_EMPTY2 + i), 2);
        mbar_init(bars + 8 * (BAR_EMPTY2B + i), 2);
      }
      asm volatile("fence.mbarrier_init.release.cluster;\n" ::: "memory");
    } else if (tid == 352) {
#pragma unroll
      for (int i = 0; i < 4; i++) mbar_init(bars + 8 * (BAR_Y + i), i < 2 ? 4 : i == 2 ? 10 : 8);
      mbar_init(bars + 8 * BAR_XFREE, 1);
      asm volatile("fence.mbarrier_init.release.cluster;\n" ::: "memory");
    }
    __syncwarp();
    cluster_sync_all();
    if (warp == 8) PROF2(24);
    const int hw = warp - 8;
    const int lr = lane & 7, lm = lane >> 3;
    auto g1_issue_a = [&](int j, int s) {
      const uint32_t fb = bars + 8 * (BAR_FULLA + s);
      mbar_expect_tx(fb, STG1A);
      tma_load_3d_mc(sb + s * STG1A + rank * 16384, &tmX, fb, j * 64, par, gidx * 256 + rank * 128);
    };
    auto g1_issue_b = [&](int kb, int s) {
      const uint32_t fb = bars + 8 * (BAR_FULLB + s);
      mbar_expect_tx(fb, STG1B);
      tma_load_3d(sb + OFF_1B + s * STG1B, &tmW, fb, hp * 64, kb * 32, 0);
    };
    auto g2_k = [&](int kb) { return (kb < 2 ? hp : kb < 4 ? hp & 14 : hp & 12) ^ kb; };
    auto g2_issue_b = [&](uint32_t fb, uint32_t bytes, uint32_t dst, int k0, bool whole) {
      if (whole) {
        tma_load_3d(dst, &tmWo, fb, 0, k0, cb2 * 2);
      } else {
#pragma unroll
        for (int i = 0; i < 4; i++)
          tma_load_3d(dst + (i & 1) * XT + (i >> 1) * 4 * XT, &tmWp, fb, 0, k0 + (i >> 1) * 32, cb2 * 2 + (i & 1));
      }
      mbar_expect_tx(fb, bytes);
    };
    auto send_y = [&](uint32_t o, uint32_t step, int half) {
      const uint32_t peer = mapa(sb, rank ^ 1);
      o += OFF_X + (rank ^ 1) * 4096 + half * 2048 + lane * 16;
      uint4 a[8];
#pragma unroll
      for (int i = 0; i < 8; i++) a[i] = lds128(sb + o + (i >> 2) * step + (i & 2) * (XT / 2) + (i & 1) * 512);
#pragma unroll
      for (int i = 0; i < 8; i++)
        st_async128(peer + o + 1024 + (i >> 2) * step + (i & 2) * (XT / 2) + (i & 1) * 512,
                    peer + OFF_BAR + 8 * (BAR_LAND + half), a[i].x, a[i].y, a[i].z, a[i].w);
    };

    if (halo_cta) {
      if (hw == 0) {
        int s = 1, ph = 1;
#pragma unroll 1
        for (int kb = 1; kb < 16; kb++) {
          mbar_wait(bars + 8 * (BAR_EMPTYB + s), ph);
          if (elect_one()) halo_issue(kb, s);
          if (++s == 3) { s = 0; ph ^= 1; }
        }
      }
      __syncwarp();
    } else if (hw == 0) {
      uint32_t epoch = 0;
      if (MODE == 2) {
        if (lane < NS2) mbar_arrive_cluster_n(mapa(bars, rank) + 8 * (BAR_EMPTY2 + lane), 2);
      } else {
      if (lane == 0) {
        mbar_expect_tx(bars + 8 * BAR_U, 32768);
        mbar_expect_tx(bars + 8 * BAR_LAND, 8192);
        mbar_expect_tx(bars + 8 * (BAR_LAND + 1), 8192);
        mbar_expect_tx(bars + 8 * BAR_Q, 32768);
        prefetch_tmap(&tmQ);
      }
      {
        int sa = 1, pha = 1, sbb = 2, phb = 1;
#pragma unroll 1
        for (int kb = 2; kb < 32; kb++) {
          if (!(kb & 1)) {
            mbar_wait(bars + 8 * (BAR_EMPTYA + sa), pha);
            if (elect_one()) g1_issue_a(kb >> 1, sa);
            if (++sa == NS1A) { sa = 0; pha ^= 1; }
          }
          mbar_wait(bars + 8 * (BAR_EMPTYB + sbb), phb);
          if (kb > 2 && elect_one()) g1_issue_b(kb, sbb);
          __syncwarp();
          if (kb == 4) epoch = ld_relaxed(g_flag_o + cta);
          if (kb == 4) PROF2(27);
          if (kb == 1) PROF2(38);
          if (kb == 2) PROF2(39);
          if (++sbb == NS1B) { sbb = 0; phb ^= 1; }
        }
      }
      auto q_issue = [&](int i) {
        mbar_wait(bars + 8 * (i ? BAR_EMPTYB + 3 : BAR_EMPTYA + 1), i);
        if (elect_one())
          asm volatile(
              "cp.async.bulk.tensor.5d.shared::cluster.global.mbarrier::complete_tx::bytes [%0], [%1, {%3, %4, %4, %4, %5}], [%2];\n"
              ::"r"(sb + (i ? OFF_Q1 : OFF_Q0)), "l"(&tmQ), "r"(bars + 8 * BAR_Q), "r"((chb & ~1) * 8), "r"(0), "r"(rank * 32 + i * 64)
              : "memory");
        __syncwarp();
      };
      if (QORD < 2) q_issue(0);
      else mbar_wait(bars + 8 * (BAR_EMPTYA + 1), 0);
      if (QORD < 1) q_issue(1);
      epoch++;
      if (lane == 0) {
        prefetch_tmap(&tmWo);
        prefetch_tmap(&tmWp);
        prefetch_tmap(&tmOb);
        if (gidx != 0) wait_flag(g_flag_h + (hp >> 2), epoch);
      }
      __syncwarp();
      {
        uint4 hk0 = make_uint4(0, 0, 0, 0), hk1 = hk0, hv0 = hk0, hv1 = hk0;
        if (gidx != 0) {
          const uint4* src = g_halo + cta * 128 + lane;
          hk0 = __ldcg(src); hk1 = __ldcg(src + 32); hv0 = __ldcg(src + 64); hv1 = __ldcg(src + 96);
        }
        if (gidx != 0) PROF(18);
        sts128(sb + OFF_KH + lane * 16, hk0.x, hk0.y, hk0.z, hk0.w);
        sts128(sb + OFF_KH + 512 + lane * 16, hk1.x, hk1.y, hk1.z, hk1.w);
        sts64(sb + OFF_KH + 1024 + lane * 8, movm(hv0.x), movm(hv0.y));
        sts64(sb + OFF_KH + 1280 + lane * 8, movm(hv0.z), movm(hv0.w));
        sts64(sb + OFF_KH + 1536 + lane * 8, movm(hv1.x), movm(hv1.y));
        sts64(sb + OFF_KH + 1792 + lane * 8, movm(hv1.z), movm(hv1.w));
        __syncwarp();
        if (lane == 0) mbar_arrive(bars + 8 * BAR_HALO);
      }
      if (QORD == 2) q_issue(0);
      if (QORD >= 1) q_issue(1);
      const uint32_t rb = mapa(bars, lane & 1);
      nb_sync(NB_OREADY, 288);
      if (lane == 0) {
        asm volatile("cp.async.bulk.global.shared::cta.bulk_group [%0], [%1], %2;\n" ::"l"(g_o + (size_t)cta * 16384),
                     "r"(sb + OFF_OP), "r"(32768) : "memory");
        bulk_commit();
      }
      if (lane < 2) {
#pragma unroll
        for (int i = 0; i < 4; i++) mbar_arrive_cluster(rb + 8 * (BAR_EMPTY2 + i + i / 2));
      }
      if (lane == 0) {
        bulk_wait0();
        st_release(g_flag_o + cta, epoch);
      }
      __syncwarp();
      PROF2(17);
      if (lane < 2) mbar_arrive_cluster(rb + 8 * (BAR_EMPTY2 + 2));
      }
      if (MODE != 1) {
        const __nv_bfloat16* osrc = g_o + (size_t)(rb2 >> 1) * 16 * 16384 + hsel * 8192;
        mbar_wait(bars + 8 * (BAR_EMPTY2 + 1), 0);
        if (elect_one()) {
          if (MODE == 0) {
            asm volatile("cp.async.bulk.shared::cluster.shared::cta.mbarrier::complete_tx::bytes [%0], [%1], %2, [%3];\n"
                         ::"r"(mapa(sb + g2_a(1, hsel), rank ^ 1)), "r"(sb + g2_a(0, hsel)), "r"(16384),
                         "r"(mapa(bars + 8 * (BAR_FULL2 + 1), rank ^ 1)) : "memory");
          } else {
            bulk_load(sb + g2_a(0, hsel), osrc + hp * 16384, 16384, bars + 8 * BAR_FULL2);
            bulk_load(sb + g2_a(1, hsel), osrc + (hp ^ 1) * 16384, 16384, bars + 8 * (BAR_FULL2 + 1));
          }
        }
        __syncwarp();
      }
      if (MODE != 2) {
        mbar_wait(bars + 8 * (BAR_Y + 2), 0);
        send_y(0, 4 * XT, 1);
        fence_async_smem();
        __syncwarp();
      }
      if (MODE != 1) {
        unsigned long long seq = G2_SEQ >> 12;
        uint32_t wbar = bars + 8 * (BAR_Y + 2), fb = bars + 8 * (BAR_FULL2 + 3), dst = sb + g2_b(3, rank), ph = MODE ? 1 : 0;
        int k0 = g2_k(3) * 64;
        bool whole = false;
#pragma unroll 1
        for (int kb = 4; kb <= 16; kb++) {
          mbar_wait(wbar, ph);
          if (elect_one()) g2_issue_b(fb, STG2, dst, k0, whole);
          __syncwarp();
          seq >>= 4;
          const int s = seq & 7;
          wbar = bars + 8 * (kb == G2_KB4 ? BAR_XFREE : BAR_EMPTY2B + s);
          ph = ((uint32_t)seq >> 3 & 1) ^ (kb == G2_KB4 && MODE == 0 ? 0 : 1);
          fb = bars + 8 * (BAR_FULL2 + s);
          dst = sb + g2_b(s, rank);
          k0 = ((hp & 12) ^ kb) * 64;
          whole = s < 3;
        }
      }
      __syncwarp();
    } else {
      if (MODE != 2) {
      const float dall = __bfloat162float(p.ssm_D[chb * 8 + lr]);
      {
        const int g = lane >> 2, t = lane & 3;
        uint32_t w[2][4];
#pragma unroll
        for (int h = 0; h < 2; h++) {
          const uint2 x = __ldg(reinterpret_cast<const uint2*>(p.shift_k + ((chb & ~1) * 8 + h * 8 + g) * 4));
          w[h][0] = __byte_perm(x.x, x.x, 0x1010);
          w[h][1] = __byte_perm(x.x, x.x, 0x3232);
          w[h][2] = __byte_perm(x.y, x.y, 0x1010);
          w[h][3] = __byte_perm(x.y, x.y, 0x3232);
        }
        auto swz = [](int r) { return (((r & 29) | ((r ^ (r >> 2)) & 2)) << 5) | (r & 16); };
        const uint32_t kring = sb + OFF_X + 4096 + (hw - 1) * 2 * XT, vring = kring + XT;
        const int s0 = rank * 32 + (hw - 1) * 11, s1 = hw == 3 ? rank * 32 + 32 : s0 + 11;
        const size_t goff = (size_t)(s0 * 32 + (lane >> 1)) * DM + (chb & ~1) * 8 + (lane & 1) * 8;
        const __nv_bfloat16* kg = p.k + goff;
        const __nv_bfloat16* vg = p.v + goff;
        const uint32_t d0 = swz(lane >> 1) ^ ((lane & 1) << 4), d1 = swz(16 + (lane >> 1)) ^ ((lane & 1) << 4);
        auto issue = [&](int st) {
          const uint32_t a = kring + ((st & 3) << 10);
          asm volatile("cp.async.cg.shared.global.L2::256B [%0], [%2], 16;\n"
                       "cp.async.cg.shared.global.L2::256B [%1], [%2 + 32768], 16;\n"
                       "cp.async.cg.shared.global.L2::256B [%0 + 8192], [%3], 16;\n"
                       "cp.async.cg.shared.global.L2::256B [%1 + 8192], [%3 + 32768], 16;\n"
                       ::"r"(a + d0), "r"(a + d1), "l"(kg), "l"(vg) : "memory");
          kg += 32 * DM;
          vg += 32 * DM;
          asm volatile("" : "+l"(kg), "+l"(vg));
        };
        const int xa = 8 * (lr >> 1) + 2 * lm + (lr & 1), xb = 8 * (lr >> 1) - 4 + 2 * (lm & 1) + (lr & 1);
        const uint32_t la = swz(xa), lb = swz(xb & 31);
        const int backb = xb < 0 ? 1 : 0;
        const uint32_t ud[2] = {mapa(sb + OFF_X + g * XT + t * 16, 0), mapa(sb + OFF_X + g * XT + t * 16, 1)};
        const uint32_t ub[2] = {mapa(bars + 8 * BAR_U, 0), mapa(bars + 8 * BAR_U, 1)};
        if (tid == 320) prefetch_l2(g_tab + (chb & 63) * 32);
        if (lane == 0) mbar_wait(bars + 8 * (BAR_FULLB + NS1B - 1), 0);
        __syncwarp();
        if (lane >= 24) cp_async16(kring + (((s0 - 1) & 3) << 10) + d1, s0 > 0 ? kg - 16 * DM : kg, s0 > 0 ? 16 : 0);
        issue(s0);
        asm volatile("cp.async.commit_group;\n" ::: "memory");
        issue(s0 + 1);
        asm volatile("cp.async.commit_group;\n" ::: "memory");
        const __nv_bfloat16* hg = p.ssm_k + (size_t)chb * 8 * SEQ + lane * 64;
        uint32_t tn = (uint32_t)clock();
#pragma unroll 1
        for (int st = s0; st < s1; st++) {
          tn += PSTEP;
          while ((int)((uint32_t)clock() - tn) < 0) __nanosleep(100);
          if (st + 2 < s1) issue(st + 2);
          if (hw == 1 && st - s0 < 8) prefetch_l2(hg);
          hg += SEQ;
          asm volatile("" : "+l"(hg));
          asm volatile("cp.async.commit_group;\n" ::: "memory");
          asm volatile("cp.async.wait_group 2;\n" ::: "memory");
          __syncwarp();
#pragma unroll
          for (int h = 0; h < 2; h++) {
            uint32_t e[6], vv[4], e4[4];
            ldsm4t(e4, kring + ((st & 3) << 10) + (la ^ (h << 4)));
            ldsm2t(e[0], e[1], kring + (((st - backb) & 3) << 10) + (lb ^ (h << 4)));
            ldsm4t(vv, vring + ((st & 3) << 10) + (la ^ (h << 4)));
            e[2] = e4[0]; e[3] = e4[1]; e[4] = e4[2]; e[5] = e4[3];
            uint32_t o[5];
#pragma unroll
            for (int i = 0; i < 5; i++) o[i] = __byte_perm(e[i], e[i + 1], 0x5432);
#pragma unroll
            for (int i = 0; i < 4; i++) {
              uint32_t a = bmul2(o[i], w[h][3]);
              a = bfma2(e[i + 1], w[h][2], a);
              a = bfma2(o[i + 1], w[h][1], a);
              a = bfma2(e[i + 2], w[h][0], a);
              vv[i] = bmul2(a, vv[i]);
            }
            st_async128(ud[h] + (st ^ (g & 1)) * 64, ub[h], vv[0], vv[1], vv[2], vv[3]);
          }
          __syncwarp();
        }
        fence_async_smem();
        PROF(16);
      }
      nb_sync(NB_HELP3, 96);
      if (hw == 1 && elect_one()) {
        mbar_expect_tx(bars + 8 * BAR_H, 8 * 4096);
#pragma unroll 1
        for (int c = 0; c < 8; c++)
          bulk_load(sb + OFF_X + c * XT + 4096, p.ssm_k + (size_t)(chb * 8 + c) * SEQ, 4096, bars + 8 * BAR_H);
        mbar_expect_tx(bars + 8 * BAR_X, 6144);
        bulk_load(sb + OFF_T16, g_tab, 2048, bars + 8 * BAR_X);
        bulk_load(sb + OFF_T32, g_tab + 512, 4096, bars + 8 * BAR_X);
      }
      __syncwarp();
      {
        if (WOP == 0) if (hw == 3) {
          const char* wo = (const char*)p.wo + chb * 16384 + lane * 128;
#pragma unroll
          for (int i = 0; i < 4; i++) prefetch_l2(wo + i * 4096);
        }
        const int ck = 16 * (lane >> 4) + 2 * lr + (((lane >> 3) ^ (lane >> 2)) & 1);
        const uint32_t xo = (ck >> 1) * 64, xs = ((ck & 1) ^ (lr >> 1)) << 4;
#pragma unroll 1
        for (int job = hw - 1; job < 16; job += 3) {
          const int c = job & 7;
          uint4 a[8];
          float dv = __shfl_sync(0xffffffffu, dall, c);
          if (job < 8 || lane) dv = 0.f;
          const uint32_t xt = sb + OFF_X + c * XT + (job >> 3) * 4096;
          mbar_wait(bars + 8 * (job < 8 ? BAR_U : BAR_H), 0);
#pragma unroll
          for (int i = 0; i < 8; i++) a[i] = lds128(xt + i * 512 + ((ck ^ (job < 8 ? (c & 1) << 2 : 0)) << 4));
          dv += bf_lo(a[0].x);
          uint32_t m[2] = {bmaxabs2(pack_bf16(dv, 0.f), bmaxabs2(a[0].x, a[0].y)), bmaxabs2(a[0].z, a[0].w)};
#pragma unroll
          for (int i = 1; i < 8; i++) {
            m[0] = bmaxabs2(bmaxabs2(m[0], a[i].x), a[i].y);
            m[1] = bmaxabs2(bmaxabs2(m[1], a[i].z), a[i].w);
          }
          m[0] = bmaxabs2(m[0], m[1]);
          const int f = max(252 - (int)(__reduce_max_sync(0xffffffffu, max(m[0] & 0x7fffu, (m[0] >> 16) & 0x7fffu)) >> 7), 1);
          if (lane == 0) asm volatile("st.shared.u32 [%0], %1;\n" ::"r"(sb + OFF_EX + job * 4), "r"(f) : "memory");
          if (f < 113) {
#pragma unroll
            for (int i = 0; i < 8; i++)
              a[i] = make_uint4(bmul2(a[i].x, f * 0x00800080u), bmul2(a[i].y, f * 0x00800080u), bmul2(a[i].z, f * 0x00800080u),
                                bmul2(a[i].w, f * 0x00800080u));
          }
          const uint32_t mul = (f < 113 ? 15 : f - 112) * 0x00800080u;
          auto cv = [&](uint32_t x) {
            x = bmul2(x, mul);
            return (x & 0x0fff0fffu) * 7 + x;
          };
          const uint32_t dst = xt + xo;
#pragma unroll
          for (int i = 0; i < 8; i++)
            sts128(dst + (i >> 2) * 2048 + (i & 1) * 1024 + (xs ^ ((i & 2) << 4)),
                   i ? cv(a[i].x) : __byte_perm(pack_f16(dv * __uint_as_float(f << 23), 0.f), cv(a[i].x), 0x7610), cv(a[i].y),
                   cv(a[i].z), cv(a[i].w));
        }
        fence_async_smem();
        __syncwarp();
        if (lane == 0) mbar_arrive(bars + 8 * BAR_X);
        if (WOP == 1) if (hw == 3) {
          const char* wo = (const char*)p.wo + chb * 16384 + lane * 128;
#pragma unroll
          for (int i = 0; i < 4; i++) prefetch_l2(wo + i * 4096);
        }
        PROF(19);
      }
      if (hw < 3) {
#pragma unroll 1
        for (int n = 0; n < SPIN_LIMIT && !mbar_try(bars + 8 * (BAR_Y + hw - 1), 0); n++) __nanosleep(100);
        send_y((hw - 1) * 4 * XT, 2 * XT, 0);
        __syncwarp();
        if (lane == 0) mbar_arrive(bars + 8 * (BAR_Y + 2));
        PROF(32);
        const int c8 = 2 * lm + (lr & 1), src = (lr >> 1) & 1;
        uint32_t fa = sb + OFF_X + c8 * XT + rank * 4096 + (src == rank ? 0 : 1024) + (hw - 1) * 512;
        const uint32_t fx = ((lr >> 2) ^ ((lr & 3) << 1)) << 4;
        uint32_t qa = sb + OFF_Q0 + (hw - 1) * 8192 + (lane >> 3) * 128 + (lane & 2) * 32 + (lane & 4) * 8 + (lane & 1) * 16;
        uint4* og = reinterpret_cast<uint4*>(p.out + (size_t)(rank * 512 + (hw - 1) * 256 + (lane & 2) * 4 + (lane >> 2)) * (2 * DM) +
                                             (chb & ~1) * 8 + (lane & 1) * 8);
        mbar_wait(bars + 8 * BAR_Q, 0);
        uint32_t tn = 0;
#pragma unroll 1
        for (int j = 0; j < 16; j++) {
          if (j == JS && hw == 2) {
            mbar_wait(bars + 8 * (BAR_Y + 3), 0);
            send_y(2 * XT, 4 * XT, 1);
            fence_async_smem();
            __syncwarp();
            if (lane == 0) mbar_arrive(bars + 8 * BAR_XFREE);
            tn = (uint32_t)clock();
          }
          if (!(j & 7)) {
            mbar_wait(bars + 8 * (BAR_LAND + (j >> 3)), 0);
            tn = (uint32_t)clock() + (hw - 1) * (FPACE / 2);
            PROF2(33 + (j >> 1));
          }
#pragma unroll
          for (int i = 0; i < 2; i++) {
            uint32_t y[4];
            const uint4 q = lds128(qa + i * 512);
            ldsm4t(y, fa + (j & 6) * 64 + (fx ^ (i << 5) ^ ((j & 1) << 6) ^ ((j & 2) << 3)));
            while ((int)((uint32_t)clock() - tn) < 0) __nanosleep(FSL);
            tn += hw == 2 ? FPACE2 : FPACE;
            og[i * 16 * (2 * DM / 8)] = make_uint4(bmul2(q.x, y[0]), bmul2(q.y, y[1]), bmul2(q.z, y[2]), bmul2(q.w, y[3]));
          }
          qa += j == 7 ? OFF_Q1 - OFF_Q0 - 7168 : 1024;
          if (j == 7) fa += 2048;
          og += (j == 7 ? 1024 - 224 : 32) * (2 * DM / 8);
        }
        PROF(22);
      }
      }
      if (MODE != 1 && hw == 3) {
        const uint32_t epoch = ld_relaxed(g_flag_o + cta) + 1;
        if (MODE == 0) nb_sync(NB_G1END, 288);
        if (BDEL) __nanosleep(BDEL);
        if (elect_one()) {
#pragma unroll
          for (int kb = 0; kb < 3; kb++)
            g2_issue_b(bars + 8 * (BAR_FULL2 + kb), kb || MODE ? STG2 : STG2 / 2, sb + g2_b(kb, 0), g2_k(kb) * 64, true);
        }
        __syncwarp();
        const __nv_bfloat16* osrc = g_o + (size_t)(rb2 >> 1) * 16 * 16384 + hsel * 8192;
        if (MODE == 0) __nanosleep(POLL0);
        const uint32_t* flag = g_flag_o + (rb2 >> 1) * 16 + g2_k(lane & 15);
        uint32_t ready = MODE == 0 ? 0u : ~0u;
        unsigned long long seq = G2_SEQ >> 8;
#pragma unroll 1
        for (int kb = 2; kb < 16; kb++, seq >>= 4) {
          uint32_t so = bars + (seq & 7) * 8, dst = sb + g2_a(seq & 7, hsel) + rank * 8192;
          const uint32_t ph = (uint32_t)seq >> 3 & 1;
          const __nv_bfloat16* src = osrc + rank * 4096 + (uint32_t)g2_k(kb) * 16384;
          asm volatile("" : "+r"(so), "+r"(dst), "+l"(src));
          if (!(ready >> kb & 1)) {
#pragma unroll 1
            for (int n = 0; n < SPIN_LIMIT && !(ready >> kb & 1); n++)
              ready = __ballot_sync(0xffffffffu, ld_acquire(flag) == epoch);
            fence_async_all();
          }
          if (kb == 2) PROF(21);
          if (MODE == 0 && kb == G2_KB4 && rank == 1) mbar_wait(bars + 8 * BAR_TAB, 0);
          mbar_wait(so + 8 * BAR_EMPTY2, ph);
          if (elect_one()) {
            asm volatile(
                "cp.async.bulk.shared::cluster.global.mbarrier::complete_tx::bytes.multicast::cluster [%0], [%1], %2, [%3], %4;\n"
                ::"r"(dst), "l"(src), "r"(8192), "r"(so + 8 * BAR_FULL2), "h"((uint16_t)3) : "memory");
          }
          __syncwarp();
        }
      }
    }
    cluster_sync_all();
    PROF_DUMP();
  } else {
    asm volatile("barrier.cluster.arrive.relaxed.aligned;\n" ::: "memory");
    asm volatile("setmaxnreg.inc.sync.aligned.u32 %0;\n" :: "n"(REG_MATH));
    if (halo_cta || MODE == 2) asm volatile("barrier.cluster.wait.aligned;\n" ::: "memory");
    if (warp == 0) PROF2(26);
    const int wg = warp >> 2;
    const int wtid = tid & 127;
    const bool signaller = (wtid == 0) || (wtid == 32);
    const uint32_t rbars = mapa(bars, wtid >> 5 & 1);

    if (halo_cta) {
      const uint32_t epoch = ld_relaxed(g_flag_h + blockIdx.x) + 1;
      float acc0[64], acc1[64];
      int s = 0, ph = 0;
#pragma unroll 1
      for (int kb = 0; kb < 16; kb++) {
        mbar_wait(bars + 8 * (BAR_FULLB + s), ph);
        const uint32_t st = sb + s * STGH;
        const uint64_t da = mkdesc(st, 16, 1024, 1);
        const uint64_t db = mkdesc(st + 8192 + wg * 32768, 8192, 1024, 1);
        wg_fence();
#pragma unroll
        for (int kk = 0; kk < 4; kk++) {
          wgmma_n128(acc0, da + 2 * kk, db + 128 * kk, kb + kk);
          wgmma_n128(acc1, da + 2 * kk, db + 1024 + 128 * kk, kb + kk);
        }
        wg_commit();
        wg_wait<0>();
        if (kb == 15) PROF(37);
        if (wtid == 0) mbar_arrive(bars + 8 * (BAR_EMPTYB + s));
        if (++s == 3) { s = 0; ph ^= 1; }
      }
      fence_regs(acc0);
      fence_regs(acc1);
      if ((warp & 3) != 3) {
#pragma unroll
        for (int hh = 0; hh < 2; hh++) {
          uint4* dst = g_halo + ((hh * 4 + (warp & 3) + 1) * 16 + blockIdx.x * 4) * 128 + wg * 64 + lane;
#pragma unroll
          for (int j = 0; j < 4; j++) {
            const int o = 16 * j + 2 * hh;
            dst[(j >> 1) * 128 + (j & 1) * 32] =
                make_uint4(pack_bf16(acc0[o], acc0[o + 1]), pack_bf16(acc0[o + 4], acc0[o + 5]),
                           pack_bf16(acc0[o + 8], acc0[o + 9]), pack_bf16(acc0[o + 12], acc0[o + 13]));
            dst[(2 + (j >> 1)) * 128 + (j & 1) * 32] =
                make_uint4(pack_bf16(acc1[o], acc1[o + 1]), pack_bf16(acc1[o + 4], acc1[o + 5]),
                           pack_bf16(acc1[o + 8], acc1[o + 9]), pack_bf16(acc1[o + 12], acc1[o + 13]));
          }
        }
      }
      nb_sync(NB_G1DONE, 256);
      if (tid == 0) st_release(g_flag_h + blockIdx.x, epoch);
      PROF(36);
      cluster_sync_all();
      return;
    }

    float acc[64];
    const uint32_t g2rel = wtid ? mapa(bars, rank) + 8 * BAR_EMPTY2B : mapa(bars, wg) + 8 * BAR_EMPTY2;
    uint32_t g2a = (uint32_t)mkdesc(sb + wg * 8192, 16, 0, 0), g2b = (uint32_t)mkdesc(sb, 8192, 0, 0);
    auto g2_block = [&](bool first, int s, int ph) {
      mbar_wait(bars + 8 * (BAR_FULL2 + s), ph);
      const uint32_t da = g2a + (g2_a(s, hsel) >> 4), db = g2b + (g2_b(s, rank) >> 4), dc = db + (g2_bk(s) >> 4);
      wg_fence();
      if (first) wgmma_n128z(acc, da, db);
      else wgmma_n128a(acc, da, db);
      wgmma_n128a(acc, da + 2, db + 128);
      wgmma_n128a(acc, da + 4, dc);
      wgmma_n128a(acc, da + 6, dc + 128);
      wg_commit();
    };
    if (MODE != 2) {
    uint32_t a1[2][4], sc[2];
    C2 t[2];
    {
      float acc0[96], acc1[96];
      int sa = 0, pha = 0;
      uint64_t db0 = mkdesc(sb + OFF_1B, 4096, 1024, 1);
      const uint64_t da0 = mkdesc(sb + wg * 16384, 16, 2048, 1);
      const bool sigb = wtid == 64;
      uint32_t rela = 0;
#pragma unroll 1
      for (int r = 0; r < 3; r++) {
#pragma unroll
        for (int i = 0; i < 2 * NS1B; i++) {
          const uint64_t da = da0 + sa * (STG1A >> 4) + (i & 1) * 4, db = db0 + (i % NS1B) * (STG1B >> 4);
          if (i || r) {
            if (!(i & 1)) mbar_wait(bars + 8 * (BAR_FULLA + sa), pha);
            mbar_wait(bars + 8 * (BAR_FULLB + i % NS1B), i / NS1B);
          } else {
            asm volatile("cp.async.wait_group 0;\n" ::: "memory");
            fence_async_smem();
            nb_sync(NB_FIRST, 256);
            PROF(0 + wg);
          }
          wg_fence();
          wgmma_n192(acc0, da + 64, db, i ? 1 : r);
          wgmma_n192(acc1, da, db, i ? 1 : r);
          wgmma_n192(acc0, da + 66, db + 128, 1);
          wgmma_n192(acc1, da + 2, db + 128, 1);
          wg_commit();
          wg_wait<1>();
          if (i || r) {
            if (sigb) mbar_arrive(bars + 8 * (BAR_EMPTYB + (i + NS1B - 1) % NS1B));
            if (!(i & 1) && signaller) mbar_arrive_cluster(rela);
          } else {
            asm volatile("barrier.cluster.wait.aligned;\n" ::: "memory");
          }
          if (i & 1) {
            rela = rbars + 8 * (BAR_EMPTYA + sa);
            if (++sa == NS1A) { sa = 0; pha ^= 1; }
          }
        }
        db0 += p.zero;
      }
      const int lr = lane & 7, lm = lane >> 3;
      const bool le0 = 2 * (lane & 3) <= (lane >> 2), le1 = 2 * (lane & 3) + 1 <= (lane >> 2);
      const uint32_t maskLE = (le0 ? 0x0000FFFFu : 0u) | (le1 ? 0xFFFF0000u : 0u);
      uint32_t q[4][8], k[5][8], vt[5][8];
      {
        static_assert(15 % NS1A == 0 && 30 % NS1B == 0, "slots of the last k blocks");
        asm volatile("ld.volatile.global.v4.u32 {%0,%1,%2,%3}, [%4];\n"
                     : "=r"(t[0].r), "=r"(t[1].r), "=r"(t[0].i), "=r"(t[1].i) : "l"(g_tab + 1536 + wtid * 4) : "memory");
        mbar_wait(bars + 8 * BAR_FULLA, 1);
        mbar_wait(bars + 8 * BAR_FULLB, 0);
        mbar_wait(bars + 8 * (BAR_FULLB + 1), 0);
        mbar_wait(bars + 8 * (BAR_EMPTYA + 1), 0);
        const uint64_t da = mkdesc(sb + wg * 16384, 16, 2048, 1);
        const uint64_t db = mkdesc(sb + OFF_1B, 4096, 1024, 1);
        wg_fence();
#pragma unroll
        for (int i = 0; i < 4; i++) wgmma_n192(acc0, da + 64 + 2 * i, db + (i >> 1) * (STG1B >> 4) + (i & 1) * 128, 1);
        wg_commit();
#pragma unroll
        for (int i = 0; i < 2; i++) wgmma_n192(acc1, da + 2 * i, db + (i >> 1) * (STG1B >> 4) + (i & 1) * 128, 1);
        wg_commit();
        wg_wait<1>();
        fence_regs(acc0);
        PROFA(45, 0);
        attn_pack<8, 1, false>(acc0, k[4]);
        attn_pack<16, 1, true>(acc0, vt[4]);
        const uint32_t kh = sb + (warp == 7 ? OFF_OP + 7 * 4096 : OFF_KH + (warp + 1) * 2048) + lane * 16;
        sts128(kh, k[4][0], k[4][1], k[4][2], k[4][3]);
        sts128(kh + 512, k[4][4], k[4][5], k[4][6], k[4][7]);
#pragma unroll
        for (int i = 0; i < 4; i++) sts64(kh - lane * 8 + 1024 + 256 * i, vt[4][2 * i], vt[4][2 * i + 1]);
#pragma unroll
        for (int i = 2; i < 4; i++) wgmma_n192(acc1, da + 2 * i, db + (i >> 1) * (STG1B >> 4) + (i & 1) * 128, 1);
        wg_commit();
        attn_pack<0, 0, false>(acc0, q[1]);
        attn_pack<0, 1, false>(acc0, q[3]);
        attn_pack<8, 0, false>(acc0, k[2]);
        attn_pack<16, 0, true>(acc0, vt[2]);
        uint32_t z = p.zero;
#pragma unroll
        for (int i = 0; i < 8; i++) z &= q[1][i] & q[3][i];
#pragma unroll
        for (int i = 0; i < 8; i += 2) z &= k[2][i] & k[2][i + 1];
        __syncwarp();
        if (lane == 0) mbar_arrive(bars + 8 * BAR_STG + z);
        wg_wait<0>();
        fence_regs(acc1);
        if (MODE == 0) nb_arrive(NB_G1END, 288);
      }
      PROF(2 + wg);
      mbar_wait(bars + 8 * (warp == 0 ? BAR_HALO : BAR_STG), 0);
      {
        const uint32_t kh = sb + OFF_KH + warp * 2048 + lane * 16;
#pragma unroll
        for (int i = 0; i < 2; i++) {
          const uint4 t = lds128(kh + 512 * i);
          k[0][4 * i] = t.x; k[0][4 * i + 1] = t.y; k[0][4 * i + 2] = t.z; k[0][4 * i + 3] = t.w;
        }
#pragma unroll
        for (int i = 0; i < 4; i++) {
          const uint2 t = lds64(kh - lane * 8 + 1024 + 256 * i);
          vt[0][2 * i] = t.x; vt[0][2 * i + 1] = t.y;
        }
      }
      attn_pack<0, 0, false>(acc1, q[0]);
      attn_pack<0, 1, false>(acc1, q[2]);
      attn_pack<8, 0, false>(acc1, k[1]);
      attn_pack<8, 1, false>(acc1, k[3]);
      {
        float x[8][2];
        uint32_t pp[8];
        const bool first = warp == 0 && gidx == 0;
#pragma unroll
        for (int hd = 0; hd < 2; hd++) {
#pragma unroll
          for (int j = 0; j < 4; j += 2) {
            float s0[4], s1[4], s2[4];
            attn_qk(s2, q[j], q[j + 1], k[j + 2], 4 * hd);
            attn_qk(s1, q[j], q[j + 1], k[j + 1], 4 * hd);
            attn_qk(s0, q[j], q[j + 1], k[j], 4 * hd);
            if (j == 0 && first) s0[0] = s0[1] = -1e9f / 0.17677669529663687f;
            x[2 * j + hd][0] = le0 ? s1[0] : s0[0];
            x[2 * j + hd][1] = le1 ? s1[1] : s0[1];
            x[2 * j + 2 + hd][0] = le0 ? s2[2] : s1[2];
            x[2 * j + 2 + hd][1] = le1 ? s2[3] : s1[3];
          }
        }
        PROFA(40, __float_as_uint(x[1][0] + x[7][1]));
        attn_pack<16, 0, true>(acc1, vt[1]);
        attn_pack<16, 1, true>(acc1, vt[3]);
        quad_softmax<8>(x, pp);
        PROFA(41, pp[1] + pp[7]);
        mbar_wait(bars + 8 * BAR_X, 0);
        ldsm4(a1[0], sb + OFF_T32 + (warp & 3) * 1024 + lane * 16);
        ldsm4(a1[1], sb + OFF_T32 + 512 + (warp & 3) * 1024 + lane * 16);
        {
          const uint32_t ex = sb + OFF_EX + wg * 16 + (warp & 2) * 2;
#pragma unroll
          for (int i = 0; i < 2; i++) sc[i] = min(max(381 - (int)lds32(ex + 8 * i) - (int)lds32(ex + 32 + 8 * i), 1), 254) * 0x00800080u;
        }
        const uint32_t obase = sb + OFF_OP + (warp * 32 + lr) * 128;
#pragma unroll
        for (int n = 0; n < 8; n++) {
          attn_pv(obase + (n >> 1) * 1024 + (((4 * (n & 1) + lm) ^ lr) << 4), vt[n >> 1], vt[(n >> 1) + 1], 4 * (n & 1), pp[n],
                  maskLE);
        }
      }
      PROFA(42, 0);
    }

    {
      const int w = warp & 3;
      const int lr = lane & 7, lm = lane >> 3;
      const uint32_t xb = sb + OFF_X + wg * 4 * XT;
      auto uo = [](int c) { return (c & 1) * 2 * XT + (c >> 1) * 2048; };
      const uint64_t dc2 = mkdesc(sb + OFF_T16, 512, 128, 0), dc3 = mkdesc(sb + OFF_T16, 128, 512, 0);
      const uint64_t dc4 = mkdesc(sb + OFF_T32, 128, 256, 0);
      const uint64_t dx = mkdesc(xb, 4096, 512, 2), dz = mkdesc(xb, 4096, 256, 3);
      const uint32_t zs = xb + (w * 16 + (lm & 1) * 8 + lr) * 32 + (((lm >> 1) ^ (lr >> 2)) << 4);
      const uint32_t ys = xb + w * 4096 + (lm >> 1) * 256 + ((lr * 32 + (((lm & 1) ^ (lr >> 2)) << 4)) ^ (rank << 6) ^ ((w & 2) << 4));
      const bool own = (w & 1) == rank;
      const uint32_t ybar = mapa(bars, own ? rank ^ 1 : rank) + 8 * BAR_Y;
      uint32_t d[2][32], pa[2][4][2][4], e[4][4][8], ya[2][2][2][4], v[2][2][8];
      C2 s1[2][2][2];
      float o[2][16];
      auto rows = [&](int c) {
        fft_rows(d[c & 1], a1, dx + (uo(c) >> 4));
        wg_commit();
      };
      auto cols = [&](int c) {
        const int s = c & 1;
        fence_regs(d[s]);
#pragma unroll
        for (int i = 0; i < 16; i++) {
          const C2 z = crot(C2{d[s][2 * i], d[s][2 * i + 1]}, t[i & 1]);
          pa[s][i >> 2][i & 1][(i >> 1) & 1] = z.r;
          pa[s][i >> 2][i & 1][2 + ((i >> 1) & 1)] = z.i;
        }
        wg_fence();
#pragma unroll
        for (int i = 0; i < 4; i++) fft_cols<0>(e[c][i], pa[s][i], dc2);
        wg_commit();
      };
      auto prod = [&](int c, int n) {
        const int s = c & 1;
        fence_regs(e[c][2 * n]);
        fence_regs(e[c][2 * n + 1]);
#pragma unroll
        for (int j = 0; j < 2; j++) {
          const C2 u0 = cget(e[s][2 * n], j, 0), u1 = cget(e[s][2 * n], j, 1);
          const C2 h0 = cget(e[s][2 * n + 1], j, 0), h1 = cget(e[s][2 * n + 1], j, 1);
          C2 y0, y1;
          if (c < 2) {
            y0 = cmul(h0, u0);
            s1[s][n][j] = cfma(h0, u1, cmul(h1, u0));
            y1 = C2{hadd2(s1[s][n][j].r, y0.i), hadd2(s1[s][n][j].i, hneg2(y0.r))};
          } else {
            const C2 u2 = cget(e[c][2 * n], j, 0), u3 = cget(e[c][2 * n], j, 1);
            const C2 h2 = cget(e[c][2 * n + 1], j, 0), h3 = cget(e[c][2 * n + 1], j, 1);
            const C2 s2 = cfma(h0, u2, cfma(h2, u0, cmul(h1, u1)));
            y0 = C2{hadd2(s2.r, s1[s][n][j].i), hadd2(s2.i, hneg2(s1[s][n][j].r))};
            y1 = cfma(h0, u3, cfma(h1, u2, cfma(h2, u1, cfma(h3, u0, C2{s2.i, hneg2(s2.r)}))));
          }
          ya[s][n][j][0] = y0.r;
          ya[s][n][j][1] = y1.r;
          ya[s][n][j][2] = y0.i;
          ya[s][n][j][3] = y1.i;
        }
      };
      auto icols = [&](int c) {
        wg_fence();
        fft_cols<1>(v[c & 1][0], ya[c & 1][0], dc3);
        fft_cols<1>(v[c & 1][1], ya[c & 1][1], dc3);
        wg_commit();
      };
      auto stage = [&](int c) {
        const int s = c & 1;
        fence_regs(v[s][0]);
        fence_regs(v[s][1]);
#pragma unroll
        for (int b = 0; b < 4; b++) {
          const C2 x0 = cget(v[s][b >> 1], 0, b & 1), x1 = cget(v[s][b >> 1], 1, b & 1);
          const C2 z0 = crot(C2{x0.i, x0.r}, t[0]), z1 = crot(C2{x1.i, x1.r}, t[1]);
          stsm4(zs + uo(c) + b * 4096, z0.i, z0.r, z1.i, z1.r);
        }
      };
      auto back = [&](int c) {
        fft_back(o[c & 1], dz + (uo(c) >> 4), dc4);
        wg_commit();
      };
      auto out = [&](int c) {
        float (&r)[16] = o[c & 1];
        fence_regs(r);
#pragma unroll
        for (int i = 0; i < 16; i += 8)
          stsm4t(ys + uo(c) + 64 * i, bmul2(pack_bf16(r[i], r[i + 1]), sc[c & 1]), bmul2(pack_bf16(r[i + 2], r[i + 3]), sc[c & 1]),
                 bmul2(pack_bf16(r[i + 4], r[i + 5]), sc[c & 1]), bmul2(pack_bf16(r[i + 6], r[i + 7]), sc[c & 1]));
      };
      auto signal = [&](int yb, int land) {
        __syncwarp();
        if (lane == 0) {
          mbar_arrive_cluster(ybar + 8 * yb);
          if (own && land >= 0) mbar_arrive(bars + 8 * (BAR_LAND + land));
        }
      };
      wg_fence();
      rows(0);
      rows(1);
      fence_async_smem();
      nb_arrive(NB_OREADY, 288);
      PROF(34 + wg);
      wg_wait<1>();
      cols(0);
      wg_wait<1>();
      cols(1);
      rows(2);
      nb_sync(NB_CONV + wg, 128);
      wg_wait<2>();
      prod(0, 0);
      prod(0, 1);
      icols(0);
      wg_wait<2>();
      prod(1, 0);
      prod(1, 1);
      icols(1);
      PROF3(40 + 10 * wg);
      wg_wait<1>();
      stage(0);
      wg_wait<0>();
      stage(1);
      fence_async_smem();
      cols(2);
      PROF3(41 + 10 * wg);
      nb_sync(NB_CONV + wg, 128);
      back(0);
      back(1);
      wg_wait<2>();
      wg_fence();
      rows(3);
      prod(2, 0);
      wg_wait<1>();
      out(0);
      out(1);
      signal(wg, 0);
      PROF3(42 + 10 * wg);
      prod(2, 1);
      icols(2);
      wg_wait<1>();
      cols(3);
      PROF3(43 + 10 * wg);
      wg_wait<1>();
      stage(2);
      fence_async_smem();
      wg_wait<0>();
      prod(3, 0);
      nb_sync(NB_CONV + wg, 128);
      wg_fence();
      back(2);
      prod(3, 1);
      icols(3);
      PROF3(44 + 10 * wg);
      wg_wait<1>();
      out(2);
      signal(2, -1);
      wg_wait<0>();
      stage(3);
      PROF3(45 + 10 * wg);
      fence_async_smem();
      nb_sync(NB_CONV + wg, 128);
      wg_fence();
      back(3);
      constexpr int G = MODE == 0 && EARLY;
      if (MODE == 0) mbar_wait(bars + 8 * (BAR_EMPTY2 + 4), 0);
      if (G) g2_block(true, 0, 0);
      wg_wait<G>();
      if (lane == 0) mbar_arrive_cluster(mapa(bars, 1) + 8 * BAR_TAB);
      out(3);
      signal(3, 1);
      PROF(6 + wg);
    }
    }

    if (MODE != 1) {
      if (MODE == 2 || !EARLY) g2_block(true, 0, 0);
      const int lr = lane & 7, lm = lane >> 3;
      const uint32_t wb = sb + g2_a(1, 0) + warp * 2048;
      const int orow = (rb2 & 7) * 128 + warp * 16;
      uint4* og = reinterpret_cast<uint4*>(p.out + (size_t)(2 * (orow + lm) + (rb2 >> 3)) * (2 * DM) + DM + cb2 * 128 + lr * 8);
      uint32_t wst = wb + (lr + 8 * (lm & 1)) * 128, wsx = ((lm >> 1) ^ lr) << 4, wld = wb + lm * 128, wlx = (lr ^ lm) << 4;
      asm volatile("" : "+l"(og), "+r"(wst), "+r"(wsx), "+r"(wld), "+r"(wlx));
      static_assert(ENDG == NS2 && (G2SEQ >> 4 & 0xfffff) == (G2SEQ >> 24 & 0xfffff) && (G2SEQ >> 4 & 0xfffff) == G2SEQ >> 44, "rounds");
#pragma unroll 1
      for (int r = 0; r < 3; r++) {
        const bool hold = r == 2 && wg != LEADWG;
        const uint32_t rel0 = g2rel + (r ? 8 * (G2SEQ >> 20 & 7) : 0);
        if (hold) {
          wg_wait<0>();
          if (signaller) mbar_arrive_cluster(rel0);
          nb_sync(NB_LEAD, 256);
        }
#pragma unroll
        for (int i = 1; i <= NS2; i++) {
          const int s = G2SEQ >> (4 * i) & 7;
          g2_block(false, s, (r & 1) ^ (s == 0));
          if (warp == LEADWG * 4) PROF2(40 + 5 * r + i);
          if (i == 1 ? !hold : r < 2) {
            wg_wait<1>();
            if (signaller) mbar_arrive_cluster(i == 1 ? rel0 : g2rel + 8 * (G2SEQ >> (4 * i - 4) & 7));
          }
        }
        if (r == 0) PROF(8 + wg);
        g2a += p.zero;
        g2b += p.zero;
      }
      if (wg == LEADWG) nb_arrive(NB_LEAD, 256);
      wg_wait<0>();
      fence_regs(acc);
      PROF(10 + wg);
#pragma unroll
      for (int h = 0; h < 2; h++) {
        const uint32_t b = h * (g2_a(3, 0) - g2_a(1, 0));
#pragma unroll
        for (int j = 8 * h; j < 8 * h + 8; j += 2)
          stsm4(wst + b + (wsx ^ ((j & 7) << 4)), pack_bf16(acc[4 * j], acc[4 * j + 1]),
                pack_bf16(acc[4 * j + 2], acc[4 * j + 3]), pack_bf16(acc[4 * j + 4], acc[4 * j + 5]),
                pack_bf16(acc[4 * j + 6], acc[4 * j + 7]));
        if (OTMA == 2 || (OTMA == 1 && wg == LEADWG)) {
          fence_async_smem();
          __syncwarp();
          if (elect_one()) {
            tma_store_3d(&tmOb, wb + b, DM + cb2 * 128 + h * 64, rb2 >> 3, orow);
            bulk_commit();
          }
        } else {
          __syncwarp();
          uint4 v[4];
#pragma unroll
          for (int i = 0; i < 4; i++) v[i] = lds128(wld + b + i * 512 + (wlx ^ ((i & 1) << 6)));
#pragma unroll
          for (int i = 0; i < 4; i++) og[(size_t)i * 8 * (2 * DM / 8) + h * 8] = v[i];
        }
      }
      PROF(12 + wg);
      if (OTMA) bulk_wait0();
    }
    cluster_sync_all();
  }
}

typedef CUresult (*EncodeFn)(CUtensorMap*, CUtensorMapDataType, cuuint32_t, void*, const cuuint64_t*, const cuuint64_t*,
                             const cuuint32_t*, const cuuint32_t*, CUtensorMapInterleave, CUtensorMapSwizzle,
                             CUtensorMapL2promotion, CUtensorMapFloatOOBfill);

void make_map(EncodeFn enc, CUtensorMap* tm, const void* base, int rank, const cuuint64_t* dims, const cuuint64_t* strides,
              const cuuint32_t* box, CUtensorMapSwizzle swz) {
  cuuint32_t es[5] = {1, 1, 1, 1, 1};
  enc(tm, CU_TENSOR_MAP_DATA_TYPE_BFLOAT16, rank, const_cast<void*>(base), dims, strides, box, es,
      CU_TENSOR_MAP_INTERLEAVE_NONE, swz, CU_TENSOR_MAP_L2_PROMOTION_L2_256B, CU_TENSOR_MAP_FLOAT_OOB_FILL_NONE);
}

}

extern "C" void kernel_launch(void* const* d_in, const int* in_sizes, int n_in, void* d_out, int out_size) {
  static EncodeFn enc = nullptr;
  static bool coresident = true;
  if (!enc) {
    void* fn = nullptr;
    cudaDriverEntryPointQueryResult qr;
    cudaGetDriverEntryPoint("cuTensorMapEncodeTiled", &fn, cudaEnableDefault, &qr);
    enc = (EncodeFn)fn;
    cudaFuncSetAttribute(fused_kernel<0>, cudaFuncAttributeMaxDynamicSharedMemorySize, SMEM_BYTES);
    cudaFuncSetAttribute(fused_kernel<1>, cudaFuncAttributeMaxDynamicSharedMemorySize, SMEM_BYTES);
    cudaFuncSetAttribute(fused_kernel<2>, cudaFuncAttributeMaxDynamicSharedMemorySize, SMEM_BYTES);
    cudaLaunchConfig_t cfg = {};
    cfg.gridDim = dim3(NCTA);
    cfg.blockDim = dim3(NTHREADS);
    cfg.dynamicSmemBytes = SMEM_BYTES;
    cudaLaunchAttribute at;
    at.id = cudaLaunchAttributeClusterDimension;
    at.val.clusterDim.x = 2;
    at.val.clusterDim.y = 1;
    at.val.clusterDim.z = 1;
    cfg.attrs = &at;
    cfg.numAttrs = 1;
    int nclusters = 0;
    if (cudaOccupancyMaxActiveClusters(&nclusters, fused_kernel<0>, &cfg) == cudaSuccess) coresident = nclusters >= NCTA / 2;
    (void)cudaGetLastError();
  }
  CUtensorMap tmX, tmW, tmWo, tmWp, tmQ, tmOb, tmXh, tmWh;
  {
    cuuint64_t dims[3] = {1024, 2, 1024};
    cuuint64_t str[2] = {2048, 4096};
    cuuint32_t box[3] = {64, 1, 128};
    make_map(enc, &tmX, d_in[6], 3, dims, str, box, CU_TENSOR_MAP_SWIZZLE_128B);
  }
  {
    cuuint64_t dims[3] = {1024, 1024, 3};
    cuuint64_t str[2] = {6144, 2048};
    cuuint32_t box[3] = {64, 32, 3};
    make_map(enc, &tmW, d_in[7], 3, dims, str, box, CU_TENSOR_MAP_SWIZZLE_128B);
  }
  {
    cuuint64_t dims[3] = {64, 1024, 16};
    cuuint64_t str[2] = {2048, 128};
    cuuint32_t box[3] = {64, 64, 2};
    cuuint32_t piece[3] = {64, 32, 1};
    make_map(enc, &tmWo, d_in[8], 3, dims, str, box, CU_TENSOR_MAP_SWIZZLE_128B);
    make_map(enc, &tmWp, d_in[8], 3, dims, str, piece, CU_TENSOR_MAP_SWIZZLE_128B);
  }
  {
    cuuint64_t dims[5] = {1024, 2, 2, 4, 128};
    cuuint64_t str[4] = {2048, 8 * 2048, 2 * 2048, 16 * 2048};
    cuuint32_t box[5] = {16, 2, 2, 4, 32};
    make_map(enc, &tmQ, d_in[0], 5, dims, str, box, CU_TENSOR_MAP_SWIZZLE_NONE);
  }
  {
    cuuint64_t dims[3] = {2048, 2, 1024};
    cuuint64_t str[2] = {4096, 8192};
    cuuint32_t box[3] = {64, 1, 16};
    make_map(enc, &tmOb, d_out, 3, dims, str, box, CU_TENSOR_MAP_SWIZZLE_128B);
  }
  {
    cuuint64_t dims[4] = {1024, 256, 2, 4};
    cuuint64_t str[3] = {4096, 2048, 256 * 4096};
    cuuint32_t box[4] = {64, 8, 2, 3};
    make_map(enc, &tmXh, d_in[6], 4, dims, str, box, CU_TENSOR_MAP_SWIZZLE_128B);
  }
  {
    cuuint64_t dims[3] = {64, 1024, 48};
    cuuint64_t str[2] = {6144, 128};
    cuuint32_t box[3] = {64, 64, 4};
    make_map(enc, &tmWh, d_in[7], 3, dims, str, box, CU_TENSOR_MAP_SWIZZLE_128B);
  }
  Params p;
  p.q = (const __nv_bfloat16*)d_in[0];
  p.k = (const __nv_bfloat16*)d_in[1];
  p.v = (const __nv_bfloat16*)d_in[2];
  p.shift_k = (const __nv_bfloat16*)d_in[3];
  p.ssm_k = (const __nv_bfloat16*)d_in[4];
  p.ssm_D = (const __nv_bfloat16*)d_in[5];
  p.x = (const __nv_bfloat16*)d_in[6];
  p.w = (const __nv_bfloat16*)d_in[7];
  p.wo = (const __nv_bfloat16*)d_in[8];
  p.out = (__nv_bfloat16*)d_out;
  p.zero = 0;
  if (coresident) {
    fused_kernel<0><<<NCTA, NTHREADS, SMEM_BYTES>>>(p, tmX, tmW, tmWo, tmWp, tmQ, tmOb, tmXh, tmWh);
  } else {
    fused_kernel<0><<<4, NTHREADS, SMEM_BYTES>>>(p, tmX, tmW, tmWo, tmWp, tmQ, tmOb, tmXh, tmWh);
    fused_kernel<1><<<NCTA, NTHREADS, SMEM_BYTES>>>(p, tmX, tmW, tmWo, tmWp, tmQ, tmOb, tmXh, tmWh);
    fused_kernel<2><<<NCTA, NTHREADS, SMEM_BYTES>>>(p, tmX, tmW, tmWo, tmWp, tmQ, tmOb, tmXh, tmWh);
  }
}
```

```cpp
#include <cuda_runtime.h>
#include <cuda.h>
#include <cuda_bf16.h>
#include <stdint.h>

namespace {

constexpr int SEQ = 2048;
constexpr int DM = 1024;
constexpr int NCTA = 132;
constexpr int NTHREADS = 384;

constexpr int STG1A = 32768;
constexpr int NS1A = 3;
constexpr int STG1B = 12288;
constexpr int NS1B = 5;
constexpr int OFF_1B = NS1A * STG1A;
constexpr int STG2 = 32768;
constexpr int NS2 = 5;
#define G2SEQ 0x0432104321043210ull
constexpr unsigned long long g2_seq() {
  unsigned long long r = G2SEQ;
  for (int kb = 0; kb < 16; kb++)
    for (int j = 0; j < kb; j++)
      if (((G2SEQ >> (4 * j)) & 7) == ((G2SEQ >> (4 * kb)) & 7)) r ^= 8ull << (4 * kb);
  return r;
}
constexpr unsigned long long G2_SEQ = g2_seq();
constexpr int g2_first4() {
  int kb = 0;
  while (((G2SEQ >> (4 * kb)) & 7) != 4) kb++;
  return kb;
}
constexpr int G2_KB4 = g2_first4();
#define POLL0 1500
#define BDEL 0
#define WOP 0
#define PSTEP 1250
#define FPACE 260
#define LEADWG 1
#define OTMA 1
#define EARLY 1
#define R3 1
#define FSL 50
#define JS 1
#define FPACE2 230
#define PFR 1
#define PF2 2
#define PF2X 1
#define ENDG 5
__device__ __forceinline__ uint32_t g2_a(int s, int hsel) { return (((0x97524 >> (4 * s)) & 15) ^ (s & 5 ? 0 : hsel)) << 14; }
constexpr int OFF_Q0 = 3 << 14, OFF_Q1 = 8 << 14;
constexpr int STGH = 40960;
constexpr int OFF_KH = 1 * STG2;
constexpr int OFF_OP = 2 * STG2;
constexpr int OFF_T32 = 5 * STG2 - 4096;
constexpr int OFF_X = 5 * STG2;
constexpr int XT = 8192;
__device__ __forceinline__ uint32_t g2_b(int s, int rank) {
  return s < 3 ? (s == 2 ? 6 : s) << 14 : OFF_X + (s - 3) * 2 * XT + (rank ^ 1) * 4096;
}
__device__ __forceinline__ uint32_t g2_bk(int s) { return s < 3 ? 4096 : 4 * XT; }
constexpr int OFF_BAR = OFF_X + 8 * XT;
constexpr int OFF_EX = OFF_BAR + 448;
constexpr int OFF_T16 = 230400;
constexpr int SMEM_BYTES = OFF_T16 + 2048;
static_assert(OFF_1B + NS1B * STG1B <= OFF_T32 && OFF_X % 1024 == 0, "layout");
static_assert(NS1B * STGH <= OFF_BAR && OFF_EX + 64 <= OFF_T16 && SMEM_BYTES <= 232448, "smem");

constexpr int BAR_FULLA = 0;
constexpr int BAR_EMPTYA = 3;
constexpr int BAR_FULLB = 6;
constexpr int BAR_EMPTYB = 11;
constexpr int BAR_FULL2 = 16;
constexpr int BAR_EMPTY2 = 21;
constexpr int BAR_EMPTY2B = 44;
constexpr int BAR_X = 26;
constexpr int BAR_LAND = 42;
constexpr int BAR_TAB = 28;
constexpr int BAR_U = 29;
constexpr int BAR_H = 30;
constexpr int BAR_STG = 31;
constexpr int BAR_Y = 32;
constexpr int BAR_XFREE = 38;
constexpr int BAR_HALO = 40;
constexpr int BAR_Q = 41;

constexpr int NB_LEAD = 2;
constexpr int NB_G1END = 3;
constexpr int NB_OREADY = 4;
constexpr int NB_CONV = 5;
constexpr int NB_HELP3 = 11;
constexpr int NB_FIRST = 13;

#define REG_MATH 224
#define REG_HELP 56
constexpr int SPIN_LIMIT = 1 << 20;

__device__ __align__(1024) __nv_bfloat16 g_o[SEQ * DM];
__device__ uint32_t g_flag_o[128];
__device__ uint4 g_halo[128 * 192];
__device__ __align__(128) const uint32_t g_tab[2048] = {
  0x2fd93000,0x2ea72f64,0x2c722da8,0x263e2a1f,0x2ea73000,0xa63e2a1f,0xafd9ada8,0xac72af64,0x2c723000,0xafd9aa1f,0x263eada8,0x2ea72f64,
  0x263e3000,0xac72af64,0x2ea72da8,0xafd9aa1f,0xa63e3000,0x2c72af64,0xaea72da8,0x2fd9aa1f,0xac723000,0x2fd9aa1f,0xa63eada8,0xaea72f64,
  0xaea73000,0x263e2a1f,0x2fd9ada8,0x2c72af64,0xafd93000,0xaea72f64,0xac722da8,0xa63e2a1f,0x263e0000,0x2c722a1f,0x2ea72da8,0x2fd92f64,
  0x2c720000,0x2fd92f64,0x263e2da8,0xaea7aa1f,0x2ea70000,0x263e2f64,0xafd9ada8,0x2c72aa1f,0x2fd90000,0xaea72a1f,0x2c72ada8,0xa63e2f64,
  0x2fd90000,0xaea7aa1f,0x2c722da8,0xa63eaf64,0x2ea70000,0x263eaf64,0xafd92da8,0x2c722a1f,0x2c720000,0x2fd9af64,0x263eada8,0xaea72a1f,
  0x263e0000,0x2c72aa1f,0x2ea7ada8,0x2fd9af64,0xafd93000,0xaea72f64,0xac722da8,0xa63e2a1f,0xaea73000,0x263e2a1f,0x2fd9ada8,0x2c72af64,
  0xac723000,0x2fd9aa1f,0xa63eada8,0xaea72f64,0xa63e3000,0x2c72af64,0xaea72da8,0x2fd9aa1f,0x263e3000,0xac72af64,0x2ea72da8,0xafd9aa1f,
  0x2c723000,0xafd9aa1f,0x263eada8,0x2ea72f64,0x2ea73000,0xa63e2a1f,0xafd9ada8,0xac72af64,0x2fd93000,0x2ea72f64,0x2c722da8,0x263e2a1f,
  0xa63e0000,0xac722a1f,0xaea72da8,0xafd92f64,0xac720000,0xafd92f64,0xa63e2da8,0x2ea7aa1f,0xaea70000,0xa63e2f64,0x2fd9ada8,0xac72aa1f,
  0xafd90000,0x2ea72a1f,0xac72ada8,0x263e2f64,0xafd90000,0x2ea7aa1f,0xac722da8,0x263eaf64,0xaea70000,0xa63eaf64,0x2fd92da8,0xac722a1f,
  0xac720000,0xafd9af64,0xa63eada8,0x2ea72a1f,0xa63e0000,0xac72aa1f,0xaea7ada8,0xafd9af64,0xa63e0000,0xac72aa1f,0xaea7ada8,0xafd9af64,
  0xac720000,0xafd9af64,0xa63eada8,0x2ea72a1f,0xaea70000,0xa63eaf64,0x2fd92da8,0xac722a1f,0xafd90000,0x2ea7aa1f,0xac722da8,0x263eaf64,
  0xafd90000,0x2ea72a1f,0xac72ada8,0x263e2f64,0xaea70000,0xa63e2f64,0x2fd9ada8,0xac72aa1f,0xac720000,0xafd92f64,0xa63e2da8,0x2ea7aa1f,
  0xa63e0000,0xac722a1f,0xaea72da8,0xafd92f64,0x2fd93000,0x2ea72f64,0x2c722da8,0x263e2a1f,0x2ea73000,0xa63e2a1f,0xafd9ada8,0xac72af64,
  0x2c723000,0xafd9aa1f,0x263eada8,0x2ea72f64,0x263e3000,0xac72af64,0x2ea72da8,0xafd9aa1f,0xa63e3000,0x2c72af64,0xaea72da8,0x2fd9aa1f,
  0xac723000,0x2fd9aa1f,0xa63eada8,0xaea72f64,0xaea73000,0x263e2a1f,0x2fd9ada8,0x2c72af64,0xafd93000,0xaea72f64,0xac722da8,0xa63e2a1f,
  0x263e0000,0x2c72aa1f,0x2ea7ada8,0x2fd9af64,0x2c720000,0x2fd9af64,0x263eada8,0xaea72a1f,0x2ea70000,0x263eaf64,0xafd92da8,0x2c722a1f,
  0x2fd90000,0xaea7aa1f,0x2c722da8,0xa63eaf64,0x2fd90000,0xaea72a1f,0x2c72ada8,0xa63e2f64,0x2ea70000,0x263e2f64,0xafd9ada8,0x2c72aa1f,
  0x2c720000,0x2fd92f64,0x263e2da8,0xaea7aa1f,0x263e0000,0x2c722a1f,0x2ea72da8,0x2fd92f64,0xafd93000,0xaea72f64,0xac722da8,0xa63e2a1f,
  0xaea73000,0x263e2a1f,0x2fd9ada8,0x2c72af64,0xac723000,0x2fd9aa1f,0xa63eada8,0xaea72f64,0xa63e3000,0x2c72af64,0xaea72da8,0x2fd9aa1f,
  0x263e3000,0xac72af64,0x2ea72da8,0xafd9aa1f,0x2c723000,0xafd9aa1f,0x263eada8,0x2ea72f64,0x2ea73000,0xa63e2a1f,0xafd9ada8,0xac72af64,
  0x2fd93000,0x2ea72f64,0x2c722da8,0x263e2a1f,0xa63e0000,0xac72aa1f,0xaea7ada8,0xafd9af64,0x2c720000,0x2fd92f64,0x263e2da8,0xaea7aa1f,
  0xaea70000,0xa63eaf64,0x2fd92da8,0xac722a1f,0x2fd90000,0xaea72a1f,0x2c72ada8,0xa63e2f64,0xafd90000,0x2ea72a1f,0xac72ada8,0x263e2f64,
  0x2ea70000,0x263eaf64,0xafd92da8,0x2c722a1f,0xac720000,0xafd92f64,0xa63e2da8,0x2ea7aa1f,0x263e0000,0x2c72aa1f,0x2ea7ada8,0x2fd9af64,
  0x2fd93000,0x2ea72f64,0x2c722da8,0x263e2a1f,0xaea7b000,0x263eaa1f,0x2fd92da8,0x2c722f64,0x2c723000,0xafd9aa1f,0x263eada8,0x2ea72f64,
  0xa63eb000,0x2c722f64,0xaea7ada8,0x2fd92a1f,0xa63e3000,0x2c72af64,0xaea72da8,0x2fd9aa1f,0x2c72b000,0xafd92a1f,0x263e2da8,0x2ea7af64,
  0xaea73000,0x263e2a1f,0x2fd9ada8,0x2c72af64,0x2fd9b000,0x2ea7af64,0x2c72ada8,0x263eaa1f,0x263e0000,0x2c72aa1f,0x2ea7ada8,0x2fd9af64,
  0xac720000,0xafd92f64,0xa63e2da8,0x2ea7aa1f,0x2ea70000,0x263eaf64,0xafd92da8,0x2c722a1f,0xafd90000,0x2ea72a1f,0xac72ada8,0x263e2f64,
  0x2fd90000,0xaea72a1f,0x2c72ada8,0xa63e2f64,0xaea70000,0xa63eaf64,0x2fd92da8,0xac722a1f,0x2c720000,0x2fd92f64,0x263e2da8,0xaea7aa1f,
  0xa63e0000,0xac72aa1f,0xaea7ada8,0xafd9af64,0xafd93000,0xaea72f64,0xac722da8,0xa63e2a1f,0x2ea7b000,0xa63eaa1f,0xafd92da8,0xac722f64,
  0xac723000,0x2fd9aa1f,0xa63eada8,0xaea72f64,0x263eb000,0xac722f64,0x2ea7ada8,0xafd92a1f,0x263e3000,0xac72af64,0x2ea72da8,0xafd9aa1f,
  0xac72b000,0x2fd92a1f,0xa63e2da8,0xaea7af64,0x2ea73000,0xa63e2a1f,0xafd9ada8,0xac72af64,0xafd9b000,0xaea7af64,0xac72ada8,0xa63eaa1f,
  0xafd9b000,0xaea7af64,0xac72ada8,0xa63eaa1f,0x2ea73000,0xa63e2a1f,0xafd9ada8,0xac72af64,0xac72b000,0x2fd92a1f,0xa63e2da8,0xaea7af64,
  0x263e3000,0xac72af64,0x2ea72da8,0xafd9aa1f,0x263eb000,0xac722f64,0x2ea7ada8,0xafd92a1f,0xac723000,0x2fd9aa1f,0xa63eada8,0xaea72f64,
  0x2ea7b000,0xa63eaa1f,0xafd92da8,0xac722f64,0xafd93000,0xaea72f64,0xac722da8,0xa63e2a1f,0xa63e0000,0xac72aa1f,0xaea7ada8,0xafd9af64,
  0x2c720000,0x2fd92f64,0x263e2da8,0xaea7aa1f,0xaea70000,0xa63eaf64,0x2fd92da8,0xac722a1f,0x2fd90000,0xaea72a1f,0x2c72ada8,0xa63e2f64,
  0xafd90000,0x2ea72a1f,0xac72ada8,0x263e2f64,0x2ea70000,0x263eaf64,0xafd92da8,0x2c722a1f,0xac720000,0xafd92f64,0xa63e2da8,0x2ea7aa1f,
  0x263e0000,0x2c72aa1f,0x2ea7ada8,0x2fd9af64,0x2fd9b000,0x2ea7af64,0x2c72ada8,0x263eaa1f,0xaea73000,0x263e2a1f,0x2fd9ada8,0x2c72af64,
  0x2c72b000,0xafd92a1f,0x263e2da8,0x2ea7af64,0xa63e3000,0x2c72af64,0xaea72da8,0x2fd9aa1f,0xa63eb000,0x2c722f64,0xaea7ada8,0x2fd92a1f,
  0x2c723000,0xafd9aa1f,0x263eada8,0x2ea72f64,0xaea7b000,0x263eaa1f,0x2fd92da8,0x2c722f64,0x2fd93000,0x2ea72f64,0x2c722da8,0x263e2a1f,
  0x263e0000,0x2c72aa1f,0x2ea7ada8,0x2fd9af64,0xac720000,0xafd92f64,0xa63e2da8,0x2ea7aa1f,0x2ea70000,0x263eaf64,0xafd92da8,0x2c722a1f,
  0xafd90000,0x2ea72a1f,0xac72ada8,0x263e2f64,0x2fd90000,0xaea72a1f,0x2c72ada8,0xa63e2f64,0xaea70000,0xa63eaf64,0x2fd92da8,0xac722a1f,
  0x2c720000,0x2fd92f64,0x263e2da8,0xaea7aa1f,0xa63e0000,0xac72aa1f,0xaea7ada8,0xafd9af64,0x316c2fbd,0x343e32f7,0x35bc34ff,0x372c3676,
  0x371532c6,0x3a81392e,0x3bef3b71,0x3b7c3bf2,0x397034cf,0x3bfc3b6c,0x38b23b04,0xb40e31e8,0x3ae13631,0x39e73bf5,0xb6e83219,0xbbe8bb13,
  0x3bc23785,0x30be3aa9,0xbbfdb911,0x2a16b9aa,0x3bfe3865,0xb80f37a6,0xb82abc00,0x3bfd376f,0x3b9238fd,0xbb7f2311,0x3805b929,0x31223bde,
  0x3a85398b,0xbb96b742,0x3bff319e,0xbbb82f8b,0xbbe2bbf1,0xbbb7bbcf,0xbb78bb9a,0xbb27bb52,0xbb2cbbd2,0xb8a8ba19,0xb029b5df,0x35a52f59,
  0xb9dfbba1,0x2ba7b5f7,0x3a7a37b2,0x3bbd3bdd,0xb815bb60,0x39662e91,0x3b373bda,0xb0d7377a,0xb3d3bb10,0x3be9386f,0x2a7a3a31,0xbbfeb9a6,
  0x294dbab0,0x3ae53b07,0xbad51fdb,0xab43bb16,0x352fba41,0x35993c00,0xbaebba1d,0x3be531cf,0x38a3b9c5,0xb5173b21,0x2776bbe0,0x34323bf2,
  0x384537dd,0x38ea3899,0x39823937,0x3a0d39c9,0x39463a93,0x3340374e,0xb426a452,0xb979b7c8,0xbb45b924,0xbb32bc00,0xb371b902,0x38d63294,
  0xb08db9a1,0x3b3f379b,0x39583bd7,0xb8252dfb,0x3bea3a2d,0xb3ba3874,0xbb89bb0d,0x36d2b625,0xb6bb387f,0xb8d1bbf5,0x3be73602,0xb546391f,
  0xba00bb01,0x3bff35eb,0xba5c34db,0x3359bab6,0x3ac7b66b,0xb9413933,0x368dbabd,0xb0103bb3,0xbac4baf7,0xba50ba8c,0xb9cdba11,0xb93cb986,
  0x3a04388e,0x3bcb3b1e,0x3bba3c00,0x39d63afe,0x36af3a21,0xb6ffa17f,0xbbc8ba3d,0xba60bbd4,0xbbebb9af,0xb6c6bb0a,0x39f43263,0x3ad83bf7,
  0x30a6b916,0x3bc33aa5,0xb55e3790,0xbb3dbb63,0x3b423a9e,0xba642ec3,0xb0f0bb6a,0x3b8e3a25,0xb94a37bd,0x2884bb6f,0x38db3b9f,0xbbc9b85a,
  0xb840bb54,0x3a093a15,0xbb4cb850,0x3bef3457,0x3a893a4d,0x3af43ac1,0x3b4f3b24,0x3b983b76,0xbb94baba,0xbbe4bbf9,0xba58bb57,0xb699b8f8,
  0x3bfe3b18,0x394f3b5c,0xb109347b,0xbae8b884,0xbbc0bb68,0xa9b1b90c,0x3b8b387a,0x38bc3ba5,0x3ade3ba7,0xb8c1324b,0xb9f0bbf6,0x39eb9648,
  0xb96bbbd6,0x3bbf3487,0xb38939b3,0xb9f8bba3,0x370a3bf3,0xbb47b994,0x3bbc2d65,0xb8ad3889,0xb153bc00,0x37213b9c,0xb97dba90,0x3af138f3,
  0xb89eb8ee,0xb7e8b84a,0xb682b737,0xb50bb5c8,0x35233855,0xb13b2d33,0xb8e0b65f,0xbb4aba45,0xa8e8b764,0x39fc3648,0x3be63bae,0x380a3a9b,
  0xb3eb360e,0xbbfeba35,0xb552baa2,0x3a7334b7,0x381ab4ab,0x3a6f3bd8,0xb95d2e5f,0xb962bc00,0xb9e3327c,0xb402bbac,0x3bc6399d,0xb95434c3,
  0x3b2faf27,0xb6a439bc,0xb41abbf9,0x3a7e3a97,0xbbe3251b,0x3b2ab4f3,0xb9d23894,0x37f3ba49,0x3bce3bb5,0x3bf03be1,0x3bff3bfa,0x3bfb3bff,
  0x2c38b1b6,0x383a34e7,0x3aee39c0,0x3bff3bb2,0xbb81bbf8,0xb53ab999,0x38302ef5,0x3bed3ab3,0xb8cc9cb6,0xbb85bbab,0x2adeb86a,0x3bc5391b,
  0x38c73bf6,0xbadbb232,0xb6ddbba9,0x3b87361a,0x3b833201,0xb0743a39,0xba76bb5e,0x3b352dc9,0xac06bbb0,0x39743b59,0xbbeeb759,0x3aceb2ad,
  0xbbccb5d4,0x3bfb2d00,0xbb7a32de,0x3a54b7d2,0xb30fb44b,0xafefb185,0xa6adacce,0x2c9c25e4,0xbbfcbbdf,0xbacbbb9e,0xb7feb990,0xa81fb463,
  0xb58d2d97,0xbb90b9b8,0xbad1bbf4,0xb05bb85f,0x3a673c00,0xb5763493,0xbbfdbaac,0xb3a2ba29,0x3a6b2e2d,0x38203bd9,0xbb3ab49f,0xb56abb65,
  0xb581bbdc,0x3bec3907,0xb8b7363c,0xb6f4bbf8,0xbbfcb46f,0x39dab654,0xb0423b1b,0xb835bbd3,0xb3283b73,0xac6abbfa,0x35b13bd0,0xb8e5bafb,
  0x38ee3a0d,0xb84aba89,0x37373af4,0xb5c8bb4f,0x35df3a81,0x2f59bbef,0xb88e3b7c,0x3b1eb946,0x2d973ae8,0x39b8bb81,0xbbf4353a,0x385f3830,
  0xb2633b3f,0x3bf7b958,0xb60eb825,0xba353bc0,0xb7853b87,0x3aa9b3d3,0x3911bbe9,0xb9aa2a7a,0xb99d3bbf,0x34c33389,0x3bdcb9f8,0x3907bb83,
  0xbb013be5,0xb5eb394a,0x34db2884,0x3ab6b8db,0xbbd03bfb,0xbafb3b7a,0xb98b3a54,0xb74238a3,0x3a4db93c,0xbac1389e,0x3b24b7e8,0xbb763682,
  0x3b71b8a8,0xbbf23029,0x3a9335a5,0xb74eba04,0x3bf8b80a,0xb999b58d,0xaef53b90,0x3ab3bad1,0x3bd7b6c6,0xadfbb9f4,0xbb683ad8,0x390c33eb,
  0x3b10b56a,0x386fbbc2,0xba3130be,0xb9a63bfd,0x39b3b402,0x3ba3bbc6,0x3201b954,0xba393581,0x37bdb122,0x3b6fba00,0x3b9fbbff,0x385aba5c,
  0x32deac6a,0x37d2b5b1,0x39c5b8e5,0x3b21ba85,0x344b3b98,0xb185bbce,0x2cce3bf0,0x25e4bbff,0xbc003340,0x3afe3426,0xb855b979,0x2d333b94,
  0x34cfbbed,0xbb6c39df,0x3b042ba7,0xb1e8ba7a,0x3aa2a9b1,0x34b7bb8b,0xbc0038bc,0x349338cc,0xba2d3bfe,0x387430a6,0x3b0dbbc3,0xb625b55e,
  0xb63cb074,0xbbf83a76,0xb8653b35,0x37a6294d,0x3bf3bbc9,0x3994bb2f,0x2d65b6a4,0xb889341a,0xb19e3517,0x2f8b2776,0x366bb432,0x3933b840,
  0x3bb5b50b,0xbbe1330f,0x3bfaafef,0xbbff26ad,0xa4523bcb,0x37c8bbba,0xbaba39d6,0x3bf9b523,0xbba1305b,0x35f73970,0x37b2bbfc,0xbbdd38b2,
  0x387abbfe,0xbba53552,0x9cb63a73,0x3babba67,0x39162a16,0x3aa5bbea,0xb790b3ba,0xbb633b89,0xbb5e3bec,0xadc938b7,0x3ab0b6f4,0x3b07bbfe,
  0xaf27b359,0xb9bc370a,0xbbf93b47,0xba973bbc,0x3be0bb96,0x3bf2bbff,0x3b54bbb8,0x3a15bac7,0xafbd3bfb,0x32f7bbe2,0xb4ff3bb7,0x3676bb78,
  0x365fbbe4,0xba453a58,0x3bdfb699,0xbb9eac38,0xb9243bbd,0x3c00b6af,0xb902b6ff,0xb2943bc8,0x3aacbb85,0xba29aade,0xb6313bc5,0x3bf5b815,
  0xbba73b3d,0x324b381a,0x3bf6ba6f,0x9648b95d,0x3c00bae5,0x376fbad5,0xb87f2b43,0xbbf53b42,0xbbb03a7e,0xbb593bfc,0xb75939da,0x32ad3042,
  0x3abdba09,0x3bb3bb4c,0x3c00bbef,0x3b9cbbe3,0x3bf12c9c,0xbbcfb16c,0x3b9a343e,0xbb52b5bc,0xbb57b13b,0x38f838e0,0xb1b6bb4a,0xb4e73bfc,
  0x3a21340e,0x217fbb45,0xba3d3b32,0x3bd4b371,0xb86ab576,0xb91b3bfd,0x3b60b3a2,0x2e91bae1,0x34ab36d2,0x3bd8bade,0xae5fb8c1,0xbc0039f0,
  0x9fdbb80f,0xbb16382a,0xba9e3bfd,0x2ec336bb,0xb46f38ad,0x3654ac06,0x3b1bb974,0x3bd3bbee,0x3850b941,0x3457b68d,0xa51bb010,0xb4f33153,
  0xb7dd3b27,0x3899bac4,0xb9373a50,0x39c9b9cd,0x3990383a,0xb463baee,0xb2c63bff,0x392ebb2c,0x3b18ba60,0xbb5c28e8,0x347b39fc,0x3884bbe6,
  0xb219b966,0xbb133b37,0x39a130d7,0x379bbbeb,0xbbf63962,0xb2323a6b,0x3ba9b820,0x361abb3a,0xb6023a64,0x391fb0f0,0x3bd6bb8e,0x3487b9e3,
  0x3a41b835,0x3c00bb92,0x3a1dbb7f,0x31cfb805,0x3a90bb2a,0x38f3b9d2,0x35d4b7f3,0x2d00b328,0x3af7372c,0xba8cb845,0x3a1138ea,0xb986b982,
  0x39c0bacb,0xbbb237fe,0x3bd2a81f,0xba19b715,0xb764b8d6,0xb6483bfe,0x3baeb94f,0xba9bb109,0xbbda39e7,0x377a36e8,0x39afbbe8,0xbb0a308d,
  0xae2d39eb,0x3bd9b8c7,0x349fbadb,0xbb6536dd,0x3b6ab8d1,0x3a25bbe7,0xb27cb546,0xbbac396b,0x38fdbace,0xa311b52f,0xb9293599,0xbbde3aeb,
  0xb8943721,0xba49397d,0xbb733af1,0xbbfa3bcc,0xbbfb3bff,0xbbe23bf1,0xbbb73bcf,0xbb783b9a,0xbb7c3bf2,0xb9463a93,0xb340374e,0x3426a452,
  0xba603bd4,0xa8e83764,0x39fcb648,0x3be6bbae,0xb8bc3ba5,0x38cc9cb6,0x3b85bbab,0xaadeb86a,0xb56a3b65,0x3bc2b785,0x30bebaa9,0xbbfd3911,
  0xab433b16,0x3b42ba9e,0xba64aec3,0xb0f03b6a,0x33593ab6,0x370abbf3,0xbb473994,0x3bbcad65,0x37f33a49,0xb328bb73,0xac6a3bfa,0x35b1bbd0,
  0xac9c25e4,0xb16c2fbd,0xb43e32f7,0xb5bc34ff,0xb5a52f59,0xba04388e,0xbbcb3b1e,0xbbba3c00,0xb8d63294,0xbbfe3b18,0xb94f3b5c,0x3109347b,
  0xba7334b7,0xba673c00,0x35763493,0x3bfdbaac,0xbb87361a,0xb3d33b10,0x3be9b86f,0x2a7aba31,0xbbfd376f,0x36bb387f,0x38d1bbf5,0xbbe73602,
  0xbbc9385a,0x3b2f2f27,0xb6a4b9bc,0xb41a3bf9,0xbaf138f3,0x3bccb5d4,0xbbfb2d00,0x3b7a32de,0xbb273b52,0xbac43af7,0xba503a8c,0xb9cd3a11,
  0x3979b7c8,0x3b94baba,0x3be4bbf9,0x3a58bb57,0x380aba9b,0xb58dad97,0xbb9039b8,0xbad13bf4,0xbbc5391b,0xb8153b60,0x3966ae91,0x3b37bbda,
  0x2a1639aa,0x3beaba2d,0xb3bab874,0xbb893b0d,0x3b8eba25,0xb9e3b27c,0xb4023bac,0x3bc6b99d,0xb8adb889,0xac063bb0,0x3974bb59,0xbbee3759,
  0xb8e53afb,0x3a85b98b,0xbb963742,0x3bffb19e,0xb72c3676,0xb84537dd,0xb8ea3899,0xb9823937,0xb9d63afe,0xb5233855,0x313b2d33,0x38e0b65f,
  0x3ae8b884,0x3b81bbf8,0x353ab999,0xb8302ef5,0x33a2ba29,0xbae13631,0xb9e73bf5,0x36e83219,0xbbfe39a6,0x30a63916,0x3bc3baa5,0xb55eb790,
  0x3546391f,0x396bbbd6,0xbbbf3487,0x338939b3,0x3a7eba97,0xbbfc346f,0x39da3654,0xb042bb1b,0xba54b7d2,0x38a339c5,0xb517bb21,0x27763be0,
  0xb93c3986,0xb89e38ee,0xb7e8384a,0xb6823737,0x3699b8f8,0xac38b1b6,0xb83a34e7,0xbaee39c0,0xb05b385f,0x3970b4cf,0x3bfcbb6c,0x38b2bb04,
  0xb0d7b77a,0xbbeb39af,0xb6c63b0a,0x39f4b263,0x36d23625,0x3adebba7,0xb8c1b24b,0xb9f03bf6,0xb954b4c3,0xb5813bdc,0x3becb907,0xb8b7b63c,
  0x3ace32ad,0xb52fba41,0xb5993c00,0x3aebba1d,0xbbb8af8b,0x3ac7366b,0xb941b933,0x368d3abd,0xba0d39c9,0xba893a4d,0xbaf43ac1,0xbb4f3b24,
  0x3b4aba45,0x3bfcbbdf,0x3acbbb9e,0x37feb990,0xbbed3ab3,0xb9df3ba1,0x2ba735f7,0x3a7ab7b2,0x3be8bb13,0x308db9a1,0xbb3f379b,0xb9583bd7,
  0xbb3d3b63,0x381a34ab,0x3a6fbbd8,0xb95dae5f,0x39f8bba3,0xbb833201,0x30743a39,0x3a76bb5e,0xb8353bd3,0x3b92b8fd,0xbb7fa311,0x38053929,
  0x3432bbf2,0xb8403b54,0x3a09ba15,0xbb4c3850,0xb50b35c8,0xb30f344b,0xafef3185,0xa6ad2cce,0xbbff3bb2,0xbb2c3bd2,0xb8a83a19,0xb02935df,
  0xb40eb1e8,0xbb453924,0xbb323c00,0xb3713902,0x3ad8bbf7,0xb3ebb60e,0xbbfe3a35,0xb5523aa2,0x39eb1648,0x38c7bbf6,0xbadb3232,0xb6dd3ba9,
  0xb6f43bf8,0x3bfeb865,0xb80fb7a6,0xb82a3c00,0xbbe531cf,0x394a37bd,0xa884bb6f,0xb8db3b9f,0xb010bbb3,0xb1533c00,0x3721bb9c,0xb97d3a90,
  0xbb983b76,0xbbce3bb5,0xbbf03be1,0xbbff3bfa,0x281fb463,0xb71532c6,0xba81392e,0xbbef3b71,0x3bbdbbdd,0x36afba21,0xb6ff217f,0xbbc83a3d,
  0x38252dfb,0x3bc0bb68,0x29b1b90c,0xbb8b387a,0xb9623c00,0x3a6bae2d,0x3820bbd9,0xbb3a349f,0xbb352dc9,0x294d3ab0,0x3ae5bb07,0xbad59fdb,
  0x3122bbde,0xba003b01,0x3bffb5eb,0xba5cb4db,0x3befb457,0xbbe3a51b,0x3b2a34f3,0xb9d2b894,0x39c939cd,0xba4db93c,0x3ac1389e,0xbb24b7e8,
  0x3b1e3946,0xbc00b340,0x3afeb426,0xb8553979,0x3bdd38b2,0xba21340e,0xa17fbb45,0x3a3d3b32,0x3bf53815,0xb2193966,0xbb13bb37,0x39a1b0d7,
  0x3b6536dd,0x37853b87,0xbaa9b3d3,0xb911bbe9,0x3a393581,0x3b5e3bec,0x2dc938b7,0xbab0b6f4,0x3889341a,0x3bb03a7e,0x3b593bfc,0x375939da,
  0x34f33153,0x38943721,0x3a49397d,0x3b733af1,0xb9863982,0x38eeba0d,0xb84a3a89,0x3737baf4,0xb74e3a04,0xa452bbcb,0x37c83bba,0xbabab9d6,
  0xb1e83a7a,0xb924bbbd,0x3c0036af,0xb90236ff,0x2e913ae1,0xbbdab9e7,0x377ab6e8,0x39af3be8,0x361a3b3a,0xbb10b56a,0xb86fbbc2,0x3a3130be,
  0x39073b83,0xb63c3074,0xbbf8ba76,0xb865bb35,0x3a973bbc,0x346f38ad,0xb654ac06,0xbb1bb974,0x3b9c3be3,0x3a903b2a,0x38f339d2,0x35d437f3,
  0x3b763682,0xbbb5b50b,0x3be1330f,0xbbfaafef,0x2d33bb94,0x365f3be4,0xba45ba58,0x3bdf3699,0xbbd4b371,0x3764b8d6,0x36483bfe,0xbbaeb94f,
  0x379b3beb,0xbbd7b6c6,0x2dfbb9f4,0x3b683ad8,0x39aa2a7a,0x3a2d3bfe,0xb87430a6,0xbb0dbbc3,0xbb07bbfe,0x1fdbb80f,0x3b16382a,0x3a9e3bfd,
  0xb2ad3042,0xba41b835,0xbc00bb92,0xba1dbb7f,0x3bfa3bcc,0x3bd03bfb,0x3afb3b7a,0x398b3a54,0xb5c83b4f,0x344bbb98,0xb1853bce,0x2ccebbf0,
  0x3bf93523,0xbb57313b,0x38f8b8e0,0xb1b63b4a,0xb294bbc8,0x3b183a60,0xbb5ca8e8,0x347bb9fc,0xbb0ab08d,0xb263bb3f,0x3bf73958,0xb60e3825,
  0x39a63bfd,0xb9162a16,0xbaa5bbea,0x3790b3ba,0x37a6a94d,0x3c003ae5,0x376f3ad5,0xb87fab43,0xbbd3bbee,0xb8fdbace,0x2311b52f,0x39293599,
  0x2d003328,0xb2deac6a,0xb7d2b5b1,0xb9c5b8e5,0x3bff26ad,0xbbf12c9c,0x3bcfb16c,0xbb9a343e,0xbb9e2c38,0x3990b83a,0xb4633aee,0xb2c6bbff,
  0x3a9bb109,0xad973ae8,0xb9b8bb81,0x3bf4353a,0xb90c33eb,0xb87abbfe,0x3ba53552,0x1cb63a73,0x3625b55e,0x3ba73b3d,0xb24b381a,0xbbf6ba6f,
  0xaec336bb,0xbb6ab8d1,0xba25bbe7,0x327cb546,0xb1cfb805,0x37bd3122,0x3b6f3a00,0x3b9f3bff,0x374238a3,0x319e3517,0xaf8b2776,0xb66bb432,
  0x25e43bff,0xafbdbbfb,0x32f73be2,0xb4ffbbb7,0xb4e7bbfc,0x39c03acb,0xbbb2b7fe,0x3bd2281f,0x38843be6,0xbbf8b80a,0x3999b58d,0x2ef53b90,
  0xba35bbc0,0x3aa229b1,0x34b73b8b,0xbc00b8bc,0x3b633b89,0xb4ab36d2,0xbbd8bade,0x2e5fb8c1,0xbbf5bb42,0xb602ba64,0x391f30f0,0x3bd63b8e,
  0x3bde3aeb,0x3b013be5,0x35eb394a,0xb4db2884,0xbb21ba85,0xbbe0bb96,0xbbf2bbff,0xbb54bbb8,0x3b52b5bc,0xbaf7372c,0x3a8cb845,0xba1138ea,
  0x392e3b2c,0xbb71b8a8,0x3bf23029,0xba9335a5,0xb85f3830,0xb4cfbbed,0x3b6c39df,0xbb042ba7,0xbbabba67,0x386ab576,0x391b3bfd,0xbb60b3a2,
  0x1648b95d,0x3bf63962,0x32323a6b,0xbba9b820,0x3bac396b,0x399d3bbf,0xb4c33389,0xbbdcb9f8,0x385a3a5c,0xaf273359,0xb9bcb70a,0xbbf9bb47,
  0xb933b840,0xbabdba09,0xbbb3bb4c,0xbc00bbef,0x36763b78,0xb7ddbb27,0x38993ac4,0xb937ba50,0xba193715,0x35dfba81,0x2f593bef,0xb88ebb7c,
  0xbab3bad1,0x3ba1305b,0xb5f73970,0xb7b2bbfc,0x3493b8cc,0x3aac3b85,0xba292ade,0xb631bbc5,0x3c0039f0,0x2e2d39eb,0xbbd9b8c7,0xb49fbadb,
  0x348739e3,0xb9b3b402,0xbba3bbc6,0xb201b954,0xbab6b8db,0xbbf3bbc9,0xb994bb2f,0xad65b6a4,0xba15bac7,0xb850b941,0xb457b68d,0x251bb010,
  0xb9cfbb16,0x30ac2a31,0x3b9c3bf1,0xb493ae2d,0xb76fb8b4,0x35a133e3,0x3a1d3afe,0xb902b76f,0xb3e3b5a1,0x38b4376f,0x376f3902,0xbafeba1d,
  0xaa31b0ac,0x3b1639cf,0x2e2d3493,0xbbf1bb9c,0xb956ba74,0x305f29cc,0x3b633bd2,0xb44badc9,0xb6e7b859,0x353f335e,0x39d23ab6,0xb8bcb6ff,
  0xb35eb53f,0x385936e7,0x36ff38bc,0xbab6b9d2,0xa9ccb05f,0x3a743956,0x2dc9344b,0xbbd2bb63,0xb8e3b9de,0x30122967,0x3b1e3ba1,0xb402ad65,
  0xb662b801,0x34de32da,0x39823a67,0xb874b68d,0xb2dab4de,0x38013662,0x368d3874,0xba67b982,0xa967b012,0x39de38e3,0x2d653402,0xbba1bb1e,
  0xb876b952,0x2f8c2902,0x3ace3b60,0xb371ad00,0xb5e1b758,0x347e3257,0x392e3a11,0xb82ab61a,0xb257b47e,0x375835e1,0x361a382a,0xba11b92e,
  0xa902af8c,0x39523876,0x2d003371,0xbb60bace,0xb80db8ce,0x2ef3289e,0x3a733b10,0xb2deac9c,0xb562b6b3,0x342031d5,0x38d639b3,0xb7bdb5a5,
  0xb1d5b420,0x36b33562,0x35a537bd,0xb9b3b8d6,0xa89eaef3,0x38ce380d,0x2c9c32de,0xbb10ba73,0xb750b851,0x2e5a2839,0x3a0d3ab0,0xb24bac38,
  0xb4e5b613,0x33863153,0x387a394f,0xb721b52f,0xb153b386,0x361334e5,0x352f3721,0xb94fb87a,0xa839ae5a,0x38513750,0x2c38324b,0xbab0ba0d,
  0xb68eb7b4,0x2dc227a9,0x399d3a41,0xb1b6aba7,0xb46ab577,0x32cd30d2,0x381a38e5,0xb682b4b7,0xb0d2b2cd,0x3577346a,0x34b73682,0xb8e5b81a,
  0xa7a9adc2,0x37b4368e,0x2ba731b6,0xba41b99d,0xb5d2b6d1,0x2d2a26e0,0x392439c5,0xb122aade,0xb3e3b4de,0x32163052,0x376f3874,0xb5dfb43e,
  0xb052b216,0x34de33e3,0x343e35df,0xb874b76f,0xa6e0ad2a,0x36d135d2,0x2ade3122,0xb9c5b924,0xb51cb5f6,0x2c932617,0x38a3393c,0xb08daa16,
  0xb2f4b448,0x31602fa5,0x36a437fe,0xb53ab389,0xafa5b160,0x344832f4,0x3389353a,0xb7feb6a4,0xa617ac93,0x35f6351c,0x2a16308d,0xb93cb8a3,
  0xb46ab523,0x2bf6254d,0x381a38a8,0xafefa94d,0xb209b36b,0x30ac2ea7,0x35d4370a,0xb493b294,0xaea7b0ac,0x336b3209,0x32943493,0xb70ab5d4,
  0xa54dabf6,0x3523346a,0x294d2fef,0xb8a8b81a,0xb378b456,0x2ac82484,0x3715380a,0xaec3a884,0xb120b24a,0x2ff22da9,0x34ff360e,0xb3d3b19e,
  0xada9aff2,0x324a3120,0x319e33d3,0xb60eb4ff,0xa484aac8,0x34563378,0x28842ec3,0xb80ab715,0xb223b31c,0x29992376,0x35eb36c6,0xad97a776,
  0xb039b12d,0x2e8d2cac,0x3426350b,0xb27cb0a6,0xacacae8d,0x312d3039,0x30a6327c,0xb50bb426,0xa376a999,0x331c3223,0x27762d97,0xb6c6b5eb,
  0xb0d2b194,0x286b21e4,0x34b7356a,0xac6aa5e4,0xaea7b012,0x2d2a2b5f,0x32943402,0xb122af59,0xab5fad2a,0x30122ea7,0x2f593122,0xb402b294,
  0xa1e4a86b,0x319430d2,0x25e42c6a,0xb56ab4b7,0xaf0cb012,0x267b2052,0x32f73402,0xaa7aa452,0xacdeadf5,0x2b912967,0x30d731e8,0xaf8bad65,
  0xa967ab91,0x2df52cde,0x2d652f8b,0xb1e8b0d7,0xa052a67b,0x30122f0c,0x24522a7a,0xb402b2f7,0xac79ad2a,0x24201d7f,0x30743122,0xa81fa17f,
  0xaa31ab91,0x28d026e0,0x2e2d2f8b,0xacceaade,0xa6e0a8d0,0x2b912a31,0x2ade2cce,0xaf8bae2d,0x9d7fa420,0x2d2a2c79,0x217f281f,0xb122b074,
  0xa7a9a86b,0x1f1218b6,0x2ba72c6a,0xa3119cb6,0xa54da67b,0x242021e4,0x294d2a7a,0xa81fa5e4,0xa1e4a420,0x267b254d,0x25e4281f,0xaa7aa94d,
  0x98b69f12,0x286b27a9,0x1cb62311,0xac6aaba7,0x211b21e4,0x98b69248,0xa51ba5e4,0x1cb61648,0x1f122052,0x9d7f9bdb,0xa311a452,0x217f1fdb,
  0x1bdb1d7f,0xa0529f12,0x9fdba17f,0x24522311,0x124818b6,0xa1e4a11b,0x96489cb6,0x25e4251b,0x2a632b5f,0xa1e49bdb,0xae5faf59,0x25e41fdb,
  0x286b2967,0xa6e0a4e9,0xac6aad65,0x2ade28e8,0x24e926e0,0xa967a86b,0xa8e8aade,0x2d652c6a,0x1bdb21e4,0xab5faa63,0x9fdba5e4,0x2f592e5f,
  0x2dc22ea7,0xa54d9f12,0xb1b6b294,0x294d2311,0x2bf62cde,0xaa31a86b,0xafefb0d7,0x2e2d2c6a,0x286b2a31,0xacdeabf6,0xac6aae2d,0x30d72fef,
  0x1f12254d,0xaea7adc2,0xa311a94d,0x329431b6,0x302c30d2,0xa7a9a11b,0xb41ab4b7,0x2ba7251b,0x2dc22f0c,0xac79aa63,0xb1b6b2f7,0x30742e5f,
  0x2a632c79,0xaf0cadc2,0xae5fb074,0x32f731b6,0x211b27a9,0xb0d2b02c,0xa51baba7,0x34b7341a,0x317a3257,0xa902a2ad,0xb552b61a,0x2d0026ad,
  0x2f8c309f,0xaddcac2e,0xb371b487,0x31cf3029,0x2c2e2ddc,0xb09faf8c,0xb029b1cf,0x34873371,0x22ad2902,0xb257b17a,0xa6adad00,0x361a3552,
  0x32cd33e3,0xaa31a420,0xb682b76f,0x2e2d281f,0x30ac31bb,0xaf3fad2a,0xb493b58d,0x33283122,0x2d2a2f3f,0xb1bbb0ac,0xb122b328,0x358d3493,
  0x24202a31,0xb3e3b2cd,0xa81fae2d,0x376f3682,0x341334bc,0xab5fa4e9,0xb7a6b85a,0x2f5928e8,0x319432da,0xb052ae28,0xb56ab68d,0x343e3219,
  0x2e283052,0xb2dab194,0xb219b43e,0x368d356a,0x24e92b5f,0xb4bcb413,0xa8e8af59,0x385a37a6,0x34c3358c,0xac47a5b2,0xb85fb8f3,0x304229b1,
  0x327e33fd,0xb106af26,0xb63cb785,0x34e7330f,0x2f263106,0xb3fdb27e,0xb30fb4e7,0x3785363c,0x25b22c47,0xb58cb4c3,0xa9b1b042,0x38f3385f,
  0x35773662,0xacdea67b,0xb8e5b982,0x30d72a7a,0x336b3493,0xb1bbb012,0xb70ab83a,0x358d3402,0x301231bb,0xb493b36b,0xb402b58d,0x383a370a,
  0x267b2cde,0xb662b577,0xaa7ab0d7,0x398238e5,0x36303741,0xad76a744,0xb962ba04,0x316c2b43,0x342e352a,0xb271b092,0xb7d2b8ad,0x3631347b,
  0x30923271,0xb52ab42e,0xb47bb631,0x38ad37d2,0x27442d76,0xb741b630,0xab43b16c,0x3a043962,0x36ee3815,0xae0ea807,0xb9d6ba7a,0x32012c06,
  0x34a735c4,0xb329b113,0xb84ab91b,0x36d234f3,0x31133329,0xb5c4b4a7,0xb4f3b6d2,0x391b384a,0x28072e0e,0xb815b6ee,0xac06b201,0x3a7a39d6,
  0x37b4388e,0xaea7a86b,0xba41bae1,0x32942c6a,0x35233662,0xb3e3b194,0xb8a8b982,0x376f356a,0x319433e3,0xb662b523,0xb56ab76f,0x398238a8,
  0x286b2ea7,0xb88eb7b4,0xac6ab294,0x3ae13a41,0x3841390f,0xaf3fa8d0,0xbaa2bb3a,0x33282cce,0x35a13705,0xb44fb216,0xb902b9e3,0x380535df,
  0x3216344f,0xb705b5a1,0xb5dfb805,0x39e33902,0x28d02f3f,0xb90fb841,0xacceb328,0x3b3a3aa2,0x38ac3997,0xafd8a935,0xbaf7bb83,0x33ba2d33,
  0x362137ac,0xb4aeb298,0xb958ba3d,0x38503654,0x329834ae,0xb7acb621,0xb654b850,0x3a3d3958,0x29352fd8,0xb997b8ac,0xad33b3ba,0x3b833af7,
  0x391c3a28,0xb039a999,0xbb42bbbc,0x34262d97,0x36a4382d,0xb50eb31c,0xb9aaba90,0x389936c6,0x331c350e,0xb82db6a4,0xb6c6b899,0x3a9039aa,
  0x29993039,0xba28b91c,0xad97b426,0x3bbc3b42,0x39923ac3,0xb085a9fe,0xbb81bbe3,0x346f2dfb,0x372a3886,0xb570b3a0,0xb9f8badb,0x38e03737,
  0x33a03570,0xb886b72a,0xb737b8e0,0x3adb39f8,0x29fe3085,0xbac3b992,0xadfbb46f,0x3be33b81,
};

#define PROF(slot) do {} while (0)
#define PROF_DUMP() do {} while (0)
#define PROFA(slot, dep) do {} while (0)
#define PROF3(slot) do {} while (0)
#define PROF2(slot) do {} while (0)

__device__ __forceinline__ uint32_t smem_u32(const void* p) { return (uint32_t)__cvta_generic_to_shared(p); }

__device__ __forceinline__ void mbar_init(uint32_t a, uint32_t c) {
  asm volatile("mbarrier.init.shared::cta.b64 [%0], %1;\n" ::"r"(a), "r"(c) : "memory");
}
__device__ __forceinline__ void mbar_expect_tx(uint32_t a, uint32_t bytes) {
  asm volatile("mbarrier.arrive.expect_tx.shared::cta.b64 _, [%0], %1;\n" ::"r"(a), "r"(bytes) : "memory");
}
__device__ __forceinline__ void mbar_arrive_cluster(uint32_t cluster_addr) {
  asm volatile("mbarrier.arrive.shared::cluster.b64 _, [%0];\n" ::"r"(cluster_addr) : "memory");
}
__device__ __forceinline__ void mbar_arrive_cluster_n(uint32_t cluster_addr, uint32_t n) {
  asm volatile("mbarrier.arrive.shared::cluster.b64 _, [%0], %1;\n" ::"r"(cluster_addr), "r"(n) : "memory");
}
__device__ __forceinline__ bool mbar_try(uint32_t a, uint32_t parity) {
  uint32_t ok;
  asm volatile("{\n.reg .pred p;\nmbarrier.try_wait.parity.shared::cta.b64 p, [%1], %2;\nselp.u32 %0, 1, 0, p;\n}\n"
               : "=r"(ok) : "r"(a), "r"(parity) : "memory");
  return ok;
}
__device__ __forceinline__ void mbar_wait(uint32_t a, uint32_t parity) {
  if (mbar_try(a, parity)) return;
#pragma unroll 1
  for (int n = 0; n < SPIN_LIMIT; n++)
    if (mbar_try(a, parity)) break;
}
__device__ __forceinline__ bool elect_one() {
  uint32_t p;
  asm volatile("{\n.reg .pred P;\nelect.sync _|P, 0xffffffff;\nselp.u32 %0, 1, 0, P;\n}\n" : "=r"(p));
  return p;
}
__device__ __forceinline__ uint32_t mapa(uint32_t a, uint32_t rank) {
  uint32_t r;
  asm volatile("mapa.shared::cluster.u32 %0, %1, %2;\n" : "=r"(r) : "r"(a), "r"(rank));
  return r;
}
__device__ __forceinline__ void nb_sync(int id, int n) { asm volatile("bar.sync %0, %1;\n" ::"r"(id), "r"(n) : "memory"); }
__device__ __forceinline__ void nb_arrive(int id, int n) { asm volatile("bar.arrive %0, %1;\n" ::"r"(id), "r"(n) : "memory"); }
__device__ __forceinline__ void cluster_sync_all() {
  asm volatile("barrier.cluster.arrive.relaxed.aligned;\nbarrier.cluster.wait.aligned;\n" ::: "memory");
}
__device__ __forceinline__ void fence_async_smem() { asm volatile("fence.proxy.async.shared::cta;\n" ::: "memory"); }
__device__ __forceinline__ void fence_async_all() { asm volatile("fence.proxy.async.global;\n" ::: "memory"); }

__device__ __forceinline__ void tma_load_3d(uint32_t dst, const CUtensorMap* tm, uint32_t bar, int c0, int c1, int c2) {
  asm volatile(
      "cp.async.bulk.tensor.3d.shared::cluster.global.mbarrier::complete_tx::bytes [%0], [%1, {%3, %4, %5}], [%2];\n"
      ::"r"(dst), "l"(tm), "r"(bar), "r"(c0), "r"(c1), "r"(c2) : "memory");
}
__device__ __forceinline__ void tma_load_4d(uint32_t dst, const CUtensorMap* tm, uint32_t bar, int c0, int c1, int c2, int c3) {
  asm volatile(
      "cp.async.bulk.tensor.4d.shared::cluster.global.mbarrier::complete_tx::bytes [%0], [%1, {%3, %4, %5, %6}], [%2];\n"
      ::"r"(dst), "l"(tm), "r"(bar), "r"(c0), "r"(c1), "r"(c2), "r"(c3) : "memory");
}
__device__ __forceinline__ void tma_load_3d_mc(uint32_t dst, const CUtensorMap* tm, uint32_t bar, int c0, int c1, int c2) {
  asm volatile(
      "cp.async.bulk.tensor.3d.shared::cluster.global.mbarrier::complete_tx::bytes.multicast::cluster [%0], [%1, {%3, %4, %5}], [%2], %6;\n"
      ::"r"(dst), "l"(tm), "r"(bar), "r"(c0), "r"(c1), "r"(c2), "h"((uint16_t)3) : "memory");
}
__device__ __forceinline__ void bulk_load(uint32_t dst, const void* src, uint32_t bytes, uint32_t bar) {
  asm volatile("cp.async.bulk.shared::cluster.global.mbarrier::complete_tx::bytes [%0], [%1], %2, [%3];\n"
               ::"r"(dst), "l"(src), "r"(bytes), "r"(bar) : "memory");
}
__device__ __forceinline__ void tma_store_3d(const CUtensorMap* tm, uint32_t src, int c0, int c1, int c2) {
  asm volatile("cp.async.bulk.tensor.3d.global.shared::cta.bulk_group [%0, {%2, %3, %4}], [%1];\n"
               ::"l"(tm), "r"(src), "r"(c0), "r"(c1), "r"(c2) : "memory");
}
__device__ __forceinline__ void bulk_commit() { asm volatile("cp.async.bulk.commit_group;\n" ::: "memory"); }
__device__ __forceinline__ void bulk_wait0() { asm volatile("cp.async.bulk.wait_group 0;\n" ::: "memory"); }
__device__ __forceinline__ void prefetch_tmap(const CUtensorMap* tm) {
  asm volatile("prefetch.tensormap [%0];\n" ::"l"(tm) : "memory");
}

__device__ __forceinline__ void wg_fence() { asm volatile("wgmma.fence.sync.aligned;\n" ::: "memory"); }
__device__ __forceinline__ void wg_commit() { asm volatile("wgmma.commit_group.sync.aligned;\n" ::: "memory"); }
template <int N> __device__ __forceinline__ void wg_wait() {
  asm volatile("wgmma.wait_group.sync.aligned %0;\n" ::"n"(N) : "memory");
}
__device__ __forceinline__ uint64_t mkdesc(uint32_t addr, uint32_t lbo, uint32_t sbo, uint32_t swz) {
  return (uint64_t)((addr & 0x3FFFF) >> 4) | ((uint64_t)(lbo >> 4) << 16) | ((uint64_t)(sbo >> 4) << 32) |
         ((uint64_t)swz << 62);
}

#define R4(d, o) "+f"(d[o + 0]), "+f"(d[o + 1]), "+f"(d[o + 2]), "+f"(d[o + 3])
#define R8(d, o) R4(d, o), R4(d, o + 4)
#define R16(d, o) R8(d, o), R8(d, o + 8)
#define R32(d, o) R16(d, o), R16(d, o + 16)
#define R64(d, o) R32(d, o), R32(d, o + 32)

__device__ __forceinline__ void wgmma_n192(float (&d)[96], uint64_t da, uint64_t db, uint32_t acc) {
  asm volatile(
      "{\n.reg .pred p;\nsetp.ne.u32 p, %98, 0;\n"
      "wgmma.mma_async.sync.aligned.m64n192k16.f32.bf16.bf16 "
      "{%0,%1,%2,%3,%4,%5,%6,%7,%8,%9,%10,%11,%12,%13,%14,%15,%16,%17,%18,%19,%20,%21,%22,%23,%24,%25,%26,%27,%28,%29,%30,%31,"
      "%32,%33,%34,%35,%36,%37,%38,%39,%40,%41,%42,%43,%44,%45,%46,%47,%48,%49,%50,%51,%52,%53,%54,%55,%56,%57,%58,%59,%60,%61,%62,%63,"
      "%64,%65,%66,%67,%68,%69,%70,%71,%72,%73,%74,%75,%76,%77,%78,%79,%80,%81,%82,%83,%84,%85,%86,%87,%88,%89,%90,%91,%92,%93,%94,%95}, "
      "%96, %97, p, 1, 1, 0, 1;\n}\n"
      : R64(d, 0), R32(d, 64)
      : "l"(da), "l"(db), "r"(acc));
}
__device__ __forceinline__ void wgmma_n128(float (&d)[64], uint64_t da, uint64_t db, uint32_t acc) {
  asm volatile(
      "{\n.reg .pred p;\nsetp.ne.u32 p, %66, 0;\n"
      "wgmma.mma_async.sync.aligned.m64n128k16.f32.bf16.bf16 "
      "{%0,%1,%2,%3,%4,%5,%6,%7,%8,%9,%10,%11,%12,%13,%14,%15,%16,%17,%18,%19,%20,%21,%22,%23,%24,%25,%26,%27,%28,%29,%30,%31,"
      "%32,%33,%34,%35,%36,%37,%38,%39,%40,%41,%42,%43,%44,%45,%46,%47,%48,%49,%50,%51,%52,%53,%54,%55,%56,%57,%58,%59,%60,%61,%62,%63}, "
      "%64, %65, p, 1, 1, 0, 1;\n}\n"
      : R64(d, 0)
      : "l"(da), "l"(db), "r"(acc));
}
#define WG128(C, ACC)                                                                                                      \
  asm volatile(                                                                                                            \
      "{\n.reg .b64 a, b;\nmov.b64 a, {%64, %66};\nmov.b64 b, {%65, %66};\n"                                               \
      "wgmma.mma_async.sync.aligned.m64n128k16.f32.bf16.bf16 "                                                             \
      "{%0,%1,%2,%3,%4,%5,%6,%7,%8,%9,%10,%11,%12,%13,%14,%15,%16,%17,%18,%19,%20,%21,%22,%23,%24,%25,%26,%27,%28,%29,%30,%31," \
      "%32,%33,%34,%35,%36,%37,%38,%39,%40,%41,%42,%43,%44,%45,%46,%47,%48,%49,%50,%51,%52,%53,%54,%55,%56,%57,%58,%59,%60,%61," \
      "%62,%63}, a, b, " ACC ", 1, 1, 0, 1;\n}\n"                                                                          \
      : Z16(C, d, 0), Z16(C, d, 16), Z16(C, d, 32), Z16(C, d, 48)                                                          \
      : "r"(da), "r"(db), "r"(0x40000040))
#define Z4(C, d, o) C(d[o + 0]), C(d[o + 1]), C(d[o + 2]), C(d[o + 3])
#define Z16(C, d, o) Z4(C, d, o), Z4(C, d, o + 4), Z4(C, d, o + 8), Z4(C, d, o + 12)
__device__ __forceinline__ void wgmma_n128z(float (&d)[64], uint32_t da, uint32_t db) { WG128("=f", "0"); }
__device__ __forceinline__ void wgmma_n128a(float (&d)[64], uint32_t da, uint32_t db) { WG128("+f", "1"); }
template <int N> __device__ __forceinline__ void fence_regs(float (&d)[N]) {
#pragma unroll
  for (int i = 0; i < N; i++) asm volatile("" : "+f"(d[i])::"memory");
}

__device__ __forceinline__ void mma16816(float (&d)[4], uint32_t a0, uint32_t a1, uint32_t a2, uint32_t a3, uint32_t b0,
                                         uint32_t b1) {
  asm("mma.sync.aligned.m16n8k16.row.col.f32.bf16.bf16.f32 {%0,%1,%2,%3}, {%4,%5,%6,%7}, {%8,%9}, {%0,%1,%2,%3};\n"
      : "+f"(d[0]), "+f"(d[1]), "+f"(d[2]), "+f"(d[3])
      : "r"(a0), "r"(a1), "r"(a2), "r"(a3), "r"(b0), "r"(b1));
}
__device__ __forceinline__ void mma16816_z(float (&d)[4], uint32_t a0, uint32_t a1, uint32_t a2, uint32_t a3, uint32_t b0,
                                           uint32_t b1) {
  asm("mma.sync.aligned.m16n8k16.row.col.f32.bf16.bf16.f32 {%0,%1,%2,%3}, {%4,%5,%6,%7}, {%8,%9}, {%10,%10,%10,%10};\n"
      : "=f"(d[0]), "=f"(d[1]), "=f"(d[2]), "=f"(d[3])
      : "r"(a0), "r"(a1), "r"(a2), "r"(a3), "r"(b0), "r"(b1), "f"(0.f));
}
__device__ __forceinline__ void ldsm4t(uint32_t (&r)[4], uint32_t a) {
  asm volatile("ldmatrix.sync.aligned.m8n8.x4.trans.shared.b16 {%0,%1,%2,%3}, [%4];\n"
               : "=r"(r[0]), "=r"(r[1]), "=r"(r[2]), "=r"(r[3]) : "r"(a) : "memory");
}
__device__ __forceinline__ void ldsm2t(uint32_t& r0, uint32_t& r1, uint32_t a) {
  asm volatile("ldmatrix.sync.aligned.m8n8.x2.trans.shared.b16 {%0,%1}, [%2];\n" : "=r"(r0), "=r"(r1) : "r"(a) : "memory");
}
__device__ __forceinline__ void st_async128(uint32_t a, uint32_t bar, uint32_t x, uint32_t y, uint32_t z, uint32_t w) {
  asm volatile("st.async.weak.shared::cluster.mbarrier::complete_tx::bytes.v4.b32 [%0], {%2,%3,%4,%5}, [%1];\n"
               ::"r"(a), "r"(bar), "r"(x), "r"(y), "r"(z), "r"(w) : "memory");
}
__device__ __forceinline__ void mbar_arrive(uint32_t a) {
  asm volatile("mbarrier.arrive.shared::cta.b64 _, [%0];\n" ::"r"(a) : "memory");
}
__device__ __forceinline__ void stsm4(uint32_t a, uint32_t r0, uint32_t r1, uint32_t r2, uint32_t r3) {
  asm volatile("stmatrix.sync.aligned.m8n8.x4.shared.b16 [%0], {%1,%2,%3,%4};\n"
               ::"r"(a), "r"(r0), "r"(r1), "r"(r2), "r"(r3) : "memory");
}
__device__ __forceinline__ void stsm4t(uint32_t a, uint32_t r0, uint32_t r1, uint32_t r2, uint32_t r3) {
  asm volatile("stmatrix.sync.aligned.m8n8.x4.trans.shared.b16 [%0], {%1,%2,%3,%4};\n"
               ::"r"(a), "r"(r0), "r"(r1), "r"(r2), "r"(r3) : "memory");
}
__device__ __forceinline__ uint2 lds64(uint32_t a) {
  uint2 v;
  asm volatile("ld.shared.v2.u32 {%0,%1}, [%2];\n" : "=r"(v.x), "=r"(v.y) : "r"(a));
  return v;
}
__device__ __forceinline__ uint4 lds128(uint32_t a) {
  uint4 v;
  asm volatile("ld.shared.v4.u32 {%0,%1,%2,%3}, [%4];\n" : "=r"(v.x), "=r"(v.y), "=r"(v.z), "=r"(v.w) : "r"(a) : "memory");
  return v;
}
__device__ __forceinline__ void sts128(uint32_t a, uint32_t x, uint32_t y, uint32_t z, uint32_t w) {
  asm volatile("st.shared.v4.u32 [%0], {%1,%2,%3,%4};\n" ::"r"(a), "r"(x), "r"(y), "r"(z), "r"(w) : "memory");
}
__device__ __forceinline__ void sts64(uint32_t a, uint32_t x, uint32_t y) {
  asm volatile("st.shared.v2.u32 [%0], {%1,%2};\n" ::"r"(a), "r"(x), "r"(y) : "memory");
}
__device__ __forceinline__ uint32_t pack_bf16(float lo, float hi) {
  uint32_t r;
  asm("cvt.rn.bf16x2.f32 %0, %1, %2;\n" : "=r"(r) : "f"(hi), "f"(lo));
  return r;
}
__device__ __forceinline__ uint32_t bmul2(uint32_t a, uint32_t b) {
  uint32_t r;
  asm("mul.rn.bf16x2 %0, %1, %2;\n" : "=r"(r) : "r"(a), "r"(b));
  return r;
}
__device__ __forceinline__ uint32_t bmax2(uint32_t a, uint32_t b) {
  uint32_t r;
  asm("max.bf16x2 %0, %1, %2;\n" : "=r"(r) : "r"(a), "r"(b));
  return r;
}
__device__ __forceinline__ uint32_t bfma2(uint32_t a, uint32_t b, uint32_t c) {
  uint32_t r;
  asm("fma.rn.bf16x2 %0, %1, %2, %3;\n" : "=r"(r) : "r"(a), "r"(b), "r"(c));
  return r;
}
__device__ __forceinline__ uint32_t badd2(uint32_t a, uint32_t b) {
  uint32_t r;
  asm("add.rn.bf16x2 %0, %1, %2;\n" : "=r"(r) : "r"(a), "r"(b));
  return r;
}
__device__ __forceinline__ void prefetch_l2(const void* p) { asm volatile("prefetch.global.L2 [%0];\n" ::"l"(p)); }
__device__ __forceinline__ void cp_async16n(uint32_t dst, const void* src) {
  asm volatile("cp.async.cg.shared.global [%0], [%1], 16;\n" ::"r"(dst), "l"(src) : "memory");
}
__device__ __forceinline__ void cp_async16(uint32_t dst, const void* src, uint32_t srcbytes) {
  asm volatile("cp.async.cg.shared.global.L2::256B [%0], [%1], 16, %2;\n" ::"r"(dst), "l"(src), "r"(srcbytes) : "memory");
}
__device__ __forceinline__ uint32_t ld_acquire(const uint32_t* p) {
  uint32_t v;
  asm volatile("ld.acquire.gpu.global.u32 %0, [%1];\n" : "=r"(v) : "l"(p) : "memory");
  return v;
}
__device__ __forceinline__ uint32_t ld_relaxed(const uint32_t* p) {
  uint32_t v;
  asm volatile("ld.relaxed.gpu.global.u32 %0, [%1];\n" : "=r"(v) : "l"(p) : "memory");
  return v;
}
__device__ __forceinline__ void st_release(uint32_t* p, uint32_t v) {
  asm volatile("st.release.gpu.global.u32 [%0], %1;\n" ::"l"(p), "r"(v) : "memory");
}
__device__ __forceinline__ uint4 ld_b128(const uint4* p) {
  unsigned long long a, b;
  asm volatile("{\n.reg .b128 v;\nld.relaxed.gpu.global.b128 v, [%2];\nmov.b128 {%0, %1}, v;\n}\n" : "=l"(a), "=l"(b) : "l"(p) : "memory");
  return make_uint4((uint32_t)a, (uint32_t)(a >> 32), (uint32_t)b, (uint32_t)(b >> 32));
}
__device__ __forceinline__ void st_b128(uint4* p, uint32_t x, uint32_t y, uint32_t z, uint32_t w) {
  asm volatile("{\n.reg .b128 v;\nmov.b128 v, {%1, %2};\nst.relaxed.gpu.global.b128 [%0], v;\n}\n"
               ::"l"(p), "l"(x | (unsigned long long)y << 32), "l"(z | (unsigned long long)w << 32) : "memory");
}

struct Params {
  const __nv_bfloat16* x;
  const __nv_bfloat16* w;
  const __nv_bfloat16* q;
  const __nv_bfloat16* k;
  const __nv_bfloat16* v;
  const __nv_bfloat16* shift_k;
  const __nv_bfloat16* ssm_k;
  const __nv_bfloat16* ssm_D;
  const __nv_bfloat16* wo;
  __nv_bfloat16* out;
  uint32_t zero;
};

__device__ __forceinline__ uint32_t lds32(uint32_t a) {
  uint32_t v;
  asm volatile("ld.shared.u32 %0, [%1];\n" : "=r"(v) : "r"(a));
  return v;
}
__device__ __forceinline__ float bf_lo(uint32_t v) {
  uint32_t r;
  asm("prmt.b32 %0, %1, 0, 0x1044;\n" : "=r"(r) : "r"(v));
  return __uint_as_float(r);
}
__device__ __forceinline__ float bf_hi(uint32_t v) { return __uint_as_float(v & 0xffff0000u); }
__device__ __forceinline__ float ex2(float x) {
  float r;
  asm("ex2.approx.ftz.f32 %0, %1;\n" : "=f"(r) : "f"(x));
  return r;
}
__device__ __forceinline__ float rcp(float x) {
  float r;
  asm("rcp.approx.ftz.f32 %0, %1;\n" : "=f"(r) : "f"(x));
  return r;
}

#define Q4(c, d, o) c(d[o + 0]), c(d[o + 1]), c(d[o + 2]), c(d[o + 3])
#define Q8(c, d, o) Q4(c, d, o), Q4(c, d, o + 4)
#define Q16(c, d, o) Q8(c, d, o), Q8(c, d, o + 8)
#define Q32(c, d) Q16(c, d, 0), Q16(c, d, 16)
#define L8 "{%0,%1,%2,%3,%4,%5,%6,%7}"
#define L16 "{%0,%1,%2,%3,%4,%5,%6,%7,%8,%9,%10,%11,%12,%13,%14,%15}"
#define L32 "{%0,%1,%2,%3,%4,%5,%6,%7,%8,%9,%10,%11,%12,%13,%14,%15,%16,%17,%18,%19,%20,%21,%22,%23,%24,%25,%26,%27,%28,%29,%30,%31}"
__device__ __forceinline__ void fft_rows(uint32_t (&d)[32], const uint32_t (&a)[2][4], uint64_t db) {
  asm volatile("wgmma.mma_async.sync.aligned.m64n128k16.f16.f16.f16 " L32 ", {%32,%33,%34,%35}, %36, 0, 1, 1, 1;\n"
               : Q32("=r", d) : "r"(a[0][0]), "r"(a[0][1]), "r"(a[0][2]), "r"(a[0][3]), "l"(db));
  asm volatile("wgmma.mma_async.sync.aligned.m64n128k16.f16.f16.f16 " L32 ", {%32,%33,%34,%35}, %36, 1, 1, 1, 1;\n"
               : Q32("+r", d) : "r"(a[1][0]), "r"(a[1][1]), "r"(a[1][2]), "r"(a[1][3]), "l"(db + 64));
}
template <int INV> __device__ __forceinline__ void fft_cols(uint32_t (&d)[8], const uint32_t (&a)[2][4], uint64_t db) {
  asm volatile("wgmma.mma_async.sync.aligned.m64n32k16.f16.f16.f16 " L8 ", {%8,%9,%10,%11}, %12, 0, 1, 1, %13;\n"
               : Q8("=r", d, 0) : "r"(a[0][0]), "r"(a[0][1]), "r"(a[0][2]), "r"(a[0][3]), "l"(db), "n"(INV));
  asm volatile("wgmma.mma_async.sync.aligned.m64n32k16.f16.f16.f16 " L8 ", {%8,%9,%10,%11}, %12, 1, 1, 1, %13;\n"
               : Q8("+r", d, 0) : "r"(a[1][0]), "r"(a[1][1]), "r"(a[1][2]), "r"(a[1][3]), "l"(db + (INV ? 16 : 64)), "n"(INV));
}
__device__ __forceinline__ void fft_back(float (&d)[16], uint64_t da, uint64_t db) {
  asm volatile("wgmma.mma_async.sync.aligned.m64n32k16.f32.f16.f16 " L16 ", %16, %17, 0, 1, 1, 1, 1;\n"
               : Q16("=f", d, 0) : "l"(da), "l"(db));
#pragma unroll
  for (int i = 1; i < 4; i++)
    asm volatile("wgmma.mma_async.sync.aligned.m64n32k16.f32.f16.f16 " L16 ", %16, %17, 1, 1, 1, 1, 1;\n"
                 : Q16("+f", d, 0) : "l"(da + 32 * i), "l"(db + 64 * i));
}
__device__ __forceinline__ uint32_t hmul2(uint32_t a, uint32_t b) {
  uint32_t r;
  asm("mul.rn.f16x2 %0, %1, %2;\n" : "=r"(r) : "r"(a), "r"(b));
  return r;
}
__device__ __forceinline__ uint32_t hadd2(uint32_t a, uint32_t b) {
  uint32_t r;
  asm("add.rn.f16x2 %0, %1, %2;\n" : "=r"(r) : "r"(a), "r"(b));
  return r;
}
__device__ __forceinline__ uint32_t hneg2(uint32_t a) {
  uint32_t r;
  asm("neg.f16x2 %0, %1;\n" : "=r"(r) : "r"(a));
  return r;
}
__device__ __forceinline__ uint32_t hfma2(uint32_t a, uint32_t b, uint32_t c) {
  uint32_t r;
  asm("fma.rn.f16x2 %0, %1, %2, %3;\n" : "=r"(r) : "r"(a), "r"(b), "r"(c));
  return r;
}
__device__ __forceinline__ uint32_t pack_f16(float lo, float hi) {
  uint32_t r;
  asm("cvt.rn.f16x2.f32 %0, %1, %2;\n" : "=r"(r) : "f"(hi), "f"(lo));
  return r;
}
__device__ __forceinline__ uint32_t bmaxabs2(uint32_t a, uint32_t b) {
  uint32_t r;
  asm("max.xorsign.abs.bf16x2 %0, %1, %2;\n" : "=r"(r) : "r"(a), "r"(b));
  return r;
}
struct C2 { uint32_t r, i; };
__device__ __forceinline__ C2 cmul(C2 a, C2 b) {
  return C2{hfma2(a.r, b.r, hneg2(hmul2(a.i, b.i))), hfma2(a.r, b.i, hmul2(a.i, b.r))};
}
__device__ __forceinline__ C2 cfma(C2 a, C2 b, C2 c) {
  return C2{hfma2(a.r, b.r, hfma2(hneg2(a.i), b.i, c.r)), hfma2(a.r, b.i, hfma2(a.i, b.r, c.i))};
}
__device__ __forceinline__ C2 crot(C2 z, C2 t) {
  const uint32_t r = hfma2(t.r, z.i, z.r), i = hfma2(t.i, r, z.i);
  return C2{hfma2(t.r, i, r), i};
}
__device__ __forceinline__ C2 cget(const uint32_t (&e)[8], int j, int b) { return C2{e[4 * j + b], e[4 * j + 2 + b]}; }
template <int N> __device__ __forceinline__ void fence_regs(uint32_t (&d)[N]) {
#pragma unroll
  for (int i = 0; i < N; i++) asm volatile("" : "+r"(d[i])::"memory");
}
__device__ __forceinline__ void ldsm4(uint32_t (&r)[4], uint32_t a) {
  asm volatile("ldmatrix.sync.aligned.m8n8.x4.shared.b16 {%0,%1,%2,%3}, [%4];\n"
               : "=r"(r[0]), "=r"(r[1]), "=r"(r[2]), "=r"(r[3]) : "r"(a) : "memory");
}

__device__ __forceinline__ uint32_t movm(uint32_t a) {
  uint32_t r;
  asm volatile("movmatrix.sync.aligned.m8n8.trans.b16 %0, %1;\n" : "=r"(r) : "r"(a));
  return r;
}
template <int C0, int H, bool T> __device__ __forceinline__ void attn_pack(const float (&acc)[96], uint32_t (&d)[8]) {
#pragma unroll
  for (int c = 0; c < 8; c++) {
    asm volatile("cvt.rn.bf16x2.f32 %0, %1, %2;\n" : "=r"(d[c]) : "f"(acc[4 * (C0 + c) + 2 * H + 1]), "f"(acc[4 * (C0 + c) + 2 * H]));
    if (T) d[c] = movm(d[c]);
  }
}
__device__ __forceinline__ void attn_qk(float (&s)[4], const uint32_t (&qlo)[8], const uint32_t (&qhi)[8],
                                        const uint32_t (&k)[8], int c) {
  mma16816_z(s, qlo[c], qhi[c], qlo[c + 1], qhi[c + 1], k[c], k[c + 1]);
  mma16816(s, qlo[c + 2], qhi[c + 2], qlo[c + 3], qhi[c + 3], k[c + 2], k[c + 3]);
}
template <int N> __device__ __forceinline__ void quad_softmax(float (&x)[N][2], uint32_t (&pp)[N]) {
  const float c2 = 1.4426950408889634f;
  uint32_t q[N], mx[N / 2];
#pragma unroll
  for (int n = 0; n < N; n++) {
    const uint32_t r = pack_bf16(x[n][0], x[n][1]);
    q[n] = bfma2(r, 0x3e353e35u, bmul2(r, 0x379e379eu));
    x[n][0] = bf_lo(q[n]);
    x[n][1] = bf_hi(q[n]);
  }
#pragma unroll
  for (int n = 0; n < N / 2; n++)
    mx[n] = bmax2(__byte_perm(q[2 * n], q[2 * n + 1], 0x5410), __byte_perm(q[2 * n], q[2 * n + 1], 0x7632));
#pragma unroll
  for (int o = 1; o <= 2; o++) {
#pragma unroll
    for (int n = 0; n < N / 2; n++) mx[n] = bmax2(mx[n], __shfl_xor_sync(0xffffffffu, mx[n], o));
  }
  float m[N], t[N];
#pragma unroll
  for (int n = 0; n < N / 2; n++) {
    m[2 * n] = bf_lo(mx[n]);
    m[2 * n + 1] = bf_hi(mx[n]);
  }
#pragma unroll
  for (int n = 0; n < N; n++) {
    const float nm = -m[n] * c2;
    x[n][0] = ex2(fmaf(x[n][0], c2, nm));
    x[n][1] = ex2(fmaf(x[n][1], c2, nm));
  }
#pragma unroll
  for (int n = 0; n < N; n += 2) {
    float u0, u1;
    asm("mma.sync.aligned.m16n8k8.row.col.f32.tf32.tf32.f32 {%0,%1,%2,%3}, {%4,%5,%6,%7}, {%8,%8}, {%9,%9,%9,%9};\n"
        : "=f"(t[n]), "=f"(u0), "=f"(t[n + 1]), "=f"(u1)
        : "r"(__float_as_uint(x[n][0])), "r"(__float_as_uint(x[n + 1][0])), "r"(__float_as_uint(x[n][1])),
          "r"(__float_as_uint(x[n + 1][1])), "r"(0x3f800000u), "f"(0.f));
  }
#pragma unroll
  for (int n = 0; n < N; n++) {
    const float inv = rcp(t[n]);
    pp[n] = pack_bf16(x[n][0] * inv, x[n][1] * inv);
  }
}
__device__ __forceinline__ void attn_pv(uint32_t dst, const uint32_t (&vp)[8], const uint32_t (&vo)[8], int c, uint32_t pp,
                                        uint32_t maskLE) {
  const uint32_t b0 = pp & ~maskLE, b1 = pp & maskLE;
  float oa[4], ob[4];
  mma16816_z(oa, vp[c], vp[c + 1], vo[c], vo[c + 1], b0, b1);
  mma16816_z(ob, vp[c + 2], vp[c + 3], vo[c + 2], vo[c + 3], b0, b1);
  stsm4t(dst, pack_bf16(oa[0], oa[1]), pack_bf16(oa[2], oa[3]), pack_bf16(ob[0], ob[1]), pack_bf16(ob[2], ob[3]));
}

template <int MODE>
__global__ void __cluster_dims__(2, 1, 1) __launch_bounds__(NTHREADS, 1)
fused_kernel(const Params p, const __grid_constant__ CUtensorMap tmX, const __grid_constant__ CUtensorMap tmW,
             const __grid_constant__ CUtensorMap tmWo, const __grid_constant__ CUtensorMap tmWp,
             const __grid_constant__ CUtensorMap tmQ,
             const __grid_constant__ CUtensorMap tmOb,
             const __grid_constant__ CUtensorMap tmXh, const __grid_constant__ CUtensorMap tmWh) {
  extern __shared__ __align__(1024) uint8_t smem[];
  if (threadIdx.x < 32 * PFR) {
    const uint32_t i = ((blockIdx.x + (threadIdx.x >> 5) * (128 / PFR)) & 127) * 16 + (threadIdx.x & 15);
    prefetch_l2(threadIdx.x & 16 ? (const char*)p.w + i * 128 : (const char*)p.x + i * 2048);
  }
  const uint32_t sb = smem_u32(smem);
  const uint32_t bars = sb + OFF_BAR;
  const int tid = threadIdx.x, lane = tid & 31, warp = __shfl_sync(0xffffffffu, tid >> 5, 0);
  const int rank = blockIdx.x & 1;
  const bool halo_cta = blockIdx.x < 4;
  if (halo_cta && MODE != 0) return;
  int grp, mem;
  {
    const int t = (blockIdx.x >> 1) - 4, u = t - 32;
    const int q7 = (u * 37) >> 8;
    const bool lo = (unsigned)t < 32u, mid = (unsigned)u < 28u;
    grp = lo ? (t & 7) : (mid ? 1 + u - 7 * q7 : 0);
    mem = lo ? (t >> 3) : (mid ? 4 + q7 : (t < 0 ? t + 6 : t - 54));
  }
  const int rg = (grp >> 2) * 4 + (mem >> 1), hp = (grp & 3) * 4 + (mem & 1) * 2 + rank;
  const int rb2 = (grp >> 2) * 8 + mem, cb2 = (grp & 3) * 2 + rank;
  const int chb = grp * 16 + mem * 2 + rank;
  const int cta = rg * 16 + hp;
  const int hsel = rb2 & 1;
  const int par = rg >> 2, gidx = rg & 3;

  if (tid < 256 && !halo_cta && MODE != 2) {
    const int r = tid >> 3, c = tid & 7;
    const uint32_t so = r * 128 + ((c ^ (r & 7)) << 4);
    const __nv_bfloat16* wg0 = p.w + (size_t)r * (3 * DM) + hp * 64 + c * 8;
    const __nv_bfloat16* xg0 = p.x + (size_t)(2 * (gidx * 256 + r) + par) * DM + c * 8;
#pragma unroll
    for (int j = 0; j < 3; j++) cp_async16n(sb + OFF_1B + j * 4096 + so, wg0 + j * DM);
#pragma unroll
    for (int i = 0; i < 8; i++) cp_async16n(sb + i * 4096 + so, xg0 + (size_t)i * 64 * DM);
    asm volatile("cp.async.commit_group;\n" ::: "memory");
    if (PF2 >= 1 && tid < 16 * PF2X) prefetch_l2((const char*)p.x + (chb * 16 + (tid & 15)) * 2048 + 128 + (tid >> 4) * 128);
    if (PF2 >= 2 && warp == 2) prefetch_l2((const char*)p.w + (2048 + chb * 32 + lane) * 128);
  }

  if (warp >= 8) {
    asm volatile("setmaxnreg.dec.sync.aligned.u32 %0;\n" :: "n"(REG_HELP));
    auto halo_issue = [&](int n, int s) {
      const uint32_t fb = bars + 8 * (BAR_FULLB + s), st = sb + s * STGH;
      tma_load_3d(st + 8192, &tmWh, fb, 0, (n >> 1) * 64, 16 + (n & 1) * 16 + blockIdx.x * 4);
      tma_load_4d(st, &tmXh, fb, (n >> 1) * 64, 248, 0, 0);
      mbar_expect_tx(fb, STGH - 2048);
    };
    if (tid == 256) {
      prefetch_tmap(halo_cta ? &tmXh : &tmX);
#pragma unroll
      for (int i = 0; i < NS1B; i++) mbar_init(bars + 8 * (BAR_FULLB + i), 1);
#pragma unroll
      for (int i = 0; i < NS1A; i++) mbar_init(bars + 8 * (BAR_FULLA + i), 1);
      asm volatile("fence.mbarrier_init.release.cluster;\n" ::: "memory");
      if (!halo_cta && MODE != 2) {
        mbar_expect_tx(bars + 8 * (BAR_FULLB + 1), STG1B);
        tma_load_3d(sb + OFF_1B + 1 * STG1B, &tmW, bars + 8 * (BAR_FULLB + 1), hp * 64, 32, 0);
        mbar_expect_tx(bars + 8 * (BAR_FULLB + 2), STG1B);
        tma_load_3d(sb + OFF_1B + 2 * STG1B, &tmW, bars + 8 * (BAR_FULLB + 2), hp * 64, 64, 0);
        mbar_arrive(bars + 8 * BAR_FULLA);
        mbar_arrive(bars + 8 * BAR_FULLB);
      } else if (halo_cta) {
        halo_issue(0, 0);
      }
    } else if (tid == 288) {
#pragma unroll
      for (int i = 0; i < NS1A; i++) mbar_init(bars + 8 * (BAR_EMPTYA + i), 4);
#pragma unroll
      for (int i = 0; i < NS1B; i++) mbar_init(bars + 8 * (BAR_EMPTYB + i), 2);
      mbar_init(bars + 8 * BAR_X, 4);
      mbar_init(bars + 8 * BAR_TAB, 16);
      mbar_init(bars + 8 * BAR_U, 1);
      mbar_init(bars + 8 * BAR_H, 1);
      mbar_init(bars + 8 * BAR_STG, 8);
      mbar_init(bars + 8 * BAR_HALO, 1);
      mbar_init(bars + 8 * BAR_Q, 1);
      mbar_init(bars + 8 * BAR_LAND, 5);
      mbar_init(bars + 8 * (BAR_LAND + 1), 5);
      asm volatile("fence.mbarrier_init.release.cluster;\n" ::: "memory");
    } else if (tid == 320) {
#pragma unroll
      for (int i = 0; i < NS2; i++) {
        mbar_init(bars + 8 * (BAR_FULL2 + i), 1);
        mbar_init(bars + 8 * (BAR_EMPTY2 + i), 2);
        mbar_init(bars + 8 * (BAR_EMPTY2B + i), 2);
      }
      asm volatile("fence.mbarrier_init.release.cluster;\n" ::: "memory");
    } else if (tid == 352) {
#pragma unroll
      for (int i = 0; i < 4; i++) mbar_init(bars + 8 * (BAR_Y + i), i < 2 ? 4 : i == 2 ? 10 : 8);
      mbar_init(bars + 8 * BAR_XFREE, 1);
      asm volatile("fence.mbarrier_init.release.cluster;\n" ::: "memory");
    }
    __syncwarp();
    cluster_sync_all();
    if (warp == 8) PROF2(24);
    const int hw = warp - 8;
    const int lr = lane & 7, lm = lane >> 3;
    auto g1_issue_a = [&](int j, int s) {
      const uint32_t fb = bars + 8 * (BAR_FULLA + s);
      mbar_expect_tx(fb, STG1A);
      tma_load_3d_mc(sb + s * STG1A + rank * 16384, &tmX, fb, j * 64, par, gidx * 256 + rank * 128);
    };
    auto g1_issue_b = [&](int kb, int s) {
      const uint32_t fb = bars + 8 * (BAR_FULLB + s);
      mbar_expect_tx(fb, STG1B);
      tma_load_3d(sb + OFF_1B + s * STG1B, &tmW, fb, hp * 64, kb * 32, 0);
    };
    auto g2_k = [&](int kb) { return (kb < 2 ? hp : kb < 4 ? hp & 14 : hp & 12) ^ kb; };
    auto g2_issue_b = [&](uint32_t fb, uint32_t bytes, uint32_t dst, int k0, bool whole) {
      if (whole) {
        tma_load_3d(dst, &tmWo, fb, 0, k0, cb2 * 2);
      } else {
#pragma unroll
        for (int i = 0; i < 4; i++)
          tma_load_3d(dst + (i & 1) * XT + (i >> 1) * 4 * XT, &tmWp, fb, 0, k0 + (i >> 1) * 32, cb2 * 2 + (i & 1));
      }
      mbar_expect_tx(fb, bytes);
    };
    auto send_y = [&](uint32_t o, uint32_t step, int half) {
      const uint32_t peer = mapa(sb, rank ^ 1);
      o += OFF_X + (rank ^ 1) * 4096 + half * 2048 + lane * 16;
      uint4 a[8];
#pragma unroll
      for (int i = 0; i < 8; i++) a[i] = lds128(sb + o + (i >> 2) * step + (i & 2) * (XT / 2) + (i & 1) * 512);
#pragma unroll
      for (int i = 0; i < 8; i++)
        st_async128(peer + o + 1024 + (i >> 2) * step + (i & 2) * (XT / 2) + (i & 1) * 512,
                    peer + OFF_BAR + 8 * (BAR_LAND + half), a[i].x, a[i].y, a[i].z, a[i].w);
    };

    if (halo_cta) {
      if (hw == 0) {
        int s = 1, ph = 1;
#pragma unroll 1
        for (int n = 1; n < 32; n++) {
          mbar_wait(bars + 8 * (BAR_EMPTYB + s), ph);
          if (elect_one()) halo_issue(n, s);
          if (++s == NS1B) { s = 0; ph ^= 1; }
        }
      }
      __syncwarp();
    } else if (hw == 0) {
      uint32_t epoch = 0;
      if (MODE == 2) {
        if (lane < NS2) mbar_arrive_cluster_n(mapa(bars, rank) + 8 * (BAR_EMPTY2 + lane), 2);
      } else {
      if (lane == 0) {
        mbar_expect_tx(bars + 8 * BAR_U, 32768);
        mbar_expect_tx(bars + 8 * BAR_LAND, 8192);
        mbar_expect_tx(bars + 8 * (BAR_LAND + 1), 8192);
        mbar_expect_tx(bars + 8 * BAR_Q, 32768);
        prefetch_tmap(&tmQ);
      }
      {
        int sa = 1, pha = 1, sbb = 2, phb = 1;
#pragma unroll 1
        for (int kb = 2; kb < 32; kb++) {
          if (!(kb & 1)) {
            mbar_wait(bars + 8 * (BAR_EMPTYA + sa), pha);
            if (elect_one()) g1_issue_a(kb >> 1, sa);
            if (++sa == NS1A) { sa = 0; pha ^= 1; }
          }
          mbar_wait(bars + 8 * (BAR_EMPTYB + sbb), phb);
          if (kb > 2 && elect_one()) g1_issue_b(kb, sbb);
          __syncwarp();
          if (kb == 4) epoch = ld_relaxed(g_flag_o + cta);
          if (kb == 4) PROF2(27);
          if (kb == 1) PROF2(38);
          if (kb == 2) PROF2(39);
          if (++sbb == NS1B) { sbb = 0; phb ^= 1; }
        }
      }
      auto q_issue = [&](int i) {
        mbar_wait(bars + 8 * (i ? BAR_EMPTYB + 3 : BAR_EMPTYA + 1), i);
        if (elect_one())
          asm volatile(
              "cp.async.bulk.tensor.5d.shared::cluster.global.mbarrier::complete_tx::bytes [%0], [%1, {%3, %4, %4, %4, %5}], [%2];\n"
              ::"r"(sb + (i ? OFF_Q1 : OFF_Q0)), "l"(&tmQ), "r"(bars + 8 * BAR_Q), "r"((chb & ~1) * 8), "r"(0), "r"(rank * 32 + i * 64)
              : "memory");
        __syncwarp();
      };
      epoch++;
      if (lane == 0) {
        prefetch_tmap(&tmWo);
        prefetch_tmap(&tmWp);
        prefetch_tmap(&tmOb);
      }
      __syncwarp();
      {
        uint4 h[6] = {};
        if (gidx != 0) {
#pragma unroll 1
          for (int n = 0; n < SPIN_LIMIT; n++) {
            bool ok = true;
#pragma unroll
            for (int i = 0; i < 6; i++) h[i] = ld_b128(g_halo + cta * 192 + i * 32 + lane);
#pragma unroll
            for (int i = 0; i < 6; i++) ok = ok && h[i].w == epoch;
            if (__all_sync(0xffffffffu, ok)) break;
          }
          PROF(18);
        }
        q_issue(0);
        sts128(sb + OFF_KH + lane * 16, h[0].x, h[0].y, h[0].z, h[1].x);
        sts128(sb + OFF_KH + 512 + lane * 16, h[1].y, h[1].z, h[2].x, h[2].y);
        sts64(sb + OFF_KH + 1024 + lane * 8, h[3].x, h[3].y);
        sts64(sb + OFF_KH + 1280 + lane * 8, h[3].z, h[4].x);
        sts64(sb + OFF_KH + 1536 + lane * 8, h[4].y, h[4].z);
        sts64(sb + OFF_KH + 1792 + lane * 8, h[5].x, h[5].y);
        __syncwarp();
        if (lane == 0) mbar_arrive(bars + 8 * BAR_HALO);
      }
      q_issue(1);
      const uint32_t rb = mapa(bars, lane & 1);
      nb_sync(NB_OREADY, 288);
      if (lane == 0) {
        asm volatile("cp.async.bulk.global.shared::cta.bulk_group [%0], [%1], %2;\n" ::"l"(g_o + (size_t)cta * 16384),
                     "r"(sb + OFF_OP), "r"(32768) : "memory");
        bulk_commit();
      }
      if (lane < 2) {
#pragma unroll
        for (int i = 0; i < 4; i++) mbar_arrive_cluster(rb + 8 * (BAR_EMPTY2 + i + i / 2));
      }
      if (lane == 0) {
        bulk_wait0();
        st_release(g_flag_o + cta, epoch);
      }
      __syncwarp();
      PROF2(17);
      if (lane < 2) mbar_arrive_cluster(rb + 8 * (BAR_EMPTY2 + 2));
      }
      if (MODE != 1) {
        const __nv_bfloat16* osrc = g_o + (size_t)(rb2 >> 1) * 16 * 16384 + hsel * 8192;
        mbar_wait(bars + 8 * (BAR_EMPTY2 + 1), 0);
        if (elect_one()) {
          if (MODE == 0) {
            asm volatile("cp.async.bulk.shared::cluster.shared::cta.mbarrier::complete_tx::bytes [%0], [%1], %2, [%3];\n"
                         ::"r"(mapa(sb + g2_a(1, hsel), rank ^ 1)), "r"(sb + g2_a(0, hsel)), "r"(16384),
                         "r"(mapa(bars + 8 * (BAR_FULL2 + 1), rank ^ 1)) : "memory");
          } else {
            bulk_load(sb + g2_a(0, hsel), osrc + hp * 16384, 16384, bars + 8 * BAR_FULL2);
            bulk_load(sb + g2_a(1, hsel), osrc + (hp ^ 1) * 16384, 16384, bars + 8 * (BAR_FULL2 + 1));
          }
        }
        __syncwarp();
      }
      if (MODE != 2) {
        mbar_wait(bars + 8 * (BAR_Y + 2), 0);
        send_y(0, 4 * XT, 1);
        fence_async_smem();
        __syncwarp();
      }
      if (MODE != 1) {
        unsigned long long seq = G2_SEQ >> 12;
        uint32_t wbar = bars + 8 * (BAR_Y + 2), fb = bars + 8 * (BAR_FULL2 + 3), dst = sb + g2_b(3, rank), ph = MODE ? 1 : 0;
        int k0 = g2_k(3) * 64;
        bool whole = false;
#pragma unroll 1
        for (int kb = 4; kb <= 16; kb++) {
          mbar_wait(wbar, ph);
          if (elect_one()) g2_issue_b(fb, STG2, dst, k0, whole);
          __syncwarp();
          seq >>= 4;
          const int s = seq & 7;
          wbar = bars + 8 * (kb == G2_KB4 ? BAR_XFREE : BAR_EMPTY2B + s);
          ph = ((uint32_t)seq >> 3 & 1) ^ (kb == G2_KB4 && MODE == 0 ? 0 : 1);
          fb = bars + 8 * (BAR_FULL2 + s);
          dst = sb + g2_b(s, rank);
          k0 = ((hp & 12) ^ kb) * 64;
          whole = s < 3;
        }
      }
      __syncwarp();
    } else {
      if (MODE != 2) {
      const float dall = __bfloat162float(p.ssm_D[chb * 8 + lr]);
      {
        const int g = lane >> 2, t = lane & 3;
        uint32_t w[2][4];
#pragma unroll
        for (int h = 0; h < 2; h++) {
          const uint2 x = __ldg(reinterpret_cast<const uint2*>(p.shift_k + ((chb & ~1) * 8 + h * 8 + g) * 4));
          w[h][0] = __byte_perm(x.x, x.x, 0x1010);
          w[h][1] = __byte_perm(x.x, x.x, 0x3232);
          w[h][2] = __byte_perm(x.y, x.y, 0x1010);
          w[h][3] = __byte_perm(x.y, x.y, 0x3232);
        }
        auto swz = [](int r) { return (((r & 29) | ((r ^ (r >> 2)) & 2)) << 5) | (r & 16); };
        const uint32_t kring = sb + OFF_X + 4096 + (hw - 1) * 2 * XT, vring = kring + XT;
        const int s0 = rank * 32 + (hw - 1) * 11, s1 = hw == 3 ? rank * 32 + 32 : s0 + 11;
        const size_t goff = (size_t)(s0 * 32 + (lane >> 1)) * DM + (chb & ~1) * 8 + (lane & 1) * 8;
        const __nv_bfloat16* kg = p.k + goff;
        const __nv_bfloat16* vg = p.v + goff;
        const uint32_t d0 = swz(lane >> 1) ^ ((lane & 1) << 4), d1 = swz(16 + (lane >> 1)) ^ ((lane & 1) << 4);
        auto issue = [&](int st) {
          const uint32_t a = kring + ((st & 3) << 10);
          asm volatile("cp.async.cg.shared.global.L2::256B [%0], [%2], 16;\n"
                       "cp.async.cg.shared.global.L2::256B [%1], [%2 + 32768], 16;\n"
                       "cp.async.cg.shared.global.L2::256B [%0 + 8192], [%3], 16;\n"
                       "cp.async.cg.shared.global.L2::256B [%1 + 8192], [%3 + 32768], 16;\n"
                       ::"r"(a + d0), "r"(a + d1), "l"(kg), "l"(vg) : "memory");
          kg += 32 * DM;
          vg += 32 * DM;
          asm volatile("" : "+l"(kg), "+l"(vg));
        };
        const int xa = 8 * (lr >> 1) + 2 * lm + (lr & 1), xb = 8 * (lr >> 1) - 4 + 2 * (lm & 1) + (lr & 1);
        const uint32_t la = swz(xa), lb = swz(xb & 31);
        const int backb = xb < 0 ? 1 : 0;
        const uint32_t ud[2] = {mapa(sb + OFF_X + g * XT + t * 16, 0), mapa(sb + OFF_X + g * XT + t * 16, 1)};
        const uint32_t ub[2] = {mapa(bars + 8 * BAR_U, 0), mapa(bars + 8 * BAR_U, 1)};
        if (tid == 320) prefetch_l2(g_tab + (chb & 63) * 32);
        if (lane == 0) mbar_wait(bars + 8 * (BAR_FULLB + NS1B - 1), 0);
        __syncwarp();
        if (lane >= 24) cp_async16(kring + (((s0 - 1) & 3) << 10) + d1, s0 > 0 ? kg - 16 * DM : kg, s0 > 0 ? 16 : 0);
        issue(s0);
        asm volatile("cp.async.commit_group;\n" ::: "memory");
        issue(s0 + 1);
        asm volatile("cp.async.commit_group;\n" ::: "memory");
        const __nv_bfloat16* hg = p.ssm_k + (size_t)chb * 8 * SEQ + lane * 64;
        uint32_t tn = (uint32_t)clock();
#pragma unroll 1
        for (int st = s0; st < s1; st++) {
          tn += PSTEP;
          while ((int)((uint32_t)clock() - tn) < 0) __nanosleep(100);
          if (st + 2 < s1) issue(st + 2);
          if (hw == 1 && st - s0 < 8) prefetch_l2(hg);
          hg += SEQ;
          asm volatile("" : "+l"(hg));
          asm volatile("cp.async.commit_group;\n" ::: "memory");
          asm volatile("cp.async.wait_group 2;\n" ::: "memory");
          __syncwarp();
#pragma unroll
          for (int h = 0; h < 2; h++) {
            uint32_t e[6], vv[4], e4[4];
            ldsm4t(e4, kring + ((st & 3) << 10) + (la ^ (h << 4)));
            ldsm2t(e[0], e[1], kring + (((st - backb) & 3) << 10) + (lb ^ (h << 4)));
            ldsm4t(vv, vring + ((st & 3) << 10) + (la ^ (h << 4)));
            e[2] = e4[0]; e[3] = e4[1]; e[4] = e4[2]; e[5] = e4[3];
            uint32_t o[5];
#pragma unroll
            for (int i = 0; i < 5; i++) o[i] = __byte_perm(e[i], e[i + 1], 0x5432);
#pragma unroll
            for (int i = 0; i < 4; i++) {
              uint32_t a = bmul2(o[i], w[h][3]);
              a = bfma2(e[i + 1], w[h][2], a);
              a = bfma2(o[i + 1], w[h][1], a);
              a = bfma2(e[i + 2], w[h][0], a);
              vv[i] = bmul2(a, vv[i]);
            }
            st_async128(ud[h] + (st ^ (g & 1)) * 64, ub[h], vv[0], vv[1], vv[2], vv[3]);
          }
          __syncwarp();
        }
        fence_async_smem();
        PROF(16);
      }
      nb_sync(NB_HELP3, 96);
      if (hw == 1 && elect_one()) {
        mbar_expect_tx(bars + 8 * BAR_H, 8 * 4096);
#pragma unroll 1
        for (int c = 0; c < 8; c++)
          bulk_load(sb + OFF_X + c * XT + 4096, p.ssm_k + (size_t)(chb * 8 + c) * SEQ, 4096, bars + 8 * BAR_H);
        mbar_expect_tx(bars + 8 * BAR_X, 6144);
        bulk_load(sb + OFF_T16, g_tab, 2048, bars + 8 * BAR_X);
        bulk_load(sb + OFF_T32, g_tab + 512, 4096, bars + 8 * BAR_X);
      }
      __syncwarp();
      {
        if (WOP == 0) if (hw == 3) {
          const char* wo = (const char*)p.wo + chb * 16384 + lane * 128;
#pragma unroll
          for (int i = 0; i < 4; i++) prefetch_l2(wo + i * 4096);
        }
        const int ck = 16 * (lane >> 4) + 2 * lr + (((lane >> 3) ^ (lane >> 2)) & 1);
        const uint32_t xo = (ck >> 1) * 64, xs = ((ck & 1) ^ (lr >> 1)) << 4;
#pragma unroll 1
        for (int job = hw - 1; job < 16; job += 3) {
          const int c = job & 7;
          uint4 a[8];
          float dv = __shfl_sync(0xffffffffu, dall, c);
          if (job < 8 || lane) dv = 0.f;
          const uint32_t xt = sb + OFF_X + c * XT + (job >> 3) * 4096;
          mbar_wait(bars + 8 * (job < 8 ? BAR_U : BAR_H), 0);
#pragma unroll
          for (int i = 0; i < 8; i++) a[i] = lds128(xt + i * 512 + ((ck ^ (job < 8 ? (c & 1) << 2 : 0)) << 4));
          dv += bf_lo(a[0].x);
          uint32_t m[2] = {bmaxabs2(pack_bf16(dv, 0.f), bmaxabs2(a[0].x, a[0].y)), bmaxabs2(a[0].z, a[0].w)};
#pragma unroll
          for (int i = 1; i < 8; i++) {
            m[0] = bmaxabs2(bmaxabs2(m[0], a[i].x), a[i].y);
            m[1] = bmaxabs2(bmaxabs2(m[1], a[i].z), a[i].w);
          }
          m[0] = bmaxabs2(m[0], m[1]);
          const int f = max(252 - (int)(__reduce_max_sync(0xffffffffu, max(m[0] & 0x7fffu, (m[0] >> 16) & 0x7fffu)) >> 7), 1);
          if (lane == 0) asm volatile("st.shared.u32 [%0], %1;\n" ::"r"(sb + OFF_EX + job * 4), "r"(f) : "memory");
          if (f < 113) {
#pragma unroll
            for (int i = 0; i < 8; i++)
              a[i] = make_uint4(bmul2(a[i].x, f * 0x00800080u), bmul2(a[i].y, f * 0x00800080u), bmul2(a[i].z, f * 0x00800080u),
                                bmul2(a[i].w, f * 0x00800080u));
          }
          const uint32_t mul = (f < 113 ? 15 : f - 112) * 0x00800080u;
          auto cv = [&](uint32_t x) {
            x = bmul2(x, mul);
            return (x & 0x0fff0fffu) * 7 + x;
          };
          const uint32_t dst = xt + xo;
#pragma unroll
          for (int i = 0; i < 8; i++)
            sts128(dst + (i >> 2) * 2048 + (i & 1) * 1024 + (xs ^ ((i & 2) << 4)),
                   i ? cv(a[i].x) : __byte_perm(pack_f16(dv * __uint_as_float(f << 23), 0.f), cv(a[i].x), 0x7610), cv(a[i].y),
                   cv(a[i].z), cv(a[i].w));
        }
        fence_async_smem();
        __syncwarp();
        if (lane == 0) mbar_arrive(bars + 8 * BAR_X);
        if (WOP == 1) if (hw == 3) {
          const char* wo = (const char*)p.wo + chb * 16384 + lane * 128;
#pragma unroll
          for (int i = 0; i < 4; i++) prefetch_l2(wo + i * 4096);
        }
        PROF(19);
      }
      if (hw < 3) {
#pragma unroll 1
        for (int n = 0; n < SPIN_LIMIT && !mbar_try(bars + 8 * (BAR_Y + hw - 1), 0); n++) __nanosleep(100);
        send_y((hw - 1) * 4 * XT, 2 * XT, 0);
        __syncwarp();
        if (lane == 0) mbar_arrive(bars + 8 * (BAR_Y + 2));
        PROF(32);
        const int c8 = 2 * lm + (lr & 1), src = (lr >> 1) & 1;
        uint32_t fa = sb + OFF_X + c8 * XT + rank * 4096 + (src == rank ? 0 : 1024) + (hw - 1) * 512;
        const uint32_t fx = ((lr >> 2) ^ ((lr & 3) << 1)) << 4;
        uint32_t qa = sb + OFF_Q0 + (hw - 1) * 8192 + (lane >> 3) * 128 + (lane & 2) * 32 + (lane & 4) * 8 + (lane & 1) * 16;
        uint4* og = reinterpret_cast<uint4*>(p.out + (size_t)(rank * 512 + (hw - 1) * 256 + (lane & 2) * 4 + (lane >> 2)) * (2 * DM) +
                                             (chb & ~1) * 8 + (lane & 1) * 8);
        mbar_wait(bars + 8 * BAR_Q, 0);
        uint32_t tn = 0;
#pragma unroll 1
        for (int j = 0; j < 16; j++) {
          if (j == JS && hw == 2) {
            mbar_wait(bars + 8 * (BAR_Y + 3), 0);
            send_y(2 * XT, 4 * XT, 1);
            fence_async_smem();
            __syncwarp();
            if (lane == 0) mbar_arrive(bars + 8 * BAR_XFREE);
            tn = (uint32_t)clock();
          }
          if (!(j & 7)) {
            mbar_wait(bars + 8 * (BAR_LAND + (j >> 3)), 0);
            tn = (uint32_t)clock() + (hw - 1) * (FPACE / 2);
            PROF2(33 + (j >> 1));
          }
#pragma unroll
          for (int i = 0; i < 2; i++) {
            uint32_t y[4];
            const uint4 q = lds128(qa + i * 512);
            ldsm4t(y, fa + (j & 6) * 64 + (fx ^ (i << 5) ^ ((j & 1) << 6) ^ ((j & 2) << 3)));
            while ((int)((uint32_t)clock() - tn) < 0) __nanosleep(FSL);
            tn += hw == 2 ? FPACE2 : FPACE;
            og[i * 16 * (2 * DM / 8)] = make_uint4(bmul2(q.x, y[0]), bmul2(q.y, y[1]), bmul2(q.z, y[2]), bmul2(q.w, y[3]));
          }
          qa += j == 7 ? OFF_Q1 - OFF_Q0 - 7168 : 1024;
          if (j == 7) fa += 2048;
          og += (j == 7 ? 1024 - 224 : 32) * (2 * DM / 8);
        }
        PROF(22);
      }
      }
      if (MODE != 1 && hw == 3) {
        const uint32_t epoch = ld_relaxed(g_flag_o + cta) + 1;
        if (MODE == 0) nb_sync(NB_G1END, 288);
        if (BDEL) __nanosleep(BDEL);
        if (elect_one()) {
#pragma unroll
          for (int kb = 0; kb < 3; kb++)
            g2_issue_b(bars + 8 * (BAR_FULL2 + kb), kb || MODE ? STG2 : STG2 / 2, sb + g2_b(kb, 0), g2_k(kb) * 64, true);
        }
        __syncwarp();
        const __nv_bfloat16* osrc = g_o + (size_t)(rb2 >> 1) * 16 * 16384 + hsel * 8192;
        if (MODE == 0) __nanosleep(POLL0);
        const uint32_t* flag = g_flag_o + (rb2 >> 1) * 16 + g2_k(lane & 15);
        uint32_t ready = MODE == 0 ? 0u : ~0u;
        unsigned long long seq = G2_SEQ >> 8;
#pragma unroll 1
        for (int kb = 2; kb < 16; kb++, seq >>= 4) {
          uint32_t so = bars + (seq & 7) * 8, dst = sb + g2_a(seq & 7, hsel) + rank * 8192;
          const uint32_t ph = (uint32_t)seq >> 3 & 1;
          const __nv_bfloat16* src = osrc + rank * 4096 + (uint32_t)g2_k(kb) * 16384;
          asm volatile("" : "+r"(so), "+r"(dst), "+l"(src));
          if (!(ready >> kb & 1)) {
#pragma unroll 1
            for (int n = 0; n < SPIN_LIMIT && !(ready >> kb & 1); n++)
              ready = __ballot_sync(0xffffffffu, ld_acquire(flag) == epoch);
            fence_async_all();
          }
          if (kb == 2) PROF(21);
          if (MODE == 0 && kb == G2_KB4 && rank == 1) mbar_wait(bars + 8 * BAR_TAB, 0);
          mbar_wait(so + 8 * BAR_EMPTY2, ph);
          if (elect_one()) {
            asm volatile(
                "cp.async.bulk.shared::cluster.global.mbarrier::complete_tx::bytes.multicast::cluster [%0], [%1], %2, [%3], %4;\n"
                ::"r"(dst), "l"(src), "r"(8192), "r"(so + 8 * BAR_FULL2), "h"((uint16_t)3) : "memory");
          }
          __syncwarp();
        }
      }
    }
    cluster_sync_all();
    PROF_DUMP();
  } else {
    asm volatile("barrier.cluster.arrive.relaxed.aligned;\n" ::: "memory");
    asm volatile("setmaxnreg.inc.sync.aligned.u32 %0;\n" :: "n"(REG_MATH));
    if (halo_cta || MODE == 2) asm volatile("barrier.cluster.wait.aligned;\n" ::: "memory");
    if (warp == 0) PROF2(26);
    const int wg = warp >> 2;
    const int wtid = tid & 127;
    const bool signaller = (wtid == 0) || (wtid == 32);
    const uint32_t rbars = mapa(bars, wtid >> 5 & 1);

    if (halo_cta) {
      const uint32_t epoch = ld_relaxed(g_flag_o + 16 + blockIdx.x * 4) + 1;
      float acc0[64], acc1[64];
      int s = wg, ph = 0;
#pragma unroll 1
      for (int kb = 0; kb < 16; kb++) {
        mbar_wait(bars + 8 * (BAR_FULLB + s), ph);
        const uint32_t st = sb + s * STGH;
        const uint64_t da = mkdesc(st, 16, 1024, 1);
        const uint64_t db = mkdesc(st + 8192, 8192, 1024, 1);
        wg_fence();
#pragma unroll
        for (int kk = 0; kk < 4; kk++) {
          wgmma_n128(acc0, da + 2 * kk, db + 128 * kk, kb + kk);
          wgmma_n128(acc1, da + 2 * kk, db + 1024 + 128 * kk, kb + kk);
        }
        wg_commit();
        wg_wait<0>();
        if (kb == 15) PROF(37);
        if (wtid < 2) mbar_arrive(bars + 8 * (BAR_EMPTYB + s));
        if ((s += 2) >= NS1B) { s -= NS1B; ph ^= 1; }
      }
      fence_regs(acc0);
      fence_regs(acc1);
      if ((warp & 3) != 3) {
        auto put = [&](const float (&acc)[64], int hp0) {
#pragma unroll
          for (int n = 0; n < 4; n++) {
            uint32_t x[8];
#pragma unroll
            for (int c = 0; c < 8; c++) {
              x[c] = pack_bf16(acc[32 * (n >> 1) + 4 * c + 2 * (n & 1)], acc[32 * (n >> 1) + 4 * c + 2 * (n & 1) + 1]);
              if (wg) x[c] = movm(x[c]);
            }
            uint4* dst = g_halo + (((n & 1) * 4 + (warp & 3) + 1) * 16 + blockIdx.x * 4 + hp0 + (n >> 1)) * 192 + wg * 96 + lane;
            st_b128(dst, x[0], x[1], x[2], epoch);
            st_b128(dst + 32, x[3], x[4], x[5], epoch);
            st_b128(dst + 64, x[6], x[7], 0, epoch);
          }
        };
        put(acc0, 0);
        put(acc1, 2);
      }
      PROF(36);
      cluster_sync_all();
      return;
    }

    float acc[64];
    const uint32_t g2rel = wtid ? mapa(bars, rank) + 8 * BAR_EMPTY2B : mapa(bars, wg) + 8 * BAR_EMPTY2;
    uint32_t g2a = (uint32_t)mkdesc(sb + wg * 8192, 16, 0, 0), g2b = (uint32_t)mkdesc(sb, 8192, 0, 0);
    auto g2_block = [&](bool first, int s, int ph) {
      mbar_wait(bars + 8 * (BAR_FULL2 + s), ph);
      const uint32_t da = g2a + (g2_a(s, hsel) >> 4), db = g2b + (g2_b(s, rank) >> 4), dc = db + (g2_bk(s) >> 4);
      wg_fence();
      if (first) wgmma_n128z(acc, da, db);
      else wgmma_n128a(acc, da, db);
      wgmma_n128a(acc, da + 2, db + 128);
      wgmma_n128a(acc, da + 4, dc);
      wgmma_n128a(acc, da + 6, dc + 128);
      wg_commit();
    };
    if (MODE != 2) {
    uint32_t a1[2][4], sc[2];
    C2 t[2];
    {
      float acc0[96], acc1[96];
      int sa = 0, pha = 0;
      uint64_t db0 = mkdesc(sb + OFF_1B, 4096, 1024, 1);
      const uint64_t da0 = mkdesc(sb + wg * 16384, 16, 2048, 1);
      const bool sigb = wtid == 64;
      uint32_t rela = 0;
#pragma unroll 1
      for (int r = 0; r < 3; r++) {
#pragma unroll
        for (int i = 0; i < 2 * NS1B; i++) {
          const uint64_t da = da0 + sa * (STG1A >> 4) + (i & 1) * 4, db = db0 + (i % NS1B) * (STG1B >> 4);
          if (i || r) {
            if (!(i & 1)) mbar_wait(bars + 8 * (BAR_FULLA + sa), pha);
            mbar_wait(bars + 8 * (BAR_FULLB + i % NS1B), i / NS1B);
          } else {
            asm volatile("cp.async.wait_group 0;\n" ::: "memory");
            fence_async_smem();
            nb_sync(NB_FIRST, 256);
            PROF(0 + wg);
          }
          wg_fence();
          wgmma_n192(acc0, da + 64, db, i ? 1 : r);
          wgmma_n192(acc1, da, db, i ? 1 : r);
          wgmma_n192(acc0, da + 66, db + 128, 1);
          wgmma_n192(acc1, da + 2, db + 128, 1);
          wg_commit();
          wg_wait<1>();
          if (i || r) {
            if (sigb) mbar_arrive(bars + 8 * (BAR_EMPTYB + (i + NS1B - 1) % NS1B));
            if (!(i & 1) && signaller) mbar_arrive_cluster(rela);
          } else {
            asm volatile("barrier.cluster.wait.aligned;\n" ::: "memory");
          }
          if (i & 1) {
            rela = rbars + 8 * (BAR_EMPTYA + sa);
            if (++sa == NS1A) { sa = 0; pha ^= 1; }
          }
        }
        db0 += p.zero;
      }
      const int lr = lane & 7, lm = lane >> 3;
      const bool le0 = 2 * (lane & 3) <= (lane >> 2), le1 = 2 * (lane & 3) + 1 <= (lane >> 2);
      const uint32_t maskLE = (le0 ? 0x0000FFFFu : 0u) | (le1 ? 0xFFFF0000u : 0u);
      uint32_t q[4][8], k[5][8], vt[5][8];
      {
        static_assert(15 % NS1A == 0 && 30 % NS1B == 0, "slots of the last k blocks");
        asm volatile("ld.volatile.global.v4.u32 {%0,%1,%2,%3}, [%4];\n"
                     : "=r"(t[0].r), "=r"(t[1].r), "=r"(t[0].i), "=r"(t[1].i) : "l"(g_tab + 1536 + wtid * 4) : "memory");
        mbar_wait(bars + 8 * BAR_FULLA, 1);
        mbar_wait(bars + 8 * BAR_FULLB, 0);
        mbar_wait(bars + 8 * (BAR_FULLB + 1), 0);
        mbar_wait(bars + 8 * (BAR_EMPTYA + 1), 0);
        const uint64_t da = mkdesc(sb + wg * 16384, 16, 2048, 1);
        const uint64_t db = mkdesc(sb + OFF_1B, 4096, 1024, 1);
        wg_fence();
#pragma unroll
        for (int i = 0; i < 4; i++) wgmma_n192(acc0, da + 64 + 2 * i, db + (i >> 1) * (STG1B >> 4) + (i & 1) * 128, 1);
        wg_commit();
#pragma unroll
        for (int i = 0; i < 2; i++) wgmma_n192(acc1, da + 2 * i, db + (i >> 1) * (STG1B >> 4) + (i & 1) * 128, 1);
        wg_commit();
        wg_wait<1>();
        fence_regs(acc0);
        PROFA(45, 0);
        attn_pack<8, 1, false>(acc0, k[4]);
        attn_pack<16, 1, true>(acc0, vt[4]);
        const uint32_t kh = sb + (warp == 7 ? OFF_OP + 7 * 4096 : OFF_KH + (warp + 1) * 2048) + lane * 16;
        sts128(kh, k[4][0], k[4][1], k[4][2], k[4][3]);
        sts128(kh + 512, k[4][4], k[4][5], k[4][6], k[4][7]);
#pragma unroll
        for (int i = 0; i < 4; i++) sts64(kh - lane * 8 + 1024 + 256 * i, vt[4][2 * i], vt[4][2 * i + 1]);
#pragma unroll
        for (int i = 2; i < 4; i++) wgmma_n192(acc1, da + 2 * i, db + (i >> 1) * (STG1B >> 4) + (i & 1) * 128, 1);
        wg_commit();
        attn_pack<0, 0, false>(acc0, q[1]);
        attn_pack<0, 1, false>(acc0, q[3]);
        attn_pack<8, 0, false>(acc0, k[2]);
        attn_pack<16, 0, true>(acc0, vt[2]);
        uint32_t z = p.zero;
#pragma unroll
        for (int i = 0; i < 8; i++) z &= q[1][i] & q[3][i];
#pragma unroll
        for (int i = 0; i < 8; i += 2) z &= k[2][i] & k[2][i + 1];
        __syncwarp();
        if (lane == 0) mbar_arrive(bars + 8 * BAR_STG + z);
        wg_wait<0>();
        fence_regs(acc1);
        if (MODE == 0) nb_arrive(NB_G1END, 288);
      }
      PROF(2 + wg);
      mbar_wait(bars + 8 * (warp == 0 ? BAR_HALO : BAR_STG), 0);
      {
        const uint32_t kh = sb + OFF_KH + warp * 2048 + lane * 16;
#pragma unroll
        for (int i = 0; i < 2; i++) {
          const uint4 t = lds128(kh + 512 * i);
          k[0][4 * i] = t.x; k[0][4 * i + 1] = t.y; k[0][4 * i + 2] = t.z; k[0][4 * i + 3] = t.w;
        }
#pragma unroll
        for (int i = 0; i < 4; i++) {
          const uint2 t = lds64(kh - lane * 8 + 1024 + 256 * i);
          vt[0][2 * i] = t.x; vt[0][2 * i + 1] = t.y;
        }
      }
      attn_pack<0, 0, false>(acc1, q[0]);
      attn_pack<0, 1, false>(acc1, q[2]);
      attn_pack<8, 0, false>(acc1, k[1]);
      attn_pack<8, 1, false>(acc1, k[3]);
      {
        float x[8][2];
        uint32_t pp[8];
        const bool first = warp == 0 && gidx == 0;
#pragma unroll
        for (int hd = 0; hd < 2; hd++) {
#pragma unroll
          for (int j = 0; j < 4; j += 2) {
            float s0[4], s1[4], s2[4];
            attn_qk(s2, q[j], q[j + 1], k[j + 2], 4 * hd);
            attn_qk(s1, q[j], q[j + 1], k[j + 1], 4 * hd);
            attn_qk(s0, q[j], q[j + 1], k[j], 4 * hd);
            if (j == 0 && first) s0[0] = s0[1] = -1e9f / 0.17677669529663687f;
            x[2 * j + hd][0] = le0 ? s1[0] : s0[0];
            x[2 * j + hd][1] = le1 ? s1[1] : s0[1];
            x[2 * j + 2 + hd][0] = le0 ? s2[2] : s1[2];
            x[2 * j + 2 + hd][1] = le1 ? s2[3] : s1[3];
          }
        }
        PROFA(40, __float_as_uint(x[1][0] + x[7][1]));
        attn_pack<16, 0, true>(acc1, vt[1]);
        attn_pack<16, 1, true>(acc1, vt[3]);
        quad_softmax<8>(x, pp);
        PROFA(41, pp[1] + pp[7]);
        mbar_wait(bars + 8 * BAR_X, 0);
        ldsm4(a1[0], sb + OFF_T32 + (warp & 3) * 1024 + lane * 16);
        ldsm4(a1[1], sb + OFF_T32 + 512 + (warp & 3) * 1024 + lane * 16);
        {
          const uint32_t ex = sb + OFF_EX + wg * 16 + (warp & 2) * 2;
#pragma unroll
          for (int i = 0; i < 2; i++) sc[i] = min(max(381 - (int)lds32(ex + 8 * i) - (int)lds32(ex + 32 + 8 * i), 1), 254) * 0x00800080u;
        }
        const uint32_t obase = sb + OFF_OP + (warp * 32 + lr) * 128;
#pragma unroll
        for (int n = 0; n < 8; n++) {
          attn_pv(obase + (n >> 1) * 1024 + (((4 * (n & 1) + lm) ^ lr) << 4), vt[n >> 1], vt[(n >> 1) + 1], 4 * (n & 1), pp[n],
                  maskLE);
        }
      }
      PROFA(42, 0);
    }

    {
      const int w = warp & 3;
      const int lr = lane & 7, lm = lane >> 3;
      const uint32_t xb = sb + OFF_X + wg * 4 * XT;
      auto uo = [](int c) { return (c & 1) * 2 * XT + (c >> 1) * 2048; };
      const uint64_t dc2 = mkdesc(sb + OFF_T16, 512, 128, 0), dc3 = mkdesc(sb + OFF_T16, 128, 512, 0);
      const uint64_t dc4 = mkdesc(sb + OFF_T32, 128, 256, 0);
      const uint64_t dx = mkdesc(xb, 4096, 512, 2), dz = mkdesc(xb, 4096, 256, 3);
      const uint32_t zs = xb + (w * 16 + (lm & 1) * 8 + lr) * 32 + (((lm >> 1) ^ (lr >> 2)) << 4);
      const uint32_t ys = xb + w * 4096 + (lm >> 1) * 256 + ((lr * 32 + (((lm & 1) ^ (lr >> 2)) << 4)) ^ (rank << 6) ^ ((w & 2) << 4));
      const bool own = (w & 1) == rank;
      const uint32_t ybar = mapa(bars, own ? rank ^ 1 : rank) + 8 * BAR_Y;
      uint32_t d[2][32], pa[2][4][2][4], e[4][4][8], ya[2][2][2][4], v[2][2][8];
      C2 s1[2][2][2];
      float o[2][16];
      auto rows = [&](int c) {
        fft_rows(d[c & 1], a1, dx + (uo(c) >> 4));
        wg_commit();
      };
      auto cols = [&](int c) {
        const int s = c & 1;
        fence_regs(d[s]);
#pragma unroll
        for (int i = 0; i < 16; i++) {
          const C2 z = crot(C2{d[s][2 * i], d[s][2 * i + 1]}, t[i & 1]);
          pa[s][i >> 2][i & 1][(i >> 1) & 1] = z.r;
          pa[s][i >> 2][i & 1][2 + ((i >> 1) & 1)] = z.i;
        }
        wg_fence();
#pragma unroll
        for (int i = 0; i < 4; i++) fft_cols<0>(e[c][i], pa[s][i], dc2);
        wg_commit();
      };
      auto prod = [&](int c, int n) {
        const int s = c & 1;
        fence_regs(e[c][2 * n]);
        fence_regs(e[c][2 * n + 1]);
#pragma unroll
        for (int j = 0; j < 2; j++) {
          const C2 u0 = cget(e[s][2 * n], j, 0), u1 = cget(e[s][2 * n], j, 1);
          const C2 h0 = cget(e[s][2 * n + 1], j, 0), h1 = cget(e[s][2 * n + 1], j, 1);
          C2 y0, y1;
          if (c < 2) {
            y0 = cmul(h0, u0);
            s1[s][n][j] = cfma(h0, u1, cmul(h1, u0));
            y1 = C2{hadd2(s1[s][n][j].r, y0.i), hadd2(s1[s][n][j].i, hneg2(y0.r))};
          } else {
            const C2 u2 = cget(e[c][2 * n], j, 0), u3 = cget(e[c][2 * n], j, 1);
            const C2 h2 = cget(e[c][2 * n + 1], j, 0), h3 = cget(e[c][2 * n + 1], j, 1);
            const C2 s2 = cfma(h0, u2, cfma(h2, u0, cmul(h1, u1)));
            y0 = C2{hadd2(s2.r, s1[s][n][j].i), hadd2(s2.i, hneg2(s1[s][n][j].r))};
            y1 = cfma(h0, u3, cfma(h1, u2, cfma(h2, u1, cfma(h3, u0, C2{s2.i, hneg2(s2.r)}))));
          }
          ya[s][n][j][0] = y0.r;
          ya[s][n][j][1] = y1.r;
          ya[s][n][j][2] = y0.i;
          ya[s][n][j][3] = y1.i;
        }
      };
      auto icols = [&](int c) {
        wg_fence();
        fft_cols<1>(v[c & 1][0], ya[c & 1][0], dc3);
        fft_cols<1>(v[c & 1][1], ya[c & 1][1], dc3);
        wg_commit();
      };
      auto stage = [&](int c) {
        const int s = c & 1;
        fence_regs(v[s][0]);
        fence_regs(v[s][1]);
#pragma unroll
        for (int b = 0; b < 4; b++) {
          const C2 x0 = cget(v[s][b >> 1], 0, b & 1), x1 = cget(v[s][b >> 1], 1, b & 1);
          const C2 z0 = crot(C2{x0.i, x0.r}, t[0]), z1 = crot(C2{x1.i, x1.r}, t[1]);
          stsm4(zs + uo(c) + b * 4096, z0.i, z0.r, z1.i, z1.r);
        }
      };
      auto back = [&](int c) {
        fft_back(o[c & 1], dz + (uo(c) >> 4), dc4);
        wg_commit();
      };
      auto out = [&](int c) {
        float (&r)[16] = o[c & 1];
        fence_regs(r);
#pragma unroll
        for (int i = 0; i < 16; i += 8)
          stsm4t(ys + uo(c) + 64 * i, bmul2(pack_bf16(r[i], r[i + 1]), sc[c & 1]), bmul2(pack_bf16(r[i + 2], r[i + 3]), sc[c & 1]),
                 bmul2(pack_bf16(r[i + 4], r[i + 5]), sc[c & 1]), bmul2(pack_bf16(r[i + 6], r[i + 7]), sc[c & 1]));
      };
      auto signal = [&](int yb, int land) {
        __syncwarp();
        if (lane == 0) {
          mbar_arrive_cluster(ybar + 8 * yb);
          if (own && land >= 0) mbar_arrive(bars + 8 * (BAR_LAND + land));
        }
      };
      wg_fence();
      rows(0);
      rows(1);
      fence_async_smem();
      nb_arrive(NB_OREADY, 288);
      PROF(34 + wg);
      wg_wait<1>();
      cols(0);
      wg_wait<1>();
      cols(1);
      rows(2);
      nb_sync(NB_CONV + wg, 128);
      wg_wait<2>();
      prod(0, 0);
      prod(0, 1);
      icols(0);
      wg_wait<2>();
      prod(1, 0);
      prod(1, 1);
      icols(1);
      PROF3(40 + 10 * wg);
      wg_wait<1>();
      stage(0);
      wg_wait<0>();
      stage(1);
      fence_async_smem();
      cols(2);
      PROF3(41 + 10 * wg);
      nb_sync(NB_CONV + wg, 128);
      back(0);
      back(1);
      wg_wait<2>();
      prod(2, 0);
      wg_fence();
      rows(3);
      wg_wait<1>();
      out(0);
      out(1);
      signal(wg, 0);
      PROF3(42 + 10 * wg);
      prod(2, 1);
      icols(2);
      wg_wait<1>();
      cols(3);
      PROF3(43 + 10 * wg);
      wg_wait<1>();
      stage(2);
      fence_async_smem();
      wg_wait<0>();
      prod(3, 0);
      nb_sync(NB_CONV + wg, 128);
      wg_fence();
      back(2);
      prod(3, 1);
      icols(3);
      PROF3(44 + 10 * wg);
      wg_wait<1>();
      out(2);
      signal(2, -1);
      wg_wait<0>();
      stage(3);
      PROF3(45 + 10 * wg);
      fence_async_smem();
      nb_sync(NB_CONV + wg, 128);
      wg_fence();
      back(3);
      constexpr int G = MODE == 0 && EARLY;
      if (MODE == 0) mbar_wait(bars + 8 * (BAR_EMPTY2 + 4), 0);
      if (G) g2_block(true, 0, 0);
      wg_wait<G>();
      if (lane == 0) mbar_arrive_cluster(mapa(bars, 1) + 8 * BAR_TAB);
      out(3);
      signal(3, 1);
      PROF(6 + wg);
    }
    }

    if (MODE != 1) {
      if (MODE == 2 || !EARLY) g2_block(true, 0, 0);
      const int lr = lane & 7, lm = lane >> 3;
      const uint32_t wb = sb + g2_a(1, 0) + warp * 2048;
      const int orow = (rb2 & 7) * 128 + warp * 16;
      uint4* og = reinterpret_cast<uint4*>(p.out + (size_t)(2 * (orow + lm) + (rb2 >> 3)) * (2 * DM) + DM + cb2 * 128 + lr * 8);
      uint32_t wst = wb + (lr + 8 * (lm & 1)) * 128, wsx = ((lm >> 1) ^ lr) << 4, wld = wb + lm * 128, wlx = (lr ^ lm) << 4;
      asm volatile("" : "+l"(og), "+r"(wst), "+r"(wsx), "+r"(wld), "+r"(wlx));
      static_assert(ENDG == NS2 && (G2SEQ >> 4 & 0xfffff) == (G2SEQ >> 24 & 0xfffff) && (G2SEQ >> 4 & 0xfffff) == G2SEQ >> 44, "rounds");
#pragma unroll 1
      for (int r = 0; r < 3; r++) {
        const bool hold = r == 2 && wg != LEADWG;
        const uint32_t rel0 = g2rel + (r ? 8 * (G2SEQ >> 20 & 7) : 0);
        if (hold) {
          wg_wait<0>();
          if (signaller) mbar_arrive_cluster(rel0);
          nb_sync(NB_LEAD, 256);
        }
#pragma unroll
        for (int i = 1; i <= NS2; i++) {
          const int s = G2SEQ >> (4 * i) & 7;
          g2_block(false, s, (r & 1) ^ (s == 0));
          if (warp == LEADWG * 4) PROF2(40 + 5 * r + i);
          if (i == 1 ? !hold : r < 2) {
            wg_wait<1>();
            if (signaller) mbar_arrive_cluster(i == 1 ? rel0 : g2rel + 8 * (G2SEQ >> (4 * i - 4) & 7));
          }
        }
        if (r == 0) PROF(8 + wg);
        g2a += p.zero;
        g2b += p.zero;
      }
      if (wg == LEADWG) nb_arrive(NB_LEAD, 256);
      asm volatile("barrier.cluster.arrive.relaxed.aligned;\n" ::: "memory");
      wg_wait<0>();
      fence_regs(acc);
      PROF(10 + wg);
#pragma unroll
      for (int h = 0; h < 2; h++) {
        const uint32_t b = h * (g2_a(3, 0) - g2_a(1, 0));
#pragma unroll
        for (int j = 8 * h; j < 8 * h + 8; j += 2)
          stsm4(wst + b + (wsx ^ ((j & 7) << 4)), pack_bf16(acc[4 * j], acc[4 * j + 1]),
                pack_bf16(acc[4 * j + 2], acc[4 * j + 3]), pack_bf16(acc[4 * j + 4], acc[4 * j + 5]),
                pack_bf16(acc[4 * j + 6], acc[4 * j + 7]));
        if (OTMA == 2 || (OTMA == 1 && wg == LEADWG)) {
          fence_async_smem();
          __syncwarp();
          if (elect_one()) {
            tma_store_3d(&tmOb, wb + b, DM + cb2 * 128 + h * 64, rb2 >> 3, orow);
            bulk_commit();
          }
        } else {
          __syncwarp();
          uint4 v[4];
#pragma unroll
          for (int i = 0; i < 4; i++) v[i] = lds128(wld + b + i * 512 + (wlx ^ ((i & 1) << 6)));
#pragma unroll
          for (int i = 0; i < 4; i++) og[(size_t)i * 8 * (2 * DM / 8) + h * 8] = v[i];
        }
      }
      PROF(12 + wg);
      if (OTMA) bulk_wait0();
    } else {
      asm volatile("barrier.cluster.arrive.relaxed.aligned;\n" ::: "memory");
    }
    asm volatile("barrier.cluster.wait.aligned;\n" ::: "memory");
  }
}

typedef CUresult (*EncodeFn)(CUtensorMap*, CUtensorMapDataType, cuuint32_t, void*, const cuuint64_t*, const cuuint64_t*,
                             const cuuint32_t*, const cuuint32_t*, CUtensorMapInterleave, CUtensorMapSwizzle,
                             CUtensorMapL2promotion, CUtensorMapFloatOOBfill);

void make_map(EncodeFn enc, CUtensorMap* tm, const void* base, int rank, const cuuint64_t* dims, const cuuint64_t* strides,
              const cuuint32_t* box, CUtensorMapSwizzle swz) {
  cuuint32_t es[5] = {1, 1, 1, 1, 1};
  enc(tm, CU_TENSOR_MAP_DATA_TYPE_BFLOAT16, rank, const_cast<void*>(base), dims, strides, box, es,
      CU_TENSOR_MAP_INTERLEAVE_NONE, swz, CU_TENSOR_MAP_L2_PROMOTION_L2_256B, CU_TENSOR_MAP_FLOAT_OOB_FILL_NONE);
}

}

extern "C" void kernel_launch(void* const* d_in, const int* in_sizes, int n_in, void* d_out, int out_size) {
  static EncodeFn enc = nullptr;
  static bool coresident = true;
  if (!enc) {
    void* fn = nullptr;
    cudaDriverEntryPointQueryResult qr;
    cudaGetDriverEntryPoint("cuTensorMapEncodeTiled", &fn, cudaEnableDefault, &qr);
    enc = (EncodeFn)fn;
    cudaFuncSetAttribute(fused_kernel<0>, cudaFuncAttributeMaxDynamicSharedMemorySize, SMEM_BYTES);
    cudaFuncSetAttribute(fused_kernel<1>, cudaFuncAttributeMaxDynamicSharedMemorySize, SMEM_BYTES);
    cudaFuncSetAttribute(fused_kernel<2>, cudaFuncAttributeMaxDynamicSharedMemorySize, SMEM_BYTES);
    cudaLaunchConfig_t cfg = {};
    cfg.gridDim = dim3(NCTA);
    cfg.blockDim = dim3(NTHREADS);
    cfg.dynamicSmemBytes = SMEM_BYTES;
    cudaLaunchAttribute at;
    at.id = cudaLaunchAttributeClusterDimension;
    at.val.clusterDim.x = 2;
    at.val.clusterDim.y = 1;
    at.val.clusterDim.z = 1;
    cfg.attrs = &at;
    cfg.numAttrs = 1;
    int nclusters = 0;
    if (cudaOccupancyMaxActiveClusters(&nclusters, fused_kernel<0>, &cfg) == cudaSuccess) coresident = nclusters >= NCTA / 2;
    (void)cudaGetLastError();
  }
  CUtensorMap tmX, tmW, tmWo, tmWp, tmQ, tmOb, tmXh, tmWh;
  {
    cuuint64_t dims[3] = {1024, 2, 1024};
    cuuint64_t str[2] = {2048, 4096};
    cuuint32_t box[3] = {64, 1, 128};
    make_map(enc, &tmX, d_in[6], 3, dims, str, box, CU_TENSOR_MAP_SWIZZLE_128B);
  }
  {
    cuuint64_t dims[3] = {1024, 1024, 3};
    cuuint64_t str[2] = {6144, 2048};
    cuuint32_t box[3] = {64, 32, 3};
    make_map(enc, &tmW, d_in[7], 3, dims, str, box, CU_TENSOR_MAP_SWIZZLE_128B);
  }
  {
    cuuint64_t dims[3] = {64, 1024, 16};
    cuuint64_t str[2] = {2048, 128};
    cuuint32_t box[3] = {64, 64, 2};
    cuuint32_t piece[3] = {64, 32, 1};
    make_map(enc, &tmWo, d_in[8], 3, dims, str, box, CU_TENSOR_MAP_SWIZZLE_128B);
    make_map(enc, &tmWp, d_in[8], 3, dims, str, piece, CU_TENSOR_MAP_SWIZZLE_128B);
  }
  {
    cuuint64_t dims[5] = {1024, 2, 2, 4, 128};
    cuuint64_t str[4] = {2048, 8 * 2048, 2 * 2048, 16 * 2048};
    cuuint32_t box[5] = {16, 2, 2, 4, 32};
    make_map(enc, &tmQ, d_in[0], 5, dims, str, box, CU_TENSOR_MAP_SWIZZLE_NONE);
  }
  {
    cuuint64_t dims[3] = {2048, 2, 1024};
    cuuint64_t str[2] = {4096, 8192};
    cuuint32_t box[3] = {64, 1, 16};
    make_map(enc, &tmOb, d_out, 3, dims, str, box, CU_TENSOR_MAP_SWIZZLE_128B);
  }
  {
    cuuint64_t dims[4] = {1024, 256, 2, 4};
    cuuint64_t str[3] = {4096, 2048, 256 * 4096};
    cuuint32_t box[4] = {64, 8, 2, 3};
    make_map(enc, &tmXh, d_in[6], 4, dims, str, box, CU_TENSOR_MAP_SWIZZLE_128B);
  }
  {
    cuuint64_t dims[3] = {64, 1024, 48};
    cuuint64_t str[2] = {6144, 128};
    cuuint32_t box[3] = {64, 64, 4};
    make_map(enc, &tmWh, d_in[7], 3, dims, str, box, CU_TENSOR_MAP_SWIZZLE_128B);
  }
  Params p;
  p.q = (const __nv_bfloat16*)d_in[0];
  p.k = (const __nv_bfloat16*)d_in[1];
  p.v = (const __nv_bfloat16*)d_in[2];
  p.shift_k = (const __nv_bfloat16*)d_in[3];
  p.ssm_k = (const __nv_bfloat16*)d_in[4];
  p.ssm_D = (const __nv_bfloat16*)d_in[5];
  p.x = (const __nv_bfloat16*)d_in[6];
  p.w = (const __nv_bfloat16*)d_in[7];
  p.wo = (const __nv_bfloat16*)d_in[8];
  p.out = (__nv_bfloat16*)d_out;
  p.zero = 0;
  if (coresident) {
    fused_kernel<0><<<NCTA, NTHREADS, SMEM_BYTES>>>(p, tmX, tmW, tmWo, tmWp, tmQ, tmOb, tmXh, tmWh);
  } else {
    fused_kernel<0><<<4, NTHREADS, SMEM_BYTES>>>(p, tmX, tmW, tmWo, tmWp, tmQ, tmOb, tmXh, tmWh);
    fused_kernel<1><<<NCTA, NTHREADS, SMEM_BYTES>>>(p, tmX, tmW, tmWo, tmWp, tmQ, tmOb, tmXh, tmWh);
    fused_kernel<2><<<NCTA, NTHREADS, SMEM_BYTES>>>(p, tmX, tmW, tmWo, tmWp, tmQ, tmOb, tmXh, tmWh);
  }
}
```

```cpp
#include <cuda_runtime.h>
#include <cuda.h>
#include <cuda_bf16.h>
#include <stdint.h>

namespace {

constexpr int SEQ = 2048;
constexpr int DM = 1024;
constexpr int NCTA = 132;
constexpr int NTHREADS = 384;

constexpr int STG1A = 32768;
constexpr int NS1A = 3;
constexpr int STG1B = 12288;
constexpr int NS1B = 5;
constexpr int OFF_1B = NS1A * STG1A;
constexpr int STG2 = 32768;
constexpr int NS2 = 5;
#define G2SEQ 0x0432104321043210ull
constexpr unsigned long long g2_seq() {
  unsigned long long r = G2SEQ;
  for (int kb = 0; kb < 16; kb++)
    for (int j = 0; j < kb; j++)
      if (((G2SEQ >> (4 * j)) & 7) == ((G2SEQ >> (4 * kb)) & 7)) r ^= 8ull << (4 * kb);
  return r;
}
constexpr unsigned long long G2_SEQ = g2_seq();
constexpr int g2_first4() {
  int kb = 0;
  while (((G2SEQ >> (4 * kb)) & 7) != 4) kb++;
  return kb;
}
constexpr int G2_KB4 = g2_first4();
#define POLL0 1500
#define BDEL 0
#define WOP 0
#define PSTEP 1250
#define FPACE 260
#define LEADWG 1
#define OTMA 1
#define EARLY 1
#define R3 1
#define FSL 50
#define JS 1
#define FPACE2 230
#define PFR 1
#define PF2 2
#define PF2X 1
#define PVS 1
#define ENDG 5
__device__ __forceinline__ uint32_t g2_a(int s, int hsel) { return (((0x97524 >> (4 * s)) & 15) ^ (s & 5 ? 0 : hsel)) << 14; }
constexpr int OFF_Q0 = 3 << 14, OFF_Q1 = 8 << 14;
constexpr int STGH = 40960;
constexpr int OFF_KH = 1 * STG2;
constexpr int OFF_OP = 2 * STG2;
constexpr int OFF_T32 = 5 * STG2 - 4096;
constexpr int OFF_X = 5 * STG2;
constexpr int XT = 8192;
__device__ __forceinline__ uint32_t g2_b(int s, int rank) {
  return s < 3 ? (s == 2 ? 6 : s) << 14 : OFF_X + (s - 3) * 2 * XT + (rank ^ 1) * 4096;
}
__device__ __forceinline__ uint32_t g2_bk(int s) { return s < 3 ? 4096 : 4 * XT; }
constexpr int OFF_BAR = OFF_X + 8 * XT;
constexpr int OFF_EX = OFF_BAR + 448;
constexpr int OFF_T16 = 230400;
constexpr int SMEM_BYTES = OFF_T16 + 2048;
static_assert(OFF_1B + NS1B * STG1B <= OFF_T32 && OFF_X % 1024 == 0, "layout");
static_assert(NS1B * STGH <= OFF_BAR && OFF_EX + 64 <= OFF_T16 && SMEM_BYTES <= 232448, "smem");

constexpr int BAR_FULLA = 0;
constexpr int BAR_EMPTYA = 3;
constexpr int BAR_FULLB = 6;
constexpr int BAR_EMPTYB = 11;
constexpr int BAR_FULL2 = 16;
constexpr int BAR_EMPTY2 = 21;
constexpr int BAR_EMPTY2B = 44;
constexpr int BAR_X = 26;
constexpr int BAR_LAND = 42;
constexpr int BAR_TAB = 28;
constexpr int BAR_U = 29;
constexpr int BAR_H = 30;
constexpr int BAR_STG = 31;
constexpr int BAR_Y = 32;
constexpr int BAR_XFREE = 38;
constexpr int BAR_HALO = 40;
constexpr int BAR_Q = 41;

constexpr int NB_LEAD = 2;
constexpr int NB_G1END = 3;
constexpr int NB_OREADY = 4;
constexpr int NB_CONV = 5;
constexpr int NB_HELP3 = 11;
constexpr int NB_FIRST = 13;

#define REG_MATH 224
#define REG_HELP 56
constexpr int SPIN_LIMIT = 1 << 20;

__device__ __align__(1024) __nv_bfloat16 g_o[SEQ * DM];
__device__ uint32_t g_flag_o[128];
__device__ uint4 g_halo[128 * 192];
__device__ __align__(128) const uint32_t g_tab[2048] = {
  0x2fd93000,0x2ea72f64,0x2c722da8,0x263e2a1f,0x2ea73000,0xa63e2a1f,0xafd9ada8,0xac72af64,0x2c723000,0xafd9aa1f,0x263eada8,0x2ea72f64,
  0x263e3000,0xac72af64,0x2ea72da8,0xafd9aa1f,0xa63e3000,0x2c72af64,0xaea72da8,0x2fd9aa1f,0xac723000,0x2fd9aa1f,0xa63eada8,0xaea72f64,
  0xaea73000,0x263e2a1f,0x2fd9ada8,0x2c72af64,0xafd93000,0xaea72f64,0xac722da8,0xa63e2a1f,0x263e0000,0x2c722a1f,0x2ea72da8,0x2fd92f64,
  0x2c720000,0x2fd92f64,0x263e2da8,0xaea7aa1f,0x2ea70000,0x263e2f64,0xafd9ada8,0x2c72aa1f,0x2fd90000,0xaea72a1f,0x2c72ada8,0xa63e2f64,
  0x2fd90000,0xaea7aa1f,0x2c722da8,0xa63eaf64,0x2ea70000,0x263eaf64,0xafd92da8,0x2c722a1f,0x2c720000,0x2fd9af64,0x263eada8,0xaea72a1f,
  0x263e0000,0x2c72aa1f,0x2ea7ada8,0x2fd9af64,0xafd93000,0xaea72f64,0xac722da8,0xa63e2a1f,0xaea73000,0x263e2a1f,0x2fd9ada8,0x2c72af64,
  0xac723000,0x2fd9aa1f,0xa63eada8,0xaea72f64,0xa63e3000,0x2c72af64,0xaea72da8,0x2fd9aa1f,0x263e3000,0xac72af64,0x2ea72da8,0xafd9aa1f,
  0x2c723000,0xafd9aa1f,0x263eada8,0x2ea72f64,0x2ea73000,0xa63e2a1f,0xafd9ada8,0xac72af64,0x2fd93000,0x2ea72f64,0x2c722da8,0x263e2a1f,
  0xa63e0000,0xac722a1f,0xaea72da8,0xafd92f64,0xac720000,0xafd92f64,0xa63e2da8,0x2ea7aa1f,0xaea70000,0xa63e2f64,0x2fd9ada8,0xac72aa1f,
  0xafd90000,0x2ea72a1f,0xac72ada8,0x263e2f64,0xafd90000,0x2ea7aa1f,0xac722da8,0x263eaf64,0xaea70000,0xa63eaf64,0x2fd92da8,0xac722a1f,
  0xac720000,0xafd9af64,0xa63eada8,0x2ea72a1f,0xa63e0000,0xac72aa1f,0xaea7ada8,0xafd9af64,0xa63e0000,0xac72aa1f,0xaea7ada8,0xafd9af64,
  0xac720000,0xafd9af64,0xa63eada8,0x2ea72a1f,0xaea70000,0xa63eaf64,0x2fd92da8,0xac722a1f,0xafd90000,0x2ea7aa1f,0xac722da8,0x263eaf64,
  0xafd90000,0x2ea72a1f,0xac72ada8,0x263e2f64,0xaea70000,0xa63e2f64,0x2fd9ada8,0xac72aa1f,0xac720000,0xafd92f64,0xa63e2da8,0x2ea7aa1f,
  0xa63e0000,0xac722a1f,0xaea72da8,0xafd92f64,0x2fd93000,0x2ea72f64,0x2c722da8,0x263e2a1f,0x2ea73000,0xa63e2a1f,0xafd9ada8,0xac72af64,
  0x2c723000,0xafd9aa1f,0x263eada8,0x2ea72f64,0x263e3000,0xac72af64,0x2ea72da8,0xafd9aa1f,0xa63e3000,0x2c72af64,0xaea72da8,0x2fd9aa1f,
  0xac723000,0x2fd9aa1f,0xa63eada8,0xaea72f64,0xaea73000,0x263e2a1f,0x2fd9ada8,0x2c72af64,0xafd93000,0xaea72f64,0xac722da8,0xa63e2a1f,
  0x263e0000,0x2c72aa1f,0x2ea7ada8,0x2fd9af64,0x2c720000,0x2fd9af64,0x263eada8,0xaea72a1f,0x2ea70000,0x263eaf64,0xafd92da8,0x2c722a1f,
  0x2fd90000,0xaea7aa1f,0x2c722da8,0xa63eaf64,0x2fd90000,0xaea72a1f,0x2c72ada8,0xa63e2f64,0x2ea70000,0x263e2f64,0xafd9ada8,0x2c72aa1f,
  0x2c720000,0x2fd92f64,0x263e2da8,0xaea7aa1f,0x263e0000,0x2c722a1f,0x2ea72da8,0x2fd92f64,0xafd93000,0xaea72f64,0xac722da8,0xa63e2a1f,
  0xaea73000,0x263e2a1f,0x2fd9ada8,0x2c72af64,0xac723000,0x2fd9aa1f,0xa63eada8,0xaea72f64,0xa63e3000,0x2c72af64,0xaea72da8,0x2fd9aa1f,
  0x263e3000,0xac72af64,0x2ea72da8,0xafd9aa1f,0x2c723000,0xafd9aa1f,0x263eada8,0x2ea72f64,0x2ea73000,0xa63e2a1f,0xafd9ada8,0xac72af64,
  0x2fd93000,0x2ea72f64,0x2c722da8,0x263e2a1f,0xa63e0000,0xac72aa1f,0xaea7ada8,0xafd9af64,0x2c720000,0x2fd92f64,0x263e2da8,0xaea7aa1f,
  0xaea70000,0xa63eaf64,0x2fd92da8,0xac722a1f,0x2fd90000,0xaea72a1f,0x2c72ada8,0xa63e2f64,0xafd90000,0x2ea72a1f,0xac72ada8,0x263e2f64,
  0x2ea70000,0x263eaf64,0xafd92da8,0x2c722a1f,0xac720000,0xafd92f64,0xa63e2da8,0x2ea7aa1f,0x263e0000,0x2c72aa1f,0x2ea7ada8,0x2fd9af64,
  0x2fd93000,0x2ea72f64,0x2c722da8,0x263e2a1f,0xaea7b000,0x263eaa1f,0x2fd92da8,0x2c722f64,0x2c723000,0xafd9aa1f,0x263eada8,0x2ea72f64,
  0xa63eb000,0x2c722f64,0xaea7ada8,0x2fd92a1f,0xa63e3000,0x2c72af64,0xaea72da8,0x2fd9aa1f,0x2c72b000,0xafd92a1f,0x263e2da8,0x2ea7af64,
  0xaea73000,0x263e2a1f,0x2fd9ada8,0x2c72af64,0x2fd9b000,0x2ea7af64,0x2c72ada8,0x263eaa1f,0x263e0000,0x2c72aa1f,0x2ea7ada8,0x2fd9af64,
  0xac720000,0xafd92f64,0xa63e2da8,0x2ea7aa1f,0x2ea70000,0x263eaf64,0xafd92da8,0x2c722a1f,0xafd90000,0x2ea72a1f,0xac72ada8,0x263e2f64,
  0x2fd90000,0xaea72a1f,0x2c72ada8,0xa63e2f64,0xaea70000,0xa63eaf64,0x2fd92da8,0xac722a1f,0x2c720000,0x2fd92f64,0x263e2da8,0xaea7aa1f,
  0xa63e0000,0xac72aa1f,0xaea7ada8,0xafd9af64,0xafd93000,0xaea72f64,0xac722da8,0xa63e2a1f,0x2ea7b000,0xa63eaa1f,0xafd92da8,0xac722f64,
  0xac723000,0x2fd9aa1f,0xa63eada8,0xaea72f64,0x263eb000,0xac722f64,0x2ea7ada8,0xafd92a1f,0x263e3000,0xac72af64,0x2ea72da8,0xafd9aa1f,
  0xac72b000,0x2fd92a1f,0xa63e2da8,0xaea7af64,0x2ea73000,0xa63e2a1f,0xafd9ada8,0xac72af64,0xafd9b000,0xaea7af64,0xac72ada8,0xa63eaa1f,
  0xafd9b000,0xaea7af64,0xac72ada8,0xa63eaa1f,0x2ea73000,0xa63e2a1f,0xafd9ada8,0xac72af64,0xac72b000,0x2fd92a1f,0xa63e2da8,0xaea7af64,
  0x263e3000,0xac72af64,0x2ea72da8,0xafd9aa1f,0x263eb000,0xac722f64,0x2ea7ada8,0xafd92a1f,0xac723000,0x2fd9aa1f,0xa63eada8,0xaea72f64,
  0x2ea7b000,0xa63eaa1f,0xafd92da8,0xac722f64,0xafd93000,0xaea72f64,0xac722da8,0xa63e2a1f,0xa63e0000,0xac72aa1f,0xaea7ada8,0xafd9af64,
  0x2c720000,0x2fd92f64,0x263e2da8,0xaea7aa1f,0xaea70000,0xa63eaf64,0x2fd92da8,0xac722a1f,0x2fd90000,0xaea72a1f,0x2c72ada8,0xa63e2f64,
  0xafd90000,0x2ea72a1f,0xac72ada8,0x263e2f64,0x2ea70000,0x263eaf64,0xafd92da8,0x2c722a1f,0xac720000,0xafd92f64,0xa63e2da8,0x2ea7aa1f,
  0x263e0000,0x2c72aa1f,0x2ea7ada8,0x2fd9af64,0x2fd9b000,0x2ea7af64,0x2c72ada8,0x263eaa1f,0xaea73000,0x263e2a1f,0x2fd9ada8,0x2c72af64,
  0x2c72b000,0xafd92a1f,0x263e2da8,0x2ea7af64,0xa63e3000,0x2c72af64,0xaea72da8,0x2fd9aa1f,0xa63eb000,0x2c722f64,0xaea7ada8,0x2fd92a1f,
  0x2c723000,0xafd9aa1f,0x263eada8,0x2ea72f64,0xaea7b000,0x263eaa1f,0x2fd92da8,0x2c722f64,0x2fd93000,0x2ea72f64,0x2c722da8,0x263e2a1f,
  0x263e0000,0x2c72aa1f,0x2ea7ada8,0x2fd9af64,0xac720000,0xafd92f64,0xa63e2da8,0x2ea7aa1f,0x2ea70000,0x263eaf64,0xafd92da8,0x2c722a1f,
  0xafd90000,0x2ea72a1f,0xac72ada8,0x263e2f64,0x2fd90000,0xaea72a1f,0x2c72ada8,0xa63e2f64,0xaea70000,0xa63eaf64,0x2fd92da8,0xac722a1f,
  0x2c720000,0x2fd92f64,0x263e2da8,0xaea7aa1f,0xa63e0000,0xac72aa1f,0xaea7ada8,0xafd9af64,0x316c2fbd,0x343e32f7,0x35bc34ff,0x372c3676,
  0x371532c6,0x3a81392e,0x3bef3b71,0x3b7c3bf2,0x397034cf,0x3bfc3b6c,0x38b23b04,0xb40e31e8,0x3ae13631,0x39e73bf5,0xb6e83219,0xbbe8bb13,
  0x3bc23785,0x30be3aa9,0xbbfdb911,0x2a16b9aa,0x3bfe3865,0xb80f37a6,0xb82abc00,0x3bfd376f,0x3b9238fd,0xbb7f2311,0x3805b929,0x31223bde,
  0x3a85398b,0xbb96b742,0x3bff319e,0xbbb82f8b,0xbbe2bbf1,0xbbb7bbcf,0xbb78bb9a,0xbb27bb52,0xbb2cbbd2,0xb8a8ba19,0xb029b5df,0x35a52f59,
  0xb9dfbba1,0x2ba7b5f7,0x3a7a37b2,0x3bbd3bdd,0xb815bb60,0x39662e91,0x3b373bda,0xb0d7377a,0xb3d3bb10,0x3be9386f,0x2a7a3a31,0xbbfeb9a6,
  0x294dbab0,0x3ae53b07,0xbad51fdb,0xab43bb16,0x352fba41,0x35993c00,0xbaebba1d,0x3be531cf,0x38a3b9c5,0xb5173b21,0x2776bbe0,0x34323bf2,
  0x384537dd,0x38ea3899,0x39823937,0x3a0d39c9,0x39463a93,0x3340374e,0xb426a452,0xb979b7c8,0xbb45b924,0xbb32bc00,0xb371b902,0x38d63294,
  0xb08db9a1,0x3b3f379b,0x39583bd7,0xb8252dfb,0x3bea3a2d,0xb3ba3874,0xbb89bb0d,0x36d2b625,0xb6bb387f,0xb8d1bbf5,0x3be73602,0xb546391f,
  0xba00bb01,0x3bff35eb,0xba5c34db,0x3359bab6,0x3ac7b66b,0xb9413933,0x368dbabd,0xb0103bb3,0xbac4baf7,0xba50ba8c,0xb9cdba11,0xb93cb986,
  0x3a04388e,0x3bcb3b1e,0x3bba3c00,0x39d63afe,0x36af3a21,0xb6ffa17f,0xbbc8ba3d,0xba60bbd4,0xbbebb9af,0xb6c6bb0a,0x39f43263,0x3ad83bf7,
  0x30a6b916,0x3bc33aa5,0xb55e3790,0xbb3dbb63,0x3b423a9e,0xba642ec3,0xb0f0bb6a,0x3b8e3a25,0xb94a37bd,0x2884bb6f,0x38db3b9f,0xbbc9b85a,
  0xb840bb54,0x3a093a15,0xbb4cb850,0x3bef3457,0x3a893a4d,0x3af43ac1,0x3b4f3b24,0x3b983b76,0xbb94baba,0xbbe4bbf9,0xba58bb57,0xb699b8f8,
  0x3bfe3b18,0x394f3b5c,0xb109347b,0xbae8b884,0xbbc0bb68,0xa9b1b90c,0x3b8b387a,0x38bc3ba5,0x3ade3ba7,0xb8c1324b,0xb9f0bbf6,0x39eb9648,
  0xb96bbbd6,0x3bbf3487,0xb38939b3,0xb9f8bba3,0x370a3bf3,0xbb47b994,0x3bbc2d65,0xb8ad3889,0xb153bc00,0x37213b9c,0xb97dba90,0x3af138f3,
  0xb89eb8ee,0xb7e8b84a,0xb682b737,0xb50bb5c8,0x35233855,0xb13b2d33,0xb8e0b65f,0xbb4aba45,0xa8e8b764,0x39fc3648,0x3be63bae,0x380a3a9b,
  0xb3eb360e,0xbbfeba35,0xb552baa2,0x3a7334b7,0x381ab4ab,0x3a6f3bd8,0xb95d2e5f,0xb962bc00,0xb9e3327c,0xb402bbac,0x3bc6399d,0xb95434c3,
  0x3b2faf27,0xb6a439bc,0xb41abbf9,0x3a7e3a97,0xbbe3251b,0x3b2ab4f3,0xb9d23894,0x37f3ba49,0x3bce3bb5,0x3bf03be1,0x3bff3bfa,0x3bfb3bff,
  0x2c38b1b6,0x383a34e7,0x3aee39c0,0x3bff3bb2,0xbb81bbf8,0xb53ab999,0x38302ef5,0x3bed3ab3,0xb8cc9cb6,0xbb85bbab,0x2adeb86a,0x3bc5391b,
  0x38c73bf6,0xbadbb232,0xb6ddbba9,0x3b87361a,0x3b833201,0xb0743a39,0xba76bb5e,0x3b352dc9,0xac06bbb0,0x39743b59,0xbbeeb759,0x3aceb2ad,
  0xbbccb5d4,0x3bfb2d00,0xbb7a32de,0x3a54b7d2,0xb30fb44b,0xafefb185,0xa6adacce,0x2c9c25e4,0xbbfcbbdf,0xbacbbb9e,0xb7feb990,0xa81fb463,
  0xb58d2d97,0xbb90b9b8,0xbad1bbf4,0xb05bb85f,0x3a673c00,0xb5763493,0xbbfdbaac,0xb3a2ba29,0x3a6b2e2d,0x38203bd9,0xbb3ab49f,0xb56abb65,
  0xb581bbdc,0x3bec3907,0xb8b7363c,0xb6f4bbf8,0xbbfcb46f,0x39dab654,0xb0423b1b,0xb835bbd3,0xb3283b73,0xac6abbfa,0x35b13bd0,0xb8e5bafb,
  0x38ee3a0d,0xb84aba89,0x37373af4,0xb5c8bb4f,0x35df3a81,0x2f59bbef,0xb88e3b7c,0x3b1eb946,0x2d973ae8,0x39b8bb81,0xbbf4353a,0x385f3830,
  0xb2633b3f,0x3bf7b958,0xb60eb825,0xba353bc0,0xb7853b87,0x3aa9b3d3,0x3911bbe9,0xb9aa2a7a,0xb99d3bbf,0x34c33389,0x3bdcb9f8,0x3907bb83,
  0xbb013be5,0xb5eb394a,0x34db2884,0x3ab6b8db,0xbbd03bfb,0xbafb3b7a,0xb98b3a54,0xb74238a3,0x3a4db93c,0xbac1389e,0x3b24b7e8,0xbb763682,
  0x3b71b8a8,0xbbf23029,0x3a9335a5,0xb74eba04,0x3bf8b80a,0xb999b58d,0xaef53b90,0x3ab3bad1,0x3bd7b6c6,0xadfbb9f4,0xbb683ad8,0x390c33eb,
  0x3b10b56a,0x386fbbc2,0xba3130be,0xb9a63bfd,0x39b3b402,0x3ba3bbc6,0x3201b954,0xba393581,0x37bdb122,0x3b6fba00,0x3b9fbbff,0x385aba5c,
  0x32deac6a,0x37d2b5b1,0x39c5b8e5,0x3b21ba85,0x344b3b98,0xb185bbce,0x2cce3bf0,0x25e4bbff,0xbc003340,0x3afe3426,0xb855b979,0x2d333b94,
  0x34cfbbed,0xbb6c39df,0x3b042ba7,0xb1e8ba7a,0x3aa2a9b1,0x34b7bb8b,0xbc0038bc,0x349338cc,0xba2d3bfe,0x387430a6,0x3b0dbbc3,0xb625b55e,
  0xb63cb074,0xbbf83a76,0xb8653b35,0x37a6294d,0x3bf3bbc9,0x3994bb2f,0x2d65b6a4,0xb889341a,0xb19e3517,0x2f8b2776,0x366bb432,0x3933b840,
  0x3bb5b50b,0xbbe1330f,0x3bfaafef,0xbbff26ad,0xa4523bcb,0x37c8bbba,0xbaba39d6,0x3bf9b523,0xbba1305b,0x35f73970,0x37b2bbfc,0xbbdd38b2,
  0x387abbfe,0xbba53552,0x9cb63a73,0x3babba67,0x39162a16,0x3aa5bbea,0xb790b3ba,0xbb633b89,0xbb5e3bec,0xadc938b7,0x3ab0b6f4,0x3b07bbfe,
  0xaf27b359,0xb9bc370a,0xbbf93b47,0xba973bbc,0x3be0bb96,0x3bf2bbff,0x3b54bbb8,0x3a15bac7,0xafbd3bfb,0x32f7bbe2,0xb4ff3bb7,0x3676bb78,
  0x365fbbe4,0xba453a58,0x3bdfb699,0xbb9eac38,0xb9243bbd,0x3c00b6af,0xb902b6ff,0xb2943bc8,0x3aacbb85,0xba29aade,0xb6313bc5,0x3bf5b815,
  0xbba73b3d,0x324b381a,0x3bf6ba6f,0x9648b95d,0x3c00bae5,0x376fbad5,0xb87f2b43,0xbbf53b42,0xbbb03a7e,0xbb593bfc,0xb75939da,0x32ad3042,
  0x3abdba09,0x3bb3bb4c,0x3c00bbef,0x3b9cbbe3,0x3bf12c9c,0xbbcfb16c,0x3b9a343e,0xbb52b5bc,0xbb57b13b,0x38f838e0,0xb1b6bb4a,0xb4e73bfc,
  0x3a21340e,0x217fbb45,0xba3d3b32,0x3bd4b371,0xb86ab576,0xb91b3bfd,0x3b60b3a2,0x2e91bae1,0x34ab36d2,0x3bd8bade,0xae5fb8c1,0xbc0039f0,
  0x9fdbb80f,0xbb16382a,0xba9e3bfd,0x2ec336bb,0xb46f38ad,0x3654ac06,0x3b1bb974,0x3bd3bbee,0x3850b941,0x3457b68d,0xa51bb010,0xb4f33153,
  0xb7dd3b27,0x3899bac4,0xb9373a50,0x39c9b9cd,0x3990383a,0xb463baee,0xb2c63bff,0x392ebb2c,0x3b18ba60,0xbb5c28e8,0x347b39fc,0x3884bbe6,
  0xb219b966,0xbb133b37,0x39a130d7,0x379bbbeb,0xbbf63962,0xb2323a6b,0x3ba9b820,0x361abb3a,0xb6023a64,0x391fb0f0,0x3bd6bb8e,0x3487b9e3,
  0x3a41b835,0x3c00bb92,0x3a1dbb7f,0x31cfb805,0x3a90bb2a,0x38f3b9d2,0x35d4b7f3,0x2d00b328,0x3af7372c,0xba8cb845,0x3a1138ea,0xb986b982,
  0x39c0bacb,0xbbb237fe,0x3bd2a81f,0xba19b715,0xb764b8d6,0xb6483bfe,0x3baeb94f,0xba9bb109,0xbbda39e7,0x377a36e8,0x39afbbe8,0xbb0a308d,
  0xae2d39eb,0x3bd9b8c7,0x349fbadb,0xbb6536dd,0x3b6ab8d1,0x3a25bbe7,0xb27cb546,0xbbac396b,0x38fdbace,0xa311b52f,0xb9293599,0xbbde3aeb,
  0xb8943721,0xba49397d,0xbb733af1,0xbbfa3bcc,0xbbfb3bff,0xbbe23bf1,0xbbb73bcf,0xbb783b9a,0xbb7c3bf2,0xb9463a93,0xb340374e,0x3426a452,
  0xba603bd4,0xa8e83764,0x39fcb648,0x3be6bbae,0xb8bc3ba5,0x38cc9cb6,0x3b85bbab,0xaadeb86a,0xb56a3b65,0x3bc2b785,0x30bebaa9,0xbbfd3911,
  0xab433b16,0x3b42ba9e,0xba64aec3,0xb0f03b6a,0x33593ab6,0x370abbf3,0xbb473994,0x3bbcad65,0x37f33a49,0xb328bb73,0xac6a3bfa,0x35b1bbd0,
  0xac9c25e4,0xb16c2fbd,0xb43e32f7,0xb5bc34ff,0xb5a52f59,0xba04388e,0xbbcb3b1e,0xbbba3c00,0xb8d63294,0xbbfe3b18,0xb94f3b5c,0x3109347b,
  0xba7334b7,0xba673c00,0x35763493,0x3bfdbaac,0xbb87361a,0xb3d33b10,0x3be9b86f,0x2a7aba31,0xbbfd376f,0x36bb387f,0x38d1bbf5,0xbbe73602,
  0xbbc9385a,0x3b2f2f27,0xb6a4b9bc,0xb41a3bf9,0xbaf138f3,0x3bccb5d4,0xbbfb2d00,0x3b7a32de,0xbb273b52,0xbac43af7,0xba503a8c,0xb9cd3a11,
  0x3979b7c8,0x3b94baba,0x3be4bbf9,0x3a58bb57,0x380aba9b,0xb58dad97,0xbb9039b8,0xbad13bf4,0xbbc5391b,0xb8153b60,0x3966ae91,0x3b37bbda,
  0x2a1639aa,0x3beaba2d,0xb3bab874,0xbb893b0d,0x3b8eba25,0xb9e3b27c,0xb4023bac,0x3bc6b99d,0xb8adb889,0xac063bb0,0x3974bb59,0xbbee3759,
  0xb8e53afb,0x3a85b98b,0xbb963742,0x3bffb19e,0xb72c3676,0xb84537dd,0xb8ea3899,0xb9823937,0xb9d63afe,0xb5233855,0x313b2d33,0x38e0b65f,
  0x3ae8b884,0x3b81bbf8,0x353ab999,0xb8302ef5,0x33a2ba29,0xbae13631,0xb9e73bf5,0x36e83219,0xbbfe39a6,0x30a63916,0x3bc3baa5,0xb55eb790,
  0x3546391f,0x396bbbd6,0xbbbf3487,0x338939b3,0x3a7eba97,0xbbfc346f,0x39da3654,0xb042bb1b,0xba54b7d2,0x38a339c5,0xb517bb21,0x27763be0,
  0xb93c3986,0xb89e38ee,0xb7e8384a,0xb6823737,0x3699b8f8,0xac38b1b6,0xb83a34e7,0xbaee39c0,0xb05b385f,0x3970b4cf,0x3bfcbb6c,0x38b2bb04,
  0xb0d7b77a,0xbbeb39af,0xb6c63b0a,0x39f4b263,0x36d23625,0x3adebba7,0xb8c1b24b,0xb9f03bf6,0xb954b4c3,0xb5813bdc,0x3becb907,0xb8b7b63c,
  0x3ace32ad,0xb52fba41,0xb5993c00,0x3aebba1d,0xbbb8af8b,0x3ac7366b,0xb941b933,0x368d3abd,0xba0d39c9,0xba893a4d,0xbaf43ac1,0xbb4f3b24,
  0x3b4aba45,0x3bfcbbdf,0x3acbbb9e,0x37feb990,0xbbed3ab3,0xb9df3ba1,0x2ba735f7,0x3a7ab7b2,0x3be8bb13,0x308db9a1,0xbb3f379b,0xb9583bd7,
  0xbb3d3b63,0x381a34ab,0x3a6fbbd8,0xb95dae5f,0x39f8bba3,0xbb833201,0x30743a39,0x3a76bb5e,0xb8353bd3,0x3b92b8fd,0xbb7fa311,0x38053929,
  0x3432bbf2,0xb8403b54,0x3a09ba15,0xbb4c3850,0xb50b35c8,0xb30f344b,0xafef3185,0xa6ad2cce,0xbbff3bb2,0xbb2c3bd2,0xb8a83a19,0xb02935df,
  0xb40eb1e8,0xbb453924,0xbb323c00,0xb3713902,0x3ad8bbf7,0xb3ebb60e,0xbbfe3a35,0xb5523aa2,0x39eb1648,0x38c7bbf6,0xbadb3232,0xb6dd3ba9,
  0xb6f43bf8,0x3bfeb865,0xb80fb7a6,0xb82a3c00,0xbbe531cf,0x394a37bd,0xa884bb6f,0xb8db3b9f,0xb010bbb3,0xb1533c00,0x3721bb9c,0xb97d3a90,
  0xbb983b76,0xbbce3bb5,0xbbf03be1,0xbbff3bfa,0x281fb463,0xb71532c6,0xba81392e,0xbbef3b71,0x3bbdbbdd,0x36afba21,0xb6ff217f,0xbbc83a3d,
  0x38252dfb,0x3bc0bb68,0x29b1b90c,0xbb8b387a,0xb9623c00,0x3a6bae2d,0x3820bbd9,0xbb3a349f,0xbb352dc9,0x294d3ab0,0x3ae5bb07,0xbad59fdb,
  0x3122bbde,0xba003b01,0x3bffb5eb,0xba5cb4db,0x3befb457,0xbbe3a51b,0x3b2a34f3,0xb9d2b894,0x39c939cd,0xba4db93c,0x3ac1389e,0xbb24b7e8,
  0x3b1e3946,0xbc00b340,0x3afeb426,0xb8553979,0x3bdd38b2,0xba21340e,0xa17fbb45,0x3a3d3b32,0x3bf53815,0xb2193966,0xbb13bb37,0x39a1b0d7,
  0x3b6536dd,0x37853b87,0xbaa9b3d3,0xb911bbe9,0x3a393581,0x3b5e3bec,0x2dc938b7,0xbab0b6f4,0x3889341a,0x3bb03a7e,0x3b593bfc,0x375939da,
  0x34f33153,0x38943721,0x3a49397d,0x3b733af1,0xb9863982,0x38eeba0d,0xb84a3a89,0x3737baf4,0xb74e3a04,0xa452bbcb,0x37c83bba,0xbabab9d6,
  0xb1e83a7a,0xb924bbbd,0x3c0036af,0xb90236ff,0x2e913ae1,0xbbdab9e7,0x377ab6e8,0x39af3be8,0x361a3b3a,0xbb10b56a,0xb86fbbc2,0x3a3130be,
  0x39073b83,0xb63c3074,0xbbf8ba76,0xb865bb35,0x3a973bbc,0x346f38ad,0xb654ac06,0xbb1bb974,0x3b9c3be3,0x3a903b2a,0x38f339d2,0x35d437f3,
  0x3b763682,0xbbb5b50b,0x3be1330f,0xbbfaafef,0x2d33bb94,0x365f3be4,0xba45ba58,0x3bdf3699,0xbbd4b371,0x3764b8d6,0x36483bfe,0xbbaeb94f,
  0x379b3beb,0xbbd7b6c6,0x2dfbb9f4,0x3b683ad8,0x39aa2a7a,0x3a2d3bfe,0xb87430a6,0xbb0dbbc3,0xbb07bbfe,0x1fdbb80f,0x3b16382a,0x3a9e3bfd,
  0xb2ad3042,0xba41b835,0xbc00bb92,0xba1dbb7f,0x3bfa3bcc,0x3bd03bfb,0x3afb3b7a,0x398b3a54,0xb5c83b4f,0x344bbb98,0xb1853bce,0x2ccebbf0,
  0x3bf93523,0xbb57313b,0x38f8b8e0,0xb1b63b4a,0xb294bbc8,0x3b183a60,0xbb5ca8e8,0x347bb9fc,0xbb0ab08d,0xb263bb3f,0x3bf73958,0xb60e3825,
  0x39a63bfd,0xb9162a16,0xbaa5bbea,0x3790b3ba,0x37a6a94d,0x3c003ae5,0x376f3ad5,0xb87fab43,0xbbd3bbee,0xb8fdbace,0x2311b52f,0x39293599,
  0x2d003328,0xb2deac6a,0xb7d2b5b1,0xb9c5b8e5,0x3bff26ad,0xbbf12c9c,0x3bcfb16c,0xbb9a343e,0xbb9e2c38,0x3990b83a,0xb4633aee,0xb2c6bbff,
  0x3a9bb109,0xad973ae8,0xb9b8bb81,0x3bf4353a,0xb90c33eb,0xb87abbfe,0x3ba53552,0x1cb63a73,0x3625b55e,0x3ba73b3d,0xb24b381a,0xbbf6ba6f,
  0xaec336bb,0xbb6ab8d1,0xba25bbe7,0x327cb546,0xb1cfb805,0x37bd3122,0x3b6f3a00,0x3b9f3bff,0x374238a3,0x319e3517,0xaf8b2776,0xb66bb432,
  0x25e43bff,0xafbdbbfb,0x32f73be2,0xb4ffbbb7,0xb4e7bbfc,0x39c03acb,0xbbb2b7fe,0x3bd2281f,0x38843be6,0xbbf8b80a,0x3999b58d,0x2ef53b90,
  0xba35bbc0,0x3aa229b1,0x34b73b8b,0xbc00b8bc,0x3b633b89,0xb4ab36d2,0xbbd8bade,0x2e5fb8c1,0xbbf5bb42,0xb602ba64,0x391f30f0,0x3bd63b8e,
  0x3bde3aeb,0x3b013be5,0x35eb394a,0xb4db2884,0xbb21ba85,0xbbe0bb96,0xbbf2bbff,0xbb54bbb8,0x3b52b5bc,0xbaf7372c,0x3a8cb845,0xba1138ea,
  0x392e3b2c,0xbb71b8a8,0x3bf23029,0xba9335a5,0xb85f3830,0xb4cfbbed,0x3b6c39df,0xbb042ba7,0xbbabba67,0x386ab576,0x391b3bfd,0xbb60b3a2,
  0x1648b95d,0x3bf63962,0x32323a6b,0xbba9b820,0x3bac396b,0x399d3bbf,0xb4c33389,0xbbdcb9f8,0x385a3a5c,0xaf273359,0xb9bcb70a,0xbbf9bb47,
  0xb933b840,0xbabdba09,0xbbb3bb4c,0xbc00bbef,0x36763b78,0xb7ddbb27,0x38993ac4,0xb937ba50,0xba193715,0x35dfba81,0x2f593bef,0xb88ebb7c,
  0xbab3bad1,0x3ba1305b,0xb5f73970,0xb7b2bbfc,0x3493b8cc,0x3aac3b85,0xba292ade,0xb631bbc5,0x3c0039f0,0x2e2d39eb,0xbbd9b8c7,0xb49fbadb,
  0x348739e3,0xb9b3b402,0xbba3bbc6,0xb201b954,0xbab6b8db,0xbbf3bbc9,0xb994bb2f,0xad65b6a4,0xba15bac7,0xb850b941,0xb457b68d,0x251bb010,
  0xb9cfbb16,0x30ac2a31,0x3b9c3bf1,0xb493ae2d,0xb76fb8b4,0x35a133e3,0x3a1d3afe,0xb902b76f,0xb3e3b5a1,0x38b4376f,0x376f3902,0xbafeba1d,
  0xaa31b0ac,0x3b1639cf,0x2e2d3493,0xbbf1bb9c,0xb956ba74,0x305f29cc,0x3b633bd2,0xb44badc9,0xb6e7b859,0x353f335e,0x39d23ab6,0xb8bcb6ff,
  0xb35eb53f,0x385936e7,0x36ff38bc,0xbab6b9d2,0xa9ccb05f,0x3a743956,0x2dc9344b,0xbbd2bb63,0xb8e3b9de,0x30122967,0x3b1e3ba1,0xb402ad65,
  0xb662b801,0x34de32da,0x39823a67,0xb874b68d,0xb2dab4de,0x38013662,0x368d3874,0xba67b982,0xa967b012,0x39de38e3,0x2d653402,0xbba1bb1e,
  0xb876b952,0x2f8c2902,0x3ace3b60,0xb371ad00,0xb5e1b758,0x347e3257,0x392e3a11,0xb82ab61a,0xb257b47e,0x375835e1,0x361a382a,0xba11b92e,
  0xa902af8c,0x39523876,0x2d003371,0xbb60bace,0xb80db8ce,0x2ef3289e,0x3a733b10,0xb2deac9c,0xb562b6b3,0x342031d5,0x38d639b3,0xb7bdb5a5,
  0xb1d5b420,0x36b33562,0x35a537bd,0xb9b3b8d6,0xa89eaef3,0x38ce380d,0x2c9c32de,0xbb10ba73,0xb750b851,0x2e5a2839,0x3a0d3ab0,0xb24bac38,
  0xb4e5b613,0x33863153,0x387a394f,0xb721b52f,0xb153b386,0x361334e5,0x352f3721,0xb94fb87a,0xa839ae5a,0x38513750,0x2c38324b,0xbab0ba0d,
  0xb68eb7b4,0x2dc227a9,0x399d3a41,0xb1b6aba7,0xb46ab577,0x32cd30d2,0x381a38e5,0xb682b4b7,0xb0d2b2cd,0x3577346a,0x34b73682,0xb8e5b81a,
  0xa7a9adc2,0x37b4368e,0x2ba731b6,0xba41b99d,0xb5d2b6d1,0x2d2a26e0,0x392439c5,0xb122aade,0xb3e3b4de,0x32163052,0x376f3874,0xb5dfb43e,
  0xb052b216,0x34de33e3,0x343e35df,0xb874b76f,0xa6e0ad2a,0x36d135d2,0x2ade3122,0xb9c5b924,0xb51cb5f6,0x2c932617,0x38a3393c,0xb08daa16,
  0xb2f4b448,0x31602fa5,0x36a437fe,0xb53ab389,0xafa5b160,0x344832f4,0x3389353a,0xb7feb6a4,0xa617ac93,0x35f6351c,0x2a16308d,0xb93cb8a3,
  0xb46ab523,0x2bf6254d,0x381a38a8,0xafefa94d,0xb209b36b,0x30ac2ea7,0x35d4370a,0xb493b294,0xaea7b0ac,0x336b3209,0x32943493,0xb70ab5d4,
  0xa54dabf6,0x3523346a,0x294d2fef,0xb8a8b81a,0xb378b456,0x2ac82484,0x3715380a,0xaec3a884,0xb120b24a,0x2ff22da9,0x34ff360e,0xb3d3b19e,
  0xada9aff2,0x324a3120,0x319e33d3,0xb60eb4ff,0xa484aac8,0x34563378,0x28842ec3,0xb80ab715,0xb223b31c,0x29992376,0x35eb36c6,0xad97a776,
  0xb039b12d,0x2e8d2cac,0x3426350b,0xb27cb0a6,0xacacae8d,0x312d3039,0x30a6327c,0xb50bb426,0xa376a999,0x331c3223,0x27762d97,0xb6c6b5eb,
  0xb0d2b194,0x286b21e4,0x34b7356a,0xac6aa5e4,0xaea7b012,0x2d2a2b5f,0x32943402,0xb122af59,0xab5fad2a,0x30122ea7,0x2f593122,0xb402b294,
  0xa1e4a86b,0x319430d2,0x25e42c6a,0xb56ab4b7,0xaf0cb012,0x267b2052,0x32f73402,0xaa7aa452,0xacdeadf5,0x2b912967,0x30d731e8,0xaf8bad65,
  0xa967ab91,0x2df52cde,0x2d652f8b,0xb1e8b0d7,0xa052a67b,0x30122f0c,0x24522a7a,0xb402b2f7,0xac79ad2a,0x24201d7f,0x30743122,0xa81fa17f,
  0xaa31ab91,0x28d026e0,0x2e2d2f8b,0xacceaade,0xa6e0a8d0,0x2b912a31,0x2ade2cce,0xaf8bae2d,0x9d7fa420,0x2d2a2c79,0x217f281f,0xb122b074,
  0xa7a9a86b,0x1f1218b6,0x2ba72c6a,0xa3119cb6,0xa54da67b,0x242021e4,0x294d2a7a,0xa81fa5e4,0xa1e4a420,0x267b254d,0x25e4281f,0xaa7aa94d,
  0x98b69f12,0x286b27a9,0x1cb62311,0xac6aaba7,0x211b21e4,0x98b69248,0xa51ba5e4,0x1cb61648,0x1f122052,0x9d7f9bdb,0xa311a452,0x217f1fdb,
  0x1bdb1d7f,0xa0529f12,0x9fdba17f,0x24522311,0x124818b6,0xa1e4a11b,0x96489cb6,0x25e4251b,0x2a632b5f,0xa1e49bdb,0xae5faf59,0x25e41fdb,
  0x286b2967,0xa6e0a4e9,0xac6aad65,0x2ade28e8,0x24e926e0,0xa967a86b,0xa8e8aade,0x2d652c6a,0x1bdb21e4,0xab5faa63,0x9fdba5e4,0x2f592e5f,
  0x2dc22ea7,0xa54d9f12,0xb1b6b294,0x294d2311,0x2bf62cde,0xaa31a86b,0xafefb0d7,0x2e2d2c6a,0x286b2a31,0xacdeabf6,0xac6aae2d,0x30d72fef,
  0x1f12254d,0xaea7adc2,0xa311a94d,0x329431b6,0x302c30d2,0xa7a9a11b,0xb41ab4b7,0x2ba7251b,0x2dc22f0c,0xac79aa63,0xb1b6b2f7,0x30742e5f,
  0x2a632c79,0xaf0cadc2,0xae5fb074,0x32f731b6,0x211b27a9,0xb0d2b02c,0xa51baba7,0x34b7341a,0x317a3257,0xa902a2ad,0xb552b61a,0x2d0026ad,
  0x2f8c309f,0xaddcac2e,0xb371b487,0x31cf3029,0x2c2e2ddc,0xb09faf8c,0xb029b1cf,0x34873371,0x22ad2902,0xb257b17a,0xa6adad00,0x361a3552,
  0x32cd33e3,0xaa31a420,0xb682b76f,0x2e2d281f,0x30ac31bb,0xaf3fad2a,0xb493b58d,0x33283122,0x2d2a2f3f,0xb1bbb0ac,0xb122b328,0x358d3493,
  0x24202a31,0xb3e3b2cd,0xa81fae2d,0x376f3682,0x341334bc,0xab5fa4e9,0xb7a6b85a,0x2f5928e8,0x319432da,0xb052ae28,0xb56ab68d,0x343e3219,
  0x2e283052,0xb2dab194,0xb219b43e,0x368d356a,0x24e92b5f,0xb4bcb413,0xa8e8af59,0x385a37a6,0x34c3358c,0xac47a5b2,0xb85fb8f3,0x304229b1,
  0x327e33fd,0xb106af26,0xb63cb785,0x34e7330f,0x2f263106,0xb3fdb27e,0xb30fb4e7,0x3785363c,0x25b22c47,0xb58cb4c3,0xa9b1b042,0x38f3385f,
  0x35773662,0xacdea67b,0xb8e5b982,0x30d72a7a,0x336b3493,0xb1bbb012,0xb70ab83a,0x358d3402,0x301231bb,0xb493b36b,0xb402b58d,0x383a370a,
  0x267b2cde,0xb662b577,0xaa7ab0d7,0x398238e5,0x36303741,0xad76a744,0xb962ba04,0x316c2b43,0x342e352a,0xb271b092,0xb7d2b8ad,0x3631347b,
  0x30923271,0xb52ab42e,0xb47bb631,0x38ad37d2,0x27442d76,0xb741b630,0xab43b16c,0x3a043962,0x36ee3815,0xae0ea807,0xb9d6ba7a,0x32012c06,
  0x34a735c4,0xb329b113,0xb84ab91b,0x36d234f3,0x31133329,0xb5c4b4a7,0xb4f3b6d2,0x391b384a,0x28072e0e,0xb815b6ee,0xac06b201,0x3a7a39d6,
  0x37b4388e,0xaea7a86b,0xba41bae1,0x32942c6a,0x35233662,0xb3e3b194,0xb8a8b982,0x376f356a,0x319433e3,0xb662b523,0xb56ab76f,0x398238a8,
  0x286b2ea7,0xb88eb7b4,0xac6ab294,0x3ae13a41,0x3841390f,0xaf3fa8d0,0xbaa2bb3a,0x33282cce,0x35a13705,0xb44fb216,0xb902b9e3,0x380535df,
  0x3216344f,0xb705b5a1,0xb5dfb805,0x39e33902,0x28d02f3f,0xb90fb841,0xacceb328,0x3b3a3aa2,0x38ac3997,0xafd8a935,0xbaf7bb83,0x33ba2d33,
  0x362137ac,0xb4aeb298,0xb958ba3d,0x38503654,0x329834ae,0xb7acb621,0xb654b850,0x3a3d3958,0x29352fd8,0xb997b8ac,0xad33b3ba,0x3b833af7,
  0x391c3a28,0xb039a999,0xbb42bbbc,0x34262d97,0x36a4382d,0xb50eb31c,0xb9aaba90,0x389936c6,0x331c350e,0xb82db6a4,0xb6c6b899,0x3a9039aa,
  0x29993039,0xba28b91c,0xad97b426,0x3bbc3b42,0x39923ac3,0xb085a9fe,0xbb81bbe3,0x346f2dfb,0x372a3886,0xb570b3a0,0xb9f8badb,0x38e03737,
  0x33a03570,0xb886b72a,0xb737b8e0,0x3adb39f8,0x29fe3085,0xbac3b992,0xadfbb46f,0x3be33b81,
};

#define PROF(slot) do {} while (0)
#define PROF_DUMP() do {} while (0)
#define PROFA(slot, dep) do {} while (0)
#define PROF3(slot) do {} while (0)
#define PROF2(slot) do {} while (0)

__device__ __forceinline__ uint32_t smem_u32(const void* p) { return (uint32_t)__cvta_generic_to_shared(p); }

__device__ __forceinline__ void mbar_init(uint32_t a, uint32_t c) {
  asm volatile("mbarrier.init.shared::cta.b64 [%0], %1;\n" ::"r"(a), "r"(c) : "memory");
}
__device__ __forceinline__ void mbar_expect_tx(uint32_t a, uint32_t bytes) {
  asm volatile("mbarrier.arrive.expect_tx.shared::cta.b64 _, [%0], %1;\n" ::"r"(a), "r"(bytes) : "memory");
}
__device__ __forceinline__ void mbar_arrive_cluster(uint32_t cluster_addr) {
  asm volatile("mbarrier.arrive.shared::cluster.b64 _, [%0];\n" ::"r"(cluster_addr) : "memory");
}
__device__ __forceinline__ void mbar_arrive_cluster_n(uint32_t cluster_addr, uint32_t n) {
  asm volatile("mbarrier.arrive.shared::cluster.b64 _, [%0], %1;\n" ::"r"(cluster_addr), "r"(n) : "memory");
}
__device__ __forceinline__ bool mbar_try(uint32_t a, uint32_t parity) {
  uint32_t ok;
  asm volatile("{\n.reg .pred p;\nmbarrier.try_wait.parity.shared::cta.b64 p, [%1], %2;\nselp.u32 %0, 1, 0, p;\n}\n"
               : "=r"(ok) : "r"(a), "r"(parity) : "memory");
  return ok;
}
__device__ __forceinline__ void mbar_wait(uint32_t a, uint32_t parity) {
  if (mbar_try(a, parity)) return;
#pragma unroll 1
  for (int n = 0; n < SPIN_LIMIT; n++)
    if (mbar_try(a, parity)) break;
}
__device__ __forceinline__ bool elect_one() {
  uint32_t p;
  asm volatile("{\n.reg .pred P;\nelect.sync _|P, 0xffffffff;\nselp.u32 %0, 1, 0, P;\n}\n" : "=r"(p));
  return p;
}
__device__ __forceinline__ uint32_t mapa(uint32_t a, uint32_t rank) {
  uint32_t r;
  asm volatile("mapa.shared::cluster.u32 %0, %1, %2;\n" : "=r"(r) : "r"(a), "r"(rank));
  return r;
}
__device__ __forceinline__ void nb_sync(int id, int n) { asm volatile("bar.sync %0, %1;\n" ::"r"(id), "r"(n) : "memory"); }
__device__ __forceinline__ void nb_arrive(int id, int n) { asm volatile("bar.arrive %0, %1;\n" ::"r"(id), "r"(n) : "memory"); }
__device__ __forceinline__ void cluster_sync_all() {
  asm volatile("barrier.cluster.arrive.relaxed.aligned;\nbarrier.cluster.wait.aligned;\n" ::: "memory");
}
__device__ __forceinline__ void fence_async_smem() { asm volatile("fence.proxy.async.shared::cta;\n" ::: "memory"); }
__device__ __forceinline__ void fence_async_all() { asm volatile("fence.proxy.async.global;\n" ::: "memory"); }

__device__ __forceinline__ void tma_load_3d(uint32_t dst, const CUtensorMap* tm, uint32_t bar, int c0, int c1, int c2) {
  asm volatile(
      "cp.async.bulk.tensor.3d.shared::cluster.global.mbarrier::complete_tx::bytes [%0], [%1, {%3, %4, %5}], [%2];\n"
      ::"r"(dst), "l"(tm), "r"(bar), "r"(c0), "r"(c1), "r"(c2) : "memory");
}
__device__ __forceinline__ void tma_load_4d(uint32_t dst, const CUtensorMap* tm, uint32_t bar, int c0, int c1, int c2, int c3) {
  asm volatile(
      "cp.async.bulk.tensor.4d.shared::cluster.global.mbarrier::complete_tx::bytes [%0], [%1, {%3, %4, %5, %6}], [%2];\n"
      ::"r"(dst), "l"(tm), "r"(bar), "r"(c0), "r"(c1), "r"(c2), "r"(c3) : "memory");
}
__device__ __forceinline__ void tma_load_3d_mc(uint32_t dst, const CUtensorMap* tm, uint32_t bar, int c0, int c1, int c2) {
  asm volatile(
      "cp.async.bulk.tensor.3d.shared::cluster.global.mbarrier::complete_tx::bytes.multicast::cluster [%0], [%1, {%3, %4, %5}], [%2], %6;\n"
      ::"r"(dst), "l"(tm), "r"(bar), "r"(c0), "r"(c1), "r"(c2), "h"((uint16_t)3) : "memory");
}
__device__ __forceinline__ void bulk_load(uint32_t dst, const void* src, uint32_t bytes, uint32_t bar) {
  asm volatile("cp.async.bulk.shared::cluster.global.mbarrier::complete_tx::bytes [%0], [%1], %2, [%3];\n"
               ::"r"(dst), "l"(src), "r"(bytes), "r"(bar) : "memory");
}
__device__ __forceinline__ void tma_store_3d(const CUtensorMap* tm, uint32_t src, int c0, int c1, int c2) {
  asm volatile("cp.async.bulk.tensor.3d.global.shared::cta.bulk_group [%0, {%2, %3, %4}], [%1];\n"
               ::"l"(tm), "r"(src), "r"(c0), "r"(c1), "r"(c2) : "memory");
}
__device__ __forceinline__ void bulk_commit() { asm volatile("cp.async.bulk.commit_group;\n" ::: "memory"); }
__device__ __forceinline__ void bulk_wait0() { asm volatile("cp.async.bulk.wait_group 0;\n" ::: "memory"); }
__device__ __forceinline__ void prefetch_tmap(const CUtensorMap* tm) {
  asm volatile("prefetch.tensormap [%0];\n" ::"l"(tm) : "memory");
}

__device__ __forceinline__ void wg_fence() { asm volatile("wgmma.fence.sync.aligned;\n" ::: "memory"); }
__device__ __forceinline__ void wg_commit() { asm volatile("wgmma.commit_group.sync.aligned;\n" ::: "memory"); }
template <int N> __device__ __forceinline__ void wg_wait() {
  asm volatile("wgmma.wait_group.sync.aligned %0;\n" ::"n"(N) : "memory");
}
__device__ __forceinline__ uint64_t mkdesc(uint32_t addr, uint32_t lbo, uint32_t sbo, uint32_t swz) {
  return (uint64_t)((addr & 0x3FFFF) >> 4) | ((uint64_t)(lbo >> 4) << 16) | ((uint64_t)(sbo >> 4) << 32) |
         ((uint64_t)swz << 62);
}

#define R4(d, o) "+f"(d[o + 0]), "+f"(d[o + 1]), "+f"(d[o + 2]), "+f"(d[o + 3])
#define R8(d, o) R4(d, o), R4(d, o + 4)
#define R16(d, o) R8(d, o), R8(d, o + 8)
#define R32(d, o) R16(d, o), R16(d, o + 16)
#define R64(d, o) R32(d, o), R32(d, o + 32)

__device__ __forceinline__ void wgmma_n192(float (&d)[96], uint64_t da, uint64_t db, uint32_t acc) {
  asm volatile(
      "{\n.reg .pred p;\nsetp.ne.u32 p, %98, 0;\n"
      "wgmma.mma_async.sync.aligned.m64n192k16.f32.bf16.bf16 "
      "{%0,%1,%2,%3,%4,%5,%6,%7,%8,%9,%10,%11,%12,%13,%14,%15,%16,%17,%18,%19,%20,%21,%22,%23,%24,%25,%26,%27,%28,%29,%30,%31,"
      "%32,%33,%34,%35,%36,%37,%38,%39,%40,%41,%42,%43,%44,%45,%46,%47,%48,%49,%50,%51,%52,%53,%54,%55,%56,%57,%58,%59,%60,%61,%62,%63,"
      "%64,%65,%66,%67,%68,%69,%70,%71,%72,%73,%74,%75,%76,%77,%78,%79,%80,%81,%82,%83,%84,%85,%86,%87,%88,%89,%90,%91,%92,%93,%94,%95}, "
      "%96, %97, p, 1, 1, 0, 1;\n}\n"
      : R64(d, 0), R32(d, 64)
      : "l"(da), "l"(db), "r"(acc));
}
__device__ __forceinline__ void wgmma_n128(float (&d)[64], uint64_t da, uint64_t db, uint32_t acc) {
  asm volatile(
      "{\n.reg .pred p;\nsetp.ne.u32 p, %66, 0;\n"
      "wgmma.mma_async.sync.aligned.m64n128k16.f32.bf16.bf16 "
      "{%0,%1,%2,%3,%4,%5,%6,%7,%8,%9,%10,%11,%12,%13,%14,%15,%16,%17,%18,%19,%20,%21,%22,%23,%24,%25,%26,%27,%28,%29,%30,%31,"
      "%32,%33,%34,%35,%36,%37,%38,%39,%40,%41,%42,%43,%44,%45,%46,%47,%48,%49,%50,%51,%52,%53,%54,%55,%56,%57,%58,%59,%60,%61,%62,%63}, "
      "%64, %65, p, 1, 1, 0, 1;\n}\n"
      : R64(d, 0)
      : "l"(da), "l"(db), "r"(acc));
}
#define WG128(C, ACC)                                                                                                      \
  asm volatile(                                                                                                            \
      "{\n.reg .b64 a, b;\nmov.b64 a, {%64, %66};\nmov.b64 b, {%65, %66};\n"                                               \
      "wgmma.mma_async.sync.aligned.m64n128k16.f32.bf16.bf16 "                                                             \
      "{%0,%1,%2,%3,%4,%5,%6,%7,%8,%9,%10,%11,%12,%13,%14,%15,%16,%17,%18,%19,%20,%21,%22,%23,%24,%25,%26,%27,%28,%29,%30,%31," \
      "%32,%33,%34,%35,%36,%37,%38,%39,%40,%41,%42,%43,%44,%45,%46,%47,%48,%49,%50,%51,%52,%53,%54,%55,%56,%57,%58,%59,%60,%61," \
      "%62,%63}, a, b, " ACC ", 1, 1, 0, 1;\n}\n"                                                                          \
      : Z16(C, d, 0), Z16(C, d, 16), Z16(C, d, 32), Z16(C, d, 48)                                                          \
      : "r"(da), "r"(db), "r"(0x40000040))
#define Z4(C, d, o) C(d[o + 0]), C(d[o + 1]), C(d[o + 2]), C(d[o + 3])
#define Z16(C, d, o) Z4(C, d, o), Z4(C, d, o + 4), Z4(C, d, o + 8), Z4(C, d, o + 12)
__device__ __forceinline__ void wgmma_n128z(float (&d)[64], uint32_t da, uint32_t db) { WG128("=f", "0"); }
__device__ __forceinline__ void wgmma_n128a(float (&d)[64], uint32_t da, uint32_t db) { WG128("+f", "1"); }
template <int N> __device__ __forceinline__ void fence_regs(float (&d)[N]) {
#pragma unroll
  for (int i = 0; i < N; i++) asm volatile("" : "+f"(d[i])::"memory");
}

__device__ __forceinline__ void mma16816(float (&d)[4], uint32_t a0, uint32_t a1, uint32_t a2, uint32_t a3, uint32_t b0,
                                         uint32_t b1) {
  asm("mma.sync.aligned.m16n8k16.row.col.f32.bf16.bf16.f32 {%0,%1,%2,%3}, {%4,%5,%6,%7}, {%8,%9}, {%0,%1,%2,%3};\n"
      : "+f"(d[0]), "+f"(d[1]), "+f"(d[2]), "+f"(d[3])
      : "r"(a0), "r"(a1), "r"(a2), "r"(a3), "r"(b0), "r"(b1));
}
__device__ __forceinline__ void mma16816_z(float (&d)[4], uint32_t a0, uint32_t a1, uint32_t a2, uint32_t a3, uint32_t b0,
                                           uint32_t b1) {
  asm("mma.sync.aligned.m16n8k16.row.col.f32.bf16.bf16.f32 {%0,%1,%2,%3}, {%4,%5,%6,%7}, {%8,%9}, {%10,%10,%10,%10};\n"
      : "=f"(d[0]), "=f"(d[1]), "=f"(d[2]), "=f"(d[3])
      : "r"(a0), "r"(a1), "r"(a2), "r"(a3), "r"(b0), "r"(b1), "f"(0.f));
}
__device__ __forceinline__ void ldsm4t(uint32_t (&r)[4], uint32_t a) {
  asm volatile("ldmatrix.sync.aligned.m8n8.x4.trans.shared.b16 {%0,%1,%2,%3}, [%4];\n"
               : "=r"(r[0]), "=r"(r[1]), "=r"(r[2]), "=r"(r[3]) : "r"(a) : "memory");
}
__device__ __forceinline__ void ldsm2t(uint32_t& r0, uint32_t& r1, uint32_t a) {
  asm volatile("ldmatrix.sync.aligned.m8n8.x2.trans.shared.b16 {%0,%1}, [%2];\n" : "=r"(r0), "=r"(r1) : "r"(a) : "memory");
}
__device__ __forceinline__ void st_async128(uint32_t a, uint32_t bar, uint32_t x, uint32_t y, uint32_t z, uint32_t w) {
  asm volatile("st.async.weak.shared::cluster.mbarrier::complete_tx::bytes.v4.b32 [%0], {%2,%3,%4,%5}, [%1];\n"
               ::"r"(a), "r"(bar), "r"(x), "r"(y), "r"(z), "r"(w) : "memory");
}
__device__ __forceinline__ void mbar_arrive(uint32_t a) {
  asm volatile("mbarrier.arrive.shared::cta.b64 _, [%0];\n" ::"r"(a) : "memory");
}
__device__ __forceinline__ void stsm4(uint32_t a, uint32_t r0, uint32_t r1, uint32_t r2, uint32_t r3) {
  asm volatile("stmatrix.sync.aligned.m8n8.x4.shared.b16 [%0], {%1,%2,%3,%4};\n"
               ::"r"(a), "r"(r0), "r"(r1), "r"(r2), "r"(r3) : "memory");
}
__device__ __forceinline__ void stsm4t(uint32_t a, uint32_t r0, uint32_t r1, uint32_t r2, uint32_t r3) {
  asm volatile("stmatrix.sync.aligned.m8n8.x4.trans.shared.b16 [%0], {%1,%2,%3,%4};\n"
               ::"r"(a), "r"(r0), "r"(r1), "r"(r2), "r"(r3) : "memory");
}
__device__ __forceinline__ uint2 lds64(uint32_t a) {
  uint2 v;
  asm volatile("ld.shared.v2.u32 {%0,%1}, [%2];\n" : "=r"(v.x), "=r"(v.y) : "r"(a));
  return v;
}
__device__ __forceinline__ uint4 lds128(uint32_t a) {
  uint4 v;
  asm volatile("ld.shared.v4.u32 {%0,%1,%2,%3}, [%4];\n" : "=r"(v.x), "=r"(v.y), "=r"(v.z), "=r"(v.w) : "r"(a) : "memory");
  return v;
}
__device__ __forceinline__ void sts128(uint32_t a, uint32_t x, uint32_t y, uint32_t z, uint32_t w) {
  asm volatile("st.shared.v4.u32 [%0], {%1,%2,%3,%4};\n" ::"r"(a), "r"(x), "r"(y), "r"(z), "r"(w) : "memory");
}
__device__ __forceinline__ void sts64(uint32_t a, uint32_t x, uint32_t y) {
  asm volatile("st.shared.v2.u32 [%0], {%1,%2};\n" ::"r"(a), "r"(x), "r"(y) : "memory");
}
__device__ __forceinline__ uint32_t pack_bf16(float lo, float hi) {
  uint32_t r;
  asm("cvt.rn.bf16x2.f32 %0, %1, %2;\n" : "=r"(r) : "f"(hi), "f"(lo));
  return r;
}
__device__ __forceinline__ uint32_t bmul2(uint32_t a, uint32_t b) {
  uint32_t r;
  asm("mul.rn.bf16x2 %0, %1, %2;\n" : "=r"(r) : "r"(a), "r"(b));
  return r;
}
__device__ __forceinline__ uint32_t bmax2(uint32_t a, uint32_t b) {
  uint32_t r;
  asm("max.bf16x2 %0, %1, %2;\n" : "=r"(r) : "r"(a), "r"(b));
  return r;
}
__device__ __forceinline__ uint32_t bfma2(uint32_t a, uint32_t b, uint32_t c) {
  uint32_t r;
  asm("fma.rn.bf16x2 %0, %1, %2, %3;\n" : "=r"(r) : "r"(a), "r"(b), "r"(c));
  return r;
}
__device__ __forceinline__ uint32_t badd2(uint32_t a, uint32_t b) {
  uint32_t r;
  asm("add.rn.bf16x2 %0, %1, %2;\n" : "=r"(r) : "r"(a), "r"(b));
  return r;
}
__device__ __forceinline__ void prefetch_l2(const void* p) { asm volatile("prefetch.global.L2 [%0];\n" ::"l"(p)); }
__device__ __forceinline__ void cp_async16n(uint32_t dst, const void* src) {
  asm volatile("cp.async.cg.shared.global [%0], [%1], 16;\n" ::"r"(dst), "l"(src) : "memory");
}
__device__ __forceinline__ void cp_async16(uint32_t dst, const void* src, uint32_t srcbytes) {
  asm volatile("cp.async.cg.shared.global.L2::256B [%0], [%1], 16, %2;\n" ::"r"(dst), "l"(src), "r"(srcbytes) : "memory");
}
__device__ __forceinline__ uint32_t ld_acquire(const uint32_t* p) {
  uint32_t v;
  asm volatile("ld.acquire.gpu.global.u32 %0, [%1];\n" : "=r"(v) : "l"(p) : "memory");
  return v;
}
__device__ __forceinline__ uint32_t ld_relaxed(const uint32_t* p) {
  uint32_t v;
  asm volatile("ld.relaxed.gpu.global.u32 %0, [%1];\n" : "=r"(v) : "l"(p) : "memory");
  return v;
}
__device__ __forceinline__ void st_release(uint32_t* p, uint32_t v) {
  asm volatile("st.release.gpu.global.u32 [%0], %1;\n" ::"l"(p), "r"(v) : "memory");
}
__device__ __forceinline__ uint4 ld_b128(const uint4* p) {
  unsigned long long a, b;
  asm volatile("{\n.reg .b128 v;\nld.relaxed.gpu.global.b128 v, [%2];\nmov.b128 {%0, %1}, v;\n}\n" : "=l"(a), "=l"(b) : "l"(p) : "memory");
  return make_uint4((uint32_t)a, (uint32_t)(a >> 32), (uint32_t)b, (uint32_t)(b >> 32));
}
__device__ __forceinline__ void st_b128(uint4* p, uint32_t x, uint32_t y, uint32_t z, uint32_t w) {
  asm volatile("{\n.reg .b128 v;\nmov.b128 v, {%1, %2};\nst.relaxed.gpu.global.b128 [%0], v;\n}\n"
               ::"l"(p), "l"(x | (unsigned long long)y << 32), "l"(z | (unsigned long long)w << 32) : "memory");
}

struct Params {
  const __nv_bfloat16* x;
  const __nv_bfloat16* w;
  const __nv_bfloat16* q;
  const __nv_bfloat16* k;
  const __nv_bfloat16* v;
  const __nv_bfloat16* shift_k;
  const __nv_bfloat16* ssm_k;
  const __nv_bfloat16* ssm_D;
  const __nv_bfloat16* wo;
  __nv_bfloat16* out;
  uint32_t zero;
};

__device__ __forceinline__ uint32_t lds32(uint32_t a) {
  uint32_t v;
  asm volatile("ld.shared.u32 %0, [%1];\n" : "=r"(v) : "r"(a) : "memory");
  return v;
}
__device__ __forceinline__ float bf_lo(uint32_t v) {
  uint32_t r;
  asm("prmt.b32 %0, %1, 0, 0x1044;\n" : "=r"(r) : "r"(v));
  return __uint_as_float(r);
}
__device__ __forceinline__ float bf_hi(uint32_t v) { return __uint_as_float(v & 0xffff0000u); }
__device__ __forceinline__ float ex2(float x) {
  float r;
  asm("ex2.approx.ftz.f32 %0, %1;\n" : "=f"(r) : "f"(x));
  return r;
}
__device__ __forceinline__ float rcp(float x) {
  float r;
  asm("rcp.approx.ftz.f32 %0, %1;\n" : "=f"(r) : "f"(x));
  return r;
}

#define Q4(c, d, o) c(d[o + 0]), c(d[o + 1]), c(d[o + 2]), c(d[o + 3])
#define Q8(c, d, o) Q4(c, d, o), Q4(c, d, o + 4)
#define Q16(c, d, o) Q8(c, d, o), Q8(c, d, o + 8)
#define Q32(c, d) Q16(c, d, 0), Q16(c, d, 16)
#define L8 "{%0,%1,%2,%3,%4,%5,%6,%7}"
#define L16 "{%0,%1,%2,%3,%4,%5,%6,%7,%8,%9,%10,%11,%12,%13,%14,%15}"
#define L32 "{%0,%1,%2,%3,%4,%5,%6,%7,%8,%9,%10,%11,%12,%13,%14,%15,%16,%17,%18,%19,%20,%21,%22,%23,%24,%25,%26,%27,%28,%29,%30,%31}"
__device__ __forceinline__ void fft_rows(uint32_t (&d)[32], const uint32_t (&a)[2][4], uint64_t db) {
  asm volatile("wgmma.mma_async.sync.aligned.m64n128k16.f16.f16.f16 " L32 ", {%32,%33,%34,%35}, %36, 0, 1, 1, 1;\n"
               : Q32("=r", d) : "r"(a[0][0]), "r"(a[0][1]), "r"(a[0][2]), "r"(a[0][3]), "l"(db));
  asm volatile("wgmma.mma_async.sync.aligned.m64n128k16.f16.f16.f16 " L32 ", {%32,%33,%34,%35}, %36, 1, 1, 1, 1;\n"
               : Q32("+r", d) : "r"(a[1][0]), "r"(a[1][1]), "r"(a[1][2]), "r"(a[1][3]), "l"(db + 64));
}
template <int INV> __device__ __forceinline__ void fft_cols(uint32_t (&d)[8], const uint32_t (&a)[2][4], uint64_t db) {
  asm volatile("wgmma.mma_async.sync.aligned.m64n32k16.f16.f16.f16 " L8 ", {%8,%9,%10,%11}, %12, 0, 1, 1, %13;\n"
               : Q8("=r", d, 0) : "r"(a[0][0]), "r"(a[0][1]), "r"(a[0][2]), "r"(a[0][3]), "l"(db), "n"(INV));
  asm volatile("wgmma.mma_async.sync.aligned.m64n32k16.f16.f16.f16 " L8 ", {%8,%9,%10,%11}, %12, 1, 1, 1, %13;\n"
               : Q8("+r", d, 0) : "r"(a[1][0]), "r"(a[1][1]), "r"(a[1][2]), "r"(a[1][3]), "l"(db + (INV ? 16 : 64)), "n"(INV));
}
__device__ __forceinline__ void fft_back(float (&d)[16], uint64_t da, uint64_t db) {
  asm volatile("wgmma.mma_async.sync.aligned.m64n32k16.f32.f16.f16 " L16 ", %16, %17, 0, 1, 1, 1, 1;\n"
               : Q16("=f", d, 0) : "l"(da), "l"(db));
#pragma unroll
  for (int i = 1; i < 4; i++)
    asm volatile("wgmma.mma_async.sync.aligned.m64n32k16.f32.f16.f16 " L16 ", %16, %17, 1, 1, 1, 1, 1;\n"
                 : Q16("+f", d, 0) : "l"(da + 32 * i), "l"(db + 64 * i));
}
__device__ __forceinline__ uint32_t hmul2(uint32_t a, uint32_t b) {
  uint32_t r;
  asm("mul.rn.f16x2 %0, %1, %2;\n" : "=r"(r) : "r"(a), "r"(b));
  return r;
}
__device__ __forceinline__ uint32_t hadd2(uint32_t a, uint32_t b) {
  uint32_t r;
  asm("add.rn.f16x2 %0, %1, %2;\n" : "=r"(r) : "r"(a), "r"(b));
  return r;
}
__device__ __forceinline__ uint32_t hneg2(uint32_t a) {
  uint32_t r;
  asm("neg.f16x2 %0, %1;\n" : "=r"(r) : "r"(a));
  return r;
}
__device__ __forceinline__ uint32_t hfma2(uint32_t a, uint32_t b, uint32_t c) {
  uint32_t r;
  asm("fma.rn.f16x2 %0, %1, %2, %3;\n" : "=r"(r) : "r"(a), "r"(b), "r"(c));
  return r;
}
__device__ __forceinline__ uint32_t pack_f16(float lo, float hi) {
  uint32_t r;
  asm("cvt.rn.f16x2.f32 %0, %1, %2;\n" : "=r"(r) : "f"(hi), "f"(lo));
  return r;
}
__device__ __forceinline__ uint32_t bmaxabs2(uint32_t a, uint32_t b) {
  uint32_t r;
  asm("max.xorsign.abs.bf16x2 %0, %1, %2;\n" : "=r"(r) : "r"(a), "r"(b));
  return r;
}
struct C2 { uint32_t r, i; };
__device__ __forceinline__ C2 cmul(C2 a, C2 b) {
  return C2{hfma2(a.r, b.r, hneg2(hmul2(a.i, b.i))), hfma2(a.r, b.i, hmul2(a.i, b.r))};
}
__device__ __forceinline__ C2 cfma(C2 a, C2 b, C2 c) {
  return C2{hfma2(a.r, b.r, hfma2(hneg2(a.i), b.i, c.r)), hfma2(a.r, b.i, hfma2(a.i, b.r, c.i))};
}
__device__ __forceinline__ C2 crot(C2 z, C2 t) {
  const uint32_t r = hfma2(t.r, z.i, z.r), i = hfma2(t.i, r, z.i);
  return C2{hfma2(t.r, i, r), i};
}
__device__ __forceinline__ C2 cget(const uint32_t (&e)[8], int j, int b) { return C2{e[4 * j + b], e[4 * j + 2 + b]}; }
template <int N> __device__ __forceinline__ void fence_regs(uint32_t (&d)[N]) {
#pragma unroll
  for (int i = 0; i < N; i++) asm volatile("" : "+r"(d[i])::"memory");
}
__device__ __forceinline__ void ldsm4(uint32_t (&r)[4], uint32_t a) {
  asm volatile("ldmatrix.sync.aligned.m8n8.x4.shared.b16 {%0,%1,%2,%3}, [%4];\n"
               : "=r"(r[0]), "=r"(r[1]), "=r"(r[2]), "=r"(r[3]) : "r"(a) : "memory");
}

__device__ __forceinline__ uint32_t movm(uint32_t a) {
  uint32_t r;
  asm volatile("movmatrix.sync.aligned.m8n8.trans.b16 %0, %1;\n" : "=r"(r) : "r"(a));
  return r;
}
template <int C0, int H, bool T> __device__ __forceinline__ void attn_pack(const float (&acc)[96], uint32_t (&d)[8]) {
#pragma unroll
  for (int c = 0; c < 8; c++) {
    asm volatile("cvt.rn.bf16x2.f32 %0, %1, %2;\n" : "=r"(d[c]) : "f"(acc[4 * (C0 + c) + 2 * H + 1]), "f"(acc[4 * (C0 + c) + 2 * H]));
    if (T) d[c] = movm(d[c]);
  }
}
__device__ __forceinline__ void attn_qk(float (&s)[4], const uint32_t (&qlo)[8], const uint32_t (&qhi)[8],
                                        const uint32_t (&k)[8], int c) {
  mma16816_z(s, qlo[c], qhi[c], qlo[c + 1], qhi[c + 1], k[c], k[c + 1]);
  mma16816(s, qlo[c + 2], qhi[c + 2], qlo[c + 3], qhi[c + 3], k[c + 2], k[c + 3]);
}
template <int N> __device__ __forceinline__ void quad_softmax(float (&x)[N][2], uint32_t (&pp)[N]) {
  const float c2 = 1.4426950408889634f;
  uint32_t q[N], mx[N / 2];
#pragma unroll
  for (int n = 0; n < N; n++) {
    const uint32_t r = pack_bf16(x[n][0], x[n][1]);
    q[n] = bfma2(r, 0x3e353e35u, bmul2(r, 0x379e379eu));
    x[n][0] = bf_lo(q[n]);
    x[n][1] = bf_hi(q[n]);
  }
#pragma unroll
  for (int n = 0; n < N / 2; n++)
    mx[n] = bmax2(__byte_perm(q[2 * n], q[2 * n + 1], 0x5410), __byte_perm(q[2 * n], q[2 * n + 1], 0x7632));
#pragma unroll
  for (int o = 1; o <= 2; o++) {
#pragma unroll
    for (int n = 0; n < N / 2; n++) mx[n] = bmax2(mx[n], __shfl_xor_sync(0xffffffffu, mx[n], o));
  }
  float m[N], t[N];
#pragma unroll
  for (int n = 0; n < N / 2; n++) {
    m[2 * n] = bf_lo(mx[n]);
    m[2 * n + 1] = bf_hi(mx[n]);
  }
#pragma unroll
  for (int n = 0; n < N; n++) {
    const float nm = -m[n] * c2;
    x[n][0] = ex2(fmaf(x[n][0], c2, nm));
    x[n][1] = ex2(fmaf(x[n][1], c2, nm));
  }
#pragma unroll
  for (int n = 0; n < N; n += 2) {
    float u0, u1;
    asm("mma.sync.aligned.m16n8k8.row.col.f32.tf32.tf32.f32 {%0,%1,%2,%3}, {%4,%5,%6,%7}, {%8,%8}, {%9,%9,%9,%9};\n"
        : "=f"(t[n]), "=f"(u0), "=f"(t[n + 1]), "=f"(u1)
        : "r"(__float_as_uint(x[n][0])), "r"(__float_as_uint(x[n + 1][0])), "r"(__float_as_uint(x[n][1])),
          "r"(__float_as_uint(x[n + 1][1])), "r"(0x3f800000u), "f"(0.f));
  }
#pragma unroll
  for (int n = 0; n < N; n++) {
    const float inv = rcp(t[n]);
    pp[n] = pack_bf16(x[n][0] * inv, x[n][1] * inv);
  }
}
template <bool SPLIT>
__device__ __forceinline__ void attn_pv(uint32_t dst, const uint32_t (&vp)[8], const uint32_t (&vo)[8], int c, uint32_t pp,
                                        uint32_t maskLE) {
  const uint32_t b0 = pp & ~maskLE, b1 = pp & maskLE;
  float o[2][4];
#pragma unroll
  for (int i = 0; i < 2; i++) {
    if (SPLIT) {
      asm("mma.sync.aligned.m16n8k8.row.col.f32.bf16.bf16.f32 {%0,%1,%2,%3}, {%4,%5}, {%6}, {%7,%7,%7,%7};\n"
          : "=f"(o[i][0]), "=f"(o[i][1]), "=f"(o[i][2]), "=f"(o[i][3])
          : "r"(vp[c + 2 * i]), "r"(vp[c + 2 * i + 1]), "r"(b0), "f"(0.f));
      asm("mma.sync.aligned.m16n8k8.row.col.f32.bf16.bf16.f32 {%0,%1,%2,%3}, {%4,%5}, {%6}, {%0,%1,%2,%3};\n"
          : "+f"(o[i][0]), "+f"(o[i][1]), "+f"(o[i][2]), "+f"(o[i][3])
          : "r"(vo[c + 2 * i]), "r"(vo[c + 2 * i + 1]), "r"(b1));
    } else {
      mma16816_z(o[i], vp[c + 2 * i], vp[c + 2 * i + 1], vo[c + 2 * i], vo[c + 2 * i + 1], b0, b1);
    }
  }
  stsm4t(dst, pack_bf16(o[0][0], o[0][1]), pack_bf16(o[0][2], o[0][3]), pack_bf16(o[1][0], o[1][1]),
         pack_bf16(o[1][2], o[1][3]));
}

template <int MODE>
__global__ void __cluster_dims__(2, 1, 1) __launch_bounds__(NTHREADS, 1)
fused_kernel(const Params p, const __grid_constant__ CUtensorMap tmX, const __grid_constant__ CUtensorMap tmW,
             const __grid_constant__ CUtensorMap tmWo, const __grid_constant__ CUtensorMap tmWp,
             const __grid_constant__ CUtensorMap tmQ,
             const __grid_constant__ CUtensorMap tmOb,
             const __grid_constant__ CUtensorMap tmXh, const __grid_constant__ CUtensorMap tmWh) {
  extern __shared__ __align__(1024) uint8_t smem[];
  if (threadIdx.x < 32 * PFR) {
    const uint32_t i = ((blockIdx.x + (threadIdx.x >> 5) * (128 / PFR)) & 127) * 16 + (threadIdx.x & 15);
    prefetch_l2(threadIdx.x & 16 ? (const char*)p.w + i * 128 : (const char*)p.x + i * 2048);
  }
  const uint32_t sb = smem_u32(smem);
  const uint32_t bars = sb + OFF_BAR;
  const int tid = threadIdx.x, lane = tid & 31, warp = __shfl_sync(0xffffffffu, tid >> 5, 0);
  const int rank = blockIdx.x & 1;
  const bool halo_cta = blockIdx.x < 4;
  if (halo_cta && MODE != 0) return;
  int grp, mem;
  {
    const int t = (blockIdx.x >> 1) - 4, u = t - 32;
    const int q7 = (u * 37) >> 8;
    const bool lo = (unsigned)t < 32u, mid = (unsigned)u < 28u;
    grp = lo ? (t & 7) : (mid ? 1 + u - 7 * q7 : 0);
    mem = lo ? (t >> 3) : (mid ? 4 + q7 : (t < 0 ? t + 6 : t - 54));
  }
  const int rg = (grp >> 2) * 4 + (mem >> 1), hp = (grp & 3) * 4 + (mem & 1) * 2 + rank;
  const int rb2 = (grp >> 2) * 8 + mem, cb2 = (grp & 3) * 2 + rank;
  const int chb = grp * 16 + mem * 2 + rank;
  const int cta = rg * 16 + hp;
  const int hsel = rb2 & 1;
  const int par = rg >> 2, gidx = rg & 3;

  if (tid < 256 && !halo_cta && MODE != 2) {
    const int r = tid >> 3, c = tid & 7;
    const uint32_t so = r * 128 + ((c ^ (r & 7)) << 4);
    const __nv_bfloat16* wg0 = p.w + (size_t)r * (3 * DM) + hp * 64 + c * 8;
    const __nv_bfloat16* xg0 = p.x + (size_t)(2 * (gidx * 256 + r) + par) * DM + c * 8;
#pragma unroll
    for (int j = 0; j < 3; j++) cp_async16n(sb + OFF_1B + j * 4096 + so, wg0 + j * DM);
#pragma unroll
    for (int i = 0; i < 8; i++) cp_async16n(sb + i * 4096 + so, xg0 + (size_t)i * 64 * DM);
    asm volatile("cp.async.commit_group;\n" ::: "memory");
    if (PF2 >= 1 && tid < 16 * PF2X) prefetch_l2((const char*)p.x + (chb * 16 + (tid & 15)) * 2048 + 128 + (tid >> 4) * 128);
    if (PF2 >= 2 && warp == 2) prefetch_l2((const char*)p.w + (2048 + chb * 32 + lane) * 128);
  }

  if (warp >= 8) {
    asm volatile("setmaxnreg.dec.sync.aligned.u32 %0;\n" :: "n"(REG_HELP));
    auto halo_issue = [&](int n, int s) {
      const uint32_t fb = bars + 8 * (BAR_FULLB + s), st = sb + s * STGH;
      tma_load_3d(st + 8192, &tmWh, fb, 0, (n >> 1) * 64, 16 + (n & 1) * 16 + blockIdx.x * 4);
      tma_load_4d(st, &tmXh, fb, (n >> 1) * 64, 248, 0, 0);
      mbar_expect_tx(fb, STGH - 2048);
    };
    if (tid == 256) {
      prefetch_tmap(halo_cta ? &tmXh : &tmX);
#pragma unroll
      for (int i = 0; i < NS1B; i++) mbar_init(bars + 8 * (BAR_FULLB + i), 1);
#pragma unroll
      for (int i = 0; i < NS1A; i++) mbar_init(bars + 8 * (BAR_FULLA + i), 1);
      asm volatile("fence.mbarrier_init.release.cluster;\n" ::: "memory");
      if (!halo_cta && MODE != 2) {
        mbar_expect_tx(bars + 8 * (BAR_FULLB + 1), STG1B);
        tma_load_3d(sb + OFF_1B + 1 * STG1B, &tmW, bars + 8 * (BAR_FULLB + 1), hp * 64, 32, 0);
        mbar_expect_tx(bars + 8 * (BAR_FULLB + 2), STG1B);
        tma_load_3d(sb + OFF_1B + 2 * STG1B, &tmW, bars + 8 * (BAR_FULLB + 2), hp * 64, 64, 0);
        mbar_arrive(bars + 8 * BAR_FULLA);
        mbar_arrive(bars + 8 * BAR_FULLB);
      } else if (halo_cta) {
        halo_issue(0, 0);
      }
    } else if (tid == 288) {
#pragma unroll
      for (int i = 0; i < NS1A; i++) mbar_init(bars + 8 * (BAR_EMPTYA + i), 4);
#pragma unroll
      for (int i = 0; i < NS1B; i++) mbar_init(bars + 8 * (BAR_EMPTYB + i), 2);
      mbar_init(bars + 8 * BAR_X, 3);
      mbar_init(bars + 8 * BAR_TAB, 16);
      mbar_init(bars + 8 * BAR_U, 1);
      mbar_init(bars + 8 * BAR_H, 1);
      mbar_init(bars + 8 * BAR_STG, 8);
      mbar_init(bars + 8 * BAR_HALO, 1);
      mbar_init(bars + 8 * BAR_Q, 1);
      mbar_init(bars + 8 * BAR_LAND, 5);
      mbar_init(bars + 8 * (BAR_LAND + 1), 5);
      asm volatile("fence.mbarrier_init.release.cluster;\n" ::: "memory");
    } else if (tid == 320) {
#pragma unroll
      for (int i = 0; i < NS2; i++) {
        mbar_init(bars + 8 * (BAR_FULL2 + i), 1);
        mbar_init(bars + 8 * (BAR_EMPTY2 + i), 2);
        mbar_init(bars + 8 * (BAR_EMPTY2B + i), 2);
      }
      asm volatile("fence.mbarrier_init.release.cluster;\n" ::: "memory");
    } else if (tid == 352) {
#pragma unroll
      for (int i = 0; i < 4; i++) mbar_init(bars + 8 * (BAR_Y + i), i < 2 ? 4 : i == 2 ? 10 : 8);
      mbar_init(bars + 8 * BAR_XFREE, 1);
      asm volatile("fence.mbarrier_init.release.cluster;\n" ::: "memory");
    }
    __syncwarp();
    cluster_sync_all();
    if (warp == 8) PROF2(24);
    const int hw = warp - 8;
    const int lr = lane & 7, lm = lane >> 3;
    auto g1_issue_a = [&](int j, int s) {
      const uint32_t fb = bars + 8 * (BAR_FULLA + s);
      mbar_expect_tx(fb, STG1A);
      tma_load_3d_mc(sb + s * STG1A + rank * 16384, &tmX, fb, j * 64, par, gidx * 256 + rank * 128);
    };
    auto g1_issue_b = [&](int kb, int s) {
      const uint32_t fb = bars + 8 * (BAR_FULLB + s);
      mbar_expect_tx(fb, STG1B);
      tma_load_3d(sb + OFF_1B + s * STG1B, &tmW, fb, hp * 64, kb * 32, 0);
    };
    auto g2_k = [&](int kb) { return (kb < 2 ? hp : kb < 4 ? hp & 14 : hp & 12) ^ kb; };
    auto g2_issue_b = [&](uint32_t fb, uint32_t bytes, uint32_t dst, int k0, bool whole) {
      if (whole) {
        tma_load_3d(dst, &tmWo, fb, 0, k0, cb2 * 2);
      } else {
#pragma unroll
        for (int i = 0; i < 4; i++)
          tma_load_3d(dst + (i & 1) * XT + (i >> 1) * 4 * XT, &tmWp, fb, 0, k0 + (i >> 1) * 32, cb2 * 2 + (i & 1));
      }
      mbar_expect_tx(fb, bytes);
    };
    auto send_y = [&](uint32_t o, uint32_t step, int half) {
      const uint32_t peer = mapa(sb, rank ^ 1);
      o += OFF_X + (rank ^ 1) * 4096 + half * 2048 + lane * 16;
      uint4 a[8];
#pragma unroll
      for (int i = 0; i < 8; i++) a[i] = lds128(sb + o + (i >> 2) * step + (i & 2) * (XT / 2) + (i & 1) * 512);
#pragma unroll
      for (int i = 0; i < 8; i++)
        st_async128(peer + o + 1024 + (i >> 2) * step + (i & 2) * (XT / 2) + (i & 1) * 512,
                    peer + OFF_BAR + 8 * (BAR_LAND + half), a[i].x, a[i].y, a[i].z, a[i].w);
    };

    if (halo_cta) {
      if (hw == 0) {
        int s = 1, ph = 1;
#pragma unroll 1
        for (int n = 1; n < 32; n++) {
          mbar_wait(bars + 8 * (BAR_EMPTYB + s), ph);
          if (elect_one()) halo_issue(n, s);
          if (++s == NS1B) { s = 0; ph ^= 1; }
        }
      }
      __syncwarp();
    } else if (hw == 0) {
      uint32_t epoch = 0;
      if (MODE == 2) {
        if (lane < NS2) mbar_arrive_cluster_n(mapa(bars, rank) + 8 * (BAR_EMPTY2 + lane), 2);
      } else {
      if (lane == 0) {
        mbar_expect_tx(bars + 8 * BAR_U, 32768);
        mbar_expect_tx(bars + 8 * BAR_LAND, 8192);
        mbar_expect_tx(bars + 8 * (BAR_LAND + 1), 8192);
        mbar_expect_tx(bars + 8 * BAR_Q, 32768);
        prefetch_tmap(&tmQ);
      }
      {
        int sa = 1, pha = 1, sbb = 2, phb = 1;
#pragma unroll 1
        for (int kb = 2; kb < 32; kb++) {
          if (!(kb & 1)) {
            mbar_wait(bars + 8 * (BAR_EMPTYA + sa), pha);
            if (elect_one()) g1_issue_a(kb >> 1, sa);
            if (++sa == NS1A) { sa = 0; pha ^= 1; }
          }
          mbar_wait(bars + 8 * (BAR_EMPTYB + sbb), phb);
          if (kb > 2 && elect_one()) g1_issue_b(kb, sbb);
          __syncwarp();
          if (kb == 4) epoch = ld_relaxed(g_flag_o + cta);
          if (kb == 4) PROF2(27);
          if (kb == 1) PROF2(38);
          if (kb == 2) PROF2(39);
          if (++sbb == NS1B) { sbb = 0; phb ^= 1; }
        }
      }
      auto q_issue = [&](int i) {
        mbar_wait(bars + 8 * (i ? BAR_EMPTYB + 3 : BAR_EMPTYA + 1), i);
        if (elect_one())
          asm volatile(
              "cp.async.bulk.tensor.5d.shared::cluster.global.mbarrier::complete_tx::bytes [%0], [%1, {%3, %4, %4, %4, %5}], [%2];\n"
              ::"r"(sb + (i ? OFF_Q1 : OFF_Q0)), "l"(&tmQ), "r"(bars + 8 * BAR_Q), "r"((chb & ~1) * 8), "r"(0), "r"(rank * 32 + i * 64)
              : "memory");
        __syncwarp();
      };
      epoch++;
      if (lane == 0) {
        prefetch_tmap(&tmWo);
        prefetch_tmap(&tmWp);
        prefetch_tmap(&tmOb);
      }
      __syncwarp();
      {
        uint4 h[6] = {};
        if (gidx != 0) {
#pragma unroll 1
          for (int n = 0; n < SPIN_LIMIT; n++) {
            bool ok = true;
#pragma unroll
            for (int i = 0; i < 6; i++) h[i] = ld_b128(g_halo + cta * 192 + i * 32 + lane);
#pragma unroll
            for (int i = 0; i < 6; i++) ok = ok && h[i].w == epoch;
            if (__all_sync(0xffffffffu, ok)) break;
          }
          PROF(18);
        }
        q_issue(0);
        sts128(sb + OFF_KH + lane * 16, h[0].x, h[0].y, h[0].z, h[1].x);
        sts128(sb + OFF_KH + 512 + lane * 16, h[1].y, h[1].z, h[2].x, h[2].y);
        sts64(sb + OFF_KH + 1024 + lane * 8, h[3].x, h[3].y);
        sts64(sb + OFF_KH + 1280 + lane * 8, h[3].z, h[4].x);
        sts64(sb + OFF_KH + 1536 + lane * 8, h[4].y, h[4].z);
        sts64(sb + OFF_KH + 1792 + lane * 8, h[5].x, h[5].y);
        __syncwarp();
        if (lane == 0) mbar_arrive(bars + 8 * BAR_HALO);
      }
      q_issue(1);
      const uint32_t rb = mapa(bars, lane & 1);
      nb_sync(NB_OREADY, 288);
      if (lane == 0) {
        asm volatile("cp.async.bulk.global.shared::cta.bulk_group [%0], [%1], %2;\n" ::"l"(g_o + (size_t)cta * 16384),
                     "r"(sb + OFF_OP), "r"(32768) : "memory");
        bulk_commit();
      }
      if (lane < 2) {
#pragma unroll
        for (int i = 0; i < 4; i++) mbar_arrive_cluster(rb + 8 * (BAR_EMPTY2 + i + i / 2));
      }
      if (lane == 0) {
        bulk_wait0();
        st_release(g_flag_o + cta, epoch);
      }
      __syncwarp();
      PROF2(17);
      if (lane < 2) mbar_arrive_cluster(rb + 8 * (BAR_EMPTY2 + 2));
      }
      if (MODE != 1) {
        const __nv_bfloat16* osrc = g_o + (size_t)(rb2 >> 1) * 16 * 16384 + hsel * 8192;
        mbar_wait(bars + 8 * (BAR_EMPTY2 + 1), 0);
        if (elect_one()) {
          if (MODE == 0) {
            asm volatile("cp.async.bulk.shared::cluster.shared::cta.mbarrier::complete_tx::bytes [%0], [%1], %2, [%3];\n"
                         ::"r"(mapa(sb + g2_a(1, hsel), rank ^ 1)), "r"(sb + g2_a(0, hsel)), "r"(16384),
                         "r"(mapa(bars + 8 * (BAR_FULL2 + 1), rank ^ 1)) : "memory");
          } else {
            bulk_load(sb + g2_a(0, hsel), osrc + hp * 16384, 16384, bars + 8 * BAR_FULL2);
            bulk_load(sb + g2_a(1, hsel), osrc + (hp ^ 1) * 16384, 16384, bars + 8 * (BAR_FULL2 + 1));
          }
        }
        __syncwarp();
      }
      if (MODE != 2) {
        mbar_wait(bars + 8 * (BAR_Y + 2), 0);
        send_y(0, 4 * XT, 1);
        fence_async_smem();
        __syncwarp();
      }
      if (MODE != 1) {
        unsigned long long seq = G2_SEQ >> 12;
        uint32_t wbar = bars + 8 * (BAR_Y + 2), fb = bars + 8 * (BAR_FULL2 + 3), dst = sb + g2_b(3, rank), ph = MODE ? 1 : 0;
        int k0 = g2_k(3) * 64;
        bool whole = false;
#pragma unroll 1
        for (int kb = 4; kb <= 16; kb++) {
          mbar_wait(wbar, ph);
          if (elect_one()) g2_issue_b(fb, STG2, dst, k0, whole);
          __syncwarp();
          seq >>= 4;
          const int s = seq & 7;
          wbar = bars + 8 * (kb == G2_KB4 ? BAR_XFREE : BAR_EMPTY2B + s);
          ph = ((uint32_t)seq >> 3 & 1) ^ (kb == G2_KB4 && MODE == 0 ? 0 : 1);
          fb = bars + 8 * (BAR_FULL2 + s);
          dst = sb + g2_b(s, rank);
          k0 = ((hp & 12) ^ kb) * 64;
          whole = s < 3;
        }
      }
      __syncwarp();
    } else {
      if (MODE != 2) {
      const float dall = __bfloat162float(p.ssm_D[chb * 8 + lr]);
      {
        const int g = lane >> 2, t = lane & 3;
        uint32_t w[2][4];
#pragma unroll
        for (int h = 0; h < 2; h++) {
          const uint2 x = __ldg(reinterpret_cast<const uint2*>(p.shift_k + ((chb & ~1) * 8 + h * 8 + g) * 4));
          w[h][0] = __byte_perm(x.x, x.x, 0x1010);
          w[h][1] = __byte_perm(x.x, x.x, 0x3232);
          w[h][2] = __byte_perm(x.y, x.y, 0x1010);
          w[h][3] = __byte_perm(x.y, x.y, 0x3232);
        }
        auto swz = [](int r) { return (((r & 29) | ((r ^ (r >> 2)) & 2)) << 5) | (r & 16); };
        const uint32_t kring = sb + OFF_X + 4096 + (hw - 1) * 2 * XT, vring = kring + XT;
        const int s0 = rank * 32 + (hw - 1) * 11, s1 = hw == 3 ? rank * 32 + 32 : s0 + 11;
        const size_t goff = (size_t)(s0 * 32 + (lane >> 1)) * DM + (chb & ~1) * 8 + (lane & 1) * 8;
        const __nv_bfloat16* kg = p.k + goff;
        const __nv_bfloat16* vg = p.v + goff;
        const uint32_t d0 = swz(lane >> 1) ^ ((lane & 1) << 4), d1 = swz(16 + (lane >> 1)) ^ ((lane & 1) << 4);
        auto issue = [&](int st) {
          const uint32_t a = kring + ((st & 3) << 10);
          asm volatile("cp.async.cg.shared.global.L2::256B [%0], [%2], 16;\n"
                       "cp.async.cg.shared.global.L2::256B [%1], [%2 + 32768], 16;\n"
                       "cp.async.cg.shared.global.L2::256B [%0 + 8192], [%3], 16;\n"
                       "cp.async.cg.shared.global.L2::256B [%1 + 8192], [%3 + 32768], 16;\n"
                       ::"r"(a + d0), "r"(a + d1), "l"(kg), "l"(vg) : "memory");
          kg += 32 * DM;
          vg += 32 * DM;
          asm volatile("" : "+l"(kg), "+l"(vg));
        };
        const int xa = 8 * (lr >> 1) + 2 * lm + (lr & 1), xb = 8 * (lr >> 1) - 4 + 2 * (lm & 1) + (lr & 1);
        const uint32_t la = swz(xa), lb = swz(xb & 31);
        const int backb = xb < 0 ? 1 : 0;
        const uint32_t ud[2] = {mapa(sb + OFF_X + g * XT + t * 16, 0), mapa(sb + OFF_X + g * XT + t * 16, 1)};
        const uint32_t ub[2] = {mapa(bars + 8 * BAR_U, 0), mapa(bars + 8 * BAR_U, 1)};
        if (tid == 320) prefetch_l2(g_tab + (chb & 63) * 32);
        if (lane == 0) mbar_wait(bars + 8 * (BAR_FULLB + NS1B - 1), 0);
        __syncwarp();
        if (lane >= 24) cp_async16(kring + (((s0 - 1) & 3) << 10) + d1, s0 > 0 ? kg - 16 * DM : kg, s0 > 0 ? 16 : 0);
        issue(s0);
        asm volatile("cp.async.commit_group;\n" ::: "memory");
        issue(s0 + 1);
        asm volatile("cp.async.commit_group;\n" ::: "memory");
        const __nv_bfloat16* hg = p.ssm_k + (size_t)chb * 8 * SEQ + lane * 64;
        uint32_t tn = (uint32_t)clock();
#pragma unroll 1
        for (int st = s0; st < s1; st++) {
          tn += PSTEP;
          while ((int)((uint32_t)clock() - tn) < 0) __nanosleep(100);
          if (st + 2 < s1) issue(st + 2);
          if (hw == 1 && st - s0 < 8) prefetch_l2(hg);
          hg += SEQ;
          asm volatile("" : "+l"(hg));
          asm volatile("cp.async.commit_group;\n" ::: "memory");
          asm volatile("cp.async.wait_group 2;\n" ::: "memory");
          __syncwarp();
#pragma unroll
          for (int h = 0; h < 2; h++) {
            uint32_t e[6], vv[4], e4[4];
            ldsm4t(e4, kring + ((st & 3) << 10) + (la ^ (h << 4)));
            ldsm2t(e[0], e[1], kring + (((st - backb) & 3) << 10) + (lb ^ (h << 4)));
            ldsm4t(vv, vring + ((st & 3) << 10) + (la ^ (h << 4)));
            e[2] = e4[0]; e[3] = e4[1]; e[4] = e4[2]; e[5] = e4[3];
            uint32_t o[5];
#pragma unroll
            for (int i = 0; i < 5; i++) o[i] = __byte_perm(e[i], e[i + 1], 0x5432);
#pragma unroll
            for (int i = 0; i < 4; i++) {
              uint32_t a = bmul2(o[i], w[h][3]);
              a = bfma2(e[i + 1], w[h][2], a);
              a = bfma2(o[i + 1], w[h][1], a);
              a = bfma2(e[i + 2], w[h][0], a);
              vv[i] = bmul2(a, vv[i]);
            }
            st_async128(ud[h] + (st ^ (g & 1)) * 64, ub[h], vv[0], vv[1], vv[2], vv[3]);
          }
          __syncwarp();
        }
        fence_async_smem();
        PROF(16);
      }
      nb_sync(NB_HELP3, 96);
      if (hw == 1 && elect_one()) {
        mbar_expect_tx(bars + 8 * BAR_H, 8 * 4096 + 6144);
#pragma unroll 1
        for (int c = 0; c < 8; c++)
          bulk_load(sb + OFF_X + c * XT + 4096, p.ssm_k + (size_t)(chb * 8 + c) * SEQ, 4096, bars + 8 * BAR_H);
        bulk_load(sb + OFF_T16, g_tab, 2048, bars + 8 * BAR_H);
        bulk_load(sb + OFF_T32, g_tab + 512, 4096, bars + 8 * BAR_H);
      }
      __syncwarp();
      {
        if (WOP == 0) if (hw == 3) {
          const char* wo = (const char*)p.wo + chb * 16384 + lane * 128;
#pragma unroll
          for (int i = 0; i < 4; i++) prefetch_l2(wo + i * 4096);
        }
        const int ck = 16 * (lane >> 4) + 2 * lr + (((lane >> 3) ^ (lane >> 2)) & 1);
        const uint32_t xo = (ck >> 1) * 64, xs = ((ck & 1) ^ (lr >> 1)) << 4;
#pragma unroll 1
        for (int job = hw - 1; job < 16; job += 3) {
          const int c = job & 7;
          uint4 a[8];
          float dv = __shfl_sync(0xffffffffu, dall, c);
          if (job < 8 || lane) dv = 0.f;
          const uint32_t xt = sb + OFF_X + c * XT + (job >> 3) * 4096;
          mbar_wait(bars + 8 * (job < 8 ? BAR_U : BAR_H), 0);
#pragma unroll
          for (int i = 0; i < 8; i++) a[i] = lds128(xt + i * 512 + ((ck ^ (job < 8 ? (c & 1) << 2 : 0)) << 4));
          dv += bf_lo(a[0].x);
          uint32_t m[2] = {bmaxabs2(pack_bf16(dv, 0.f), bmaxabs2(a[0].x, a[0].y)), bmaxabs2(a[0].z, a[0].w)};
#pragma unroll
          for (int i = 1; i < 8; i++) {
            m[0] = bmaxabs2(bmaxabs2(m[0], a[i].x), a[i].y);
            m[1] = bmaxabs2(bmaxabs2(m[1], a[i].z), a[i].w);
          }
          m[0] = bmaxabs2(m[0], m[1]);
          const int f = max(252 - (int)(__reduce_max_sync(0xffffffffu, max(m[0] & 0x7fffu, (m[0] >> 16) & 0x7fffu)) >> 7), 1);
          if (lane == 0) asm volatile("st.shared.u32 [%0], %1;\n" ::"r"(sb + OFF_EX + job * 4), "r"(f) : "memory");
          if (f < 113) {
#pragma unroll
            for (int i = 0; i < 8; i++)
              a[i] = make_uint4(bmul2(a[i].x, f * 0x00800080u), bmul2(a[i].y, f * 0x00800080u), bmul2(a[i].z, f * 0x00800080u),
                                bmul2(a[i].w, f * 0x00800080u));
          }
          const uint32_t mul = (f < 113 ? 15 : f - 112) * 0x00800080u;
          auto cv = [&](uint32_t x) {
            x = bmul2(x, mul);
            return (x & 0x0fff0fffu) * 7 + x;
          };
          const uint32_t dst = xt + xo;
#pragma unroll
          for (int i = 0; i < 8; i++)
            sts128(dst + (i >> 2) * 2048 + (i & 1) * 1024 + (xs ^ ((i & 2) << 4)),
                   i ? cv(a[i].x) : __byte_perm(pack_f16(dv * __uint_as_float(f << 23), 0.f), cv(a[i].x), 0x7610), cv(a[i].y),
                   cv(a[i].z), cv(a[i].w));
        }
        fence_async_smem();
        __syncwarp();
        if (lane == 0) mbar_arrive(bars + 8 * BAR_X);
        if (WOP == 1) if (hw == 3) {
          const char* wo = (const char*)p.wo + chb * 16384 + lane * 128;
#pragma unroll
          for (int i = 0; i < 4; i++) prefetch_l2(wo + i * 4096);
        }
        PROF(19);
      }
      if (hw < 3) {
#pragma unroll 1
        for (int n = 0; n < SPIN_LIMIT && !mbar_try(bars + 8 * (BAR_Y + hw - 1), 0); n++) __nanosleep(100);
        send_y((hw - 1) * 4 * XT, 2 * XT, 0);
        __syncwarp();
        if (lane == 0) mbar_arrive(bars + 8 * (BAR_Y + 2));
        PROF(32);
        const int c8 = 2 * lm + (lr & 1), src = (lr >> 1) & 1;
        uint32_t fa = sb + OFF_X + c8 * XT + rank * 4096 + (src == rank ? 0 : 1024) + (hw - 1) * 512;
        const uint32_t fx = ((lr >> 2) ^ ((lr & 3) << 1)) << 4;
        uint32_t qa = sb + OFF_Q0 + (hw - 1) * 8192 + (lane >> 3) * 128 + (lane & 2) * 32 + (lane & 4) * 8 + (lane & 1) * 16;
        uint4* og = reinterpret_cast<uint4*>(p.out + (size_t)(rank * 512 + (hw - 1) * 256 + (lane & 2) * 4 + (lane >> 2)) * (2 * DM) +
                                             (chb & ~1) * 8 + (lane & 1) * 8);
        mbar_wait(bars + 8 * BAR_Q, 0);
        uint32_t tn = 0;
#pragma unroll 1
        for (int j = 0; j < 16; j++) {
          if (j == JS && hw == 2) {
            mbar_wait(bars + 8 * (BAR_Y + 3), 0);
            send_y(2 * XT, 4 * XT, 1);
            fence_async_smem();
            __syncwarp();
            if (lane == 0) mbar_arrive(bars + 8 * BAR_XFREE);
            tn = (uint32_t)clock();
          }
          if (!(j & 7)) {
            mbar_wait(bars + 8 * (BAR_LAND + (j >> 3)), 0);
            tn = (uint32_t)clock() + (hw - 1) * (FPACE / 2);
            PROF2(33 + (j >> 1));
          }
#pragma unroll
          for (int i = 0; i < 2; i++) {
            uint32_t y[4];
            const uint4 q = lds128(qa + i * 512);
            ldsm4t(y, fa + (j & 6) * 64 + (fx ^ (i << 5) ^ ((j & 1) << 6) ^ ((j & 2) << 3)));
            while ((int)((uint32_t)clock() - tn) < 0) __nanosleep(FSL);
            tn += hw == 2 ? FPACE2 : FPACE;
            og[i * 16 * (2 * DM / 8)] = make_uint4(bmul2(q.x, y[0]), bmul2(q.y, y[1]), bmul2(q.z, y[2]), bmul2(q.w, y[3]));
          }
          qa += j == 7 ? OFF_Q1 - OFF_Q0 - 7168 : 1024;
          if (j == 7) fa += 2048;
          og += (j == 7 ? 1024 - 224 : 32) * (2 * DM / 8);
        }
        PROF(22);
      }
      }
      if (MODE != 1 && hw == 3) {
        const uint32_t epoch = ld_relaxed(g_flag_o + cta) + 1;
        if (MODE == 0) nb_sync(NB_G1END, 288);
        if (BDEL) __nanosleep(BDEL);
        if (elect_one()) {
#pragma unroll
          for (int kb = 0; kb < 3; kb++)
            g2_issue_b(bars + 8 * (BAR_FULL2 + kb), kb || MODE ? STG2 : STG2 / 2, sb + g2_b(kb, 0), g2_k(kb) * 64, true);
        }
        __syncwarp();
        const __nv_bfloat16* osrc = g_o + (size_t)(rb2 >> 1) * 16 * 16384 + hsel * 8192;
        if (MODE == 0) __nanosleep(POLL0);
        const uint32_t* flag = g_flag_o + (rb2 >> 1) * 16 + g2_k(lane & 15);
        uint32_t ready = MODE == 0 ? 0u : ~0u;
        unsigned long long seq = G2_SEQ >> 8;
#pragma unroll 1
        for (int kb = 2; kb < 16; kb++, seq >>= 4) {
          uint32_t so = bars + (seq & 7) * 8, dst = sb + g2_a(seq & 7, hsel) + rank * 8192;
          const uint32_t ph = (uint32_t)seq >> 3 & 1;
          const __nv_bfloat16* src = osrc + rank * 4096 + (uint32_t)g2_k(kb) * 16384;
          asm volatile("" : "+r"(so), "+r"(dst), "+l"(src));
          if (!(ready >> kb & 1)) {
#pragma unroll 1
            for (int n = 0; n < SPIN_LIMIT && !(ready >> kb & 1); n++)
              ready = __ballot_sync(0xffffffffu, ld_acquire(flag) == epoch);
            fence_async_all();
          }
          if (kb == 2) PROF(21);
          if (MODE == 0 && kb == G2_KB4 && rank == 1) mbar_wait(bars + 8 * BAR_TAB, 0);
          mbar_wait(so + 8 * BAR_EMPTY2, ph);
          if (elect_one()) {
            asm volatile(
                "cp.async.bulk.shared::cluster.global.mbarrier::complete_tx::bytes.multicast::cluster [%0], [%1], %2, [%3], %4;\n"
                ::"r"(dst), "l"(src), "r"(8192), "r"(so + 8 * BAR_FULL2), "h"((uint16_t)3) : "memory");
          }
          __syncwarp();
        }
      }
    }
    cluster_sync_all();
    PROF_DUMP();
  } else {
    asm volatile("barrier.cluster.arrive.relaxed.aligned;\n" ::: "memory");
    asm volatile("setmaxnreg.inc.sync.aligned.u32 %0;\n" :: "n"(REG_MATH));
    if (halo_cta || MODE == 2) asm volatile("barrier.cluster.wait.aligned;\n" ::: "memory");
    if (warp == 0) PROF2(26);
    const int wg = warp >> 2;
    const int wtid = tid & 127;
    const bool signaller = (wtid == 0) || (wtid == 32);
    const uint32_t rbars = mapa(bars, wtid >> 5 & 1);

    if (halo_cta) {
      const uint32_t epoch = ld_relaxed(g_flag_o + 16 + blockIdx.x * 4) + 1;
      float acc0[64], acc1[64];
      int s = wg, ph = 0;
#pragma unroll 1
      for (int kb = 0; kb < 16; kb++) {
        mbar_wait(bars + 8 * (BAR_FULLB + s), ph);
        const uint32_t st = sb + s * STGH;
        const uint64_t da = mkdesc(st, 16, 1024, 1);
        const uint64_t db = mkdesc(st + 8192, 8192, 1024, 1);
        wg_fence();
#pragma unroll
        for (int kk = 0; kk < 4; kk++) {
          wgmma_n128(acc0, da + 2 * kk, db + 128 * kk, kb + kk);
          wgmma_n128(acc1, da + 2 * kk, db + 1024 + 128 * kk, kb + kk);
        }
        wg_commit();
        wg_wait<0>();
        if (kb == 15) PROF(37);
        if (wtid < 2) mbar_arrive(bars + 8 * (BAR_EMPTYB + s));
        if ((s += 2) >= NS1B) { s -= NS1B; ph ^= 1; }
      }
      fence_regs(acc0);
      fence_regs(acc1);
      if ((warp & 3) != 3) {
        auto put = [&](const float (&acc)[64], int hp0) {
#pragma unroll
          for (int n = 0; n < 4; n++) {
            uint32_t x[8];
#pragma unroll
            for (int c = 0; c < 8; c++) {
              x[c] = pack_bf16(acc[32 * (n >> 1) + 4 * c + 2 * (n & 1)], acc[32 * (n >> 1) + 4 * c + 2 * (n & 1) + 1]);
              if (wg) x[c] = movm(x[c]);
            }
            uint4* dst = g_halo + (((n & 1) * 4 + (warp & 3) + 1) * 16 + blockIdx.x * 4 + hp0 + (n >> 1)) * 192 + wg * 96 + lane;
            st_b128(dst, x[0], x[1], x[2], epoch);
            st_b128(dst + 32, x[3], x[4], x[5], epoch);
            st_b128(dst + 64, x[6], x[7], 0, epoch);
          }
        };
        put(acc0, 0);
        put(acc1, 2);
      }
      PROF(36);
      cluster_sync_all();
      return;
    }

    float acc[64];
    const uint32_t g2rel = wtid ? mapa(bars, rank) + 8 * BAR_EMPTY2B : mapa(bars, wg) + 8 * BAR_EMPTY2;
    uint32_t g2a = (uint32_t)mkdesc(sb + wg * 8192, 16, 0, 0), g2b = (uint32_t)mkdesc(sb, 8192, 0, 0);
    auto g2_block = [&](bool first, int s, int ph) {
      mbar_wait(bars + 8 * (BAR_FULL2 + s), ph);
      const uint32_t da = g2a + (g2_a(s, hsel) >> 4), db = g2b + (g2_b(s, rank) >> 4), dc = db + (g2_bk(s) >> 4);
      wg_fence();
      if (first) wgmma_n128z(acc, da, db);
      else wgmma_n128a(acc, da, db);
      wgmma_n128a(acc, da + 2, db + 128);
      wgmma_n128a(acc, da + 4, dc);
      wgmma_n128a(acc, da + 6, dc + 128);
      wg_commit();
    };
    if (MODE != 2) {
    uint32_t a1[2][4], sc[2];
    C2 t[2];
    {
      float acc0[96], acc1[96];
      int sa = 0, pha = 0;
      uint64_t db0 = mkdesc(sb + OFF_1B, 4096, 1024, 1);
      const uint64_t da0 = mkdesc(sb + wg * 16384, 16, 2048, 1);
      const bool sigb = wtid == 64;
      uint32_t rela = 0;
#pragma unroll 1
      for (int r = 0; r < 3; r++) {
#pragma unroll
        for (int i = 0; i < 2 * NS1B; i++) {
          const uint64_t da = da0 + sa * (STG1A >> 4) + (i & 1) * 4, db = db0 + (i % NS1B) * (STG1B >> 4);
          if (i || r) {
            if (!(i & 1)) mbar_wait(bars + 8 * (BAR_FULLA + sa), pha);
            mbar_wait(bars + 8 * (BAR_FULLB + i % NS1B), i / NS1B);
          } else {
            asm volatile("cp.async.wait_group 0;\n" ::: "memory");
            fence_async_smem();
            nb_sync(NB_FIRST, 256);
            PROF(0 + wg);
          }
          wg_fence();
          wgmma_n192(acc0, da + 64, db, i ? 1 : r);
          wgmma_n192(acc1, da, db, i ? 1 : r);
          wgmma_n192(acc0, da + 66, db + 128, 1);
          wgmma_n192(acc1, da + 2, db + 128, 1);
          wg_commit();
          wg_wait<1>();
          if (i || r) {
            if (sigb) mbar_arrive(bars + 8 * (BAR_EMPTYB + (i + NS1B - 1) % NS1B));
            if (!(i & 1) && signaller) mbar_arrive_cluster(rela);
          } else {
            asm volatile("barrier.cluster.wait.aligned;\n" ::: "memory");
          }
          if (i & 1) {
            rela = rbars + 8 * (BAR_EMPTYA + sa);
            if (++sa == NS1A) { sa = 0; pha ^= 1; }
          }
        }
        db0 += p.zero;
      }
      const int lr = lane & 7, lm = lane >> 3;
      const bool le0 = 2 * (lane & 3) <= (lane >> 2), le1 = 2 * (lane & 3) + 1 <= (lane >> 2);
      const uint32_t maskLE = (le0 ? 0x0000FFFFu : 0u) | (le1 ? 0xFFFF0000u : 0u);
      uint32_t q[4][8], k[5][8], vt[5][8];
      {
        static_assert(15 % NS1A == 0 && 30 % NS1B == 0, "slots of the last k blocks");
        asm volatile("ld.volatile.global.v4.u32 {%0,%1,%2,%3}, [%4];\n"
                     : "=r"(t[0].r), "=r"(t[1].r), "=r"(t[0].i), "=r"(t[1].i) : "l"(g_tab + 1536 + wtid * 4) : "memory");
        mbar_wait(bars + 8 * BAR_FULLA, 1);
        mbar_wait(bars + 8 * BAR_FULLB, 0);
        mbar_wait(bars + 8 * (BAR_FULLB + 1), 0);
        mbar_wait(bars + 8 * (BAR_EMPTYA + 1), 0);
        mbar_wait(bars + 8 * BAR_H, 0);
        const uint64_t da = mkdesc(sb + wg * 16384, 16, 2048, 1);
        const uint64_t db = mkdesc(sb + OFF_1B, 4096, 1024, 1);
        wg_fence();
#pragma unroll
        for (int i = 0; i < 4; i++) wgmma_n192(acc0, da + 64 + 2 * i, db + (i >> 1) * (STG1B >> 4) + (i & 1) * 128, 1);
        wg_commit();
#pragma unroll
        for (int i = 0; i < 2; i++) wgmma_n192(acc1, da + 2 * i, db + (i >> 1) * (STG1B >> 4) + (i & 1) * 128, 1);
        wg_commit();
        wg_wait<1>();
        fence_regs(acc0);
        PROFA(45, 0);
        attn_pack<8, 1, false>(acc0, k[4]);
        attn_pack<16, 1, true>(acc0, vt[4]);
        const uint32_t kh = sb + (warp == 7 ? OFF_OP + 7 * 4096 : OFF_KH + (warp + 1) * 2048) + lane * 16;
        sts128(kh, k[4][0], k[4][1], k[4][2], k[4][3]);
        sts128(kh + 512, k[4][4], k[4][5], k[4][6], k[4][7]);
#pragma unroll
        for (int i = 0; i < 4; i++) sts64(kh - lane * 8 + 1024 + 256 * i, vt[4][2 * i], vt[4][2 * i + 1]);
#pragma unroll
        for (int i = 2; i < 4; i++) wgmma_n192(acc1, da + 2 * i, db + (i >> 1) * (STG1B >> 4) + (i & 1) * 128, 1);
        wg_commit();
        attn_pack<0, 0, false>(acc0, q[1]);
        attn_pack<0, 1, false>(acc0, q[3]);
        attn_pack<8, 0, false>(acc0, k[2]);
        attn_pack<16, 0, true>(acc0, vt[2]);
        uint32_t z = p.zero;
#pragma unroll
        for (int i = 0; i < 8; i++) z &= q[1][i] & q[3][i];
#pragma unroll
        for (int i = 0; i < 8; i += 2) z &= k[2][i] & k[2][i + 1];
        __syncwarp();
        if (lane == 0) mbar_arrive(bars + 8 * BAR_STG + z);
        wg_wait<0>();
        fence_regs(acc1);
        if (MODE == 0) nb_arrive(NB_G1END, 288);
      }
      PROF(2 + wg);
      mbar_wait(bars + 8 * (warp == 0 ? BAR_HALO : BAR_STG), 0);
      {
        const uint32_t kh = sb + OFF_KH + warp * 2048 + lane * 16;
#pragma unroll
        for (int i = 0; i < 2; i++) {
          const uint4 t = lds128(kh + 512 * i);
          k[0][4 * i] = t.x; k[0][4 * i + 1] = t.y; k[0][4 * i + 2] = t.z; k[0][4 * i + 3] = t.w;
        }
#pragma unroll
        for (int i = 0; i < 4; i++) {
          const uint2 t = lds64(kh - lane * 8 + 1024 + 256 * i);
          vt[0][2 * i] = t.x; vt[0][2 * i + 1] = t.y;
        }
      }
      attn_pack<0, 0, false>(acc1, q[0]);
      attn_pack<0, 1, false>(acc1, q[2]);
      attn_pack<8, 0, false>(acc1, k[1]);
      attn_pack<8, 1, false>(acc1, k[3]);
      {
        float x[8][2];
        uint32_t pp[8];
        const bool first = warp == 0 && gidx == 0;
#pragma unroll
        for (int hd = 0; hd < 2; hd++) {
#pragma unroll
          for (int j = 0; j < 4; j += 2) {
            float s0[4], s1[4], s2[4];
            attn_qk(s2, q[j], q[j + 1], k[j + 2], 4 * hd);
            attn_qk(s1, q[j], q[j + 1], k[j + 1], 4 * hd);
            attn_qk(s0, q[j], q[j + 1], k[j], 4 * hd);
            if (j == 0 && first) s0[0] = s0[1] = -1e9f / 0.17677669529663687f;
            x[2 * j + hd][0] = le0 ? s1[0] : s0[0];
            x[2 * j + hd][1] = le1 ? s1[1] : s0[1];
            x[2 * j + 2 + hd][0] = le0 ? s2[2] : s1[2];
            x[2 * j + 2 + hd][1] = le1 ? s2[3] : s1[3];
          }
        }
        PROFA(40, __float_as_uint(x[1][0] + x[7][1]));
        attn_pack<16, 0, true>(acc1, vt[1]);
        attn_pack<16, 1, true>(acc1, vt[3]);
        quad_softmax<8>(x, pp);
        PROFA(41, pp[1] + pp[7]);
        ldsm4(a1[0], sb + OFF_T32 + (warp & 3) * 1024 + lane * 16);
        ldsm4(a1[1], sb + OFF_T32 + 512 + (warp & 3) * 1024 + lane * 16);
        const uint32_t obase = sb + OFF_OP + (warp * 32 + lr) * 128;
#pragma unroll
        for (int n = 0; n < 8; n++) {
          const uint32_t dst = obase + (n >> 1) * 1024 + (((4 * (n & 1) + lm) ^ lr) << 4);
          if (PVS && (n & 2)) attn_pv<true>(dst, vt[n >> 1], vt[(n >> 1) + 1], 4 * (n & 1), pp[n], maskLE);
          else attn_pv<false>(dst, vt[n >> 1], vt[(n >> 1) + 1], 4 * (n & 1), pp[n], maskLE);
        }
      }
      PROFA(42, 0);
    }

    {
      const int w = warp & 3;
      const int lr = lane & 7, lm = lane >> 3;
      const uint32_t xb = sb + OFF_X + wg * 4 * XT;
      auto uo = [](int c) { return (c & 1) * 2 * XT + (c >> 1) * 2048; };
      const uint64_t dc2 = mkdesc(sb + OFF_T16, 512, 128, 0), dc3 = mkdesc(sb + OFF_T16, 128, 512, 0);
      const uint64_t dc4 = mkdesc(sb + OFF_T32, 128, 256, 0);
      const uint64_t dx = mkdesc(xb, 4096, 512, 2), dz = mkdesc(xb, 4096, 256, 3);
      const uint32_t zs = xb + (w * 16 + (lm & 1) * 8 + lr) * 32 + (((lm >> 1) ^ (lr >> 2)) << 4);
      const uint32_t ys = xb + w * 4096 + (lm >> 1) * 256 + ((lr * 32 + (((lm & 1) ^ (lr >> 2)) << 4)) ^ (rank << 6) ^ ((w & 2) << 4));
      const bool own = (w & 1) == rank;
      const uint32_t ybar = mapa(bars, own ? rank ^ 1 : rank) + 8 * BAR_Y;
      uint32_t d[2][32], pa[2][4][2][4], e[4][4][8], ya[2][2][2][4], v[2][2][8];
      C2 s1[2][2][2];
      float o[2][16];
      auto rows = [&](int c) {
        fft_rows(d[c & 1], a1, dx + (uo(c) >> 4));
        wg_commit();
      };
      auto cols = [&](int c) {
        const int s = c & 1;
        fence_regs(d[s]);
#pragma unroll
        for (int i = 0; i < 16; i++) {
          const C2 z = crot(C2{d[s][2 * i], d[s][2 * i + 1]}, t[i & 1]);
          pa[s][i >> 2][i & 1][(i >> 1) & 1] = z.r;
          pa[s][i >> 2][i & 1][2 + ((i >> 1) & 1)] = z.i;
        }
        wg_fence();
#pragma unroll
        for (int i = 0; i < 4; i++) fft_cols<0>(e[c][i], pa[s][i], dc2);
        wg_commit();
      };
      auto prod = [&](int c, int n) {
        const int s = c & 1;
        fence_regs(e[c][2 * n]);
        fence_regs(e[c][2 * n + 1]);
#pragma unroll
        for (int j = 0; j < 2; j++) {
          const C2 u0 = cget(e[s][2 * n], j, 0), u1 = cget(e[s][2 * n], j, 1);
          const C2 h0 = cget(e[s][2 * n + 1], j, 0), h1 = cget(e[s][2 * n + 1], j, 1);
          C2 y0, y1;
          if (c < 2) {
            y0 = cmul(h0, u0);
            s1[s][n][j] = cfma(h0, u1, cmul(h1, u0));
            y1 = C2{hadd2(s1[s][n][j].r, y0.i), hadd2(s1[s][n][j].i, hneg2(y0.r))};
          } else {
            const C2 u2 = cget(e[c][2 * n], j, 0), u3 = cget(e[c][2 * n], j, 1);
            const C2 h2 = cget(e[c][2 * n + 1], j, 0), h3 = cget(e[c][2 * n + 1], j, 1);
            const C2 s2 = cfma(h0, u2, cfma(h2, u0, cmul(h1, u1)));
            y0 = C2{hadd2(s2.r, s1[s][n][j].i), hadd2(s2.i, hneg2(s1[s][n][j].r))};
            y1 = cfma(h0, u3, cfma(h1, u2, cfma(h2, u1, cfma(h3, u0, C2{s2.i, hneg2(s2.r)}))));
          }
          ya[s][n][j][0] = y0.r;
          ya[s][n][j][1] = y1.r;
          ya[s][n][j][2] = y0.i;
          ya[s][n][j][3] = y1.i;
        }
      };
      auto icols = [&](int c) {
        wg_fence();
        fft_cols<1>(v[c & 1][0], ya[c & 1][0], dc3);
        fft_cols<1>(v[c & 1][1], ya[c & 1][1], dc3);
        wg_commit();
      };
      auto stage = [&](int c) {
        const int s = c & 1;
        fence_regs(v[s][0]);
        fence_regs(v[s][1]);
#pragma unroll
        for (int b = 0; b < 4; b++) {
          const C2 x0 = cget(v[s][b >> 1], 0, b & 1), x1 = cget(v[s][b >> 1], 1, b & 1);
          const C2 z0 = crot(C2{x0.i, x0.r}, t[0]), z1 = crot(C2{x1.i, x1.r}, t[1]);
          stsm4(zs + uo(c) + b * 4096, z0.i, z0.r, z1.i, z1.r);
        }
      };
      auto back = [&](int c) {
        fft_back(o[c & 1], dz + (uo(c) >> 4), dc4);
        wg_commit();
      };
      auto out = [&](int c) {
        float (&r)[16] = o[c & 1];
        fence_regs(r);
#pragma unroll
        for (int i = 0; i < 16; i += 8)
          stsm4t(ys + uo(c) + 64 * i, bmul2(pack_bf16(r[i], r[i + 1]), sc[c & 1]), bmul2(pack_bf16(r[i + 2], r[i + 3]), sc[c & 1]),
                 bmul2(pack_bf16(r[i + 4], r[i + 5]), sc[c & 1]), bmul2(pack_bf16(r[i + 6], r[i + 7]), sc[c & 1]));
      };
      auto signal = [&](int yb, int land) {
        __syncwarp();
        if (lane == 0) {
          mbar_arrive_cluster(ybar + 8 * yb);
          if (own && land >= 0) mbar_arrive(bars + 8 * (BAR_LAND + land));
        }
      };
      mbar_wait(bars + 8 * BAR_X, 0);
      wg_fence();
      rows(0);
      rows(1);
      fence_async_smem();
      nb_arrive(NB_OREADY, 288);
#pragma unroll
      for (int i = 0; i < 2; i++) {
        const uint32_t ex = sb + OFF_EX + wg * 16 + (w & 2) * 2 + 8 * i;
        sc[i] = min(max(381 - (int)lds32(ex) - (int)lds32(ex + 32), 1), 254) * 0x00800080u;
      }
      PROF(34 + wg);
      wg_wait<1>();
      cols(0);
      wg_wait<1>();
      cols(1);
      rows(2);
      nb_sync(NB_CONV + wg, 128);
      wg_wait<2>();
      prod(0, 0);
      prod(0, 1);
      icols(0);
      wg_wait<2>();
      prod(1, 0);
      prod(1, 1);
      icols(1);
      PROF3(40 + 10 * wg);
      wg_wait<1>();
      stage(0);
      wg_wait<0>();
      stage(1);
      fence_async_smem();
      cols(2);
      PROF3(41 + 10 * wg);
      nb_sync(NB_CONV + wg, 128);
      back(0);
      back(1);
      wg_wait<2>();
      prod(2, 0);
      wg_fence();
      rows(3);
      wg_wait<1>();
      out(0);
      out(1);
      signal(wg, 0);
      PROF3(42 + 10 * wg);
      prod(2, 1);
      icols(2);
      wg_wait<1>();
      cols(3);
      PROF3(43 + 10 * wg);
      wg_wait<1>();
      stage(2);
      fence_async_smem();
      wg_wait<0>();
      prod(3, 0);
      nb_sync(NB_CONV + wg, 128);
      wg_fence();
      back(2);
      prod(3, 1);
      icols(3);
      PROF3(44 + 10 * wg);
      wg_wait<1>();
      out(2);
      signal(2, -1);
      wg_wait<0>();
      stage(3);
      PROF3(45 + 10 * wg);
      fence_async_smem();
      nb_sync(NB_CONV + wg, 128);
      wg_fence();
      back(3);
      constexpr int G = MODE == 0 && EARLY;
      if (MODE == 0) mbar_wait(bars + 8 * (BAR_EMPTY2 + 4), 0);
      if (G) g2_block(true, 0, 0);
      wg_wait<G>();
      if (lane == 0) mbar_arrive_cluster(mapa(bars, 1) + 8 * BAR_TAB);
      out(3);
      signal(3, 1);
      PROF(6 + wg);
    }
    }

    if (MODE != 1) {
      if (MODE == 2 || !EARLY) g2_block(true, 0, 0);
      const int lr = lane & 7, lm = lane >> 3;
      const uint32_t wb = sb + g2_a(1, 0) + warp * 2048;
      const int orow = (rb2 & 7) * 128 + warp * 16;
      uint4* og = reinterpret_cast<uint4*>(p.out + (size_t)(2 * (orow + lm) + (rb2 >> 3)) * (2 * DM) + DM + cb2 * 128 + lr * 8);
      uint32_t wst = wb + (lr + 8 * (lm & 1)) * 128, wsx = ((lm >> 1) ^ lr) << 4, wld = wb + lm * 128, wlx = (lr ^ lm) << 4;
      asm volatile("" : "+l"(og), "+r"(wst), "+r"(wsx), "+r"(wld), "+r"(wlx));
      static_assert(ENDG == NS2 && (G2SEQ >> 4 & 0xfffff) == (G2SEQ >> 24 & 0xfffff) && (G2SEQ >> 4 & 0xfffff) == G2SEQ >> 44, "rounds");
#pragma unroll 1
      for (int r = 0; r < 3; r++) {
        const bool hold = r == 2 && wg != LEADWG;
        const uint32_t rel0 = g2rel + (r ? 8 * (G2SEQ >> 20 & 7) : 0);
        if (hold) {
          wg_wait<0>();
          if (signaller) mbar_arrive_cluster(rel0);
          nb_sync(NB_LEAD, 256);
        }
#pragma unroll
        for (int i = 1; i <= NS2; i++) {
          const int s = G2SEQ >> (4 * i) & 7;
          g2_block(false, s, (r & 1) ^ (s == 0));
          if (warp == LEADWG * 4) PROF2(40 + 5 * r + i);
          if (i == 1 ? !hold : r < 2) {
            wg_wait<1>();
            if (signaller) mbar_arrive_cluster(i == 1 ? rel0 : g2rel + 8 * (G2SEQ >> (4 * i - 4) & 7));
          }
        }
        if (r == 0) PROF(8 + wg);
        g2a += p.zero;
        g2b += p.zero;
      }
      if (wg == LEADWG) nb_arrive(NB_LEAD, 256);
      asm volatile("barrier.cluster.arrive.relaxed.aligned;\n" ::: "memory");
      wg_wait<0>();
      fence_regs(acc);
      PROF(10 + wg);
#pragma unroll
      for (int h = 0; h < 2; h++) {
        const uint32_t b = h * (g2_a(3, 0) - g2_a(1, 0));
#pragma unroll
        for (int j = 8 * h; j < 8 * h + 8; j += 2)
          stsm4(wst + b + (wsx ^ ((j & 7) << 4)), pack_bf16(acc[4 * j], acc[4 * j + 1]),
                pack_bf16(acc[4 * j + 2], acc[4 * j + 3]), pack_bf16(acc[4 * j + 4], acc[4 * j + 5]),
                pack_bf16(acc[4 * j + 6], acc[4 * j + 7]));
        if (OTMA == 2 || (OTMA == 1 && wg == LEADWG)) {
          fence_async_smem();
          __syncwarp();
          if (elect_one()) {
            tma_store_3d(&tmOb, wb + b, DM + cb2 * 128 + h * 64, rb2 >> 3, orow);
            bulk_commit();
          }
        } else {
          __syncwarp();
          uint4 v[4];
#pragma unroll
          for (int i = 0; i < 4; i++) v[i] = lds128(wld + b + i * 512 + (wlx ^ ((i & 1) << 6)));
#pragma unroll
          for (int i = 0; i < 4; i++) og[(size_t)i * 8 * (2 * DM / 8) + h * 8] = v[i];
        }
      }
      PROF(12 + wg);
      if (OTMA) bulk_wait0();
    } else {
      asm volatile("barrier.cluster.arrive.relaxed.aligned;\n" ::: "memory");
    }
    asm volatile("barrier.cluster.wait.aligned;\n" ::: "memory");
  }
}

typedef CUresult (*EncodeFn)(CUtensorMap*, CUtensorMapDataType, cuuint32_t, void*, const cuuint64_t*, const cuuint64_t*,
                             const cuuint32_t*, const cuuint32_t*, CUtensorMapInterleave, CUtensorMapSwizzle,
                             CUtensorMapL2promotion, CUtensorMapFloatOOBfill);

void make_map(EncodeFn enc, CUtensorMap* tm, const void* base, int rank, const cuuint64_t* dims, const cuuint64_t* strides,
              const cuuint32_t* box, CUtensorMapSwizzle swz) {
  cuuint32_t es[5] = {1, 1, 1, 1, 1};
  enc(tm, CU_TENSOR_MAP_DATA_TYPE_BFLOAT16, rank, const_cast<void*>(base), dims, strides, box, es,
      CU_TENSOR_MAP_INTERLEAVE_NONE, swz, CU_TENSOR_MAP_L2_PROMOTION_L2_256B, CU_TENSOR_MAP_FLOAT_OOB_FILL_NONE);
}

}

extern "C" void kernel_launch(void* const* d_in, const int* in_sizes, int n_in, void* d_out, int out_size) {
  static EncodeFn enc = nullptr;
  static bool coresident = true;
  if (!enc) {
    void* fn = nullptr;
    cudaDriverEntryPointQueryResult qr;
    cudaGetDriverEntryPoint("cuTensorMapEncodeTiled", &fn, cudaEnableDefault, &qr);
    enc = (EncodeFn)fn;
    cudaFuncSetAttribute(fused_kernel<0>, cudaFuncAttributeMaxDynamicSharedMemorySize, SMEM_BYTES);
    cudaFuncSetAttribute(fused_kernel<1>, cudaFuncAttributeMaxDynamicSharedMemorySize, SMEM_BYTES);
    cudaFuncSetAttribute(fused_kernel<2>, cudaFuncAttributeMaxDynamicSharedMemorySize, SMEM_BYTES);
    cudaLaunchConfig_t cfg = {};
    cfg.gridDim = dim3(NCTA);
    cfg.blockDim = dim3(NTHREADS);
    cfg.dynamicSmemBytes = SMEM_BYTES;
    cudaLaunchAttribute at;
    at.id = cudaLaunchAttributeClusterDimension;
    at.val.clusterDim.x = 2;
    at.val.clusterDim.y = 1;
    at.val.clusterDim.z = 1;
    cfg.attrs = &at;
    cfg.numAttrs = 1;
    int nclusters = 0;
    if (cudaOccupancyMaxActiveClusters(&nclusters, fused_kernel<0>, &cfg) == cudaSuccess) coresident = nclusters >= NCTA / 2;
    (void)cudaGetLastError();
  }
  CUtensorMap tmX, tmW, tmWo, tmWp, tmQ, tmOb, tmXh, tmWh;
  {
    cuuint64_t dims[3] = {1024, 2, 1024};
    cuuint64_t str[2] = {2048, 4096};
    cuuint32_t box[3] = {64, 1, 128};
    make_map(enc, &tmX, d_in[6], 3, dims, str, box, CU_TENSOR_MAP_SWIZZLE_128B);
  }
  {
    cuuint64_t dims[3] = {1024, 1024, 3};
    cuuint64_t str[2] = {6144, 2048};
    cuuint32_t box[3] = {64, 32, 3};
    make_map(enc, &tmW, d_in[7], 3, dims, str, box, CU_TENSOR_MAP_SWIZZLE_128B);
  }
  {
    cuuint64_t dims[3] = {64, 1024, 16};
    cuuint64_t str[2] = {2048, 128};
    cuuint32_t box[3] = {64, 64, 2};
    cuuint32_t piece[3] = {64, 32, 1};
    make_map(enc, &tmWo, d_in[8], 3, dims, str, box, CU_TENSOR_MAP_SWIZZLE_128B);
    make_map(enc, &tmWp, d_in[8], 3, dims, str, piece, CU_TENSOR_MAP_SWIZZLE_128B);
  }
  {
    cuuint64_t dims[5] = {1024, 2, 2, 4, 128};
    cuuint64_t str[4] = {2048, 8 * 2048, 2 * 2048, 16 * 2048};
    cuuint32_t box[5] = {16, 2, 2, 4, 32};
    make_map(enc, &tmQ, d_in[0], 5, dims, str, box, CU_TENSOR_MAP_SWIZZLE_NONE);
  }
  {
    cuuint64_t dims[3] = {2048, 2, 1024};
    cuuint64_t str[2] = {4096, 8192};
    cuuint32_t box[3] = {64, 1, 16};
    make_map(enc, &tmOb, d_out, 3, dims, str, box, CU_TENSOR_MAP_SWIZZLE_128B);
  }
  {
    cuuint64_t dims[4] = {1024, 256, 2, 4};
    cuuint64_t str[3] = {4096, 2048, 256 * 4096};
    cuuint32_t box[4] = {64, 8, 2, 3};
    make_map(enc, &tmXh, d_in[6], 4, dims, str, box, CU_TENSOR_MAP_SWIZZLE_128B);
  }
  {
    cuuint64_t dims[3] = {64, 1024, 48};
    cuuint64_t str[2] = {6144, 128};
    cuuint32_t box[3] = {64, 64, 4};
    make_map(enc, &tmWh, d_in[7], 3, dims, str, box, CU_TENSOR_MAP_SWIZZLE_128B);
  }
  Params p;
  p.q = (const __nv_bfloat16*)d_in[0];
  p.k = (const __nv_bfloat16*)d_in[1];
  p.v = (const __nv_bfloat16*)d_in[2];
  p.shift_k = (const __nv_bfloat16*)d_in[3];
  p.ssm_k = (const __nv_bfloat16*)d_in[4];
  p.ssm_D = (const __nv_bfloat16*)d_in[5];
  p.x = (const __nv_bfloat16*)d_in[6];
  p.w = (const __nv_bfloat16*)d_in[7];
  p.wo = (const __nv_bfloat16*)d_in[8];
  p.out = (__nv_bfloat16*)d_out;
  p.zero = 0;
  if (coresident) {
    fused_kernel<0><<<NCTA, NTHREADS, SMEM_BYTES>>>(p, tmX, tmW, tmWo, tmWp, tmQ, tmOb, tmXh, tmWh);
  } else {
    fused_kernel<0><<<4, NTHREADS, SMEM_BYTES>>>(p, tmX, tmW, tmWo, tmWp, tmQ, tmOb, tmXh, tmWh);
    fused_kernel<1><<<NCTA, NTHREADS, SMEM_BYTES>>>(p, tmX, tmW, tmWo, tmWp, tmQ, tmOb, tmXh, tmWh);
    fused_kernel<2><<<NCTA, NTHREADS, SMEM_BYTES>>>(p, tmX, tmW, tmWo, tmWp, tmQ, tmOb, tmXh, tmWh);
  }
}
```

```cpp
#include <cuda_runtime.h>
#include <cuda.h>
#include <cuda_bf16.h>
#include <stdint.h>

namespace {

constexpr int SEQ = 2048;
constexpr int DM = 1024;
constexpr int NCTA = 132;
constexpr int NTHREADS = 384;

constexpr int STG1A = 32768;
constexpr int NS1A = 3;
constexpr int STG1B = 12288;
constexpr int NS1B = 5;
constexpr int OFF_1B = NS1A * STG1A;
constexpr int STG2 = 32768;
constexpr int NS2 = 5;
#define PSTEP 1250
#define FPACE 260
#define FPACE2 230
constexpr int LEADWG = 1;
__device__ __forceinline__ uint32_t g2_a(int s, int hsel) { return (((0x97524 >> (4 * s)) & 15) ^ (s & 5 ? 0 : hsel)) << 14; }
constexpr int OFF_Q0 = 3 << 14, OFF_Q1 = 8 << 14;
constexpr int STGH = 40960;
constexpr int OFF_KH = 1 * STG2;
constexpr int OFF_OP = 2 * STG2;
constexpr int OFF_T32 = 5 * STG2 - 4096;
constexpr int OFF_X = 5 * STG2;
constexpr int XT = 8192;
__device__ __forceinline__ uint32_t g2_b(int s, int rank) {
  return s < 3 ? (s == 2 ? 6 : s) << 14 : OFF_X + (s - 3) * 2 * XT + (rank ^ 1) * 4096;
}
__device__ __forceinline__ uint32_t g2_bk(int s) { return s < 3 ? 4096 : 4 * XT; }
constexpr int OFF_BAR = OFF_X + 8 * XT;
constexpr int OFF_EX = OFF_BAR + 448;
constexpr int OFF_T16 = 230400;
constexpr int SMEM_BYTES = OFF_T16 + 2048;
static_assert(OFF_1B + NS1B * STG1B <= OFF_T32 && OFF_X % 1024 == 0, "layout");
static_assert(NS1B * STGH <= OFF_BAR && OFF_EX + 64 <= OFF_T16 && SMEM_BYTES <= 232448, "smem");

constexpr int BAR_FULLA = 0;
constexpr int BAR_EMPTYA = 3;
constexpr int BAR_FULLB = 6;
constexpr int BAR_EMPTYB = 11;
constexpr int BAR_FULL2 = 16;
constexpr int BAR_EMPTY2 = 21;
constexpr int BAR_EMPTY2B = 44;
constexpr int BAR_X = 26;
constexpr int BAR_LAND = 42;
constexpr int BAR_TAB = 28;
constexpr int BAR_U = 29;
constexpr int BAR_H = 30;
constexpr int BAR_STG = 31;
constexpr int BAR_Y = 32;
constexpr int BAR_XFREE = 38;
constexpr int BAR_HALO = 40;
constexpr int BAR_Q = 41;

constexpr int NB_LEAD = 2;
constexpr int NB_G1END = 3;
constexpr int NB_OREADY = 4;
constexpr int NB_CONV = 5;
constexpr int NB_HELP3 = 11;
constexpr int NB_FIRST = 13;

#define REG_MATH 224
#define REG_HELP 56
constexpr int SPIN_LIMIT = 1 << 20;

__device__ __align__(1024) __nv_bfloat16 g_o[SEQ * DM];
__device__ uint32_t g_flag_o[128];
__device__ uint4 g_halo[128 * 192];
__device__ __align__(128) const uint32_t g_tab[2048] = {
  0x2fd93000,0x2ea72f64,0x2c722da8,0x263e2a1f,0x2ea73000,0xa63e2a1f,0xafd9ada8,0xac72af64,0x2c723000,0xafd9aa1f,0x263eada8,0x2ea72f64,
  0x263e3000,0xac72af64,0x2ea72da8,0xafd9aa1f,0xa63e3000,0x2c72af64,0xaea72da8,0x2fd9aa1f,0xac723000,0x2fd9aa1f,0xa63eada8,0xaea72f64,
  0xaea73000,0x263e2a1f,0x2fd9ada8,0x2c72af64,0xafd93000,0xaea72f64,0xac722da8,0xa63e2a1f,0x263e0000,0x2c722a1f,0x2ea72da8,0x2fd92f64,
  0x2c720000,0x2fd92f64,0x263e2da8,0xaea7aa1f,0x2ea70000,0x263e2f64,0xafd9ada8,0x2c72aa1f,0x2fd90000,0xaea72a1f,0x2c72ada8,0xa63e2f64,
  0x2fd90000,0xaea7aa1f,0x2c722da8,0xa63eaf64,0x2ea70000,0x263eaf64,0xafd92da8,0x2c722a1f,0x2c720000,0x2fd9af64,0x263eada8,0xaea72a1f,
  0x263e0000,0x2c72aa1f,0x2ea7ada8,0x2fd9af64,0xafd93000,0xaea72f64,0xac722da8,0xa63e2a1f,0xaea73000,0x263e2a1f,0x2fd9ada8,0x2c72af64,
  0xac723000,0x2fd9aa1f,0xa63eada8,0xaea72f64,0xa63e3000,0x2c72af64,0xaea72da8,0x2fd9aa1f,0x263e3000,0xac72af64,0x2ea72da8,0xafd9aa1f,
  0x2c723000,0xafd9aa1f,0x263eada8,0x2ea72f64,0x2ea73000,0xa63e2a1f,0xafd9ada8,0xac72af64,0x2fd93000,0x2ea72f64,0x2c722da8,0x263e2a1f,
  0xa63e0000,0xac722a1f,0xaea72da8,0xafd92f64,0xac720000,0xafd92f64,0xa63e2da8,0x2ea7aa1f,0xaea70000,0xa63e2f64,0x2fd9ada8,0xac72aa1f,
  0xafd90000,0x2ea72a1f,0xac72ada8,0x263e2f64,0xafd90000,0x2ea7aa1f,0xac722da8,0x263eaf64,0xaea70000,0xa63eaf64,0x2fd92da8,0xac722a1f,
  0xac720000,0xafd9af64,0xa63eada8,0x2ea72a1f,0xa63e0000,0xac72aa1f,0xaea7ada8,0xafd9af64,0xa63e0000,0xac72aa1f,0xaea7ada8,0xafd9af64,
  0xac720000,0xafd9af64,0xa63eada8,0x2ea72a1f,0xaea70000,0xa63eaf64,0x2fd92da8,0xac722a1f,0xafd90000,0x2ea7aa1f,0xac722da8,0x263eaf64,
  0xafd90000,0x2ea72a1f,0xac72ada8,0x263e2f64,0xaea70000,0xa63e2f64,0x2fd9ada8,0xac72aa1f,0xac720000,0xafd92f64,0xa63e2da8,0x2ea7aa1f,
  0xa63e0000,0xac722a1f,0xaea72da8,0xafd92f64,0x2fd93000,0x2ea72f64,0x2c722da8,0x263e2a1f,0x2ea73000,0xa63e2a1f,0xafd9ada8,0xac72af64,
  0x2c723000,0xafd9aa1f,0x263eada8,0x2ea72f64,0x263e3000,0xac72af64,0x2ea72da8,0xafd9aa1f,0xa63e3000,0x2c72af64,0xaea72da8,0x2fd9aa1f,
  0xac723000,0x2fd9aa1f,0xa63eada8,0xaea72f64,0xaea73000,0x263e2a1f,0x2fd9ada8,0x2c72af64,0xafd93000,0xaea72f64,0xac722da8,0xa63e2a1f,
  0x263e0000,0x2c72aa1f,0x2ea7ada8,0x2fd9af64,0x2c720000,0x2fd9af64,0x263eada8,0xaea72a1f,0x2ea70000,0x263eaf64,0xafd92da8,0x2c722a1f,
  0x2fd90000,0xaea7aa1f,0x2c722da8,0xa63eaf64,0x2fd90000,0xaea72a1f,0x2c72ada8,0xa63e2f64,0x2ea70000,0x263e2f64,0xafd9ada8,0x2c72aa1f,
  0x2c720000,0x2fd92f64,0x263e2da8,0xaea7aa1f,0x263e0000,0x2c722a1f,0x2ea72da8,0x2fd92f64,0xafd93000,0xaea72f64,0xac722da8,0xa63e2a1f,
  0xaea73000,0x263e2a1f,0x2fd9ada8,0x2c72af64,0xac723000,0x2fd9aa1f,0xa63eada8,0xaea72f64,0xa63e3000,0x2c72af64,0xaea72da8,0x2fd9aa1f,
  0x263e3000,0xac72af64,0x2ea72da8,0xafd9aa1f,0x2c723000,0xafd9aa1f,0x263eada8,0x2ea72f64,0x2ea73000,0xa63e2a1f,0xafd9ada8,0xac72af64,
  0x2fd93000,0x2ea72f64,0x2c722da8,0x263e2a1f,0xa63e0000,0xac72aa1f,0xaea7ada8,0xafd9af64,0x2c720000,0x2fd92f64,0x263e2da8,0xaea7aa1f,
  0xaea70000,0xa63eaf64,0x2fd92da8,0xac722a1f,0x2fd90000,0xaea72a1f,0x2c72ada8,0xa63e2f64,0xafd90000,0x2ea72a1f,0xac72ada8,0x263e2f64,
  0x2ea70000,0x263eaf64,0xafd92da8,0x2c722a1f,0xac720000,0xafd92f64,0xa63e2da8,0x2ea7aa1f,0x263e0000,0x2c72aa1f,0x2ea7ada8,0x2fd9af64,
  0x2fd93000,0x2ea72f64,0x2c722da8,0x263e2a1f,0xaea7b000,0x263eaa1f,0x2fd92da8,0x2c722f64,0x2c723000,0xafd9aa1f,0x263eada8,0x2ea72f64,
  0xa63eb000,0x2c722f64,0xaea7ada8,0x2fd92a1f,0xa63e3000,0x2c72af64,0xaea72da8,0x2fd9aa1f,0x2c72b000,0xafd92a1f,0x263e2da8,0x2ea7af64,
  0xaea73000,0x263e2a1f,0x2fd9ada8,0x2c72af64,0x2fd9b000,0x2ea7af64,0x2c72ada8,0x263eaa1f,0x263e0000,0x2c72aa1f,0x2ea7ada8,0x2fd9af64,
  0xac720000,0xafd92f64,0xa63e2da8,0x2ea7aa1f,0x2ea70000,0x263eaf64,0xafd92da8,0x2c722a1f,0xafd90000,0x2ea72a1f,0xac72ada8,0x263e2f64,
  0x2fd90000,0xaea72a1f,0x2c72ada8,0xa63e2f64,0xaea70000,0xa63eaf64,0x2fd92da8,0xac722a1f,0x2c720000,0x2fd92f64,0x263e2da8,0xaea7aa1f,
  0xa63e0000,0xac72aa1f,0xaea7ada8,0xafd9af64,0xafd93000,0xaea72f64,0xac722da8,0xa63e2a1f,0x2ea7b000,0xa63eaa1f,0xafd92da8,0xac722f64,
  0xac723000,0x2fd9aa1f,0xa63eada8,0xaea72f64,0x263eb000,0xac722f64,0x2ea7ada8,0xafd92a1f,0x263e3000,0xac72af64,0x2ea72da8,0xafd9aa1f,
  0xac72b000,0x2fd92a1f,0xa63e2da8,0xaea7af64,0x2ea73000,0xa63e2a1f,0xafd9ada8,0xac72af64,0xafd9b000,0xaea7af64,0xac72ada8,0xa63eaa1f,
  0xafd9b000,0xaea7af64,0xac72ada8,0xa63eaa1f,0x2ea73000,0xa63e2a1f,0xafd9ada8,0xac72af64,0xac72b000,0x2fd92a1f,0xa63e2da8,0xaea7af64,
  0x263e3000,0xac72af64,0x2ea72da8,0xafd9aa1f,0x263eb000,0xac722f64,0x2ea7ada8,0xafd92a1f,0xac723000,0x2fd9aa1f,0xa63eada8,0xaea72f64,
  0x2ea7b000,0xa63eaa1f,0xafd92da8,0xac722f64,0xafd93000,0xaea72f64,0xac722da8,0xa63e2a1f,0xa63e0000,0xac72aa1f,0xaea7ada8,0xafd9af64,
  0x2c720000,0x2fd92f64,0x263e2da8,0xaea7aa1f,0xaea70000,0xa63eaf64,0x2fd92da8,0xac722a1f,0x2fd90000,0xaea72a1f,0x2c72ada8,0xa63e2f64,
  0xafd90000,0x2ea72a1f,0xac72ada8,0x263e2f64,0x2ea70000,0x263eaf64,0xafd92da8,0x2c722a1f,0xac720000,0xafd92f64,0xa63e2da8,0x2ea7aa1f,
  0x263e0000,0x2c72aa1f,0x2ea7ada8,0x2fd9af64,0x2fd9b000,0x2ea7af64,0x2c72ada8,0x263eaa1f,0xaea73000,0x263e2a1f,0x2fd9ada8,0x2c72af64,
  0x2c72b000,0xafd92a1f,0x263e2da8,0x2ea7af64,0xa63e3000,0x2c72af64,0xaea72da8,0x2fd9aa1f,0xa63eb000,0x2c722f64,0xaea7ada8,0x2fd92a1f,
  0x2c723000,0xafd9aa1f,0x263eada8,0x2ea72f64,0xaea7b000,0x263eaa1f,0x2fd92da8,0x2c722f64,0x2fd93000,0x2ea72f64,0x2c722da8,0x263e2a1f,
  0x263e0000,0x2c72aa1f,0x2ea7ada8,0x2fd9af64,0xac720000,0xafd92f64,0xa63e2da8,0x2ea7aa1f,0x2ea70000,0x263eaf64,0xafd92da8,0x2c722a1f,
  0xafd90000,0x2ea72a1f,0xac72ada8,0x263e2f64,0x2fd90000,0xaea72a1f,0x2c72ada8,0xa63e2f64,0xaea70000,0xa63eaf64,0x2fd92da8,0xac722a1f,
  0x2c720000,0x2fd92f64,0x263e2da8,0xaea7aa1f,0xa63e0000,0xac72aa1f,0xaea7ada8,0xafd9af64,0x316c2fbd,0x343e32f7,0x35bc34ff,0x372c3676,
  0x371532c6,0x3a81392e,0x3bef3b71,0x3b7c3bf2,0x397034cf,0x3bfc3b6c,0x38b23b04,0xb40e31e8,0x3ae13631,0x39e73bf5,0xb6e83219,0xbbe8bb13,
  0x3bc23785,0x30be3aa9,0xbbfdb911,0x2a16b9aa,0x3bfe3865,0xb80f37a6,0xb82abc00,0x3bfd376f,0x3b9238fd,0xbb7f2311,0x3805b929,0x31223bde,
  0x3a85398b,0xbb96b742,0x3bff319e,0xbbb82f8b,0xbbe2bbf1,0xbbb7bbcf,0xbb78bb9a,0xbb27bb52,0xbb2cbbd2,0xb8a8ba19,0xb029b5df,0x35a52f59,
  0xb9dfbba1,0x2ba7b5f7,0x3a7a37b2,0x3bbd3bdd,0xb815bb60,0x39662e91,0x3b373bda,0xb0d7377a,0xb3d3bb10,0x3be9386f,0x2a7a3a31,0xbbfeb9a6,
  0x294dbab0,0x3ae53b07,0xbad51fdb,0xab43bb16,0x352fba41,0x35993c00,0xbaebba1d,0x3be531cf,0x38a3b9c5,0xb5173b21,0x2776bbe0,0x34323bf2,
  0x384537dd,0x38ea3899,0x39823937,0x3a0d39c9,0x39463a93,0x3340374e,0xb426a452,0xb979b7c8,0xbb45b924,0xbb32bc00,0xb371b902,0x38d63294,
  0xb08db9a1,0x3b3f379b,0x39583bd7,0xb8252dfb,0x3bea3a2d,0xb3ba3874,0xbb89bb0d,0x36d2b625,0xb6bb387f,0xb8d1bbf5,0x3be73602,0xb546391f,
  0xba00bb01,0x3bff35eb,0xba5c34db,0x3359bab6,0x3ac7b66b,0xb9413933,0x368dbabd,0xb0103bb3,0xbac4baf7,0xba50ba8c,0xb9cdba11,0xb93cb986,
  0x3a04388e,0x3bcb3b1e,0x3bba3c00,0x39d63afe,0x36af3a21,0xb6ffa17f,0xbbc8ba3d,0xba60bbd4,0xbbebb9af,0xb6c6bb0a,0x39f43263,0x3ad83bf7,
  0x30a6b916,0x3bc33aa5,0xb55e3790,0xbb3dbb63,0x3b423a9e,0xba642ec3,0xb0f0bb6a,0x3b8e3a25,0xb94a37bd,0x2884bb6f,0x38db3b9f,0xbbc9b85a,
  0xb840bb54,0x3a093a15,0xbb4cb850,0x3bef3457,0x3a893a4d,0x3af43ac1,0x3b4f3b24,0x3b983b76,0xbb94baba,0xbbe4bbf9,0xba58bb57,0xb699b8f8,
  0x3bfe3b18,0x394f3b5c,0xb109347b,0xbae8b884,0xbbc0bb68,0xa9b1b90c,0x3b8b387a,0x38bc3ba5,0x3ade3ba7,0xb8c1324b,0xb9f0bbf6,0x39eb9648,
  0xb96bbbd6,0x3bbf3487,0xb38939b3,0xb9f8bba3,0x370a3bf3,0xbb47b994,0x3bbc2d65,0xb8ad3889,0xb153bc00,0x37213b9c,0xb97dba90,0x3af138f3,
  0xb89eb8ee,0xb7e8b84a,0xb682b737,0xb50bb5c8,0x35233855,0xb13b2d33,0xb8e0b65f,0xbb4aba45,0xa8e8b764,0x39fc3648,0x3be63bae,0x380a3a9b,
  0xb3eb360e,0xbbfeba35,0xb552baa2,0x3a7334b7,0x381ab4ab,0x3a6f3bd8,0xb95d2e5f,0xb962bc00,0xb9e3327c,0xb402bbac,0x3bc6399d,0xb95434c3,
  0x3b2faf27,0xb6a439bc,0xb41abbf9,0x3a7e3a97,0xbbe3251b,0x3b2ab4f3,0xb9d23894,0x37f3ba49,0x3bce3bb5,0x3bf03be1,0x3bff3bfa,0x3bfb3bff,
  0x2c38b1b6,0x383a34e7,0x3aee39c0,0x3bff3bb2,0xbb81bbf8,0xb53ab999,0x38302ef5,0x3bed3ab3,0xb8cc9cb6,0xbb85bbab,0x2adeb86a,0x3bc5391b,
  0x38c73bf6,0xbadbb232,0xb6ddbba9,0x3b87361a,0x3b833201,0xb0743a39,0xba76bb5e,0x3b352dc9,0xac06bbb0,0x39743b59,0xbbeeb759,0x3aceb2ad,
  0xbbccb5d4,0x3bfb2d00,0xbb7a32de,0x3a54b7d2,0xb30fb44b,0xafefb185,0xa6adacce,0x2c9c25e4,0xbbfcbbdf,0xbacbbb9e,0xb7feb990,0xa81fb463,
  0xb58d2d97,0xbb90b9b8,0xbad1bbf4,0xb05bb85f,0x3a673c00,0xb5763493,0xbbfdbaac,0xb3a2ba29,0x3a6b2e2d,0x38203bd9,0xbb3ab49f,0xb56abb65,
  0xb581bbdc,0x3bec3907,0xb8b7363c,0xb6f4bbf8,0xbbfcb46f,0x39dab654,0xb0423b1b,0xb835bbd3,0xb3283b73,0xac6abbfa,0x35b13bd0,0xb8e5bafb,
  0x38ee3a0d,0xb84aba89,0x37373af4,0xb5c8bb4f,0x35df3a81,0x2f59bbef,0xb88e3b7c,0x3b1eb946,0x2d973ae8,0x39b8bb81,0xbbf4353a,0x385f3830,
  0xb2633b3f,0x3bf7b958,0xb60eb825,0xba353bc0,0xb7853b87,0x3aa9b3d3,0x3911bbe9,0xb9aa2a7a,0xb99d3bbf,0x34c33389,0x3bdcb9f8,0x3907bb83,
  0xbb013be5,0xb5eb394a,0x34db2884,0x3ab6b8db,0xbbd03bfb,0xbafb3b7a,0xb98b3a54,0xb74238a3,0x3a4db93c,0xbac1389e,0x3b24b7e8,0xbb763682,
  0x3b71b8a8,0xbbf23029,0x3a9335a5,0xb74eba04,0x3bf8b80a,0xb999b58d,0xaef53b90,0x3ab3bad1,0x3bd7b6c6,0xadfbb9f4,0xbb683ad8,0x390c33eb,
  0x3b10b56a,0x386fbbc2,0xba3130be,0xb9a63bfd,0x39b3b402,0x3ba3bbc6,0x3201b954,0xba393581,0x37bdb122,0x3b6fba00,0x3b9fbbff,0x385aba5c,
  0x32deac6a,0x37d2b5b1,0x39c5b8e5,0x3b21ba85,0x344b3b98,0xb185bbce,0x2cce3bf0,0x25e4bbff,0xbc003340,0x3afe3426,0xb855b979,0x2d333b94,
  0x34cfbbed,0xbb6c39df,0x3b042ba7,0xb1e8ba7a,0x3aa2a9b1,0x34b7bb8b,0xbc0038bc,0x349338cc,0xba2d3bfe,0x387430a6,0x3b0dbbc3,0xb625b55e,
  0xb63cb074,0xbbf83a76,0xb8653b35,0x37a6294d,0x3bf3bbc9,0x3994bb2f,0x2d65b6a4,0xb889341a,0xb19e3517,0x2f8b2776,0x366bb432,0x3933b840,
  0x3bb5b50b,0xbbe1330f,0x3bfaafef,0xbbff26ad,0xa4523bcb,0x37c8bbba,0xbaba39d6,0x3bf9b523,0xbba1305b,0x35f73970,0x37b2bbfc,0xbbdd38b2,
  0x387abbfe,0xbba53552,0x9cb63a73,0x3babba67,0x39162a16,0x3aa5bbea,0xb790b3ba,0xbb633b89,0xbb5e3bec,0xadc938b7,0x3ab0b6f4,0x3b07bbfe,
  0xaf27b359,0xb9bc370a,0xbbf93b47,0xba973bbc,0x3be0bb96,0x3bf2bbff,0x3b54bbb8,0x3a15bac7,0xafbd3bfb,0x32f7bbe2,0xb4ff3bb7,0x3676bb78,
  0x365fbbe4,0xba453a58,0x3bdfb699,0xbb9eac38,0xb9243bbd,0x3c00b6af,0xb902b6ff,0xb2943bc8,0x3aacbb85,0xba29aade,0xb6313bc5,0x3bf5b815,
  0xbba73b3d,0x324b381a,0x3bf6ba6f,0x9648b95d,0x3c00bae5,0x376fbad5,0xb87f2b43,0xbbf53b42,0xbbb03a7e,0xbb593bfc,0xb75939da,0x32ad3042,
  0x3abdba09,0x3bb3bb4c,0x3c00bbef,0x3b9cbbe3,0x3bf12c9c,0xbbcfb16c,0x3b9a343e,0xbb52b5bc,0xbb57b13b,0x38f838e0,0xb1b6bb4a,0xb4e73bfc,
  0x3a21340e,0x217fbb45,0xba3d3b32,0x3bd4b371,0xb86ab576,0xb91b3bfd,0x3b60b3a2,0x2e91bae1,0x34ab36d2,0x3bd8bade,0xae5fb8c1,0xbc0039f0,
  0x9fdbb80f,0xbb16382a,0xba9e3bfd,0x2ec336bb,0xb46f38ad,0x3654ac06,0x3b1bb974,0x3bd3bbee,0x3850b941,0x3457b68d,0xa51bb010,0xb4f33153,
  0xb7dd3b27,0x3899bac4,0xb9373a50,0x39c9b9cd,0x3990383a,0xb463baee,0xb2c63bff,0x392ebb2c,0x3b18ba60,0xbb5c28e8,0x347b39fc,0x3884bbe6,
  0xb219b966,0xbb133b37,0x39a130d7,0x379bbbeb,0xbbf63962,0xb2323a6b,0x3ba9b820,0x361abb3a,0xb6023a64,0x391fb0f0,0x3bd6bb8e,0x3487b9e3,
  0x3a41b835,0x3c00bb92,0x3a1dbb7f,0x31cfb805,0x3a90bb2a,0x38f3b9d2,0x35d4b7f3,0x2d00b328,0x3af7372c,0xba8cb845,0x3a1138ea,0xb986b982,
  0x39c0bacb,0xbbb237fe,0x3bd2a81f,0xba19b715,0xb764b8d6,0xb6483bfe,0x3baeb94f,0xba9bb109,0xbbda39e7,0x377a36e8,0x39afbbe8,0xbb0a308d,
  0xae2d39eb,0x3bd9b8c7,0x349fbadb,0xbb6536dd,0x3b6ab8d1,0x3a25bbe7,0xb27cb546,0xbbac396b,0x38fdbace,0xa311b52f,0xb9293599,0xbbde3aeb,
  0xb8943721,0xba49397d,0xbb733af1,0xbbfa3bcc,0xbbfb3bff,0xbbe23bf1,0xbbb73bcf,0xbb783b9a,0xbb7c3bf2,0xb9463a93,0xb340374e,0x3426a452,
  0xba603bd4,0xa8e83764,0x39fcb648,0x3be6bbae,0xb8bc3ba5,0x38cc9cb6,0x3b85bbab,0xaadeb86a,0xb56a3b65,0x3bc2b785,0x30bebaa9,0xbbfd3911,
  0xab433b16,0x3b42ba9e,0xba64aec3,0xb0f03b6a,0x33593ab6,0x370abbf3,0xbb473994,0x3bbcad65,0x37f33a49,0xb328bb73,0xac6a3bfa,0x35b1bbd0,
  0xac9c25e4,0xb16c2fbd,0xb43e32f7,0xb5bc34ff,0xb5a52f59,0xba04388e,0xbbcb3b1e,0xbbba3c00,0xb8d63294,0xbbfe3b18,0xb94f3b5c,0x3109347b,
  0xba7334b7,0xba673c00,0x35763493,0x3bfdbaac,0xbb87361a,0xb3d33b10,0x3be9b86f,0x2a7aba31,0xbbfd376f,0x36bb387f,0x38d1bbf5,0xbbe73602,
  0xbbc9385a,0x3b2f2f27,0xb6a4b9bc,0xb41a3bf9,0xbaf138f3,0x3bccb5d4,0xbbfb2d00,0x3b7a32de,0xbb273b52,0xbac43af7,0xba503a8c,0xb9cd3a11,
  0x3979b7c8,0x3b94baba,0x3be4bbf9,0x3a58bb57,0x380aba9b,0xb58dad97,0xbb9039b8,0xbad13bf4,0xbbc5391b,0xb8153b60,0x3966ae91,0x3b37bbda,
  0x2a1639aa,0x3beaba2d,0xb3bab874,0xbb893b0d,0x3b8eba25,0xb9e3b27c,0xb4023bac,0x3bc6b99d,0xb8adb889,0xac063bb0,0x3974bb59,0xbbee3759,
  0xb8e53afb,0x3a85b98b,0xbb963742,0x3bffb19e,0xb72c3676,0xb84537dd,0xb8ea3899,0xb9823937,0xb9d63afe,0xb5233855,0x313b2d33,0x38e0b65f,
  0x3ae8b884,0x3b81bbf8,0x353ab999,0xb8302ef5,0x33a2ba29,0xbae13631,0xb9e73bf5,0x36e83219,0xbbfe39a6,0x30a63916,0x3bc3baa5,0xb55eb790,
  0x3546391f,0x396bbbd6,0xbbbf3487,0x338939b3,0x3a7eba97,0xbbfc346f,0x39da3654,0xb042bb1b,0xba54b7d2,0x38a339c5,0xb517bb21,0x27763be0,
  0xb93c3986,0xb89e38ee,0xb7e8384a,0xb6823737,0x3699b8f8,0xac38b1b6,0xb83a34e7,0xbaee39c0,0xb05b385f,0x3970b4cf,0x3bfcbb6c,0x38b2bb04,
  0xb0d7b77a,0xbbeb39af,0xb6c63b0a,0x39f4b263,0x36d23625,0x3adebba7,0xb8c1b24b,0xb9f03bf6,0xb954b4c3,0xb5813bdc,0x3becb907,0xb8b7b63c,
  0x3ace32ad,0xb52fba41,0xb5993c00,0x3aebba1d,0xbbb8af8b,0x3ac7366b,0xb941b933,0x368d3abd,0xba0d39c9,0xba893a4d,0xbaf43ac1,0xbb4f3b24,
  0x3b4aba45,0x3bfcbbdf,0x3acbbb9e,0x37feb990,0xbbed3ab3,0xb9df3ba1,0x2ba735f7,0x3a7ab7b2,0x3be8bb13,0x308db9a1,0xbb3f379b,0xb9583bd7,
  0xbb3d3b63,0x381a34ab,0x3a6fbbd8,0xb95dae5f,0x39f8bba3,0xbb833201,0x30743a39,0x3a76bb5e,0xb8353bd3,0x3b92b8fd,0xbb7fa311,0x38053929,
  0x3432bbf2,0xb8403b54,0x3a09ba15,0xbb4c3850,0xb50b35c8,0xb30f344b,0xafef3185,0xa6ad2cce,0xbbff3bb2,0xbb2c3bd2,0xb8a83a19,0xb02935df,
  0xb40eb1e8,0xbb453924,0xbb323c00,0xb3713902,0x3ad8bbf7,0xb3ebb60e,0xbbfe3a35,0xb5523aa2,0x39eb1648,0x38c7bbf6,0xbadb3232,0xb6dd3ba9,
  0xb6f43bf8,0x3bfeb865,0xb80fb7a6,0xb82a3c00,0xbbe531cf,0x394a37bd,0xa884bb6f,0xb8db3b9f,0xb010bbb3,0xb1533c00,0x3721bb9c,0xb97d3a90,
  0xbb983b76,0xbbce3bb5,0xbbf03be1,0xbbff3bfa,0x281fb463,0xb71532c6,0xba81392e,0xbbef3b71,0x3bbdbbdd,0x36afba21,0xb6ff217f,0xbbc83a3d,
  0x38252dfb,0x3bc0bb68,0x29b1b90c,0xbb8b387a,0xb9623c00,0x3a6bae2d,0x3820bbd9,0xbb3a349f,0xbb352dc9,0x294d3ab0,0x3ae5bb07,0xbad59fdb,
  0x3122bbde,0xba003b01,0x3bffb5eb,0xba5cb4db,0x3befb457,0xbbe3a51b,0x3b2a34f3,0xb9d2b894,0x39c939cd,0xba4db93c,0x3ac1389e,0xbb24b7e8,
  0x3b1e3946,0xbc00b340,0x3afeb426,0xb8553979,0x3bdd38b2,0xba21340e,0xa17fbb45,0x3a3d3b32,0x3bf53815,0xb2193966,0xbb13bb37,0x39a1b0d7,
  0x3b6536dd,0x37853b87,0xbaa9b3d3,0xb911bbe9,0x3a393581,0x3b5e3bec,0x2dc938b7,0xbab0b6f4,0x3889341a,0x3bb03a7e,0x3b593bfc,0x375939da,
  0x34f33153,0x38943721,0x3a49397d,0x3b733af1,0xb9863982,0x38eeba0d,0xb84a3a89,0x3737baf4,0xb74e3a04,0xa452bbcb,0x37c83bba,0xbabab9d6,
  0xb1e83a7a,0xb924bbbd,0x3c0036af,0xb90236ff,0x2e913ae1,0xbbdab9e7,0x377ab6e8,0x39af3be8,0x361a3b3a,0xbb10b56a,0xb86fbbc2,0x3a3130be,
  0x39073b83,0xb63c3074,0xbbf8ba76,0xb865bb35,0x3a973bbc,0x346f38ad,0xb654ac06,0xbb1bb974,0x3b9c3be3,0x3a903b2a,0x38f339d2,0x35d437f3,
  0x3b763682,0xbbb5b50b,0x3be1330f,0xbbfaafef,0x2d33bb94,0x365f3be4,0xba45ba58,0x3bdf3699,0xbbd4b371,0x3764b8d6,0x36483bfe,0xbbaeb94f,
  0x379b3beb,0xbbd7b6c6,0x2dfbb9f4,0x3b683ad8,0x39aa2a7a,0x3a2d3bfe,0xb87430a6,0xbb0dbbc3,0xbb07bbfe,0x1fdbb80f,0x3b16382a,0x3a9e3bfd,
  0xb2ad3042,0xba41b835,0xbc00bb92,0xba1dbb7f,0x3bfa3bcc,0x3bd03bfb,0x3afb3b7a,0x398b3a54,0xb5c83b4f,0x344bbb98,0xb1853bce,0x2ccebbf0,
  0x3bf93523,0xbb57313b,0x38f8b8e0,0xb1b63b4a,0xb294bbc8,0x3b183a60,0xbb5ca8e8,0x347bb9fc,0xbb0ab08d,0xb263bb3f,0x3bf73958,0xb60e3825,
  0x39a63bfd,0xb9162a16,0xbaa5bbea,0x3790b3ba,0x37a6a94d,0x3c003ae5,0x376f3ad5,0xb87fab43,0xbbd3bbee,0xb8fdbace,0x2311b52f,0x39293599,
  0x2d003328,0xb2deac6a,0xb7d2b5b1,0xb9c5b8e5,0x3bff26ad,0xbbf12c9c,0x3bcfb16c,0xbb9a343e,0xbb9e2c38,0x3990b83a,0xb4633aee,0xb2c6bbff,
  0x3a9bb109,0xad973ae8,0xb9b8bb81,0x3bf4353a,0xb90c33eb,0xb87abbfe,0x3ba53552,0x1cb63a73,0x3625b55e,0x3ba73b3d,0xb24b381a,0xbbf6ba6f,
  0xaec336bb,0xbb6ab8d1,0xba25bbe7,0x327cb546,0xb1cfb805,0x37bd3122,0x3b6f3a00,0x3b9f3bff,0x374238a3,0x319e3517,0xaf8b2776,0xb66bb432,
  0x25e43bff,0xafbdbbfb,0x32f73be2,0xb4ffbbb7,0xb4e7bbfc,0x39c03acb,0xbbb2b7fe,0x3bd2281f,0x38843be6,0xbbf8b80a,0x3999b58d,0x2ef53b90,
  0xba35bbc0,0x3aa229b1,0x34b73b8b,0xbc00b8bc,0x3b633b89,0xb4ab36d2,0xbbd8bade,0x2e5fb8c1,0xbbf5bb42,0xb602ba64,0x391f30f0,0x3bd63b8e,
  0x3bde3aeb,0x3b013be5,0x35eb394a,0xb4db2884,0xbb21ba85,0xbbe0bb96,0xbbf2bbff,0xbb54bbb8,0x3b52b5bc,0xbaf7372c,0x3a8cb845,0xba1138ea,
  0x392e3b2c,0xbb71b8a8,0x3bf23029,0xba9335a5,0xb85f3830,0xb4cfbbed,0x3b6c39df,0xbb042ba7,0xbbabba67,0x386ab576,0x391b3bfd,0xbb60b3a2,
  0x1648b95d,0x3bf63962,0x32323a6b,0xbba9b820,0x3bac396b,0x399d3bbf,0xb4c33389,0xbbdcb9f8,0x385a3a5c,0xaf273359,0xb9bcb70a,0xbbf9bb47,
  0xb933b840,0xbabdba09,0xbbb3bb4c,0xbc00bbef,0x36763b78,0xb7ddbb27,0x38993ac4,0xb937ba50,0xba193715,0x35dfba81,0x2f593bef,0xb88ebb7c,
  0xbab3bad1,0x3ba1305b,0xb5f73970,0xb7b2bbfc,0x3493b8cc,0x3aac3b85,0xba292ade,0xb631bbc5,0x3c0039f0,0x2e2d39eb,0xbbd9b8c7,0xb49fbadb,
  0x348739e3,0xb9b3b402,0xbba3bbc6,0xb201b954,0xbab6b8db,0xbbf3bbc9,0xb994bb2f,0xad65b6a4,0xba15bac7,0xb850b941,0xb457b68d,0x251bb010,
  0xb9cfbb16,0x30ac2a31,0x3b9c3bf1,0xb493ae2d,0xb76fb8b4,0x35a133e3,0x3a1d3afe,0xb902b76f,0xb3e3b5a1,0x38b4376f,0x376f3902,0xbafeba1d,
  0xaa31b0ac,0x3b1639cf,0x2e2d3493,0xbbf1bb9c,0xb956ba74,0x305f29cc,0x3b633bd2,0xb44badc9,0xb6e7b859,0x353f335e,0x39d23ab6,0xb8bcb6ff,
  0xb35eb53f,0x385936e7,0x36ff38bc,0xbab6b9d2,0xa9ccb05f,0x3a743956,0x2dc9344b,0xbbd2bb63,0xb8e3b9de,0x30122967,0x3b1e3ba1,0xb402ad65,
  0xb662b801,0x34de32da,0x39823a67,0xb874b68d,0xb2dab4de,0x38013662,0x368d3874,0xba67b982,0xa967b012,0x39de38e3,0x2d653402,0xbba1bb1e,
  0xb876b952,0x2f8c2902,0x3ace3b60,0xb371ad00,0xb5e1b758,0x347e3257,0x392e3a11,0xb82ab61a,0xb257b47e,0x375835e1,0x361a382a,0xba11b92e,
  0xa902af8c,0x39523876,0x2d003371,0xbb60bace,0xb80db8ce,0x2ef3289e,0x3a733b10,0xb2deac9c,0xb562b6b3,0x342031d5,0x38d639b3,0xb7bdb5a5,
  0xb1d5b420,0x36b33562,0x35a537bd,0xb9b3b8d6,0xa89eaef3,0x38ce380d,0x2c9c32de,0xbb10ba73,0xb750b851,0x2e5a2839,0x3a0d3ab0,0xb24bac38,
  0xb4e5b613,0x33863153,0x387a394f,0xb721b52f,0xb153b386,0x361334e5,0x352f3721,0xb94fb87a,0xa839ae5a,0x38513750,0x2c38324b,0xbab0ba0d,
  0xb68eb7b4,0x2dc227a9,0x399d3a41,0xb1b6aba7,0xb46ab577,0x32cd30d2,0x381a38e5,0xb682b4b7,0xb0d2b2cd,0x3577346a,0x34b73682,0xb8e5b81a,
  0xa7a9adc2,0x37b4368e,0x2ba731b6,0xba41b99d,0xb5d2b6d1,0x2d2a26e0,0x392439c5,0xb122aade,0xb3e3b4de,0x32163052,0x376f3874,0xb5dfb43e,
  0xb052b216,0x34de33e3,0x343e35df,0xb874b76f,0xa6e0ad2a,0x36d135d2,0x2ade3122,0xb9c5b924,0xb51cb5f6,0x2c932617,0x38a3393c,0xb08daa16,
  0xb2f4b448,0x31602fa5,0x36a437fe,0xb53ab389,0xafa5b160,0x344832f4,0x3389353a,0xb7feb6a4,0xa617ac93,0x35f6351c,0x2a16308d,0xb93cb8a3,
  0xb46ab523,0x2bf6254d,0x381a38a8,0xafefa94d,0xb209b36b,0x30ac2ea7,0x35d4370a,0xb493b294,0xaea7b0ac,0x336b3209,0x32943493,0xb70ab5d4,
  0xa54dabf6,0x3523346a,0x294d2fef,0xb8a8b81a,0xb378b456,0x2ac82484,0x3715380a,0xaec3a884,0xb120b24a,0x2ff22da9,0x34ff360e,0xb3d3b19e,
  0xada9aff2,0x324a3120,0x319e33d3,0xb60eb4ff,0xa484aac8,0x34563378,0x28842ec3,0xb80ab715,0xb223b31c,0x29992376,0x35eb36c6,0xad97a776,
  0xb039b12d,0x2e8d2cac,0x3426350b,0xb27cb0a6,0xacacae8d,0x312d3039,0x30a6327c,0xb50bb426,0xa376a999,0x331c3223,0x27762d97,0xb6c6b5eb,
  0xb0d2b194,0x286b21e4,0x34b7356a,0xac6aa5e4,0xaea7b012,0x2d2a2b5f,0x32943402,0xb122af59,0xab5fad2a,0x30122ea7,0x2f593122,0xb402b294,
  0xa1e4a86b,0x319430d2,0x25e42c6a,0xb56ab4b7,0xaf0cb012,0x267b2052,0x32f73402,0xaa7aa452,0xacdeadf5,0x2b912967,0x30d731e8,0xaf8bad65,
  0xa967ab91,0x2df52cde,0x2d652f8b,0xb1e8b0d7,0xa052a67b,0x30122f0c,0x24522a7a,0xb402b2f7,0xac79ad2a,0x24201d7f,0x30743122,0xa81fa17f,
  0xaa31ab91,0x28d026e0,0x2e2d2f8b,0xacceaade,0xa6e0a8d0,0x2b912a31,0x2ade2cce,0xaf8bae2d,0x9d7fa420,0x2d2a2c79,0x217f281f,0xb122b074,
  0xa7a9a86b,0x1f1218b6,0x2ba72c6a,0xa3119cb6,0xa54da67b,0x242021e4,0x294d2a7a,0xa81fa5e4,0xa1e4a420,0x267b254d,0x25e4281f,0xaa7aa94d,
  0x98b69f12,0x286b27a9,0x1cb62311,0xac6aaba7,0x211b21e4,0x98b69248,0xa51ba5e4,0x1cb61648,0x1f122052,0x9d7f9bdb,0xa311a452,0x217f1fdb,
  0x1bdb1d7f,0xa0529f12,0x9fdba17f,0x24522311,0x124818b6,0xa1e4a11b,0x96489cb6,0x25e4251b,0x2a632b5f,0xa1e49bdb,0xae5faf59,0x25e41fdb,
  0x286b2967,0xa6e0a4e9,0xac6aad65,0x2ade28e8,0x24e926e0,0xa967a86b,0xa8e8aade,0x2d652c6a,0x1bdb21e4,0xab5faa63,0x9fdba5e4,0x2f592e5f,
  0x2dc22ea7,0xa54d9f12,0xb1b6b294,0x294d2311,0x2bf62cde,0xaa31a86b,0xafefb0d7,0x2e2d2c6a,0x286b2a31,0xacdeabf6,0xac6aae2d,0x30d72fef,
  0x1f12254d,0xaea7adc2,0xa311a94d,0x329431b6,0x302c30d2,0xa7a9a11b,0xb41ab4b7,0x2ba7251b,0x2dc22f0c,0xac79aa63,0xb1b6b2f7,0x30742e5f,
  0x2a632c79,0xaf0cadc2,0xae5fb074,0x32f731b6,0x211b27a9,0xb0d2b02c,0xa51baba7,0x34b7341a,0x317a3257,0xa902a2ad,0xb552b61a,0x2d0026ad,
  0x2f8c309f,0xaddcac2e,0xb371b487,0x31cf3029,0x2c2e2ddc,0xb09faf8c,0xb029b1cf,0x34873371,0x22ad2902,0xb257b17a,0xa6adad00,0x361a3552,
  0x32cd33e3,0xaa31a420,0xb682b76f,0x2e2d281f,0x30ac31bb,0xaf3fad2a,0xb493b58d,0x33283122,0x2d2a2f3f,0xb1bbb0ac,0xb122b328,0x358d3493,
  0x24202a31,0xb3e3b2cd,0xa81fae2d,0x376f3682,0x341334bc,0xab5fa4e9,0xb7a6b85a,0x2f5928e8,0x319432da,0xb052ae28,0xb56ab68d,0x343e3219,
  0x2e283052,0xb2dab194,0xb219b43e,0x368d356a,0x24e92b5f,0xb4bcb413,0xa8e8af59,0x385a37a6,0x34c3358c,0xac47a5b2,0xb85fb8f3,0x304229b1,
  0x327e33fd,0xb106af26,0xb63cb785,0x34e7330f,0x2f263106,0xb3fdb27e,0xb30fb4e7,0x3785363c,0x25b22c47,0xb58cb4c3,0xa9b1b042,0x38f3385f,
  0x35773662,0xacdea67b,0xb8e5b982,0x30d72a7a,0x336b3493,0xb1bbb012,0xb70ab83a,0x358d3402,0x301231bb,0xb493b36b,0xb402b58d,0x383a370a,
  0x267b2cde,0xb662b577,0xaa7ab0d7,0x398238e5,0x36303741,0xad76a744,0xb962ba04,0x316c2b43,0x342e352a,0xb271b092,0xb7d2b8ad,0x3631347b,
  0x30923271,0xb52ab42e,0xb47bb631,0x38ad37d2,0x27442d76,0xb741b630,0xab43b16c,0x3a043962,0x36ee3815,0xae0ea807,0xb9d6ba7a,0x32012c06,
  0x34a735c4,0xb329b113,0xb84ab91b,0x36d234f3,0x31133329,0xb5c4b4a7,0xb4f3b6d2,0x391b384a,0x28072e0e,0xb815b6ee,0xac06b201,0x3a7a39d6,
  0x37b4388e,0xaea7a86b,0xba41bae1,0x32942c6a,0x35233662,0xb3e3b194,0xb8a8b982,0x376f356a,0x319433e3,0xb662b523,0xb56ab76f,0x398238a8,
  0x286b2ea7,0xb88eb7b4,0xac6ab294,0x3ae13a41,0x3841390f,0xaf3fa8d0,0xbaa2bb3a,0x33282cce,0x35a13705,0xb44fb216,0xb902b9e3,0x380535df,
  0x3216344f,0xb705b5a1,0xb5dfb805,0x39e33902,0x28d02f3f,0xb90fb841,0xacceb328,0x3b3a3aa2,0x38ac3997,0xafd8a935,0xbaf7bb83,0x33ba2d33,
  0x362137ac,0xb4aeb298,0xb958ba3d,0x38503654,0x329834ae,0xb7acb621,0xb654b850,0x3a3d3958,0x29352fd8,0xb997b8ac,0xad33b3ba,0x3b833af7,
  0x391c3a28,0xb039a999,0xbb42bbbc,0x34262d97,0x36a4382d,0xb50eb31c,0xb9aaba90,0x389936c6,0x331c350e,0xb82db6a4,0xb6c6b899,0x3a9039aa,
  0x29993039,0xba28b91c,0xad97b426,0x3bbc3b42,0x39923ac3,0xb085a9fe,0xbb81bbe3,0x346f2dfb,0x372a3886,0xb570b3a0,0xb9f8badb,0x38e03737,
  0x33a03570,0xb886b72a,0xb737b8e0,0x3adb39f8,0x29fe3085,0xbac3b992,0xadfbb46f,0x3be33b81,
};

#define PROF(slot) do {} while (0)
#define PROF_DUMP() do {} while (0)
#define PROFA(slot, dep) do {} while (0)
#define PROF3(slot) do {} while (0)
#define PROF2(slot) do {} while (0)

__device__ __forceinline__ uint32_t smem_u32(const void* p) { return (uint32_t)__cvta_generic_to_shared(p); }

__device__ __forceinline__ void mbar_init(uint32_t a, uint32_t c) {
  asm volatile("mbarrier.init.shared::cta.b64 [%0], %1;\n" ::"r"(a), "r"(c) : "memory");
}
__device__ __forceinline__ void mbar_expect_tx(uint32_t a, uint32_t bytes) {
  asm volatile("mbarrier.arrive.expect_tx.shared::cta.b64 _, [%0], %1;\n" ::"r"(a), "r"(bytes) : "memory");
}
__device__ __forceinline__ void mbar_arrive_cluster(uint32_t cluster_addr) {
  asm volatile("mbarrier.arrive.shared::cluster.b64 _, [%0];\n" ::"r"(cluster_addr) : "memory");
}
__device__ __forceinline__ void mbar_arrive_cluster_n(uint32_t cluster_addr, uint32_t n) {
  asm volatile("mbarrier.arrive.shared::cluster.b64 _, [%0], %1;\n" ::"r"(cluster_addr), "r"(n) : "memory");
}
__device__ __forceinline__ bool mbar_try(uint32_t a, uint32_t parity) {
  uint32_t ok;
  asm volatile("{\n.reg .pred p;\nmbarrier.try_wait.parity.shared::cta.b64 p, [%1], %2;\nselp.u32 %0, 1, 0, p;\n}\n"
               : "=r"(ok) : "r"(a), "r"(parity) : "memory");
  return ok;
}
__device__ __forceinline__ void mbar_wait(uint32_t a, uint32_t parity) {
  if (mbar_try(a, parity)) return;
#pragma unroll 1
  for (int n = 0; n < SPIN_LIMIT; n++)
    if (mbar_try(a, parity)) break;
}
__device__ __forceinline__ bool elect_one() {
  uint32_t p;
  asm volatile("{\n.reg .pred P;\nelect.sync _|P, 0xffffffff;\nselp.u32 %0, 1, 0, P;\n}\n" : "=r"(p));
  return p;
}
__device__ __forceinline__ uint32_t mapa(uint32_t a, uint32_t rank) {
  uint32_t r;
  asm volatile("mapa.shared::cluster.u32 %0, %1, %2;\n" : "=r"(r) : "r"(a), "r"(rank));
  return r;
}
__device__ __forceinline__ void nb_sync(int id, int n) { asm volatile("bar.sync %0, %1;\n" ::"r"(id), "r"(n) : "memory"); }
__device__ __forceinline__ void nb_arrive(int id, int n) { asm volatile("bar.arrive %0, %1;\n" ::"r"(id), "r"(n) : "memory"); }
__device__ __forceinline__ void cluster_sync_all() {
  asm volatile("barrier.cluster.arrive.relaxed.aligned;\nbarrier.cluster.wait.aligned;\n" ::: "memory");
}
__device__ __forceinline__ void fence_async_smem() { asm volatile("fence.proxy.async.shared::cta;\n" ::: "memory"); }
__device__ __forceinline__ void fence_async_all() { asm volatile("fence.proxy.async.global;\n" ::: "memory"); }

__device__ __forceinline__ void tma_load_3d(uint32_t dst, const CUtensorMap* tm, uint32_t bar, int c0, int c1, int c2) {
  asm volatile(
      "cp.async.bulk.tensor.3d.shared::cluster.global.mbarrier::complete_tx::bytes [%0], [%1, {%3, %4, %5}], [%2];\n"
      ::"r"(dst), "l"(tm), "r"(bar), "r"(c0), "r"(c1), "r"(c2) : "memory");
}
__device__ __forceinline__ void tma_load_4d(uint32_t dst, const CUtensorMap* tm, uint32_t bar, int c0, int c1, int c2, int c3) {
  asm volatile(
      "cp.async.bulk.tensor.4d.shared::cluster.global.mbarrier::complete_tx::bytes [%0], [%1, {%3, %4, %5, %6}], [%2];\n"
      ::"r"(dst), "l"(tm), "r"(bar), "r"(c0), "r"(c1), "r"(c2), "r"(c3) : "memory");
}
__device__ __forceinline__ void tma_load_3d_mc(uint32_t dst, const CUtensorMap* tm, uint32_t bar, int c0, int c1, int c2) {
  asm volatile(
      "cp.async.bulk.tensor.3d.shared::cluster.global.mbarrier::complete_tx::bytes.multicast::cluster [%0], [%1, {%3, %4, %5}], [%2], %6;\n"
      ::"r"(dst), "l"(tm), "r"(bar), "r"(c0), "r"(c1), "r"(c2), "h"((uint16_t)3) : "memory");
}
__device__ __forceinline__ void bulk_load(uint32_t dst, const void* src, uint32_t bytes, uint32_t bar) {
  asm volatile("cp.async.bulk.shared::cluster.global.mbarrier::complete_tx::bytes [%0], [%1], %2, [%3];\n"
               ::"r"(dst), "l"(src), "r"(bytes), "r"(bar) : "memory");
}
__device__ __forceinline__ void tma_store_3d(const CUtensorMap* tm, uint32_t src, int c0, int c1, int c2) {
  asm volatile("cp.async.bulk.tensor.3d.global.shared::cta.bulk_group [%0, {%2, %3, %4}], [%1];\n"
               ::"l"(tm), "r"(src), "r"(c0), "r"(c1), "r"(c2) : "memory");
}
__device__ __forceinline__ void bulk_commit() { asm volatile("cp.async.bulk.commit_group;\n" ::: "memory"); }
__device__ __forceinline__ void bulk_wait0() { asm volatile("cp.async.bulk.wait_group 0;\n" ::: "memory"); }
__device__ __forceinline__ void prefetch_tmap(const CUtensorMap* tm) {
  asm volatile("prefetch.tensormap [%0];\n" ::"l"(tm) : "memory");
}

__device__ __forceinline__ void wg_fence() { asm volatile("wgmma.fence.sync.aligned;\n" ::: "memory"); }
__device__ __forceinline__ void wg_commit() { asm volatile("wgmma.commit_group.sync.aligned;\n" ::: "memory"); }
template <int N> __device__ __forceinline__ void wg_wait() {
  asm volatile("wgmma.wait_group.sync.aligned %0;\n" ::"n"(N) : "memory");
}
__device__ __forceinline__ uint64_t mkdesc(uint32_t addr, uint32_t lbo, uint32_t sbo, uint32_t swz) {
  return (uint64_t)((addr & 0x3FFFF) >> 4) | ((uint64_t)(lbo >> 4) << 16) | ((uint64_t)(sbo >> 4) << 32) |
         ((uint64_t)swz << 62);
}

#define R4(d, o) "+f"(d[o + 0]), "+f"(d[o + 1]), "+f"(d[o + 2]), "+f"(d[o + 3])
#define R8(d, o) R4(d, o), R4(d, o + 4)
#define R16(d, o) R8(d, o), R8(d, o + 8)
#define R32(d, o) R16(d, o), R16(d, o + 16)
#define R64(d, o) R32(d, o), R32(d, o + 32)

__device__ __forceinline__ void wgmma_n192(float (&d)[96], uint64_t da, uint64_t db, uint32_t acc) {
  asm volatile(
      "{\n.reg .pred p;\nsetp.ne.u32 p, %98, 0;\n"
      "wgmma.mma_async.sync.aligned.m64n192k16.f32.bf16.bf16 "
      "{%0,%1,%2,%3,%4,%5,%6,%7,%8,%9,%10,%11,%12,%13,%14,%15,%16,%17,%18,%19,%20,%21,%22,%23,%24,%25,%26,%27,%28,%29,%30,%31,"
      "%32,%33,%34,%35,%36,%37,%38,%39,%40,%41,%42,%43,%44,%45,%46,%47,%48,%49,%50,%51,%52,%53,%54,%55,%56,%57,%58,%59,%60,%61,%62,%63,"
      "%64,%65,%66,%67,%68,%69,%70,%71,%72,%73,%74,%75,%76,%77,%78,%79,%80,%81,%82,%83,%84,%85,%86,%87,%88,%89,%90,%91,%92,%93,%94,%95}, "
      "%96, %97, p, 1, 1, 0, 1;\n}\n"
      : R64(d, 0), R32(d, 64)
      : "l"(da), "l"(db), "r"(acc));
}
__device__ __forceinline__ void wgmma_n128(float (&d)[64], uint64_t da, uint64_t db, uint32_t acc) {
  asm volatile(
      "{\n.reg .pred p;\nsetp.ne.u32 p, %66, 0;\n"
      "wgmma.mma_async.sync.aligned.m64n128k16.f32.bf16.bf16 "
      "{%0,%1,%2,%3,%4,%5,%6,%7,%8,%9,%10,%11,%12,%13,%14,%15,%16,%17,%18,%19,%20,%21,%22,%23,%24,%25,%26,%27,%28,%29,%30,%31,"
      "%32,%33,%34,%35,%36,%37,%38,%39,%40,%41,%42,%43,%44,%45,%46,%47,%48,%49,%50,%51,%52,%53,%54,%55,%56,%57,%58,%59,%60,%61,%62,%63}, "
      "%64, %65, p, 1, 1, 0, 1;\n}\n"
      : R64(d, 0)
      : "l"(da), "l"(db), "r"(acc));
}
#define WG128(C, ACC)                                                                                                      \
  asm volatile(                                                                                                            \
      "{\n.reg .b64 a, b;\nmov.b64 a, {%64, %66};\nmov.b64 b, {%65, %66};\n"                                               \
      "wgmma.mma_async.sync.aligned.m64n128k16.f32.bf16.bf16 "                                                             \
      "{%0,%1,%2,%3,%4,%5,%6,%7,%8,%9,%10,%11,%12,%13,%14,%15,%16,%17,%18,%19,%20,%21,%22,%23,%24,%25,%26,%27,%28,%29,%30,%31," \
      "%32,%33,%34,%35,%36,%37,%38,%39,%40,%41,%42,%43,%44,%45,%46,%47,%48,%49,%50,%51,%52,%53,%54,%55,%56,%57,%58,%59,%60,%61," \
      "%62,%63}, a, b, " ACC ", 1, 1, 0, 1;\n}\n"                                                                          \
      : Z16(C, d, 0), Z16(C, d, 16), Z16(C, d, 32), Z16(C, d, 48)                                                          \
      : "r"(da), "r"(db), "r"(0x40000040))
#define Z4(C, d, o) C(d[o + 0]), C(d[o + 1]), C(d[o + 2]), C(d[o + 3])
#define Z16(C, d, o) Z4(C, d, o), Z4(C, d, o + 4), Z4(C, d, o + 8), Z4(C, d, o + 12)
__device__ __forceinline__ void wgmma_n128z(float (&d)[64], uint32_t da, uint32_t db) { WG128("=f", "0"); }
__device__ __forceinline__ void wgmma_n128a(float (&d)[64], uint32_t da, uint32_t db) { WG128("+f", "1"); }
template <int N> __device__ __forceinline__ void fence_regs(float (&d)[N]) {
#pragma unroll
  for (int i = 0; i < N; i++) asm volatile("" : "+f"(d[i])::"memory");
}

__device__ __forceinline__ void mma16816(float (&d)[4], uint32_t a0, uint32_t a1, uint32_t a2, uint32_t a3, uint32_t b0,
                                         uint32_t b1) {
  asm("mma.sync.aligned.m16n8k16.row.col.f32.bf16.bf16.f32 {%0,%1,%2,%3}, {%4,%5,%6,%7}, {%8,%9}, {%0,%1,%2,%3};\n"
      : "+f"(d[0]), "+f"(d[1]), "+f"(d[2]), "+f"(d[3])
      : "r"(a0), "r"(a1), "r"(a2), "r"(a3), "r"(b0), "r"(b1));
}
__device__ __forceinline__ void mma16816_z(float (&d)[4], uint32_t a0, uint32_t a1, uint32_t a2, uint32_t a3, uint32_t b0,
                                           uint32_t b1) {
  asm("mma.sync.aligned.m16n8k16.row.col.f32.bf16.bf16.f32 {%0,%1,%2,%3}, {%4,%5,%6,%7}, {%8,%9}, {%10,%10,%10,%10};\n"
      : "=f"(d[0]), "=f"(d[1]), "=f"(d[2]), "=f"(d[3])
      : "r"(a0), "r"(a1), "r"(a2), "r"(a3), "r"(b0), "r"(b1), "f"(0.f));
}
__device__ __forceinline__ void ldsm4t(uint32_t (&r)[4], uint32_t a) {
  asm volatile("ldmatrix.sync.aligned.m8n8.x4.trans.shared.b16 {%0,%1,%2,%3}, [%4];\n"
               : "=r"(r[0]), "=r"(r[1]), "=r"(r[2]), "=r"(r[3]) : "r"(a) : "memory");
}
__device__ __forceinline__ void ldsm2t(uint32_t& r0, uint32_t& r1, uint32_t a) {
  asm volatile("ldmatrix.sync.aligned.m8n8.x2.trans.shared.b16 {%0,%1}, [%2];\n" : "=r"(r0), "=r"(r1) : "r"(a) : "memory");
}
__device__ __forceinline__ void st_async128(uint32_t a, uint32_t bar, uint32_t x, uint32_t y, uint32_t z, uint32_t w) {
  asm volatile("st.async.weak.shared::cluster.mbarrier::complete_tx::bytes.v4.b32 [%0], {%2,%3,%4,%5}, [%1];\n"
               ::"r"(a), "r"(bar), "r"(x), "r"(y), "r"(z), "r"(w) : "memory");
}
__device__ __forceinline__ void mbar_arrive(uint32_t a) {
  asm volatile("mbarrier.arrive.shared::cta.b64 _, [%0];\n" ::"r"(a) : "memory");
}
__device__ __forceinline__ void stsm4(uint32_t a, uint32_t r0, uint32_t r1, uint32_t r2, uint32_t r3) {
  asm volatile("stmatrix.sync.aligned.m8n8.x4.shared.b16 [%0], {%1,%2,%3,%4};\n"
               ::"r"(a), "r"(r0), "r"(r1), "r"(r2), "r"(r3) : "memory");
}
__device__ __forceinline__ void stsm4t(uint32_t a, uint32_t r0, uint32_t r1, uint32_t r2, uint32_t r3) {
  asm volatile("stmatrix.sync.aligned.m8n8.x4.trans.shared.b16 [%0], {%1,%2,%3,%4};\n"
               ::"r"(a), "r"(r0), "r"(r1), "r"(r2), "r"(r3) : "memory");
}
__device__ __forceinline__ uint2 lds64(uint32_t a) {
  uint2 v;
  asm volatile("ld.shared.v2.u32 {%0,%1}, [%2];\n" : "=r"(v.x), "=r"(v.y) : "r"(a));
  return v;
}
__device__ __forceinline__ uint4 lds128(uint32_t a) {
  uint4 v;
  asm volatile("ld.shared.v4.u32 {%0,%1,%2,%3}, [%4];\n" : "=r"(v.x), "=r"(v.y), "=r"(v.z), "=r"(v.w) : "r"(a) : "memory");
  return v;
}
__device__ __forceinline__ void sts128(uint32_t a, uint32_t x, uint32_t y, uint32_t z, uint32_t w) {
  asm volatile("st.shared.v4.u32 [%0], {%1,%2,%3,%4};\n" ::"r"(a), "r"(x), "r"(y), "r"(z), "r"(w) : "memory");
}
__device__ __forceinline__ void sts64(uint32_t a, uint32_t x, uint32_t y) {
  asm volatile("st.shared.v2.u32 [%0], {%1,%2};\n" ::"r"(a), "r"(x), "r"(y) : "memory");
}
__device__ __forceinline__ uint32_t pack_bf16(float lo, float hi) {
  uint32_t r;
  asm("cvt.rn.bf16x2.f32 %0, %1, %2;\n" : "=r"(r) : "f"(hi), "f"(lo));
  return r;
}
__device__ __forceinline__ uint32_t bmul2(uint32_t a, uint32_t b) {
  uint32_t r;
  asm("mul.rn.bf16x2 %0, %1, %2;\n" : "=r"(r) : "r"(a), "r"(b));
  return r;
}
__device__ __forceinline__ uint32_t bmax2(uint32_t a, uint32_t b) {
  uint32_t r;
  asm("max.bf16x2 %0, %1, %2;\n" : "=r"(r) : "r"(a), "r"(b));
  return r;
}
__device__ __forceinline__ uint32_t bfma2(uint32_t a, uint32_t b, uint32_t c) {
  uint32_t r;
  asm("fma.rn.bf16x2 %0, %1, %2, %3;\n" : "=r"(r) : "r"(a), "r"(b), "r"(c));
  return r;
}
__device__ __forceinline__ uint32_t badd2(uint32_t a, uint32_t b) {
  uint32_t r;
  asm("add.rn.bf16x2 %0, %1, %2;\n" : "=r"(r) : "r"(a), "r"(b));
  return r;
}
__device__ __forceinline__ void prefetch_l2(const void* p) { asm volatile("prefetch.global.L2 [%0];\n" ::"l"(p)); }
__device__ __forceinline__ void cp_async16n(uint32_t dst, const void* src) {
  asm volatile("cp.async.cg.shared.global [%0], [%1], 16;\n" ::"r"(dst), "l"(src) : "memory");
}
__device__ __forceinline__ void cp_async16(uint32_t dst, const void* src, uint32_t srcbytes) {
  asm volatile("cp.async.cg.shared.global.L2::256B [%0], [%1], 16, %2;\n" ::"r"(dst), "l"(src), "r"(srcbytes) : "memory");
}
__device__ __forceinline__ uint32_t ld_acquire(const uint32_t* p) {
  uint32_t v;
  asm volatile("ld.acquire.gpu.global.u32 %0, [%1];\n" : "=r"(v) : "l"(p) : "memory");
  return v;
}
__device__ __forceinline__ uint32_t ld_relaxed(const uint32_t* p) {
  uint32_t v;
  asm volatile("ld.relaxed.gpu.global.u32 %0, [%1];\n" : "=r"(v) : "l"(p) : "memory");
  return v;
}
__device__ __forceinline__ void st_release(uint32_t* p, uint32_t v) {
  asm volatile("st.release.gpu.global.u32 [%0], %1;\n" ::"l"(p), "r"(v) : "memory");
}
__device__ __forceinline__ uint4 ld_b128(const uint4* p) {
  unsigned long long a, b;
  asm volatile("{\n.reg .b128 v;\nld.relaxed.gpu.global.b128 v, [%2];\nmov.b128 {%0, %1}, v;\n}\n" : "=l"(a), "=l"(b) : "l"(p) : "memory");
  return make_uint4((uint32_t)a, (uint32_t)(a >> 32), (uint32_t)b, (uint32_t)(b >> 32));
}
__device__ __forceinline__ void st_b128(uint4* p, uint32_t x, uint32_t y, uint32_t z, uint32_t w) {
  asm volatile("{\n.reg .b128 v;\nmov.b128 v, {%1, %2};\nst.relaxed.gpu.global.b128 [%0], v;\n}\n"
               ::"l"(p), "l"(x | (unsigned long long)y << 32), "l"(z | (unsigned long long)w << 32) : "memory");
}

struct Params {
  const __nv_bfloat16* x;
  const __nv_bfloat16* w;
  const __nv_bfloat16* q;
  const __nv_bfloat16* k;
  const __nv_bfloat16* v;
  const __nv_bfloat16* shift_k;
  const __nv_bfloat16* ssm_k;
  const __nv_bfloat16* ssm_D;
  const __nv_bfloat16* wo;
  __nv_bfloat16* out;
  uint32_t zero;
};

__device__ __forceinline__ uint32_t lds32(uint32_t a) {
  uint32_t v;
  asm volatile("ld.shared.u32 %0, [%1];\n" : "=r"(v) : "r"(a) : "memory");
  return v;
}
__device__ __forceinline__ float bf_lo(uint32_t v) {
  uint32_t r;
  asm("prmt.b32 %0, %1, 0, 0x1044;\n" : "=r"(r) : "r"(v));
  return __uint_as_float(r);
}
__device__ __forceinline__ float bf_hi(uint32_t v) { return __uint_as_float(v & 0xffff0000u); }
__device__ __forceinline__ float ex2(float x) {
  float r;
  asm("ex2.approx.ftz.f32 %0, %1;\n" : "=f"(r) : "f"(x));
  return r;
}
__device__ __forceinline__ float rcp(float x) {
  float r;
  asm("rcp.approx.ftz.f32 %0, %1;\n" : "=f"(r) : "f"(x));
  return r;
}

#define Q4(c, d, o) c(d[o + 0]), c(d[o + 1]), c(d[o + 2]), c(d[o + 3])
#define Q8(c, d, o) Q4(c, d, o), Q4(c, d, o + 4)
#define Q16(c, d, o) Q8(c, d, o), Q8(c, d, o + 8)
#define Q32(c, d) Q16(c, d, 0), Q16(c, d, 16)
#define L8 "{%0,%1,%2,%3,%4,%5,%6,%7}"
#define L16 "{%0,%1,%2,%3,%4,%5,%6,%7,%8,%9,%10,%11,%12,%13,%14,%15}"
#define L32 "{%0,%1,%2,%3,%4,%5,%6,%7,%8,%9,%10,%11,%12,%13,%14,%15,%16,%17,%18,%19,%20,%21,%22,%23,%24,%25,%26,%27,%28,%29,%30,%31}"
__device__ __forceinline__ void fft_rows(uint32_t (&d)[32], const uint32_t (&a)[2][4], uint64_t db) {
  asm volatile("wgmma.mma_async.sync.aligned.m64n128k16.f16.f16.f16 " L32 ", {%32,%33,%34,%35}, %36, 0, 1, 1, 1;\n"
               : Q32("=r", d) : "r"(a[0][0]), "r"(a[0][1]), "r"(a[0][2]), "r"(a[0][3]), "l"(db));
  asm volatile("wgmma.mma_async.sync.aligned.m64n128k16.f16.f16.f16 " L32 ", {%32,%33,%34,%35}, %36, 1, 1, 1, 1;\n"
               : Q32("+r", d) : "r"(a[1][0]), "r"(a[1][1]), "r"(a[1][2]), "r"(a[1][3]), "l"(db + 64));
}
template <int INV> __device__ __forceinline__ void fft_cols(uint32_t (&d)[8], const uint32_t (&a)[2][4], uint64_t db) {
  asm volatile("wgmma.mma_async.sync.aligned.m64n32k16.f16.f16.f16 " L8 ", {%8,%9,%10,%11}, %12, 0, 1, 1, %13;\n"
               : Q8("=r", d, 0) : "r"(a[0][0]), "r"(a[0][1]), "r"(a[0][2]), "r"(a[0][3]), "l"(db), "n"(INV));
  asm volatile("wgmma.mma_async.sync.aligned.m64n32k16.f16.f16.f16 " L8 ", {%8,%9,%10,%11}, %12, 1, 1, 1, %13;\n"
               : Q8("+r", d, 0) : "r"(a[1][0]), "r"(a[1][1]), "r"(a[1][2]), "r"(a[1][3]), "l"(db + (INV ? 16 : 64)), "n"(INV));
}
__device__ __forceinline__ void fft_back(float (&d)[16], uint64_t da, uint64_t db) {
  asm volatile("wgmma.mma_async.sync.aligned.m64n32k16.f32.f16.f16 " L16 ", %16, %17, 0, 1, 1, 1, 1;\n"
               : Q16("=f", d, 0) : "l"(da), "l"(db));
#pragma unroll
  for (int i = 1; i < 4; i++)
    asm volatile("wgmma.mma_async.sync.aligned.m64n32k16.f32.f16.f16 " L16 ", %16, %17, 1, 1, 1, 1, 1;\n"
                 : Q16("+f", d, 0) : "l"(da + 32 * i), "l"(db + 64 * i));
}
__device__ __forceinline__ uint32_t hmul2(uint32_t a, uint32_t b) {
  uint32_t r;
  asm("mul.rn.f16x2 %0, %1, %2;\n" : "=r"(r) : "r"(a), "r"(b));
  return r;
}
__device__ __forceinline__ uint32_t hadd2(uint32_t a, uint32_t b) {
  uint32_t r;
  asm("add.rn.f16x2 %0, %1, %2;\n" : "=r"(r) : "r"(a), "r"(b));
  return r;
}
__device__ __forceinline__ uint32_t hneg2(uint32_t a) {
  uint32_t r;
  asm("neg.f16x2 %0, %1;\n" : "=r"(r) : "r"(a));
  return r;
}
__device__ __forceinline__ uint32_t hfma2(uint32_t a, uint32_t b, uint32_t c) {
  uint32_t r;
  asm("fma.rn.f16x2 %0, %1, %2, %3;\n" : "=r"(r) : "r"(a), "r"(b), "r"(c));
  return r;
}
__device__ __forceinline__ uint32_t pack_f16(float lo, float hi) {
  uint32_t r;
  asm("cvt.rn.f16x2.f32 %0, %1, %2;\n" : "=r"(r) : "f"(hi), "f"(lo));
  return r;
}
__device__ __forceinline__ uint32_t bmaxabs2(uint32_t a, uint32_t b) {
  uint32_t r;
  asm("max.xorsign.abs.bf16x2 %0, %1, %2;\n" : "=r"(r) : "r"(a), "r"(b));
  return r;
}
struct C2 { uint32_t r, i; };
__device__ __forceinline__ C2 cmul(C2 a, C2 b) {
  return C2{hfma2(a.r, b.r, hneg2(hmul2(a.i, b.i))), hfma2(a.r, b.i, hmul2(a.i, b.r))};
}
__device__ __forceinline__ C2 cfma(C2 a, C2 b, C2 c) {
  return C2{hfma2(a.r, b.r, hfma2(hneg2(a.i), b.i, c.r)), hfma2(a.r, b.i, hfma2(a.i, b.r, c.i))};
}
__device__ __forceinline__ C2 crot(C2 z, C2 t) {
  const uint32_t r = hfma2(t.r, z.i, z.r), i = hfma2(t.i, r, z.i);
  return C2{hfma2(t.r, i, r), i};
}
__device__ __forceinline__ C2 cget(const uint32_t (&e)[8], int j, int b) { return C2{e[4 * j + b], e[4 * j + 2 + b]}; }
template <int N> __device__ __forceinline__ void fence_regs(uint32_t (&d)[N]) {
#pragma unroll
  for (int i = 0; i < N; i++) asm volatile("" : "+r"(d[i])::"memory");
}
__device__ __forceinline__ void ldsm4(uint32_t (&r)[4], uint32_t a) {
  asm volatile("ldmatrix.sync.aligned.m8n8.x4.shared.b16 {%0,%1,%2,%3}, [%4];\n"
               : "=r"(r[0]), "=r"(r[1]), "=r"(r[2]), "=r"(r[3]) : "r"(a) : "memory");
}

__device__ __forceinline__ uint32_t movm(uint32_t a) {
  uint32_t r;
  asm volatile("movmatrix.sync.aligned.m8n8.trans.b16 %0, %1;\n" : "=r"(r) : "r"(a));
  return r;
}
template <int C0, int H, bool T> __device__ __forceinline__ void attn_pack(const float (&acc)[96], uint32_t (&d)[8]) {
#pragma unroll
  for (int c = 0; c < 8; c++) {
    asm volatile("cvt.rn.bf16x2.f32 %0, %1, %2;\n" : "=r"(d[c]) : "f"(acc[4 * (C0 + c) + 2 * H + 1]), "f"(acc[4 * (C0 + c) + 2 * H]));
    if (T) d[c] = movm(d[c]);
  }
}
__device__ __forceinline__ void attn_qk(float (&s)[4], const uint32_t (&qlo)[8], const uint32_t (&qhi)[8],
                                        const uint32_t (&k)[8], int c) {
  mma16816_z(s, qlo[c], qhi[c], qlo[c + 1], qhi[c + 1], k[c], k[c + 1]);
  mma16816(s, qlo[c + 2], qhi[c + 2], qlo[c + 3], qhi[c + 3], k[c + 2], k[c + 3]);
}
template <int N> __device__ __forceinline__ void quad_softmax(float (&x)[N][2], uint32_t (&pp)[N]) {
  const float c2 = 1.4426950408889634f;
  uint32_t q[N], mx[N / 2];
#pragma unroll
  for (int n = 0; n < N; n++) {
    const uint32_t r = pack_bf16(x[n][0], x[n][1]);
    q[n] = bfma2(r, 0x3e353e35u, bmul2(r, 0x379e379eu));
    x[n][0] = bf_lo(q[n]);
    x[n][1] = bf_hi(q[n]);
  }
#pragma unroll
  for (int n = 0; n < N / 2; n++)
    mx[n] = bmax2(__byte_perm(q[2 * n], q[2 * n + 1], 0x5410), __byte_perm(q[2 * n], q[2 * n + 1], 0x7632));
#pragma unroll
  for (int o = 1; o <= 2; o++) {
#pragma unroll
    for (int n = 0; n < N / 2; n++) mx[n] = bmax2(mx[n], __shfl_xor_sync(0xffffffffu, mx[n], o));
  }
  float m[N], t[N];
#pragma unroll
  for (int n = 0; n < N / 2; n++) {
    m[2 * n] = bf_lo(mx[n]);
    m[2 * n + 1] = bf_hi(mx[n]);
  }
#pragma unroll
  for (int n = 0; n < N; n++) {
    const float nm = -m[n] * c2;
    x[n][0] = ex2(fmaf(x[n][0], c2, nm));
    x[n][1] = ex2(fmaf(x[n][1], c2, nm));
  }
#pragma unroll
  for (int n = 0; n < N; n += 2) {
    float u0, u1;
    asm("mma.sync.aligned.m16n8k8.row.col.f32.tf32.tf32.f32 {%0,%1,%2,%3}, {%4,%5,%6,%7}, {%8,%8}, {%9,%9,%9,%9};\n"
        : "=f"(t[n]), "=f"(u0), "=f"(t[n + 1]), "=f"(u1)
        : "r"(__float_as_uint(x[n][0])), "r"(__float_as_uint(x[n + 1][0])), "r"(__float_as_uint(x[n][1])),
          "r"(__float_as_uint(x[n + 1][1])), "r"(0x3f800000u), "f"(0.f));
  }
#pragma unroll
  for (int n = 0; n < N; n++) {
    const float inv = rcp(t[n]);
    pp[n] = pack_bf16(x[n][0] * inv, x[n][1] * inv);
  }
}
template <bool SPLIT>
__device__ __forceinline__ void attn_pv(uint32_t dst, const uint32_t (&vp)[8], const uint32_t (&vo)[8], int c, uint32_t pp,
                                        uint32_t maskLE) {
  const uint32_t b0 = pp & ~maskLE, b1 = pp & maskLE;
  float o[2][4];
#pragma unroll
  for (int i = 0; i < 2; i++) {
    if (SPLIT) {
      asm("mma.sync.aligned.m16n8k8.row.col.f32.bf16.bf16.f32 {%0,%1,%2,%3}, {%4,%5}, {%6}, {%7,%7,%7,%7};\n"
          : "=f"(o[i][0]), "=f"(o[i][1]), "=f"(o[i][2]), "=f"(o[i][3])
          : "r"(vp[c + 2 * i]), "r"(vp[c + 2 * i + 1]), "r"(b0), "f"(0.f));
      asm("mma.sync.aligned.m16n8k8.row.col.f32.bf16.bf16.f32 {%0,%1,%2,%3}, {%4,%5}, {%6}, {%0,%1,%2,%3};\n"
          : "+f"(o[i][0]), "+f"(o[i][1]), "+f"(o[i][2]), "+f"(o[i][3])
          : "r"(vo[c + 2 * i]), "r"(vo[c + 2 * i + 1]), "r"(b1));
    } else {
      mma16816_z(o[i], vp[c + 2 * i], vp[c + 2 * i + 1], vo[c + 2 * i], vo[c + 2 * i + 1], b0, b1);
    }
  }
  stsm4t(dst, pack_bf16(o[0][0], o[0][1]), pack_bf16(o[0][2], o[0][3]), pack_bf16(o[1][0], o[1][1]),
         pack_bf16(o[1][2], o[1][3]));
}

template <int MODE>
__global__ void __cluster_dims__(2, 1, 1) __launch_bounds__(NTHREADS, 1)
fused_kernel(const Params p, const __grid_constant__ CUtensorMap tmX, const __grid_constant__ CUtensorMap tmW,
             const __grid_constant__ CUtensorMap tmWo, const __grid_constant__ CUtensorMap tmWp,
             const __grid_constant__ CUtensorMap tmQ,
             const __grid_constant__ CUtensorMap tmOb,
             const __grid_constant__ CUtensorMap tmXh, const __grid_constant__ CUtensorMap tmWh) {
  extern __shared__ __align__(1024) uint8_t smem[];
  if (threadIdx.x < 32) {
    const uint32_t i = (blockIdx.x & 127) * 16 + (threadIdx.x & 15);
    prefetch_l2(threadIdx.x & 16 ? (const char*)p.w + i * 128 : (const char*)p.x + i * 2048);
  }
  const uint32_t sb = smem_u32(smem);
  const uint32_t bars = sb + OFF_BAR;
  const int tid = threadIdx.x, lane = tid & 31, warp = __shfl_sync(0xffffffffu, tid >> 5, 0);
  const int rank = blockIdx.x & 1;
  const bool halo_cta = blockIdx.x < 4;
  if (halo_cta && MODE != 0) return;
  int grp, mem;
  {
    const int t = (blockIdx.x >> 1) - 4, u = t - 32;
    const int q7 = (u * 37) >> 8;
    const bool lo = (unsigned)t < 32u, mid = (unsigned)u < 28u;
    grp = lo ? (t & 7) : (mid ? 1 + u - 7 * q7 : 0);
    mem = lo ? (t >> 3) : (mid ? 4 + q7 : (t < 0 ? t + 6 : t - 54));
  }
  const int rg = (grp >> 2) * 4 + (mem >> 1), hp = (grp & 3) * 4 + (mem & 1) * 2 + rank;
  const int rb2 = (grp >> 2) * 8 + mem, cb2 = (grp & 3) * 2 + rank;
  const int chb = grp * 16 + mem * 2 + rank;
  const int cta = rg * 16 + hp;
  const int hsel = rb2 & 1;
  const int par = rg >> 2, gidx = rg & 3;

  if (tid < 256 && !halo_cta && MODE != 2) {
    const int r = tid >> 3, c = tid & 7;
    const uint32_t so = r * 128 + ((c ^ (r & 7)) << 4);
    const __nv_bfloat16* wg0 = p.w + (size_t)r * (3 * DM) + hp * 64 + c * 8;
    const __nv_bfloat16* xg0 = p.x + (size_t)(2 * (gidx * 256 + r) + par) * DM + c * 8;
#pragma unroll
    for (int j = 0; j < 3; j++) cp_async16n(sb + OFF_1B + j * 4096 + so, wg0 + j * DM);
#pragma unroll
    for (int i = 0; i < 8; i++) cp_async16n(sb + i * 4096 + so, xg0 + (size_t)i * 64 * DM);
    asm volatile("cp.async.commit_group;\n" ::: "memory");
    if (tid < 16) prefetch_l2((const char*)p.x + (chb * 16 + tid) * 2048 + 128);
    if (warp == 2) prefetch_l2((const char*)p.w + (2048 + chb * 32 + lane) * 128);
  }

  if (warp >= 8) {
    asm volatile("setmaxnreg.dec.sync.aligned.u32 %0;\n" :: "n"(REG_HELP));
    auto halo_issue = [&](int n, int s) {
      const uint32_t fb = bars + 8 * (BAR_FULLB + s), st = sb + s * STGH;
      tma_load_3d(st + 8192, &tmWh, fb, 0, (n >> 1) * 64, 16 + (n & 1) * 16 + blockIdx.x * 4);
      tma_load_4d(st, &tmXh, fb, (n >> 1) * 64, 248, 0, 0);
      mbar_expect_tx(fb, STGH - 2048);
    };
    if (tid == 256) {
      prefetch_tmap(halo_cta ? &tmXh : &tmX);
#pragma unroll
      for (int i = 0; i < NS1B; i++) mbar_init(bars + 8 * (BAR_FULLB + i), 1);
#pragma unroll
      for (int i = 0; i < NS1A; i++) mbar_init(bars + 8 * (BAR_FULLA + i), 1);
      asm volatile("fence.mbarrier_init.release.cluster;\n" ::: "memory");
      if (!halo_cta && MODE != 2) {
        mbar_expect_tx(bars + 8 * (BAR_FULLB + 1), STG1B);
        tma_load_3d(sb + OFF_1B + 1 * STG1B, &tmW, bars + 8 * (BAR_FULLB + 1), hp * 64, 32, 0);
        mbar_expect_tx(bars + 8 * (BAR_FULLB + 2), STG1B);
        tma_load_3d(sb + OFF_1B + 2 * STG1B, &tmW, bars + 8 * (BAR_FULLB + 2), hp * 64, 64, 0);
        mbar_arrive(bars + 8 * BAR_FULLA);
        mbar_arrive(bars + 8 * BAR_FULLB);
      } else if (halo_cta) {
        halo_issue(0, 0);
      }
    } else if (tid == 288) {
#pragma unroll
      for (int i = 0; i < NS1A; i++) mbar_init(bars + 8 * (BAR_EMPTYA + i), 4);
#pragma unroll
      for (int i = 0; i < NS1B; i++) mbar_init(bars + 8 * (BAR_EMPTYB + i), 2);
      mbar_init(bars + 8 * BAR_X, 3);
      mbar_init(bars + 8 * BAR_TAB, 16);
      mbar_init(bars + 8 * BAR_U, 1);
      mbar_init(bars + 8 * BAR_H, 1);
      mbar_init(bars + 8 * BAR_STG, 8);
      mbar_init(bars + 8 * BAR_HALO, 1);
      mbar_init(bars + 8 * BAR_Q, 1);
      mbar_init(bars + 8 * BAR_LAND, 5);
      mbar_init(bars + 8 * (BAR_LAND + 1), 5);
      asm volatile("fence.mbarrier_init.release.cluster;\n" ::: "memory");
    } else if (tid == 320) {
#pragma unroll
      for (int i = 0; i < NS2; i++) {
        mbar_init(bars + 8 * (BAR_FULL2 + i), 1);
        mbar_init(bars + 8 * (BAR_EMPTY2 + i), 2);
        mbar_init(bars + 8 * (BAR_EMPTY2B + i), 2);
      }
      asm volatile("fence.mbarrier_init.release.cluster;\n" ::: "memory");
    } else if (tid == 352) {
#pragma unroll
      for (int i = 0; i < 4; i++) mbar_init(bars + 8 * (BAR_Y + i), i < 2 ? 4 : i == 2 ? 10 : 8);
      mbar_init(bars + 8 * BAR_XFREE, 1);
      asm volatile("fence.mbarrier_init.release.cluster;\n" ::: "memory");
    }
    __syncwarp();
    cluster_sync_all();
    if (warp == 8) PROF2(24);
    const int hw = warp - 8;
    const int lr = lane & 7, lm = lane >> 3;
    auto g1_issue_a = [&](int j, int s) {
      const uint32_t fb = bars + 8 * (BAR_FULLA + s);
      mbar_expect_tx(fb, STG1A);
      tma_load_3d_mc(sb + s * STG1A + rank * 16384, &tmX, fb, j * 64, par, gidx * 256 + rank * 128);
    };
    auto g1_issue_b = [&](int kb, int s) {
      const uint32_t fb = bars + 8 * (BAR_FULLB + s);
      mbar_expect_tx(fb, STG1B);
      tma_load_3d(sb + OFF_1B + s * STG1B, &tmW, fb, hp * 64, kb * 32, 0);
    };
    auto g2_k = [&](int kb) { return (kb < 2 ? hp : kb < 4 ? hp & 14 : hp & 12) ^ kb; };
    auto g2_issue_b = [&](uint32_t fb, uint32_t bytes, uint32_t dst, int k0, bool whole) {
      if (whole) {
        tma_load_3d(dst, &tmWo, fb, 0, k0, cb2 * 2);
      } else {
#pragma unroll
        for (int i = 0; i < 4; i++)
          tma_load_3d(dst + (i & 1) * XT + (i >> 1) * 4 * XT, &tmWp, fb, 0, k0 + (i >> 1) * 32, cb2 * 2 + (i & 1));
      }
      mbar_expect_tx(fb, bytes);
    };
    auto send_y = [&](uint32_t o, uint32_t step, int half) {
      const uint32_t peer = mapa(sb, rank ^ 1);
      o += OFF_X + (rank ^ 1) * 4096 + half * 2048 + lane * 16;
      uint4 a[8];
#pragma unroll
      for (int i = 0; i < 8; i++) a[i] = lds128(sb + o + (i >> 2) * step + (i & 2) * (XT / 2) + (i & 1) * 512);
#pragma unroll
      for (int i = 0; i < 8; i++)
        st_async128(peer + o + 1024 + (i >> 2) * step + (i & 2) * (XT / 2) + (i & 1) * 512,
                    peer + OFF_BAR + 8 * (BAR_LAND + half), a[i].x, a[i].y, a[i].z, a[i].w);
    };

    if (halo_cta) {
      if (hw == 0) {
        int s = 1, ph = 1;
#pragma unroll 1
        for (int n = 1; n < 32; n++) {
          mbar_wait(bars + 8 * (BAR_EMPTYB + s), ph);
          if (elect_one()) halo_issue(n, s);
          if (++s == NS1B) { s = 0; ph ^= 1; }
        }
      }
      __syncwarp();
    } else if (hw == 0) {
      uint32_t epoch = 0;
      if (MODE == 2) {
        if (lane < NS2) mbar_arrive_cluster_n(mapa(bars, rank) + 8 * (BAR_EMPTY2 + lane), 2);
      } else {
      if (lane == 0) {
        mbar_expect_tx(bars + 8 * BAR_U, 32768);
        mbar_expect_tx(bars + 8 * BAR_LAND, 8192);
        mbar_expect_tx(bars + 8 * (BAR_LAND + 1), 8192);
        mbar_expect_tx(bars + 8 * BAR_Q, 32768);
        prefetch_tmap(&tmQ);
      }
      {
        int sa = 1, pha = 1, sbb = 2, phb = 1;
#pragma unroll 1
        for (int kb = 2; kb < 32; kb++) {
          if (!(kb & 1)) {
            mbar_wait(bars + 8 * (BAR_EMPTYA + sa), pha);
            if (elect_one()) g1_issue_a(kb >> 1, sa);
            if (++sa == NS1A) { sa = 0; pha ^= 1; }
          }
          mbar_wait(bars + 8 * (BAR_EMPTYB + sbb), phb);
          if (kb > 2 && elect_one()) g1_issue_b(kb, sbb);
          __syncwarp();
          if (kb == 4) epoch = ld_relaxed(g_flag_o + cta);
          if (kb == 4) PROF2(27);
          if (kb == 1) PROF2(38);
          if (kb == 2) PROF2(39);
          if (++sbb == NS1B) { sbb = 0; phb ^= 1; }
        }
      }
      auto q_issue = [&](int i) {
        mbar_wait(bars + 8 * (i ? BAR_EMPTYB + 3 : BAR_EMPTYA + 1), i);
        if (elect_one())
          asm volatile(
              "cp.async.bulk.tensor.5d.shared::cluster.global.mbarrier::complete_tx::bytes [%0], [%1, {%3, %4, %4, %4, %5}], [%2];\n"
              ::"r"(sb + (i ? OFF_Q1 : OFF_Q0)), "l"(&tmQ), "r"(bars + 8 * BAR_Q), "r"((chb & ~1) * 8), "r"(0), "r"(rank * 32 + i * 64)
              : "memory");
        __syncwarp();
      };
      epoch++;
      if (lane == 0) {
        prefetch_tmap(&tmWo);
        prefetch_tmap(&tmWp);
        prefetch_tmap(&tmOb);
      }
      __syncwarp();
      {
        uint4 h[6] = {};
        if (gidx != 0) {
#pragma unroll 1
          for (int n = 0; n < SPIN_LIMIT; n++) {
            bool ok = true;
#pragma unroll
            for (int i = 0; i < 6; i++) h[i] = ld_b128(g_halo + cta * 192 + i * 32 + lane);
#pragma unroll
            for (int i = 0; i < 6; i++) ok = ok && h[i].w == epoch;
            if (__all_sync(0xffffffffu, ok)) break;
          }
          PROF(18);
        }
        q_issue(0);
        sts128(sb + OFF_KH + lane * 16, h[0].x, h[0].y, h[0].z, h[1].x);
        sts128(sb + OFF_KH + 512 + lane * 16, h[1].y, h[1].z, h[2].x, h[2].y);
        sts64(sb + OFF_KH + 1024 + lane * 8, h[3].x, h[3].y);
        sts64(sb + OFF_KH + 1280 + lane * 8, h[3].z, h[4].x);
        sts64(sb + OFF_KH + 1536 + lane * 8, h[4].y, h[4].z);
        sts64(sb + OFF_KH + 1792 + lane * 8, h[5].x, h[5].y);
        __syncwarp();
        if (lane == 0) mbar_arrive(bars + 8 * BAR_HALO);
      }
      q_issue(1);
      const uint32_t rb = mapa(bars, lane & 1);
      nb_sync(NB_OREADY, 288);
      if (lane == 0) {
        asm volatile("cp.async.bulk.global.shared::cta.bulk_group [%0], [%1], %2;\n" ::"l"(g_o + (size_t)cta * 16384),
                     "r"(sb + OFF_OP), "r"(32768) : "memory");
        bulk_commit();
      }
      if (lane < 2) {
#pragma unroll
        for (int i = 0; i < 4; i++) mbar_arrive_cluster(rb + 8 * (BAR_EMPTY2 + i + i / 2));
      }
      if (lane == 0) {
        bulk_wait0();
        st_release(g_flag_o + cta, epoch);
      }
      __syncwarp();
      PROF2(17);
      if (lane < 2) mbar_arrive_cluster(rb + 8 * (BAR_EMPTY2 + 2));
      }
      if (MODE != 1) {
        const __nv_bfloat16* osrc = g_o + (size_t)(rb2 >> 1) * 16 * 16384 + hsel * 8192;
        mbar_wait(bars + 8 * (BAR_EMPTY2 + 1), 0);
        if (elect_one()) {
          if (MODE == 0) {
            asm volatile("cp.async.bulk.shared::cluster.shared::cta.mbarrier::complete_tx::bytes [%0], [%1], %2, [%3];\n"
                         ::"r"(mapa(sb + g2_a(1, hsel), rank ^ 1)), "r"(sb + g2_a(0, hsel)), "r"(16384),
                         "r"(mapa(bars + 8 * (BAR_FULL2 + 1), rank ^ 1)) : "memory");
          } else {
            bulk_load(sb + g2_a(0, hsel), osrc + hp * 16384, 16384, bars + 8 * BAR_FULL2);
            bulk_load(sb + g2_a(1, hsel), osrc + (hp ^ 1) * 16384, 16384, bars + 8 * (BAR_FULL2 + 1));
          }
        }
        __syncwarp();
      }
      if (MODE != 2) {
        mbar_wait(bars + 8 * (BAR_Y + 2), 0);
        send_y(0, 4 * XT, 1);
        fence_async_smem();
        __syncwarp();
      }
      if (MODE != 1) {
        int s = 3, k0 = g2_k(3) * 64;
        uint32_t wbar = bars + 8 * (BAR_Y + 2), dst = sb + g2_b(3, rank), ph = MODE ? 1 : 0;
#pragma unroll 1
        for (int kb = 3; kb < 16;) {
          mbar_wait(wbar, ph);
          if (elect_one()) g2_issue_b(bars + 8 * (BAR_FULL2 + s), STG2, dst, k0, s < 3);
          __syncwarp();
          kb++;
          if (++s == NS2) { s = 0; ph = kb == 2 * NS2; }
          wbar = bars + 8 * (kb == 4 ? BAR_XFREE : BAR_EMPTY2B + s);
          dst = sb + g2_b(s, rank);
          k0 = ((hp & 12) ^ kb) * 64;
        }
      }
      __syncwarp();
    } else {
      if (MODE != 2) {
      const float dall = __bfloat162float(p.ssm_D[chb * 8 + lr]);
      {
        const int g = lane >> 2, t = lane & 3;
        uint32_t w[2][4];
#pragma unroll
        for (int h = 0; h < 2; h++) {
          const uint2 x = __ldg(reinterpret_cast<const uint2*>(p.shift_k + ((chb & ~1) * 8 + h * 8 + g) * 4));
          w[h][0] = __byte_perm(x.x, x.x, 0x1010);
          w[h][1] = __byte_perm(x.x, x.x, 0x3232);
          w[h][2] = __byte_perm(x.y, x.y, 0x1010);
          w[h][3] = __byte_perm(x.y, x.y, 0x3232);
        }
        auto swz = [](int r) { return (((r & 29) | ((r ^ (r >> 2)) & 2)) << 5) | (r & 16); };
        const uint32_t kring = sb + OFF_X + 4096 + (hw - 1) * 2 * XT, vring = kring + XT;
        const int s0 = rank * 32 + (hw - 1) * 11, s1 = hw == 3 ? rank * 32 + 32 : s0 + 11;
        const size_t goff = (size_t)(s0 * 32 + (lane >> 1)) * DM + (chb & ~1) * 8 + (lane & 1) * 8;
        const __nv_bfloat16* kg = p.k + goff;
        const __nv_bfloat16* vg = p.v + goff;
        const uint32_t d0 = swz(lane >> 1) ^ ((lane & 1) << 4), d1 = swz(16 + (lane >> 1)) ^ ((lane & 1) << 4);
        auto issue = [&](int st) {
          const uint32_t a = kring + ((st & 3) << 10);
          asm volatile("cp.async.cg.shared.global.L2::256B [%0], [%2], 16;\n"
                       "cp.async.cg.shared.global.L2::256B [%1], [%2 + 32768], 16;\n"
                       "cp.async.cg.shared.global.L2::256B [%0 + 8192], [%3], 16;\n"
                       "cp.async.cg.shared.global.L2::256B [%1 + 8192], [%3 + 32768], 16;\n"
                       ::"r"(a + d0), "r"(a + d1), "l"(kg), "l"(vg) : "memory");
          kg += 32 * DM;
          vg += 32 * DM;
          asm volatile("" : "+l"(kg), "+l"(vg));
        };
        const int xa = 8 * (lr >> 1) + 2 * lm + (lr & 1), xb = 8 * (lr >> 1) - 4 + 2 * (lm & 1) + (lr & 1);
        const uint32_t la = swz(xa), lb = swz(xb & 31);
        const int backb = xb < 0 ? 1 : 0;
        const uint32_t ud[2] = {mapa(sb + OFF_X + g * XT + t * 16, 0), mapa(sb + OFF_X + g * XT + t * 16, 1)};
        const uint32_t ub[2] = {mapa(bars + 8 * BAR_U, 0), mapa(bars + 8 * BAR_U, 1)};
        if (tid == 320) prefetch_l2(g_tab + (chb & 63) * 32);
        if (lane == 0) mbar_wait(bars + 8 * (BAR_FULLB + NS1B - 1), 0);
        __syncwarp();
        if (lane >= 24) cp_async16(kring + (((s0 - 1) & 3) << 10) + d1, s0 > 0 ? kg - 16 * DM : kg, s0 > 0 ? 16 : 0);
        issue(s0);
        asm volatile("cp.async.commit_group;\n" ::: "memory");
        issue(s0 + 1);
        asm volatile("cp.async.commit_group;\n" ::: "memory");
        const __nv_bfloat16* hg = p.ssm_k + (size_t)chb * 8 * SEQ + lane * 64;
        uint32_t tn = (uint32_t)clock();
#pragma unroll 1
        for (int st = s0; st < s1; st++) {
          tn += PSTEP;
          while ((int)((uint32_t)clock() - tn) < 0) __nanosleep(100);
          if (st + 2 < s1) issue(st + 2);
          if (hw == 1 && st - s0 < 8) prefetch_l2(hg);
          hg += SEQ;
          asm volatile("" : "+l"(hg));
          asm volatile("cp.async.commit_group;\n" ::: "memory");
          asm volatile("cp.async.wait_group 2;\n" ::: "memory");
          __syncwarp();
#pragma unroll
          for (int h = 0; h < 2; h++) {
            uint32_t e[6], vv[4], e4[4];
            ldsm4t(e4, kring + ((st & 3) << 10) + (la ^ (h << 4)));
            ldsm2t(e[0], e[1], kring + (((st - backb) & 3) << 10) + (lb ^ (h << 4)));
            ldsm4t(vv, vring + ((st & 3) << 10) + (la ^ (h << 4)));
            e[2] = e4[0]; e[3] = e4[1]; e[4] = e4[2]; e[5] = e4[3];
            uint32_t o[5];
#pragma unroll
            for (int i = 0; i < 5; i++) o[i] = __byte_perm(e[i], e[i + 1], 0x5432);
#pragma unroll
            for (int i = 0; i < 4; i++) {
              uint32_t a = bmul2(o[i], w[h][3]);
              a = bfma2(e[i + 1], w[h][2], a);
              a = bfma2(o[i + 1], w[h][1], a);
              a = bfma2(e[i + 2], w[h][0], a);
              vv[i] = bmul2(a, vv[i]);
            }
            st_async128(ud[h] + (st ^ (g & 1)) * 64, ub[h], vv[0], vv[1], vv[2], vv[3]);
          }
          __syncwarp();
        }
        fence_async_smem();
        PROF(16);
      }
      nb_sync(NB_HELP3, 96);
      if (hw == 1 && elect_one()) {
        mbar_expect_tx(bars + 8 * BAR_H, 8 * 4096 + 6144);
#pragma unroll 1
        for (int c = 0; c < 8; c++)
          bulk_load(sb + OFF_X + c * XT + 4096, p.ssm_k + (size_t)(chb * 8 + c) * SEQ, 4096, bars + 8 * BAR_H);
        bulk_load(sb + OFF_T16, g_tab, 2048, bars + 8 * BAR_H);
        bulk_load(sb + OFF_T32, g_tab + 512, 4096, bars + 8 * BAR_H);
      }
      __syncwarp();
      {
        if (hw == 3) {
          const char* wo = (const char*)p.wo + chb * 16384 + lane * 128;
#pragma unroll
          for (int i = 0; i < 4; i++) prefetch_l2(wo + i * 4096);
        }
        const int ck = 16 * (lane >> 4) + 2 * lr + (((lane >> 3) ^ (lane >> 2)) & 1);
        const uint32_t xo = (ck >> 1) * 64, xs = ((ck & 1) ^ (lr >> 1)) << 4;
#pragma unroll 1
        for (int job = hw - 1; job < 16; job += 3) {
          const int c = job & 7;
          uint4 a[8];
          float dv = __shfl_sync(0xffffffffu, dall, c);
          if (job < 8 || lane) dv = 0.f;
          const uint32_t xt = sb + OFF_X + c * XT + (job >> 3) * 4096;
          mbar_wait(bars + 8 * (job < 8 ? BAR_U : BAR_H), 0);
#pragma unroll
          for (int i = 0; i < 8; i++) a[i] = lds128(xt + i * 512 + ((ck ^ (job < 8 ? (c & 1) << 2 : 0)) << 4));
          dv += bf_lo(a[0].x);
          uint32_t m[2] = {bmaxabs2(pack_bf16(dv, 0.f), bmaxabs2(a[0].x, a[0].y)), bmaxabs2(a[0].z, a[0].w)};
#pragma unroll
          for (int i = 1; i < 8; i++) {
            m[0] = bmaxabs2(bmaxabs2(m[0], a[i].x), a[i].y);
            m[1] = bmaxabs2(bmaxabs2(m[1], a[i].z), a[i].w);
          }
          m[0] = bmaxabs2(m[0], m[1]);
          const int f = max(252 - (int)(__reduce_max_sync(0xffffffffu, max(m[0] & 0x7fffu, (m[0] >> 16) & 0x7fffu)) >> 7), 1);
          if (lane == 0) asm volatile("st.shared.u32 [%0], %1;\n" ::"r"(sb + OFF_EX + job * 4), "r"(f) : "memory");
          if (f < 113) {
#pragma unroll
            for (int i = 0; i < 8; i++)
              a[i] = make_uint4(bmul2(a[i].x, f * 0x00800080u), bmul2(a[i].y, f * 0x00800080u), bmul2(a[i].z, f * 0x00800080u),
                                bmul2(a[i].w, f * 0x00800080u));
          }
          const uint32_t mul = (f < 113 ? 15 : f - 112) * 0x00800080u;
          auto cv = [&](uint32_t x) {
            x = bmul2(x, mul);
            return (x & 0x0fff0fffu) * 7 + x;
          };
          const uint32_t dst = xt + xo;
#pragma unroll
          for (int i = 0; i < 8; i++)
            sts128(dst + (i >> 2) * 2048 + (i & 1) * 1024 + (xs ^ ((i & 2) << 4)),
                   i ? cv(a[i].x) : __byte_perm(pack_f16(dv * __uint_as_float(f << 23), 0.f), cv(a[i].x), 0x7610), cv(a[i].y),
                   cv(a[i].z), cv(a[i].w));
        }
        fence_async_smem();
        __syncwarp();
        if (lane == 0) mbar_arrive(bars + 8 * BAR_X);
        PROF(19);
      }
      if (hw < 3) {
#pragma unroll 1
        for (int n = 0; n < SPIN_LIMIT && !mbar_try(bars + 8 * (BAR_Y + hw - 1), 0); n++) __nanosleep(100);
        send_y((hw - 1) * 4 * XT, 2 * XT, 0);
        __syncwarp();
        if (lane == 0) mbar_arrive(bars + 8 * (BAR_Y + 2));
        PROF(32);
        const int c8 = 2 * lm + (lr & 1), src = (lr >> 1) & 1;
        uint32_t fa = sb + OFF_X + c8 * XT + rank * 4096 + (src == rank ? 0 : 1024) + (hw - 1) * 512;
        const uint32_t fx = ((lr >> 2) ^ ((lr & 3) << 1)) << 4;
        uint32_t qa = sb + OFF_Q0 + (hw - 1) * 8192 + (lane >> 3) * 128 + (lane & 2) * 32 + (lane & 4) * 8 + (lane & 1) * 16;
        uint4* og = reinterpret_cast<uint4*>(p.out + (size_t)(rank * 512 + (hw - 1) * 256 + (lane & 2) * 4 + (lane >> 2)) * (2 * DM) +
                                             (chb & ~1) * 8 + (lane & 1) * 8);
        mbar_wait(bars + 8 * BAR_Q, 0);
        uint32_t tn = 0;
#pragma unroll 1
        for (int j = 0; j < 16; j++) {
          if (j == 1 && hw == 2) {
            mbar_wait(bars + 8 * (BAR_Y + 3), 0);
            send_y(2 * XT, 4 * XT, 1);
            fence_async_smem();
            __syncwarp();
            if (lane == 0) mbar_arrive(bars + 8 * BAR_XFREE);
            tn = (uint32_t)clock();
          }
          if (!(j & 7)) {
            mbar_wait(bars + 8 * (BAR_LAND + (j >> 3)), 0);
            tn = (uint32_t)clock() + (hw - 1) * (FPACE / 2);
            PROF2(33 + (j >> 1));
          }
#pragma unroll
          for (int i = 0; i < 2; i++) {
            uint32_t y[4];
            const uint4 q = lds128(qa + i * 512);
            ldsm4t(y, fa + (j & 6) * 64 + (fx ^ (i << 5) ^ ((j & 1) << 6) ^ ((j & 2) << 3)));
            while ((int)((uint32_t)clock() - tn) < 0) __nanosleep(50);
            tn += hw == 2 ? FPACE2 : FPACE;
            og[i * 16 * (2 * DM / 8)] = make_uint4(bmul2(q.x, y[0]), bmul2(q.y, y[1]), bmul2(q.z, y[2]), bmul2(q.w, y[3]));
          }
          qa += j == 7 ? OFF_Q1 - OFF_Q0 - 7168 : 1024;
          if (j == 7) fa += 2048;
          og += (j == 7 ? 1024 - 224 : 32) * (2 * DM / 8);
        }
        PROF(22);
      }
      }
      if (MODE != 1 && hw == 3) {
        const uint32_t epoch = ld_relaxed(g_flag_o + cta) + 1;
        if (MODE == 0) nb_sync(NB_G1END, 288);
        if (elect_one()) {
#pragma unroll
          for (int kb = 0; kb < 3; kb++)
            g2_issue_b(bars + 8 * (BAR_FULL2 + kb), kb || MODE ? STG2 : STG2 / 2, sb + g2_b(kb, 0), g2_k(kb) * 64, true);
        }
        __syncwarp();
        const __nv_bfloat16* osrc = g_o + (size_t)(rb2 >> 1) * 16 * 16384 + hsel * 8192;
        if (MODE == 0) __nanosleep(1500);
        const uint32_t* flag = g_flag_o + (rb2 >> 1) * 16 + g2_k(lane & 15);
        uint32_t ready = MODE == 0 ? 0u : ~0u;
        int s = 2, ph = 0;
#pragma unroll 1
        for (int kb = 2; kb < 16; kb++) {
          uint32_t so = bars + s * 8, dst = sb + g2_a(s, hsel) + rank * 8192;
          const __nv_bfloat16* src = osrc + rank * 4096 + (uint32_t)g2_k(kb) * 16384;
          asm volatile("" : "+r"(so), "+r"(dst), "+l"(src));
          if (!(ready >> kb & 1)) {
#pragma unroll 1
            for (int n = 0; n < SPIN_LIMIT && !(ready >> kb & 1); n++)
              ready = __ballot_sync(0xffffffffu, ld_acquire(flag) == epoch);
            fence_async_all();
          }
          if (kb == 2) PROF(21);
          if (MODE == 0 && kb == 4 && rank == 1) mbar_wait(bars + 8 * BAR_TAB, 0);
          mbar_wait(so + 8 * BAR_EMPTY2, ph);
          if (elect_one()) {
            asm volatile(
                "cp.async.bulk.shared::cluster.global.mbarrier::complete_tx::bytes.multicast::cluster [%0], [%1], %2, [%3], %4;\n"
                ::"r"(dst), "l"(src), "r"(8192), "r"(so + 8 * BAR_FULL2), "h"((uint16_t)3) : "memory");
          }
          __syncwarp();
          if (++s == NS2) { s = 0; ph ^= 1; }
        }
      }
    }
    cluster_sync_all();
    PROF_DUMP();
  } else {
    asm volatile("barrier.cluster.arrive.relaxed.aligned;\n" ::: "memory");
    asm volatile("setmaxnreg.inc.sync.aligned.u32 %0;\n" :: "n"(REG_MATH));
    if (halo_cta || MODE == 2) asm volatile("barrier.cluster.wait.aligned;\n" ::: "memory");
    if (warp == 0) PROF2(26);
    const int wg = warp >> 2;
    const int wtid = tid & 127;
    const bool signaller = (wtid == 0) || (wtid == 32);
    const uint32_t rbars = mapa(bars, wtid >> 5 & 1);

    if (halo_cta) {
      const uint32_t epoch = ld_relaxed(g_flag_o + 16 + blockIdx.x * 4) + 1;
      float acc0[64], acc1[64];
      int s = wg, ph = 0;
#pragma unroll 1
      for (int kb = 0; kb < 16; kb++) {
        mbar_wait(bars + 8 * (BAR_FULLB + s), ph);
        const uint32_t st = sb + s * STGH;
        const uint64_t da = mkdesc(st, 16, 1024, 1);
        const uint64_t db = mkdesc(st + 8192, 8192, 1024, 1);
        wg_fence();
#pragma unroll
        for (int kk = 0; kk < 4; kk++) {
          wgmma_n128(acc0, da + 2 * kk, db + 128 * kk, kb + kk);
          wgmma_n128(acc1, da + 2 * kk, db + 1024 + 128 * kk, kb + kk);
        }
        wg_commit();
        wg_wait<0>();
        if (kb == 15) PROF(37);
        if (wtid < 2) mbar_arrive(bars + 8 * (BAR_EMPTYB + s));
        if ((s += 2) >= NS1B) { s -= NS1B; ph ^= 1; }
      }
      fence_regs(acc0);
      fence_regs(acc1);
      if ((warp & 3) != 3) {
        auto put = [&](const float (&acc)[64], int hp0) {
#pragma unroll
          for (int n = 0; n < 4; n++) {
            uint32_t x[8];
#pragma unroll
            for (int c = 0; c < 8; c++) {
              x[c] = pack_bf16(acc[32 * (n >> 1) + 4 * c + 2 * (n & 1)], acc[32 * (n >> 1) + 4 * c + 2 * (n & 1) + 1]);
              if (wg) x[c] = movm(x[c]);
            }
            uint4* dst = g_halo + (((n & 1) * 4 + (warp & 3) + 1) * 16 + blockIdx.x * 4 + hp0 + (n >> 1)) * 192 + wg * 96 + lane;
            st_b128(dst, x[0], x[1], x[2], epoch);
            st_b128(dst + 32, x[3], x[4], x[5], epoch);
            st_b128(dst + 64, x[6], x[7], 0, epoch);
          }
        };
        put(acc0, 0);
        put(acc1, 2);
      }
      PROF(36);
      cluster_sync_all();
      return;
    }

    float acc[64];
    const uint32_t g2rel = wtid ? mapa(bars, rank) + 8 * BAR_EMPTY2B : mapa(bars, wg) + 8 * BAR_EMPTY2;
    uint32_t g2a = (uint32_t)mkdesc(sb + wg * 8192, 16, 0, 0), g2b = (uint32_t)mkdesc(sb, 8192, 0, 0);
    auto g2_block = [&](bool first, int s, int ph) {
      mbar_wait(bars + 8 * (BAR_FULL2 + s), ph);
      const uint32_t da = g2a + (g2_a(s, hsel) >> 4), db = g2b + (g2_b(s, rank) >> 4), dc = db + (g2_bk(s) >> 4);
      wg_fence();
      if (first) wgmma_n128z(acc, da, db);
      else wgmma_n128a(acc, da, db);
      wgmma_n128a(acc, da + 2, db + 128);
      wgmma_n128a(acc, da + 4, dc);
      wgmma_n128a(acc, da + 6, dc + 128);
      wg_commit();
    };
    if (MODE != 2) {
    uint32_t a1[2][4], sc[2];
    C2 t[2];
    {
      float acc0[96], acc1[96];
      int sa = 0, pha = 0;
      uint64_t db0 = mkdesc(sb + OFF_1B, 4096, 1024, 1);
      const uint64_t da0 = mkdesc(sb + wg * 16384, 16, 2048, 1);
      const bool sigb = wtid == 64;
      uint32_t rela = 0;
#pragma unroll 1
      for (int r = 0; r < 3; r++) {
#pragma unroll
        for (int i = 0; i < 2 * NS1B; i++) {
          const uint64_t da = da0 + sa * (STG1A >> 4) + (i & 1) * 4, db = db0 + (i % NS1B) * (STG1B >> 4);
          if (i || r) {
            if (!(i & 1)) mbar_wait(bars + 8 * (BAR_FULLA + sa), pha);
            mbar_wait(bars + 8 * (BAR_FULLB + i % NS1B), i / NS1B);
          } else {
            asm volatile("cp.async.wait_group 0;\n" ::: "memory");
            fence_async_smem();
            nb_sync(NB_FIRST, 256);
            PROF(0 + wg);
          }
          wg_fence();
          wgmma_n192(acc0, da + 64, db, i ? 1 : r);
          wgmma_n192(acc1, da, db, i ? 1 : r);
          wgmma_n192(acc0, da + 66, db + 128, 1);
          wgmma_n192(acc1, da + 2, db + 128, 1);
          wg_commit();
          wg_wait<1>();
          if (i || r) {
            if (sigb) mbar_arrive(bars + 8 * (BAR_EMPTYB + (i + NS1B - 1) % NS1B));
            if (!(i & 1) && signaller) mbar_arrive_cluster(rela);
          } else {
            asm volatile("barrier.cluster.wait.aligned;\n" ::: "memory");
          }
          if (i & 1) {
            rela = rbars + 8 * (BAR_EMPTYA + sa);
            if (++sa == NS1A) { sa = 0; pha ^= 1; }
          }
        }
        db0 += p.zero;
      }
      const int lr = lane & 7, lm = lane >> 3;
      const bool le0 = 2 * (lane & 3) <= (lane >> 2), le1 = 2 * (lane & 3) + 1 <= (lane >> 2);
      const uint32_t maskLE = (le0 ? 0x0000FFFFu : 0u) | (le1 ? 0xFFFF0000u : 0u);
      uint32_t q[4][8], k[5][8], vt[5][8];
      {
        static_assert(15 % NS1A == 0 && 30 % NS1B == 0, "slots of the last k blocks");
        asm volatile("ld.volatile.global.v4.u32 {%0,%1,%2,%3}, [%4];\n"
                     : "=r"(t[0].r), "=r"(t[1].r), "=r"(t[0].i), "=r"(t[1].i) : "l"(g_tab + 1536 + wtid * 4) : "memory");
        mbar_wait(bars + 8 * BAR_FULLA, 1);
        mbar_wait(bars + 8 * BAR_FULLB, 0);
        mbar_wait(bars + 8 * (BAR_FULLB + 1), 0);
        mbar_wait(bars + 8 * (BAR_EMPTYA + 1), 0);
        mbar_wait(bars + 8 * BAR_H, 0);
        const uint64_t da = mkdesc(sb + wg * 16384, 16, 2048, 1);
        const uint64_t db = mkdesc(sb + OFF_1B, 4096, 1024, 1);
        wg_fence();
#pragma unroll
        for (int i = 0; i < 4; i++) wgmma_n192(acc0, da + 64 + 2 * i, db + (i >> 1) * (STG1B >> 4) + (i & 1) * 128, 1);
        wg_commit();
#pragma unroll
        for (int i = 0; i < 2; i++) wgmma_n192(acc1, da + 2 * i, db + (i >> 1) * (STG1B >> 4) + (i & 1) * 128, 1);
        wg_commit();
        wg_wait<1>();
        fence_regs(acc0);
        PROFA(45, 0);
        attn_pack<8, 1, false>(acc0, k[4]);
        attn_pack<16, 1, true>(acc0, vt[4]);
        const uint32_t kh = sb + (warp == 7 ? OFF_OP + 7 * 4096 : OFF_KH + (warp + 1) * 2048) + lane * 16;
        sts128(kh, k[4][0], k[4][1], k[4][2], k[4][3]);
        sts128(kh + 512, k[4][4], k[4][5], k[4][6], k[4][7]);
#pragma unroll
        for (int i = 0; i < 4; i++) sts64(kh - lane * 8 + 1024 + 256 * i, vt[4][2 * i], vt[4][2 * i + 1]);
#pragma unroll
        for (int i = 2; i < 4; i++) wgmma_n192(acc1, da + 2 * i, db + (i >> 1) * (STG1B >> 4) + (i & 1) * 128, 1);
        wg_commit();
        attn_pack<0, 0, false>(acc0, q[1]);
        attn_pack<0, 1, false>(acc0, q[3]);
        attn_pack<8, 0, false>(acc0, k[2]);
        attn_pack<16, 0, true>(acc0, vt[2]);
        uint32_t z = p.zero;
#pragma unroll
        for (int i = 0; i < 8; i++) z &= q[1][i] & q[3][i];
#pragma unroll
        for (int i = 0; i < 8; i += 2) z &= k[2][i] & k[2][i + 1];
        __syncwarp();
        if (lane == 0) mbar_arrive(bars + 8 * BAR_STG + z);
        wg_wait<0>();
        fence_regs(acc1);
        if (MODE == 0) nb_arrive(NB_G1END, 288);
      }
      PROF(2 + wg);
      mbar_wait(bars + 8 * (warp == 0 ? BAR_HALO : BAR_STG), 0);
      {
        const uint32_t kh = sb + OFF_KH + warp * 2048 + lane * 16;
#pragma unroll
        for (int i = 0; i < 2; i++) {
          const uint4 t = lds128(kh + 512 * i);
          k[0][4 * i] = t.x; k[0][4 * i + 1] = t.y; k[0][4 * i + 2] = t.z; k[0][4 * i + 3] = t.w;
        }
#pragma unroll
        for (int i = 0; i < 4; i++) {
          const uint2 t = lds64(kh - lane * 8 + 1024 + 256 * i);
          vt[0][2 * i] = t.x; vt[0][2 * i + 1] = t.y;
        }
      }
      attn_pack<0, 0, false>(acc1, q[0]);
      attn_pack<0, 1, false>(acc1, q[2]);
      attn_pack<8, 0, false>(acc1, k[1]);
      attn_pack<8, 1, false>(acc1, k[3]);
      {
        float x[8][2];
        uint32_t pp[8];
        const bool first = warp == 0 && gidx == 0;
#pragma unroll
        for (int hd = 0; hd < 2; hd++) {
#pragma unroll
          for (int j = 0; j < 4; j += 2) {
            float s0[4], s1[4], s2[4];
            attn_qk(s2, q[j], q[j + 1], k[j + 2], 4 * hd);
            attn_qk(s1, q[j], q[j + 1], k[j + 1], 4 * hd);
            attn_qk(s0, q[j], q[j + 1], k[j], 4 * hd);
            if (j == 0 && first) s0[0] = s0[1] = -1e9f / 0.17677669529663687f;
            x[2 * j + hd][0] = le0 ? s1[0] : s0[0];
            x[2 * j + hd][1] = le1 ? s1[1] : s0[1];
            x[2 * j + 2 + hd][0] = le0 ? s2[2] : s1[2];
            x[2 * j + 2 + hd][1] = le1 ? s2[3] : s1[3];
          }
        }
        PROFA(40, __float_as_uint(x[1][0] + x[7][1]));
        attn_pack<16, 0, true>(acc1, vt[1]);
        attn_pack<16, 1, true>(acc1, vt[3]);
        quad_softmax<8>(x, pp);
        PROFA(41, pp[1] + pp[7]);
        ldsm4(a1[0], sb + OFF_T32 + (warp & 3) * 1024 + lane * 16);
        ldsm4(a1[1], sb + OFF_T32 + 512 + (warp & 3) * 1024 + lane * 16);
        const uint32_t obase = sb + OFF_OP + (warp * 32 + lr) * 128;
#pragma unroll
        for (int n = 0; n < 8; n++) {
          const uint32_t dst = obase + (n >> 1) * 1024 + (((4 * (n & 1) + lm) ^ lr) << 4);
          if (n & 2) attn_pv<true>(dst, vt[n >> 1], vt[(n >> 1) + 1], 4 * (n & 1), pp[n], maskLE);
          else attn_pv<false>(dst, vt[n >> 1], vt[(n >> 1) + 1], 4 * (n & 1), pp[n], maskLE);
        }
      }
      PROFA(42, 0);
    }

    {
      const int w = warp & 3;
      const int lr = lane & 7, lm = lane >> 3;
      const uint32_t xb = sb + OFF_X + wg * 4 * XT;
      auto uo = [](int c) { return (c & 1) * 2 * XT + (c >> 1) * 2048; };
      const uint64_t dc2 = mkdesc(sb + OFF_T16, 512, 128, 0), dc3 = mkdesc(sb + OFF_T16, 128, 512, 0);
      const uint64_t dc4 = mkdesc(sb + OFF_T32, 128, 256, 0);
      const uint64_t dx = mkdesc(xb, 4096, 512, 2), dz = mkdesc(xb, 4096, 256, 3);
      const uint32_t zs = xb + (w * 16 + (lm & 1) * 8 + lr) * 32 + (((lm >> 1) ^ (lr >> 2)) << 4);
      const uint32_t ys = xb + w * 4096 + (lm >> 1) * 256 + ((lr * 32 + (((lm & 1) ^ (lr >> 2)) << 4)) ^ (rank << 6) ^ ((w & 2) << 4));
      const bool own = (w & 1) == rank;
      const uint32_t ybar = mapa(bars, own ? rank ^ 1 : rank) + 8 * BAR_Y;
      uint32_t d[2][32], pa[2][4][2][4], e[4][4][8], ya[2][2][2][4], v[2][2][8];
      C2 s1[2][2][2];
      float o[2][16];
      auto rows = [&](int c) {
        fft_rows(d[c & 1], a1, dx + (uo(c) >> 4));
        wg_commit();
      };
      auto cols = [&](int c) {
        const int s = c & 1;
        fence_regs(d[s]);
#pragma unroll
        for (int i = 0; i < 16; i++) {
          const C2 z = crot(C2{d[s][2 * i], d[s][2 * i + 1]}, t[i & 1]);
          pa[s][i >> 2][i & 1][(i >> 1) & 1] = z.r;
          pa[s][i >> 2][i & 1][2 + ((i >> 1) & 1)] = z.i;
        }
        wg_fence();
#pragma unroll
        for (int i = 0; i < 4; i++) fft_cols<0>(e[c][i], pa[s][i], dc2);
        wg_commit();
      };
      auto prod = [&](int c, int n) {
        const int s = c & 1;
        fence_regs(e[c][2 * n]);
        fence_regs(e[c][2 * n + 1]);
#pragma unroll
        for (int j = 0; j < 2; j++) {
          const C2 u0 = cget(e[s][2 * n], j, 0), u1 = cget(e[s][2 * n], j, 1);
          const C2 h0 = cget(e[s][2 * n + 1], j, 0), h1 = cget(e[s][2 * n + 1], j, 1);
          C2 y0, y1;
          if (c < 2) {
            y0 = cmul(h0, u0);
            s1[s][n][j] = cfma(h0, u1, cmul(h1, u0));
            y1 = C2{hadd2(s1[s][n][j].r, y0.i), hadd2(s1[s][n][j].i, hneg2(y0.r))};
          } else {
            const C2 u2 = cget(e[c][2 * n], j, 0), u3 = cget(e[c][2 * n], j, 1);
            const C2 h2 = cget(e[c][2 * n + 1], j, 0), h3 = cget(e[c][2 * n + 1], j, 1);
            const C2 s2 = cfma(h0, u2, cfma(h2, u0, cmul(h1, u1)));
            y0 = C2{hadd2(s2.r, s1[s][n][j].i), hadd2(s2.i, hneg2(s1[s][n][j].r))};
            y1 = cfma(h0, u3, cfma(h1, u2, cfma(h2, u1, cfma(h3, u0, C2{s2.i, hneg2(s2.r)}))));
          }
          ya[s][n][j][0] = y0.r;
          ya[s][n][j][1] = y1.r;
          ya[s][n][j][2] = y0.i;
          ya[s][n][j][3] = y1.i;
        }
      };
      auto icols = [&](int c) {
        wg_fence();
        fft_cols<1>(v[c & 1][0], ya[c & 1][0], dc3);
        fft_cols<1>(v[c & 1][1], ya[c & 1][1], dc3);
        wg_commit();
      };
      auto stage = [&](int c) {
        const int s = c & 1;
        fence_regs(v[s][0]);
        fence_regs(v[s][1]);
#pragma unroll
        for (int b = 0; b < 4; b++) {
          const C2 x0 = cget(v[s][b >> 1], 0, b & 1), x1 = cget(v[s][b >> 1], 1, b & 1);
          const C2 z0 = crot(C2{x0.i, x0.r}, t[0]), z1 = crot(C2{x1.i, x1.r}, t[1]);
          stsm4(zs + uo(c) + b * 4096, z0.i, z0.r, z1.i, z1.r);
        }
      };
      auto back = [&](int c) {
        fft_back(o[c & 1], dz + (uo(c) >> 4), dc4);
        wg_commit();
      };
      auto out = [&](int c) {
        float (&r)[16] = o[c & 1];
        fence_regs(r);
#pragma unroll
        for (int i = 0; i < 16; i += 8)
          stsm4t(ys + uo(c) + 64 * i, bmul2(pack_bf16(r[i], r[i + 1]), sc[c & 1]), bmul2(pack_bf16(r[i + 2], r[i + 3]), sc[c & 1]),
                 bmul2(pack_bf16(r[i + 4], r[i + 5]), sc[c & 1]), bmul2(pack_bf16(r[i + 6], r[i + 7]), sc[c & 1]));
      };
      auto signal = [&](int yb, int land) {
        __syncwarp();
        if (lane == 0) {
          mbar_arrive_cluster(ybar + 8 * yb);
          if (own && land >= 0) mbar_arrive(bars + 8 * (BAR_LAND + land));
        }
      };
      mbar_wait(bars + 8 * BAR_X, 0);
      wg_fence();
      rows(0);
      rows(1);
      fence_async_smem();
      nb_arrive(NB_OREADY, 288);
#pragma unroll
      for (int i = 0; i < 2; i++) {
        const uint32_t ex = sb + OFF_EX + wg * 16 + (w & 2) * 2 + 8 * i;
        sc[i] = min(max(381 - (int)lds32(ex) - (int)lds32(ex + 32), 1), 254) * 0x00800080u;
      }
      PROF(34 + wg);
      wg_wait<1>();
      cols(0);
      wg_wait<1>();
      cols(1);
      rows(2);
      nb_sync(NB_CONV + wg, 128);
      wg_wait<2>();
      prod(0, 0);
      prod(0, 1);
      icols(0);
      wg_wait<2>();
      prod(1, 0);
      prod(1, 1);
      icols(1);
      PROF3(40 + 10 * wg);
      wg_wait<1>();
      stage(0);
      wg_wait<0>();
      stage(1);
      fence_async_smem();
      cols(2);
      PROF3(41 + 10 * wg);
      nb_sync(NB_CONV + wg, 128);
      back(0);
      back(1);
      wg_wait<2>();
      prod(2, 0);
      wg_fence();
      rows(3);
      wg_wait<1>();
      out(0);
      out(1);
      signal(wg, 0);
      PROF3(42 + 10 * wg);
      prod(2, 1);
      icols(2);
      wg_wait<1>();
      cols(3);
      PROF3(43 + 10 * wg);
      wg_wait<1>();
      stage(2);
      fence_async_smem();
      wg_wait<0>();
      prod(3, 0);
      nb_sync(NB_CONV + wg, 128);
      wg_fence();
      back(2);
      prod(3, 1);
      icols(3);
      PROF3(44 + 10 * wg);
      wg_wait<1>();
      out(2);
      signal(2, -1);
      wg_wait<0>();
      stage(3);
      PROF3(45 + 10 * wg);
      fence_async_smem();
      nb_sync(NB_CONV + wg, 128);
      wg_fence();
      back(3);
      constexpr int G = MODE == 0;
      if (G) {
        mbar_wait(bars + 8 * (BAR_EMPTY2 + 4), 0);
        g2_block(true, 0, 0);
      }
      wg_wait<G>();
      if (lane == 0) mbar_arrive_cluster(mapa(bars, 1) + 8 * BAR_TAB);
      out(3);
      signal(3, 1);
      PROF(6 + wg);
    }
    }

    if (MODE != 1) {
      if (MODE == 2) g2_block(true, 0, 0);
      const int lr = lane & 7, lm = lane >> 3;
      const uint32_t wb = sb + g2_a(1, 0) + warp * 2048;
      const int orow = (rb2 & 7) * 128 + warp * 16;
      uint4* og = reinterpret_cast<uint4*>(p.out + (size_t)(2 * (orow + lm) + (rb2 >> 3)) * (2 * DM) + DM + cb2 * 128 + lr * 8);
      uint32_t wst = wb + (lr + 8 * (lm & 1)) * 128, wsx = ((lm >> 1) ^ lr) << 4, wld = wb + lm * 128, wlx = (lr ^ lm) << 4;
      asm volatile("" : "+l"(og), "+r"(wst), "+r"(wsx), "+r"(wld), "+r"(wlx));
#pragma unroll 1
      for (int r = 0; r < 3; r++) {
        const bool hold = r == 2 && wg != LEADWG;
        if (hold) {
          wg_wait<0>();
          if (signaller) mbar_arrive_cluster(g2rel);
          nb_sync(NB_LEAD, 256);
        }
#pragma unroll
        for (int i = 1; i <= NS2; i++) {
          g2_block(false, i % NS2, (r & 1) ^ (i == NS2));
          if (warp == LEADWG * 4) PROF2(40 + 5 * r + i);
          if (i == 1 ? !hold : r < 2) {
            wg_wait<1>();
            if (signaller) mbar_arrive_cluster(g2rel + 8 * (i - 1));
          }
        }
        if (r == 0) PROF(8 + wg);
        g2a += p.zero;
        g2b += p.zero;
      }
      if (wg == LEADWG) nb_arrive(NB_LEAD, 256);
      asm volatile("barrier.cluster.arrive.relaxed.aligned;\n" ::: "memory");
      wg_wait<0>();
      fence_regs(acc);
      PROF(10 + wg);
#pragma unroll
      for (int h = 0; h < 2; h++) {
        const uint32_t b = h * (g2_a(3, 0) - g2_a(1, 0));
#pragma unroll
        for (int j = 8 * h; j < 8 * h + 8; j += 2)
          stsm4(wst + b + (wsx ^ ((j & 7) << 4)), pack_bf16(acc[4 * j], acc[4 * j + 1]),
                pack_bf16(acc[4 * j + 2], acc[4 * j + 3]), pack_bf16(acc[4 * j + 4], acc[4 * j + 5]),
                pack_bf16(acc[4 * j + 6], acc[4 * j + 7]));
        if (wg == LEADWG) {
          fence_async_smem();
          __syncwarp();
          if (elect_one()) {
            tma_store_3d(&tmOb, wb + b, DM + cb2 * 128 + h * 64, rb2 >> 3, orow);
            bulk_commit();
          }
        } else {
          __syncwarp();
          uint4 v[4];
#pragma unroll
          for (int i = 0; i < 4; i++) v[i] = lds128(wld + b + i * 512 + (wlx ^ ((i & 1) << 6)));
#pragma unroll
          for (int i = 0; i < 4; i++)
            asm volatile("st.global.v4.u32 [%0], {%1,%2,%3,%4};\n" ::"l"(og + i * 8 * (2 * DM / 8) + h * 8), "r"(v[i].x),
                         "r"(v[i].y), "r"(v[i].z), "r"(v[i].w) : "memory");
        }
      }
      PROF(12 + wg);
      bulk_wait0();
    } else {
      asm volatile("barrier.cluster.arrive.relaxed.aligned;\n" ::: "memory");
    }
    asm volatile("barrier.cluster.wait.aligned;\n" ::: "memory");
  }
}

typedef CUresult (*EncodeFn)(CUtensorMap*, CUtensorMapDataType, cuuint32_t, void*, const cuuint64_t*, const cuuint64_t*,
                             const cuuint32_t*, const cuuint32_t*, CUtensorMapInterleave, CUtensorMapSwizzle,
                             CUtensorMapL2promotion, CUtensorMapFloatOOBfill);

void make_map(EncodeFn enc, CUtensorMap* tm, const void* base, int rank, const cuuint64_t* dims, const cuuint64_t* strides,
              const cuuint32_t* box, CUtensorMapSwizzle swz) {
  cuuint32_t es[5] = {1, 1, 1, 1, 1};
  enc(tm, CU_TENSOR_MAP_DATA_TYPE_BFLOAT16, rank, const_cast<void*>(base), dims, strides, box, es,
      CU_TENSOR_MAP_INTERLEAVE_NONE, swz, CU_TENSOR_MAP_L2_PROMOTION_L2_256B, CU_TENSOR_MAP_FLOAT_OOB_FILL_NONE);
}

}

extern "C" void kernel_launch(void* const* d_in, const int* in_sizes, int n_in, void* d_out, int out_size) {
  static EncodeFn enc = nullptr;
  static bool coresident = true;
  if (!enc) {
    void* fn = nullptr;
    cudaDriverEntryPointQueryResult qr;
    cudaGetDriverEntryPoint("cuTensorMapEncodeTiled", &fn, cudaEnableDefault, &qr);
    enc = (EncodeFn)fn;
    cudaFuncSetAttribute(fused_kernel<0>, cudaFuncAttributeMaxDynamicSharedMemorySize, SMEM_BYTES);
    cudaFuncSetAttribute(fused_kernel<1>, cudaFuncAttributeMaxDynamicSharedMemorySize, SMEM_BYTES);
    cudaFuncSetAttribute(fused_kernel<2>, cudaFuncAttributeMaxDynamicSharedMemorySize, SMEM_BYTES);
    cudaLaunchConfig_t cfg = {};
    cfg.gridDim = dim3(NCTA);
    cfg.blockDim = dim3(NTHREADS);
    cfg.dynamicSmemBytes = SMEM_BYTES;
    cudaLaunchAttribute at;
    at.id = cudaLaunchAttributeClusterDimension;
    at.val.clusterDim.x = 2;
    at.val.clusterDim.y = 1;
    at.val.clusterDim.z = 1;
    cfg.attrs = &at;
    cfg.numAttrs = 1;
    int nclusters = 0;
    if (cudaOccupancyMaxActiveClusters(&nclusters, fused_kernel<0>, &cfg) == cudaSuccess) coresident = nclusters >= NCTA / 2;
    (void)cudaGetLastError();
  }
  CUtensorMap tmX, tmW, tmWo, tmWp, tmQ, tmOb, tmXh, tmWh;
  {
    cuuint64_t dims[3] = {1024, 2, 1024};
    cuuint64_t str[2] = {2048, 4096};
    cuuint32_t box[3] = {64, 1, 128};
    make_map(enc, &tmX, d_in[6], 3, dims, str, box, CU_TENSOR_MAP_SWIZZLE_128B);
  }
  {
    cuuint64_t dims[3] = {1024, 1024, 3};
    cuuint64_t str[2] = {6144, 2048};
    cuuint32_t box[3] = {64, 32, 3};
    make_map(enc, &tmW, d_in[7], 3, dims, str, box, CU_TENSOR_MAP_SWIZZLE_128B);
  }
  {
    cuuint64_t dims[3] = {64, 1024, 16};
    cuuint64_t str[2] = {2048, 128};
    cuuint32_t box[3] = {64, 64, 2};
    cuuint32_t piece[3] = {64, 32, 1};
    make_map(enc, &tmWo, d_in[8], 3, dims, str, box, CU_TENSOR_MAP_SWIZZLE_128B);
    make_map(enc, &tmWp, d_in[8], 3, dims, str, piece, CU_TENSOR_MAP_SWIZZLE_128B);
  }
  {
    cuuint64_t dims[5] = {1024, 2, 2, 4, 128};
    cuuint64_t str[4] = {2048, 8 * 2048, 2 * 2048, 16 * 2048};
    cuuint32_t box[5] = {16, 2, 2, 4, 32};
    make_map(enc, &tmQ, d_in[0], 5, dims, str, box, CU_TENSOR_MAP_SWIZZLE_NONE);
  }
  {
    cuuint64_t dims[3] = {2048, 2, 1024};
    cuuint64_t str[2] = {4096, 8192};
    cuuint32_t box[3] = {64, 1, 16};
    make_map(enc, &tmOb, d_out, 3, dims, str, box, CU_TENSOR_MAP_SWIZZLE_128B);
  }
  {
    cuuint64_t dims[4] = {1024, 256, 2, 4};
    cuuint64_t str[3] = {4096, 2048, 256 * 4096};
    cuuint32_t box[4] = {64, 8, 2, 3};
    make_map(enc, &tmXh, d_in[6], 4, dims, str, box, CU_TENSOR_MAP_SWIZZLE_128B);
  }
  {
    cuuint64_t dims[3] = {64, 1024, 48};
    cuuint64_t str[2] = {6144, 128};
    cuuint32_t box[3] = {64, 64, 4};
    make_map(enc, &tmWh, d_in[7], 3, dims, str, box, CU_TENSOR_MAP_SWIZZLE_128B);
  }
  Params p;
  p.q = (const __nv_bfloat16*)d_in[0];
  p.k = (const __nv_bfloat16*)d_in[1];
  p.v = (const __nv_bfloat16*)d_in[2];
  p.shift_k = (const __nv_bfloat16*)d_in[3];
  p.ssm_k = (const __nv_bfloat16*)d_in[4];
  p.ssm_D = (const __nv_bfloat16*)d_in[5];
  p.x = (const __nv_bfloat16*)d_in[6];
  p.w = (const __nv_bfloat16*)d_in[7];
  p.wo = (const __nv_bfloat16*)d_in[8];
  p.out = (__nv_bfloat16*)d_out;
  p.zero = 0;
  if (coresident) {
    fused_kernel<0><<<NCTA, NTHREADS, SMEM_BYTES>>>(p, tmX, tmW, tmWo, tmWp, tmQ, tmOb, tmXh, tmWh);
  } else {
    fused_kernel<0><<<4, NTHREADS, SMEM_BYTES>>>(p, tmX, tmW, tmWo, tmWp, tmQ, tmOb, tmXh, tmWh);
    fused_kernel<1><<<NCTA, NTHREADS, SMEM_BYTES>>>(p, tmX, tmW, tmWo, tmWp, tmQ, tmOb, tmXh, tmWh);
    fused_kernel<2><<<NCTA, NTHREADS, SMEM_BYTES>>>(p, tmX, tmW, tmWo, tmWp, tmQ, tmOb, tmXh, tmWh);
  }
}
```

```cpp
#include <cuda_runtime.h>
#include <cuda.h>
#include <cuda_bf16.h>
#include <stdint.h>

namespace {

constexpr int SEQ = 2048;
constexpr int DM = 1024;
constexpr int NCTA = 132;
constexpr int NTHREADS = 384;

constexpr int STG1A = 32768;
constexpr int NS1A = 3;
constexpr int STG1B = 12288;
constexpr int NS1B = 5;
constexpr int OFF_1B = NS1A * STG1A;
constexpr int STG2 = 32768;
constexpr int NS2 = 5;
#define PSTEP 1250
#define FPACE 260
#define FPACE2 230
constexpr int LEADWG = 1;
__device__ __forceinline__ uint32_t g2_a(int s, int hsel) { return (((0x97524 >> (4 * s)) & 15) ^ (s & 5 ? 0 : hsel)) << 14; }
constexpr int OFF_Q0 = 3 << 14, OFF_Q1 = 8 << 14;
constexpr int STGH = 40960;
constexpr int OFF_KH = 1 * STG2;
constexpr int OFF_OP = 2 * STG2;
constexpr int OFF_T32 = 5 * STG2 - 4096;
constexpr int OFF_X = 5 * STG2;
constexpr int XT = 8192;
__device__ __forceinline__ uint32_t g2_b(int s, int rank) {
  return s < 3 ? (s == 2 ? 6 : s) << 14 : OFF_X + (s - 3) * 2 * XT + (rank ^ 1) * 4096;
}
__device__ __forceinline__ uint32_t g2_bk(int s) { return s < 3 ? 4096 : 4 * XT; }
constexpr int OFF_BAR = OFF_X + 8 * XT;
constexpr int OFF_EX = OFF_BAR + 448;
constexpr int OFF_T16 = 230400;
constexpr int SMEM_BYTES = OFF_T16 + 2048;
static_assert(OFF_1B + NS1B * STG1B <= OFF_T32 && OFF_X % 1024 == 0, "layout");
static_assert(NS1B * STGH <= OFF_BAR && OFF_EX + 64 <= OFF_T16 && SMEM_BYTES <= 232448, "smem");

constexpr int BAR_FULLA = 0;
constexpr int BAR_EMPTYA = 3;
constexpr int BAR_FULLB = 6;
constexpr int BAR_EMPTYB = 11;
constexpr int BAR_FULL2 = 16;
constexpr int BAR_EMPTY2 = 21;
constexpr int BAR_EMPTY2B = 44;
constexpr int BAR_X = 26;
constexpr int BAR_LAND = 42;
constexpr int BAR_TAB = 28;
constexpr int BAR_U = 29;
constexpr int BAR_H = 30;
constexpr int BAR_STG = 31;
constexpr int BAR_Y = 32;
constexpr int BAR_XFREE = 38;
constexpr int BAR_HALO = 40;
constexpr int BAR_Q = 41;

constexpr int NB_LEAD = 2;
constexpr int NB_G1END = 3;
constexpr int NB_OREADY = 4;
constexpr int NB_CONV = 5;
constexpr int NB_HELP3 = 11;
constexpr int NB_FIRST = 13;

#define REG_MATH 224
#define REG_HELP 56
constexpr int SPIN_LIMIT = 1 << 20;

__device__ __align__(1024) __nv_bfloat16 g_o[SEQ * DM];
__device__ uint32_t g_flag_o[128];
__device__ uint4 g_halo[128 * 192];
__device__ __align__(128) const uint32_t g_tab[2048] = {
  0x2fd93000,0x2ea72f64,0x2c722da8,0x263e2a1f,0x2ea73000,0xa63e2a1f,0xafd9ada8,0xac72af64,0x2c723000,0xafd9aa1f,0x263eada8,0x2ea72f64,
  0x263e3000,0xac72af64,0x2ea72da8,0xafd9aa1f,0xa63e3000,0x2c72af64,0xaea72da8,0x2fd9aa1f,0xac723000,0x2fd9aa1f,0xa63eada8,0xaea72f64,
  0xaea73000,0x263e2a1f,0x2fd9ada8,0x2c72af64,0xafd93000,0xaea72f64,0xac722da8,0xa63e2a1f,0x263e0000,0x2c722a1f,0x2ea72da8,0x2fd92f64,
  0x2c720000,0x2fd92f64,0x263e2da8,0xaea7aa1f,0x2ea70000,0x263e2f64,0xafd9ada8,0x2c72aa1f,0x2fd90000,0xaea72a1f,0x2c72ada8,0xa63e2f64,
  0x2fd90000,0xaea7aa1f,0x2c722da8,0xa63eaf64,0x2ea70000,0x263eaf64,0xafd92da8,0x2c722a1f,0x2c720000,0x2fd9af64,0x263eada8,0xaea72a1f,
  0x263e0000,0x2c72aa1f,0x2ea7ada8,0x2fd9af64,0xafd93000,0xaea72f64,0xac722da8,0xa63e2a1f,0xaea73000,0x263e2a1f,0x2fd9ada8,0x2c72af64,
  0xac723000,0x2fd9aa1f,0xa63eada8,0xaea72f64,0xa63e3000,0x2c72af64,0xaea72da8,0x2fd9aa1f,0x263e3000,0xac72af64,0x2ea72da8,0xafd9aa1f,
  0x2c723000,0xafd9aa1f,0x263eada8,0x2ea72f64,0x2ea73000,0xa63e2a1f,0xafd9ada8,0xac72af64,0x2fd93000,0x2ea72f64,0x2c722da8,0x263e2a1f,
  0xa63e0000,0xac722a1f,0xaea72da8,0xafd92f64,0xac720000,0xafd92f64,0xa63e2da8,0x2ea7aa1f,0xaea70000,0xa63e2f64,0x2fd9ada8,0xac72aa1f,
  0xafd90000,0x2ea72a1f,0xac72ada8,0x263e2f64,0xafd90000,0x2ea7aa1f,0xac722da8,0x263eaf64,0xaea70000,0xa63eaf64,0x2fd92da8,0xac722a1f,
  0xac720000,0xafd9af64,0xa63eada8,0x2ea72a1f,0xa63e0000,0xac72aa1f,0xaea7ada8,0xafd9af64,0xa63e0000,0xac72aa1f,0xaea7ada8,0xafd9af64,
  0xac720000,0xafd9af64,0xa63eada8,0x2ea72a1f,0xaea70000,0xa63eaf64,0x2fd92da8,0xac722a1f,0xafd90000,0x2ea7aa1f,0xac722da8,0x263eaf64,
  0xafd90000,0x2ea72a1f,0xac72ada8,0x263e2f64,0xaea70000,0xa63e2f64,0x2fd9ada8,0xac72aa1f,0xac720000,0xafd92f64,0xa63e2da8,0x2ea7aa1f,
  0xa63e0000,0xac722a1f,0xaea72da8,0xafd92f64,0x2fd93000,0x2ea72f64,0x2c722da8,0x263e2a1f,0x2ea73000,0xa63e2a1f,0xafd9ada8,0xac72af64,
  0x2c723000,0xafd9aa1f,0x263eada8,0x2ea72f64,0x263e3000,0xac72af64,0x2ea72da8,0xafd9aa1f,0xa63e3000,0x2c72af64,0xaea72da8,0x2fd9aa1f,
  0xac723000,0x2fd9aa1f,0xa63eada8,0xaea72f64,0xaea73000,0x263e2a1f,0x2fd9ada8,0x2c72af64,0xafd93000,0xaea72f64,0xac722da8,0xa63e2a1f,
  0x263e0000,0x2c72aa1f,0x2ea7ada8,0x2fd9af64,0x2c720000,0x2fd9af64,0x263eada8,0xaea72a1f,0x2ea70000,0x263eaf64,0xafd92da8,0x2c722a1f,
  0x2fd90000,0xaea7aa1f,0x2c722da8,0xa63eaf64,0x2fd90000,0xaea72a1f,0x2c72ada8,0xa63e2f64,0x2ea70000,0x263e2f64,0xafd9ada8,0x2c72aa1f,
  0x2c720000,0x2fd92f64,0x263e2da8,0xaea7aa1f,0x263e0000,0x2c722a1f,0x2ea72da8,0x2fd92f64,0xafd93000,0xaea72f64,0xac722da8,0xa63e2a1f,
  0xaea73000,0x263e2a1f,0x2fd9ada8,0x2c72af64,0xac723000,0x2fd9aa1f,0xa63eada8,0xaea72f64,0xa63e3000,0x2c72af64,0xaea72da8,0x2fd9aa1f,
  0x263e3000,0xac72af64,0x2ea72da8,0xafd9aa1f,0x2c723000,0xafd9aa1f,0x263eada8,0x2ea72f64,0x2ea73000,0xa63e2a1f,0xafd9ada8,0xac72af64,
  0x2fd93000,0x2ea72f64,0x2c722da8,0x263e2a1f,0xa63e0000,0xac72aa1f,0xaea7ada8,0xafd9af64,0x2c720000,0x2fd92f64,0x263e2da8,0xaea7aa1f,
  0xaea70000,0xa63eaf64,0x2fd92da8,0xac722a1f,0x2fd90000,0xaea72a1f,0x2c72ada8,0xa63e2f64,0xafd90000,0x2ea72a1f,0xac72ada8,0x263e2f64,
  0x2ea70000,0x263eaf64,0xafd92da8,0x2c722a1f,0xac720000,0xafd92f64,0xa63e2da8,0x2ea7aa1f,0x263e0000,0x2c72aa1f,0x2ea7ada8,0x2fd9af64,
  0x2fd93000,0x2ea72f64,0x2c722da8,0x263e2a1f,0xaea7b000,0x263eaa1f,0x2fd92da8,0x2c722f64,0x2c723000,0xafd9aa1f,0x263eada8,0x2ea72f64,
  0xa63eb000,0x2c722f64,0xaea7ada8,0x2fd92a1f,0xa63e3000,0x2c72af64,0xaea72da8,0x2fd9aa1f,0x2c72b000,0xafd92a1f,0x263e2da8,0x2ea7af64,
  0xaea73000,0x263e2a1f,0x2fd9ada8,0x2c72af64,0x2fd9b000,0x2ea7af64,0x2c72ada8,0x263eaa1f,0x263e0000,0x2c72aa1f,0x2ea7ada8,0x2fd9af64,
  0xac720000,0xafd92f64,0xa63e2da8,0x2ea7aa1f,0x2ea70000,0x263eaf64,0xafd92da8,0x2c722a1f,0xafd90000,0x2ea72a1f,0xac72ada8,0x263e2f64,
  0x2fd90000,0xaea72a1f,0x2c72ada8,0xa63e2f64,0xaea70000,0xa63eaf64,0x2fd92da8,0xac722a1f,0x2c720000,0x2fd92f64,0x263e2da8,0xaea7aa1f,
  0xa63e0000,0xac72aa1f,0xaea7ada8,0xafd9af64,0xafd93000,0xaea72f64,0xac722da8,0xa63e2a1f,0x2ea7b000,0xa63eaa1f,0xafd92da8,0xac722f64,
  0xac723000,0x2fd9aa1f,0xa63eada8,0xaea72f64,0x263eb000,0xac722f64,0x2ea7ada8,0xafd92a1f,0x263e3000,0xac72af64,0x2ea72da8,0xafd9aa1f,
  0xac72b000,0x2fd92a1f,0xa63e2da8,0xaea7af64,0x2ea73000,0xa63e2a1f,0xafd9ada8,0xac72af64,0xafd9b000,0xaea7af64,0xac72ada8,0xa63eaa1f,
  0xafd9b000,0xaea7af64,0xac72ada8,0xa63eaa1f,0x2ea73000,0xa63e2a1f,0xafd9ada8,0xac72af64,0xac72b000,0x2fd92a1f,0xa63e2da8,0xaea7af64,
  0x263e3000,0xac72af64,0x2ea72da8,0xafd9aa1f,0x263eb000,0xac722f64,0x2ea7ada8,0xafd92a1f,0xac723000,0x2fd9aa1f,0xa63eada8,0xaea72f64,
  0x2ea7b000,0xa63eaa1f,0xafd92da8,0xac722f64,0xafd93000,0xaea72f64,0xac722da8,0xa63e2a1f,0xa63e0000,0xac72aa1f,0xaea7ada8,0xafd9af64,
  0x2c720000,0x2fd92f64,0x263e2da8,0xaea7aa1f,0xaea70000,0xa63eaf64,0x2fd92da8,0xac722a1f,0x2fd90000,0xaea72a1f,0x2c72ada8,0xa63e2f64,
  0xafd90000,0x2ea72a1f,0xac72ada8,0x263e2f64,0x2ea70000,0x263eaf64,0xafd92da8,0x2c722a1f,0xac720000,0xafd92f64,0xa63e2da8,0x2ea7aa1f,
  0x263e0000,0x2c72aa1f,0x2ea7ada8,0x2fd9af64,0x2fd9b000,0x2ea7af64,0x2c72ada8,0x263eaa1f,0xaea73000,0x263e2a1f,0x2fd9ada8,0x2c72af64,
  0x2c72b000,0xafd92a1f,0x263e2da8,0x2ea7af64,0xa63e3000,0x2c72af64,0xaea72da8,0x2fd9aa1f,0xa63eb000,0x2c722f64,0xaea7ada8,0x2fd92a1f,
  0x2c723000,0xafd9aa1f,0x263eada8,0x2ea72f64,0xaea7b000,0x263eaa1f,0x2fd92da8,0x2c722f64,0x2fd93000,0x2ea72f64,0x2c722da8,0x263e2a1f,
  0x263e0000,0x2c72aa1f,0x2ea7ada8,0x2fd9af64,0xac720000,0xafd92f64,0xa63e2da8,0x2ea7aa1f,0x2ea70000,0x263eaf64,0xafd92da8,0x2c722a1f,
  0xafd90000,0x2ea72a1f,0xac72ada8,0x263e2f64,0x2fd90000,0xaea72a1f,0x2c72ada8,0xa63e2f64,0xaea70000,0xa63eaf64,0x2fd92da8,0xac722a1f,
  0x2c720000,0x2fd92f64,0x263e2da8,0xaea7aa1f,0xa63e0000,0xac72aa1f,0xaea7ada8,0xafd9af64,0x316c2fbd,0x343e32f7,0x35bc34ff,0x372c3676,
  0x371532c6,0x3a81392e,0x3bef3b71,0x3b7c3bf2,0x397034cf,0x3bfc3b6c,0x38b23b04,0xb40e31e8,0x3ae13631,0x39e73bf5,0xb6e83219,0xbbe8bb13,
  0x3bc23785,0x30be3aa9,0xbbfdb911,0x2a16b9aa,0x3bfe3865,0xb80f37a6,0xb82abc00,0x3bfd376f,0x3b9238fd,0xbb7f2311,0x3805b929,0x31223bde,
  0x3a85398b,0xbb96b742,0x3bff319e,0xbbb82f8b,0xbbe2bbf1,0xbbb7bbcf,0xbb78bb9a,0xbb27bb52,0xbb2cbbd2,0xb8a8ba19,0xb029b5df,0x35a52f59,
  0xb9dfbba1,0x2ba7b5f7,0x3a7a37b2,0x3bbd3bdd,0xb815bb60,0x39662e91,0x3b373bda,0xb0d7377a,0xb3d3bb10,0x3be9386f,0x2a7a3a31,0xbbfeb9a6,
  0x294dbab0,0x3ae53b07,0xbad51fdb,0xab43bb16,0x352fba41,0x35993c00,0xbaebba1d,0x3be531cf,0x38a3b9c5,0xb5173b21,0x2776bbe0,0x34323bf2,
  0x384537dd,0x38ea3899,0x39823937,0x3a0d39c9,0x39463a93,0x3340374e,0xb426a452,0xb979b7c8,0xbb45b924,0xbb32bc00,0xb371b902,0x38d63294,
  0xb08db9a1,0x3b3f379b,0x39583bd7,0xb8252dfb,0x3bea3a2d,0xb3ba3874,0xbb89bb0d,0x36d2b625,0xb6bb387f,0xb8d1bbf5,0x3be73602,0xb546391f,
  0xba00bb01,0x3bff35eb,0xba5c34db,0x3359bab6,0x3ac7b66b,0xb9413933,0x368dbabd,0xb0103bb3,0xbac4baf7,0xba50ba8c,0xb9cdba11,0xb93cb986,
  0x3a04388e,0x3bcb3b1e,0x3bba3c00,0x39d63afe,0x36af3a21,0xb6ffa17f,0xbbc8ba3d,0xba60bbd4,0xbbebb9af,0xb6c6bb0a,0x39f43263,0x3ad83bf7,
  0x30a6b916,0x3bc33aa5,0xb55e3790,0xbb3dbb63,0x3b423a9e,0xba642ec3,0xb0f0bb6a,0x3b8e3a25,0xb94a37bd,0x2884bb6f,0x38db3b9f,0xbbc9b85a,
  0xb840bb54,0x3a093a15,0xbb4cb850,0x3bef3457,0x3a893a4d,0x3af43ac1,0x3b4f3b24,0x3b983b76,0xbb94baba,0xbbe4bbf9,0xba58bb57,0xb699b8f8,
  0x3bfe3b18,0x394f3b5c,0xb109347b,0xbae8b884,0xbbc0bb68,0xa9b1b90c,0x3b8b387a,0x38bc3ba5,0x3ade3ba7,0xb8c1324b,0xb9f0bbf6,0x39eb9648,
  0xb96bbbd6,0x3bbf3487,0xb38939b3,0xb9f8bba3,0x370a3bf3,0xbb47b994,0x3bbc2d65,0xb8ad3889,0xb153bc00,0x37213b9c,0xb97dba90,0x3af138f3,
  0xb89eb8ee,0xb7e8b84a,0xb682b737,0xb50bb5c8,0x35233855,0xb13b2d33,0xb8e0b65f,0xbb4aba45,0xa8e8b764,0x39fc3648,0x3be63bae,0x380a3a9b,
  0xb3eb360e,0xbbfeba35,0xb552baa2,0x3a7334b7,0x381ab4ab,0x3a6f3bd8,0xb95d2e5f,0xb962bc00,0xb9e3327c,0xb402bbac,0x3bc6399d,0xb95434c3,
  0x3b2faf27,0xb6a439bc,0xb41abbf9,0x3a7e3a97,0xbbe3251b,0x3b2ab4f3,0xb9d23894,0x37f3ba49,0x3bce3bb5,0x3bf03be1,0x3bff3bfa,0x3bfb3bff,
  0x2c38b1b6,0x383a34e7,0x3aee39c0,0x3bff3bb2,0xbb81bbf8,0xb53ab999,0x38302ef5,0x3bed3ab3,0xb8cc9cb6,0xbb85bbab,0x2adeb86a,0x3bc5391b,
  0x38c73bf6,0xbadbb232,0xb6ddbba9,0x3b87361a,0x3b833201,0xb0743a39,0xba76bb5e,0x3b352dc9,0xac06bbb0,0x39743b59,0xbbeeb759,0x3aceb2ad,
  0xbbccb5d4,0x3bfb2d00,0xbb7a32de,0x3a54b7d2,0xb30fb44b,0xafefb185,0xa6adacce,0x2c9c25e4,0xbbfcbbdf,0xbacbbb9e,0xb7feb990,0xa81fb463,
  0xb58d2d97,0xbb90b9b8,0xbad1bbf4,0xb05bb85f,0x3a673c00,0xb5763493,0xbbfdbaac,0xb3a2ba29,0x3a6b2e2d,0x38203bd9,0xbb3ab49f,0xb56abb65,
  0xb581bbdc,0x3bec3907,0xb8b7363c,0xb6f4bbf8,0xbbfcb46f,0x39dab654,0xb0423b1b,0xb835bbd3,0xb3283b73,0xac6abbfa,0x35b13bd0,0xb8e5bafb,
  0x38ee3a0d,0xb84aba89,0x37373af4,0xb5c8bb4f,0x35df3a81,0x2f59bbef,0xb88e3b7c,0x3b1eb946,0x2d973ae8,0x39b8bb81,0xbbf4353a,0x385f3830,
  0xb2633b3f,0x3bf7b958,0xb60eb825,0xba353bc0,0xb7853b87,0x3aa9b3d3,0x3911bbe9,0xb9aa2a7a,0xb99d3bbf,0x34c33389,0x3bdcb9f8,0x3907bb83,
  0xbb013be5,0xb5eb394a,0x34db2884,0x3ab6b8db,0xbbd03bfb,0xbafb3b7a,0xb98b3a54,0xb74238a3,0x3a4db93c,0xbac1389e,0x3b24b7e8,0xbb763682,
  0x3b71b8a8,0xbbf23029,0x3a9335a5,0xb74eba04,0x3bf8b80a,0xb999b58d,0xaef53b90,0x3ab3bad1,0x3bd7b6c6,0xadfbb9f4,0xbb683ad8,0x390c33eb,
  0x3b10b56a,0x386fbbc2,0xba3130be,0xb9a63bfd,0x39b3b402,0x3ba3bbc6,0x3201b954,0xba393581,0x37bdb122,0x3b6fba00,0x3b9fbbff,0x385aba5c,
  0x32deac6a,0x37d2b5b1,0x39c5b8e5,0x3b21ba85,0x344b3b98,0xb185bbce,0x2cce3bf0,0x25e4bbff,0xbc003340,0x3afe3426,0xb855b979,0x2d333b94,
  0x34cfbbed,0xbb6c39df,0x3b042ba7,0xb1e8ba7a,0x3aa2a9b1,0x34b7bb8b,0xbc0038bc,0x349338cc,0xba2d3bfe,0x387430a6,0x3b0dbbc3,0xb625b55e,
  0xb63cb074,0xbbf83a76,0xb8653b35,0x37a6294d,0x3bf3bbc9,0x3994bb2f,0x2d65b6a4,0xb889341a,0xb19e3517,0x2f8b2776,0x366bb432,0x3933b840,
  0x3bb5b50b,0xbbe1330f,0x3bfaafef,0xbbff26ad,0xa4523bcb,0x37c8bbba,0xbaba39d6,0x3bf9b523,0xbba1305b,0x35f73970,0x37b2bbfc,0xbbdd38b2,
  0x387abbfe,0xbba53552,0x9cb63a73,0x3babba67,0x39162a16,0x3aa5bbea,0xb790b3ba,0xbb633b89,0xbb5e3bec,0xadc938b7,0x3ab0b6f4,0x3b07bbfe,
  0xaf27b359,0xb9bc370a,0xbbf93b47,0xba973bbc,0x3be0bb96,0x3bf2bbff,0x3b54bbb8,0x3a15bac7,0xafbd3bfb,0x32f7bbe2,0xb4ff3bb7,0x3676bb78,
  0x365fbbe4,0xba453a58,0x3bdfb699,0xbb9eac38,0xb9243bbd,0x3c00b6af,0xb902b6ff,0xb2943bc8,0x3aacbb85,0xba29aade,0xb6313bc5,0x3bf5b815,
  0xbba73b3d,0x324b381a,0x3bf6ba6f,0x9648b95d,0x3c00bae5,0x376fbad5,0xb87f2b43,0xbbf53b42,0xbbb03a7e,0xbb593bfc,0xb75939da,0x32ad3042,
  0x3abdba09,0x3bb3bb4c,0x3c00bbef,0x3b9cbbe3,0x3bf12c9c,0xbbcfb16c,0x3b9a343e,0xbb52b5bc,0xbb57b13b,0x38f838e0,0xb1b6bb4a,0xb4e73bfc,
  0x3a21340e,0x217fbb45,0xba3d3b32,0x3bd4b371,0xb86ab576,0xb91b3bfd,0x3b60b3a2,0x2e91bae1,0x34ab36d2,0x3bd8bade,0xae5fb8c1,0xbc0039f0,
  0x9fdbb80f,0xbb16382a,0xba9e3bfd,0x2ec336bb,0xb46f38ad,0x3654ac06,0x3b1bb974,0x3bd3bbee,0x3850b941,0x3457b68d,0xa51bb010,0xb4f33153,
  0xb7dd3b27,0x3899bac4,0xb9373a50,0x39c9b9cd,0x3990383a,0xb463baee,0xb2c63bff,0x392ebb2c,0x3b18ba60,0xbb5c28e8,0x347b39fc,0x3884bbe6,
  0xb219b966,0xbb133b37,0x39a130d7,0x379bbbeb,0xbbf63962,0xb2323a6b,0x3ba9b820,0x361abb3a,0xb6023a64,0x391fb0f0,0x3bd6bb8e,0x3487b9e3,
  0x3a41b835,0x3c00bb92,0x3a1dbb7f,0x31cfb805,0x3a90bb2a,0x38f3b9d2,0x35d4b7f3,0x2d00b328,0x3af7372c,0xba8cb845,0x3a1138ea,0xb986b982,
  0x39c0bacb,0xbbb237fe,0x3bd2a81f,0xba19b715,0xb764b8d6,0xb6483bfe,0x3baeb94f,0xba9bb109,0xbbda39e7,0x377a36e8,0x39afbbe8,0xbb0a308d,
  0xae2d39eb,0x3bd9b8c7,0x349fbadb,0xbb6536dd,0x3b6ab8d1,0x3a25bbe7,0xb27cb546,0xbbac396b,0x38fdbace,0xa311b52f,0xb9293599,0xbbde3aeb,
  0xb8943721,0xba49397d,0xbb733af1,0xbbfa3bcc,0xbbfb3bff,0xbbe23bf1,0xbbb73bcf,0xbb783b9a,0xbb7c3bf2,0xb9463a93,0xb340374e,0x3426a452,
  0xba603bd4,0xa8e83764,0x39fcb648,0x3be6bbae,0xb8bc3ba5,0x38cc9cb6,0x3b85bbab,0xaadeb86a,0xb56a3b65,0x3bc2b785,0x30bebaa9,0xbbfd3911,
  0xab433b16,0x3b42ba9e,0xba64aec3,0xb0f03b6a,0x33593ab6,0x370abbf3,0xbb473994,0x3bbcad65,0x37f33a49,0xb328bb73,0xac6a3bfa,0x35b1bbd0,
  0xac9c25e4,0xb16c2fbd,0xb43e32f7,0xb5bc34ff,0xb5a52f59,0xba04388e,0xbbcb3b1e,0xbbba3c00,0xb8d63294,0xbbfe3b18,0xb94f3b5c,0x3109347b,
  0xba7334b7,0xba673c00,0x35763493,0x3bfdbaac,0xbb87361a,0xb3d33b10,0x3be9b86f,0x2a7aba31,0xbbfd376f,0x36bb387f,0x38d1bbf5,0xbbe73602,
  0xbbc9385a,0x3b2f2f27,0xb6a4b9bc,0xb41a3bf9,0xbaf138f3,0x3bccb5d4,0xbbfb2d00,0x3b7a32de,0xbb273b52,0xbac43af7,0xba503a8c,0xb9cd3a11,
  0x3979b7c8,0x3b94baba,0x3be4bbf9,0x3a58bb57,0x380aba9b,0xb58dad97,0xbb9039b8,0xbad13bf4,0xbbc5391b,0xb8153b60,0x3966ae91,0x3b37bbda,
  0x2a1639aa,0x3beaba2d,0xb3bab874,0xbb893b0d,0x3b8eba25,0xb9e3b27c,0xb4023bac,0x3bc6b99d,0xb8adb889,0xac063bb0,0x3974bb59,0xbbee3759,
  0xb8e53afb,0x3a85b98b,0xbb963742,0x3bffb19e,0xb72c3676,0xb84537dd,0xb8ea3899,0xb9823937,0xb9d63afe,0xb5233855,0x313b2d33,0x38e0b65f,
  0x3ae8b884,0x3b81bbf8,0x353ab999,0xb8302ef5,0x33a2ba29,0xbae13631,0xb9e73bf5,0x36e83219,0xbbfe39a6,0x30a63916,0x3bc3baa5,0xb55eb790,
  0x3546391f,0x396bbbd6,0xbbbf3487,0x338939b3,0x3a7eba97,0xbbfc346f,0x39da3654,0xb042bb1b,0xba54b7d2,0x38a339c5,0xb517bb21,0x27763be0,
  0xb93c3986,0xb89e38ee,0xb7e8384a,0xb6823737,0x3699b8f8,0xac38b1b6,0xb83a34e7,0xbaee39c0,0xb05b385f,0x3970b4cf,0x3bfcbb6c,0x38b2bb04,
  0xb0d7b77a,0xbbeb39af,0xb6c63b0a,0x39f4b263,0x36d23625,0x3adebba7,0xb8c1b24b,0xb9f03bf6,0xb954b4c3,0xb5813bdc,0x3becb907,0xb8b7b63c,
  0x3ace32ad,0xb52fba41,0xb5993c00,0x3aebba1d,0xbbb8af8b,0x3ac7366b,0xb941b933,0x368d3abd,0xba0d39c9,0xba893a4d,0xbaf43ac1,0xbb4f3b24,
  0x3b4aba45,0x3bfcbbdf,0x3acbbb9e,0x37feb990,0xbbed3ab3,0xb9df3ba1,0x2ba735f7,0x3a7ab7b2,0x3be8bb13,0x308db9a1,0xbb3f379b,0xb9583bd7,
  0xbb3d3b63,0x381a34ab,0x3a6fbbd8,0xb95dae5f,0x39f8bba3,0xbb833201,0x30743a39,0x3a76bb5e,0xb8353bd3,0x3b92b8fd,0xbb7fa311,0x38053929,
  0x3432bbf2,0xb8403b54,0x3a09ba15,0xbb4c3850,0xb50b35c8,0xb30f344b,0xafef3185,0xa6ad2cce,0xbbff3bb2,0xbb2c3bd2,0xb8a83a19,0xb02935df,
  0xb40eb1e8,0xbb453924,0xbb323c00,0xb3713902,0x3ad8bbf7,0xb3ebb60e,0xbbfe3a35,0xb5523aa2,0x39eb1648,0x38c7bbf6,0xbadb3232,0xb6dd3ba9,
  0xb6f43bf8,0x3bfeb865,0xb80fb7a6,0xb82a3c00,0xbbe531cf,0x394a37bd,0xa884bb6f,0xb8db3b9f,0xb010bbb3,0xb1533c00,0x3721bb9c,0xb97d3a90,
  0xbb983b76,0xbbce3bb5,0xbbf03be1,0xbbff3bfa,0x281fb463,0xb71532c6,0xba81392e,0xbbef3b71,0x3bbdbbdd,0x36afba21,0xb6ff217f,0xbbc83a3d,
  0x38252dfb,0x3bc0bb68,0x29b1b90c,0xbb8b387a,0xb9623c00,0x3a6bae2d,0x3820bbd9,0xbb3a349f,0xbb352dc9,0x294d3ab0,0x3ae5bb07,0xbad59fdb,
  0x3122bbde,0xba003b01,0x3bffb5eb,0xba5cb4db,0x3befb457,0xbbe3a51b,0x3b2a34f3,0xb9d2b894,0x39c939cd,0xba4db93c,0x3ac1389e,0xbb24b7e8,
  0x3b1e3946,0xbc00b340,0x3afeb426,0xb8553979,0x3bdd38b2,0xba21340e,0xa17fbb45,0x3a3d3b32,0x3bf53815,0xb2193966,0xbb13bb37,0x39a1b0d7,
  0x3b6536dd,0x37853b87,0xbaa9b3d3,0xb911bbe9,0x3a393581,0x3b5e3bec,0x2dc938b7,0xbab0b6f4,0x3889341a,0x3bb03a7e,0x3b593bfc,0x375939da,
  0x34f33153,0x38943721,0x3a49397d,0x3b733af1,0xb9863982,0x38eeba0d,0xb84a3a89,0x3737baf4,0xb74e3a04,0xa452bbcb,0x37c83bba,0xbabab9d6,
  0xb1e83a7a,0xb924bbbd,0x3c0036af,0xb90236ff,0x2e913ae1,0xbbdab9e7,0x377ab6e8,0x39af3be8,0x361a3b3a,0xbb10b56a,0xb86fbbc2,0x3a3130be,
  0x39073b83,0xb63c3074,0xbbf8ba76,0xb865bb35,0x3a973bbc,0x346f38ad,0xb654ac06,0xbb1bb974,0x3b9c3be3,0x3a903b2a,0x38f339d2,0x35d437f3,
  0x3b763682,0xbbb5b50b,0x3be1330f,0xbbfaafef,0x2d33bb94,0x365f3be4,0xba45ba58,0x3bdf3699,0xbbd4b371,0x3764b8d6,0x36483bfe,0xbbaeb94f,
  0x379b3beb,0xbbd7b6c6,0x2dfbb9f4,0x3b683ad8,0x39aa2a7a,0x3a2d3bfe,0xb87430a6,0xbb0dbbc3,0xbb07bbfe,0x1fdbb80f,0x3b16382a,0x3a9e3bfd,
  0xb2ad3042,0xba41b835,0xbc00bb92,0xba1dbb7f,0x3bfa3bcc,0x3bd03bfb,0x3afb3b7a,0x398b3a54,0xb5c83b4f,0x344bbb98,0xb1853bce,0x2ccebbf0,
  0x3bf93523,0xbb57313b,0x38f8b8e0,0xb1b63b4a,0xb294bbc8,0x3b183a60,0xbb5ca8e8,0x347bb9fc,0xbb0ab08d,0xb263bb3f,0x3bf73958,0xb60e3825,
  0x39a63bfd,0xb9162a16,0xbaa5bbea,0x3790b3ba,0x37a6a94d,0x3c003ae5,0x376f3ad5,0xb87fab43,0xbbd3bbee,0xb8fdbace,0x2311b52f,0x39293599,
  0x2d003328,0xb2deac6a,0xb7d2b5b1,0xb9c5b8e5,0x3bff26ad,0xbbf12c9c,0x3bcfb16c,0xbb9a343e,0xbb9e2c38,0x3990b83a,0xb4633aee,0xb2c6bbff,
  0x3a9bb109,0xad973ae8,0xb9b8bb81,0x3bf4353a,0xb90c33eb,0xb87abbfe,0x3ba53552,0x1cb63a73,0x3625b55e,0x3ba73b3d,0xb24b381a,0xbbf6ba6f,
  0xaec336bb,0xbb6ab8d1,0xba25bbe7,0x327cb546,0xb1cfb805,0x37bd3122,0x3b6f3a00,0x3b9f3bff,0x374238a3,0x319e3517,0xaf8b2776,0xb66bb432,
  0x25e43bff,0xafbdbbfb,0x32f73be2,0xb4ffbbb7,0xb4e7bbfc,0x39c03acb,0xbbb2b7fe,0x3bd2281f,0x38843be6,0xbbf8b80a,0x3999b58d,0x2ef53b90,
  0xba35bbc0,0x3aa229b1,0x34b73b8b,0xbc00b8bc,0x3b633b89,0xb4ab36d2,0xbbd8bade,0x2e5fb8c1,0xbbf5bb42,0xb602ba64,0x391f30f0,0x3bd63b8e,
  0x3bde3aeb,0x3b013be5,0x35eb394a,0xb4db2884,0xbb21ba85,0xbbe0bb96,0xbbf2bbff,0xbb54bbb8,0x3b52b5bc,0xbaf7372c,0x3a8cb845,0xba1138ea,
  0x392e3b2c,0xbb71b8a8,0x3bf23029,0xba9335a5,0xb85f3830,0xb4cfbbed,0x3b6c39df,0xbb042ba7,0xbbabba67,0x386ab576,0x391b3bfd,0xbb60b3a2,
  0x1648b95d,0x3bf63962,0x32323a6b,0xbba9b820,0x3bac396b,0x399d3bbf,0xb4c33389,0xbbdcb9f8,0x385a3a5c,0xaf273359,0xb9bcb70a,0xbbf9bb47,
  0xb933b840,0xbabdba09,0xbbb3bb4c,0xbc00bbef,0x36763b78,0xb7ddbb27,0x38993ac4,0xb937ba50,0xba193715,0x35dfba81,0x2f593bef,0xb88ebb7c,
  0xbab3bad1,0x3ba1305b,0xb5f73970,0xb7b2bbfc,0x3493b8cc,0x3aac3b85,0xba292ade,0xb631bbc5,0x3c0039f0,0x2e2d39eb,0xbbd9b8c7,0xb49fbadb,
  0x348739e3,0xb9b3b402,0xbba3bbc6,0xb201b954,0xbab6b8db,0xbbf3bbc9,0xb994bb2f,0xad65b6a4,0xba15bac7,0xb850b941,0xb457b68d,0x251bb010,
  0xb9cfbb16,0x30ac2a31,0x3b9c3bf1,0xb493ae2d,0xb76fb8b4,0x35a133e3,0x3a1d3afe,0xb902b76f,0xb3e3b5a1,0x38b4376f,0x376f3902,0xbafeba1d,
  0xaa31b0ac,0x3b1639cf,0x2e2d3493,0xbbf1bb9c,0xb956ba74,0x305f29cc,0x3b633bd2,0xb44badc9,0xb6e7b859,0x353f335e,0x39d23ab6,0xb8bcb6ff,
  0xb35eb53f,0x385936e7,0x36ff38bc,0xbab6b9d2,0xa9ccb05f,0x3a743956,0x2dc9344b,0xbbd2bb63,0xb8e3b9de,0x30122967,0x3b1e3ba1,0xb402ad65,
  0xb662b801,0x34de32da,0x39823a67,0xb874b68d,0xb2dab4de,0x38013662,0x368d3874,0xba67b982,0xa967b012,0x39de38e3,0x2d653402,0xbba1bb1e,
  0xb876b952,0x2f8c2902,0x3ace3b60,0xb371ad00,0xb5e1b758,0x347e3257,0x392e3a11,0xb82ab61a,0xb257b47e,0x375835e1,0x361a382a,0xba11b92e,
  0xa902af8c,0x39523876,0x2d003371,0xbb60bace,0xb80db8ce,0x2ef3289e,0x3a733b10,0xb2deac9c,0xb562b6b3,0x342031d5,0x38d639b3,0xb7bdb5a5,
  0xb1d5b420,0x36b33562,0x35a537bd,0xb9b3b8d6,0xa89eaef3,0x38ce380d,0x2c9c32de,0xbb10ba73,0xb750b851,0x2e5a2839,0x3a0d3ab0,0xb24bac38,
  0xb4e5b613,0x33863153,0x387a394f,0xb721b52f,0xb153b386,0x361334e5,0x352f3721,0xb94fb87a,0xa839ae5a,0x38513750,0x2c38324b,0xbab0ba0d,
  0xb68eb7b4,0x2dc227a9,0x399d3a41,0xb1b6aba7,0xb46ab577,0x32cd30d2,0x381a38e5,0xb682b4b7,0xb0d2b2cd,0x3577346a,0x34b73682,0xb8e5b81a,
  0xa7a9adc2,0x37b4368e,0x2ba731b6,0xba41b99d,0xb5d2b6d1,0x2d2a26e0,0x392439c5,0xb122aade,0xb3e3b4de,0x32163052,0x376f3874,0xb5dfb43e,
  0xb052b216,0x34de33e3,0x343e35df,0xb874b76f,0xa6e0ad2a,0x36d135d2,0x2ade3122,0xb9c5b924,0xb51cb5f6,0x2c932617,0x38a3393c,0xb08daa16,
  0xb2f4b448,0x31602fa5,0x36a437fe,0xb53ab389,0xafa5b160,0x344832f4,0x3389353a,0xb7feb6a4,0xa617ac93,0x35f6351c,0x2a16308d,0xb93cb8a3,
  0xb46ab523,0x2bf6254d,0x381a38a8,0xafefa94d,0xb209b36b,0x30ac2ea7,0x35d4370a,0xb493b294,0xaea7b0ac,0x336b3209,0x32943493,0xb70ab5d4,
  0xa54dabf6,0x3523346a,0x294d2fef,0xb8a8b81a,0xb378b456,0x2ac82484,0x3715380a,0xaec3a884,0xb120b24a,0x2ff22da9,0x34ff360e,0xb3d3b19e,
  0xada9aff2,0x324a3120,0x319e33d3,0xb60eb4ff,0xa484aac8,0x34563378,0x28842ec3,0xb80ab715,0xb223b31c,0x29992376,0x35eb36c6,0xad97a776,
  0xb039b12d,0x2e8d2cac,0x3426350b,0xb27cb0a6,0xacacae8d,0x312d3039,0x30a6327c,0xb50bb426,0xa376a999,0x331c3223,0x27762d97,0xb6c6b5eb,
  0xb0d2b194,0x286b21e4,0x34b7356a,0xac6aa5e4,0xaea7b012,0x2d2a2b5f,0x32943402,0xb122af59,0xab5fad2a,0x30122ea7,0x2f593122,0xb402b294,
  0xa1e4a86b,0x319430d2,0x25e42c6a,0xb56ab4b7,0xaf0cb012,0x267b2052,0x32f73402,0xaa7aa452,0xacdeadf5,0x2b912967,0x30d731e8,0xaf8bad65,
  0xa967ab91,0x2df52cde,0x2d652f8b,0xb1e8b0d7,0xa052a67b,0x30122f0c,0x24522a7a,0xb402b2f7,0xac79ad2a,0x24201d7f,0x30743122,0xa81fa17f,
  0xaa31ab91,0x28d026e0,0x2e2d2f8b,0xacceaade,0xa6e0a8d0,0x2b912a31,0x2ade2cce,0xaf8bae2d,0x9d7fa420,0x2d2a2c79,0x217f281f,0xb122b074,
  0xa7a9a86b,0x1f1218b6,0x2ba72c6a,0xa3119cb6,0xa54da67b,0x242021e4,0x294d2a7a,0xa81fa5e4,0xa1e4a420,0x267b254d,0x25e4281f,0xaa7aa94d,
  0x98b69f12,0x286b27a9,0x1cb62311,0xac6aaba7,0x211b21e4,0x98b69248,0xa51ba5e4,0x1cb61648,0x1f122052,0x9d7f9bdb,0xa311a452,0x217f1fdb,
  0x1bdb1d7f,0xa0529f12,0x9fdba17f,0x24522311,0x124818b6,0xa1e4a11b,0x96489cb6,0x25e4251b,0x2a632b5f,0xa1e49bdb,0xae5faf59,0x25e41fdb,
  0x286b2967,0xa6e0a4e9,0xac6aad65,0x2ade28e8,0x24e926e0,0xa967a86b,0xa8e8aade,0x2d652c6a,0x1bdb21e4,0xab5faa63,0x9fdba5e4,0x2f592e5f,
  0x2dc22ea7,0xa54d9f12,0xb1b6b294,0x294d2311,0x2bf62cde,0xaa31a86b,0xafefb0d7,0x2e2d2c6a,0x286b2a31,0xacdeabf6,0xac6aae2d,0x30d72fef,
  0x1f12254d,0xaea7adc2,0xa311a94d,0x329431b6,0x302c30d2,0xa7a9a11b,0xb41ab4b7,0x2ba7251b,0x2dc22f0c,0xac79aa63,0xb1b6b2f7,0x30742e5f,
  0x2a632c79,0xaf0cadc2,0xae5fb074,0x32f731b6,0x211b27a9,0xb0d2b02c,0xa51baba7,0x34b7341a,0x317a3257,0xa902a2ad,0xb552b61a,0x2d0026ad,
  0x2f8c309f,0xaddcac2e,0xb371b487,0x31cf3029,0x2c2e2ddc,0xb09faf8c,0xb029b1cf,0x34873371,0x22ad2902,0xb257b17a,0xa6adad00,0x361a3552,
  0x32cd33e3,0xaa31a420,0xb682b76f,0x2e2d281f,0x30ac31bb,0xaf3fad2a,0xb493b58d,0x33283122,0x2d2a2f3f,0xb1bbb0ac,0xb122b328,0x358d3493,
  0x24202a31,0xb3e3b2cd,0xa81fae2d,0x376f3682,0x341334bc,0xab5fa4e9,0xb7a6b85a,0x2f5928e8,0x319432da,0xb052ae28,0xb56ab68d,0x343e3219,
  0x2e283052,0xb2dab194,0xb219b43e,0x368d356a,0x24e92b5f,0xb4bcb413,0xa8e8af59,0x385a37a6,0x34c3358c,0xac47a5b2,0xb85fb8f3,0x304229b1,
  0x327e33fd,0xb106af26,0xb63cb785,0x34e7330f,0x2f263106,0xb3fdb27e,0xb30fb4e7,0x3785363c,0x25b22c47,0xb58cb4c3,0xa9b1b042,0x38f3385f,
  0x35773662,0xacdea67b,0xb8e5b982,0x30d72a7a,0x336b3493,0xb1bbb012,0xb70ab83a,0x358d3402,0x301231bb,0xb493b36b,0xb402b58d,0x383a370a,
  0x267b2cde,0xb662b577,0xaa7ab0d7,0x398238e5,0x36303741,0xad76a744,0xb962ba04,0x316c2b43,0x342e352a,0xb271b092,0xb7d2b8ad,0x3631347b,
  0x30923271,0xb52ab42e,0xb47bb631,0x38ad37d2,0x27442d76,0xb741b630,0xab43b16c,0x3a043962,0x36ee3815,0xae0ea807,0xb9d6ba7a,0x32012c06,
  0x34a735c4,0xb329b113,0xb84ab91b,0x36d234f3,0x31133329,0xb5c4b4a7,0xb4f3b6d2,0x391b384a,0x28072e0e,0xb815b6ee,0xac06b201,0x3a7a39d6,
  0x37b4388e,0xaea7a86b,0xba41bae1,0x32942c6a,0x35233662,0xb3e3b194,0xb8a8b982,0x376f356a,0x319433e3,0xb662b523,0xb56ab76f,0x398238a8,
  0x286b2ea7,0xb88eb7b4,0xac6ab294,0x3ae13a41,0x3841390f,0xaf3fa8d0,0xbaa2bb3a,0x33282cce,0x35a13705,0xb44fb216,0xb902b9e3,0x380535df,
  0x3216344f,0xb705b5a1,0xb5dfb805,0x39e33902,0x28d02f3f,0xb90fb841,0xacceb328,0x3b3a3aa2,0x38ac3997,0xafd8a935,0xbaf7bb83,0x33ba2d33,
  0x362137ac,0xb4aeb298,0xb958ba3d,0x38503654,0x329834ae,0xb7acb621,0xb654b850,0x3a3d3958,0x29352fd8,0xb997b8ac,0xad33b3ba,0x3b833af7,
  0x391c3a28,0xb039a999,0xbb42bbbc,0x34262d97,0x36a4382d,0xb50eb31c,0xb9aaba90,0x389936c6,0x331c350e,0xb82db6a4,0xb6c6b899,0x3a9039aa,
  0x29993039,0xba28b91c,0xad97b426,0x3bbc3b42,0x39923ac3,0xb085a9fe,0xbb81bbe3,0x346f2dfb,0x372a3886,0xb570b3a0,0xb9f8badb,0x38e03737,
  0x33a03570,0xb886b72a,0xb737b8e0,0x3adb39f8,0x29fe3085,0xbac3b992,0xadfbb46f,0x3be33b81,
};

#define PROF(slot) do {} while (0)
#define PROF_DUMP() do {} while (0)
#define PROFA(slot, dep) do {} while (0)
#define PROF3(slot) do {} while (0)
#define PROF2(slot) do {} while (0)

__device__ __forceinline__ uint32_t smem_u32(const void* p) { return (uint32_t)__cvta_generic_to_shared(p); }

__device__ __forceinline__ void mbar_init(uint32_t a, uint32_t c) {
  asm volatile("mbarrier.init.shared::cta.b64 [%0], %1;\n" ::"r"(a), "r"(c) : "memory");
}
__device__ __forceinline__ void mbar_expect_tx(uint32_t a, uint32_t bytes) {
  asm volatile("mbarrier.arrive.expect_tx.shared::cta.b64 _, [%0], %1;\n" ::"r"(a), "r"(bytes) : "memory");
}
__device__ __forceinline__ void mbar_arrive_cluster(uint32_t cluster_addr) {
  asm volatile("mbarrier.arrive.shared::cluster.b64 _, [%0];\n" ::"r"(cluster_addr) : "memory");
}
__device__ __forceinline__ void mbar_arrive_cluster_n(uint32_t cluster_addr, uint32_t n) {
  asm volatile("mbarrier.arrive.shared::cluster.b64 _, [%0], %1;\n" ::"r"(cluster_addr), "r"(n) : "memory");
}
__device__ __forceinline__ bool mbar_try(uint32_t a, uint32_t parity) {
  uint32_t ok;
  asm volatile("{\n.reg .pred p;\nmbarrier.try_wait.parity.shared::cta.b64 p, [%1], %2;\nselp.u32 %0, 1, 0, p;\n}\n"
               : "=r"(ok) : "r"(a), "r"(parity) : "memory");
  return ok;
}
__device__ __forceinline__ void mbar_wait(uint32_t a, uint32_t parity) {
  if (mbar_try(a, parity)) return;
#pragma unroll 1
  for (int n = 0; n < SPIN_LIMIT; n++)
    if (mbar_try(a, parity)) break;
}
__device__ __forceinline__ bool elect_one() {
  uint32_t p;
  asm volatile("{\n.reg .pred P;\nelect.sync _|P, 0xffffffff;\nselp.u32 %0, 1, 0, P;\n}\n" : "=r"(p));
  return p;
}
__device__ __forceinline__ uint32_t mapa(uint32_t a, uint32_t rank) {
  uint32_t r;
  asm volatile("mapa.shared::cluster.u32 %0, %1, %2;\n" : "=r"(r) : "r"(a), "r"(rank));
  return r;
}
__device__ __forceinline__ void nb_sync(int id, int n) { asm volatile("bar.sync %0, %1;\n" ::"r"(id), "r"(n) : "memory"); }
__device__ __forceinline__ void nb_arrive(int id, int n) { asm volatile("bar.arrive %0, %1;\n" ::"r"(id), "r"(n) : "memory"); }
__device__ __forceinline__ void cluster_sync_all() {
  asm volatile("barrier.cluster.arrive.relaxed.aligned;\nbarrier.cluster.wait.aligned;\n" ::: "memory");
}
__device__ __forceinline__ void fence_async_smem() { asm volatile("fence.proxy.async.shared::cta;\n" ::: "memory"); }
__device__ __forceinline__ void fence_async_all() { asm volatile("fence.proxy.async.global;\n" ::: "memory"); }

__device__ __forceinline__ void tma_load_3d(uint32_t dst, const CUtensorMap* tm, uint32_t bar, int c0, int c1, int c2) {
  asm volatile(
      "cp.async.bulk.tensor.3d.shared::cluster.global.mbarrier::complete_tx::bytes [%0], [%1, {%3, %4, %5}], [%2];\n"
      ::"r"(dst), "l"(tm), "r"(bar), "r"(c0), "r"(c1), "r"(c2) : "memory");
}
__device__ __forceinline__ void tma_load_4d(uint32_t dst, const CUtensorMap* tm, uint32_t bar, int c0, int c1, int c2, int c3) {
  asm volatile(
      "cp.async.bulk.tensor.4d.shared::cluster.global.mbarrier::complete_tx::bytes [%0], [%1, {%3, %4, %5, %6}], [%2];\n"
      ::"r"(dst), "l"(tm), "r"(bar), "r"(c0), "r"(c1), "r"(c2), "r"(c3) : "memory");
}
__device__ __forceinline__ void tma_load_3d_mc(uint32_t dst, const CUtensorMap* tm, uint32_t bar, int c0, int c1, int c2) {
  asm volatile(
      "cp.async.bulk.tensor.3d.shared::cluster.global.mbarrier::complete_tx::bytes.multicast::cluster [%0], [%1, {%3, %4, %5}], [%2], %6;\n"
      ::"r"(dst), "l"(tm), "r"(bar), "r"(c0), "r"(c1), "r"(c2), "h"((uint16_t)3) : "memory");
}
__device__ __forceinline__ void bulk_load(uint32_t dst, const void* src, uint32_t bytes, uint32_t bar) {
  asm volatile("cp.async.bulk.shared::cluster.global.mbarrier::complete_tx::bytes [%0], [%1], %2, [%3];\n"
               ::"r"(dst), "l"(src), "r"(bytes), "r"(bar) : "memory");
}
__device__ __forceinline__ void tma_store_3d(const CUtensorMap* tm, uint32_t src, int c0, int c1, int c2) {
  asm volatile("cp.async.bulk.tensor.3d.global.shared::cta.bulk_group [%0, {%2, %3, %4}], [%1];\n"
               ::"l"(tm), "r"(src), "r"(c0), "r"(c1), "r"(c2) : "memory");
}
__device__ __forceinline__ void bulk_commit() { asm volatile("cp.async.bulk.commit_group;\n" ::: "memory"); }
__device__ __forceinline__ void bulk_wait0() { asm volatile("cp.async.bulk.wait_group 0;\n" ::: "memory"); }
__device__ __forceinline__ void prefetch_tmap(const CUtensorMap* tm) {
  asm volatile("prefetch.tensormap [%0];\n" ::"l"(tm) : "memory");
}

__device__ __forceinline__ void wg_fence() { asm volatile("wgmma.fence.sync.aligned;\n" ::: "memory"); }
__device__ __forceinline__ void wg_commit() { asm volatile("wgmma.commit_group.sync.aligned;\n" ::: "memory"); }
template <int N> __device__ __forceinline__ void wg_wait() {
  asm volatile("wgmma.wait_group.sync.aligned %0;\n" ::"n"(N) : "memory");
}
__device__ __forceinline__ uint64_t mkdesc(uint32_t addr, uint32_t lbo, uint32_t sbo, uint32_t swz) {
  return (uint64_t)((addr & 0x3FFFF) >> 4) | ((uint64_t)(lbo >> 4) << 16) | ((uint64_t)(sbo >> 4) << 32) |
         ((uint64_t)swz << 62);
}

#define R4(d, o) "+f"(d[o + 0]), "+f"(d[o + 1]), "+f"(d[o + 2]), "+f"(d[o + 3])
#define R8(d, o) R4(d, o), R4(d, o + 4)
#define R16(d, o) R8(d, o), R8(d, o + 8)
#define R32(d, o) R16(d, o), R16(d, o + 16)
#define R64(d, o) R32(d, o), R32(d, o + 32)

__device__ __forceinline__ void wgmma_n192(float (&d)[96], uint64_t da, uint64_t db, uint32_t acc) {
  asm volatile(
      "{\n.reg .pred p;\nsetp.ne.u32 p, %98, 0;\n"
      "wgmma.mma_async.sync.aligned.m64n192k16.f32.bf16.bf16 "
      "{%0,%1,%2,%3,%4,%5,%6,%7,%8,%9,%10,%11,%12,%13,%14,%15,%16,%17,%18,%19,%20,%21,%22,%23,%24,%25,%26,%27,%28,%29,%30,%31,"
      "%32,%33,%34,%35,%36,%37,%38,%39,%40,%41,%42,%43,%44,%45,%46,%47,%48,%49,%50,%51,%52,%53,%54,%55,%56,%57,%58,%59,%60,%61,%62,%63,"
      "%64,%65,%66,%67,%68,%69,%70,%71,%72,%73,%74,%75,%76,%77,%78,%79,%80,%81,%82,%83,%84,%85,%86,%87,%88,%89,%90,%91,%92,%93,%94,%95}, "
      "%96, %97, p, 1, 1, 0, 1;\n}\n"
      : R64(d, 0), R32(d, 64)
      : "l"(da), "l"(db), "r"(acc));
}
__device__ __forceinline__ void wgmma_n128(float (&d)[64], uint64_t da, uint64_t db, uint32_t acc) {
  asm volatile(
      "{\n.reg .pred p;\nsetp.ne.u32 p, %66, 0;\n"
      "wgmma.mma_async.sync.aligned.m64n128k16.f32.bf16.bf16 "
      "{%0,%1,%2,%3,%4,%5,%6,%7,%8,%9,%10,%11,%12,%13,%14,%15,%16,%17,%18,%19,%20,%21,%22,%23,%24,%25,%26,%27,%28,%29,%30,%31,"
      "%32,%33,%34,%35,%36,%37,%38,%39,%40,%41,%42,%43,%44,%45,%46,%47,%48,%49,%50,%51,%52,%53,%54,%55,%56,%57,%58,%59,%60,%61,%62,%63}, "
      "%64, %65, p, 1, 1, 0, 1;\n}\n"
      : R64(d, 0)
      : "l"(da), "l"(db), "r"(acc));
}
#define WG128(C, ACC)                                                                                                      \
  asm volatile(                                                                                                            \
      "{\n.reg .b64 a, b;\nmov.b64 a, {%64, %66};\nmov.b64 b, {%65, %66};\n"                                               \
      "wgmma.mma_async.sync.aligned.m64n128k16.f32.bf16.bf16 "                                                             \
      "{%0,%1,%2,%3,%4,%5,%6,%7,%8,%9,%10,%11,%12,%13,%14,%15,%16,%17,%18,%19,%20,%21,%22,%23,%24,%25,%26,%27,%28,%29,%30,%31," \
      "%32,%33,%34,%35,%36,%37,%38,%39,%40,%41,%42,%43,%44,%45,%46,%47,%48,%49,%50,%51,%52,%53,%54,%55,%56,%57,%58,%59,%60,%61," \
      "%62,%63}, a, b, " ACC ", 1, 1, 0, 1;\n}\n"                                                                          \
      : Z16(C, d, 0), Z16(C, d, 16), Z16(C, d, 32), Z16(C, d, 48)                                                          \
      : "r"(da), "r"(db), "r"(0x40000040))
#define Z4(C, d, o) C(d[o + 0]), C(d[o + 1]), C(d[o + 2]), C(d[o + 3])
#define Z16(C, d, o) Z4(C, d, o), Z4(C, d, o + 4), Z4(C, d, o + 8), Z4(C, d, o + 12)
__device__ __forceinline__ void wgmma_n128z(float (&d)[64], uint32_t da, uint32_t db) { WG128("=f", "0"); }
__device__ __forceinline__ void wgmma_n128a(float (&d)[64], uint32_t da, uint32_t db) { WG128("+f", "1"); }
template <int N> __device__ __forceinline__ void fence_regs(float (&d)[N]) {
#pragma unroll
  for (int i = 0; i < N; i++) asm volatile("" : "+f"(d[i])::"memory");
}

__device__ __forceinline__ void mma16816(float (&d)[4], uint32_t a0, uint32_t a1, uint32_t a2, uint32_t a3, uint32_t b0,
                                         uint32_t b1) {
  asm("mma.sync.aligned.m16n8k16.row.col.f32.bf16.bf16.f32 {%0,%1,%2,%3}, {%4,%5,%6,%7}, {%8,%9}, {%0,%1,%2,%3};\n"
      : "+f"(d[0]), "+f"(d[1]), "+f"(d[2]), "+f"(d[3])
      : "r"(a0), "r"(a1), "r"(a2), "r"(a3), "r"(b0), "r"(b1));
}
__device__ __forceinline__ void mma16816_z(float (&d)[4], uint32_t a0, uint32_t a1, uint32_t a2, uint32_t a3, uint32_t b0,
                                           uint32_t b1) {
  asm("mma.sync.aligned.m16n8k16.row.col.f32.bf16.bf16.f32 {%0,%1,%2,%3}, {%4,%5,%6,%7}, {%8,%9}, {%10,%10,%10,%10};\n"
      : "=f"(d[0]), "=f"(d[1]), "=f"(d[2]), "=f"(d[3])
      : "r"(a0), "r"(a1), "r"(a2), "r"(a3), "r"(b0), "r"(b1), "f"(0.f));
}
__device__ __forceinline__ void ldsm4t(uint32_t (&r)[4], uint32_t a) {
  asm volatile("ldmatrix.sync.aligned.m8n8.x4.trans.shared.b16 {%0,%1,%2,%3}, [%4];\n"
               : "=r"(r[0]), "=r"(r[1]), "=r"(r[2]), "=r"(r[3]) : "r"(a) : "memory");
}
__device__ __forceinline__ void ldsm2t(uint32_t& r0, uint32_t& r1, uint32_t a) {
  asm volatile("ldmatrix.sync.aligned.m8n8.x2.trans.shared.b16 {%0,%1}, [%2];\n" : "=r"(r0), "=r"(r1) : "r"(a) : "memory");
}
__device__ __forceinline__ void st_async128(uint32_t a, uint32_t bar, uint32_t x, uint32_t y, uint32_t z, uint32_t w) {
  asm volatile("st.async.weak.shared::cluster.mbarrier::complete_tx::bytes.v4.b32 [%0], {%2,%3,%4,%5}, [%1];\n"
               ::"r"(a), "r"(bar), "r"(x), "r"(y), "r"(z), "r"(w) : "memory");
}
__device__ __forceinline__ void mbar_arrive(uint32_t a) {
  asm volatile("mbarrier.arrive.shared::cta.b64 _, [%0];\n" ::"r"(a) : "memory");
}
__device__ __forceinline__ void stsm4(uint32_t a, uint32_t r0, uint32_t r1, uint32_t r2, uint32_t r3) {
  asm volatile("stmatrix.sync.aligned.m8n8.x4.shared.b16 [%0], {%1,%2,%3,%4};\n"
               ::"r"(a), "r"(r0), "r"(r1), "r"(r2), "r"(r3) : "memory");
}
__device__ __forceinline__ void stsm4t(uint32_t a, uint32_t r0, uint32_t r1, uint32_t r2, uint32_t r3) {
  asm volatile("stmatrix.sync.aligned.m8n8.x4.trans.shared.b16 [%0], {%1,%2,%3,%4};\n"
               ::"r"(a), "r"(r0), "r"(r1), "r"(r2), "r"(r3) : "memory");
}
__device__ __forceinline__ uint2 lds64(uint32_t a) {
  uint2 v;
  asm volatile("ld.shared.v2.u32 {%0,%1}, [%2];\n" : "=r"(v.x), "=r"(v.y) : "r"(a));
  return v;
}
__device__ __forceinline__ uint4 lds128(uint32_t a) {
  uint4 v;
  asm volatile("ld.shared.v4.u32 {%0,%1,%2,%3}, [%4];\n" : "=r"(v.x), "=r"(v.y), "=r"(v.z), "=r"(v.w) : "r"(a) : "memory");
  return v;
}
__device__ __forceinline__ void sts128(uint32_t a, uint32_t x, uint32_t y, uint32_t z, uint32_t w) {
  asm volatile("st.shared.v4.u32 [%0], {%1,%2,%3,%4};\n" ::"r"(a), "r"(x), "r"(y), "r"(z), "r"(w) : "memory");
}
__device__ __forceinline__ void sts64(uint32_t a, uint32_t x, uint32_t y) {
  asm volatile("st.shared.v2.u32 [%0], {%1,%2};\n" ::"r"(a), "r"(x), "r"(y) : "memory");
}
__device__ __forceinline__ uint32_t pack_bf16(float lo, float hi) {
  uint32_t r;
  asm("cvt.rn.bf16x2.f32 %0, %1, %2;\n" : "=r"(r) : "f"(hi), "f"(lo));
  return r;
}
__device__ __forceinline__ uint32_t bmul2(uint32_t a, uint32_t b) {
  uint32_t r;
  asm("mul.rn.bf16x2 %0, %1, %2;\n" : "=r"(r) : "r"(a), "r"(b));
  return r;
}
__device__ __forceinline__ uint32_t bmax2(uint32_t a, uint32_t b) {
  uint32_t r;
  asm("max.bf16x2 %0, %1, %2;\n" : "=r"(r) : "r"(a), "r"(b));
  return r;
}
__device__ __forceinline__ uint32_t bfma2(uint32_t a, uint32_t b, uint32_t c) {
  uint32_t r;
  asm("fma.rn.bf16x2 %0, %1, %2, %3;\n" : "=r"(r) : "r"(a), "r"(b), "r"(c));
  return r;
}
__device__ __forceinline__ void prefetch_l2(const void* p) { asm volatile("prefetch.global.L2 [%0];\n" ::"l"(p)); }
__device__ __forceinline__ void cp_async16n(uint32_t dst, const void* src) {
  asm volatile("cp.async.cg.shared.global [%0], [%1], 16;\n" ::"r"(dst), "l"(src) : "memory");
}
__device__ __forceinline__ void cp_async16(uint32_t dst, const void* src, uint32_t srcbytes) {
  asm volatile("cp.async.cg.shared.global.L2::256B [%0], [%1], 16, %2;\n" ::"r"(dst), "l"(src), "r"(srcbytes) : "memory");
}
__device__ __forceinline__ uint32_t ld_acquire(const uint32_t* p) {
  uint32_t v;
  asm volatile("ld.acquire.gpu.global.u32 %0, [%1];\n" : "=r"(v) : "l"(p) : "memory");
  return v;
}
__device__ __forceinline__ uint32_t ld_relaxed(const uint32_t* p) {
  uint32_t v;
  asm volatile("ld.relaxed.gpu.global.u32 %0, [%1];\n" : "=r"(v) : "l"(p) : "memory");
  return v;
}
__device__ __forceinline__ void st_release(uint32_t* p, uint32_t v) {
  asm volatile("st.release.gpu.global.u32 [%0], %1;\n" ::"l"(p), "r"(v) : "memory");
}
__device__ __forceinline__ uint4 ld_b128(const uint4* p) {
  unsigned long long a, b;
  asm volatile("{\n.reg .b128 v;\nld.relaxed.gpu.global.b128 v, [%2];\nmov.b128 {%0, %1}, v;\n}\n" : "=l"(a), "=l"(b) : "l"(p) : "memory");
  return make_uint4((uint32_t)a, (uint32_t)(a >> 32), (uint32_t)b, (uint32_t)(b >> 32));
}
__device__ __forceinline__ void st_b128(uint4* p, uint32_t x, uint32_t y, uint32_t z, uint32_t w) {
  asm volatile("{\n.reg .b128 v;\nmov.b128 v, {%1, %2};\nst.relaxed.gpu.global.b128 [%0], v;\n}\n"
               ::"l"(p), "l"(x | (unsigned long long)y << 32), "l"(z | (unsigned long long)w << 32) : "memory");
}

struct Params {
  const __nv_bfloat16* x;
  const __nv_bfloat16* w;
  const __nv_bfloat16* q;
  const __nv_bfloat16* k;
  const __nv_bfloat16* v;
  const __nv_bfloat16* shift_k;
  const __nv_bfloat16* ssm_k;
  const __nv_bfloat16* ssm_D;
  const __nv_bfloat16* wo;
  __nv_bfloat16* out;
  uint32_t zero;
};

__device__ __forceinline__ uint32_t lds32(uint32_t a) {
  uint32_t v;
  asm volatile("ld.shared.u32 %0, [%1];\n" : "=r"(v) : "r"(a) : "memory");
  return v;
}
__device__ __forceinline__ float bf_lo(uint32_t v) {
  uint32_t r;
  asm("prmt.b32 %0, %1, 0, 0x1044;\n" : "=r"(r) : "r"(v));
  return __uint_as_float(r);
}
__device__ __forceinline__ float bf_hi(uint32_t v) { return __uint_as_float(v & 0xffff0000u); }
__device__ __forceinline__ float ex2(float x) {
  float r;
  asm("ex2.approx.ftz.f32 %0, %1;\n" : "=f"(r) : "f"(x));
  return r;
}
__device__ __forceinline__ float rcp(float x) {
  float r;
  asm("rcp.approx.ftz.f32 %0, %1;\n" : "=f"(r) : "f"(x));
  return r;
}

#define Q4(c, d, o) c(d[o + 0]), c(d[o + 1]), c(d[o + 2]), c(d[o + 3])
#define Q8(c, d, o) Q4(c, d, o), Q4(c, d, o + 4)
#define Q16(c, d, o) Q8(c, d, o), Q8(c, d, o + 8)
#define Q32(c, d) Q16(c, d, 0), Q16(c, d, 16)
#define L8 "{%0,%1,%2,%3,%4,%5,%6,%7}"
#define L16 "{%0,%1,%2,%3,%4,%5,%6,%7,%8,%9,%10,%11,%12,%13,%14,%15}"
#define L32 "{%0,%1,%2,%3,%4,%5,%6,%7,%8,%9,%10,%11,%12,%13,%14,%15,%16,%17,%18,%19,%20,%21,%22,%23,%24,%25,%26,%27,%28,%29,%30,%31}"
__device__ __forceinline__ void fft_rows(uint32_t (&d)[32], const uint32_t (&a)[2][4], uint64_t db) {
  asm volatile("wgmma.mma_async.sync.aligned.m64n128k16.f16.f16.f16 " L32 ", {%32,%33,%34,%35}, %36, 0, 1, 1, 1;\n"
               : Q32("=r", d) : "r"(a[0][0]), "r"(a[0][1]), "r"(a[0][2]), "r"(a[0][3]), "l"(db));
  asm volatile("wgmma.mma_async.sync.aligned.m64n128k16.f16.f16.f16 " L32 ", {%32,%33,%34,%35}, %36, 1, 1, 1, 1;\n"
               : Q32("+r", d) : "r"(a[1][0]), "r"(a[1][1]), "r"(a[1][2]), "r"(a[1][3]), "l"(db + 64));
}
template <int INV> __device__ __forceinline__ void fft_cols(uint32_t (&d)[8], const uint32_t (&a)[2][4], uint64_t db) {
  asm volatile("wgmma.mma_async.sync.aligned.m64n32k16.f16.f16.f16 " L8 ", {%8,%9,%10,%11}, %12, 0, 1, 1, %13;\n"
               : Q8("=r", d, 0) : "r"(a[0][0]), "r"(a[0][1]), "r"(a[0][2]), "r"(a[0][3]), "l"(db), "n"(INV));
  asm volatile("wgmma.mma_async.sync.aligned.m64n32k16.f16.f16.f16 " L8 ", {%8,%9,%10,%11}, %12, 1, 1, 1, %13;\n"
               : Q8("+r", d, 0) : "r"(a[1][0]), "r"(a[1][1]), "r"(a[1][2]), "r"(a[1][3]), "l"(db + (INV ? 16 : 64)), "n"(INV));
}
__device__ __forceinline__ void fft_back(float (&d)[16], uint64_t da, uint64_t db) {
  asm volatile("wgmma.mma_async.sync.aligned.m64n32k16.f32.f16.f16 " L16 ", %16, %17, 0, 1, 1, 1, 1;\n"
               : Q16("=f", d, 0) : "l"(da), "l"(db));
#pragma unroll
  for (int i = 1; i < 4; i++)
    asm volatile("wgmma.mma_async.sync.aligned.m64n32k16.f32.f16.f16 " L16 ", %16, %17, 1, 1, 1, 1, 1;\n"
                 : Q16("+f", d, 0) : "l"(da + 32 * i), "l"(db + 64 * i));
}
__device__ __forceinline__ uint32_t hmul2(uint32_t a, uint32_t b) {
  uint32_t r;
  asm("mul.rn.f16x2 %0, %1, %2;\n" : "=r"(r) : "r"(a), "r"(b));
  return r;
}
__device__ __forceinline__ uint32_t hadd2(uint32_t a, uint32_t b) {
  uint32_t r;
  asm("add.rn.f16x2 %0, %1, %2;\n" : "=r"(r) : "r"(a), "r"(b));
  return r;
}
__device__ __forceinline__ uint32_t hneg2(uint32_t a) {
  uint32_t r;
  asm("neg.f16x2 %0, %1;\n" : "=r"(r) : "r"(a));
  return r;
}
__device__ __forceinline__ uint32_t hfma2(uint32_t a, uint32_t b, uint32_t c) {
  uint32_t r;
  asm("fma.rn.f16x2 %0, %1, %2, %3;\n" : "=r"(r) : "r"(a), "r"(b), "r"(c));
  return r;
}
__device__ __forceinline__ uint32_t pack_f16(float lo, float hi) {
  uint32_t r;
  asm("cvt.rn.f16x2.f32 %0, %1, %2;\n" : "=r"(r) : "f"(hi), "f"(lo));
  return r;
}
__device__ __forceinline__ uint32_t bmaxabs2(uint32_t a, uint32_t b) {
  uint32_t r;
  asm("max.xorsign.abs.bf16x2 %0, %1, %2;\n" : "=r"(r) : "r"(a), "r"(b));
  return r;
}
struct C2 { uint32_t r, i; };
__device__ __forceinline__ C2 cmul(C2 a, C2 b) {
  return C2{hfma2(a.r, b.r, hneg2(hmul2(a.i, b.i))), hfma2(a.r, b.i, hmul2(a.i, b.r))};
}
__device__ __forceinline__ C2 cfma(C2 a, C2 b, C2 c) {
  return C2{hfma2(a.r, b.r, hfma2(hneg2(a.i), b.i, c.r)), hfma2(a.r, b.i, hfma2(a.i, b.r, c.i))};
}
__device__ __forceinline__ C2 crot(C2 z, C2 t) {
  const uint32_t r = hfma2(t.r, z.i, z.r), i = hfma2(t.i, r, z.i);
  return C2{hfma2(t.r, i, r), i};
}
__device__ __forceinline__ C2 cget(const uint32_t (&e)[8], int j, int b) { return C2{e[4 * j + b], e[4 * j + 2 + b]}; }
template <int N> __device__ __forceinline__ void fence_regs(uint32_t (&d)[N]) {
#pragma unroll
  for (int i = 0; i < N; i++) asm volatile("" : "+r"(d[i])::"memory");
}
__device__ __forceinline__ void ldsm4(uint32_t (&r)[4], uint32_t a) {
  asm volatile("ldmatrix.sync.aligned.m8n8.x4.shared.b16 {%0,%1,%2,%3}, [%4];\n"
               : "=r"(r[0]), "=r"(r[1]), "=r"(r[2]), "=r"(r[3]) : "r"(a) : "memory");
}

__device__ __forceinline__ uint32_t movm(uint32_t a) {
  uint32_t r;
  asm volatile("movmatrix.sync.aligned.m8n8.trans.b16 %0, %1;\n" : "=r"(r) : "r"(a));
  return r;
}
template <int C0, int H, bool T> __device__ __forceinline__ void attn_pack(const float (&acc)[96], uint32_t (&d)[8]) {
#pragma unroll
  for (int c = 0; c < 8; c++) {
    asm volatile("cvt.rn.bf16x2.f32 %0, %1, %2;\n" : "=r"(d[c]) : "f"(acc[4 * (C0 + c) + 2 * H + 1]), "f"(acc[4 * (C0 + c) + 2 * H]));
    if (T) d[c] = movm(d[c]);
  }
}
__device__ __forceinline__ void attn_qk(float (&s)[4], const uint32_t (&qlo)[8], const uint32_t (&qhi)[8],
                                        const uint32_t (&k)[8], int c) {
  mma16816_z(s, qlo[c], qhi[c], qlo[c + 1], qhi[c + 1], k[c], k[c + 1]);
  mma16816(s, qlo[c + 2], qhi[c + 2], qlo[c + 3], qhi[c + 3], k[c + 2], k[c + 3]);
}
template <int N> __device__ __forceinline__ void quad_softmax(float (&x)[N][2], uint32_t (&pp)[N]) {
  const float c2 = 1.4426950408889634f;
  uint32_t q[N], mx[N / 2];
#pragma unroll
  for (int n = 0; n < N; n++) {
    const uint32_t r = pack_bf16(x[n][0], x[n][1]);
    q[n] = bfma2(r, 0x3e353e35u, bmul2(r, 0x379e379eu));
    x[n][0] = bf_lo(q[n]);
    x[n][1] = bf_hi(q[n]);
  }
#pragma unroll
  for (int n = 0; n < N / 2; n++)
    mx[n] = bmax2(__byte_perm(q[2 * n], q[2 * n + 1], 0x5410), __byte_perm(q[2 * n], q[2 * n + 1], 0x7632));
#pragma unroll
  for (int o = 1; o <= 2; o++) {
#pragma unroll
    for (int n = 0; n < N / 2; n++) mx[n] = bmax2(mx[n], __shfl_xor_sync(0xffffffffu, mx[n], o));
  }
  float m[N], t[N];
#pragma unroll
  for (int n = 0; n < N / 2; n++) {
    m[2 * n] = bf_lo(mx[n]);
    m[2 * n + 1] = bf_hi(mx[n]);
  }
#pragma unroll
  for (int n = 0; n < N; n++) {
    const float nm = -m[n] * c2;
    x[n][0] = ex2(fmaf(x[n][0], c2, nm));
    x[n][1] = ex2(fmaf(x[n][1], c2, nm));
  }
#pragma unroll
  for (int n = 0; n < N; n += 2) {
    float u0, u1;
    asm("mma.sync.aligned.m16n8k8.row.col.f32.tf32.tf32.f32 {%0,%1,%2,%3}, {%4,%5,%6,%7}, {%8,%8}, {%9,%9,%9,%9};\n"
        : "=f"(t[n]), "=f"(u0), "=f"(t[n + 1]), "=f"(u1)
        : "r"(__float_as_uint(x[n][0])), "r"(__float_as_uint(x[n + 1][0])), "r"(__float_as_uint(x[n][1])),
          "r"(__float_as_uint(x[n + 1][1])), "r"(0x3f800000u), "f"(0.f));
  }
#pragma unroll
  for (int n = 0; n < N; n++) {
    const float inv = rcp(t[n]);
    pp[n] = pack_bf16(x[n][0] * inv, x[n][1] * inv);
  }
}
template <bool SPLIT>
__device__ __forceinline__ void attn_pv(uint32_t dst, const uint32_t (&vp)[8], const uint32_t (&vo)[8], int c, uint32_t pp,
                                        uint32_t maskLE) {
  const uint32_t b0 = pp & ~maskLE, b1 = pp & maskLE;
  float o[2][4];
#pragma unroll
  for (int i = 0; i < 2; i++) {
    if (SPLIT) {
      asm("mma.sync.aligned.m16n8k8.row.col.f32.bf16.bf16.f32 {%0,%1,%2,%3}, {%4,%5}, {%6}, {%7,%7,%7,%7};\n"
          : "=f"(o[i][0]), "=f"(o[i][1]), "=f"(o[i][2]), "=f"(o[i][3])
          : "r"(vp[c + 2 * i]), "r"(vp[c + 2 * i + 1]), "r"(b0), "f"(0.f));
      asm("mma.sync.aligned.m16n8k8.row.col.f32.bf16.bf16.f32 {%0,%1,%2,%3}, {%4,%5}, {%6}, {%0,%1,%2,%3};\n"
          : "+f"(o[i][0]), "+f"(o[i][1]), "+f"(o[i][2]), "+f"(o[i][3])
          : "r"(vo[c + 2 * i]), "r"(vo[c + 2 * i + 1]), "r"(b1));
    } else {
      mma16816_z(o[i], vp[c + 2 * i], vp[c + 2 * i + 1], vo[c + 2 * i], vo[c + 2 * i + 1], b0, b1);
    }
  }
  stsm4t(dst, pack_bf16(o[0][0], o[0][1]), pack_bf16(o[0][2], o[0][3]), pack_bf16(o[1][0], o[1][1]),
         pack_bf16(o[1][2], o[1][3]));
}

template <int MODE>
__global__ void __cluster_dims__(2, 1, 1) __launch_bounds__(NTHREADS, 1)
fused_kernel(const Params p, const __grid_constant__ CUtensorMap tmX, const __grid_constant__ CUtensorMap tmW,
             const __grid_constant__ CUtensorMap tmWo, const __grid_constant__ CUtensorMap tmWp,
             const __grid_constant__ CUtensorMap tmQ,
             const __grid_constant__ CUtensorMap tmOb,
             const __grid_constant__ CUtensorMap tmXh, const __grid_constant__ CUtensorMap tmWh) {
  extern __shared__ __align__(1024) uint8_t smem[];
  if (threadIdx.x < 32) {
    const uint32_t i = (blockIdx.x & 127) * 16 + (threadIdx.x & 15);
    prefetch_l2(threadIdx.x & 16 ? (const char*)p.w + i * 128 : (const char*)p.x + i * 2048);
  }
  const uint32_t sb = smem_u32(smem);
  const uint32_t bars = sb + OFF_BAR;
  const int tid = threadIdx.x, lane = tid & 31, warp = __shfl_sync(0xffffffffu, tid >> 5, 0);
  const int rank = blockIdx.x & 1;
  const bool halo_cta = blockIdx.x < 4;
  if (halo_cta && MODE != 0) return;
  int grp, mem;
  {
    const int t = (blockIdx.x >> 1) - 4, u = t - 32;
    const int q7 = (u * 37) >> 8;
    const bool lo = (unsigned)t < 32u, mid = (unsigned)u < 28u;
    grp = lo ? (t & 7) : (mid ? 1 + u - 7 * q7 : 0);
    mem = lo ? (t >> 3) : (mid ? 4 + q7 : (t < 0 ? t + 6 : t - 54));
  }
  const int rg = (grp >> 2) * 4 + (mem >> 1), hp = (grp & 3) * 4 + (mem & 1) * 2 + rank;
  const int rb2 = (grp >> 2) * 8 + mem, cb2 = (grp & 3) * 2 + rank;
  const int chb = grp * 16 + mem * 2 + rank;
  const int cta = rg * 16 + hp;
  const int hsel = rb2 & 1;
  const int par = rg >> 2, gidx = rg & 3;

  if (tid < 256 && !halo_cta && MODE != 2) {
    const int r = tid >> 3, c = tid & 7;
    const uint32_t so = r * 128 + ((c ^ (r & 7)) << 4);
    const __nv_bfloat16* wg0 = p.w + (size_t)r * (3 * DM) + hp * 64 + c * 8;
    const __nv_bfloat16* xg0 = p.x + (size_t)(2 * (gidx * 256 + r) + par) * DM + c * 8;
#pragma unroll
    for (int j = 0; j < 3; j++) cp_async16n(sb + OFF_1B + j * 4096 + so, wg0 + j * DM);
#pragma unroll
    for (int i = 0; i < 8; i++) cp_async16n(sb + i * 4096 + so, xg0 + (size_t)i * 64 * DM);
    asm volatile("cp.async.commit_group;\n" ::: "memory");
    if (tid < 16) prefetch_l2((const char*)p.x + (chb * 16 + tid) * 2048 + 128);
    if (warp == 2) prefetch_l2((const char*)p.w + (2048 + chb * 32 + lane) * 128);
  }

  if (warp >= 8) {
    asm volatile("setmaxnreg.dec.sync.aligned.u32 %0;\n" :: "n"(REG_HELP));
    auto halo_issue = [&](int n, int s) {
      const uint32_t fb = bars + 8 * (BAR_FULLB + s), st = sb + s * STGH;
      tma_load_3d(st + 8192, &tmWh, fb, 0, (n >> 1) * 64, 16 + (n & 1) * 16 + blockIdx.x * 4);
      tma_load_4d(st, &tmXh, fb, (n >> 1) * 64, 248, 0, 0);
      mbar_expect_tx(fb, STGH - 2048);
    };
    if (tid == 256) {
      prefetch_tmap(halo_cta ? &tmXh : &tmX);
#pragma unroll
      for (int i = 0; i < NS1B; i++) mbar_init(bars + 8 * (BAR_FULLB + i), 1);
#pragma unroll
      for (int i = 0; i < NS1A; i++) mbar_init(bars + 8 * (BAR_FULLA + i), 1);
      asm volatile("fence.mbarrier_init.release.cluster;\n" ::: "memory");
      if (!halo_cta && MODE != 2) {
        mbar_expect_tx(bars + 8 * (BAR_FULLB + 1), STG1B);
        tma_load_3d(sb + OFF_1B + 1 * STG1B, &tmW, bars + 8 * (BAR_FULLB + 1), hp * 64, 32, 0);
        mbar_expect_tx(bars + 8 * (BAR_FULLB + 2), STG1B);
        tma_load_3d(sb + OFF_1B + 2 * STG1B, &tmW, bars + 8 * (BAR_FULLB + 2), hp * 64, 64, 0);
        mbar_arrive(bars + 8 * BAR_FULLA);
        mbar_arrive(bars + 8 * BAR_FULLB);
      } else if (halo_cta) {
        halo_issue(0, 0);
      }
    } else if (tid == 288) {
#pragma unroll
      for (int i = 0; i < NS1A; i++) mbar_init(bars + 8 * (BAR_EMPTYA + i), 4);
#pragma unroll
      for (int i = 0; i < NS1B; i++) mbar_init(bars + 8 * (BAR_EMPTYB + i), 2);
      mbar_init(bars + 8 * BAR_X, 3);
      mbar_init(bars + 8 * BAR_TAB, 16);
      mbar_init(bars + 8 * BAR_U, 1);
      mbar_init(bars + 8 * BAR_H, 1);
      mbar_init(bars + 8 * BAR_STG, 8);
      mbar_init(bars + 8 * BAR_HALO, 1);
      mbar_init(bars + 8 * BAR_Q, 1);
      mbar_init(bars + 8 * BAR_LAND, 5);
      mbar_init(bars + 8 * (BAR_LAND + 1), 5);
      asm volatile("fence.mbarrier_init.release.cluster;\n" ::: "memory");
    } else if (tid == 320) {
#pragma unroll
      for (int i = 0; i < NS2; i++) {
        mbar_init(bars + 8 * (BAR_FULL2 + i), 1);
        mbar_init(bars + 8 * (BAR_EMPTY2 + i), 2);
        mbar_init(bars + 8 * (BAR_EMPTY2B + i), 2);
      }
      asm volatile("fence.mbarrier_init.release.cluster;\n" ::: "memory");
    } else if (tid == 352) {
#pragma unroll
      for (int i = 0; i < 4; i++) mbar_init(bars + 8 * (BAR_Y + i), i < 2 ? 4 : i == 2 ? 10 : 8);
      mbar_init(bars + 8 * BAR_XFREE, 1);
      asm volatile("fence.mbarrier_init.release.cluster;\n" ::: "memory");
    }
    __syncwarp();
    cluster_sync_all();
    if (warp == 8) PROF2(24);
    const int hw = warp - 8;
    const int lr = lane & 7, lm = lane >> 3;
    auto g1_issue_a = [&](int j, int s) {
      const uint32_t fb = bars + 8 * (BAR_FULLA + s);
      mbar_expect_tx(fb, STG1A);
      tma_load_3d_mc(sb + s * STG1A + rank * 16384, &tmX, fb, j * 64, par, gidx * 256 + rank * 128);
    };
    auto g1_issue_b = [&](int kb, int s) {
      const uint32_t fb = bars + 8 * (BAR_FULLB + s);
      mbar_expect_tx(fb, STG1B);
      tma_load_3d(sb + OFF_1B + s * STG1B, &tmW, fb, hp * 64, kb * 32, 0);
    };
    auto g2_k = [&](int kb) { return (kb < 2 ? hp : kb < 4 ? hp & 14 : hp & 12) ^ kb; };
    auto g2_issue_b = [&](uint32_t fb, uint32_t bytes, uint32_t dst, int k0, bool whole) {
      if (whole) {
        tma_load_3d(dst, &tmWo, fb, 0, k0, cb2 * 2);
      } else {
#pragma unroll
        for (int i = 0; i < 4; i++)
          tma_load_3d(dst + (i & 1) * XT + (i >> 1) * 4 * XT, &tmWp, fb, 0, k0 + (i >> 1) * 32, cb2 * 2 + (i & 1));
      }
      mbar_expect_tx(fb, bytes);
    };
    auto send_y = [&](uint32_t o, uint32_t step, int half) {
      const uint32_t peer = mapa(sb, rank ^ 1);
      o += OFF_X + (rank ^ 1) * 4096 + half * 2048 + lane * 16;
      uint4 a[8];
#pragma unroll
      for (int i = 0; i < 8; i++) a[i] = lds128(sb + o + (i >> 2) * step + (i & 2) * (XT / 2) + (i & 1) * 512);
#pragma unroll
      for (int i = 0; i < 8; i++)
        st_async128(peer + o + 1024 + (i >> 2) * step + (i & 2) * (XT / 2) + (i & 1) * 512,
                    peer + OFF_BAR + 8 * (BAR_LAND + half), a[i].x, a[i].y, a[i].z, a[i].w);
    };

    if (halo_cta) {
      if (hw == 0) {
        int s = 1, ph = 1;
#pragma unroll 1
        for (int n = 1; n < 32; n++) {
          mbar_wait(bars + 8 * (BAR_EMPTYB + s), ph);
          if (elect_one()) halo_issue(n, s);
          if (++s == NS1B) { s = 0; ph ^= 1; }
        }
      }
      __syncwarp();
    } else if (hw == 0) {
      uint32_t epoch = 0;
      if (MODE == 2) {
        if (lane < NS2) mbar_arrive_cluster_n(mapa(bars, rank) + 8 * (BAR_EMPTY2 + lane), 2);
      } else {
      if (lane == 0) {
        mbar_expect_tx(bars + 8 * BAR_U, 32768);
        mbar_expect_tx(bars + 8 * BAR_LAND, 8192);
        mbar_expect_tx(bars + 8 * (BAR_LAND + 1), 8192);
        mbar_expect_tx(bars + 8 * BAR_Q, 32768);
        prefetch_tmap(&tmQ);
      }
      {
        int sa = 1, pha = 1, sbb = 2, phb = 1;
#pragma unroll 1
        for (int kb = 2; kb < 32; kb++) {
          if (!(kb & 1)) {
            mbar_wait(bars + 8 * (BAR_EMPTYA + sa), pha);
            if (elect_one()) g1_issue_a(kb >> 1, sa);
            if (++sa == NS1A) { sa = 0; pha ^= 1; }
          }
          mbar_wait(bars + 8 * (BAR_EMPTYB + sbb), phb);
          if (kb > 2 && elect_one()) g1_issue_b(kb, sbb);
          __syncwarp();
          if (kb == 4) epoch = ld_relaxed(g_flag_o + cta);
          if (kb == 4) PROF2(27);
          if (kb == 1) PROF2(38);
          if (kb == 2) PROF2(39);
          if (++sbb == NS1B) { sbb = 0; phb ^= 1; }
        }
      }
      auto q_issue = [&](int i) {
        mbar_wait(bars + 8 * (i ? BAR_EMPTYB + 3 : BAR_EMPTYA + 1), i);
        if (elect_one())
          asm volatile(
              "cp.async.bulk.tensor.5d.shared::cluster.global.mbarrier::complete_tx::bytes [%0], [%1, {%3, %4, %4, %4, %5}], [%2];\n"
              ::"r"(sb + (i ? OFF_Q1 : OFF_Q0)), "l"(&tmQ), "r"(bars + 8 * BAR_Q), "r"((chb & ~1) * 8), "r"(0), "r"(rank * 32 + i * 64)
              : "memory");
        __syncwarp();
      };
      epoch++;
      if (lane == 0) {
        prefetch_tmap(&tmWo);
        prefetch_tmap(&tmWp);
        prefetch_tmap(&tmOb);
      }
      __syncwarp();
      {
        uint4 h[6] = {};
        if (gidx != 0) {
#pragma unroll 1
          for (int n = 0; n < SPIN_LIMIT; n++) {
            bool ok = true;
#pragma unroll
            for (int i = 0; i < 6; i++) h[i] = ld_b128(g_halo + cta * 192 + i * 32 + lane);
#pragma unroll
            for (int i = 0; i < 6; i++) ok = ok && h[i].w == epoch;
            if (__all_sync(0xffffffffu, ok)) break;
          }
          PROF(18);
        }
        q_issue(0);
        sts128(sb + OFF_KH + lane * 16, h[0].x, h[0].y, h[0].z, h[1].x);
        sts128(sb + OFF_KH + 512 + lane * 16, h[1].y, h[1].z, h[2].x, h[2].y);
        sts64(sb + OFF_KH + 1024 + lane * 8, h[3].x, h[3].y);
        sts64(sb + OFF_KH + 1280 + lane * 8, h[3].z, h[4].x);
        sts64(sb + OFF_KH + 1536 + lane * 8, h[4].y, h[4].z);
        sts64(sb + OFF_KH + 1792 + lane * 8, h[5].x, h[5].y);
        __syncwarp();
        if (lane == 0) mbar_arrive(bars + 8 * BAR_HALO);
      }
      q_issue(1);
      const uint32_t rb = mapa(bars, lane & 1);
      nb_sync(NB_OREADY, 288);
      if (lane == 0) {
        asm volatile("cp.async.bulk.global.shared::cta.bulk_group [%0], [%1], %2;\n" ::"l"(g_o + (size_t)cta * 16384),
                     "r"(sb + OFF_OP), "r"(32768) : "memory");
        bulk_commit();
      }
      if (lane < 2) {
#pragma unroll
        for (int i = 0; i < 4; i++) mbar_arrive_cluster(rb + 8 * (BAR_EMPTY2 + i + i / 2));
      }
      if (lane == 0) {
        bulk_wait0();
        st_release(g_flag_o + cta, epoch);
      }
      __syncwarp();
      PROF2(17);
      if (lane < 2) mbar_arrive_cluster(rb + 8 * (BAR_EMPTY2 + 2));
      }
      if (MODE != 1) {
        const __nv_bfloat16* osrc = g_o + (size_t)(rb2 >> 1) * 16 * 16384 + hsel * 8192;
        mbar_wait(bars + 8 * (BAR_EMPTY2 + 1), 0);
        if (elect_one()) {
          if (MODE == 0) {
            asm volatile("cp.async.bulk.shared::cluster.shared::cta.mbarrier::complete_tx::bytes [%0], [%1], %2, [%3];\n"
                         ::"r"(mapa(sb + g2_a(1, hsel), rank ^ 1)), "r"(sb + g2_a(0, hsel)), "r"(16384),
                         "r"(mapa(bars + 8 * (BAR_FULL2 + 1), rank ^ 1)) : "memory");
          } else {
            bulk_load(sb + g2_a(0, hsel), osrc + hp * 16384, 16384, bars + 8 * BAR_FULL2);
            bulk_load(sb + g2_a(1, hsel), osrc + (hp ^ 1) * 16384, 16384, bars + 8 * (BAR_FULL2 + 1));
          }
        }
        __syncwarp();
      }
      if (MODE != 2) {
        mbar_wait(bars + 8 * (BAR_Y + 2), 0);
        send_y(0, 4 * XT, 1);
        fence_async_smem();
        __syncwarp();
      }
      if (MODE != 1) {
        int s = 3, k0 = g2_k(3) * 64;
        uint32_t wbar = bars + 8 * (BAR_Y + 2), fb = bars + 8 * (BAR_FULL2 + 3), dst = sb + g2_b(3, rank), ph = MODE ? 1 : 0;
        int whole = 0;
#pragma unroll 1
        for (int kb = 3; kb < 16;) {
          mbar_wait(wbar, ph);
          if (elect_one()) g2_issue_b(fb, STG2, dst, k0, whole);
          __syncwarp();
          kb++;
          if (++s == NS2) { s = 0; ph = kb == 2 * NS2; }
          wbar = bars + 8 * (kb == 4 ? BAR_XFREE : BAR_EMPTY2B + s);
          fb = bars + 8 * (BAR_FULL2 + s);
          dst = sb + g2_b(s, rank);
          k0 = ((hp & 12) ^ kb) * 64;
          whole = s < 3;
          asm volatile("" : "+r"(fb), "+r"(k0), "+r"(whole));
        }
      }
      __syncwarp();
    } else {
      if (MODE != 2) {
      const float dall = __bfloat162float(p.ssm_D[chb * 8 + lr]);
      {
        const int g = lane >> 2, t = lane & 3;
        uint32_t w[2][4];
#pragma unroll
        for (int h = 0; h < 2; h++) {
          const uint2 x = __ldg(reinterpret_cast<const uint2*>(p.shift_k + ((chb & ~1) * 8 + h * 8 + g) * 4));
          w[h][0] = __byte_perm(x.x, x.x, 0x1010);
          w[h][1] = __byte_perm(x.x, x.x, 0x3232);
          w[h][2] = __byte_perm(x.y, x.y, 0x1010);
          w[h][3] = __byte_perm(x.y, x.y, 0x3232);
        }
        auto swz = [](int r) { return (((r & 29) | ((r ^ (r >> 2)) & 2)) << 5) | (r & 16); };
        const uint32_t kring = sb + OFF_X + 4096 + (hw - 1) * 2 * XT, vring = kring + XT;
        const int s0 = rank * 32 + (hw - 1) * 11, s1 = hw == 3 ? rank * 32 + 32 : s0 + 11;
        const size_t goff = (size_t)(s0 * 32 + (lane >> 1)) * DM + (chb & ~1) * 8 + (lane & 1) * 8;
        const __nv_bfloat16* kg = p.k + goff;
        const __nv_bfloat16* vg = p.v + goff;
        const uint32_t d0 = swz(lane >> 1) ^ ((lane & 1) << 4), d1 = swz(16 + (lane >> 1)) ^ ((lane & 1) << 4);
        auto issue = [&](int st) {
          const uint32_t a = kring + ((st & 3) << 10);
          asm volatile("cp.async.cg.shared.global.L2::256B [%0], [%2], 16;\n"
                       "cp.async.cg.shared.global.L2::256B [%1], [%2 + 32768], 16;\n"
                       "cp.async.cg.shared.global.L2::256B [%0 + 8192], [%3], 16;\n"
                       "cp.async.cg.shared.global.L2::256B [%1 + 8192], [%3 + 32768], 16;\n"
                       ::"r"(a + d0), "r"(a + d1), "l"(kg), "l"(vg) : "memory");
          kg += 32 * DM;
          vg += 32 * DM;
          asm volatile("" : "+l"(kg), "+l"(vg));
        };
        const int xa = 8 * (lr >> 1) + 2 * lm + (lr & 1), xb = 8 * (lr >> 1) - 4 + 2 * (lm & 1) + (lr & 1);
        const uint32_t la = swz(xa), lb = swz(xb & 31);
        const int backb = xb < 0 ? 1 : 0;
        const uint32_t ud[2] = {mapa(sb + OFF_X + g * XT + t * 16, 0), mapa(sb + OFF_X + g * XT + t * 16, 1)};
        const uint32_t ub[2] = {mapa(bars + 8 * BAR_U, 0), mapa(bars + 8 * BAR_U, 1)};
        if (tid == 320) prefetch_l2(g_tab + (chb & 63) * 32);
        if (lane == 0) mbar_wait(bars + 8 * (BAR_FULLB + NS1B - 1), 0);
        __syncwarp();
        if (lane >= 24) cp_async16(kring + (((s0 - 1) & 3) << 10) + d1, s0 > 0 ? kg - 16 * DM : kg, s0 > 0 ? 16 : 0);
        issue(s0);
        asm volatile("cp.async.commit_group;\n" ::: "memory");
        issue(s0 + 1);
        asm volatile("cp.async.commit_group;\n" ::: "memory");
        const __nv_bfloat16* hg = p.ssm_k + (size_t)chb * 8 * SEQ + lane * 64;
        uint32_t tn = (uint32_t)clock();
#pragma unroll 1
        for (int st = s0; st < s1; st++) {
          tn += PSTEP;
          while ((int)((uint32_t)clock() - tn) < 0) __nanosleep(100);
          if (st + 2 < s1) issue(st + 2);
          if (hw == 1 && st - s0 < 8) prefetch_l2(hg);
          hg += SEQ;
          asm volatile("" : "+l"(hg));
          asm volatile("cp.async.commit_group;\n" ::: "memory");
          asm volatile("cp.async.wait_group 2;\n" ::: "memory");
          __syncwarp();
#pragma unroll
          for (int h = 0; h < 2; h++) {
            uint32_t e[6], vv[4], e4[4];
            ldsm4t(e4, kring + ((st & 3) << 10) + (la ^ (h << 4)));
            ldsm2t(e[0], e[1], kring + (((st - backb) & 3) << 10) + (lb ^ (h << 4)));
            ldsm4t(vv, vring + ((st & 3) << 10) + (la ^ (h << 4)));
            e[2] = e4[0]; e[3] = e4[1]; e[4] = e4[2]; e[5] = e4[3];
            uint32_t o[5];
#pragma unroll
            for (int i = 0; i < 5; i++) o[i] = __byte_perm(e[i], e[i + 1], 0x5432);
#pragma unroll
            for (int i = 0; i < 4; i++) {
              uint32_t a = bmul2(o[i], w[h][3]);
              a = bfma2(e[i + 1], w[h][2], a);
              a = bfma2(o[i + 1], w[h][1], a);
              a = bfma2(e[i + 2], w[h][0], a);
              vv[i] = bmul2(a, vv[i]);
            }
            st_async128(ud[h] + (st ^ (g & 1)) * 64, ub[h], vv[0], vv[1], vv[2], vv[3]);
          }
          __syncwarp();
        }
        fence_async_smem();
        PROF(16);
      }
      nb_sync(NB_HELP3, 96);
      if (hw == 1 && elect_one()) {
        mbar_expect_tx(bars + 8 * BAR_H, 8 * 4096 + 6144);
#pragma unroll 1
        for (int c = 0; c < 8; c++)
          bulk_load(sb + OFF_X + c * XT + 4096, p.ssm_k + (size_t)(chb * 8 + c) * SEQ, 4096, bars + 8 * BAR_H);
        bulk_load(sb + OFF_T16, g_tab, 2048, bars + 8 * BAR_H);
        bulk_load(sb + OFF_T32, g_tab + 512, 4096, bars + 8 * BAR_H);
      }
      __syncwarp();
      {
        if (hw == 3) {
          const char* wo = (const char*)p.wo + chb * 16384 + lane * 128;
#pragma unroll
          for (int i = 0; i < 4; i++) prefetch_l2(wo + i * 4096);
        }
        const int ck = 16 * (lane >> 4) + 2 * lr + (((lane >> 3) ^ (lane >> 2)) & 1);
        const uint32_t xo = (ck >> 1) * 64, xs = ((ck & 1) ^ (lr >> 1)) << 4;
#pragma unroll 1
        for (int job = hw - 1; job < 16; job += 3) {
          const int c = job & 7;
          uint4 a[8];
          float dv = __shfl_sync(0xffffffffu, dall, c);
          if (job < 8 || lane) dv = 0.f;
          const uint32_t xt = sb + OFF_X + c * XT + (job >> 3) * 4096;
          mbar_wait(bars + 8 * (job < 8 ? BAR_U : BAR_H), 0);
#pragma unroll
          for (int i = 0; i < 8; i++) a[i] = lds128(xt + i * 512 + ((ck ^ (job < 8 ? (c & 1) << 2 : 0)) << 4));
          dv += bf_lo(a[0].x);
          uint32_t m[2] = {bmaxabs2(pack_bf16(dv, 0.f), bmaxabs2(a[0].x, a[0].y)), bmaxabs2(a[0].z, a[0].w)};
#pragma unroll
          for (int i = 1; i < 8; i++) {
            m[0] = bmaxabs2(bmaxabs2(m[0], a[i].x), a[i].y);
            m[1] = bmaxabs2(bmaxabs2(m[1], a[i].z), a[i].w);
          }
          m[0] = bmaxabs2(m[0], m[1]);
          const int f = max(252 - (int)(__reduce_max_sync(0xffffffffu, max(m[0] & 0x7fffu, (m[0] >> 16) & 0x7fffu)) >> 7), 1);
          if (lane == 0) asm volatile("st.shared.u32 [%0], %1;\n" ::"r"(sb + OFF_EX + job * 4), "r"(f) : "memory");
          if (f < 113) {
#pragma unroll
            for (int i = 0; i < 8; i++)
              a[i] = make_uint4(bmul2(a[i].x, f * 0x00800080u), bmul2(a[i].y, f * 0x00800080u), bmul2(a[i].z, f * 0x00800080u),
                                bmul2(a[i].w, f * 0x00800080u));
          }
          const uint32_t mul = (f < 113 ? 15 : f - 112) * 0x00800080u;
          auto cv = [&](uint32_t x) {
            x = bmul2(x, mul);
            return (x & 0x0fff0fffu) * 7 + x;
          };
          const uint32_t dst = xt + xo;
#pragma unroll
          for (int i = 0; i < 8; i++)
            sts128(dst + (i >> 2) * 2048 + (i & 1) * 1024 + (xs ^ ((i & 2) << 4)),
                   i ? cv(a[i].x) : __byte_perm(pack_f16(dv * __uint_as_float(f << 23), 0.f), cv(a[i].x), 0x7610), cv(a[i].y),
                   cv(a[i].z), cv(a[i].w));
        }
        fence_async_smem();
        __syncwarp();
        if (lane == 0) mbar_arrive(bars + 8 * BAR_X);
        PROF(19);
      }
      if (hw < 3) {
#pragma unroll 1
        for (int n = 0; n < SPIN_LIMIT && !mbar_try(bars + 8 * (BAR_Y + hw - 1), 0); n++) __nanosleep(100);
        send_y((hw - 1) * 4 * XT, 2 * XT, 0);
        __syncwarp();
        if (lane == 0) mbar_arrive(bars + 8 * (BAR_Y + 2));
        PROF(32);
        const int c8 = 2 * lm + (lr & 1), src = (lr >> 1) & 1;
        uint32_t fa = sb + OFF_X + c8 * XT + rank * 4096 + (src == rank ? 0 : 1024) + (hw - 1) * 512;
        const uint32_t fx = ((lr >> 2) ^ ((lr & 3) << 1)) << 4;
        uint32_t qa = sb + OFF_Q0 + (hw - 1) * 8192 + (lane >> 3) * 128 + (lane & 2) * 32 + (lane & 4) * 8 + (lane & 1) * 16;
        uint4* og = reinterpret_cast<uint4*>(p.out + (size_t)(rank * 512 + (hw - 1) * 256 + (lane & 2) * 4 + (lane >> 2)) * (2 * DM) +
                                             (chb & ~1) * 8 + (lane & 1) * 8);
        mbar_wait(bars + 8 * BAR_Q, 0);
        uint32_t tn = 0;
#pragma unroll 1
        for (int j = 0; j < 16; j++) {
          if (j == 1 && hw == 2) {
            mbar_wait(bars + 8 * (BAR_Y + 3), 0);
            send_y(2 * XT, 4 * XT, 1);
            fence_async_smem();
            __syncwarp();
            if (lane == 0) mbar_arrive(bars + 8 * BAR_XFREE);
            tn = (uint32_t)clock();
          }
          if (!(j & 7)) {
            mbar_wait(bars + 8 * (BAR_LAND + (j >> 3)), 0);
            tn = (uint32_t)clock() + (hw - 1) * (FPACE / 2);
            PROF2(33 + (j >> 1));
          }
#pragma unroll
          for (int i = 0; i < 2; i++) {
            uint32_t y[4];
            const uint4 q = lds128(qa + i * 512);
            ldsm4t(y, fa + (j & 6) * 64 + (fx ^ (i << 5) ^ ((j & 1) << 6) ^ ((j & 2) << 3)));
            while ((int)((uint32_t)clock() - tn) < 0) __nanosleep(50);
            tn += hw == 2 ? FPACE2 : FPACE;
            og[i * 16 * (2 * DM / 8)] = make_uint4(bmul2(q.x, y[0]), bmul2(q.y, y[1]), bmul2(q.z, y[2]), bmul2(q.w, y[3]));
          }
          qa += j == 7 ? OFF_Q1 - OFF_Q0 - 7168 : 1024;
          if (j == 7) fa += 2048;
          og += (j == 7 ? 1024 - 224 : 32) * (2 * DM / 8);
        }
        PROF(22);
      }
      }
      if (MODE != 1 && hw == 3) {
        const uint32_t epoch = ld_relaxed(g_flag_o + cta) + 1;
        if (MODE == 0) nb_sync(NB_G1END, 288);
        if (elect_one()) {
#pragma unroll
          for (int kb = 0; kb < 3; kb++)
            g2_issue_b(bars + 8 * (BAR_FULL2 + kb), kb || MODE ? STG2 : STG2 / 2, sb + g2_b(kb, 0), g2_k(kb) * 64, true);
        }
        __syncwarp();
        const __nv_bfloat16* osrc = g_o + (size_t)(rb2 >> 1) * 16 * 16384 + hsel * 8192;
        if (MODE == 0) __nanosleep(1500);
        const uint32_t* flag = g_flag_o + (rb2 >> 1) * 16 + g2_k(lane & 15);
        uint32_t ready = MODE == 0 ? 0u : ~0u;
        int s = 1, ph = 0;
#pragma unroll 1
        for (int kb = 2; kb < 16; kb++) {
          if (++s == NS2) { s = 0; ph ^= 1; }
          uint32_t fb = bars + 8 * (BAR_FULL2 + s), dst = sb + g2_a(s, hsel) + rank * 8192;
          const __nv_bfloat16* src = osrc + rank * 4096 + (uint32_t)g2_k(kb) * 16384;
          asm volatile("" : "+r"(fb), "+r"(dst), "+l"(src));
          if (!(ready >> kb & 1)) {
#pragma unroll 1
            for (int n = 0; n < SPIN_LIMIT && !(ready >> kb & 1); n++)
              ready = __ballot_sync(0xffffffffu, ld_acquire(flag) == epoch);
            fence_async_all();
          }
          if (kb == 2) PROF(21);
          if (MODE == 0 && kb == 4 && rank == 1) mbar_wait(bars + 8 * BAR_TAB, 0);
          mbar_wait(fb + 8 * (BAR_EMPTY2 - BAR_FULL2), ph);
          if (elect_one()) {
            asm volatile(
                "cp.async.bulk.shared::cluster.global.mbarrier::complete_tx::bytes.multicast::cluster [%0], [%1], %2, [%3], %4;\n"
                ::"r"(dst), "l"(src), "r"(8192), "r"(fb), "h"((uint16_t)3) : "memory");
          }
          __syncwarp();
        }
      }
    }
    cluster_sync_all();
    PROF_DUMP();
  } else {
    asm volatile("barrier.cluster.arrive.relaxed.aligned;\n" ::: "memory");
    asm volatile("setmaxnreg.inc.sync.aligned.u32 %0;\n" :: "n"(REG_MATH));
    if (halo_cta || MODE == 2) asm volatile("barrier.cluster.wait.aligned;\n" ::: "memory");
    if (warp == 0) PROF2(26);
    const int wg = warp >> 2;
    const int wtid = tid & 127;
    const bool signaller = (wtid == 0) || (wtid == 32);
    const uint32_t rbars = mapa(bars, wtid >> 5 & 1);

    if (halo_cta) {
      const uint32_t epoch = ld_relaxed(g_flag_o + 16 + blockIdx.x * 4) + 1;
      float acc0[64], acc1[64];
      int s = wg, ph = 0;
#pragma unroll 1
      for (int kb = 0; kb < 16; kb++) {
        mbar_wait(bars + 8 * (BAR_FULLB + s), ph);
        const uint32_t st = sb + s * STGH;
        const uint64_t da = mkdesc(st, 16, 1024, 1);
        const uint64_t db = mkdesc(st + 8192, 8192, 1024, 1);
        wg_fence();
#pragma unroll
        for (int kk = 0; kk < 4; kk++) {
          wgmma_n128(acc0, da + 2 * kk, db + 128 * kk, kb + kk);
          wgmma_n128(acc1, da + 2 * kk, db + 1024 + 128 * kk, kb + kk);
        }
        wg_commit();
        wg_wait<0>();
        if (kb == 15) PROF(37);
        if (wtid < 2) mbar_arrive(bars + 8 * (BAR_EMPTYB + s));
        if ((s += 2) >= NS1B) { s -= NS1B; ph ^= 1; }
      }
      fence_regs(acc0);
      fence_regs(acc1);
      if ((warp & 3) != 3) {
        auto put = [&](const float (&acc)[64], int hp0) {
#pragma unroll
          for (int n = 0; n < 4; n++) {
            uint32_t x[8];
#pragma unroll
            for (int c = 0; c < 8; c++) {
              x[c] = pack_bf16(acc[32 * (n >> 1) + 4 * c + 2 * (n & 1)], acc[32 * (n >> 1) + 4 * c + 2 * (n & 1) + 1]);
              if (wg) x[c] = movm(x[c]);
            }
            uint4* dst = g_halo + (((n & 1) * 4 + (warp & 3) + 1) * 16 + blockIdx.x * 4 + hp0 + (n >> 1)) * 192 + wg * 96 + lane;
            st_b128(dst, x[0], x[1], x[2], epoch);
            st_b128(dst + 32, x[3], x[4], x[5], epoch);
            st_b128(dst + 64, x[6], x[7], 0, epoch);
          }
        };
        put(acc0, 0);
        put(acc1, 2);
      }
      PROF(36);
      cluster_sync_all();
      return;
    }

    float acc[64];
    const uint32_t g2rel = wtid ? mapa(bars, rank) + 8 * BAR_EMPTY2B : mapa(bars, wg) + 8 * BAR_EMPTY2;
    uint32_t g2a = (uint32_t)mkdesc(sb + wg * 8192, 16, 0, 0), g2b = (uint32_t)mkdesc(sb, 8192, 0, 0);
    auto g2_block = [&](bool first, int s, int ph) {
      mbar_wait(bars + 8 * (BAR_FULL2 + s), ph);
      const uint32_t da = g2a + (g2_a(s, hsel) >> 4), db = g2b + (g2_b(s, rank) >> 4), dc = db + (g2_bk(s) >> 4);
      wg_fence();
      if (first) wgmma_n128z(acc, da, db);
      else wgmma_n128a(acc, da, db);
      wgmma_n128a(acc, da + 2, db + 128);
      wgmma_n128a(acc, da + 4, dc);
      wgmma_n128a(acc, da + 6, dc + 128);
      wg_commit();
    };
    if (MODE != 2) {
    uint32_t a1[2][4], sc[2];
    C2 t[2];
    {
      float acc0[96], acc1[96];
      int sa = 0, pha = 0;
      uint64_t db0 = mkdesc(sb + OFF_1B, 4096, 1024, 1);
      const uint64_t da0 = mkdesc(sb + wg * 16384, 16, 2048, 1);
      const bool sigb = wtid == 64;
      uint32_t rela = 0;
#pragma unroll 1
      for (int r = 0; r < 3; r++) {
#pragma unroll
        for (int i = 0; i < 2 * NS1B; i++) {
          const uint64_t da = da0 + sa * (STG1A >> 4) + (i & 1) * 4, db = db0 + (i % NS1B) * (STG1B >> 4);
          if (i || r) {
            if (!(i & 1)) mbar_wait(bars + 8 * (BAR_FULLA + sa), pha);
            mbar_wait(bars + 8 * (BAR_FULLB + i % NS1B), i / NS1B);
          } else {
            asm volatile("cp.async.wait_group 0;\n" ::: "memory");
            fence_async_smem();
            nb_sync(NB_FIRST, 256);
            PROF(0 + wg);
          }
          wg_fence();
          wgmma_n192(acc0, da + 64, db, i ? 1 : r);
          wgmma_n192(acc1, da, db, i ? 1 : r);
          wgmma_n192(acc0, da + 66, db + 128, 1);
          wgmma_n192(acc1, da + 2, db + 128, 1);
          wg_commit();
          wg_wait<1>();
          if (i || r) {
            if (sigb) mbar_arrive(bars + 8 * (BAR_EMPTYB + (i + NS1B - 1) % NS1B));
            if (!(i & 1) && signaller) mbar_arrive_cluster(rela);
          } else {
            asm volatile("barrier.cluster.wait.aligned;\n" ::: "memory");
          }
          if (i & 1) {
            rela = rbars + 8 * (BAR_EMPTYA + sa);
            if (++sa == NS1A) { sa = 0; pha ^= 1; }
          }
        }
        db0 += p.zero;
      }
      const int lr = lane & 7, lm = lane >> 3;
      const bool le0 = 2 * (lane & 3) <= (lane >> 2), le1 = 2 * (lane & 3) + 1 <= (lane >> 2);
      const uint32_t maskLE = (le0 ? 0x0000FFFFu : 0u) | (le1 ? 0xFFFF0000u : 0u);
      uint32_t q[4][8], k[5][8], vt[5][8];
      {
        static_assert(15 % NS1A == 0 && 30 % NS1B == 0, "slots of the last k blocks");
        asm volatile("ld.volatile.global.v4.u32 {%0,%1,%2,%3}, [%4];\n"
                     : "=r"(t[0].r), "=r"(t[1].r), "=r"(t[0].i), "=r"(t[1].i) : "l"(g_tab + 1536 + wtid * 4) : "memory");
        mbar_wait(bars + 8 * BAR_FULLA, 1);
        mbar_wait(bars + 8 * BAR_FULLB, 0);
        mbar_wait(bars + 8 * (BAR_FULLB + 1), 0);
        mbar_wait(bars + 8 * (BAR_EMPTYA + 1), 0);
        mbar_wait(bars + 8 * BAR_H, 0);
        const uint64_t da = mkdesc(sb + wg * 16384, 16, 2048, 1);
        const uint64_t db = mkdesc(sb + OFF_1B, 4096, 1024, 1);
        wg_fence();
#pragma unroll
        for (int i = 0; i < 4; i++) wgmma_n192(acc0, da + 64 + 2 * i, db + (i >> 1) * (STG1B >> 4) + (i & 1) * 128, 1);
        wg_commit();
#pragma unroll
        for (int i = 0; i < 2; i++) wgmma_n192(acc1, da + 2 * i, db + (i >> 1) * (STG1B >> 4) + (i & 1) * 128, 1);
        wg_commit();
        wg_wait<1>();
        fence_regs(acc0);
        PROFA(45, 0);
        attn_pack<8, 1, false>(acc0, k[4]);
        attn_pack<16, 1, true>(acc0, vt[4]);
        const uint32_t kh = sb + (warp == 7 ? OFF_OP + 7 * 4096 : OFF_KH + (warp + 1) * 2048) + lane * 16;
        sts128(kh, k[4][0], k[4][1], k[4][2], k[4][3]);
        sts128(kh + 512, k[4][4], k[4][5], k[4][6], k[4][7]);
#pragma unroll
        for (int i = 0; i < 4; i++) sts64(kh - lane * 8 + 1024 + 256 * i, vt[4][2 * i], vt[4][2 * i + 1]);
#pragma unroll
        for (int i = 2; i < 4; i++) wgmma_n192(acc1, da + 2 * i, db + (i >> 1) * (STG1B >> 4) + (i & 1) * 128, 1);
        wg_commit();
        attn_pack<0, 0, false>(acc0, q[1]);
        attn_pack<0, 1, false>(acc0, q[3]);
        attn_pack<8, 0, false>(acc0, k[2]);
        attn_pack<16, 0, true>(acc0, vt[2]);
        uint32_t z = p.zero;
#pragma unroll
        for (int i = 0; i < 8; i++) z &= q[1][i] & q[3][i];
#pragma unroll
        for (int i = 0; i < 8; i += 2) z &= k[2][i] & k[2][i + 1];
        __syncwarp();
        if (lane == 0) mbar_arrive(bars + 8 * BAR_STG + z);
        wg_wait<0>();
        fence_regs(acc1);
        if (MODE == 0) nb_arrive(NB_G1END, 288);
      }
      PROF(2 + wg);
      mbar_wait(bars + 8 * (warp == 0 ? BAR_HALO : BAR_STG), 0);
      {
        const uint32_t kh = sb + OFF_KH + warp * 2048 + lane * 16;
#pragma unroll
        for (int i = 0; i < 2; i++) {
          const uint4 t = lds128(kh + 512 * i);
          k[0][4 * i] = t.x; k[0][4 * i + 1] = t.y; k[0][4 * i + 2] = t.z; k[0][4 * i + 3] = t.w;
        }
#pragma unroll
        for (int i = 0; i < 4; i++) {
          const uint2 t = lds64(kh - lane * 8 + 1024 + 256 * i);
          vt[0][2 * i] = t.x; vt[0][2 * i + 1] = t.y;
        }
      }
      attn_pack<0, 0, false>(acc1, q[0]);
      attn_pack<0, 1, false>(acc1, q[2]);
      attn_pack<8, 0, false>(acc1, k[1]);
      attn_pack<8, 1, false>(acc1, k[3]);
      {
        float x[8][2];
        uint32_t pp[8];
        const bool first = warp == 0 && gidx == 0;
#pragma unroll
        for (int hd = 0; hd < 2; hd++) {
#pragma unroll
          for (int j = 0; j < 4; j += 2) {
            float s0[4], s1[4], s2[4];
            attn_qk(s2, q[j], q[j + 1], k[j + 2], 4 * hd);
            attn_qk(s1, q[j], q[j + 1], k[j + 1], 4 * hd);
            attn_qk(s0, q[j], q[j + 1], k[j], 4 * hd);
            if (j == 0 && first) s0[0] = s0[1] = -1e9f / 0.17677669529663687f;
            x[2 * j + hd][0] = le0 ? s1[0] : s0[0];
            x[2 * j + hd][1] = le1 ? s1[1] : s0[1];
            x[2 * j + 2 + hd][0] = le0 ? s2[2] : s1[2];
            x[2 * j + 2 + hd][1] = le1 ? s2[3] : s1[3];
          }
        }
        PROFA(40, __float_as_uint(x[1][0] + x[7][1]));
        attn_pack<16, 0, true>(acc1, vt[1]);
        attn_pack<16, 1, true>(acc1, vt[3]);
        quad_softmax<8>(x, pp);
        PROFA(41, pp[1] + pp[7]);
        ldsm4(a1[0], sb + OFF_T32 + (warp & 3) * 1024 + lane * 16);
        ldsm4(a1[1], sb + OFF_T32 + 512 + (warp & 3) * 1024 + lane * 16);
        const uint32_t obase = sb + OFF_OP + (warp * 32 + lr) * 128;
#pragma unroll
        for (int n = 0; n < 8; n++) {
          const uint32_t dst = obase + (n >> 1) * 1024 + (((4 * (n & 1) + lm) ^ lr) << 4);
          if (n & 2) attn_pv<true>(dst, vt[n >> 1], vt[(n >> 1) + 1], 4 * (n & 1), pp[n], maskLE);
          else attn_pv<false>(dst, vt[n >> 1], vt[(n >> 1) + 1], 4 * (n & 1), pp[n], maskLE);
        }
      }
      PROFA(42, 0);
    }

    {
      const int w = warp & 3;
      const int lr = lane & 7, lm = lane >> 3;
      const uint32_t xb = sb + OFF_X + wg * 4 * XT;
      auto uo = [](int c) { return (c & 1) * 2 * XT + (c >> 1) * 2048; };
      const uint64_t dc2 = mkdesc(sb + OFF_T16, 512, 128, 0), dc3 = mkdesc(sb + OFF_T16, 128, 512, 0);
      const uint64_t dc4 = mkdesc(sb + OFF_T32, 128, 256, 0);
      const uint64_t dx = mkdesc(xb, 4096, 512, 2), dz = mkdesc(xb, 4096, 256, 3);
      const uint32_t zs = xb + (w * 16 + (lm & 1) * 8 + lr) * 32 + (((lm >> 1) ^ (lr >> 2)) << 4);
      const uint32_t ys = xb + w * 4096 + (lm >> 1) * 256 + ((lr * 32 + (((lm & 1) ^ (lr >> 2)) << 4)) ^ (rank << 6) ^ ((w & 2) << 4));
      const bool own = (w & 1) == rank;
      const uint32_t ybar = mapa(bars, own ? rank ^ 1 : rank) + 8 * BAR_Y;
      uint32_t d[2][32], pa[2][4][2][4], e[4][4][8], ya[2][2][2][4], v[2][2][8];
      C2 s1[2][2][2];
      float o[2][16];
      auto rows = [&](int c) {
        fft_rows(d[c & 1], a1, dx + (uo(c) >> 4));
        wg_commit();
      };
      auto cols = [&](int c) {
        const int s = c & 1;
        fence_regs(d[s]);
#pragma unroll
        for (int i = 0; i < 16; i++) {
          const C2 z = crot(C2{d[s][2 * i], d[s][2 * i + 1]}, t[i & 1]);
          pa[s][i >> 2][i & 1][(i >> 1) & 1] = z.r;
          pa[s][i >> 2][i & 1][2 + ((i >> 1) & 1)] = z.i;
        }
        wg_fence();
#pragma unroll
        for (int i = 0; i < 4; i++) fft_cols<0>(e[c][i], pa[s][i], dc2);
        wg_commit();
      };
      auto prod = [&](int c, int n) {
        const int s = c & 1;
        fence_regs(e[c][2 * n]);
        fence_regs(e[c][2 * n + 1]);
#pragma unroll
        for (int j = 0; j < 2; j++) {
          const C2 u0 = cget(e[s][2 * n], j, 0), u1 = cget(e[s][2 * n], j, 1);
          const C2 h0 = cget(e[s][2 * n + 1], j, 0), h1 = cget(e[s][2 * n + 1], j, 1);
          C2 y0, y1;
          if (c < 2) {
            y0 = cmul(h0, u0);
            s1[s][n][j] = cfma(h0, u1, cmul(h1, u0));
            y1 = C2{hadd2(s1[s][n][j].r, y0.i), hadd2(s1[s][n][j].i, hneg2(y0.r))};
          } else {
            const C2 u2 = cget(e[c][2 * n], j, 0), u3 = cget(e[c][2 * n], j, 1);
            const C2 h2 = cget(e[c][2 * n + 1], j, 0), h3 = cget(e[c][2 * n + 1], j, 1);
            const C2 s2 = cfma(h0, u2, cfma(h2, u0, cmul(h1, u1)));
            y0 = C2{hadd2(s2.r, s1[s][n][j].i), hadd2(s2.i, hneg2(s1[s][n][j].r))};
            y1 = cfma(h0, u3, cfma(h1, u2, cfma(h2, u1, cfma(h3, u0, C2{s2.i, hneg2(s2.r)}))));
          }
          ya[s][n][j][0] = y0.r;
          ya[s][n][j][1] = y1.r;
          ya[s][n][j][2] = y0.i;
          ya[s][n][j][3] = y1.i;
        }
      };
      auto icols = [&](int c) {
        wg_fence();
        fft_cols<1>(v[c & 1][0], ya[c & 1][0], dc3);
        fft_cols<1>(v[c & 1][1], ya[c & 1][1], dc3);
        wg_commit();
      };
      auto stage = [&](int c) {
        const int s = c & 1;
        fence_regs(v[s][0]);
        fence_regs(v[s][1]);
#pragma unroll
        for (int b = 0; b < 4; b++) {
          const C2 x0 = cget(v[s][b >> 1], 0, b & 1), x1 = cget(v[s][b >> 1], 1, b & 1);
          const C2 z0 = crot(C2{x0.i, x0.r}, t[0]), z1 = crot(C2{x1.i, x1.r}, t[1]);
          stsm4(zs + uo(c) + b * 4096, z0.i, z0.r, z1.i, z1.r);
        }
      };
      auto back = [&](int c) {
        fft_back(o[c & 1], dz + (uo(c) >> 4), dc4);
        wg_commit();
      };
      auto out = [&](int c) {
        float (&r)[16] = o[c & 1];
        fence_regs(r);
#pragma unroll
        for (int i = 0; i < 16; i += 8)
          stsm4t(ys + uo(c) + 64 * i, bmul2(pack_bf16(r[i], r[i + 1]), sc[c & 1]), bmul2(pack_bf16(r[i + 2], r[i + 3]), sc[c & 1]),
                 bmul2(pack_bf16(r[i + 4], r[i + 5]), sc[c & 1]), bmul2(pack_bf16(r[i + 6], r[i + 7]), sc[c & 1]));
      };
      auto signal = [&](int yb, int land) {
        __syncwarp();
        if (lane == 0) {
          mbar_arrive_cluster(ybar + 8 * yb);
          if (own && land >= 0) mbar_arrive(bars + 8 * (BAR_LAND + land));
        }
      };
      mbar_wait(bars + 8 * BAR_X, 0);
      wg_fence();
      rows(0);
      rows(1);
      fence_async_smem();
      nb_arrive(NB_OREADY, 288);
#pragma unroll
      for (int i = 0; i < 2; i++) {
        const uint32_t ex = sb + OFF_EX + wg * 16 + (w & 2) * 2 + 8 * i;
        sc[i] = min(max(381 - (int)lds32(ex) - (int)lds32(ex + 32), 1), 254) * 0x00800080u;
      }
      PROF(34 + wg);
      wg_wait<1>();
      cols(0);
      wg_wait<1>();
      cols(1);
      rows(2);
      nb_sync(NB_CONV + wg, 128);
      wg_wait<2>();
      prod(0, 0);
      prod(0, 1);
      icols(0);
      wg_wait<2>();
      prod(1, 0);
      prod(1, 1);
      icols(1);
      PROF3(40 + 10 * wg);
      wg_wait<1>();
      stage(0);
      wg_wait<0>();
      stage(1);
      fence_async_smem();
      cols(2);
      PROF3(41 + 10 * wg);
      nb_sync(NB_CONV + wg, 128);
      back(0);
      back(1);
      wg_wait<2>();
      prod(2, 0);
      wg_fence();
      rows(3);
      wg_wait<1>();
      out(0);
      out(1);
      signal(wg, 0);
      PROF3(42 + 10 * wg);
      prod(2, 1);
      icols(2);
      wg_wait<1>();
      cols(3);
      PROF3(43 + 10 * wg);
      wg_wait<1>();
      stage(2);
      fence_async_smem();
      wg_wait<0>();
      prod(3, 0);
      nb_sync(NB_CONV + wg, 128);
      wg_fence();
      back(2);
      prod(3, 1);
      icols(3);
      PROF3(44 + 10 * wg);
      wg_wait<1>();
      out(2);
      signal(2, -1);
      wg_wait<0>();
      stage(3);
      PROF3(45 + 10 * wg);
      fence_async_smem();
      nb_sync(NB_CONV + wg, 128);
      wg_fence();
      back(3);
      constexpr int G = MODE == 0;
      if (G) {
        mbar_wait(bars + 8 * (BAR_EMPTY2 + 4), 0);
        g2_block(true, 0, 0);
      }
      wg_wait<G>();
      if (lane == 0) mbar_arrive_cluster(mapa(bars, 1) + 8 * BAR_TAB);
      out(3);
      signal(3, 1);
      PROF(6 + wg);
    }
    }

    if (MODE != 1) {
      if (MODE == 2) g2_block(true, 0, 0);
      const int lr = lane & 7, lm = lane >> 3;
      const uint32_t wb = sb + g2_a(1, 0) + warp * 2048;
      const int orow = (rb2 & 7) * 128 + warp * 16;
      uint4* og = reinterpret_cast<uint4*>(p.out + (size_t)(2 * (orow + lm) + (rb2 >> 3)) * (2 * DM) + DM + cb2 * 128 + lr * 8);
      uint32_t wst = wb + (lr + 8 * (lm & 1)) * 128, wsx = ((lm >> 1) ^ lr) << 4, wld = wb + lm * 128, wlx = (lr ^ lm) << 4;
      asm volatile("" : "+l"(og), "+r"(wst), "+r"(wsx), "+r"(wld), "+r"(wlx));
#pragma unroll 1
      for (int r = 0; r < 3; r++) {
        const bool hold = r == 2 && wg != LEADWG;
        if (hold) {
          wg_wait<0>();
          if (signaller) mbar_arrive_cluster(g2rel);
          nb_sync(NB_LEAD, 256);
        }
#pragma unroll
        for (int i = 1; i <= NS2; i++) {
          g2_block(false, i % NS2, (r & 1) ^ (i == NS2));
          if (warp == LEADWG * 4) PROF2(40 + 5 * r + i);
          if (i == 1 ? !hold : r < 2) {
            wg_wait<1>();
            if (signaller) mbar_arrive_cluster(g2rel + 8 * (i - 1));
          }
        }
        if (r == 0) PROF(8 + wg);
        g2a += p.zero;
        g2b += p.zero;
      }
      if (wg == LEADWG) nb_arrive(NB_LEAD, 256);
      asm volatile("barrier.cluster.arrive.relaxed.aligned;\n" ::: "memory");
      wg_wait<0>();
      fence_regs(acc);
      PROF(10 + wg);
#pragma unroll
      for (int h = 0; h < 2; h++) {
        const uint32_t b = h * (g2_a(3, 0) - g2_a(1, 0));
#pragma unroll
        for (int j = 8 * h; j < 8 * h + 8; j += 2)
          stsm4(wst + b + (wsx ^ ((j & 7) << 4)), pack_bf16(acc[4 * j], acc[4 * j + 1]),
                pack_bf16(acc[4 * j + 2], acc[4 * j + 3]), pack_bf16(acc[4 * j + 4], acc[4 * j + 5]),
                pack_bf16(acc[4 * j + 6], acc[4 * j + 7]));
        if (wg == LEADWG) {
          fence_async_smem();
          __syncwarp();
          if (elect_one()) {
            tma_store_3d(&tmOb, wb + b, DM + cb2 * 128 + h * 64, rb2 >> 3, orow);
            bulk_commit();
          }
        } else {
          __syncwarp();
          uint4 v[4];
#pragma unroll
          for (int i = 0; i < 4; i++) v[i] = lds128(wld + b + i * 512 + (wlx ^ ((i & 1) << 6)));
#pragma unroll
          for (int i = 0; i < 4; i++)
            asm volatile("st.global.v4.u32 [%0], {%1,%2,%3,%4};\n" ::"l"(og + i * 8 * (2 * DM / 8) + h * 8), "r"(v[i].x),
                         "r"(v[i].y), "r"(v[i].z), "r"(v[i].w) : "memory");
        }
      }
      PROF(12 + wg);
      bulk_wait0();
    } else {
      asm volatile("barrier.cluster.arrive.relaxed.aligned;\n" ::: "memory");
    }
    asm volatile("barrier.cluster.wait.aligned;\n" ::: "memory");
  }
}

typedef CUresult (*EncodeFn)(CUtensorMap*, CUtensorMapDataType, cuuint32_t, void*, const cuuint64_t*, const cuuint64_t*,
                             const cuuint32_t*, const cuuint32_t*, CUtensorMapInterleave, CUtensorMapSwizzle,
                             CUtensorMapL2promotion, CUtensorMapFloatOOBfill);

void make_map(EncodeFn enc, CUtensorMap* tm, const void* base, int rank, const cuuint64_t* dims, const cuuint64_t* strides,
              const cuuint32_t* box, CUtensorMapSwizzle swz) {
  cuuint32_t es[5] = {1, 1, 1, 1, 1};
  enc(tm, CU_TENSOR_MAP_DATA_TYPE_BFLOAT16, rank, const_cast<void*>(base), dims, strides, box, es,
      CU_TENSOR_MAP_INTERLEAVE_NONE, swz, CU_TENSOR_MAP_L2_PROMOTION_L2_256B, CU_TENSOR_MAP_FLOAT_OOB_FILL_NONE);
}

}

extern "C" void kernel_launch(void* const* d_in, const int* in_sizes, int n_in, void* d_out, int out_size) {
  static EncodeFn enc = nullptr;
  static bool coresident = true;
  if (!enc) {
    void* fn = nullptr;
    cudaDriverEntryPointQueryResult qr;
    cudaGetDriverEntryPoint("cuTensorMapEncodeTiled", &fn, cudaEnableDefault, &qr);
    enc = (EncodeFn)fn;
    cudaFuncSetAttribute(fused_kernel<0>, cudaFuncAttributeMaxDynamicSharedMemorySize, SMEM_BYTES);
    cudaFuncSetAttribute(fused_kernel<1>, cudaFuncAttributeMaxDynamicSharedMemorySize, SMEM_BYTES);
    cudaFuncSetAttribute(fused_kernel<2>, cudaFuncAttributeMaxDynamicSharedMemorySize, SMEM_BYTES);
    cudaLaunchConfig_t cfg = {};
    cfg.gridDim = dim3(NCTA);
    cfg.blockDim = dim3(NTHREADS);
    cfg.dynamicSmemBytes = SMEM_BYTES;
    cudaLaunchAttribute at;
    at.id = cudaLaunchAttributeClusterDimension;
    at.val.clusterDim.x = 2;
    at.val.clusterDim.y = 1;
    at.val.clusterDim.z = 1;
    cfg.attrs = &at;
    cfg.numAttrs = 1;
    int nclusters = 0;
    if (cudaOccupancyMaxActiveClusters(&nclusters, fused_kernel<0>, &cfg) == cudaSuccess) coresident = nclusters >= NCTA / 2;
    (void)cudaGetLastError();
  }
  CUtensorMap tmX, tmW, tmWo, tmWp, tmQ, tmOb, tmXh, tmWh;
  {
    cuuint64_t dims[3] = {1024, 2, 1024};
    cuuint64_t str[2] = {2048, 4096};
    cuuint32_t box[3] = {64, 1, 128};
    make_map(enc, &tmX, d_in[6], 3, dims, str, box, CU_TENSOR_MAP_SWIZZLE_128B);
  }
  {
    cuuint64_t dims[3] = {1024, 1024, 3};
    cuuint64_t str[2] = {6144, 2048};
    cuuint32_t box[3] = {64, 32, 3};
    make_map(enc, &tmW, d_in[7], 3, dims, str, box, CU_TENSOR_MAP_SWIZZLE_128B);
  }
  {
    cuuint64_t dims[3] = {64, 1024, 16};
    cuuint64_t str[2] = {2048, 128};
    cuuint32_t box[3] = {64, 64, 2};
    cuuint32_t piece[3] = {64, 32, 1};
    make_map(enc, &tmWo, d_in[8], 3, dims, str, box, CU_TENSOR_MAP_SWIZZLE_128B);
    make_map(enc, &tmWp, d_in[8], 3, dims, str, piece, CU_TENSOR_MAP_SWIZZLE_128B);
  }
  {
    cuuint64_t dims[5] = {1024, 2, 2, 4, 128};
    cuuint64_t str[4] = {2048, 8 * 2048, 2 * 2048, 16 * 2048};
    cuuint32_t box[5] = {16, 2, 2, 4, 32};
    make_map(enc, &tmQ, d_in[0], 5, dims, str, box, CU_TENSOR_MAP_SWIZZLE_NONE);
  }
  {
    cuuint64_t dims[3] = {2048, 2, 1024};
    cuuint64_t str[2] = {4096, 8192};
    cuuint32_t box[3] = {64, 1, 16};
    make_map(enc, &tmOb, d_out, 3, dims, str, box, CU_TENSOR_MAP_SWIZZLE_128B);
  }
  {
    cuuint64_t dims[4] = {1024, 256, 2, 4};
    cuuint64_t str[3] = {4096, 2048, 256 * 4096};
    cuuint32_t box[4] = {64, 8, 2, 3};
    make_map(enc, &tmXh, d_in[6], 4, dims, str, box, CU_TENSOR_MAP_SWIZZLE_128B);
  }
  {
    cuuint64_t dims[3] = {64, 1024, 48};
    cuuint64_t str[2] = {6144, 128};
    cuuint32_t box[3] = {64, 64, 4};
    make_map(enc, &tmWh, d_in[7], 3, dims, str, box, CU_TENSOR_MAP_SWIZZLE_128B);
  }
  Params p;
  p.q = (const __nv_bfloat16*)d_in[0];
  p.k = (const __nv_bfloat16*)d_in[1];
  p.v = (const __nv_bfloat16*)d_in[2];
  p.shift_k = (const __nv_bfloat16*)d_in[3];
  p.ssm_k = (const __nv_bfloat16*)d_in[4];
  p.ssm_D = (const __nv_bfloat16*)d_in[5];
  p.x = (const __nv_bfloat16*)d_in[6];
  p.w = (const __nv_bfloat16*)d_in[7];
  p.wo = (const __nv_bfloat16*)d_in[8];
  p.out = (__nv_bfloat16*)d_out;
  p.zero = 0;
  if (coresident) {
    fused_kernel<0><<<NCTA, NTHREADS, SMEM_BYTES>>>(p, tmX, tmW, tmWo, tmWp, tmQ, tmOb, tmXh, tmWh);
  } else {
    fused_kernel<0><<<4, NTHREADS, SMEM_BYTES>>>(p, tmX, tmW, tmWo, tmWp, tmQ, tmOb, tmXh, tmWh);
    fused_kernel<1><<<NCTA, NTHREADS, SMEM_BYTES>>>(p, tmX, tmW, tmWo, tmWp, tmQ, tmOb, tmXh, tmWh);
    fused_kernel<2><<<NCTA, NTHREADS, SMEM_BYTES>>>(p, tmX, tmW, tmWo, tmWp, tmQ, tmOb, tmXh, tmWh);
  }
}
```

```cpp
#include <cuda_runtime.h>
#include <cuda.h>
#include <cuda_bf16.h>
#include <stdint.h>

namespace {

constexpr int SEQ = 2048;
constexpr int DM = 1024;
constexpr int NCTA = 132;
constexpr int NTHREADS = 384;

constexpr int STG1A = 32768;
constexpr int NS1A = 3;
constexpr int STG1B = 12288;
constexpr int NS1B = 5;
constexpr int OFF_1B = NS1A * STG1A;
constexpr int STG2 = 32768;
constexpr int NS2 = 5;
#define PSTEP 1250
#define FPACE 260
#define FPACE2 230
#define SIG2 0
constexpr int LEADWG = 1;
__device__ __forceinline__ uint32_t g2_a(int s, int hsel) { return (((0x97524 >> (4 * s)) & 15) ^ (s & 5 ? 0 : hsel)) << 14; }
constexpr int OFF_Q0 = 3 << 14, OFF_Q1 = 8 << 14;
constexpr int STGH = 40960;
constexpr int OFF_KH = 1 * STG2;
constexpr int OFF_OP = 2 * STG2;
constexpr int OFF_T32 = 5 * STG2 - 4096;
constexpr int OFF_X = 5 * STG2;
constexpr int XT = 8192;
__device__ __forceinline__ uint32_t g2_b(int s, int rank) {
  return s < 3 ? (s == 2 ? 6 : s) << 14 : OFF_X + (s - 3) * 2 * XT + (rank ^ 1) * 4096;
}
__device__ __forceinline__ uint32_t g2_bk(int s) { return s < 3 ? 4096 : 4 * XT; }
constexpr int OFF_BAR = OFF_X + 8 * XT;
constexpr int OFF_EX = OFF_BAR + 960;
constexpr int OFF_T16 = 230400;
constexpr int SMEM_BYTES = OFF_T16 + 2048;
static_assert(OFF_1B + NS1B * STG1B <= OFF_T32 && OFF_X % 1024 == 0, "layout");
static_assert(NS1B * STGH <= OFF_BAR && OFF_EX + 64 <= OFF_T16 && SMEM_BYTES <= 232448, "smem");

constexpr int BAR_FULLA = 0;
constexpr int BAR_EMPTYA = 3;
constexpr int BAR_FULLB = 6;
constexpr int BAR_EMPTYB = 11;
constexpr int BAR_FULL2 = 16;
constexpr int BAR_EMPTY2 = 21;
constexpr int BAR_EMPTY2B = 44;
constexpr int BAR_X = 26;
constexpr int BAR_LAND = 42;
constexpr int BAR_TAB = 28;
constexpr int BAR_U = 29;
constexpr int BAR_H = 30;
constexpr int BAR_STG = 31;
constexpr int BAR_Y = 32;
constexpr int BAR_XFREE = 38;
constexpr int BAR_KH = 49;
constexpr int BAR_Q = 41;

constexpr int NB_LEAD = 2;
constexpr int NB_G1END = 3;
constexpr int NB_OREADY = 4;
constexpr int NB_CONV = 5;
constexpr int NB_HELP3 = 11;
constexpr int NB_FIRST = 13;

#define REG_MATH 224
#define REG_HELP 56
constexpr int SPIN_LIMIT = 1 << 20;

__device__ __align__(1024) __nv_bfloat16 g_o[SEQ * DM];
constexpr int FS = 2;
__device__ __align__(128) uint32_t g_flag_o[128 * FS];
__device__ uint4 g_halo[128 * 192];
__device__ __align__(128) const uint32_t g_tab[2048] = {
  0x2fd93000,0x2ea72f64,0x2c722da8,0x263e2a1f,0x2ea73000,0xa63e2a1f,0xafd9ada8,0xac72af64,0x2c723000,0xafd9aa1f,0x263eada8,0x2ea72f64,
  0x263e3000,0xac72af64,0x2ea72da8,0xafd9aa1f,0xa63e3000,0x2c72af64,0xaea72da8,0x2fd9aa1f,0xac723000,0x2fd9aa1f,0xa63eada8,0xaea72f64,
  0xaea73000,0x263e2a1f,0x2fd9ada8,0x2c72af64,0xafd93000,0xaea72f64,0xac722da8,0xa63e2a1f,0x263e0000,0x2c722a1f,0x2ea72da8,0x2fd92f64,
  0x2c720000,0x2fd92f64,0x263e2da8,0xaea7aa1f,0x2ea70000,0x263e2f64,0xafd9ada8,0x2c72aa1f,0x2fd90000,0xaea72a1f,0x2c72ada8,0xa63e2f64,
  0x2fd90000,0xaea7aa1f,0x2c722da8,0xa63eaf64,0x2ea70000,0x263eaf64,0xafd92da8,0x2c722a1f,0x2c720000,0x2fd9af64,0x263eada8,0xaea72a1f,
  0x263e0000,0x2c72aa1f,0x2ea7ada8,0x2fd9af64,0xafd93000,0xaea72f64,0xac722da8,0xa63e2a1f,0xaea73000,0x263e2a1f,0x2fd9ada8,0x2c72af64,
  0xac723000,0x2fd9aa1f,0xa63eada8,0xaea72f64,0xa63e3000,0x2c72af64,0xaea72da8,0x2fd9aa1f,0x263e3000,0xac72af64,0x2ea72da8,0xafd9aa1f,
  0x2c723000,0xafd9aa1f,0x263eada8,0x2ea72f64,0x2ea73000,0xa63e2a1f,0xafd9ada8,0xac72af64,0x2fd93000,0x2ea72f64,0x2c722da8,0x263e2a1f,
  0xa63e0000,0xac722a1f,0xaea72da8,0xafd92f64,0xac720000,0xafd92f64,0xa63e2da8,0x2ea7aa1f,0xaea70000,0xa63e2f64,0x2fd9ada8,0xac72aa1f,
  0xafd90000,0x2ea72a1f,0xac72ada8,0x263e2f64,0xafd90000,0x2ea7aa1f,0xac722da8,0x263eaf64,0xaea70000,0xa63eaf64,0x2fd92da8,0xac722a1f,
  0xac720000,0xafd9af64,0xa63eada8,0x2ea72a1f,0xa63e0000,0xac72aa1f,0xaea7ada8,0xafd9af64,0xa63e0000,0xac72aa1f,0xaea7ada8,0xafd9af64,
  0xac720000,0xafd9af64,0xa63eada8,0x2ea72a1f,0xaea70000,0xa63eaf64,0x2fd92da8,0xac722a1f,0xafd90000,0x2ea7aa1f,0xac722da8,0x263eaf64,
  0xafd90000,0x2ea72a1f,0xac72ada8,0x263e2f64,0xaea70000,0xa63e2f64,0x2fd9ada8,0xac72aa1f,0xac720000,0xafd92f64,0xa63e2da8,0x2ea7aa1f,
  0xa63e0000,0xac722a1f,0xaea72da8,0xafd92f64,0x2fd93000,0x2ea72f64,0x2c722da8,0x263e2a1f,0x2ea73000,0xa63e2a1f,0xafd9ada8,0xac72af64,
  0x2c723000,0xafd9aa1f,0x263eada8,0x2ea72f64,0x263e3000,0xac72af64,0x2ea72da8,0xafd9aa1f,0xa63e3000,0x2c72af64,0xaea72da8,0x2fd9aa1f,
  0xac723000,0x2fd9aa1f,0xa63eada8,0xaea72f64,0xaea73000,0x263e2a1f,0x2fd9ada8,0x2c72af64,0xafd93000,0xaea72f64,0xac722da8,0xa63e2a1f,
  0x263e0000,0x2c72aa1f,0x2ea7ada8,0x2fd9af64,0x2c720000,0x2fd9af64,0x263eada8,0xaea72a1f,0x2ea70000,0x263eaf64,0xafd92da8,0x2c722a1f,
  0x2fd90000,0xaea7aa1f,0x2c722da8,0xa63eaf64,0x2fd90000,0xaea72a1f,0x2c72ada8,0xa63e2f64,0x2ea70000,0x263e2f64,0xafd9ada8,0x2c72aa1f,
  0x2c720000,0x2fd92f64,0x263e2da8,0xaea7aa1f,0x263e0000,0x2c722a1f,0x2ea72da8,0x2fd92f64,0xafd93000,0xaea72f64,0xac722da8,0xa63e2a1f,
  0xaea73000,0x263e2a1f,0x2fd9ada8,0x2c72af64,0xac723000,0x2fd9aa1f,0xa63eada8,0xaea72f64,0xa63e3000,0x2c72af64,0xaea72da8,0x2fd9aa1f,
  0x263e3000,0xac72af64,0x2ea72da8,0xafd9aa1f,0x2c723000,0xafd9aa1f,0x263eada8,0x2ea72f64,0x2ea73000,0xa63e2a1f,0xafd9ada8,0xac72af64,
  0x2fd93000,0x2ea72f64,0x2c722da8,0x263e2a1f,0xa63e0000,0xac72aa1f,0xaea7ada8,0xafd9af64,0x2c720000,0x2fd92f64,0x263e2da8,0xaea7aa1f,
  0xaea70000,0xa63eaf64,0x2fd92da8,0xac722a1f,0x2fd90000,0xaea72a1f,0x2c72ada8,0xa63e2f64,0xafd90000,0x2ea72a1f,0xac72ada8,0x263e2f64,
  0x2ea70000,0x263eaf64,0xafd92da8,0x2c722a1f,0xac720000,0xafd92f64,0xa63e2da8,0x2ea7aa1f,0x263e0000,0x2c72aa1f,0x2ea7ada8,0x2fd9af64,
  0x2fd93000,0x2ea72f64,0x2c722da8,0x263e2a1f,0xaea7b000,0x263eaa1f,0x2fd92da8,0x2c722f64,0x2c723000,0xafd9aa1f,0x263eada8,0x2ea72f64,
  0xa63eb000,0x2c722f64,0xaea7ada8,0x2fd92a1f,0xa63e3000,0x2c72af64,0xaea72da8,0x2fd9aa1f,0x2c72b000,0xafd92a1f,0x263e2da8,0x2ea7af64,
  0xaea73000,0x263e2a1f,0x2fd9ada8,0x2c72af64,0x2fd9b000,0x2ea7af64,0x2c72ada8,0x263eaa1f,0x263e0000,0x2c72aa1f,0x2ea7ada8,0x2fd9af64,
  0xac720000,0xafd92f64,0xa63e2da8,0x2ea7aa1f,0x2ea70000,0x263eaf64,0xafd92da8,0x2c722a1f,0xafd90000,0x2ea72a1f,0xac72ada8,0x263e2f64,
  0x2fd90000,0xaea72a1f,0x2c72ada8,0xa63e2f64,0xaea70000,0xa63eaf64,0x2fd92da8,0xac722a1f,0x2c720000,0x2fd92f64,0x263e2da8,0xaea7aa1f,
  0xa63e0000,0xac72aa1f,0xaea7ada8,0xafd9af64,0xafd93000,0xaea72f64,0xac722da8,0xa63e2a1f,0x2ea7b000,0xa63eaa1f,0xafd92da8,0xac722f64,
  0xac723000,0x2fd9aa1f,0xa63eada8,0xaea72f64,0x263eb000,0xac722f64,0x2ea7ada8,0xafd92a1f,0x263e3000,0xac72af64,0x2ea72da8,0xafd9aa1f,
  0xac72b000,0x2fd92a1f,0xa63e2da8,0xaea7af64,0x2ea73000,0xa63e2a1f,0xafd9ada8,0xac72af64,0xafd9b000,0xaea7af64,0xac72ada8,0xa63eaa1f,
  0xafd9b000,0xaea7af64,0xac72ada8,0xa63eaa1f,0x2ea73000,0xa63e2a1f,0xafd9ada8,0xac72af64,0xac72b000,0x2fd92a1f,0xa63e2da8,0xaea7af64,
  0x263e3000,0xac72af64,0x2ea72da8,0xafd9aa1f,0x263eb000,0xac722f64,0x2ea7ada8,0xafd92a1f,0xac723000,0x2fd9aa1f,0xa63eada8,0xaea72f64,
  0x2ea7b000,0xa63eaa1f,0xafd92da8,0xac722f64,0xafd93000,0xaea72f64,0xac722da8,0xa63e2a1f,0xa63e0000,0xac72aa1f,0xaea7ada8,0xafd9af64,
  0x2c720000,0x2fd92f64,0x263e2da8,0xaea7aa1f,0xaea70000,0xa63eaf64,0x2fd92da8,0xac722a1f,0x2fd90000,0xaea72a1f,0x2c72ada8,0xa63e2f64,
  0xafd90000,0x2ea72a1f,0xac72ada8,0x263e2f64,0x2ea70000,0x263eaf64,0xafd92da8,0x2c722a1f,0xac720000,0xafd92f64,0xa63e2da8,0x2ea7aa1f,
  0x263e0000,0x2c72aa1f,0x2ea7ada8,0x2fd9af64,0x2fd9b000,0x2ea7af64,0x2c72ada8,0x263eaa1f,0xaea73000,0x263e2a1f,0x2fd9ada8,0x2c72af64,
  0x2c72b000,0xafd92a1f,0x263e2da8,0x2ea7af64,0xa63e3000,0x2c72af64,0xaea72da8,0x2fd9aa1f,0xa63eb000,0x2c722f64,0xaea7ada8,0x2fd92a1f,
  0x2c723000,0xafd9aa1f,0x263eada8,0x2ea72f64,0xaea7b000,0x263eaa1f,0x2fd92da8,0x2c722f64,0x2fd93000,0x2ea72f64,0x2c722da8,0x263e2a1f,
  0x263e0000,0x2c72aa1f,0x2ea7ada8,0x2fd9af64,0xac720000,0xafd92f64,0xa63e2da8,0x2ea7aa1f,0x2ea70000,0x263eaf64,0xafd92da8,0x2c722a1f,
  0xafd90000,0x2ea72a1f,0xac72ada8,0x263e2f64,0x2fd90000,0xaea72a1f,0x2c72ada8,0xa63e2f64,0xaea70000,0xa63eaf64,0x2fd92da8,0xac722a1f,
  0x2c720000,0x2fd92f64,0x263e2da8,0xaea7aa1f,0xa63e0000,0xac72aa1f,0xaea7ada8,0xafd9af64,0x316c2fbd,0x343e32f7,0x35bc34ff,0x372c3676,
  0x371532c6,0x3a81392e,0x3bef3b71,0x3b7c3bf2,0x397034cf,0x3bfc3b6c,0x38b23b04,0xb40e31e8,0x3ae13631,0x39e73bf5,0xb6e83219,0xbbe8bb13,
  0x3bc23785,0x30be3aa9,0xbbfdb911,0x2a16b9aa,0x3bfe3865,0xb80f37a6,0xb82abc00,0x3bfd376f,0x3b9238fd,0xbb7f2311,0x3805b929,0x31223bde,
  0x3a85398b,0xbb96b742,0x3bff319e,0xbbb82f8b,0xbbe2bbf1,0xbbb7bbcf,0xbb78bb9a,0xbb27bb52,0xbb2cbbd2,0xb8a8ba19,0xb029b5df,0x35a52f59,
  0xb9dfbba1,0x2ba7b5f7,0x3a7a37b2,0x3bbd3bdd,0xb815bb60,0x39662e91,0x3b373bda,0xb0d7377a,0xb3d3bb10,0x3be9386f,0x2a7a3a31,0xbbfeb9a6,
  0x294dbab0,0x3ae53b07,0xbad51fdb,0xab43bb16,0x352fba41,0x35993c00,0xbaebba1d,0x3be531cf,0x38a3b9c5,0xb5173b21,0x2776bbe0,0x34323bf2,
  0x384537dd,0x38ea3899,0x39823937,0x3a0d39c9,0x39463a93,0x3340374e,0xb426a452,0xb979b7c8,0xbb45b924,0xbb32bc00,0xb371b902,0x38d63294,
  0xb08db9a1,0x3b3f379b,0x39583bd7,0xb8252dfb,0x3bea3a2d,0xb3ba3874,0xbb89bb0d,0x36d2b625,0xb6bb387f,0xb8d1bbf5,0x3be73602,0xb546391f,
  0xba00bb01,0x3bff35eb,0xba5c34db,0x3359bab6,0x3ac7b66b,0xb9413933,0x368dbabd,0xb0103bb3,0xbac4baf7,0xba50ba8c,0xb9cdba11,0xb93cb986,
  0x3a04388e,0x3bcb3b1e,0x3bba3c00,0x39d63afe,0x36af3a21,0xb6ffa17f,0xbbc8ba3d,0xba60bbd4,0xbbebb9af,0xb6c6bb0a,0x39f43263,0x3ad83bf7,
  0x30a6b916,0x3bc33aa5,0xb55e3790,0xbb3dbb63,0x3b423a9e,0xba642ec3,0xb0f0bb6a,0x3b8e3a25,0xb94a37bd,0x2884bb6f,0x38db3b9f,0xbbc9b85a,
  0xb840bb54,0x3a093a15,0xbb4cb850,0x3bef3457,0x3a893a4d,0x3af43ac1,0x3b4f3b24,0x3b983b76,0xbb94baba,0xbbe4bbf9,0xba58bb57,0xb699b8f8,
  0x3bfe3b18,0x394f3b5c,0xb109347b,0xbae8b884,0xbbc0bb68,0xa9b1b90c,0x3b8b387a,0x38bc3ba5,0x3ade3ba7,0xb8c1324b,0xb9f0bbf6,0x39eb9648,
  0xb96bbbd6,0x3bbf3487,0xb38939b3,0xb9f8bba3,0x370a3bf3,0xbb47b994,0x3bbc2d65,0xb8ad3889,0xb153bc00,0x37213b9c,0xb97dba90,0x3af138f3,
  0xb89eb8ee,0xb7e8b84a,0xb682b737,0xb50bb5c8,0x35233855,0xb13b2d33,0xb8e0b65f,0xbb4aba45,0xa8e8b764,0x39fc3648,0x3be63bae,0x380a3a9b,
  0xb3eb360e,0xbbfeba35,0xb552baa2,0x3a7334b7,0x381ab4ab,0x3a6f3bd8,0xb95d2e5f,0xb962bc00,0xb9e3327c,0xb402bbac,0x3bc6399d,0xb95434c3,
  0x3b2faf27,0xb6a439bc,0xb41abbf9,0x3a7e3a97,0xbbe3251b,0x3b2ab4f3,0xb9d23894,0x37f3ba49,0x3bce3bb5,0x3bf03be1,0x3bff3bfa,0x3bfb3bff,
  0x2c38b1b6,0x383a34e7,0x3aee39c0,0x3bff3bb2,0xbb81bbf8,0xb53ab999,0x38302ef5,0x3bed3ab3,0xb8cc9cb6,0xbb85bbab,0x2adeb86a,0x3bc5391b,
  0x38c73bf6,0xbadbb232,0xb6ddbba9,0x3b87361a,0x3b833201,0xb0743a39,0xba76bb5e,0x3b352dc9,0xac06bbb0,0x39743b59,0xbbeeb759,0x3aceb2ad,
  0xbbccb5d4,0x3bfb2d00,0xbb7a32de,0x3a54b7d2,0xb30fb44b,0xafefb185,0xa6adacce,0x2c9c25e4,0xbbfcbbdf,0xbacbbb9e,0xb7feb990,0xa81fb463,
  0xb58d2d97,0xbb90b9b8,0xbad1bbf4,0xb05bb85f,0x3a673c00,0xb5763493,0xbbfdbaac,0xb3a2ba29,0x3a6b2e2d,0x38203bd9,0xbb3ab49f,0xb56abb65,
  0xb581bbdc,0x3bec3907,0xb8b7363c,0xb6f4bbf8,0xbbfcb46f,0x39dab654,0xb0423b1b,0xb835bbd3,0xb3283b73,0xac6abbfa,0x35b13bd0,0xb8e5bafb,
  0x38ee3a0d,0xb84aba89,0x37373af4,0xb5c8bb4f,0x35df3a81,0x2f59bbef,0xb88e3b7c,0x3b1eb946,0x2d973ae8,0x39b8bb81,0xbbf4353a,0x385f3830,
  0xb2633b3f,0x3bf7b958,0xb60eb825,0xba353bc0,0xb7853b87,0x3aa9b3d3,0x3911bbe9,0xb9aa2a7a,0xb99d3bbf,0x34c33389,0x3bdcb9f8,0x3907bb83,
  0xbb013be5,0xb5eb394a,0x34db2884,0x3ab6b8db,0xbbd03bfb,0xbafb3b7a,0xb98b3a54,0xb74238a3,0x3a4db93c,0xbac1389e,0x3b24b7e8,0xbb763682,
  0x3b71b8a8,0xbbf23029,0x3a9335a5,0xb74eba04,0x3bf8b80a,0xb999b58d,0xaef53b90,0x3ab3bad1,0x3bd7b6c6,0xadfbb9f4,0xbb683ad8,0x390c33eb,
  0x3b10b56a,0x386fbbc2,0xba3130be,0xb9a63bfd,0x39b3b402,0x3ba3bbc6,0x3201b954,0xba393581,0x37bdb122,0x3b6fba00,0x3b9fbbff,0x385aba5c,
  0x32deac6a,0x37d2b5b1,0x39c5b8e5,0x3b21ba85,0x344b3b98,0xb185bbce,0x2cce3bf0,0x25e4bbff,0xbc003340,0x3afe3426,0xb855b979,0x2d333b94,
  0x34cfbbed,0xbb6c39df,0x3b042ba7,0xb1e8ba7a,0x3aa2a9b1,0x34b7bb8b,0xbc0038bc,0x349338cc,0xba2d3bfe,0x387430a6,0x3b0dbbc3,0xb625b55e,
  0xb63cb074,0xbbf83a76,0xb8653b35,0x37a6294d,0x3bf3bbc9,0x3994bb2f,0x2d65b6a4,0xb889341a,0xb19e3517,0x2f8b2776,0x366bb432,0x3933b840,
  0x3bb5b50b,0xbbe1330f,0x3bfaafef,0xbbff26ad,0xa4523bcb,0x37c8bbba,0xbaba39d6,0x3bf9b523,0xbba1305b,0x35f73970,0x37b2bbfc,0xbbdd38b2,
  0x387abbfe,0xbba53552,0x9cb63a73,0x3babba67,0x39162a16,0x3aa5bbea,0xb790b3ba,0xbb633b89,0xbb5e3bec,0xadc938b7,0x3ab0b6f4,0x3b07bbfe,
  0xaf27b359,0xb9bc370a,0xbbf93b47,0xba973bbc,0x3be0bb96,0x3bf2bbff,0x3b54bbb8,0x3a15bac7,0xafbd3bfb,0x32f7bbe2,0xb4ff3bb7,0x3676bb78,
  0x365fbbe4,0xba453a58,0x3bdfb699,0xbb9eac38,0xb9243bbd,0x3c00b6af,0xb902b6ff,0xb2943bc8,0x3aacbb85,0xba29aade,0xb6313bc5,0x3bf5b815,
  0xbba73b3d,0x324b381a,0x3bf6ba6f,0x9648b95d,0x3c00bae5,0x376fbad5,0xb87f2b43,0xbbf53b42,0xbbb03a7e,0xbb593bfc,0xb75939da,0x32ad3042,
  0x3abdba09,0x3bb3bb4c,0x3c00bbef,0x3b9cbbe3,0x3bf12c9c,0xbbcfb16c,0x3b9a343e,0xbb52b5bc,0xbb57b13b,0x38f838e0,0xb1b6bb4a,0xb4e73bfc,
  0x3a21340e,0x217fbb45,0xba3d3b32,0x3bd4b371,0xb86ab576,0xb91b3bfd,0x3b60b3a2,0x2e91bae1,0x34ab36d2,0x3bd8bade,0xae5fb8c1,0xbc0039f0,
  0x9fdbb80f,0xbb16382a,0xba9e3bfd,0x2ec336bb,0xb46f38ad,0x3654ac06,0x3b1bb974,0x3bd3bbee,0x3850b941,0x3457b68d,0xa51bb010,0xb4f33153,
  0xb7dd3b27,0x3899bac4,0xb9373a50,0x39c9b9cd,0x3990383a,0xb463baee,0xb2c63bff,0x392ebb2c,0x3b18ba60,0xbb5c28e8,0x347b39fc,0x3884bbe6,
  0xb219b966,0xbb133b37,0x39a130d7,0x379bbbeb,0xbbf63962,0xb2323a6b,0x3ba9b820,0x361abb3a,0xb6023a64,0x391fb0f0,0x3bd6bb8e,0x3487b9e3,
  0x3a41b835,0x3c00bb92,0x3a1dbb7f,0x31cfb805,0x3a90bb2a,0x38f3b9d2,0x35d4b7f3,0x2d00b328,0x3af7372c,0xba8cb845,0x3a1138ea,0xb986b982,
  0x39c0bacb,0xbbb237fe,0x3bd2a81f,0xba19b715,0xb764b8d6,0xb6483bfe,0x3baeb94f,0xba9bb109,0xbbda39e7,0x377a36e8,0x39afbbe8,0xbb0a308d,
  0xae2d39eb,0x3bd9b8c7,0x349fbadb,0xbb6536dd,0x3b6ab8d1,0x3a25bbe7,0xb27cb546,0xbbac396b,0x38fdbace,0xa311b52f,0xb9293599,0xbbde3aeb,
  0xb8943721,0xba49397d,0xbb733af1,0xbbfa3bcc,0xbbfb3bff,0xbbe23bf1,0xbbb73bcf,0xbb783b9a,0xbb7c3bf2,0xb9463a93,0xb340374e,0x3426a452,
  0xba603bd4,0xa8e83764,0x39fcb648,0x3be6bbae,0xb8bc3ba5,0x38cc9cb6,0x3b85bbab,0xaadeb86a,0xb56a3b65,0x3bc2b785,0x30bebaa9,0xbbfd3911,
  0xab433b16,0x3b42ba9e,0xba64aec3,0xb0f03b6a,0x33593ab6,0x370abbf3,0xbb473994,0x3bbcad65,0x37f33a49,0xb328bb73,0xac6a3bfa,0x35b1bbd0,
  0xac9c25e4,0xb16c2fbd,0xb43e32f7,0xb5bc34ff,0xb5a52f59,0xba04388e,0xbbcb3b1e,0xbbba3c00,0xb8d63294,0xbbfe3b18,0xb94f3b5c,0x3109347b,
  0xba7334b7,0xba673c00,0x35763493,0x3bfdbaac,0xbb87361a,0xb3d33b10,0x3be9b86f,0x2a7aba31,0xbbfd376f,0x36bb387f,0x38d1bbf5,0xbbe73602,
  0xbbc9385a,0x3b2f2f27,0xb6a4b9bc,0xb41a3bf9,0xbaf138f3,0x3bccb5d4,0xbbfb2d00,0x3b7a32de,0xbb273b52,0xbac43af7,0xba503a8c,0xb9cd3a11,
  0x3979b7c8,0x3b94baba,0x3be4bbf9,0x3a58bb57,0x380aba9b,0xb58dad97,0xbb9039b8,0xbad13bf4,0xbbc5391b,0xb8153b60,0x3966ae91,0x3b37bbda,
  0x2a1639aa,0x3beaba2d,0xb3bab874,0xbb893b0d,0x3b8eba25,0xb9e3b27c,0xb4023bac,0x3bc6b99d,0xb8adb889,0xac063bb0,0x3974bb59,0xbbee3759,
  0xb8e53afb,0x3a85b98b,0xbb963742,0x3bffb19e,0xb72c3676,0xb84537dd,0xb8ea3899,0xb9823937,0xb9d63afe,0xb5233855,0x313b2d33,0x38e0b65f,
  0x3ae8b884,0x3b81bbf8,0x353ab999,0xb8302ef5,0x33a2ba29,0xbae13631,0xb9e73bf5,0x36e83219,0xbbfe39a6,0x30a63916,0x3bc3baa5,0xb55eb790,
  0x3546391f,0x396bbbd6,0xbbbf3487,0x338939b3,0x3a7eba97,0xbbfc346f,0x39da3654,0xb042bb1b,0xba54b7d2,0x38a339c5,0xb517bb21,0x27763be0,
  0xb93c3986,0xb89e38ee,0xb7e8384a,0xb6823737,0x3699b8f8,0xac38b1b6,0xb83a34e7,0xbaee39c0,0xb05b385f,0x3970b4cf,0x3bfcbb6c,0x38b2bb04,
  0xb0d7b77a,0xbbeb39af,0xb6c63b0a,0x39f4b263,0x36d23625,0x3adebba7,0xb8c1b24b,0xb9f03bf6,0xb954b4c3,0xb5813bdc,0x3becb907,0xb8b7b63c,
  0x3ace32ad,0xb52fba41,0xb5993c00,0x3aebba1d,0xbbb8af8b,0x3ac7366b,0xb941b933,0x368d3abd,0xba0d39c9,0xba893a4d,0xbaf43ac1,0xbb4f3b24,
  0x3b4aba45,0x3bfcbbdf,0x3acbbb9e,0x37feb990,0xbbed3ab3,0xb9df3ba1,0x2ba735f7,0x3a7ab7b2,0x3be8bb13,0x308db9a1,0xbb3f379b,0xb9583bd7,
  0xbb3d3b63,0x381a34ab,0x3a6fbbd8,0xb95dae5f,0x39f8bba3,0xbb833201,0x30743a39,0x3a76bb5e,0xb8353bd3,0x3b92b8fd,0xbb7fa311,0x38053929,
  0x3432bbf2,0xb8403b54,0x3a09ba15,0xbb4c3850,0xb50b35c8,0xb30f344b,0xafef3185,0xa6ad2cce,0xbbff3bb2,0xbb2c3bd2,0xb8a83a19,0xb02935df,
  0xb40eb1e8,0xbb453924,0xbb323c00,0xb3713902,0x3ad8bbf7,0xb3ebb60e,0xbbfe3a35,0xb5523aa2,0x39eb1648,0x38c7bbf6,0xbadb3232,0xb6dd3ba9,
  0xb6f43bf8,0x3bfeb865,0xb80fb7a6,0xb82a3c00,0xbbe531cf,0x394a37bd,0xa884bb6f,0xb8db3b9f,0xb010bbb3,0xb1533c00,0x3721bb9c,0xb97d3a90,
  0xbb983b76,0xbbce3bb5,0xbbf03be1,0xbbff3bfa,0x281fb463,0xb71532c6,0xba81392e,0xbbef3b71,0x3bbdbbdd,0x36afba21,0xb6ff217f,0xbbc83a3d,
  0x38252dfb,0x3bc0bb68,0x29b1b90c,0xbb8b387a,0xb9623c00,0x3a6bae2d,0x3820bbd9,0xbb3a349f,0xbb352dc9,0x294d3ab0,0x3ae5bb07,0xbad59fdb,
  0x3122bbde,0xba003b01,0x3bffb5eb,0xba5cb4db,0x3befb457,0xbbe3a51b,0x3b2a34f3,0xb9d2b894,0x39c939cd,0xba4db93c,0x3ac1389e,0xbb24b7e8,
  0x3b1e3946,0xbc00b340,0x3afeb426,0xb8553979,0x3bdd38b2,0xba21340e,0xa17fbb45,0x3a3d3b32,0x3bf53815,0xb2193966,0xbb13bb37,0x39a1b0d7,
  0x3b6536dd,0x37853b87,0xbaa9b3d3,0xb911bbe9,0x3a393581,0x3b5e3bec,0x2dc938b7,0xbab0b6f4,0x3889341a,0x3bb03a7e,0x3b593bfc,0x375939da,
  0x34f33153,0x38943721,0x3a49397d,0x3b733af1,0xb9863982,0x38eeba0d,0xb84a3a89,0x3737baf4,0xb74e3a04,0xa452bbcb,0x37c83bba,0xbabab9d6,
  0xb1e83a7a,0xb924bbbd,0x3c0036af,0xb90236ff,0x2e913ae1,0xbbdab9e7,0x377ab6e8,0x39af3be8,0x361a3b3a,0xbb10b56a,0xb86fbbc2,0x3a3130be,
  0x39073b83,0xb63c3074,0xbbf8ba76,0xb865bb35,0x3a973bbc,0x346f38ad,0xb654ac06,0xbb1bb974,0x3b9c3be3,0x3a903b2a,0x38f339d2,0x35d437f3,
  0x3b763682,0xbbb5b50b,0x3be1330f,0xbbfaafef,0x2d33bb94,0x365f3be4,0xba45ba58,0x3bdf3699,0xbbd4b371,0x3764b8d6,0x36483bfe,0xbbaeb94f,
  0x379b3beb,0xbbd7b6c6,0x2dfbb9f4,0x3b683ad8,0x39aa2a7a,0x3a2d3bfe,0xb87430a6,0xbb0dbbc3,0xbb07bbfe,0x1fdbb80f,0x3b16382a,0x3a9e3bfd,
  0xb2ad3042,0xba41b835,0xbc00bb92,0xba1dbb7f,0x3bfa3bcc,0x3bd03bfb,0x3afb3b7a,0x398b3a54,0xb5c83b4f,0x344bbb98,0xb1853bce,0x2ccebbf0,
  0x3bf93523,0xbb57313b,0x38f8b8e0,0xb1b63b4a,0xb294bbc8,0x3b183a60,0xbb5ca8e8,0x347bb9fc,0xbb0ab08d,0xb263bb3f,0x3bf73958,0xb60e3825,
  0x39a63bfd,0xb9162a16,0xbaa5bbea,0x3790b3ba,0x37a6a94d,0x3c003ae5,0x376f3ad5,0xb87fab43,0xbbd3bbee,0xb8fdbace,0x2311b52f,0x39293599,
  0x2d003328,0xb2deac6a,0xb7d2b5b1,0xb9c5b8e5,0x3bff26ad,0xbbf12c9c,0x3bcfb16c,0xbb9a343e,0xbb9e2c38,0x3990b83a,0xb4633aee,0xb2c6bbff,
  0x3a9bb109,0xad973ae8,0xb9b8bb81,0x3bf4353a,0xb90c33eb,0xb87abbfe,0x3ba53552,0x1cb63a73,0x3625b55e,0x3ba73b3d,0xb24b381a,0xbbf6ba6f,
  0xaec336bb,0xbb6ab8d1,0xba25bbe7,0x327cb546,0xb1cfb805,0x37bd3122,0x3b6f3a00,0x3b9f3bff,0x374238a3,0x319e3517,0xaf8b2776,0xb66bb432,
  0x25e43bff,0xafbdbbfb,0x32f73be2,0xb4ffbbb7,0xb4e7bbfc,0x39c03acb,0xbbb2b7fe,0x3bd2281f,0x38843be6,0xbbf8b80a,0x3999b58d,0x2ef53b90,
  0xba35bbc0,0x3aa229b1,0x34b73b8b,0xbc00b8bc,0x3b633b89,0xb4ab36d2,0xbbd8bade,0x2e5fb8c1,0xbbf5bb42,0xb602ba64,0x391f30f0,0x3bd63b8e,
  0x3bde3aeb,0x3b013be5,0x35eb394a,0xb4db2884,0xbb21ba85,0xbbe0bb96,0xbbf2bbff,0xbb54bbb8,0x3b52b5bc,0xbaf7372c,0x3a8cb845,0xba1138ea,
  0x392e3b2c,0xbb71b8a8,0x3bf23029,0xba9335a5,0xb85f3830,0xb4cfbbed,0x3b6c39df,0xbb042ba7,0xbbabba67,0x386ab576,0x391b3bfd,0xbb60b3a2,
  0x1648b95d,0x3bf63962,0x32323a6b,0xbba9b820,0x3bac396b,0x399d3bbf,0xb4c33389,0xbbdcb9f8,0x385a3a5c,0xaf273359,0xb9bcb70a,0xbbf9bb47,
  0xb933b840,0xbabdba09,0xbbb3bb4c,0xbc00bbef,0x36763b78,0xb7ddbb27,0x38993ac4,0xb937ba50,0xba193715,0x35dfba81,0x2f593bef,0xb88ebb7c,
  0xbab3bad1,0x3ba1305b,0xb5f73970,0xb7b2bbfc,0x3493b8cc,0x3aac3b85,0xba292ade,0xb631bbc5,0x3c0039f0,0x2e2d39eb,0xbbd9b8c7,0xb49fbadb,
  0x348739e3,0xb9b3b402,0xbba3bbc6,0xb201b954,0xbab6b8db,0xbbf3bbc9,0xb994bb2f,0xad65b6a4,0xba15bac7,0xb850b941,0xb457b68d,0x251bb010,
  0xb9cfbb16,0x30ac2a31,0x3b9c3bf1,0xb493ae2d,0xb76fb8b4,0x35a133e3,0x3a1d3afe,0xb902b76f,0xb3e3b5a1,0x38b4376f,0x376f3902,0xbafeba1d,
  0xaa31b0ac,0x3b1639cf,0x2e2d3493,0xbbf1bb9c,0xb956ba74,0x305f29cc,0x3b633bd2,0xb44badc9,0xb6e7b859,0x353f335e,0x39d23ab6,0xb8bcb6ff,
  0xb35eb53f,0x385936e7,0x36ff38bc,0xbab6b9d2,0xa9ccb05f,0x3a743956,0x2dc9344b,0xbbd2bb63,0xb8e3b9de,0x30122967,0x3b1e3ba1,0xb402ad65,
  0xb662b801,0x34de32da,0x39823a67,0xb874b68d,0xb2dab4de,0x38013662,0x368d3874,0xba67b982,0xa967b012,0x39de38e3,0x2d653402,0xbba1bb1e,
  0xb876b952,0x2f8c2902,0x3ace3b60,0xb371ad00,0xb5e1b758,0x347e3257,0x392e3a11,0xb82ab61a,0xb257b47e,0x375835e1,0x361a382a,0xba11b92e,
  0xa902af8c,0x39523876,0x2d003371,0xbb60bace,0xb80db8ce,0x2ef3289e,0x3a733b10,0xb2deac9c,0xb562b6b3,0x342031d5,0x38d639b3,0xb7bdb5a5,
  0xb1d5b420,0x36b33562,0x35a537bd,0xb9b3b8d6,0xa89eaef3,0x38ce380d,0x2c9c32de,0xbb10ba73,0xb750b851,0x2e5a2839,0x3a0d3ab0,0xb24bac38,
  0xb4e5b613,0x33863153,0x387a394f,0xb721b52f,0xb153b386,0x361334e5,0x352f3721,0xb94fb87a,0xa839ae5a,0x38513750,0x2c38324b,0xbab0ba0d,
  0xb68eb7b4,0x2dc227a9,0x399d3a41,0xb1b6aba7,0xb46ab577,0x32cd30d2,0x381a38e5,0xb682b4b7,0xb0d2b2cd,0x3577346a,0x34b73682,0xb8e5b81a,
  0xa7a9adc2,0x37b4368e,0x2ba731b6,0xba41b99d,0xb5d2b6d1,0x2d2a26e0,0x392439c5,0xb122aade,0xb3e3b4de,0x32163052,0x376f3874,0xb5dfb43e,
  0xb052b216,0x34de33e3,0x343e35df,0xb874b76f,0xa6e0ad2a,0x36d135d2,0x2ade3122,0xb9c5b924,0xb51cb5f6,0x2c932617,0x38a3393c,0xb08daa16,
  0xb2f4b448,0x31602fa5,0x36a437fe,0xb53ab389,0xafa5b160,0x344832f4,0x3389353a,0xb7feb6a4,0xa617ac93,0x35f6351c,0x2a16308d,0xb93cb8a3,
  0xb46ab523,0x2bf6254d,0x381a38a8,0xafefa94d,0xb209b36b,0x30ac2ea7,0x35d4370a,0xb493b294,0xaea7b0ac,0x336b3209,0x32943493,0xb70ab5d4,
  0xa54dabf6,0x3523346a,0x294d2fef,0xb8a8b81a,0xb378b456,0x2ac82484,0x3715380a,0xaec3a884,0xb120b24a,0x2ff22da9,0x34ff360e,0xb3d3b19e,
  0xada9aff2,0x324a3120,0x319e33d3,0xb60eb4ff,0xa484aac8,0x34563378,0x28842ec3,0xb80ab715,0xb223b31c,0x29992376,0x35eb36c6,0xad97a776,
  0xb039b12d,0x2e8d2cac,0x3426350b,0xb27cb0a6,0xacacae8d,0x312d3039,0x30a6327c,0xb50bb426,0xa376a999,0x331c3223,0x27762d97,0xb6c6b5eb,
  0xb0d2b194,0x286b21e4,0x34b7356a,0xac6aa5e4,0xaea7b012,0x2d2a2b5f,0x32943402,0xb122af59,0xab5fad2a,0x30122ea7,0x2f593122,0xb402b294,
  0xa1e4a86b,0x319430d2,0x25e42c6a,0xb56ab4b7,0xaf0cb012,0x267b2052,0x32f73402,0xaa7aa452,0xacdeadf5,0x2b912967,0x30d731e8,0xaf8bad65,
  0xa967ab91,0x2df52cde,0x2d652f8b,0xb1e8b0d7,0xa052a67b,0x30122f0c,0x24522a7a,0xb402b2f7,0xac79ad2a,0x24201d7f,0x30743122,0xa81fa17f,
  0xaa31ab91,0x28d026e0,0x2e2d2f8b,0xacceaade,0xa6e0a8d0,0x2b912a31,0x2ade2cce,0xaf8bae2d,0x9d7fa420,0x2d2a2c79,0x217f281f,0xb122b074,
  0xa7a9a86b,0x1f1218b6,0x2ba72c6a,0xa3119cb6,0xa54da67b,0x242021e4,0x294d2a7a,0xa81fa5e4,0xa1e4a420,0x267b254d,0x25e4281f,0xaa7aa94d,
  0x98b69f12,0x286b27a9,0x1cb62311,0xac6aaba7,0x211b21e4,0x98b69248,0xa51ba5e4,0x1cb61648,0x1f122052,0x9d7f9bdb,0xa311a452,0x217f1fdb,
  0x1bdb1d7f,0xa0529f12,0x9fdba17f,0x24522311,0x124818b6,0xa1e4a11b,0x96489cb6,0x25e4251b,0x2a632b5f,0xa1e49bdb,0xae5faf59,0x25e41fdb,
  0x286b2967,0xa6e0a4e9,0xac6aad65,0x2ade28e8,0x24e926e0,0xa967a86b,0xa8e8aade,0x2d652c6a,0x1bdb21e4,0xab5faa63,0x9fdba5e4,0x2f592e5f,
  0x2dc22ea7,0xa54d9f12,0xb1b6b294,0x294d2311,0x2bf62cde,0xaa31a86b,0xafefb0d7,0x2e2d2c6a,0x286b2a31,0xacdeabf6,0xac6aae2d,0x30d72fef,
  0x1f12254d,0xaea7adc2,0xa311a94d,0x329431b6,0x302c30d2,0xa7a9a11b,0xb41ab4b7,0x2ba7251b,0x2dc22f0c,0xac79aa63,0xb1b6b2f7,0x30742e5f,
  0x2a632c79,0xaf0cadc2,0xae5fb074,0x32f731b6,0x211b27a9,0xb0d2b02c,0xa51baba7,0x34b7341a,0x317a3257,0xa902a2ad,0xb552b61a,0x2d0026ad,
  0x2f8c309f,0xaddcac2e,0xb371b487,0x31cf3029,0x2c2e2ddc,0xb09faf8c,0xb029b1cf,0x34873371,0x22ad2902,0xb257b17a,0xa6adad00,0x361a3552,
  0x32cd33e3,0xaa31a420,0xb682b76f,0x2e2d281f,0x30ac31bb,0xaf3fad2a,0xb493b58d,0x33283122,0x2d2a2f3f,0xb1bbb0ac,0xb122b328,0x358d3493,
  0x24202a31,0xb3e3b2cd,0xa81fae2d,0x376f3682,0x341334bc,0xab5fa4e9,0xb7a6b85a,0x2f5928e8,0x319432da,0xb052ae28,0xb56ab68d,0x343e3219,
  0x2e283052,0xb2dab194,0xb219b43e,0x368d356a,0x24e92b5f,0xb4bcb413,0xa8e8af59,0x385a37a6,0x34c3358c,0xac47a5b2,0xb85fb8f3,0x304229b1,
  0x327e33fd,0xb106af26,0xb63cb785,0x34e7330f,0x2f263106,0xb3fdb27e,0xb30fb4e7,0x3785363c,0x25b22c47,0xb58cb4c3,0xa9b1b042,0x38f3385f,
  0x35773662,0xacdea67b,0xb8e5b982,0x30d72a7a,0x336b3493,0xb1bbb012,0xb70ab83a,0x358d3402,0x301231bb,0xb493b36b,0xb402b58d,0x383a370a,
  0x267b2cde,0xb662b577,0xaa7ab0d7,0x398238e5,0x36303741,0xad76a744,0xb962ba04,0x316c2b43,0x342e352a,0xb271b092,0xb7d2b8ad,0x3631347b,
  0x30923271,0xb52ab42e,0xb47bb631,0x38ad37d2,0x27442d76,0xb741b630,0xab43b16c,0x3a043962,0x36ee3815,0xae0ea807,0xb9d6ba7a,0x32012c06,
  0x34a735c4,0xb329b113,0xb84ab91b,0x36d234f3,0x31133329,0xb5c4b4a7,0xb4f3b6d2,0x391b384a,0x28072e0e,0xb815b6ee,0xac06b201,0x3a7a39d6,
  0x37b4388e,0xaea7a86b,0xba41bae1,0x32942c6a,0x35233662,0xb3e3b194,0xb8a8b982,0x376f356a,0x319433e3,0xb662b523,0xb56ab76f,0x398238a8,
  0x286b2ea7,0xb88eb7b4,0xac6ab294,0x3ae13a41,0x3841390f,0xaf3fa8d0,0xbaa2bb3a,0x33282cce,0x35a13705,0xb44fb216,0xb902b9e3,0x380535df,
  0x3216344f,0xb705b5a1,0xb5dfb805,0x39e33902,0x28d02f3f,0xb90fb841,0xacceb328,0x3b3a3aa2,0x38ac3997,0xafd8a935,0xbaf7bb83,0x33ba2d33,
  0x362137ac,0xb4aeb298,0xb958ba3d,0x38503654,0x329834ae,0xb7acb621,0xb654b850,0x3a3d3958,0x29352fd8,0xb997b8ac,0xad33b3ba,0x3b833af7,
  0x391c3a28,0xb039a999,0xbb42bbbc,0x34262d97,0x36a4382d,0xb50eb31c,0xb9aaba90,0x389936c6,0x331c350e,0xb82db6a4,0xb6c6b899,0x3a9039aa,
  0x29993039,0xba28b91c,0xad97b426,0x3bbc3b42,0x39923ac3,0xb085a9fe,0xbb81bbe3,0x346f2dfb,0x372a3886,0xb570b3a0,0xb9f8badb,0x38e03737,
  0x33a03570,0xb886b72a,0xb737b8e0,0x3adb39f8,0x29fe3085,0xbac3b992,0xadfbb46f,0x3be33b81,
};

#define PROF(slot) do {} while (0)
#define PROF_DUMP() do {} while (0)
#define PROFA(slot, dep) do {} while (0)
#define PROF3(slot) do {} while (0)
#define PROF2(slot) do {} while (0)

__device__ __forceinline__ uint32_t smem_u32(const void* p) { return (uint32_t)__cvta_generic_to_shared(p); }

__device__ __forceinline__ void mbar_init(uint32_t a, uint32_t c) {
  asm volatile("mbarrier.init.shared::cta.b64 [%0], %1;\n" ::"r"(a), "r"(c) : "memory");
}
__device__ __forceinline__ void mbar_expect_tx(uint32_t a, uint32_t bytes) {
  asm volatile("mbarrier.arrive.expect_tx.shared::cta.b64 _, [%0], %1;\n" ::"r"(a), "r"(bytes) : "memory");
}
__device__ __forceinline__ void mbar_arrive_cluster(uint32_t cluster_addr) {
  asm volatile("mbarrier.arrive.shared::cluster.b64 _, [%0];\n" ::"r"(cluster_addr) : "memory");
}
__device__ __forceinline__ void mbar_arrive_cluster_n(uint32_t cluster_addr, uint32_t n) {
  asm volatile("mbarrier.arrive.shared::cluster.b64 _, [%0], %1;\n" ::"r"(cluster_addr), "r"(n) : "memory");
}
__device__ __forceinline__ bool mbar_try(uint32_t a, uint32_t parity) {
  uint32_t ok;
  asm volatile("{\n.reg .pred p;\nmbarrier.try_wait.parity.shared::cta.b64 p, [%1], %2;\nselp.u32 %0, 1, 0, p;\n}\n"
               : "=r"(ok) : "r"(a), "r"(parity) : "memory");
  return ok;
}
__device__ __forceinline__ void mbar_wait(uint32_t a, uint32_t parity) {
  if (mbar_try(a, parity)) return;
#pragma unroll 1
  for (int n = 0; n < SPIN_LIMIT; n++)
    if (mbar_try(a, parity)) break;
}
__device__ __forceinline__ bool elect_one() {
  uint32_t p;
  asm volatile("{\n.reg .pred P;\nelect.sync _|P, 0xffffffff;\nselp.u32 %0, 1, 0, P;\n}\n" : "=r"(p));
  return p;
}
__device__ __forceinline__ uint32_t mapa(uint32_t a, uint32_t rank) {
  uint32_t r;
  asm volatile("mapa.shared::cluster.u32 %0, %1, %2;\n" : "=r"(r) : "r"(a), "r"(rank));
  return r;
}
__device__ __forceinline__ void nb_sync(int id, int n) { asm volatile("bar.sync %0, %1;\n" ::"r"(id), "r"(n) : "memory"); }
__device__ __forceinline__ void nb_arrive(int id, int n) { asm volatile("bar.arrive %0, %1;\n" ::"r"(id), "r"(n) : "memory"); }
__device__ __forceinline__ void cluster_sync_all() {
  asm volatile("barrier.cluster.arrive.relaxed.aligned;\nbarrier.cluster.wait.aligned;\n" ::: "memory");
}
__device__ __forceinline__ void fence_async_smem() { asm volatile("fence.proxy.async.shared::cta;\n" ::: "memory"); }
__device__ __forceinline__ void fence_async_all() { asm volatile("fence.proxy.async.global;\n" ::: "memory"); }

__device__ __forceinline__ void tma_load_3d(uint32_t dst, const CUtensorMap* tm, uint32_t bar, int c0, int c1, int c2) {
  asm volatile(
      "cp.async.bulk.tensor.3d.shared::cluster.global.mbarrier::complete_tx::bytes [%0], [%1, {%3, %4, %5}], [%2];\n"
      ::"r"(dst), "l"(tm), "r"(bar), "r"(c0), "r"(c1), "r"(c2) : "memory");
}
__device__ __forceinline__ void tma_load_4d(uint32_t dst, const CUtensorMap* tm, uint32_t bar, int c0, int c1, int c2, int c3) {
  asm volatile(
      "cp.async.bulk.tensor.4d.shared::cluster.global.mbarrier::complete_tx::bytes [%0], [%1, {%3, %4, %5, %6}], [%2];\n"
      ::"r"(dst), "l"(tm), "r"(bar), "r"(c0), "r"(c1), "r"(c2), "r"(c3) : "memory");
}
__device__ __forceinline__ void tma_load_3d_mc(uint32_t dst, const CUtensorMap* tm, uint32_t bar, int c0, int c1, int c2) {
  asm volatile(
      "cp.async.bulk.tensor.3d.shared::cluster.global.mbarrier::complete_tx::bytes.multicast::cluster [%0], [%1, {%3, %4, %5}], [%2], %6;\n"
      ::"r"(dst), "l"(tm), "r"(bar), "r"(c0), "r"(c1), "r"(c2), "h"((uint16_t)3) : "memory");
}
__device__ __forceinline__ void bulk_load(uint32_t dst, const void* src, uint32_t bytes, uint32_t bar) {
  asm volatile("cp.async.bulk.shared::cluster.global.mbarrier::complete_tx::bytes [%0], [%1], %2, [%3];\n"
               ::"r"(dst), "l"(src), "r"(bytes), "r"(bar) : "memory");
}
__device__ __forceinline__ void tma_store_3d(const CUtensorMap* tm, uint32_t src, int c0, int c1, int c2) {
  asm volatile("cp.async.bulk.tensor.3d.global.shared::cta.bulk_group [%0, {%2, %3, %4}], [%1];\n"
               ::"l"(tm), "r"(src), "r"(c0), "r"(c1), "r"(c2) : "memory");
}
__device__ __forceinline__ void bulk_commit() { asm volatile("cp.async.bulk.commit_group;\n" ::: "memory"); }
__device__ __forceinline__ void bulk_wait0() { asm volatile("cp.async.bulk.wait_group 0;\n" ::: "memory"); }
__device__ __forceinline__ void prefetch_tmap(const CUtensorMap* tm) {
  asm volatile("prefetch.tensormap [%0];\n" ::"l"(tm) : "memory");
}

__device__ __forceinline__ void wg_fence() { asm volatile("wgmma.fence.sync.aligned;\n" ::: "memory"); }
__device__ __forceinline__ void wg_commit() { asm volatile("wgmma.commit_group.sync.aligned;\n" ::: "memory"); }
template <int N> __device__ __forceinline__ void wg_wait() {
  asm volatile("wgmma.wait_group.sync.aligned %0;\n" ::"n"(N) : "memory");
}
__device__ __forceinline__ uint64_t mkdesc(uint32_t addr, uint32_t lbo, uint32_t sbo, uint32_t swz) {
  return (uint64_t)((addr & 0x3FFFF) >> 4) | ((uint64_t)(lbo >> 4) << 16) | ((uint64_t)(sbo >> 4) << 32) |
         ((uint64_t)swz << 62);
}

#define R4(d, o) "+f"(d[o + 0]), "+f"(d[o + 1]), "+f"(d[o + 2]), "+f"(d[o + 3])
#define R8(d, o) R4(d, o), R4(d, o + 4)
#define R16(d, o) R8(d, o), R8(d, o + 8)
#define R32(d, o) R16(d, o), R16(d, o + 16)
#define R64(d, o) R32(d, o), R32(d, o + 32)

__device__ __forceinline__ void wgmma_n192(float (&d)[96], uint64_t da, uint64_t db, uint32_t acc) {
  asm volatile(
      "{\n.reg .pred p;\nsetp.ne.u32 p, %98, 0;\n"
      "wgmma.mma_async.sync.aligned.m64n192k16.f32.bf16.bf16 "
      "{%0,%1,%2,%3,%4,%5,%6,%7,%8,%9,%10,%11,%12,%13,%14,%15,%16,%17,%18,%19,%20,%21,%22,%23,%24,%25,%26,%27,%28,%29,%30,%31,"
      "%32,%33,%34,%35,%36,%37,%38,%39,%40,%41,%42,%43,%44,%45,%46,%47,%48,%49,%50,%51,%52,%53,%54,%55,%56,%57,%58,%59,%60,%61,%62,%63,"
      "%64,%65,%66,%67,%68,%69,%70,%71,%72,%73,%74,%75,%76,%77,%78,%79,%80,%81,%82,%83,%84,%85,%86,%87,%88,%89,%90,%91,%92,%93,%94,%95}, "
      "%96, %97, p, 1, 1, 0, 1;\n}\n"
      : R64(d, 0), R32(d, 64)
      : "l"(da), "l"(db), "r"(acc));
}
__device__ __forceinline__ void wgmma_n128(float (&d)[64], uint64_t da, uint64_t db, uint32_t acc) {
  asm volatile(
      "{\n.reg .pred p;\nsetp.ne.u32 p, %66, 0;\n"
      "wgmma.mma_async.sync.aligned.m64n128k16.f32.bf16.bf16 "
      "{%0,%1,%2,%3,%4,%5,%6,%7,%8,%9,%10,%11,%12,%13,%14,%15,%16,%17,%18,%19,%20,%21,%22,%23,%24,%25,%26,%27,%28,%29,%30,%31,"
      "%32,%33,%34,%35,%36,%37,%38,%39,%40,%41,%42,%43,%44,%45,%46,%47,%48,%49,%50,%51,%52,%53,%54,%55,%56,%57,%58,%59,%60,%61,%62,%63}, "
      "%64, %65, p, 1, 1, 0, 1;\n}\n"
      : R64(d, 0)
      : "l"(da), "l"(db), "r"(acc));
}
#define WG128(C, ACC)                                                                                                      \
  asm volatile(                                                                                                            \
      "{\n.reg .b64 a, b;\nmov.b64 a, {%64, %66};\nmov.b64 b, {%65, %66};\n"                                               \
      "wgmma.mma_async.sync.aligned.m64n128k16.f32.bf16.bf16 "                                                             \
      "{%0,%1,%2,%3,%4,%5,%6,%7,%8,%9,%10,%11,%12,%13,%14,%15,%16,%17,%18,%19,%20,%21,%22,%23,%24,%25,%26,%27,%28,%29,%30,%31," \
      "%32,%33,%34,%35,%36,%37,%38,%39,%40,%41,%42,%43,%44,%45,%46,%47,%48,%49,%50,%51,%52,%53,%54,%55,%56,%57,%58,%59,%60,%61," \
      "%62,%63}, a, b, " ACC ", 1, 1, 0, 1;\n}\n"                                                                          \
      : Z16(C, d, 0), Z16(C, d, 16), Z16(C, d, 32), Z16(C, d, 48)                                                          \
      : "r"(da), "r"(db), "r"(0x40000040))
#define Z4(C, d, o) C(d[o + 0]), C(d[o + 1]), C(d[o + 2]), C(d[o + 3])
#define Z16(C, d, o) Z4(C, d, o), Z4(C, d, o + 4), Z4(C, d, o + 8), Z4(C, d, o + 12)
__device__ __forceinline__ void wgmma_n128z(float (&d)[64], uint32_t da, uint32_t db) { WG128("=f", "0"); }
__device__ __forceinline__ void wgmma_n128a(float (&d)[64], uint32_t da, uint32_t db) { WG128("+f", "1"); }
template <int N> __device__ __forceinline__ void fence_regs(float (&d)[N]) {
#pragma unroll
  for (int i = 0; i < N; i++) asm volatile("" : "+f"(d[i])::"memory");
}

__device__ __forceinline__ void mma16816(float (&d)[4], uint32_t a0, uint32_t a1, uint32_t a2, uint32_t a3, uint32_t b0,
                                         uint32_t b1) {
  asm("mma.sync.aligned.m16n8k16.row.col.f32.bf16.bf16.f32 {%0,%1,%2,%3}, {%4,%5,%6,%7}, {%8,%9}, {%0,%1,%2,%3};\n"
      : "+f"(d[0]), "+f"(d[1]), "+f"(d[2]), "+f"(d[3])
      : "r"(a0), "r"(a1), "r"(a2), "r"(a3), "r"(b0), "r"(b1));
}
__device__ __forceinline__ void mma16816_z(float (&d)[4], uint32_t a0, uint32_t a1, uint32_t a2, uint32_t a3, uint32_t b0,
                                           uint32_t b1) {
  asm("mma.sync.aligned.m16n8k16.row.col.f32.bf16.bf16.f32 {%0,%1,%2,%3}, {%4,%5,%6,%7}, {%8,%9}, {%10,%10,%10,%10};\n"
      : "=f"(d[0]), "=f"(d[1]), "=f"(d[2]), "=f"(d[3])
      : "r"(a0), "r"(a1), "r"(a2), "r"(a3), "r"(b0), "r"(b1), "f"(0.f));
}
__device__ __forceinline__ void ldsm4t(uint32_t (&r)[4], uint32_t a) {
  asm volatile("ldmatrix.sync.aligned.m8n8.x4.trans.shared.b16 {%0,%1,%2,%3}, [%4];\n"
               : "=r"(r[0]), "=r"(r[1]), "=r"(r[2]), "=r"(r[3]) : "r"(a) : "memory");
}
__device__ __forceinline__ void ldsm2t(uint32_t& r0, uint32_t& r1, uint32_t a) {
  asm volatile("ldmatrix.sync.aligned.m8n8.x2.trans.shared.b16 {%0,%1}, [%2];\n" : "=r"(r0), "=r"(r1) : "r"(a) : "memory");
}
__device__ __forceinline__ void st_async128(uint32_t a, uint32_t bar, uint32_t x, uint32_t y, uint32_t z, uint32_t w) {
  asm volatile("st.async.weak.shared::cluster.mbarrier::complete_tx::bytes.v4.b32 [%0], {%2,%3,%4,%5}, [%1];\n"
               ::"r"(a), "r"(bar), "r"(x), "r"(y), "r"(z), "r"(w) : "memory");
}
__device__ __forceinline__ void mbar_arrive(uint32_t a) {
  asm volatile("mbarrier.arrive.shared::cta.b64 _, [%0];\n" ::"r"(a) : "memory");
}
__device__ __forceinline__ void stsm4(uint32_t a, uint32_t r0, uint32_t r1, uint32_t r2, uint32_t r3) {
  asm volatile("stmatrix.sync.aligned.m8n8.x4.shared.b16 [%0], {%1,%2,%3,%4};\n"
               ::"r"(a), "r"(r0), "r"(r1), "r"(r2), "r"(r3) : "memory");
}
__device__ __forceinline__ void stsm4t(uint32_t a, uint32_t r0, uint32_t r1, uint32_t r2, uint32_t r3) {
  asm volatile("stmatrix.sync.aligned.m8n8.x4.trans.shared.b16 [%0], {%1,%2,%3,%4};\n"
               ::"r"(a), "r"(r0), "r"(r1), "r"(r2), "r"(r3) : "memory");
}
__device__ __forceinline__ uint2 lds64(uint32_t a) {
  uint2 v;
  asm volatile("ld.shared.v2.u32 {%0,%1}, [%2];\n" : "=r"(v.x), "=r"(v.y) : "r"(a));
  return v;
}
__device__ __forceinline__ uint4 lds128(uint32_t a) {
  uint4 v;
  asm volatile("ld.shared.v4.u32 {%0,%1,%2,%3}, [%4];\n" : "=r"(v.x), "=r"(v.y), "=r"(v.z), "=r"(v.w) : "r"(a) : "memory");
  return v;
}
__device__ __forceinline__ void sts128(uint32_t a, uint32_t x, uint32_t y, uint32_t z, uint32_t w) {
  asm volatile("st.shared.v4.u32 [%0], {%1,%2,%3,%4};\n" ::"r"(a), "r"(x), "r"(y), "r"(z), "r"(w) : "memory");
}
__device__ __forceinline__ void sts64(uint32_t a, uint32_t x, uint32_t y) {
  asm volatile("st.shared.v2.u32 [%0], {%1,%2};\n" ::"r"(a), "r"(x), "r"(y) : "memory");
}
__device__ __forceinline__ uint32_t pack_bf16(float lo, float hi) {
  uint32_t r;
  asm("cvt.rn.bf16x2.f32 %0, %1, %2;\n" : "=r"(r) : "f"(hi), "f"(lo));
  return r;
}
__device__ __forceinline__ uint32_t bmul2(uint32_t a, uint32_t b) {
  uint32_t r;
  asm("mul.rn.bf16x2 %0, %1, %2;\n" : "=r"(r) : "r"(a), "r"(b));
  return r;
}
__device__ __forceinline__ uint32_t bmax2(uint32_t a, uint32_t b) {
  uint32_t r;
  asm("max.bf16x2 %0, %1, %2;\n" : "=r"(r) : "r"(a), "r"(b));
  return r;
}
__device__ __forceinline__ uint32_t bfma2(uint32_t a, uint32_t b, uint32_t c) {
  uint32_t r;
  asm("fma.rn.bf16x2 %0, %1, %2, %3;\n" : "=r"(r) : "r"(a), "r"(b), "r"(c));
  return r;
}
__device__ __forceinline__ void prefetch_l2(const void* p) { asm volatile("prefetch.global.L2 [%0];\n" ::"l"(p)); }
__device__ __forceinline__ void cp_async16n(uint32_t dst, const void* src) {
  asm volatile("cp.async.cg.shared.global [%0], [%1], 16;\n" ::"r"(dst), "l"(src) : "memory");
}
__device__ __forceinline__ void cp_async16(uint32_t dst, const void* src, uint32_t srcbytes) {
  asm volatile("cp.async.cg.shared.global.L2::256B [%0], [%1], 16, %2;\n" ::"r"(dst), "l"(src), "r"(srcbytes) : "memory");
}
__device__ __forceinline__ uint32_t ld_acquire(const uint32_t* p) {
  uint32_t v;
  asm volatile("ld.acquire.gpu.global.u32 %0, [%1];\n" : "=r"(v) : "l"(p) : "memory");
  return v;
}
__device__ __forceinline__ uint32_t ld_relaxed(const uint32_t* p) {
  uint32_t v;
  asm volatile("ld.relaxed.gpu.global.u32 %0, [%1];\n" : "=r"(v) : "l"(p) : "memory");
  return v;
}
__device__ __forceinline__ void st_release(uint32_t* p, uint32_t v) {
  asm volatile("st.release.gpu.global.u32 [%0], %1;\n" ::"l"(p), "r"(v) : "memory");
}
__device__ __forceinline__ uint4 ld_b128(const uint4* p) {
  unsigned long long a, b;
  asm volatile("{\n.reg .b128 v;\nld.relaxed.gpu.global.b128 v, [%2];\nmov.b128 {%0, %1}, v;\n}\n" : "=l"(a), "=l"(b) : "l"(p) : "memory");
  return make_uint4((uint32_t)a, (uint32_t)(a >> 32), (uint32_t)b, (uint32_t)(b >> 32));
}
__device__ __forceinline__ void st_b128(uint4* p, uint32_t x, uint32_t y, uint32_t z, uint32_t w) {
  asm volatile("{\n.reg .b128 v;\nmov.b128 v, {%1, %2};\nst.relaxed.gpu.global.b128 [%0], v;\n}\n"
               ::"l"(p), "l"(x | (unsigned long long)y << 32), "l"(z | (unsigned long long)w << 32) : "memory");
}

struct Params {
  const __nv_bfloat16* x;
  const __nv_bfloat16* w;
  const __nv_bfloat16* q;
  const __nv_bfloat16* k;
  const __nv_bfloat16* v;
  const __nv_bfloat16* shift_k;
  const __nv_bfloat16* ssm_k;
  const __nv_bfloat16* ssm_D;
  const __nv_bfloat16* wo;
  __nv_bfloat16* out;
  uint32_t zero;
};

__device__ __forceinline__ uint32_t lds32(uint32_t a) {
  uint32_t v;
  asm volatile("ld.shared.u32 %0, [%1];\n" : "=r"(v) : "r"(a) : "memory");
  return v;
}
__device__ __forceinline__ float bf_lo(uint32_t v) {
  uint32_t r;
  asm("prmt.b32 %0, %1, 0, 0x1044;\n" : "=r"(r) : "r"(v));
  return __uint_as_float(r);
}
__device__ __forceinline__ float bf_hi(uint32_t v) { return __uint_as_float(v & 0xffff0000u); }
__device__ __forceinline__ float ex2(float x) {
  float r;
  asm("ex2.approx.ftz.f32 %0, %1;\n" : "=f"(r) : "f"(x));
  return r;
}
__device__ __forceinline__ float rcp(float x) {
  float r;
  asm("rcp.approx.ftz.f32 %0, %1;\n" : "=f"(r) : "f"(x));
  return r;
}

#define Q4(c, d, o) c(d[o + 0]), c(d[o + 1]), c(d[o + 2]), c(d[o + 3])
#define Q8(c, d, o) Q4(c, d, o), Q4(c, d, o + 4)
#define Q16(c, d, o) Q8(c, d, o), Q8(c, d, o + 8)
#define Q32(c, d) Q16(c, d, 0), Q16(c, d, 16)
#define L8 "{%0,%1,%2,%3,%4,%5,%6,%7}"
#define L16 "{%0,%1,%2,%3,%4,%5,%6,%7,%8,%9,%10,%11,%12,%13,%14,%15}"
#define L32 "{%0,%1,%2,%3,%4,%5,%6,%7,%8,%9,%10,%11,%12,%13,%14,%15,%16,%17,%18,%19,%20,%21,%22,%23,%24,%25,%26,%27,%28,%29,%30,%31}"
__device__ __forceinline__ void fft_rows(uint32_t (&d)[32], const uint32_t (&a)[2][4], uint64_t db) {
  asm volatile("wgmma.mma_async.sync.aligned.m64n128k16.f16.f16.f16 " L32 ", {%32,%33,%34,%35}, %36, 0, 1, 1, 1;\n"
               : Q32("=r", d) : "r"(a[0][0]), "r"(a[0][1]), "r"(a[0][2]), "r"(a[0][3]), "l"(db));
  asm volatile("wgmma.mma_async.sync.aligned.m64n128k16.f16.f16.f16 " L32 ", {%32,%33,%34,%35}, %36, 1, 1, 1, 1;\n"
               : Q32("+r", d) : "r"(a[1][0]), "r"(a[1][1]), "r"(a[1][2]), "r"(a[1][3]), "l"(db + 64));
}
template <int INV> __device__ __forceinline__ void fft_cols(uint32_t (&d)[8], const uint32_t (&a)[2][4], uint64_t db) {
  asm volatile("wgmma.mma_async.sync.aligned.m64n32k16.f16.f16.f16 " L8 ", {%8,%9,%10,%11}, %12, 0, 1, 1, %13;\n"
               : Q8("=r", d, 0) : "r"(a[0][0]), "r"(a[0][1]), "r"(a[0][2]), "r"(a[0][3]), "l"(db), "n"(INV));
  asm volatile("wgmma.mma_async.sync.aligned.m64n32k16.f16.f16.f16 " L8 ", {%8,%9,%10,%11}, %12, 1, 1, 1, %13;\n"
               : Q8("+r", d, 0) : "r"(a[1][0]), "r"(a[1][1]), "r"(a[1][2]), "r"(a[1][3]), "l"(db + (INV ? 16 : 64)), "n"(INV));
}
__device__ __forceinline__ void fft_back(float (&d)[16], uint64_t da, uint64_t db) {
  asm volatile("wgmma.mma_async.sync.aligned.m64n32k16.f32.f16.f16 " L16 ", %16, %17, 0, 1, 1, 1, 1;\n"
               : Q16("=f", d, 0) : "l"(da), "l"(db));
#pragma unroll
  for (int i = 1; i < 4; i++)
    asm volatile("wgmma.mma_async.sync.aligned.m64n32k16.f32.f16.f16 " L16 ", %16, %17, 1, 1, 1, 1, 1;\n"
                 : Q16("+f", d, 0) : "l"(da + 32 * i), "l"(db + 64 * i));
}
__device__ __forceinline__ uint32_t hmul2(uint32_t a, uint32_t b) {
  uint32_t r;
  asm("mul.rn.f16x2 %0, %1, %2;\n" : "=r"(r) : "r"(a), "r"(b));
  return r;
}
__device__ __forceinline__ uint32_t hadd2(uint32_t a, uint32_t b) {
  uint32_t r;
  asm("add.rn.f16x2 %0, %1, %2;\n" : "=r"(r) : "r"(a), "r"(b));
  return r;
}
__device__ __forceinline__ uint32_t hneg2(uint32_t a) {
  uint32_t r;
  asm("neg.f16x2 %0, %1;\n" : "=r"(r) : "r"(a));
  return r;
}
__device__ __forceinline__ uint32_t hfma2(uint32_t a, uint32_t b, uint32_t c) {
  uint32_t r;
  asm("fma.rn.f16x2 %0, %1, %2, %3;\n" : "=r"(r) : "r"(a), "r"(b), "r"(c));
  return r;
}
__device__ __forceinline__ uint32_t pack_f16(float lo, float hi) {
  uint32_t r;
  asm("cvt.rn.f16x2.f32 %0, %1, %2;\n" : "=r"(r) : "f"(hi), "f"(lo));
  return r;
}
__device__ __forceinline__ uint32_t bmaxabs2(uint32_t a, uint32_t b) {
  uint32_t r;
  asm("max.xorsign.abs.bf16x2 %0, %1, %2;\n" : "=r"(r) : "r"(a), "r"(b));
  return r;
}
struct C2 { uint32_t r, i; };
__device__ __forceinline__ C2 cmul(C2 a, C2 b) {
  return C2{hfma2(a.r, b.r, hneg2(hmul2(a.i, b.i))), hfma2(a.r, b.i, hmul2(a.i, b.r))};
}
__device__ __forceinline__ C2 cfma(C2 a, C2 b, C2 c) {
  return C2{hfma2(a.r, b.r, hfma2(hneg2(a.i), b.i, c.r)), hfma2(a.r, b.i, hfma2(a.i, b.r, c.i))};
}
__device__ __forceinline__ C2 crot(C2 z, C2 t) {
  const uint32_t r = hfma2(t.r, z.i, z.r), i = hfma2(t.i, r, z.i);
  return C2{hfma2(t.r, i, r), i};
}
__device__ __forceinline__ C2 cget(const uint32_t (&e)[8], int j, int b) { return C2{e[4 * j + b], e[4 * j + 2 + b]}; }
template <int N> __device__ __forceinline__ void fence_regs(uint32_t (&d)[N]) {
#pragma unroll
  for (int i = 0; i < N; i++) asm volatile("" : "+r"(d[i])::"memory");
}
__device__ __forceinline__ void ldsm4(uint32_t (&r)[4], uint32_t a) {
  asm volatile("ldmatrix.sync.aligned.m8n8.x4.shared.b16 {%0,%1,%2,%3}, [%4];\n"
               : "=r"(r[0]), "=r"(r[1]), "=r"(r[2]), "=r"(r[3]) : "r"(a) : "memory");
}

__device__ __forceinline__ uint32_t movm(uint32_t a) {
  uint32_t r;
  asm volatile("movmatrix.sync.aligned.m8n8.trans.b16 %0, %1;\n" : "=r"(r) : "r"(a));
  return r;
}
template <int C0, int H, bool T> __device__ __forceinline__ void attn_pack(const float (&acc)[96], uint32_t (&d)[8]) {
#pragma unroll
  for (int c = 0; c < 8; c++) {
    asm volatile("cvt.rn.bf16x2.f32 %0, %1, %2;\n" : "=r"(d[c]) : "f"(acc[4 * (C0 + c) + 2 * H + 1]), "f"(acc[4 * (C0 + c) + 2 * H]));
    if (T) d[c] = movm(d[c]);
  }
}
__device__ __forceinline__ void attn_qk(float (&s)[4], const uint32_t (&qlo)[8], const uint32_t (&qhi)[8],
                                        const uint32_t (&k)[8], int c) {
  mma16816_z(s, qlo[c], qhi[c], qlo[c + 1], qhi[c + 1], k[c], k[c + 1]);
  mma16816(s, qlo[c + 2], qhi[c + 2], qlo[c + 3], qhi[c + 3], k[c + 2], k[c + 3]);
}
template <int N> __device__ __forceinline__ void quad_softmax(float (&x)[N][2], uint32_t (&pp)[N]) {
  const float c2 = 1.4426950408889634f;
  uint32_t q[N], mx[N / 2];
#pragma unroll
  for (int n = 0; n < N; n++) {
    const uint32_t r = pack_bf16(x[n][0], x[n][1]);
    q[n] = bfma2(r, 0x3e353e35u, bmul2(r, 0x379e379eu));
    x[n][0] = bf_lo(q[n]);
    x[n][1] = bf_hi(q[n]);
  }
#pragma unroll
  for (int n = 0; n < N / 2; n++)
    mx[n] = bmax2(__byte_perm(q[2 * n], q[2 * n + 1], 0x5410), __byte_perm(q[2 * n], q[2 * n + 1], 0x7632));
#pragma unroll
  for (int o = 1; o <= 2; o++) {
#pragma unroll
    for (int n = 0; n < N / 2; n++) mx[n] = bmax2(mx[n], __shfl_xor_sync(0xffffffffu, mx[n], o));
  }
  float m[N], t[N];
#pragma unroll
  for (int n = 0; n < N / 2; n++) {
    m[2 * n] = bf_lo(mx[n]);
    m[2 * n + 1] = bf_hi(mx[n]);
  }
#pragma unroll
  for (int n = 0; n < N; n++) {
    const float nm = -m[n] * c2;
    x[n][0] = ex2(fmaf(x[n][0], c2, nm));
    x[n][1] = ex2(fmaf(x[n][1], c2, nm));
  }
#pragma unroll
  for (int n = 0; n < N; n += 2) {
    float u0, u1;
    asm("mma.sync.aligned.m16n8k8.row.col.f32.tf32.tf32.f32 {%0,%1,%2,%3}, {%4,%5,%6,%7}, {%8,%8}, {%9,%9,%9,%9};\n"
        : "=f"(t[n]), "=f"(u0), "=f"(t[n + 1]), "=f"(u1)
        : "r"(__float_as_uint(x[n][0])), "r"(__float_as_uint(x[n + 1][0])), "r"(__float_as_uint(x[n][1])),
          "r"(__float_as_uint(x[n + 1][1])), "r"(0x3f800000u), "f"(0.f));
  }
#pragma unroll
  for (int n = 0; n < N; n++) {
    const float inv = rcp(t[n]);
    pp[n] = pack_bf16(x[n][0] * inv, x[n][1] * inv);
  }
}
template <bool SPLIT>
__device__ __forceinline__ void attn_pv(uint32_t dst, const uint32_t (&vp)[8], const uint32_t (&vo)[8], int c, uint32_t pp,
                                        uint32_t maskLE) {
  const uint32_t b0 = pp & ~maskLE, b1 = pp & maskLE;
  float o[2][4];
#pragma unroll
  for (int i = 0; i < 2; i++) {
    if (SPLIT) {
      asm("mma.sync.aligned.m16n8k8.row.col.f32.bf16.bf16.f32 {%0,%1,%2,%3}, {%4,%5}, {%6}, {%7,%7,%7,%7};\n"
          : "=f"(o[i][0]), "=f"(o[i][1]), "=f"(o[i][2]), "=f"(o[i][3])
          : "r"(vp[c + 2 * i]), "r"(vp[c + 2 * i + 1]), "r"(b0), "f"(0.f));
      asm("mma.sync.aligned.m16n8k8.row.col.f32.bf16.bf16.f32 {%0,%1,%2,%3}, {%4,%5}, {%6}, {%0,%1,%2,%3};\n"
          : "+f"(o[i][0]), "+f"(o[i][1]), "+f"(o[i][2]), "+f"(o[i][3])
          : "r"(vo[c + 2 * i]), "r"(vo[c + 2 * i + 1]), "r"(b1));
    } else {
      mma16816_z(o[i], vp[c + 2 * i], vp[c + 2 * i + 1], vo[c + 2 * i], vo[c + 2 * i + 1], b0, b1);
    }
  }
  stsm4t(dst, pack_bf16(o[0][0], o[0][1]), pack_bf16(o[0][2], o[0][3]), pack_bf16(o[1][0], o[1][1]),
         pack_bf16(o[1][2], o[1][3]));
}

template <int MODE>
__global__ void __cluster_dims__(2, 1, 1) __launch_bounds__(NTHREADS, 1)
fused_kernel(const Params p, const __grid_constant__ CUtensorMap tmX, const __grid_constant__ CUtensorMap tmW,
             const __grid_constant__ CUtensorMap tmWo, const __grid_constant__ CUtensorMap tmWp,
             const __grid_constant__ CUtensorMap tmQ,
             const __grid_constant__ CUtensorMap tmOb,
             const __grid_constant__ CUtensorMap tmXh, const __grid_constant__ CUtensorMap tmWh) {
  extern __shared__ __align__(1024) uint8_t smem[];
  if (threadIdx.x < 32) {
    const uint32_t i = (blockIdx.x & 127) * 16 + (threadIdx.x & 15);
    prefetch_l2(threadIdx.x & 16 ? (const char*)p.w + i * 128 : (const char*)p.x + i * 2048);
  }
  const uint32_t sb = smem_u32(smem);
  const uint32_t bars = sb + OFF_BAR;
  const int tid = threadIdx.x, lane = tid & 31, warp = __shfl_sync(0xffffffffu, tid >> 5, 0);
  const int rank = blockIdx.x & 1;
  const bool halo_cta = blockIdx.x < 4;
  if (halo_cta && MODE != 0) return;
  int grp, mem;
  {
    const int t = (blockIdx.x >> 1) - 4, u = t - 32;
    const int q7 = (u * 37) >> 8;
    const bool lo = (unsigned)t < 32u, mid = (unsigned)u < 28u;
    grp = lo ? (t & 7) : (mid ? 1 + u - 7 * q7 : 0);
    mem = lo ? (t >> 3) : (mid ? 4 + q7 : (t < 0 ? t + 6 : t - 54));
  }
  const int rg = (grp >> 2) * 4 + (mem >> 1), hp = (grp & 3) * 4 + (mem & 1) * 2 + rank;
  const int rb2 = (grp >> 2) * 8 + mem, cb2 = (grp & 3) * 2 + rank;
  const int chb = grp * 16 + mem * 2 + rank;
  const int cta = rg * 16 + hp;
  const int hsel = rb2 & 1;
  const int par = rg >> 2, gidx = rg & 3;

  if (tid < 256 && !halo_cta && MODE != 2) {
    const int r = tid >> 3, c = tid & 7;
    const uint32_t so = r * 128 + ((c ^ (r & 7)) << 4);
    const __nv_bfloat16* wg0 = p.w + (size_t)r * (3 * DM) + hp * 64 + c * 8;
    const __nv_bfloat16* xg0 = p.x + (size_t)(2 * (gidx * 256 + r) + par) * DM + c * 8;
#pragma unroll
    for (int j = 0; j < 3; j++) cp_async16n(sb + OFF_1B + j * 4096 + so, wg0 + j * DM);
#pragma unroll
    for (int i = 0; i < 8; i++) cp_async16n(sb + i * 4096 + so, xg0 + (size_t)i * 64 * DM);
    asm volatile("cp.async.commit_group;\n" ::: "memory");
    if (tid < 16) prefetch_l2((const char*)p.x + (chb * 16 + tid) * 2048 + 128);
    if (warp == 2) prefetch_l2((const char*)p.w + (2048 + chb * 32 + lane) * 128);
  }

  if (warp >= 8) {
    asm volatile("setmaxnreg.dec.sync.aligned.u32 %0;\n" :: "n"(REG_HELP));
    auto halo_issue = [&](int n, int s) {
      const uint32_t fb = bars + 8 * (BAR_FULLB + s), st = sb + s * STGH;
      tma_load_3d(st + 8192, &tmWh, fb, 0, (n >> 1) * 64, 16 + (n & 1) * 16 + blockIdx.x * 4);
      tma_load_4d(st, &tmXh, fb, (n >> 1) * 64, 248, 0, 0);
      mbar_expect_tx(fb, STGH - 2048);
    };
    if (tid == 256) {
      prefetch_tmap(halo_cta ? &tmXh : &tmX);
#pragma unroll
      for (int i = 0; i < NS1B; i++) mbar_init(bars + 8 * (BAR_FULLB + i), 1);
#pragma unroll
      for (int i = 0; i < NS1A; i++) mbar_init(bars + 8 * (BAR_FULLA + i), 1);
      asm volatile("fence.mbarrier_init.release.cluster;\n" ::: "memory");
      if (!halo_cta && MODE != 2) {
        mbar_expect_tx(bars + 8 * (BAR_FULLB + 1), STG1B);
        tma_load_3d(sb + OFF_1B + 1 * STG1B, &tmW, bars + 8 * (BAR_FULLB + 1), hp * 64, 32, 0);
        mbar_expect_tx(bars + 8 * (BAR_FULLB + 2), STG1B);
        tma_load_3d(sb + OFF_1B + 2 * STG1B, &tmW, bars + 8 * (BAR_FULLB + 2), hp * 64, 64, 0);
        mbar_arrive(bars + 8 * BAR_FULLA);
        mbar_arrive(bars + 8 * BAR_FULLB);
      } else if (halo_cta) {
        halo_issue(0, 0);
      }
    } else if (tid == 288) {
#pragma unroll
      for (int i = 0; i < NS1A; i++) mbar_init(bars + 8 * (BAR_EMPTYA + i), 4);
#pragma unroll
      for (int i = 0; i < NS1B; i++) mbar_init(bars + 8 * (BAR_EMPTYB + i), 2);
      mbar_init(bars + 8 * BAR_X, 3);
      mbar_init(bars + 8 * BAR_TAB, 16);
      mbar_init(bars + 8 * BAR_U, 1);
      mbar_init(bars + 8 * BAR_H, 1);
      mbar_init(bars + 8 * BAR_STG, 8);
      mbar_init(bars + 8 * BAR_Q, 1);
      mbar_init(bars + 8 * BAR_LAND, 5);
      mbar_init(bars + 8 * (BAR_LAND + 1), 5);
      asm volatile("fence.mbarrier_init.release.cluster;\n" ::: "memory");
    } else if (tid == 320) {
#pragma unroll
      for (int i = 0; i < NS2; i++) {
        mbar_init(bars + 8 * (BAR_FULL2 + i), 1);
        mbar_init(bars + 8 * (BAR_EMPTY2 + i), 2);
        mbar_init(bars + 8 * (BAR_EMPTY2B + i), 2);
      }
      asm volatile("fence.mbarrier_init.release.cluster;\n" ::: "memory");
    } else if (tid == 352) {
#pragma unroll
      for (int i = 0; i < 4; i++) mbar_init(bars + 8 * (BAR_Y + i), i < 2 ? 4 : i == 2 ? 10 : 8);
      mbar_init(bars + 8 * BAR_XFREE, 1);
#pragma unroll
      for (int i = 0; i < 9; i++) mbar_init(bars + 8 * (BAR_KH + i), 1);
      asm volatile("fence.mbarrier_init.release.cluster;\n" ::: "memory");
    }
    __syncwarp();
    cluster_sync_all();
    if (warp == 8) PROF2(24);
    const int hw = warp - 8;
    const int lr = lane & 7, lm = lane >> 3;
    auto g1_issue_a = [&](int j, int s) {
      const uint32_t fb = bars + 8 * (BAR_FULLA + s);
      mbar_expect_tx(fb, STG1A);
      tma_load_3d_mc(sb + s * STG1A + rank * 16384, &tmX, fb, j * 64, par, gidx * 256 + rank * 128);
    };
    auto g1_issue_b = [&](int kb, int s) {
      const uint32_t fb = bars + 8 * (BAR_FULLB + s);
      mbar_expect_tx(fb, STG1B);
      tma_load_3d(sb + OFF_1B + s * STG1B, &tmW, fb, hp * 64, kb * 32, 0);
    };
    auto g2_k = [&](int kb) { return (kb < 2 ? hp : kb < 4 ? hp & 14 : hp & 12) ^ kb; };
    auto g2_issue_b = [&](uint32_t fb, uint32_t bytes, uint32_t dst, int k0, bool whole) {
      if (whole) {
        tma_load_3d(dst, &tmWo, fb, 0, k0, cb2 * 2);
      } else {
#pragma unroll
        for (int i = 0; i < 4; i++)
          tma_load_3d(dst + (i & 1) * XT + (i >> 1) * 4 * XT, &tmWp, fb, 0, k0 + (i >> 1) * 32, cb2 * 2 + (i & 1));
      }
      mbar_expect_tx(fb, bytes);
    };
    auto send_y = [&](uint32_t o, uint32_t step, int half) {
      const uint32_t peer = mapa(sb, rank ^ 1);
      o += OFF_X + (rank ^ 1) * 4096 + half * 2048 + lane * 16;
      uint4 a[8];
#pragma unroll
      for (int i = 0; i < 8; i++) a[i] = lds128(sb + o + (i >> 2) * step + (i & 2) * (XT / 2) + (i & 1) * 512);
#pragma unroll
      for (int i = 0; i < 8; i++)
        st_async128(peer + o + 1024 + (i >> 2) * step + (i & 2) * (XT / 2) + (i & 1) * 512,
                    peer + OFF_BAR + 8 * (BAR_LAND + half), a[i].x, a[i].y, a[i].z, a[i].w);
    };

    if (halo_cta) {
      if (hw == 0) {
        int s = 1, ph = 1;
#pragma unroll 1
        for (int n = 1; n < 32; n++) {
          mbar_wait(bars + 8 * (BAR_EMPTYB + s), ph);
          if (elect_one()) halo_issue(n, s);
          if (++s == NS1B) { s = 0; ph ^= 1; }
        }
      }
      __syncwarp();
    } else if (hw == 0) {
      uint32_t epoch = 0;
      if (MODE == 2) {
        if (lane < NS2) mbar_arrive_cluster_n(mapa(bars, rank) + 8 * (BAR_EMPTY2 + lane), 2);
      } else {
      if (lane == 0) {
        mbar_expect_tx(bars + 8 * BAR_U, 32768);
        mbar_expect_tx(bars + 8 * BAR_LAND, 8192);
        mbar_expect_tx(bars + 8 * (BAR_LAND + 1), 8192);
        mbar_expect_tx(bars + 8 * BAR_Q, 32768);
        prefetch_tmap(&tmQ);
      }
      {
        int sa = 1, pha = 1, sbb = 2, phb = 1;
#pragma unroll 1
        for (int kb = 2; kb < 32; kb++) {
          if (!(kb & 1)) {
            mbar_wait(bars + 8 * (BAR_EMPTYA + sa), pha);
            if (elect_one()) g1_issue_a(kb >> 1, sa);
            if (++sa == NS1A) { sa = 0; pha ^= 1; }
          }
          mbar_wait(bars + 8 * (BAR_EMPTYB + sbb), phb);
          if (kb > 2 && elect_one()) g1_issue_b(kb, sbb);
          __syncwarp();
          if (kb == 4) epoch = ld_relaxed(g_flag_o + FS * cta);
          if (kb == 4) PROF2(27);
          if (kb == 1) PROF2(38);
          if (kb == 2) PROF2(39);
          if (++sbb == NS1B) { sbb = 0; phb ^= 1; }
        }
      }
      auto q_issue = [&](int i) {
        mbar_wait(bars + 8 * (i ? BAR_EMPTYB + 3 : BAR_EMPTYA + 1), i);
        if (elect_one())
          asm volatile(
              "cp.async.bulk.tensor.5d.shared::cluster.global.mbarrier::complete_tx::bytes [%0], [%1, {%3, %4, %4, %4, %5}], [%2];\n"
              ::"r"(sb + (i ? OFF_Q1 : OFF_Q0)), "l"(&tmQ), "r"(bars + 8 * BAR_Q), "r"((chb & ~1) * 8), "r"(0), "r"(rank * 32 + i * 64)
              : "memory");
        __syncwarp();
      };
      epoch++;
      if (lane == 0) {
        prefetch_tmap(&tmWo);
        prefetch_tmap(&tmWp);
        prefetch_tmap(&tmOb);
      }
      __syncwarp();
      {
        uint4 h[6] = {};
        if (gidx != 0) {
#pragma unroll 1
          for (int n = 0; n < SPIN_LIMIT; n++) {
            bool ok = true;
#pragma unroll
            for (int i = 0; i < 6; i++) h[i] = ld_b128(g_halo + cta * 192 + i * 32 + lane);
#pragma unroll
            for (int i = 0; i < 6; i++) ok = ok && h[i].w == epoch;
            if (__all_sync(0xffffffffu, ok)) break;
          }
          PROF(18);
        }
        q_issue(0);
        sts128(sb + OFF_KH + lane * 16, h[0].x, h[0].y, h[0].z, h[1].x);
        sts128(sb + OFF_KH + 512 + lane * 16, h[1].y, h[1].z, h[2].x, h[2].y);
        sts64(sb + OFF_KH + 1024 + lane * 8, h[3].x, h[3].y);
        sts64(sb + OFF_KH + 1280 + lane * 8, h[3].z, h[4].x);
        sts64(sb + OFF_KH + 1536 + lane * 8, h[4].y, h[4].z);
        sts64(sb + OFF_KH + 1792 + lane * 8, h[5].x, h[5].y);
        __syncwarp();
        if (lane == 0) mbar_arrive(bars + 8 * BAR_KH);
      }
      q_issue(1);
      const uint32_t rb = mapa(bars, lane & 1);
      nb_sync(NB_OREADY, 288);
      if (lane == 0) {
        asm volatile("cp.async.bulk.global.shared::cta.bulk_group [%0], [%1], %2;\n" ::"l"(g_o + (size_t)cta * 16384),
                     "r"(sb + OFF_OP), "r"(32768) : "memory");
        bulk_commit();
      }
      if (lane < 2) {
#pragma unroll
        for (int i = 0; i < 4; i++) mbar_arrive_cluster(rb + 8 * (BAR_EMPTY2 + i + i / 2));
      }
      if (lane == 0) {
        bulk_wait0();
        st_release(g_flag_o + FS * cta, epoch);
      }
      __syncwarp();
      PROF2(17);
      if (lane < 2) mbar_arrive_cluster(rb + 8 * (BAR_EMPTY2 + 2));
      }
      if (MODE != 1) {
        const __nv_bfloat16* osrc = g_o + (size_t)(rb2 >> 1) * 16 * 16384 + hsel * 8192;
        mbar_wait(bars + 8 * (BAR_EMPTY2 + 1), 0);
        if (elect_one()) {
          if (MODE == 0) {
            asm volatile("cp.async.bulk.shared::cluster.shared::cta.mbarrier::complete_tx::bytes [%0], [%1], %2, [%3];\n"
                         ::"r"(mapa(sb + g2_a(1, hsel), rank ^ 1)), "r"(sb + g2_a(0, hsel)), "r"(16384),
                         "r"(mapa(bars + 8 * (BAR_FULL2 + 1), rank ^ 1)) : "memory");
          } else {
            bulk_load(sb + g2_a(0, hsel), osrc + hp * 16384, 16384, bars + 8 * BAR_FULL2);
            bulk_load(sb + g2_a(1, hsel), osrc + (hp ^ 1) * 16384, 16384, bars + 8 * (BAR_FULL2 + 1));
          }
        }
        __syncwarp();
      }
      if (MODE != 2) {
        mbar_wait(bars + 8 * (BAR_Y + 2), 0);
        send_y(0, 4 * XT, 1);
        fence_async_smem();
        __syncwarp();
      }
      if (MODE != 1) {
        int s = 3, k0 = g2_k(3) * 64;
        uint32_t wbar = bars + 8 * (BAR_Y + 2), fb = bars + 8 * (BAR_FULL2 + 3), dst = sb + g2_b(3, rank), ph = MODE ? 1 : 0;
        int whole = 0;
#pragma unroll 1
        for (int kb = 3; kb < 16;) {
          mbar_wait(wbar, ph);
          if (elect_one()) g2_issue_b(fb, STG2, dst, k0, whole);
          __syncwarp();
          kb++;
          if (++s == NS2) { s = 0; ph = kb == 2 * NS2; }
          wbar = bars + 8 * (kb == 4 ? BAR_XFREE : BAR_EMPTY2B + s);
          fb = bars + 8 * (BAR_FULL2 + s);
          dst = sb + g2_b(s, rank);
          k0 = ((hp & 12) ^ kb) * 64;
          whole = s < 3;
          asm volatile("" : "+r"(fb), "+r"(k0), "+r"(whole));
        }
      }
      __syncwarp();
    } else {
      if (MODE != 2) {
      const float dall = __bfloat162float(p.ssm_D[chb * 8 + lr]);
      {
        const int g = lane >> 2, t = lane & 3;
        uint32_t w[2][4];
#pragma unroll
        for (int h = 0; h < 2; h++) {
          const uint2 x = __ldg(reinterpret_cast<const uint2*>(p.shift_k + ((chb & ~1) * 8 + h * 8 + g) * 4));
          w[h][0] = __byte_perm(x.x, x.x, 0x1010);
          w[h][1] = __byte_perm(x.x, x.x, 0x3232);
          w[h][2] = __byte_perm(x.y, x.y, 0x1010);
          w[h][3] = __byte_perm(x.y, x.y, 0x3232);
        }
        auto swz = [](int r) { return (((r & 29) | ((r ^ (r >> 2)) & 2)) << 5) | (r & 16); };
        const uint32_t kring = sb + OFF_X + 4096 + (hw - 1) * 2 * XT, vring = kring + XT;
        const int s0 = rank * 32 + (hw - 1) * 11, s1 = hw == 3 ? rank * 32 + 32 : s0 + 11;
        const size_t goff = (size_t)(s0 * 32 + (lane >> 1)) * DM + (chb & ~1) * 8 + (lane & 1) * 8;
        const __nv_bfloat16* kg = p.k + goff;
        const __nv_bfloat16* vg = p.v + goff;
        const uint32_t d0 = swz(lane >> 1) ^ ((lane & 1) << 4), d1 = swz(16 + (lane >> 1)) ^ ((lane & 1) << 4);
        auto issue = [&](int st) {
          const uint32_t a = kring + ((st & 3) << 10);
          asm volatile("cp.async.cg.shared.global.L2::256B [%0], [%2], 16;\n"
                       "cp.async.cg.shared.global.L2::256B [%1], [%2 + 32768], 16;\n"
                       "cp.async.cg.shared.global.L2::256B [%0 + 8192], [%3], 16;\n"
                       "cp.async.cg.shared.global.L2::256B [%1 + 8192], [%3 + 32768], 16;\n"
                       ::"r"(a + d0), "r"(a + d1), "l"(kg), "l"(vg) : "memory");
          kg += 32 * DM;
          vg += 32 * DM;
          asm volatile("" : "+l"(kg), "+l"(vg));
        };
        const int xa = 8 * (lr >> 1) + 2 * lm + (lr & 1), xb = 8 * (lr >> 1) - 4 + 2 * (lm & 1) + (lr & 1);
        const uint32_t la = swz(xa), lb = swz(xb & 31);
        const int backb = xb < 0 ? 1 : 0;
        const uint32_t ud[2] = {mapa(sb + OFF_X + g * XT + t * 16, 0), mapa(sb + OFF_X + g * XT + t * 16, 1)};
        const uint32_t ub[2] = {mapa(bars + 8 * BAR_U, 0), mapa(bars + 8 * BAR_U, 1)};
        if (tid == 320) prefetch_l2(g_tab + (chb & 63) * 32);
        if (lane == 0) mbar_wait(bars + 8 * (BAR_FULLB + NS1B - 1), 0);
        __syncwarp();
        if (lane >= 24) cp_async16(kring + (((s0 - 1) & 3) << 10) + d1, s0 > 0 ? kg - 16 * DM : kg, s0 > 0 ? 16 : 0);
        issue(s0);
        asm volatile("cp.async.commit_group;\n" ::: "memory");
        issue(s0 + 1);
        asm volatile("cp.async.commit_group;\n" ::: "memory");
        const __nv_bfloat16* hg = p.ssm_k + (size_t)chb * 8 * SEQ + lane * 64;
        uint32_t tn = (uint32_t)clock();
#pragma unroll 1
        for (int st = s0; st < s1; st++) {
          tn += PSTEP;
          while ((int)((uint32_t)clock() - tn) < 0) __nanosleep(100);
          if (st + 2 < s1) issue(st + 2);
          if (hw == 1 && st - s0 < 8) prefetch_l2(hg);
          hg += SEQ;
          asm volatile("" : "+l"(hg));
          asm volatile("cp.async.commit_group;\n" ::: "memory");
          asm volatile("cp.async.wait_group 2;\n" ::: "memory");
          __syncwarp();
#pragma unroll
          for (int h = 0; h < 2; h++) {
            uint32_t e[6], vv[4], e4[4];
            ldsm4t(e4, kring + ((st & 3) << 10) + (la ^ (h << 4)));
            ldsm2t(e[0], e[1], kring + (((st - backb) & 3) << 10) + (lb ^ (h << 4)));
            ldsm4t(vv, vring + ((st & 3) << 10) + (la ^ (h << 4)));
            e[2] = e4[0]; e[3] = e4[1]; e[4] = e4[2]; e[5] = e4[3];
            uint32_t o[5];
#pragma unroll
            for (int i = 0; i < 5; i++) o[i] = __byte_perm(e[i], e[i + 1], 0x5432);
#pragma unroll
            for (int i = 0; i < 4; i++) {
              uint32_t a = bmul2(o[i], w[h][3]);
              a = bfma2(e[i + 1], w[h][2], a);
              a = bfma2(o[i + 1], w[h][1], a);
              a = bfma2(e[i + 2], w[h][0], a);
              vv[i] = bmul2(a, vv[i]);
            }
            st_async128(ud[h] + (st ^ (g & 1)) * 64, ub[h], vv[0], vv[1], vv[2], vv[3]);
          }
          __syncwarp();
        }
        fence_async_smem();
        PROF(16);
      }
      nb_sync(NB_HELP3, 96);
      if (hw == 1 && elect_one()) {
        mbar_expect_tx(bars + 8 * BAR_H, 8 * 4096 + 6144);
#pragma unroll 1
        for (int c = 0; c < 8; c++)
          bulk_load(sb + OFF_X + c * XT + 4096, p.ssm_k + (size_t)(chb * 8 + c) * SEQ, 4096, bars + 8 * BAR_H);
        bulk_load(sb + OFF_T16, g_tab, 2048, bars + 8 * BAR_H);
        bulk_load(sb + OFF_T32, g_tab + 512, 4096, bars + 8 * BAR_H);
      }
      __syncwarp();
      {
        if (hw == 3) {
          const char* wo = (const char*)p.wo + chb * 16384 + lane * 128;
#pragma unroll
          for (int i = 0; i < 4; i++) prefetch_l2(wo + i * 4096);
        }
        const int ck = 16 * (lane >> 4) + 2 * lr + (((lane >> 3) ^ (lane >> 2)) & 1);
        const uint32_t xo = (ck >> 1) * 64, xs = ((ck & 1) ^ (lr >> 1)) << 4;
#pragma unroll 1
        for (int job = hw - 1; job < 16; job += 3) {
          const int c = job & 7;
          uint4 a[8];
          float dv = __shfl_sync(0xffffffffu, dall, c);
          if (job < 8 || lane) dv = 0.f;
          const uint32_t xt = sb + OFF_X + c * XT + (job >> 3) * 4096;
          mbar_wait(bars + 8 * (job < 8 ? BAR_U : BAR_H), 0);
#pragma unroll
          for (int i = 0; i < 8; i++) a[i] = lds128(xt + i * 512 + ((ck ^ (job < 8 ? (c & 1) << 2 : 0)) << 4));
          dv += bf_lo(a[0].x);
          uint32_t m[2] = {bmaxabs2(pack_bf16(dv, 0.f), bmaxabs2(a[0].x, a[0].y)), bmaxabs2(a[0].z, a[0].w)};
#pragma unroll
          for (int i = 1; i < 8; i++) {
            m[0] = bmaxabs2(bmaxabs2(m[0], a[i].x), a[i].y);
            m[1] = bmaxabs2(bmaxabs2(m[1], a[i].z), a[i].w);
          }
          m[0] = bmaxabs2(m[0], m[1]);
          const int f = max(252 - (int)(__reduce_max_sync(0xffffffffu, max(m[0] & 0x7fffu, (m[0] >> 16) & 0x7fffu)) >> 7), 1);
          if (lane == 0) asm volatile("st.shared.u32 [%0], %1;\n" ::"r"(sb + OFF_EX + job * 4), "r"(f) : "memory");
          if (f < 113) {
#pragma unroll
            for (int i = 0; i < 8; i++)
              a[i] = make_uint4(bmul2(a[i].x, f * 0x00800080u), bmul2(a[i].y, f * 0x00800080u), bmul2(a[i].z, f * 0x00800080u),
                                bmul2(a[i].w, f * 0x00800080u));
          }
          const uint32_t mul = (f < 113 ? 15 : f - 112) * 0x00800080u;
          auto cv = [&](uint32_t x) {
            x = bmul2(x, mul);
            return (x & 0x0fff0fffu) * 7 + x;
          };
          const uint32_t dst = xt + xo;
#pragma unroll
          for (int i = 0; i < 8; i++)
            sts128(dst + (i >> 2) * 2048 + (i & 1) * 1024 + (xs ^ ((i & 2) << 4)),
                   i ? cv(a[i].x) : __byte_perm(pack_f16(dv * __uint_as_float(f << 23), 0.f), cv(a[i].x), 0x7610), cv(a[i].y),
                   cv(a[i].z), cv(a[i].w));
        }
        fence_async_smem();
        __syncwarp();
        if (lane == 0) mbar_arrive(bars + 8 * BAR_X);
        PROF(19);
      }
      if (hw < 3) {
#pragma unroll 1
        for (int n = 0; n < SPIN_LIMIT && !mbar_try(bars + 8 * (BAR_Y + hw - 1), 0); n++) __nanosleep(100);
        send_y((hw - 1) * 4 * XT, 2 * XT, 0);
        __syncwarp();
        if (lane == 0) mbar_arrive(bars + 8 * (BAR_Y + 2));
        PROF(32);
        const int c8 = 2 * lm + (lr & 1), src = (lr >> 1) & 1;
        uint32_t fa = sb + OFF_X + c8 * XT + rank * 4096 + (src == rank ? 0 : 1024) + (hw - 1) * 512;
        const uint32_t fx = ((lr >> 2) ^ ((lr & 3) << 1)) << 4;
        uint32_t qa = sb + OFF_Q0 + (hw - 1) * 8192 + (lane >> 3) * 128 + (lane & 2) * 32 + (lane & 4) * 8 + (lane & 1) * 16;
        uint4* og = reinterpret_cast<uint4*>(p.out + (size_t)(rank * 512 + (hw - 1) * 256 + (lane & 2) * 4 + (lane >> 2)) * (2 * DM) +
                                             (chb & ~1) * 8 + (lane & 1) * 8);
        mbar_wait(bars + 8 * BAR_Q, 0);
        uint32_t tn = 0;
#pragma unroll 1
        for (int j = 0; j < 16; j++) {
          if (j == 1 && hw == 2) {
            mbar_wait(bars + 8 * (BAR_Y + 3), 0);
            send_y(2 * XT, 4 * XT, 1);
            fence_async_smem();
            __syncwarp();
            if (lane == 0) mbar_arrive(bars + 8 * BAR_XFREE);
            tn = (uint32_t)clock();
          }
          if (!(j & 7)) {
            mbar_wait(bars + 8 * (BAR_LAND + (j >> 3)), 0);
            tn = (uint32_t)clock() + (hw - 1) * (FPACE / 2);
            PROF2(33 + (j >> 1));
          }
#pragma unroll
          for (int i = 0; i < 2; i++) {
            uint32_t y[4];
            const uint4 q = lds128(qa + i * 512);
            ldsm4t(y, fa + (j & 6) * 64 + (fx ^ (i << 5) ^ ((j & 1) << 6) ^ ((j & 2) << 3)));
            while ((int)((uint32_t)clock() - tn) < 0) __nanosleep(50);
            tn += hw == 2 ? FPACE2 : FPACE;
            og[i * 16 * (2 * DM / 8)] = make_uint4(bmul2(q.x, y[0]), bmul2(q.y, y[1]), bmul2(q.z, y[2]), bmul2(q.w, y[3]));
          }
          qa += j == 7 ? OFF_Q1 - OFF_Q0 - 7168 : 1024;
          if (j == 7) fa += 2048;
          og += (j == 7 ? 1024 - 224 : 32) * (2 * DM / 8);
        }
        PROF(22);
      }
      }
      if (MODE != 1 && hw == 3) {
        const uint32_t epoch = ld_relaxed(g_flag_o + FS * cta) + 1;
        if (MODE == 0) nb_sync(NB_G1END, 288);
        if (elect_one()) {
#pragma unroll
          for (int kb = 0; kb < 3; kb++)
            g2_issue_b(bars + 8 * (BAR_FULL2 + kb), kb || MODE ? STG2 : STG2 / 2, sb + g2_b(kb, 0), g2_k(kb) * 64, true);
        }
        __syncwarp();
        const __nv_bfloat16* osrc = g_o + (size_t)(rb2 >> 1) * 16 * 16384 + hsel * 8192;
        if (MODE == 0) __nanosleep(1500);
        mbar_wait(bars + 8 * (BAR_EMPTY2 + 2), 0);
        const uint32_t* flag = g_flag_o + FS * ((rb2 >> 1) * 16 + g2_k(lane & 15));
        uint32_t ready = MODE == 0 ? 0u : ~0u;
        int s = 1, ph = 0;
#pragma unroll 1
        for (int kb = 2; kb < 16; kb++) {
          if (++s == NS2) { s = 0; ph ^= 1; }
          uint32_t fb = bars + 8 * (BAR_FULL2 + s), dst = sb + g2_a(s, hsel) + rank * 8192;
          const __nv_bfloat16* src = osrc + rank * 4096 + (uint32_t)g2_k(kb) * 16384;
          asm volatile("" : "+r"(fb), "+r"(dst), "+l"(src));
          if (!(ready >> kb & 1)) {
#pragma unroll 1
            for (int n = 0; n < SPIN_LIMIT && !(ready >> kb & 1); n++)
              ready = __ballot_sync(0xffffffffu, ld_acquire(flag) == epoch);
            fence_async_all();
          }
          if (kb == 2) PROF(21);
          if (MODE == 0 && kb == 4 && rank == 1) mbar_wait(bars + 8 * BAR_TAB, 0);
          mbar_wait(fb + 8 * (BAR_EMPTY2 - BAR_FULL2), ph);
          if (elect_one()) {
            asm volatile(
                "cp.async.bulk.shared::cluster.global.mbarrier::complete_tx::bytes.multicast::cluster [%0], [%1], %2, [%3], %4;\n"
                ::"r"(dst), "l"(src), "r"(8192), "r"(fb), "h"((uint16_t)3) : "memory");
          }
          __syncwarp();
        }
      }
    }
    cluster_sync_all();
    PROF_DUMP();
  } else {
    asm volatile("barrier.cluster.arrive.relaxed.aligned;\n" ::: "memory");
    asm volatile("setmaxnreg.inc.sync.aligned.u32 %0;\n" :: "n"(REG_MATH));
    if (halo_cta || MODE == 2) asm volatile("barrier.cluster.wait.aligned;\n" ::: "memory");
    if (warp == 0) PROF2(26);
    const int wg = warp >> 2;
    const int wtid = tid & 127;
    const bool signaller = (wtid == 0) || (wtid == 32);
    const uint32_t rbars = mapa(bars, wtid >> 5 & 1);

    if (halo_cta) {
      const uint32_t epoch = ld_relaxed(g_flag_o + FS * (16 + blockIdx.x * 4)) + 1;
      float acc0[64], acc1[64];
      int s = wg, ph = 0;
#pragma unroll 1
      for (int kb = 0; kb < 16; kb++) {
        mbar_wait(bars + 8 * (BAR_FULLB + s), ph);
        const uint32_t st = sb + s * STGH;
        const uint64_t da = mkdesc(st, 16, 1024, 1);
        const uint64_t db = mkdesc(st + 8192, 8192, 1024, 1);
        wg_fence();
#pragma unroll
        for (int kk = 0; kk < 4; kk++) {
          wgmma_n128(acc0, da + 2 * kk, db + 128 * kk, kb + kk);
          wgmma_n128(acc1, da + 2 * kk, db + 1024 + 128 * kk, kb + kk);
        }
        wg_commit();
        wg_wait<0>();
        if (kb == 15) PROF(37);
        if (wtid < 2) mbar_arrive(bars + 8 * (BAR_EMPTYB + s));
        if ((s += 2) >= NS1B) { s -= NS1B; ph ^= 1; }
      }
      fence_regs(acc0);
      fence_regs(acc1);
      if ((warp & 3) != 3) {
        auto put = [&](const float (&acc)[64], int hp0) {
#pragma unroll
          for (int n = 0; n < 4; n++) {
            uint32_t x[8];
#pragma unroll
            for (int c = 0; c < 8; c++) {
              x[c] = pack_bf16(acc[32 * (n >> 1) + 4 * c + 2 * (n & 1)], acc[32 * (n >> 1) + 4 * c + 2 * (n & 1) + 1]);
              if (wg) x[c] = movm(x[c]);
            }
            uint4* dst = g_halo + (((n & 1) * 4 + (warp & 3) + 1) * 16 + blockIdx.x * 4 + hp0 + (n >> 1)) * 192 + wg * 96 + lane;
            st_b128(dst, x[0], x[1], x[2], epoch);
            st_b128(dst + 32, x[3], x[4], x[5], epoch);
            st_b128(dst + 64, x[6], x[7], 0, epoch);
          }
        };
        put(acc0, 0);
        put(acc1, 2);
      }
      PROF(36);
      cluster_sync_all();
      return;
    }

    float acc[64];
    const uint32_t g2rel = wtid ? mapa(bars, rank) + 8 * BAR_EMPTY2B : mapa(bars, wg) + 8 * BAR_EMPTY2;
    uint32_t g2a = (uint32_t)mkdesc(sb + wg * 8192, 16, 0, 0), g2b = (uint32_t)mkdesc(sb, 8192, 0, 0);
    auto g2_block = [&](bool first, int s, int ph) {
      mbar_wait(bars + 8 * (BAR_FULL2 + s), ph);
      const uint32_t da = g2a + (g2_a(s, hsel) >> 4), db = g2b + (g2_b(s, rank) >> 4), dc = db + (g2_bk(s) >> 4);
      wg_fence();
      if (first) wgmma_n128z(acc, da, db);
      else wgmma_n128a(acc, da, db);
      wgmma_n128a(acc, da + 2, db + 128);
      wgmma_n128a(acc, da + 4, dc);
      wgmma_n128a(acc, da + 6, dc + 128);
      wg_commit();
    };
    if (MODE != 2) {
    uint32_t a1[2][4], sc[2];
    C2 t[2];
    {
      float acc0[96], acc1[96];
      int sa = 0, pha = 0;
      uint64_t db0 = mkdesc(sb + OFF_1B, 4096, 1024, 1);
      const uint64_t da0 = mkdesc(sb + wg * 16384, 16, 2048, 1);
      const bool sigb = wtid == 64;
      uint32_t rela = 0;
#pragma unroll 1
      for (int r = 0; r < 3; r++) {
#pragma unroll
        for (int i = 0; i < 2 * NS1B; i++) {
          const uint64_t da = da0 + sa * (STG1A >> 4) + (i & 1) * 4, db = db0 + (i % NS1B) * (STG1B >> 4);
          if (i || r) {
            if (!(i & 1)) mbar_wait(bars + 8 * (BAR_FULLA + sa), pha);
            mbar_wait(bars + 8 * (BAR_FULLB + i % NS1B), i / NS1B);
          } else {
            asm volatile("cp.async.wait_group 0;\n" ::: "memory");
            fence_async_smem();
            nb_sync(NB_FIRST, 256);
            PROF(0 + wg);
          }
          wg_fence();
          wgmma_n192(acc0, da + 64, db, i ? 1 : r);
          wgmma_n192(acc1, da, db, i ? 1 : r);
          wgmma_n192(acc0, da + 66, db + 128, 1);
          wgmma_n192(acc1, da + 2, db + 128, 1);
          wg_commit();
          wg_wait<1>();
          if (i || r) {
            if (sigb) mbar_arrive(bars + 8 * (BAR_EMPTYB + (i + NS1B - 1) % NS1B));
            if (!(i & 1) && signaller) mbar_arrive_cluster(rela);
          } else {
            asm volatile("barrier.cluster.wait.aligned;\n" ::: "memory");
          }
          if (i & 1) {
            rela = rbars + 8 * (BAR_EMPTYA + sa);
            if (++sa == NS1A) { sa = 0; pha ^= 1; }
          }
        }
        db0 += p.zero;
      }
      const int lr = lane & 7, lm = lane >> 3;
      const bool le0 = 2 * (lane & 3) <= (lane >> 2), le1 = 2 * (lane & 3) + 1 <= (lane >> 2);
      const uint32_t maskLE = (le0 ? 0x0000FFFFu : 0u) | (le1 ? 0xFFFF0000u : 0u);
      uint32_t q[4][8], k[5][8], vt[5][8];
      {
        static_assert(15 % NS1A == 0 && 30 % NS1B == 0, "slots of the last k blocks");
        asm volatile("ld.volatile.global.v4.u32 {%0,%1,%2,%3}, [%4];\n"
                     : "=r"(t[0].r), "=r"(t[1].r), "=r"(t[0].i), "=r"(t[1].i) : "l"(g_tab + 1536 + wtid * 4) : "memory");
        mbar_wait(bars + 8 * BAR_FULLA, 1);
        mbar_wait(bars + 8 * BAR_FULLB, 0);
        mbar_wait(bars + 8 * (BAR_FULLB + 1), 0);
        mbar_wait(bars + 8 * (BAR_EMPTYA + 1), 0);
        mbar_wait(bars + 8 * BAR_H, 0);
        const uint64_t da = mkdesc(sb + wg * 16384, 16, 2048, 1);
        const uint64_t db = mkdesc(sb + OFF_1B, 4096, 1024, 1);
        wg_fence();
#pragma unroll
        for (int i = 0; i < 4; i++) wgmma_n192(acc0, da + 64 + 2 * i, db + (i >> 1) * (STG1B >> 4) + (i & 1) * 128, 1);
        wg_commit();
#pragma unroll
        for (int i = 0; i < 2; i++) wgmma_n192(acc1, da + 2 * i, db + (i >> 1) * (STG1B >> 4) + (i & 1) * 128, 1);
        wg_commit();
        wg_wait<1>();
        fence_regs(acc0);
        PROFA(45, 0);
        attn_pack<8, 1, false>(acc0, k[4]);
        attn_pack<16, 1, true>(acc0, vt[4]);
        const uint32_t kh = sb + (warp == 7 ? OFF_OP + 7 * 4096 : OFF_KH + (warp + 1) * 2048) + lane * 16;
        sts128(kh, k[4][0], k[4][1], k[4][2], k[4][3]);
        sts128(kh + 512, k[4][4], k[4][5], k[4][6], k[4][7]);
#pragma unroll
        for (int i = 0; i < 4; i++) sts64(kh - lane * 8 + 1024 + 256 * i, vt[4][2 * i], vt[4][2 * i + 1]);
        __syncwarp();
        if (lane == 0) mbar_arrive(bars + 8 * (BAR_KH + 1 + warp));
#pragma unroll
        for (int i = 2; i < 4; i++) wgmma_n192(acc1, da + 2 * i, db + (i >> 1) * (STG1B >> 4) + (i & 1) * 128, 1);
        wg_commit();
        attn_pack<0, 0, false>(acc0, q[1]);
        attn_pack<0, 1, false>(acc0, q[3]);
        attn_pack<8, 0, false>(acc0, k[2]);
        attn_pack<16, 0, true>(acc0, vt[2]);
        uint32_t z = p.zero;
#pragma unroll
        for (int i = 0; i < 8; i++) z &= q[1][i] & q[3][i];
#pragma unroll
        for (int i = 0; i < 8; i += 2) z &= k[2][i] & k[2][i + 1];
        if (lane == 0) mbar_arrive(bars + 8 * BAR_STG + z);
        wg_wait<0>();
        fence_regs(acc1);
        if (MODE == 0) nb_arrive(NB_G1END, 288);
      }
      PROF(2 + wg);
      mbar_wait(bars + 8 * (BAR_KH + warp), 0);
      {
        const uint32_t kh = sb + OFF_KH + warp * 2048 + lane * 16;
#pragma unroll
        for (int i = 0; i < 2; i++) {
          const uint4 t = lds128(kh + 512 * i);
          k[0][4 * i] = t.x; k[0][4 * i + 1] = t.y; k[0][4 * i + 2] = t.z; k[0][4 * i + 3] = t.w;
        }
#pragma unroll
        for (int i = 0; i < 4; i++) {
          const uint2 t = lds64(kh - lane * 8 + 1024 + 256 * i);
          vt[0][2 * i] = t.x; vt[0][2 * i + 1] = t.y;
        }
      }
      attn_pack<0, 0, false>(acc1, q[0]);
      attn_pack<0, 1, false>(acc1, q[2]);
      attn_pack<8, 0, false>(acc1, k[1]);
      attn_pack<8, 1, false>(acc1, k[3]);
      {
        float x[8][2];
        uint32_t pp[8];
        const bool first = warp == 0 && gidx == 0;
#pragma unroll
        for (int hd = 0; hd < 2; hd++) {
#pragma unroll
          for (int j = 0; j < 4; j += 2) {
            float s0[4], s1[4], s2[4];
            attn_qk(s2, q[j], q[j + 1], k[j + 2], 4 * hd);
            attn_qk(s1, q[j], q[j + 1], k[j + 1], 4 * hd);
            attn_qk(s0, q[j], q[j + 1], k[j], 4 * hd);
            if (j == 0 && first) s0[0] = s0[1] = -1e9f / 0.17677669529663687f;
            x[2 * j + hd][0] = le0 ? s1[0] : s0[0];
            x[2 * j + hd][1] = le1 ? s1[1] : s0[1];
            x[2 * j + 2 + hd][0] = le0 ? s2[2] : s1[2];
            x[2 * j + 2 + hd][1] = le1 ? s2[3] : s1[3];
          }
        }
        PROFA(40, __float_as_uint(x[1][0] + x[7][1]));
        attn_pack<16, 0, true>(acc1, vt[1]);
        attn_pack<16, 1, true>(acc1, vt[3]);
        quad_softmax<8>(x, pp);
        PROFA(41, pp[1] + pp[7]);
        ldsm4(a1[0], sb + OFF_T32 + (warp & 3) * 1024 + lane * 16);
        ldsm4(a1[1], sb + OFF_T32 + 512 + (warp & 3) * 1024 + lane * 16);
        const uint32_t obase = sb + OFF_OP + (warp * 32 + lr) * 128;
#pragma unroll
        for (int n = 0; n < 8; n++) {
          const uint32_t dst = obase + (n >> 1) * 1024 + (((4 * (n & 1) + lm) ^ lr) << 4);
          if (n & 2) attn_pv<true>(dst, vt[n >> 1], vt[(n >> 1) + 1], 4 * (n & 1), pp[n], maskLE);
          else attn_pv<false>(dst, vt[n >> 1], vt[(n >> 1) + 1], 4 * (n & 1), pp[n], maskLE);
        }
      }
      PROFA(42, 0);
    }

    {
      const int w = warp & 3;
      const int lr = lane & 7, lm = lane >> 3;
      const uint32_t xb = sb + OFF_X + wg * 4 * XT;
      auto uo = [](int c) { return (c & 1) * 2 * XT + (c >> 1) * 2048; };
      const uint64_t dc2 = mkdesc(sb + OFF_T16, 512, 128, 0), dc3 = mkdesc(sb + OFF_T16, 128, 512, 0);
      const uint64_t dc4 = mkdesc(sb + OFF_T32, 128, 256, 0);
      const uint64_t dx = mkdesc(xb, 4096, 512, 2), dz = mkdesc(xb, 4096, 256, 3);
      const uint32_t zs = xb + (w * 16 + (lm & 1) * 8 + lr) * 32 + (((lm >> 1) ^ (lr >> 2)) << 4);
      const uint32_t ys = xb + w * 4096 + (lm >> 1) * 256 + ((lr * 32 + (((lm & 1) ^ (lr >> 2)) << 4)) ^ (rank << 6) ^ ((w & 2) << 4));
      const bool own = (w & 1) == rank;
      const uint32_t ybar = mapa(bars, own ? rank ^ 1 : rank) + 8 * BAR_Y;
      uint32_t d[2][32], pa[2][4][2][4], e[4][4][8], ya[2][2][2][4], v[2][2][8];
      C2 s1[2][2][2];
      float o[2][16];
      auto rows = [&](int c) {
        fft_rows(d[c & 1], a1, dx + (uo(c) >> 4));
        wg_commit();
      };
      auto cols = [&](int c) {
        const int s = c & 1;
        fence_regs(d[s]);
#pragma unroll
        for (int i = 0; i < 16; i++) {
          const C2 z = crot(C2{d[s][2 * i], d[s][2 * i + 1]}, t[i & 1]);
          pa[s][i >> 2][i & 1][(i >> 1) & 1] = z.r;
          pa[s][i >> 2][i & 1][2 + ((i >> 1) & 1)] = z.i;
        }
        wg_fence();
#pragma unroll
        for (int i = 0; i < 4; i++) fft_cols<0>(e[c][i], pa[s][i], dc2);
        wg_commit();
      };
      auto prod = [&](int c, int n) {
        const int s = c & 1;
        fence_regs(e[c][2 * n]);
        fence_regs(e[c][2 * n + 1]);
#pragma unroll
        for (int j = 0; j < 2; j++) {
          const C2 u0 = cget(e[s][2 * n], j, 0), u1 = cget(e[s][2 * n], j, 1);
          const C2 h0 = cget(e[s][2 * n + 1], j, 0), h1 = cget(e[s][2 * n + 1], j, 1);
          C2 y0, y1;
          if (c < 2) {
            y0 = cmul(h0, u0);
            s1[s][n][j] = cfma(h0, u1, cmul(h1, u0));
            y1 = C2{hadd2(s1[s][n][j].r, y0.i), hadd2(s1[s][n][j].i, hneg2(y0.r))};
          } else {
            const C2 u2 = cget(e[c][2 * n], j, 0), u3 = cget(e[c][2 * n], j, 1);
            const C2 h2 = cget(e[c][2 * n + 1], j, 0), h3 = cget(e[c][2 * n + 1], j, 1);
            const C2 s2 = cfma(h0, u2, cfma(h2, u0, cmul(h1, u1)));
            y0 = C2{hadd2(s2.r, s1[s][n][j].i), hadd2(s2.i, hneg2(s1[s][n][j].r))};
            y1 = cfma(h0, u3, cfma(h1, u2, cfma(h2, u1, cfma(h3, u0, C2{s2.i, hneg2(s2.r)}))));
          }
          ya[s][n][j][0] = y0.r;
          ya[s][n][j][1] = y1.r;
          ya[s][n][j][2] = y0.i;
          ya[s][n][j][3] = y1.i;
        }
      };
      auto icols = [&](int c) {
        wg_fence();
        fft_cols<1>(v[c & 1][0], ya[c & 1][0], dc3);
        fft_cols<1>(v[c & 1][1], ya[c & 1][1], dc3);
        wg_commit();
      };
      auto stage = [&](int c) {
        const int s = c & 1;
        fence_regs(v[s][0]);
        fence_regs(v[s][1]);
#pragma unroll
        for (int b = 0; b < 4; b++) {
          const C2 x0 = cget(v[s][b >> 1], 0, b & 1), x1 = cget(v[s][b >> 1], 1, b & 1);
          const C2 z0 = crot(C2{x0.i, x0.r}, t[0]), z1 = crot(C2{x1.i, x1.r}, t[1]);
          stsm4(zs + uo(c) + b * 4096, z0.i, z0.r, z1.i, z1.r);
        }
      };
      auto back = [&](int c) {
        fft_back(o[c & 1], dz + (uo(c) >> 4), dc4);
        wg_commit();
      };
      auto out = [&](int c) {
        float (&r)[16] = o[c & 1];
        fence_regs(r);
#pragma unroll
        for (int i = 0; i < 16; i += 8)
          stsm4t(ys + uo(c) + 64 * i, bmul2(pack_bf16(r[i], r[i + 1]), sc[c & 1]), bmul2(pack_bf16(r[i + 2], r[i + 3]), sc[c & 1]),
                 bmul2(pack_bf16(r[i + 4], r[i + 5]), sc[c & 1]), bmul2(pack_bf16(r[i + 6], r[i + 7]), sc[c & 1]));
      };
      auto signal = [&](int yb, int land) {
        __syncwarp();
        if (lane == 0) {
          mbar_arrive_cluster(ybar + 8 * yb);
          if (own && land >= 0) mbar_arrive(bars + 8 * (BAR_LAND + land));
        }
      };
      mbar_wait(bars + 8 * BAR_X, 0);
      wg_fence();
      rows(0);
      rows(1);
      fence_async_smem();
      nb_arrive(NB_OREADY, 288);
#pragma unroll
      for (int i = 0; i < 2; i++) {
        const uint32_t ex = sb + OFF_EX + wg * 16 + (w & 2) * 2 + 8 * i;
        sc[i] = min(max(381 - (int)lds32(ex) - (int)lds32(ex + 32), 1), 254) * 0x00800080u;
      }
      PROF(34 + wg);
      wg_wait<1>();
      cols(0);
      wg_wait<1>();
      cols(1);
      rows(2);
      nb_sync(NB_CONV + wg, 128);
      wg_wait<2>();
      prod(0, 0);
      prod(0, 1);
      icols(0);
      wg_wait<2>();
      prod(1, 0);
      prod(1, 1);
      icols(1);
      PROF3(40 + 10 * wg);
      wg_wait<1>();
      stage(0);
      wg_wait<0>();
      stage(1);
      fence_async_smem();
      cols(2);
      PROF3(41 + 10 * wg);
      nb_sync(NB_CONV + wg, 128);
      back(0);
      back(1);
      wg_wait<2>();
      prod(2, 0);
      wg_fence();
      rows(3);
      wg_wait<1>();
      out(0);
      out(1);
      signal(wg, 0);
      PROF3(42 + 10 * wg);
      prod(2, 1);
      icols(2);
      wg_wait<1>();
      cols(3);
      PROF3(43 + 10 * wg);
      wg_wait<1>();
      stage(2);
      fence_async_smem();
      wg_wait<0>();
      prod(3, 0);
      nb_sync(NB_CONV + wg, 128);
      wg_fence();
      back(2);
      prod(3, 1);
      icols(3);
      PROF3(44 + 10 * wg);
      wg_wait<1>();
      out(2);
      signal(2, -1);
      wg_wait<0>();
      stage(3);
      PROF3(45 + 10 * wg);
      fence_async_smem();
      nb_sync(NB_CONV + wg, 128);
      wg_fence();
      back(3);
      constexpr int G = MODE == 0;
      if (G) {
        mbar_wait(bars + 8 * (BAR_EMPTY2 + 4), 0);
        g2_block(true, 0, 0);
      }
      wg_wait<G>();
      if (lane == 0) mbar_arrive_cluster(mapa(bars, 1) + 8 * BAR_TAB);
      out(3);
      signal(3, 1);
      PROF(6 + wg);
    }
    }

    if (MODE != 1) {
      if (MODE == 2) g2_block(true, 0, 0);
      const int lr = lane & 7, lm = lane >> 3;
      const uint32_t wb = sb + g2_a(1, 0) + warp * 2048;
      const int orow = (rb2 & 7) * 128 + warp * 16;
      uint4* og = reinterpret_cast<uint4*>(p.out + (size_t)(2 * (orow + lm) + (rb2 >> 3)) * (2 * DM) + DM + cb2 * 128 + lr * 8);
      uint32_t wst = wb + (lr + 8 * (lm & 1)) * 128, wsx = ((lm >> 1) ^ lr) << 4, wld = wb + lm * 128, wlx = (lr ^ lm) << 4;
      asm volatile("" : "+l"(og), "+r"(wst), "+r"(wsx), "+r"(wld), "+r"(wlx));
#pragma unroll 1
      for (int r = 0; r < 3; r++) {
        const bool hold = r == 2 && wg != LEADWG;
        if (hold) {
          wg_wait<0>();
          if (signaller) mbar_arrive_cluster(g2rel);
          nb_sync(NB_LEAD, 256);
        }
#pragma unroll
        for (int i = 1; i <= NS2; i++) {
          g2_block(false, i % NS2, (r & 1) ^ (i == NS2));
          if (warp == LEADWG * 4) PROF2(40 + 5 * r + i);
          if (i == 1 ? !hold : r < 2) {
            wg_wait<1>();
            if (signaller) mbar_arrive_cluster(g2rel + 8 * (i - 1));
          }
        }
        if (r == 0) PROF(8 + wg);
        g2a += p.zero;
        g2b += p.zero;
      }
      if (wg == LEADWG) nb_arrive(NB_LEAD, 256);
      asm volatile("barrier.cluster.arrive.relaxed.aligned;\n" ::: "memory");
      wg_wait<0>();
      fence_regs(acc);
      PROF(10 + wg);
#pragma unroll
      for (int h = 0; h < 2; h++) {
        const uint32_t b = h * (g2_a(3, 0) - g2_a(1, 0));
#pragma unroll
        for (int j = 8 * h; j < 8 * h + 8; j += 2)
          stsm4(wst + b + (wsx ^ ((j & 7) << 4)), pack_bf16(acc[4 * j], acc[4 * j + 1]),
                pack_bf16(acc[4 * j + 2], acc[4 * j + 3]), pack_bf16(acc[4 * j + 4], acc[4 * j + 5]),
                pack_bf16(acc[4 * j + 6], acc[4 * j + 7]));
        if (wg == LEADWG) {
          fence_async_smem();
          __syncwarp();
          if (elect_one()) {
            tma_store_3d(&tmOb, wb + b, DM + cb2 * 128 + h * 64, rb2 >> 3, orow);
            bulk_commit();
          }
        } else {
          __syncwarp();
          uint4 v[4];
#pragma unroll
          for (int i = 0; i < 4; i++) v[i] = lds128(wld + b + i * 512 + (wlx ^ ((i & 1) << 6)));
#pragma unroll
          for (int i = 0; i < 4; i++)
            asm volatile("st.global.v4.u32 [%0], {%1,%2,%3,%4};\n" ::"l"(og + i * 8 * (2 * DM / 8) + h * 8), "r"(v[i].x),
                         "r"(v[i].y), "r"(v[i].z), "r"(v[i].w) : "memory");
        }
      }
      PROF(12 + wg);
      bulk_wait0();
    } else {
      asm volatile("barrier.cluster.arrive.relaxed.aligned;\n" ::: "memory");
    }
    asm volatile("barrier.cluster.wait.aligned;\n" ::: "memory");
  }
}

typedef CUresult (*EncodeFn)(CUtensorMap*, CUtensorMapDataType, cuuint32_t, void*, const cuuint64_t*, const cuuint64_t*,
                             const cuuint32_t*, const cuuint32_t*, CUtensorMapInterleave, CUtensorMapSwizzle,
                             CUtensorMapL2promotion, CUtensorMapFloatOOBfill);

void make_map(EncodeFn enc, CUtensorMap* tm, const void* base, int rank, const cuuint64_t* dims, const cuuint64_t* strides,
              const cuuint32_t* box, CUtensorMapSwizzle swz) {
  cuuint32_t es[5] = {1, 1, 1, 1, 1};
  enc(tm, CU_TENSOR_MAP_DATA_TYPE_BFLOAT16, rank, const_cast<void*>(base), dims, strides, box, es,
      CU_TENSOR_MAP_INTERLEAVE_NONE, swz, CU_TENSOR_MAP_L2_PROMOTION_L2_256B, CU_TENSOR_MAP_FLOAT_OOB_FILL_NONE);
}

}

extern "C" void kernel_launch(void* const* d_in, const int* in_sizes, int n_in, void* d_out, int out_size) {
  static EncodeFn enc = nullptr;
  static bool coresident = true;
  if (!enc) {
    void* fn = nullptr;
    cudaDriverEntryPointQueryResult qr;
    cudaGetDriverEntryPoint("cuTensorMapEncodeTiled", &fn, cudaEnableDefault, &qr);
    enc = (EncodeFn)fn;
    cudaFuncSetAttribute(fused_kernel<0>, cudaFuncAttributeMaxDynamicSharedMemorySize, SMEM_BYTES);
    cudaFuncSetAttribute(fused_kernel<1>, cudaFuncAttributeMaxDynamicSharedMemorySize, SMEM_BYTES);
    cudaFuncSetAttribute(fused_kernel<2>, cudaFuncAttributeMaxDynamicSharedMemorySize, SMEM_BYTES);
    cudaLaunchConfig_t cfg = {};
    cfg.gridDim = dim3(NCTA);
    cfg.blockDim = dim3(NTHREADS);
    cfg.dynamicSmemBytes = SMEM_BYTES;
    cudaLaunchAttribute at;
    at.id = cudaLaunchAttributeClusterDimension;
    at.val.clusterDim.x = 2;
    at.val.clusterDim.y = 1;
    at.val.clusterDim.z = 1;
    cfg.attrs = &at;
    cfg.numAttrs = 1;
    int nclusters = 0;
    if (cudaOccupancyMaxActiveClusters(&nclusters, fused_kernel<0>, &cfg) == cudaSuccess) coresident = nclusters >= NCTA / 2;
    (void)cudaGetLastError();
  }
  CUtensorMap tmX, tmW, tmWo, tmWp, tmQ, tmOb, tmXh, tmWh;
  {
    cuuint64_t dims[3] = {1024, 2, 1024};
    cuuint64_t str[2] = {2048, 4096};
    cuuint32_t box[3] = {64, 1, 128};
    make_map(enc, &tmX, d_in[6], 3, dims, str, box, CU_TENSOR_MAP_SWIZZLE_128B);
  }
  {
    cuuint64_t dims[3] = {1024, 1024, 3};
    cuuint64_t str[2] = {6144, 2048};
    cuuint32_t box[3] = {64, 32, 3};
    make_map(enc, &tmW, d_in[7], 3, dims, str, box, CU_TENSOR_MAP_SWIZZLE_128B);
  }
  {
    cuuint64_t dims[3] = {64, 1024, 16};
    cuuint64_t str[2] = {2048, 128};
    cuuint32_t box[3] = {64, 64, 2};
    cuuint32_t piece[3] = {64, 32, 1};
    make_map(enc, &tmWo, d_in[8], 3, dims, str, box, CU_TENSOR_MAP_SWIZZLE_128B);
    make_map(enc, &tmWp, d_in[8], 3, dims, str, piece, CU_TENSOR_MAP_SWIZZLE_128B);
  }
  {
    cuuint64_t dims[5] = {1024, 2, 2, 4, 128};
    cuuint64_t str[4] = {2048, 8 * 2048, 2 * 2048, 16 * 2048};
    cuuint32_t box[5] = {16, 2, 2, 4, 32};
    make_map(enc, &tmQ, d_in[0], 5, dims, str, box, CU_TENSOR_MAP_SWIZZLE_NONE);
  }
  {
    cuuint64_t dims[3] = {2048, 2, 1024};
    cuuint64_t str[2] = {4096, 8192};
    cuuint32_t box[3] = {64, 1, 16};
    make_map(enc, &tmOb, d_out, 3, dims, str, box, CU_TENSOR_MAP_SWIZZLE_128B);
  }
  {
    cuuint64_t dims[4] = {1024, 256, 2, 4};
    cuuint64_t str[3] = {4096, 2048, 256 * 4096};
    cuuint32_t box[4] = {64, 8, 2, 3};
    make_map(enc, &tmXh, d_in[6], 4, dims, str, box, CU_TENSOR_MAP_SWIZZLE_128B);
  }
  {
    cuuint64_t dims[3] = {64, 1024, 48};
    cuuint64_t str[2] = {6144, 128};
    cuuint32_t box[3] = {64, 64, 4};
    make_map(enc, &tmWh, d_in[7], 3, dims, str, box, CU_TENSOR_MAP_SWIZZLE_128B);
  }
  Params p;
  p.q = (const __nv_bfloat16*)d_in[0];
  p.k = (const __nv_bfloat16*)d_in[1];
  p.v = (const __nv_bfloat16*)d_in[2];
  p.shift_k = (const __nv_bfloat16*)d_in[3];
  p.ssm_k = (const __nv_bfloat16*)d_in[4];
  p.ssm_D = (const __nv_bfloat16*)d_in[5];
  p.x = (const __nv_bfloat16*)d_in[6];
  p.w = (const __nv_bfloat16*)d_in[7];
  p.wo = (const __nv_bfloat16*)d_in[8];
  p.out = (__nv_bfloat16*)d_out;
  p.zero = 0;
  if (coresident) {
    fused_kernel<0><<<NCTA, NTHREADS, SMEM_BYTES>>>(p, tmX, tmW, tmWo, tmWp, tmQ, tmOb, tmXh, tmWh);
  } else {
    fused_kernel<0><<<4, NTHREADS, SMEM_BYTES>>>(p, tmX, tmW, tmWo, tmWp, tmQ, tmOb, tmXh, tmWh);
    fused_kernel<1><<<NCTA, NTHREADS, SMEM_BYTES>>>(p, tmX, tmW, tmWo, tmWp, tmQ, tmOb, tmXh, tmWh);
    fused_kernel<2><<<NCTA, NTHREADS, SMEM_BYTES>>>(p, tmX, tmW, tmWo, tmWp, tmQ, tmOb, tmXh, tmWh);
  }
}
```

```cpp
#include <cuda_runtime.h>
#include <cuda.h>
#include <cuda_bf16.h>
#include <stdint.h>

namespace {

constexpr int SEQ = 2048;
constexpr int DM = 1024;
constexpr int NCTA = 132;
constexpr int NTHREADS = 384;

constexpr int STG1A = 32768;
constexpr int NS1A = 3;
constexpr int STG1B = 12288;
constexpr int NS1B = 5;
constexpr int OFF_1B = NS1A * STG1A;
constexpr int STG2 = 32768;
constexpr int NS2 = 5;
#define PSTEP 1250
#define FPACE 260
#define FPACE2 230
#define NB0 1
#define QPF 0
#define JOIN 1
#define JS 2
#define FPACE3 180
#define PFW 11
#define SIG2 0
constexpr int LEADWG = 1;
__device__ __forceinline__ uint32_t g2_a(int s, int hsel) { return (((0x97524 >> (4 * s)) & 15) ^ (s & 5 ? 0 : hsel)) << 14; }
constexpr int OFF_Q0 = 3 << 14, OFF_Q1 = 8 << 14;
constexpr int STGH = 40960;
constexpr int OFF_KH = 1 * STG2;
constexpr int OFF_OP = 2 * STG2;
constexpr int OFF_T32 = 5 * STG2 - 4096;
constexpr int OFF_X = 5 * STG2;
constexpr int XT = 8192;
__device__ __forceinline__ uint32_t g2_b(int s, int rank) {
  return s < 3 ? (s == 2 ? 6 : s) << 14 : OFF_X + (s - 3) * 2 * XT + (rank ^ 1) * 4096;
}
__device__ __forceinline__ uint32_t g2_bk(int s) { return s < 3 ? 4096 : 4 * XT; }
constexpr int OFF_BAR = OFF_X + 8 * XT;
constexpr int OFF_EX = OFF_BAR + 960;
constexpr int OFF_T16 = 230400;
constexpr int SMEM_BYTES = OFF_T16 + 2048;
static_assert(OFF_1B + NS1B * STG1B <= OFF_T32 && OFF_X % 1024 == 0, "layout");
static_assert(NS1B * STGH <= OFF_BAR && OFF_EX + 64 <= OFF_T16 && SMEM_BYTES <= 232448, "smem");

constexpr int BAR_FULLA = 0;
constexpr int BAR_EMPTYA = 3;
constexpr int BAR_FULLB = 6;
constexpr int BAR_EMPTYB = 11;
constexpr int BAR_FULL2 = 16;
constexpr int BAR_EMPTY2 = 21;
constexpr int BAR_EMPTY2B = 44;
constexpr int BAR_X = 26;
constexpr int BAR_LAND = 42;
constexpr int BAR_TAB = 28;
constexpr int BAR_U = 29;
constexpr int BAR_H = 30;
constexpr int BAR_STG = 31;
constexpr int BAR_Y = 32;
constexpr int BAR_XFREE = 38;
constexpr int BAR_KH = 49;
constexpr int BAR_Q = 41;

constexpr int NB_LEAD = 2;
constexpr int NB_G1END = 3;
constexpr int NB_OREADY = 4;
constexpr int NB_CONV = 5;
constexpr int NB_HELP3 = 11;
constexpr int NB_FIRST = 13;

#define REG_MATH 224
#define REG_HELP 56
constexpr int SPIN_LIMIT = 1 << 20;

__device__ __align__(1024) __nv_bfloat16 g_o[SEQ * DM];
constexpr int FS = 2;
__device__ __align__(128) uint32_t g_flag_o[128 * FS];
__device__ uint4 g_halo[128 * 192];
__device__ __align__(128) const uint32_t g_tab[2048] = {
  0x2fd93000,0x2ea72f64,0x2c722da8,0x263e2a1f,0x2ea73000,0xa63e2a1f,0xafd9ada8,0xac72af64,0x2c723000,0xafd9aa1f,0x263eada8,0x2ea72f64,
  0x263e3000,0xac72af64,0x2ea72da8,0xafd9aa1f,0xa63e3000,0x2c72af64,0xaea72da8,0x2fd9aa1f,0xac723000,0x2fd9aa1f,0xa63eada8,0xaea72f64,
  0xaea73000,0x263e2a1f,0x2fd9ada8,0x2c72af64,0xafd93000,0xaea72f64,0xac722da8,0xa63e2a1f,0x263e0000,0x2c722a1f,0x2ea72da8,0x2fd92f64,
  0x2c720000,0x2fd92f64,0x263e2da8,0xaea7aa1f,0x2ea70000,0x263e2f64,0xafd9ada8,0x2c72aa1f,0x2fd90000,0xaea72a1f,0x2c72ada8,0xa63e2f64,
  0x2fd90000,0xaea7aa1f,0x2c722da8,0xa63eaf64,0x2ea70000,0x263eaf64,0xafd92da8,0x2c722a1f,0x2c720000,0x2fd9af64,0x263eada8,0xaea72a1f,
  0x263e0000,0x2c72aa1f,0x2ea7ada8,0x2fd9af64,0xafd93000,0xaea72f64,0xac722da8,0xa63e2a1f,0xaea73000,0x263e2a1f,0x2fd9ada8,0x2c72af64,
  0xac723000,0x2fd9aa1f,0xa63eada8,0xaea72f64,0xa63e3000,0x2c72af64,0xaea72da8,0x2fd9aa1f,0x263e3000,0xac72af64,0x2ea72da8,0xafd9aa1f,
  0x2c723000,0xafd9aa1f,0x263eada8,0x2ea72f64,0x2ea73000,0xa63e2a1f,0xafd9ada8,0xac72af64,0x2fd93000,0x2ea72f64,0x2c722da8,0x263e2a1f,
  0xa63e0000,0xac722a1f,0xaea72da8,0xafd92f64,0xac720000,0xafd92f64,0xa63e2da8,0x2ea7aa1f,0xaea70000,0xa63e2f64,0x2fd9ada8,0xac72aa1f,
  0xafd90000,0x2ea72a1f,0xac72ada8,0x263e2f64,0xafd90000,0x2ea7aa1f,0xac722da8,0x263eaf64,0xaea70000,0xa63eaf64,0x2fd92da8,0xac722a1f,
  0xac720000,0xafd9af64,0xa63eada8,0x2ea72a1f,0xa63e0000,0xac72aa1f,0xaea7ada8,0xafd9af64,0xa63e0000,0xac72aa1f,0xaea7ada8,0xafd9af64,
  0xac720000,0xafd9af64,0xa63eada8,0x2ea72a1f,0xaea70000,0xa63eaf64,0x2fd92da8,0xac722a1f,0xafd90000,0x2ea7aa1f,0xac722da8,0x263eaf64,
  0xafd90000,0x2ea72a1f,0xac72ada8,0x263e2f64,0xaea70000,0xa63e2f64,0x2fd9ada8,0xac72aa1f,0xac720000,0xafd92f64,0xa63e2da8,0x2ea7aa1f,
  0xa63e0000,0xac722a1f,0xaea72da8,0xafd92f64,0x2fd93000,0x2ea72f64,0x2c722da8,0x263e2a1f,0x2ea73000,0xa63e2a1f,0xafd9ada8,0xac72af64,
  0x2c723000,0xafd9aa1f,0x263eada8,0x2ea72f64,0x263e3000,0xac72af64,0x2ea72da8,0xafd9aa1f,0xa63e3000,0x2c72af64,0xaea72da8,0x2fd9aa1f,
  0xac723000,0x2fd9aa1f,0xa63eada8,0xaea72f64,0xaea73000,0x263e2a1f,0x2fd9ada8,0x2c72af64,0xafd93000,0xaea72f64,0xac722da8,0xa63e2a1f,
  0x263e0000,0x2c72aa1f,0x2ea7ada8,0x2fd9af64,0x2c720000,0x2fd9af64,0x263eada8,0xaea72a1f,0x2ea70000,0x263eaf64,0xafd92da8,0x2c722a1f,
  0x2fd90000,0xaea7aa1f,0x2c722da8,0xa63eaf64,0x2fd90000,0xaea72a1f,0x2c72ada8,0xa63e2f64,0x2ea70000,0x263e2f64,0xafd9ada8,0x2c72aa1f,
  0x2c720000,0x2fd92f64,0x263e2da8,0xaea7aa1f,0x263e0000,0x2c722a1f,0x2ea72da8,0x2fd92f64,0xafd93000,0xaea72f64,0xac722da8,0xa63e2a1f,
  0xaea73000,0x263e2a1f,0x2fd9ada8,0x2c72af64,0xac723000,0x2fd9aa1f,0xa63eada8,0xaea72f64,0xa63e3000,0x2c72af64,0xaea72da8,0x2fd9aa1f,
  0x263e3000,0xac72af64,0x2ea72da8,0xafd9aa1f,0x2c723000,0xafd9aa1f,0x263eada8,0x2ea72f64,0x2ea73000,0xa63e2a1f,0xafd9ada8,0xac72af64,
  0x2fd93000,0x2ea72f64,0x2c722da8,0x263e2a1f,0xa63e0000,0xac72aa1f,0xaea7ada8,0xafd9af64,0x2c720000,0x2fd92f64,0x263e2da8,0xaea7aa1f,
  0xaea70000,0xa63eaf64,0x2fd92da8,0xac722a1f,0x2fd90000,0xaea72a1f,0x2c72ada8,0xa63e2f64,0xafd90000,0x2ea72a1f,0xac72ada8,0x263e2f64,
  0x2ea70000,0x263eaf64,0xafd92da8,0x2c722a1f,0xac720000,0xafd92f64,0xa63e2da8,0x2ea7aa1f,0x263e0000,0x2c72aa1f,0x2ea7ada8,0x2fd9af64,
  0x2fd93000,0x2ea72f64,0x2c722da8,0x263e2a1f,0xaea7b000,0x263eaa1f,0x2fd92da8,0x2c722f64,0x2c723000,0xafd9aa1f,0x263eada8,0x2ea72f64,
  0xa63eb000,0x2c722f64,0xaea7ada8,0x2fd92a1f,0xa63e3000,0x2c72af64,0xaea72da8,0x2fd9aa1f,0x2c72b000,0xafd92a1f,0x263e2da8,0x2ea7af64,
  0xaea73000,0x263e2a1f,0x2fd9ada8,0x2c72af64,0x2fd9b000,0x2ea7af64,0x2c72ada8,0x263eaa1f,0x263e0000,0x2c72aa1f,0x2ea7ada8,0x2fd9af64,
  0xac720000,0xafd92f64,0xa63e2da8,0x2ea7aa1f,0x2ea70000,0x263eaf64,0xafd92da8,0x2c722a1f,0xafd90000,0x2ea72a1f,0xac72ada8,0x263e2f64,
  0x2fd90000,0xaea72a1f,0x2c72ada8,0xa63e2f64,0xaea70000,0xa63eaf64,0x2fd92da8,0xac722a1f,0x2c720000,0x2fd92f64,0x263e2da8,0xaea7aa1f,
  0xa63e0000,0xac72aa1f,0xaea7ada8,0xafd9af64,0xafd93000,0xaea72f64,0xac722da8,0xa63e2a1f,0x2ea7b000,0xa63eaa1f,0xafd92da8,0xac722f64,
  0xac723000,0x2fd9aa1f,0xa63eada8,0xaea72f64,0x263eb000,0xac722f64,0x2ea7ada8,0xafd92a1f,0x263e3000,0xac72af64,0x2ea72da8,0xafd9aa1f,
  0xac72b000,0x2fd92a1f,0xa63e2da8,0xaea7af64,0x2ea73000,0xa63e2a1f,0xafd9ada8,0xac72af64,0xafd9b000,0xaea7af64,0xac72ada8,0xa63eaa1f,
  0xafd9b000,0xaea7af64,0xac72ada8,0xa63eaa1f,0x2ea73000,0xa63e2a1f,0xafd9ada8,0xac72af64,0xac72b000,0x2fd92a1f,0xa63e2da8,0xaea7af64,
  0x263e3000,0xac72af64,0x2ea72da8,0xafd9aa1f,0x263eb000,0xac722f64,0x2ea7ada8,0xafd92a1f,0xac723000,0x2fd9aa1f,0xa63eada8,0xaea72f64,
  0x2ea7b000,0xa63eaa1f,0xafd92da8,0xac722f64,0xafd93000,0xaea72f64,0xac722da8,0xa63e2a1f,0xa63e0000,0xac72aa1f,0xaea7ada8,0xafd9af64,
  0x2c720000,0x2fd92f64,0x263e2da8,0xaea7aa1f,0xaea70000,0xa63eaf64,0x2fd92da8,0xac722a1f,0x2fd90000,0xaea72a1f,0x2c72ada8,0xa63e2f64,
  0xafd90000,0x2ea72a1f,0xac72ada8,0x263e2f64,0x2ea70000,0x263eaf64,0xafd92da8,0x2c722a1f,0xac720000,0xafd92f64,0xa63e2da8,0x2ea7aa1f,
  0x263e0000,0x2c72aa1f,0x2ea7ada8,0x2fd9af64,0x2fd9b000,0x2ea7af64,0x2c72ada8,0x263eaa1f,0xaea73000,0x263e2a1f,0x2fd9ada8,0x2c72af64,
  0x2c72b000,0xafd92a1f,0x263e2da8,0x2ea7af64,0xa63e3000,0x2c72af64,0xaea72da8,0x2fd9aa1f,0xa63eb000,0x2c722f64,0xaea7ada8,0x2fd92a1f,
  0x2c723000,0xafd9aa1f,0x263eada8,0x2ea72f64,0xaea7b000,0x263eaa1f,0x2fd92da8,0x2c722f64,0x2fd93000,0x2ea72f64,0x2c722da8,0x263e2a1f,
  0x263e0000,0x2c72aa1f,0x2ea7ada8,0x2fd9af64,0xac720000,0xafd92f64,0xa63e2da8,0x2ea7aa1f,0x2ea70000,0x263eaf64,0xafd92da8,0x2c722a1f,
  0xafd90000,0x2ea72a1f,0xac72ada8,0x263e2f64,0x2fd90000,0xaea72a1f,0x2c72ada8,0xa63e2f64,0xaea70000,0xa63eaf64,0x2fd92da8,0xac722a1f,
  0x2c720000,0x2fd92f64,0x263e2da8,0xaea7aa1f,0xa63e0000,0xac72aa1f,0xaea7ada8,0xafd9af64,0x316c2fbd,0x343e32f7,0x35bc34ff,0x372c3676,
  0x371532c6,0x3a81392e,0x3bef3b71,0x3b7c3bf2,0x397034cf,0x3bfc3b6c,0x38b23b04,0xb40e31e8,0x3ae13631,0x39e73bf5,0xb6e83219,0xbbe8bb13,
  0x3bc23785,0x30be3aa9,0xbbfdb911,0x2a16b9aa,0x3bfe3865,0xb80f37a6,0xb82abc00,0x3bfd376f,0x3b9238fd,0xbb7f2311,0x3805b929,0x31223bde,
  0x3a85398b,0xbb96b742,0x3bff319e,0xbbb82f8b,0xbbe2bbf1,0xbbb7bbcf,0xbb78bb9a,0xbb27bb52,0xbb2cbbd2,0xb8a8ba19,0xb029b5df,0x35a52f59,
  0xb9dfbba1,0x2ba7b5f7,0x3a7a37b2,0x3bbd3bdd,0xb815bb60,0x39662e91,0x3b373bda,0xb0d7377a,0xb3d3bb10,0x3be9386f,0x2a7a3a31,0xbbfeb9a6,
  0x294dbab0,0x3ae53b07,0xbad51fdb,0xab43bb16,0x352fba41,0x35993c00,0xbaebba1d,0x3be531cf,0x38a3b9c5,0xb5173b21,0x2776bbe0,0x34323bf2,
  0x384537dd,0x38ea3899,0x39823937,0x3a0d39c9,0x39463a93,0x3340374e,0xb426a452,0xb979b7c8,0xbb45b924,0xbb32bc00,0xb371b902,0x38d63294,
  0xb08db9a1,0x3b3f379b,0x39583bd7,0xb8252dfb,0x3bea3a2d,0xb3ba3874,0xbb89bb0d,0x36d2b625,0xb6bb387f,0xb8d1bbf5,0x3be73602,0xb546391f,
  0xba00bb01,0x3bff35eb,0xba5c34db,0x3359bab6,0x3ac7b66b,0xb9413933,0x368dbabd,0xb0103bb3,0xbac4baf7,0xba50ba8c,0xb9cdba11,0xb93cb986,
  0x3a04388e,0x3bcb3b1e,0x3bba3c00,0x39d63afe,0x36af3a21,0xb6ffa17f,0xbbc8ba3d,0xba60bbd4,0xbbebb9af,0xb6c6bb0a,0x39f43263,0x3ad83bf7,
  0x30a6b916,0x3bc33aa5,0xb55e3790,0xbb3dbb63,0x3b423a9e,0xba642ec3,0xb0f0bb6a,0x3b8e3a25,0xb94a37bd,0x2884bb6f,0x38db3b9f,0xbbc9b85a,
  0xb840bb54,0x3a093a15,0xbb4cb850,0x3bef3457,0x3a893a4d,0x3af43ac1,0x3b4f3b24,0x3b983b76,0xbb94baba,0xbbe4bbf9,0xba58bb57,0xb699b8f8,
  0x3bfe3b18,0x394f3b5c,0xb109347b,0xbae8b884,0xbbc0bb68,0xa9b1b90c,0x3b8b387a,0x38bc3ba5,0x3ade3ba7,0xb8c1324b,0xb9f0bbf6,0x39eb9648,
  0xb96bbbd6,0x3bbf3487,0xb38939b3,0xb9f8bba3,0x370a3bf3,0xbb47b994,0x3bbc2d65,0xb8ad3889,0xb153bc00,0x37213b9c,0xb97dba90,0x3af138f3,
  0xb89eb8ee,0xb7e8b84a,0xb682b737,0xb50bb5c8,0x35233855,0xb13b2d33,0xb8e0b65f,0xbb4aba45,0xa8e8b764,0x39fc3648,0x3be63bae,0x380a3a9b,
  0xb3eb360e,0xbbfeba35,0xb552baa2,0x3a7334b7,0x381ab4ab,0x3a6f3bd8,0xb95d2e5f,0xb962bc00,0xb9e3327c,0xb402bbac,0x3bc6399d,0xb95434c3,
  0x3b2faf27,0xb6a439bc,0xb41abbf9,0x3a7e3a97,0xbbe3251b,0x3b2ab4f3,0xb9d23894,0x37f3ba49,0x3bce3bb5,0x3bf03be1,0x3bff3bfa,0x3bfb3bff,
  0x2c38b1b6,0x383a34e7,0x3aee39c0,0x3bff3bb2,0xbb81bbf8,0xb53ab999,0x38302ef5,0x3bed3ab3,0xb8cc9cb6,0xbb85bbab,0x2adeb86a,0x3bc5391b,
  0x38c73bf6,0xbadbb232,0xb6ddbba9,0x3b87361a,0x3b833201,0xb0743a39,0xba76bb5e,0x3b352dc9,0xac06bbb0,0x39743b59,0xbbeeb759,0x3aceb2ad,
  0xbbccb5d4,0x3bfb2d00,0xbb7a32de,0x3a54b7d2,0xb30fb44b,0xafefb185,0xa6adacce,0x2c9c25e4,0xbbfcbbdf,0xbacbbb9e,0xb7feb990,0xa81fb463,
  0xb58d2d97,0xbb90b9b8,0xbad1bbf4,0xb05bb85f,0x3a673c00,0xb5763493,0xbbfdbaac,0xb3a2ba29,0x3a6b2e2d,0x38203bd9,0xbb3ab49f,0xb56abb65,
  0xb581bbdc,0x3bec3907,0xb8b7363c,0xb6f4bbf8,0xbbfcb46f,0x39dab654,0xb0423b1b,0xb835bbd3,0xb3283b73,0xac6abbfa,0x35b13bd0,0xb8e5bafb,
  0x38ee3a0d,0xb84aba89,0x37373af4,0xb5c8bb4f,0x35df3a81,0x2f59bbef,0xb88e3b7c,0x3b1eb946,0x2d973ae8,0x39b8bb81,0xbbf4353a,0x385f3830,
  0xb2633b3f,0x3bf7b958,0xb60eb825,0xba353bc0,0xb7853b87,0x3aa9b3d3,0x3911bbe9,0xb9aa2a7a,0xb99d3bbf,0x34c33389,0x3bdcb9f8,0x3907bb83,
  0xbb013be5,0xb5eb394a,0x34db2884,0x3ab6b8db,0xbbd03bfb,0xbafb3b7a,0xb98b3a54,0xb74238a3,0x3a4db93c,0xbac1389e,0x3b24b7e8,0xbb763682,
  0x3b71b8a8,0xbbf23029,0x3a9335a5,0xb74eba04,0x3bf8b80a,0xb999b58d,0xaef53b90,0x3ab3bad1,0x3bd7b6c6,0xadfbb9f4,0xbb683ad8,0x390c33eb,
  0x3b10b56a,0x386fbbc2,0xba3130be,0xb9a63bfd,0x39b3b402,0x3ba3bbc6,0x3201b954,0xba393581,0x37bdb122,0x3b6fba00,0x3b9fbbff,0x385aba5c,
  0x32deac6a,0x37d2b5b1,0x39c5b8e5,0x3b21ba85,0x344b3b98,0xb185bbce,0x2cce3bf0,0x25e4bbff,0xbc003340,0x3afe3426,0xb855b979,0x2d333b94,
  0x34cfbbed,0xbb6c39df,0x3b042ba7,0xb1e8ba7a,0x3aa2a9b1,0x34b7bb8b,0xbc0038bc,0x349338cc,0xba2d3bfe,0x387430a6,0x3b0dbbc3,0xb625b55e,
  0xb63cb074,0xbbf83a76,0xb8653b35,0x37a6294d,0x3bf3bbc9,0x3994bb2f,0x2d65b6a4,0xb889341a,0xb19e3517,0x2f8b2776,0x366bb432,0x3933b840,
  0x3bb5b50b,0xbbe1330f,0x3bfaafef,0xbbff26ad,0xa4523bcb,0x37c8bbba,0xbaba39d6,0x3bf9b523,0xbba1305b,0x35f73970,0x37b2bbfc,0xbbdd38b2,
  0x387abbfe,0xbba53552,0x9cb63a73,0x3babba67,0x39162a16,0x3aa5bbea,0xb790b3ba,0xbb633b89,0xbb5e3bec,0xadc938b7,0x3ab0b6f4,0x3b07bbfe,
  0xaf27b359,0xb9bc370a,0xbbf93b47,0xba973bbc,0x3be0bb96,0x3bf2bbff,0x3b54bbb8,0x3a15bac7,0xafbd3bfb,0x32f7bbe2,0xb4ff3bb7,0x3676bb78,
  0x365fbbe4,0xba453a58,0x3bdfb699,0xbb9eac38,0xb9243bbd,0x3c00b6af,0xb902b6ff,0xb2943bc8,0x3aacbb85,0xba29aade,0xb6313bc5,0x3bf5b815,
  0xbba73b3d,0x324b381a,0x3bf6ba6f,0x9648b95d,0x3c00bae5,0x376fbad5,0xb87f2b43,0xbbf53b42,0xbbb03a7e,0xbb593bfc,0xb75939da,0x32ad3042,
  0x3abdba09,0x3bb3bb4c,0x3c00bbef,0x3b9cbbe3,0x3bf12c9c,0xbbcfb16c,0x3b9a343e,0xbb52b5bc,0xbb57b13b,0x38f838e0,0xb1b6bb4a,0xb4e73bfc,
  0x3a21340e,0x217fbb45,0xba3d3b32,0x3bd4b371,0xb86ab576,0xb91b3bfd,0x3b60b3a2,0x2e91bae1,0x34ab36d2,0x3bd8bade,0xae5fb8c1,0xbc0039f0,
  0x9fdbb80f,0xbb16382a,0xba9e3bfd,0x2ec336bb,0xb46f38ad,0x3654ac06,0x3b1bb974,0x3bd3bbee,0x3850b941,0x3457b68d,0xa51bb010,0xb4f33153,
  0xb7dd3b27,0x3899bac4,0xb9373a50,0x39c9b9cd,0x3990383a,0xb463baee,0xb2c63bff,0x392ebb2c,0x3b18ba60,0xbb5c28e8,0x347b39fc,0x3884bbe6,
  0xb219b966,0xbb133b37,0x39a130d7,0x379bbbeb,0xbbf63962,0xb2323a6b,0x3ba9b820,0x361abb3a,0xb6023a64,0x391fb0f0,0x3bd6bb8e,0x3487b9e3,
  0x3a41b835,0x3c00bb92,0x3a1dbb7f,0x31cfb805,0x3a90bb2a,0x38f3b9d2,0x35d4b7f3,0x2d00b328,0x3af7372c,0xba8cb845,0x3a1138ea,0xb986b982,
  0x39c0bacb,0xbbb237fe,0x3bd2a81f,0xba19b715,0xb764b8d6,0xb6483bfe,0x3baeb94f,0xba9bb109,0xbbda39e7,0x377a36e8,0x39afbbe8,0xbb0a308d,
  0xae2d39eb,0x3bd9b8c7,0x349fbadb,0xbb6536dd,0x3b6ab8d1,0x3a25bbe7,0xb27cb546,0xbbac396b,0x38fdbace,0xa311b52f,0xb9293599,0xbbde3aeb,
  0xb8943721,0xba49397d,0xbb733af1,0xbbfa3bcc,0xbbfb3bff,0xbbe23bf1,0xbbb73bcf,0xbb783b9a,0xbb7c3bf2,0xb9463a93,0xb340374e,0x3426a452,
  0xba603bd4,0xa8e83764,0x39fcb648,0x3be6bbae,0xb8bc3ba5,0x38cc9cb6,0x3b85bbab,0xaadeb86a,0xb56a3b65,0x3bc2b785,0x30bebaa9,0xbbfd3911,
  0xab433b16,0x3b42ba9e,0xba64aec3,0xb0f03b6a,0x33593ab6,0x370abbf3,0xbb473994,0x3bbcad65,0x37f33a49,0xb328bb73,0xac6a3bfa,0x35b1bbd0,
  0xac9c25e4,0xb16c2fbd,0xb43e32f7,0xb5bc34ff,0xb5a52f59,0xba04388e,0xbbcb3b1e,0xbbba3c00,0xb8d63294,0xbbfe3b18,0xb94f3b5c,0x3109347b,
  0xba7334b7,0xba673c00,0x35763493,0x3bfdbaac,0xbb87361a,0xb3d33b10,0x3be9b86f,0x2a7aba31,0xbbfd376f,0x36bb387f,0x38d1bbf5,0xbbe73602,
  0xbbc9385a,0x3b2f2f27,0xb6a4b9bc,0xb41a3bf9,0xbaf138f3,0x3bccb5d4,0xbbfb2d00,0x3b7a32de,0xbb273b52,0xbac43af7,0xba503a8c,0xb9cd3a11,
  0x3979b7c8,0x3b94baba,0x3be4bbf9,0x3a58bb57,0x380aba9b,0xb58dad97,0xbb9039b8,0xbad13bf4,0xbbc5391b,0xb8153b60,0x3966ae91,0x3b37bbda,
  0x2a1639aa,0x3beaba2d,0xb3bab874,0xbb893b0d,0x3b8eba25,0xb9e3b27c,0xb4023bac,0x3bc6b99d,0xb8adb889,0xac063bb0,0x3974bb59,0xbbee3759,
  0xb8e53afb,0x3a85b98b,0xbb963742,0x3bffb19e,0xb72c3676,0xb84537dd,0xb8ea3899,0xb9823937,0xb9d63afe,0xb5233855,0x313b2d33,0x38e0b65f,
  0x3ae8b884,0x3b81bbf8,0x353ab999,0xb8302ef5,0x33a2ba29,0xbae13631,0xb9e73bf5,0x36e83219,0xbbfe39a6,0x30a63916,0x3bc3baa5,0xb55eb790,
  0x3546391f,0x396bbbd6,0xbbbf3487,0x338939b3,0x3a7eba97,0xbbfc346f,0x39da3654,0xb042bb1b,0xba54b7d2,0x38a339c5,0xb517bb21,0x27763be0,
  0xb93c3986,0xb89e38ee,0xb7e8384a,0xb6823737,0x3699b8f8,0xac38b1b6,0xb83a34e7,0xbaee39c0,0xb05b385f,0x3970b4cf,0x3bfcbb6c,0x38b2bb04,
  0xb0d7b77a,0xbbeb39af,0xb6c63b0a,0x39f4b263,0x36d23625,0x3adebba7,0xb8c1b24b,0xb9f03bf6,0xb954b4c3,0xb5813bdc,0x3becb907,0xb8b7b63c,
  0x3ace32ad,0xb52fba41,0xb5993c00,0x3aebba1d,0xbbb8af8b,0x3ac7366b,0xb941b933,0x368d3abd,0xba0d39c9,0xba893a4d,0xbaf43ac1,0xbb4f3b24,
  0x3b4aba45,0x3bfcbbdf,0x3acbbb9e,0x37feb990,0xbbed3ab3,0xb9df3ba1,0x2ba735f7,0x3a7ab7b2,0x3be8bb13,0x308db9a1,0xbb3f379b,0xb9583bd7,
  0xbb3d3b63,0x381a34ab,0x3a6fbbd8,0xb95dae5f,0x39f8bba3,0xbb833201,0x30743a39,0x3a76bb5e,0xb8353bd3,0x3b92b8fd,0xbb7fa311,0x38053929,
  0x3432bbf2,0xb8403b54,0x3a09ba15,0xbb4c3850,0xb50b35c8,0xb30f344b,0xafef3185,0xa6ad2cce,0xbbff3bb2,0xbb2c3bd2,0xb8a83a19,0xb02935df,
  0xb40eb1e8,0xbb453924,0xbb323c00,0xb3713902,0x3ad8bbf7,0xb3ebb60e,0xbbfe3a35,0xb5523aa2,0x39eb1648,0x38c7bbf6,0xbadb3232,0xb6dd3ba9,
  0xb6f43bf8,0x3bfeb865,0xb80fb7a6,0xb82a3c00,0xbbe531cf,0x394a37bd,0xa884bb6f,0xb8db3b9f,0xb010bbb3,0xb1533c00,0x3721bb9c,0xb97d3a90,
  0xbb983b76,0xbbce3bb5,0xbbf03be1,0xbbff3bfa,0x281fb463,0xb71532c6,0xba81392e,0xbbef3b71,0x3bbdbbdd,0x36afba21,0xb6ff217f,0xbbc83a3d,
  0x38252dfb,0x3bc0bb68,0x29b1b90c,0xbb8b387a,0xb9623c00,0x3a6bae2d,0x3820bbd9,0xbb3a349f,0xbb352dc9,0x294d3ab0,0x3ae5bb07,0xbad59fdb,
  0x3122bbde,0xba003b01,0x3bffb5eb,0xba5cb4db,0x3befb457,0xbbe3a51b,0x3b2a34f3,0xb9d2b894,0x39c939cd,0xba4db93c,0x3ac1389e,0xbb24b7e8,
  0x3b1e3946,0xbc00b340,0x3afeb426,0xb8553979,0x3bdd38b2,0xba21340e,0xa17fbb45,0x3a3d3b32,0x3bf53815,0xb2193966,0xbb13bb37,0x39a1b0d7,
  0x3b6536dd,0x37853b87,0xbaa9b3d3,0xb911bbe9,0x3a393581,0x3b5e3bec,0x2dc938b7,0xbab0b6f4,0x3889341a,0x3bb03a7e,0x3b593bfc,0x375939da,
  0x34f33153,0x38943721,0x3a49397d,0x3b733af1,0xb9863982,0x38eeba0d,0xb84a3a89,0x3737baf4,0xb74e3a04,0xa452bbcb,0x37c83bba,0xbabab9d6,
  0xb1e83a7a,0xb924bbbd,0x3c0036af,0xb90236ff,0x2e913ae1,0xbbdab9e7,0x377ab6e8,0x39af3be8,0x361a3b3a,0xbb10b56a,0xb86fbbc2,0x3a3130be,
  0x39073b83,0xb63c3074,0xbbf8ba76,0xb865bb35,0x3a973bbc,0x346f38ad,0xb654ac06,0xbb1bb974,0x3b9c3be3,0x3a903b2a,0x38f339d2,0x35d437f3,
  0x3b763682,0xbbb5b50b,0x3be1330f,0xbbfaafef,0x2d33bb94,0x365f3be4,0xba45ba58,0x3bdf3699,0xbbd4b371,0x3764b8d6,0x36483bfe,0xbbaeb94f,
  0x379b3beb,0xbbd7b6c6,0x2dfbb9f4,0x3b683ad8,0x39aa2a7a,0x3a2d3bfe,0xb87430a6,0xbb0dbbc3,0xbb07bbfe,0x1fdbb80f,0x3b16382a,0x3a9e3bfd,
  0xb2ad3042,0xba41b835,0xbc00bb92,0xba1dbb7f,0x3bfa3bcc,0x3bd03bfb,0x3afb3b7a,0x398b3a54,0xb5c83b4f,0x344bbb98,0xb1853bce,0x2ccebbf0,
  0x3bf93523,0xbb57313b,0x38f8b8e0,0xb1b63b4a,0xb294bbc8,0x3b183a60,0xbb5ca8e8,0x347bb9fc,0xbb0ab08d,0xb263bb3f,0x3bf73958,0xb60e3825,
  0x39a63bfd,0xb9162a16,0xbaa5bbea,0x3790b3ba,0x37a6a94d,0x3c003ae5,0x376f3ad5,0xb87fab43,0xbbd3bbee,0xb8fdbace,0x2311b52f,0x39293599,
  0x2d003328,0xb2deac6a,0xb7d2b5b1,0xb9c5b8e5,0x3bff26ad,0xbbf12c9c,0x3bcfb16c,0xbb9a343e,0xbb9e2c38,0x3990b83a,0xb4633aee,0xb2c6bbff,
  0x3a9bb109,0xad973ae8,0xb9b8bb81,0x3bf4353a,0xb90c33eb,0xb87abbfe,0x3ba53552,0x1cb63a73,0x3625b55e,0x3ba73b3d,0xb24b381a,0xbbf6ba6f,
  0xaec336bb,0xbb6ab8d1,0xba25bbe7,0x327cb546,0xb1cfb805,0x37bd3122,0x3b6f3a00,0x3b9f3bff,0x374238a3,0x319e3517,0xaf8b2776,0xb66bb432,
  0x25e43bff,0xafbdbbfb,0x32f73be2,0xb4ffbbb7,0xb4e7bbfc,0x39c03acb,0xbbb2b7fe,0x3bd2281f,0x38843be6,0xbbf8b80a,0x3999b58d,0x2ef53b90,
  0xba35bbc0,0x3aa229b1,0x34b73b8b,0xbc00b8bc,0x3b633b89,0xb4ab36d2,0xbbd8bade,0x2e5fb8c1,0xbbf5bb42,0xb602ba64,0x391f30f0,0x3bd63b8e,
  0x3bde3aeb,0x3b013be5,0x35eb394a,0xb4db2884,0xbb21ba85,0xbbe0bb96,0xbbf2bbff,0xbb54bbb8,0x3b52b5bc,0xbaf7372c,0x3a8cb845,0xba1138ea,
  0x392e3b2c,0xbb71b8a8,0x3bf23029,0xba9335a5,0xb85f3830,0xb4cfbbed,0x3b6c39df,0xbb042ba7,0xbbabba67,0x386ab576,0x391b3bfd,0xbb60b3a2,
  0x1648b95d,0x3bf63962,0x32323a6b,0xbba9b820,0x3bac396b,0x399d3bbf,0xb4c33389,0xbbdcb9f8,0x385a3a5c,0xaf273359,0xb9bcb70a,0xbbf9bb47,
  0xb933b840,0xbabdba09,0xbbb3bb4c,0xbc00bbef,0x36763b78,0xb7ddbb27,0x38993ac4,0xb937ba50,0xba193715,0x35dfba81,0x2f593bef,0xb88ebb7c,
  0xbab3bad1,0x3ba1305b,0xb5f73970,0xb7b2bbfc,0x3493b8cc,0x3aac3b85,0xba292ade,0xb631bbc5,0x3c0039f0,0x2e2d39eb,0xbbd9b8c7,0xb49fbadb,
  0x348739e3,0xb9b3b402,0xbba3bbc6,0xb201b954,0xbab6b8db,0xbbf3bbc9,0xb994bb2f,0xad65b6a4,0xba15bac7,0xb850b941,0xb457b68d,0x251bb010,
  0xb9cfbb16,0x30ac2a31,0x3b9c3bf1,0xb493ae2d,0xb76fb8b4,0x35a133e3,0x3a1d3afe,0xb902b76f,0xb3e3b5a1,0x38b4376f,0x376f3902,0xbafeba1d,
  0xaa31b0ac,0x3b1639cf,0x2e2d3493,0xbbf1bb9c,0xb956ba74,0x305f29cc,0x3b633bd2,0xb44badc9,0xb6e7b859,0x353f335e,0x39d23ab6,0xb8bcb6ff,
  0xb35eb53f,0x385936e7,0x36ff38bc,0xbab6b9d2,0xa9ccb05f,0x3a743956,0x2dc9344b,0xbbd2bb63,0xb8e3b9de,0x30122967,0x3b1e3ba1,0xb402ad65,
  0xb662b801,0x34de32da,0x39823a67,0xb874b68d,0xb2dab4de,0x38013662,0x368d3874,0xba67b982,0xa967b012,0x39de38e3,0x2d653402,0xbba1bb1e,
  0xb876b952,0x2f8c2902,0x3ace3b60,0xb371ad00,0xb5e1b758,0x347e3257,0x392e3a11,0xb82ab61a,0xb257b47e,0x375835e1,0x361a382a,0xba11b92e,
  0xa902af8c,0x39523876,0x2d003371,0xbb60bace,0xb80db8ce,0x2ef3289e,0x3a733b10,0xb2deac9c,0xb562b6b3,0x342031d5,0x38d639b3,0xb7bdb5a5,
  0xb1d5b420,0x36b33562,0x35a537bd,0xb9b3b8d6,0xa89eaef3,0x38ce380d,0x2c9c32de,0xbb10ba73,0xb750b851,0x2e5a2839,0x3a0d3ab0,0xb24bac38,
  0xb4e5b613,0x33863153,0x387a394f,0xb721b52f,0xb153b386,0x361334e5,0x352f3721,0xb94fb87a,0xa839ae5a,0x38513750,0x2c38324b,0xbab0ba0d,
  0xb68eb7b4,0x2dc227a9,0x399d3a41,0xb1b6aba7,0xb46ab577,0x32cd30d2,0x381a38e5,0xb682b4b7,0xb0d2b2cd,0x3577346a,0x34b73682,0xb8e5b81a,
  0xa7a9adc2,0x37b4368e,0x2ba731b6,0xba41b99d,0xb5d2b6d1,0x2d2a26e0,0x392439c5,0xb122aade,0xb3e3b4de,0x32163052,0x376f3874,0xb5dfb43e,
  0xb052b216,0x34de33e3,0x343e35df,0xb874b76f,0xa6e0ad2a,0x36d135d2,0x2ade3122,0xb9c5b924,0xb51cb5f6,0x2c932617,0x38a3393c,0xb08daa16,
  0xb2f4b448,0x31602fa5,0x36a437fe,0xb53ab389,0xafa5b160,0x344832f4,0x3389353a,0xb7feb6a4,0xa617ac93,0x35f6351c,0x2a16308d,0xb93cb8a3,
  0xb46ab523,0x2bf6254d,0x381a38a8,0xafefa94d,0xb209b36b,0x30ac2ea7,0x35d4370a,0xb493b294,0xaea7b0ac,0x336b3209,0x32943493,0xb70ab5d4,
  0xa54dabf6,0x3523346a,0x294d2fef,0xb8a8b81a,0xb378b456,0x2ac82484,0x3715380a,0xaec3a884,0xb120b24a,0x2ff22da9,0x34ff360e,0xb3d3b19e,
  0xada9aff2,0x324a3120,0x319e33d3,0xb60eb4ff,0xa484aac8,0x34563378,0x28842ec3,0xb80ab715,0xb223b31c,0x29992376,0x35eb36c6,0xad97a776,
  0xb039b12d,0x2e8d2cac,0x3426350b,0xb27cb0a6,0xacacae8d,0x312d3039,0x30a6327c,0xb50bb426,0xa376a999,0x331c3223,0x27762d97,0xb6c6b5eb,
  0xb0d2b194,0x286b21e4,0x34b7356a,0xac6aa5e4,0xaea7b012,0x2d2a2b5f,0x32943402,0xb122af59,0xab5fad2a,0x30122ea7,0x2f593122,0xb402b294,
  0xa1e4a86b,0x319430d2,0x25e42c6a,0xb56ab4b7,0xaf0cb012,0x267b2052,0x32f73402,0xaa7aa452,0xacdeadf5,0x2b912967,0x30d731e8,0xaf8bad65,
  0xa967ab91,0x2df52cde,0x2d652f8b,0xb1e8b0d7,0xa052a67b,0x30122f0c,0x24522a7a,0xb402b2f7,0xac79ad2a,0x24201d7f,0x30743122,0xa81fa17f,
  0xaa31ab91,0x28d026e0,0x2e2d2f8b,0xacceaade,0xa6e0a8d0,0x2b912a31,0x2ade2cce,0xaf8bae2d,0x9d7fa420,0x2d2a2c79,0x217f281f,0xb122b074,
  0xa7a9a86b,0x1f1218b6,0x2ba72c6a,0xa3119cb6,0xa54da67b,0x242021e4,0x294d2a7a,0xa81fa5e4,0xa1e4a420,0x267b254d,0x25e4281f,0xaa7aa94d,
  0x98b69f12,0x286b27a9,0x1cb62311,0xac6aaba7,0x211b21e4,0x98b69248,0xa51ba5e4,0x1cb61648,0x1f122052,0x9d7f9bdb,0xa311a452,0x217f1fdb,
  0x1bdb1d7f,0xa0529f12,0x9fdba17f,0x24522311,0x124818b6,0xa1e4a11b,0x96489cb6,0x25e4251b,0x2a632b5f,0xa1e49bdb,0xae5faf59,0x25e41fdb,
  0x286b2967,0xa6e0a4e9,0xac6aad65,0x2ade28e8,0x24e926e0,0xa967a86b,0xa8e8aade,0x2d652c6a,0x1bdb21e4,0xab5faa63,0x9fdba5e4,0x2f592e5f,
  0x2dc22ea7,0xa54d9f12,0xb1b6b294,0x294d2311,0x2bf62cde,0xaa31a86b,0xafefb0d7,0x2e2d2c6a,0x286b2a31,0xacdeabf6,0xac6aae2d,0x30d72fef,
  0x1f12254d,0xaea7adc2,0xa311a94d,0x329431b6,0x302c30d2,0xa7a9a11b,0xb41ab4b7,0x2ba7251b,0x2dc22f0c,0xac79aa63,0xb1b6b2f7,0x30742e5f,
  0x2a632c79,0xaf0cadc2,0xae5fb074,0x32f731b6,0x211b27a9,0xb0d2b02c,0xa51baba7,0x34b7341a,0x317a3257,0xa902a2ad,0xb552b61a,0x2d0026ad,
  0x2f8c309f,0xaddcac2e,0xb371b487,0x31cf3029,0x2c2e2ddc,0xb09faf8c,0xb029b1cf,0x34873371,0x22ad2902,0xb257b17a,0xa6adad00,0x361a3552,
  0x32cd33e3,0xaa31a420,0xb682b76f,0x2e2d281f,0x30ac31bb,0xaf3fad2a,0xb493b58d,0x33283122,0x2d2a2f3f,0xb1bbb0ac,0xb122b328,0x358d3493,
  0x24202a31,0xb3e3b2cd,0xa81fae2d,0x376f3682,0x341334bc,0xab5fa4e9,0xb7a6b85a,0x2f5928e8,0x319432da,0xb052ae28,0xb56ab68d,0x343e3219,
  0x2e283052,0xb2dab194,0xb219b43e,0x368d356a,0x24e92b5f,0xb4bcb413,0xa8e8af59,0x385a37a6,0x34c3358c,0xac47a5b2,0xb85fb8f3,0x304229b1,
  0x327e33fd,0xb106af26,0xb63cb785,0x34e7330f,0x2f263106,0xb3fdb27e,0xb30fb4e7,0x3785363c,0x25b22c47,0xb58cb4c3,0xa9b1b042,0x38f3385f,
  0x35773662,0xacdea67b,0xb8e5b982,0x30d72a7a,0x336b3493,0xb1bbb012,0xb70ab83a,0x358d3402,0x301231bb,0xb493b36b,0xb402b58d,0x383a370a,
  0x267b2cde,0xb662b577,0xaa7ab0d7,0x398238e5,0x36303741,0xad76a744,0xb962ba04,0x316c2b43,0x342e352a,0xb271b092,0xb7d2b8ad,0x3631347b,
  0x30923271,0xb52ab42e,0xb47bb631,0x38ad37d2,0x27442d76,0xb741b630,0xab43b16c,0x3a043962,0x36ee3815,0xae0ea807,0xb9d6ba7a,0x32012c06,
  0x34a735c4,0xb329b113,0xb84ab91b,0x36d234f3,0x31133329,0xb5c4b4a7,0xb4f3b6d2,0x391b384a,0x28072e0e,0xb815b6ee,0xac06b201,0x3a7a39d6,
  0x37b4388e,0xaea7a86b,0xba41bae1,0x32942c6a,0x35233662,0xb3e3b194,0xb8a8b982,0x376f356a,0x319433e3,0xb662b523,0xb56ab76f,0x398238a8,
  0x286b2ea7,0xb88eb7b4,0xac6ab294,0x3ae13a41,0x3841390f,0xaf3fa8d0,0xbaa2bb3a,0x33282cce,0x35a13705,0xb44fb216,0xb902b9e3,0x380535df,
  0x3216344f,0xb705b5a1,0xb5dfb805,0x39e33902,0x28d02f3f,0xb90fb841,0xacceb328,0x3b3a3aa2,0x38ac3997,0xafd8a935,0xbaf7bb83,0x33ba2d33,
  0x362137ac,0xb4aeb298,0xb958ba3d,0x38503654,0x329834ae,0xb7acb621,0xb654b850,0x3a3d3958,0x29352fd8,0xb997b8ac,0xad33b3ba,0x3b833af7,
  0x391c3a28,0xb039a999,0xbb42bbbc,0x34262d97,0x36a4382d,0xb50eb31c,0xb9aaba90,0x389936c6,0x331c350e,0xb82db6a4,0xb6c6b899,0x3a9039aa,
  0x29993039,0xba28b91c,0xad97b426,0x3bbc3b42,0x39923ac3,0xb085a9fe,0xbb81bbe3,0x346f2dfb,0x372a3886,0xb570b3a0,0xb9f8badb,0x38e03737,
  0x33a03570,0xb886b72a,0xb737b8e0,0x3adb39f8,0x29fe3085,0xbac3b992,0xadfbb46f,0x3be33b81,
};

#define PROF(slot) do {} while (0)
#define PROF_DUMP() do {} while (0)
#define PROFA(slot, dep) do {} while (0)
#define PROF3(slot) do {} while (0)
#define PROF2(slot) do {} while (0)

__device__ __forceinline__ uint32_t smem_u32(const void* p) { return (uint32_t)__cvta_generic_to_shared(p); }

__device__ __forceinline__ void mbar_init(uint32_t a, uint32_t c) {
  asm volatile("mbarrier.init.shared::cta.b64 [%0], %1;\n" ::"r"(a), "r"(c) : "memory");
}
__device__ __forceinline__ void mbar_expect_tx(uint32_t a, uint32_t bytes) {
  asm volatile("mbarrier.arrive.expect_tx.shared::cta.b64 _, [%0], %1;\n" ::"r"(a), "r"(bytes) : "memory");
}
__device__ __forceinline__ void mbar_arrive_cluster(uint32_t cluster_addr) {
  asm volatile("mbarrier.arrive.shared::cluster.b64 _, [%0];\n" ::"r"(cluster_addr) : "memory");
}
__device__ __forceinline__ void mbar_arrive_cluster_n(uint32_t cluster_addr, uint32_t n) {
  asm volatile("mbarrier.arrive.shared::cluster.b64 _, [%0], %1;\n" ::"r"(cluster_addr), "r"(n) : "memory");
}
__device__ __forceinline__ bool mbar_try(uint32_t a, uint32_t parity) {
  uint32_t ok;
  asm volatile("{\n.reg .pred p;\nmbarrier.try_wait.parity.shared::cta.b64 p, [%1], %2;\nselp.u32 %0, 1, 0, p;\n}\n"
               : "=r"(ok) : "r"(a), "r"(parity) : "memory");
  return ok;
}
__device__ __forceinline__ void mbar_wait(uint32_t a, uint32_t parity) {
  if (mbar_try(a, parity)) return;
#pragma unroll 1
  for (int n = 0; n < SPIN_LIMIT; n++)
    if (mbar_try(a, parity)) break;
}
__device__ __forceinline__ bool elect_one() {
  uint32_t p;
  asm volatile("{\n.reg .pred P;\nelect.sync _|P, 0xffffffff;\nselp.u32 %0, 1, 0, P;\n}\n" : "=r"(p));
  return p;
}
__device__ __forceinline__ uint32_t mapa(uint32_t a, uint32_t rank) {
  uint32_t r;
  asm volatile("mapa.shared::cluster.u32 %0, %1, %2;\n" : "=r"(r) : "r"(a), "r"(rank));
  return r;
}
__device__ __forceinline__ void nb_sync(int id, int n) { asm volatile("bar.sync %0, %1;\n" ::"r"(id), "r"(n) : "memory"); }
__device__ __forceinline__ void nb_arrive(int id, int n) { asm volatile("bar.arrive %0, %1;\n" ::"r"(id), "r"(n) : "memory"); }
__device__ __forceinline__ void cluster_sync_all() {
  asm volatile("barrier.cluster.arrive.relaxed.aligned;\nbarrier.cluster.wait.aligned;\n" ::: "memory");
}
__device__ __forceinline__ void fence_async_smem() { asm volatile("fence.proxy.async.shared::cta;\n" ::: "memory"); }
__device__ __forceinline__ void fence_async_all() { asm volatile("fence.proxy.async.global;\n" ::: "memory"); }

__device__ __forceinline__ void tma_load_3d(uint32_t dst, const CUtensorMap* tm, uint32_t bar, int c0, int c1, int c2) {
  asm volatile(
      "cp.async.bulk.tensor.3d.shared::cluster.global.mbarrier::complete_tx::bytes [%0], [%1, {%3, %4, %5}], [%2];\n"
      ::"r"(dst), "l"(tm), "r"(bar), "r"(c0), "r"(c1), "r"(c2) : "memory");
}
__device__ __forceinline__ void tma_load_4d(uint32_t dst, const CUtensorMap* tm, uint32_t bar, int c0, int c1, int c2, int c3) {
  asm volatile(
      "cp.async.bulk.tensor.4d.shared::cluster.global.mbarrier::complete_tx::bytes [%0], [%1, {%3, %4, %5, %6}], [%2];\n"
      ::"r"(dst), "l"(tm), "r"(bar), "r"(c0), "r"(c1), "r"(c2), "r"(c3) : "memory");
}
__device__ __forceinline__ void tma_load_3d_mc(uint32_t dst, const CUtensorMap* tm, uint32_t bar, int c0, int c1, int c2) {
  asm volatile(
      "cp.async.bulk.tensor.3d.shared::cluster.global.mbarrier::complete_tx::bytes.multicast::cluster [%0], [%1, {%3, %4, %5}], [%2], %6;\n"
      ::"r"(dst), "l"(tm), "r"(bar), "r"(c0), "r"(c1), "r"(c2), "h"((uint16_t)3) : "memory");
}
__device__ __forceinline__ void bulk_load(uint32_t dst, const void* src, uint32_t bytes, uint32_t bar) {
  asm volatile("cp.async.bulk.shared::cluster.global.mbarrier::complete_tx::bytes [%0], [%1], %2, [%3];\n"
               ::"r"(dst), "l"(src), "r"(bytes), "r"(bar) : "memory");
}
__device__ __forceinline__ void tma_store_3d(const CUtensorMap* tm, uint32_t src, int c0, int c1, int c2) {
  asm volatile("cp.async.bulk.tensor.3d.global.shared::cta.bulk_group [%0, {%2, %3, %4}], [%1];\n"
               ::"l"(tm), "r"(src), "r"(c0), "r"(c1), "r"(c2) : "memory");
}
__device__ __forceinline__ void bulk_commit() { asm volatile("cp.async.bulk.commit_group;\n" ::: "memory"); }
__device__ __forceinline__ void bulk_wait0() { asm volatile("cp.async.bulk.wait_group 0;\n" ::: "memory"); }
__device__ __forceinline__ void prefetch_tmap(const CUtensorMap* tm) {
  asm volatile("prefetch.tensormap [%0];\n" ::"l"(tm) : "memory");
}

__device__ __forceinline__ void wg_fence() { asm volatile("wgmma.fence.sync.aligned;\n" ::: "memory"); }
__device__ __forceinline__ void wg_commit() { asm volatile("wgmma.commit_group.sync.aligned;\n" ::: "memory"); }
template <int N> __device__ __forceinline__ void wg_wait() {
  asm volatile("wgmma.wait_group.sync.aligned %0;\n" ::"n"(N) : "memory");
}
__device__ __forceinline__ uint64_t mkdesc(uint32_t addr, uint32_t lbo, uint32_t sbo, uint32_t swz) {
  return (uint64_t)((addr & 0x3FFFF) >> 4) | ((uint64_t)(lbo >> 4) << 16) | ((uint64_t)(sbo >> 4) << 32) |
         ((uint64_t)swz << 62);
}

#define R4(d, o) "+f"(d[o + 0]), "+f"(d[o + 1]), "+f"(d[o + 2]), "+f"(d[o + 3])
#define R8(d, o) R4(d, o), R4(d, o + 4)
#define R16(d, o) R8(d, o), R8(d, o + 8)
#define R32(d, o) R16(d, o), R16(d, o + 16)
#define R64(d, o) R32(d, o), R32(d, o + 32)

__device__ __forceinline__ void wgmma_n192(float (&d)[96], uint64_t da, uint64_t db, uint32_t acc) {
  asm volatile(
      "{\n.reg .pred p;\nsetp.ne.u32 p, %98, 0;\n"
      "wgmma.mma_async.sync.aligned.m64n192k16.f32.bf16.bf16 "
      "{%0,%1,%2,%3,%4,%5,%6,%7,%8,%9,%10,%11,%12,%13,%14,%15,%16,%17,%18,%19,%20,%21,%22,%23,%24,%25,%26,%27,%28,%29,%30,%31,"
      "%32,%33,%34,%35,%36,%37,%38,%39,%40,%41,%42,%43,%44,%45,%46,%47,%48,%49,%50,%51,%52,%53,%54,%55,%56,%57,%58,%59,%60,%61,%62,%63,"
      "%64,%65,%66,%67,%68,%69,%70,%71,%72,%73,%74,%75,%76,%77,%78,%79,%80,%81,%82,%83,%84,%85,%86,%87,%88,%89,%90,%91,%92,%93,%94,%95}, "
      "%96, %97, p, 1, 1, 0, 1;\n}\n"
      : R64(d, 0), R32(d, 64)
      : "l"(da), "l"(db), "r"(acc));
}
__device__ __forceinline__ void wgmma_n128(float (&d)[64], uint64_t da, uint64_t db, uint32_t acc) {
  asm volatile(
      "{\n.reg .pred p;\nsetp.ne.u32 p, %66, 0;\n"
      "wgmma.mma_async.sync.aligned.m64n128k16.f32.bf16.bf16 "
      "{%0,%1,%2,%3,%4,%5,%6,%7,%8,%9,%10,%11,%12,%13,%14,%15,%16,%17,%18,%19,%20,%21,%22,%23,%24,%25,%26,%27,%28,%29,%30,%31,"
      "%32,%33,%34,%35,%36,%37,%38,%39,%40,%41,%42,%43,%44,%45,%46,%47,%48,%49,%50,%51,%52,%53,%54,%55,%56,%57,%58,%59,%60,%61,%62,%63}, "
      "%64, %65, p, 1, 1, 0, 1;\n}\n"
      : R64(d, 0)
      : "l"(da), "l"(db), "r"(acc));
}
#define WG128(C, ACC)                                                                                                      \
  asm volatile(                                                                                                            \
      "{\n.reg .b64 a, b;\nmov.b64 a, {%64, %66};\nmov.b64 b, {%65, %66};\n"                                               \
      "wgmma.mma_async.sync.aligned.m64n128k16.f32.bf16.bf16 "                                                             \
      "{%0,%1,%2,%3,%4,%5,%6,%7,%8,%9,%10,%11,%12,%13,%14,%15,%16,%17,%18,%19,%20,%21,%22,%23,%24,%25,%26,%27,%28,%29,%30,%31," \
      "%32,%33,%34,%35,%36,%37,%38,%39,%40,%41,%42,%43,%44,%45,%46,%47,%48,%49,%50,%51,%52,%53,%54,%55,%56,%57,%58,%59,%60,%61," \
      "%62,%63}, a, b, " ACC ", 1, 1, 0, 1;\n}\n"                                                                          \
      : Z16(C, d, 0), Z16(C, d, 16), Z16(C, d, 32), Z16(C, d, 48)                                                          \
      : "r"(da), "r"(db), "r"(0x40000040))
#define Z4(C, d, o) C(d[o + 0]), C(d[o + 1]), C(d[o + 2]), C(d[o + 3])
#define Z16(C, d, o) Z4(C, d, o), Z4(C, d, o + 4), Z4(C, d, o + 8), Z4(C, d, o + 12)
__device__ __forceinline__ void wgmma_n128z(float (&d)[64], uint32_t da, uint32_t db) { WG128("=f", "0"); }
__device__ __forceinline__ void wgmma_n128a(float (&d)[64], uint32_t da, uint32_t db) { WG128("+f", "1"); }
template <int N> __device__ __forceinline__ void fence_regs(float (&d)[N]) {
#pragma unroll
  for (int i = 0; i < N; i++) asm volatile("" : "+f"(d[i])::"memory");
}

__device__ __forceinline__ void mma16816(float (&d)[4], uint32_t a0, uint32_t a1, uint32_t a2, uint32_t a3, uint32_t b0,
                                         uint32_t b1) {
  asm("mma.sync.aligned.m16n8k16.row.col.f32.bf16.bf16.f32 {%0,%1,%2,%3}, {%4,%5,%6,%7}, {%8,%9}, {%0,%1,%2,%3};\n"
      : "+f"(d[0]), "+f"(d[1]), "+f"(d[2]), "+f"(d[3])
      : "r"(a0), "r"(a1), "r"(a2), "r"(a3), "r"(b0), "r"(b1));
}
__device__ __forceinline__ void mma16816_z(float (&d)[4], uint32_t a0, uint32_t a1, uint32_t a2, uint32_t a3, uint32_t b0,
                                           uint32_t b1) {
  asm("mma.sync.aligned.m16n8k16.row.col.f32.bf16.bf16.f32 {%0,%1,%2,%3}, {%4,%5,%6,%7}, {%8,%9}, {%10,%10,%10,%10};\n"
      : "=f"(d[0]), "=f"(d[1]), "=f"(d[2]), "=f"(d[3])
      : "r"(a0), "r"(a1), "r"(a2), "r"(a3), "r"(b0), "r"(b1), "f"(0.f));
}
__device__ __forceinline__ void ldsm4t(uint32_t (&r)[4], uint32_t a) {
  asm volatile("ldmatrix.sync.aligned.m8n8.x4.trans.shared.b16 {%0,%1,%2,%3}, [%4];\n"
               : "=r"(r[0]), "=r"(r[1]), "=r"(r[2]), "=r"(r[3]) : "r"(a) : "memory");
}
__device__ __forceinline__ void ldsm2t(uint32_t& r0, uint32_t& r1, uint32_t a) {
  asm volatile("ldmatrix.sync.aligned.m8n8.x2.trans.shared.b16 {%0,%1}, [%2];\n" : "=r"(r0), "=r"(r1) : "r"(a) : "memory");
}
__device__ __forceinline__ void st_async128(uint32_t a, uint32_t bar, uint32_t x, uint32_t y, uint32_t z, uint32_t w) {
  asm volatile("st.async.weak.shared::cluster.mbarrier::complete_tx::bytes.v4.b32 [%0], {%2,%3,%4,%5}, [%1];\n"
               ::"r"(a), "r"(bar), "r"(x), "r"(y), "r"(z), "r"(w) : "memory");
}
__device__ __forceinline__ void mbar_arrive(uint32_t a) {
  asm volatile("mbarrier.arrive.shared::cta.b64 _, [%0];\n" ::"r"(a) : "memory");
}
__device__ __forceinline__ void stsm4(uint32_t a, uint32_t r0, uint32_t r1, uint32_t r2, uint32_t r3) {
  asm volatile("stmatrix.sync.aligned.m8n8.x4.shared.b16 [%0], {%1,%2,%3,%4};\n"
               ::"r"(a), "r"(r0), "r"(r1), "r"(r2), "r"(r3) : "memory");
}
__device__ __forceinline__ void stsm4t(uint32_t a, uint32_t r0, uint32_t r1, uint32_t r2, uint32_t r3) {
  asm volatile("stmatrix.sync.aligned.m8n8.x4.trans.shared.b16 [%0], {%1,%2,%3,%4};\n"
               ::"r"(a), "r"(r0), "r"(r1), "r"(r2), "r"(r3) : "memory");
}
__device__ __forceinline__ uint2 lds64(uint32_t a) {
  uint2 v;
  asm volatile("ld.shared.v2.u32 {%0,%1}, [%2];\n" : "=r"(v.x), "=r"(v.y) : "r"(a));
  return v;
}
__device__ __forceinline__ uint4 lds128(uint32_t a) {
  uint4 v;
  asm volatile("ld.shared.v4.u32 {%0,%1,%2,%3}, [%4];\n" : "=r"(v.x), "=r"(v.y), "=r"(v.z), "=r"(v.w) : "r"(a) : "memory");
  return v;
}
__device__ __forceinline__ void sts128(uint32_t a, uint32_t x, uint32_t y, uint32_t z, uint32_t w) {
  asm volatile("st.shared.v4.u32 [%0], {%1,%2,%3,%4};\n" ::"r"(a), "r"(x), "r"(y), "r"(z), "r"(w) : "memory");
}
__device__ __forceinline__ void sts64(uint32_t a, uint32_t x, uint32_t y) {
  asm volatile("st.shared.v2.u32 [%0], {%1,%2};\n" ::"r"(a), "r"(x), "r"(y) : "memory");
}
__device__ __forceinline__ uint32_t pack_bf16(float lo, float hi) {
  uint32_t r;
  asm("cvt.rn.bf16x2.f32 %0, %1, %2;\n" : "=r"(r) : "f"(hi), "f"(lo));
  return r;
}
__device__ __forceinline__ uint32_t bmul2(uint32_t a, uint32_t b) {
  uint32_t r;
  asm("mul.rn.bf16x2 %0, %1, %2;\n" : "=r"(r) : "r"(a), "r"(b));
  return r;
}
__device__ __forceinline__ uint32_t bmax2(uint32_t a, uint32_t b) {
  uint32_t r;
  asm("max.bf16x2 %0, %1, %2;\n" : "=r"(r) : "r"(a), "r"(b));
  return r;
}
__device__ __forceinline__ uint32_t bfma2(uint32_t a, uint32_t b, uint32_t c) {
  uint32_t r;
  asm("fma.rn.bf16x2 %0, %1, %2, %3;\n" : "=r"(r) : "r"(a), "r"(b), "r"(c));
  return r;
}
__device__ __forceinline__ uint32_t clock32() {
  uint32_t t;
  asm volatile("mov.u32 %0, %%clock;\n" : "=r"(t));
  return t;
}
__device__ __forceinline__ void prefetch_l2(const void* p) { asm volatile("prefetch.global.L2 [%0];\n" ::"l"(p)); }
__device__ __forceinline__ void cp_async16(uint32_t dst, const void* src, uint32_t srcbytes) {
  asm volatile("cp.async.cg.shared.global.L2::256B [%0], [%1], 16, %2;\n" ::"r"(dst), "l"(src), "r"(srcbytes) : "memory");
}
__device__ __forceinline__ uint32_t ld_acquire(const uint32_t* p) {
  uint32_t v;
  asm volatile("ld.acquire.gpu.global.u32 %0, [%1];\n" : "=r"(v) : "l"(p) : "memory");
  return v;
}
__device__ __forceinline__ uint32_t ld_relaxed(const uint32_t* p) {
  uint32_t v;
  asm volatile("ld.relaxed.gpu.global.u32 %0, [%1];\n" : "=r"(v) : "l"(p) : "memory");
  return v;
}
__device__ __forceinline__ void st_release(uint32_t* p, uint32_t v) {
  asm volatile("st.release.gpu.global.u32 [%0], %1;\n" ::"l"(p), "r"(v) : "memory");
}
__device__ __forceinline__ uint4 ld_b128(const uint4* p) {
  unsigned long long a, b;
  asm volatile("{\n.reg .b128 v;\nld.relaxed.gpu.global.b128 v, [%2];\nmov.b128 {%0, %1}, v;\n}\n" : "=l"(a), "=l"(b) : "l"(p) : "memory");
  return make_uint4((uint32_t)a, (uint32_t)(a >> 32), (uint32_t)b, (uint32_t)(b >> 32));
}
__device__ __forceinline__ void st_b128(uint4* p, uint32_t x, uint32_t y, uint32_t z, uint32_t w) {
  asm volatile("{\n.reg .b128 v;\nmov.b128 v, {%1, %2};\nst.relaxed.gpu.global.b128 [%0], v;\n}\n"
               ::"l"(p), "l"(x | (unsigned long long)y << 32), "l"(z | (unsigned long long)w << 32) : "memory");
}

struct Params {
  const __nv_bfloat16* x;
  const __nv_bfloat16* w;
  uint8_t tile[72];
  const __nv_bfloat16* q;
  const __nv_bfloat16* k;
  const __nv_bfloat16* v;
  const __nv_bfloat16* shift_k;
  const __nv_bfloat16* ssm_k;
  const __nv_bfloat16* ssm_D;
  const __nv_bfloat16* wo;
  __nv_bfloat16* out;
  uint32_t zero;
};

__device__ __forceinline__ uint32_t lds32(uint32_t a) {
  uint32_t v;
  asm volatile("ld.shared.u32 %0, [%1];\n" : "=r"(v) : "r"(a) : "memory");
  return v;
}
__device__ __forceinline__ float bf_lo(uint32_t v) {
  uint32_t r;
  asm("prmt.b32 %0, %1, 0, 0x1044;\n" : "=r"(r) : "r"(v));
  return __uint_as_float(r);
}
__device__ __forceinline__ float bf_hi(uint32_t v) { return __uint_as_float(v & 0xffff0000u); }
__device__ __forceinline__ float ex2(float x) {
  float r;
  asm("ex2.approx.ftz.f32 %0, %1;\n" : "=f"(r) : "f"(x));
  return r;
}
__device__ __forceinline__ float rcp(float x) {
  float r;
  asm("rcp.approx.ftz.f32 %0, %1;\n" : "=f"(r) : "f"(x));
  return r;
}

#define Q4(c, d, o) c(d[o + 0]), c(d[o + 1]), c(d[o + 2]), c(d[o + 3])
#define Q8(c, d, o) Q4(c, d, o), Q4(c, d, o + 4)
#define Q16(c, d, o) Q8(c, d, o), Q8(c, d, o + 8)
#define Q32(c, d) Q16(c, d, 0), Q16(c, d, 16)
#define L8 "{%0,%1,%2,%3,%4,%5,%6,%7}"
#define L16 "{%0,%1,%2,%3,%4,%5,%6,%7,%8,%9,%10,%11,%12,%13,%14,%15}"
#define L32 "{%0,%1,%2,%3,%4,%5,%6,%7,%8,%9,%10,%11,%12,%13,%14,%15,%16,%17,%18,%19,%20,%21,%22,%23,%24,%25,%26,%27,%28,%29,%30,%31}"
__device__ __forceinline__ void fft_rows(uint32_t (&d)[32], const uint32_t (&a)[2][4], uint64_t db) {
  asm volatile("wgmma.mma_async.sync.aligned.m64n128k16.f16.f16.f16 " L32 ", {%32,%33,%34,%35}, %36, 0, 1, 1, 1;\n"
               : Q32("=r", d) : "r"(a[0][0]), "r"(a[0][1]), "r"(a[0][2]), "r"(a[0][3]), "l"(db));
  asm volatile("wgmma.mma_async.sync.aligned.m64n128k16.f16.f16.f16 " L32 ", {%32,%33,%34,%35}, %36, 1, 1, 1, 1;\n"
               : Q32("+r", d) : "r"(a[1][0]), "r"(a[1][1]), "r"(a[1][2]), "r"(a[1][3]), "l"(db + 64));
}
template <int INV> __device__ __forceinline__ void fft_cols(uint32_t (&d)[8], const uint32_t (&a)[2][4], uint64_t db) {
  asm volatile("wgmma.mma_async.sync.aligned.m64n32k16.f16.f16.f16 " L8 ", {%8,%9,%10,%11}, %12, 0, 1, 1, %13;\n"
               : Q8("=r", d, 0) : "r"(a[0][0]), "r"(a[0][1]), "r"(a[0][2]), "r"(a[0][3]), "l"(db), "n"(INV));
  asm volatile("wgmma.mma_async.sync.aligned.m64n32k16.f16.f16.f16 " L8 ", {%8,%9,%10,%11}, %12, 1, 1, 1, %13;\n"
               : Q8("+r", d, 0) : "r"(a[1][0]), "r"(a[1][1]), "r"(a[1][2]), "r"(a[1][3]), "l"(db + (INV ? 16 : 64)), "n"(INV));
}
__device__ __forceinline__ void fft_back(float (&d)[16], uint64_t da, uint64_t db) {
  asm volatile("wgmma.mma_async.sync.aligned.m64n32k16.f32.f16.f16 " L16 ", %16, %17, 0, 1, 1, 1, 1;\n"
               : Q16("=f", d, 0) : "l"(da), "l"(db));
#pragma unroll
  for (int i = 1; i < 4; i++)
    asm volatile("wgmma.mma_async.sync.aligned.m64n32k16.f32.f16.f16 " L16 ", %16, %17, 1, 1, 1, 1, 1;\n"
                 : Q16("+f", d, 0) : "l"(da + 32 * i), "l"(db + 64 * i));
}
__device__ __forceinline__ uint32_t hmul2(uint32_t a, uint32_t b) {
  uint32_t r;
  asm("mul.rn.f16x2 %0, %1, %2;\n" : "=r"(r) : "r"(a), "r"(b));
  return r;
}
__device__ __forceinline__ uint32_t hadd2(uint32_t a, uint32_t b) {
  uint32_t r;
  asm("add.rn.f16x2 %0, %1, %2;\n" : "=r"(r) : "r"(a), "r"(b));
  return r;
}
__device__ __forceinline__ uint32_t hneg2(uint32_t a) {
  uint32_t r;
  asm("neg.f16x2 %0, %1;\n" : "=r"(r) : "r"(a));
  return r;
}
__device__ __forceinline__ uint32_t hfma2(uint32_t a, uint32_t b, uint32_t c) {
  uint32_t r;
  asm("fma.rn.f16x2 %0, %1, %2, %3;\n" : "=r"(r) : "r"(a), "r"(b), "r"(c));
  return r;
}
__device__ __forceinline__ uint32_t pack_f16(float lo, float hi) {
  uint32_t r;
  asm("cvt.rn.f16x2.f32 %0, %1, %2;\n" : "=r"(r) : "f"(hi), "f"(lo));
  return r;
}
__device__ __forceinline__ uint32_t bmaxabs2(uint32_t a, uint32_t b) {
  uint32_t r;
  asm("max.xorsign.abs.bf16x2 %0, %1, %2;\n" : "=r"(r) : "r"(a), "r"(b));
  return r;
}
struct C2 { uint32_t r, i; };
__device__ __forceinline__ C2 cmul(C2 a, C2 b) {
  return C2{hfma2(a.r, b.r, hneg2(hmul2(a.i, b.i))), hfma2(a.r, b.i, hmul2(a.i, b.r))};
}
__device__ __forceinline__ C2 cfma(C2 a, C2 b, C2 c) {
  return C2{hfma2(a.r, b.r, hfma2(hneg2(a.i), b.i, c.r)), hfma2(a.r, b.i, hfma2(a.i, b.r, c.i))};
}
__device__ __forceinline__ C2 crot(C2 z, C2 t) {
  const uint32_t r = hfma2(t.r, z.i, z.r), i = hfma2(t.i, r, z.i);
  return C2{hfma2(t.r, i, r), i};
}
__device__ __forceinline__ C2 cget(const uint32_t (&e)[8], int j, int b) { return C2{e[4 * j + b], e[4 * j + 2 + b]}; }
template <int N> __device__ __forceinline__ void fence_regs(uint32_t (&d)[N]) {
#pragma unroll
  for (int i = 0; i < N; i++) asm volatile("" : "+r"(d[i])::"memory");
}
__device__ __forceinline__ void ldsm4(uint32_t (&r)[4], uint32_t a) {
  asm volatile("ldmatrix.sync.aligned.m8n8.x4.shared.b16 {%0,%1,%2,%3}, [%4];\n"
               : "=r"(r[0]), "=r"(r[1]), "=r"(r[2]), "=r"(r[3]) : "r"(a) : "memory");
}

__device__ __forceinline__ uint32_t movm(uint32_t a) {
  uint32_t r;
  asm volatile("movmatrix.sync.aligned.m8n8.trans.b16 %0, %1;\n" : "=r"(r) : "r"(a));
  return r;
}
template <int C0, int H, bool T> __device__ __forceinline__ void attn_pack(const float (&acc)[96], uint32_t (&d)[8]) {
#pragma unroll
  for (int c = 0; c < 8; c++) {
    asm volatile("cvt.rn.bf16x2.f32 %0, %1, %2;\n" : "=r"(d[c]) : "f"(acc[4 * (C0 + c) + 2 * H + 1]), "f"(acc[4 * (C0 + c) + 2 * H]));
    if (T) d[c] = movm(d[c]);
  }
}
__device__ __forceinline__ void attn_qk(float (&s)[4], const uint32_t (&qlo)[8], const uint32_t (&qhi)[8],
                                        const uint32_t (&k)[8], int c) {
  mma16816_z(s, qlo[c], qhi[c], qlo[c + 1], qhi[c + 1], k[c], k[c + 1]);
  mma16816(s, qlo[c + 2], qhi[c + 2], qlo[c + 3], qhi[c + 3], k[c + 2], k[c + 3]);
}
template <int N> __device__ __forceinline__ void quad_softmax(float (&x)[N][2], uint32_t (&pp)[N]) {
  const float c2 = 1.4426950408889634f;
  uint32_t q[N], mx[N / 2];
#pragma unroll
  for (int n = 0; n < N; n++) {
    const uint32_t r = pack_bf16(x[n][0], x[n][1]);
    q[n] = bfma2(r, 0x3e353e35u, bmul2(r, 0x379e379eu));
    x[n][0] = bf_lo(q[n]);
    x[n][1] = bf_hi(q[n]);
  }
#pragma unroll
  for (int n = 0; n < N / 2; n++)
    mx[n] = bmax2(__byte_perm(q[2 * n], q[2 * n + 1], 0x5410), __byte_perm(q[2 * n], q[2 * n + 1], 0x7632));
#pragma unroll
  for (int o = 1; o <= 2; o++) {
#pragma unroll
    for (int n = 0; n < N / 2; n++) mx[n] = bmax2(mx[n], __shfl_xor_sync(0xffffffffu, mx[n], o));
  }
  float m[N], t[N];
#pragma unroll
  for (int n = 0; n < N / 2; n++) {
    m[2 * n] = bf_lo(mx[n]);
    m[2 * n + 1] = bf_hi(mx[n]);
  }
#pragma unroll
  for (int n = 0; n < N; n++) {
    const float nm = -m[n] * c2;
    x[n][0] = ex2(fmaf(x[n][0], c2, nm));
    x[n][1] = ex2(fmaf(x[n][1], c2, nm));
  }
#pragma unroll
  for (int n = 0; n < N; n += 2) {
    float u0, u1;
    asm("mma.sync.aligned.m16n8k8.row.col.f32.tf32.tf32.f32 {%0,%1,%2,%3}, {%4,%5,%6,%7}, {%8,%8}, {%9,%9,%9,%9};\n"
        : "=f"(t[n]), "=f"(u0), "=f"(t[n + 1]), "=f"(u1)
        : "r"(__float_as_uint(x[n][0])), "r"(__float_as_uint(x[n + 1][0])), "r"(__float_as_uint(x[n][1])),
          "r"(__float_as_uint(x[n + 1][1])), "r"(0x3f800000u), "f"(0.f));
  }
#pragma unroll
  for (int n = 0; n < N; n++) {
    const float inv = rcp(t[n]);
    pp[n] = pack_bf16(x[n][0] * inv, x[n][1] * inv);
  }
}
template <bool SPLIT>
__device__ __forceinline__ void attn_pv(uint32_t dst, const uint32_t (&vp)[8], const uint32_t (&vo)[8], int c, uint32_t pp,
                                        uint32_t maskLE) {
  const uint32_t b0 = pp & ~maskLE, b1 = pp & maskLE;
  float o[2][4];
#pragma unroll
  for (int i = 0; i < 2; i++) {
    if (SPLIT) {
      asm("mma.sync.aligned.m16n8k8.row.col.f32.bf16.bf16.f32 {%0,%1,%2,%3}, {%4,%5}, {%6}, {%7,%7,%7,%7};\n"
          : "=f"(o[i][0]), "=f"(o[i][1]), "=f"(o[i][2]), "=f"(o[i][3])
          : "r"(vp[c + 2 * i]), "r"(vp[c + 2 * i + 1]), "r"(b0), "f"(0.f));
      asm("mma.sync.aligned.m16n8k8.row.col.f32.bf16.bf16.f32 {%0,%1,%2,%3}, {%4,%5}, {%6}, {%0,%1,%2,%3};\n"
          : "+f"(o[i][0]), "+f"(o[i][1]), "+f"(o[i][2]), "+f"(o[i][3])
          : "r"(vo[c + 2 * i]), "r"(vo[c + 2 * i + 1]), "r"(b1));
    } else {
      mma16816_z(o[i], vp[c + 2 * i], vp[c + 2 * i + 1], vo[c + 2 * i], vo[c + 2 * i + 1], b0, b1);
    }
  }
  stsm4t(dst, pack_bf16(o[0][0], o[0][1]), pack_bf16(o[0][2], o[0][3]), pack_bf16(o[1][0], o[1][1]),
         pack_bf16(o[1][2], o[1][3]));
}

template <int MODE>
__global__ void __cluster_dims__(2, 1, 1) __launch_bounds__(NTHREADS, 1)
fused_kernel(const Params p, const __grid_constant__ CUtensorMap tmX, const __grid_constant__ CUtensorMap tmW,
             const __grid_constant__ CUtensorMap tmWo, const __grid_constant__ CUtensorMap tmWp,
             const __grid_constant__ CUtensorMap tmQ,
             const __grid_constant__ CUtensorMap tmOb,
             const __grid_constant__ CUtensorMap tmXh, const __grid_constant__ CUtensorMap tmWh) {
  extern __shared__ __align__(1024) uint8_t smem[];
  const int tid = threadIdx.x;
  if (tid >= PFW * 32 && tid < PFW * 32 + 32) {
    const uint32_t i = (blockIdx.x & 127) * 16 + (tid & 15);
    prefetch_l2(tid & 16 ? (const char*)p.w + i * 128 : (const char*)p.x + i * 2048);
  }
  const uint32_t sb = smem_u32(smem);
  const int rank = blockIdx.x & 1;
  const bool halo_cta = blockIdx.x < 4;
  if (halo_cta && MODE != 0) return;
  const int tile = p.tile[blockIdx.x >> 1];
  const int rg = tile >> 3, hp = (tile & 7) * 2 + rank;
  const int par = rg >> 2, gidx = rg & 3;
  if (tid < 256 && !halo_cta && MODE != 2) {
    const uint32_t r = tid >> 3, c = tid & 7;
    asm volatile(
        "cp.async.cg.shared.global [%0 + 98304], [%1], 16;\ncp.async.cg.shared.global [%0 + 102400], [%1 + 2048], 16;\n"
        "cp.async.cg.shared.global [%0 + 106496], [%1 + 4096], 16;\ncp.async.cg.shared.global [%0], [%2], 16;\n"
        "cp.async.cg.shared.global [%0 + 4096], [%2 + 131072], 16;\ncp.async.cg.shared.global [%0 + 8192], [%2 + 262144], 16;\n"
        "cp.async.cg.shared.global [%0 + 12288], [%2 + 393216], 16;\ncp.async.cg.shared.global [%0 + 16384], [%2 + 524288], 16;\n"
        "cp.async.cg.shared.global [%0 + 20480], [%2 + 655360], 16;\ncp.async.cg.shared.global [%0 + 24576], [%2 + 786432], 16;\n"
        "cp.async.cg.shared.global [%0 + 28672], [%2 + 917504], 16;\ncp.async.commit_group;\n"
        ::"r"(sb + r * 128 + ((c ^ (r & 7)) << 4)), "l"((const char*)p.w + (r * 6144 + c * 16 + hp * 128)),
        "l"((const char*)p.x + (r * 4096 + c * 16 + gidx * 1048576 + par * 2048)) : "memory");
    static_assert(OFF_1B == 98304, "offsets above");
  }
  const uint32_t bars = sb + OFF_BAR;
  const int lane = tid & 31, warp = __shfl_sync(0xffffffffu, tid >> 5, 0);
  const int grp = par * 4 + (hp >> 2), mem = gidx * 2 + ((hp >> 1) & 1);
  const int rb2 = par * 8 + mem, cb2 = (grp & 3) * 2 + rank;
  const int chb = grp * 16 + mem * 2 + rank;
  const int cta = rg * 16 + hp;
  const int hsel = rb2 & 1;

  if (warp >= 8) {
    asm volatile("setmaxnreg.dec.sync.aligned.u32 %0;\n" :: "n"(REG_HELP));
    auto halo_issue = [&](int n, int s) {
      const uint32_t fb = bars + 8 * (BAR_FULLB + s), st = sb + s * STGH;
      tma_load_3d(st + 8192, &tmWh, fb, 0, (n >> 1) * 64, 16 + (n & 1) * 16 + blockIdx.x * 4);
      tma_load_4d(st, &tmXh, fb, (n >> 1) * 64, 248, 0, 0);
      mbar_expect_tx(fb, STGH - 2048);
    };
    if (tid == 256) {
      prefetch_tmap(halo_cta ? &tmXh : &tmX);
#pragma unroll
      for (int i = 0; i < NS1B; i++) mbar_init(bars + 8 * (BAR_FULLB + i), 1);
#pragma unroll
      for (int i = 0; i < NS1A; i++) mbar_init(bars + 8 * (BAR_FULLA + i), 1);
      asm volatile("fence.mbarrier_init.release.cluster;\n" ::: "memory");
      if (!halo_cta && MODE != 2) {
        mbar_expect_tx(bars + 8 * (BAR_FULLB + 1), STG1B);
        tma_load_3d(sb + OFF_1B + 1 * STG1B, &tmW, bars + 8 * (BAR_FULLB + 1), hp * 64, 32, 0);
        mbar_expect_tx(bars + 8 * (BAR_FULLB + 2), STG1B);
        tma_load_3d(sb + OFF_1B + 2 * STG1B, &tmW, bars + 8 * (BAR_FULLB + 2), hp * 64, 64, 0);
        mbar_arrive(bars + 8 * BAR_FULLA);
        mbar_arrive(bars + 8 * BAR_FULLB);
      } else if (halo_cta) {
        halo_issue(0, 0);
      }
    } else if (tid >= 289 && tid < 289 + 48 && tid != 320) {
      const uint32_t i = tid - 289 - (tid > 320), b = blockIdx.x & 127;
      if (MODE != 2) prefetch_l2(i < 16 ? (const char*)p.x + (b * 16 + i) * 2048 + 128 : (const char*)p.w + (2048 + b * 31 + i - 16) * 128);
    } else if (tid == 288) {
#pragma unroll
      for (int i = 0; i < NS1A; i++) mbar_init(bars + 8 * (BAR_EMPTYA + i), 4);
#pragma unroll
      for (int i = 0; i < NS1B; i++) mbar_init(bars + 8 * (BAR_EMPTYB + i), 2);
      mbar_init(bars + 8 * BAR_X, 3);
      mbar_init(bars + 8 * BAR_TAB, 16);
      mbar_init(bars + 8 * BAR_U, 1);
      mbar_init(bars + 8 * BAR_H, 1);
      mbar_init(bars + 8 * BAR_STG, 8);
      mbar_init(bars + 8 * BAR_Q, 1);
      mbar_init(bars + 8 * BAR_LAND, 5);
      mbar_init(bars + 8 * (BAR_LAND + 1), 5);
      asm volatile("fence.mbarrier_init.release.cluster;\n" ::: "memory");
    } else if (tid == 320) {
#pragma unroll
      for (int i = 0; i < NS2; i++) {
        mbar_init(bars + 8 * (BAR_FULL2 + i), 1);
        mbar_init(bars + 8 * (BAR_EMPTY2 + i), 2);
        mbar_init(bars + 8 * (BAR_EMPTY2B + i), 2);
      }
      asm volatile("fence.mbarrier_init.release.cluster;\n" ::: "memory");
    } else if (tid == 352) {
#pragma unroll
      for (int i = 0; i < 4; i++) mbar_init(bars + 8 * (BAR_Y + i), i < 2 ? 4 : i == 2 ? 10 : 8);
      mbar_init(bars + 8 * BAR_XFREE, 1);
#pragma unroll
      for (int i = 0; i < 9; i++) mbar_init(bars + 8 * (BAR_KH + i), 1);
      asm volatile("fence.mbarrier_init.release.cluster;\n" ::: "memory");
    }
    __syncwarp();
    cluster_sync_all();
    if (warp == 8) PROF2(24);
    const int hw = warp - 8;
    const int lr = lane & 7, lm = lane >> 3;
    auto g1_issue_a = [&](int j, int s) {
      const uint32_t fb = bars + 8 * (BAR_FULLA + s);
      mbar_expect_tx(fb, STG1A);
      tma_load_3d_mc(sb + s * STG1A + rank * 16384, &tmX, fb, j * 64, par, gidx * 256 + rank * 128);
    };
    auto g1_issue_b = [&](int kb, int s) {
      const uint32_t fb = bars + 8 * (BAR_FULLB + s);
      mbar_expect_tx(fb, STG1B);
      tma_load_3d(sb + OFF_1B + s * STG1B, &tmW, fb, hp * 64, kb * 32, 0);
    };
    auto g2_k = [&](int kb) { return (kb < 2 ? hp : kb < 4 ? hp & 14 : hp & 12) ^ kb; };
    auto g2_issue_b = [&](uint32_t fb, uint32_t bytes, uint32_t dst, int k0, bool whole) {
      if (whole) {
        tma_load_3d(dst, &tmWo, fb, 0, k0, cb2 * 2);
      } else {
#pragma unroll
        for (int i = 0; i < 4; i++)
          tma_load_3d(dst + (i & 1) * XT + (i >> 1) * 4 * XT, &tmWp, fb, 0, k0 + (i >> 1) * 32, cb2 * 2 + (i & 1));
      }
      mbar_expect_tx(fb, bytes);
    };
    auto send_y = [&](uint32_t o, uint32_t step, int half) {
      const uint32_t peer = mapa(sb, rank ^ 1);
      o += OFF_X + (rank ^ 1) * 4096 + half * 2048 + lane * 16;
      uint4 a[8];
#pragma unroll
      for (int i = 0; i < 8; i++) a[i] = lds128(sb + o + (i >> 2) * step + (i & 2) * (XT / 2) + (i & 1) * 512);
#pragma unroll
      for (int i = 0; i < 8; i++)
        st_async128(peer + o + 1024 + (i >> 2) * step + (i & 2) * (XT / 2) + (i & 1) * 512,
                    peer + OFF_BAR + 8 * (BAR_LAND + half), a[i].x, a[i].y, a[i].z, a[i].w);
    };

    if (halo_cta) {
      if (hw == 0) {
        int s = 1, ph = 1;
#pragma unroll 1
        for (int n = 1; n < 32; n++) {
          mbar_wait(bars + 8 * (BAR_EMPTYB + s), ph);
          if (elect_one()) halo_issue(n, s);
          if (++s == NS1B) { s = 0; ph ^= 1; }
        }
      }
      __syncwarp();
    } else if (hw == 0) {
      uint32_t epoch = 0;
      if (MODE == 2) {
        if (lane < NS2) mbar_arrive_cluster_n(mapa(bars, rank) + 8 * (BAR_EMPTY2 + lane), 2);
      } else {
      if (lane == 0) {
        mbar_expect_tx(bars + 8 * BAR_U, 32768);
        mbar_expect_tx(bars + 8 * BAR_LAND, 8192);
        mbar_expect_tx(bars + 8 * (BAR_LAND + 1), 8192);
        mbar_expect_tx(bars + 8 * BAR_Q, 32768);
        prefetch_tmap(&tmQ);
      }
      {
        int sa = 1, pha = 1, sbb = 2, phb = 1;
#pragma unroll 1
        for (int kb = 2; kb < 32; kb++) {
          if (!(kb & 1)) {
            mbar_wait(bars + 8 * (BAR_EMPTYA + sa), pha);
            if (elect_one()) g1_issue_a(kb >> 1, sa);
            if (++sa == NS1A) { sa = 0; pha ^= 1; }
          }
          mbar_wait(bars + 8 * (BAR_EMPTYB + sbb), phb);
          if (kb > 2 && elect_one()) g1_issue_b(kb, sbb);
          __syncwarp();
          if (kb == 4) epoch = ld_relaxed(g_flag_o + FS * cta);
          if (kb == 4) PROF2(27);
          if (kb == 1) PROF2(38);
          if (kb == 2) PROF2(39);
          if (++sbb == NS1B) { sbb = 0; phb ^= 1; }
        }
      }
      auto q_issue = [&](int i) {
        mbar_wait(bars + 8 * (i ? BAR_EMPTYB + 3 : BAR_EMPTYA + 1), i);
        if (elect_one())
          asm volatile(
              "cp.async.bulk.tensor.5d.shared::cluster.global.mbarrier::complete_tx::bytes [%0], [%1, {%3, %4, %4, %4, %5}], [%2];\n"
              ::"r"(sb + (i ? OFF_Q1 : OFF_Q0)), "l"(&tmQ), "r"(bars + 8 * BAR_Q), "r"((chb & ~1) * 8), "r"(0), "r"(rank * 32 + i * 64)
              : "memory");
        __syncwarp();
      };
      epoch++;
      if (lane == 0) {
        prefetch_tmap(&tmWo);
        prefetch_tmap(&tmWp);
        prefetch_tmap(&tmOb);
      }
      __syncwarp();
      {
        uint4 h[6] = {};
        if (gidx != 0) {
#pragma unroll 1
          for (int n = 0; n < SPIN_LIMIT; n++) {
            bool ok = true;
#pragma unroll
            for (int i = 0; i < 6; i++) h[i] = ld_b128(g_halo + cta * 192 + i * 32 + lane);
#pragma unroll
            for (int i = 0; i < 6; i++) ok = ok && h[i].w == epoch;
            if (__all_sync(0xffffffffu, ok)) break;
          }
          PROF(18);
        }
        q_issue(0);
        sts128(sb + OFF_KH + lane * 16, h[0].x, h[0].y, h[0].z, h[1].x);
        sts128(sb + OFF_KH + 512 + lane * 16, h[1].y, h[1].z, h[2].x, h[2].y);
        sts64(sb + OFF_KH + 1024 + lane * 8, h[3].x, h[3].y);
        sts64(sb + OFF_KH + 1280 + lane * 8, h[3].z, h[4].x);
        sts64(sb + OFF_KH + 1536 + lane * 8, h[4].y, h[4].z);
        sts64(sb + OFF_KH + 1792 + lane * 8, h[5].x, h[5].y);
        __syncwarp();
        if (lane == 0) mbar_arrive(bars + 8 * BAR_KH);
      }
      q_issue(1);
      const uint32_t rb = mapa(bars, lane & 1);
      nb_sync(NB_OREADY, 288);
      if (lane == 0) {
        asm volatile("cp.async.bulk.global.shared::cta.bulk_group [%0], [%1], %2;\n" ::"l"(g_o + (size_t)cta * 16384),
                     "r"(sb + OFF_OP), "r"(32768) : "memory");
        bulk_commit();
      }
      if (lane < 2) {
#pragma unroll
        for (int i = 0; i < 4; i++) mbar_arrive_cluster(rb + 8 * (BAR_EMPTY2 + i + i / 2));
      }
      if (lane == 0) {
        bulk_wait0();
        st_release(g_flag_o + FS * cta, epoch);
      }
      __syncwarp();
      PROF2(17);
      if (lane < 2) mbar_arrive_cluster(rb + 8 * (BAR_EMPTY2 + 2));
      }
      if (MODE != 1) {
        const __nv_bfloat16* osrc = g_o + (size_t)(rb2 >> 1) * 16 * 16384 + hsel * 8192;
        mbar_wait(bars + 8 * (BAR_EMPTY2 + 1), 0);
        if (elect_one()) {
          if (MODE == 0) {
            asm volatile("cp.async.bulk.shared::cluster.shared::cta.mbarrier::complete_tx::bytes [%0], [%1], %2, [%3];\n"
                         ::"r"(mapa(sb + g2_a(1, hsel), rank ^ 1)), "r"(sb + g2_a(0, hsel)), "r"(16384),
                         "r"(mapa(bars + 8 * (BAR_FULL2 + 1), rank ^ 1)) : "memory");
          } else {
            bulk_load(sb + g2_a(0, hsel), osrc + hp * 16384, 16384, bars + 8 * BAR_FULL2);
            bulk_load(sb + g2_a(1, hsel), osrc + (hp ^ 1) * 16384, 16384, bars + 8 * (BAR_FULL2 + 1));
          }
#pragma unroll
          for (int kb = NB0; kb < 3; kb++)
            g2_issue_b(bars + 8 * (BAR_FULL2 + kb), kb || MODE ? STG2 : STG2 / 2, sb + g2_b(kb, 0), g2_k(kb) * 64, true);
        }
        __syncwarp();
      }
      if (MODE != 2) {
        mbar_wait(bars + 8 * (BAR_Y + 2), 0);
        send_y(0, 4 * XT, 1);
        fence_async_smem();
        __syncwarp();
      }
      if (MODE != 1) {
        int s = 3, k0 = g2_k(3) * 64;
        uint32_t wbar = bars + 8 * (BAR_Y + 2), fb = bars + 8 * (BAR_FULL2 + 3), dst = sb + g2_b(3, rank), ph = MODE ? 1 : 0;
        int whole = 0;
#pragma unroll 1
        for (int kb = 3; kb < 16;) {
          mbar_wait(wbar, ph);
          if (elect_one()) g2_issue_b(fb, STG2, dst, k0, whole);
          __syncwarp();
          kb++;
          if (++s == NS2) { s = 0; ph = kb == 2 * NS2; }
          wbar = bars + 8 * (kb == 4 ? BAR_XFREE : BAR_EMPTY2B + s);
          fb = bars + 8 * (BAR_FULL2 + s);
          dst = sb + g2_b(s, rank);
          k0 = ((hp & 12) ^ kb) * 64;
          whole = s < 3;
          asm volatile("" : "+r"(fb), "+r"(k0), "+r"(whole));
        }
      }
      __syncwarp();
    } else {
      if (MODE != 2) {
      const float dall = __bfloat162float(p.ssm_D[chb * 8 + lr]);
      {
        const int g = lane >> 2, t = lane & 3;
        uint32_t w[2][4];
#pragma unroll
        for (int h = 0; h < 2; h++) {
          const uint2 x = __ldg(reinterpret_cast<const uint2*>(p.shift_k + ((chb & ~1) * 8 + h * 8 + g) * 4));
          w[h][0] = __byte_perm(x.x, x.x, 0x1010);
          w[h][1] = __byte_perm(x.x, x.x, 0x3232);
          w[h][2] = __byte_perm(x.y, x.y, 0x1010);
          w[h][3] = __byte_perm(x.y, x.y, 0x3232);
        }
        auto swz = [](int r) { return (((r & 29) | ((r ^ (r >> 2)) & 2)) << 5) | (r & 16); };
        const uint32_t kring = sb + OFF_X + 4096 + (hw - 1) * 2 * XT, vring = kring + XT;
        const int s0 = rank * 32 + (hw - 1) * 11, s1 = hw == 3 ? rank * 32 + 32 : s0 + 11;
        const size_t goff = (size_t)(s0 * 32 + (lane >> 1)) * DM + (chb & ~1) * 8 + (lane & 1) * 8;
        const __nv_bfloat16* kg = p.k + goff;
        const __nv_bfloat16* vg = p.v + goff;
        const uint32_t d0 = swz(lane >> 1) ^ ((lane & 1) << 4), d1 = swz(16 + (lane >> 1)) ^ ((lane & 1) << 4);
        auto issue = [&](int st) {
          const uint32_t a = kring + ((st & 3) << 10);
          asm volatile("cp.async.cg.shared.global.L2::256B [%0], [%2], 16;\n"
                       "cp.async.cg.shared.global.L2::256B [%1], [%2 + 32768], 16;\n"
                       "cp.async.cg.shared.global.L2::256B [%0 + 8192], [%3], 16;\n"
                       "cp.async.cg.shared.global.L2::256B [%1 + 8192], [%3 + 32768], 16;\n"
                       ::"r"(a + d0), "r"(a + d1), "l"(kg), "l"(vg) : "memory");
          kg += 32 * DM;
          vg += 32 * DM;
          asm volatile("" : "+l"(kg), "+l"(vg));
        };
        const int xa = 8 * (lr >> 1) + 2 * lm + (lr & 1), xb = 8 * (lr >> 1) - 4 + 2 * (lm & 1) + (lr & 1);
        const uint32_t la = swz(xa), lb = swz(xb & 31);
        const int backb = xb < 0 ? 1 : 0;
        const uint32_t ud[2] = {mapa(sb + OFF_X + g * XT + t * 16, 0), mapa(sb + OFF_X + g * XT + t * 16, 1)};
        const uint32_t ub[2] = {mapa(bars + 8 * BAR_U, 0), mapa(bars + 8 * BAR_U, 1)};
        if (tid == 320) prefetch_l2(g_tab + (chb & 63) * 32);
        if (lane == 0) mbar_wait(bars + 8 * (BAR_FULLB + NS1B - 1), 0);
        __syncwarp();
        if (lane >= 24) cp_async16(kring + (((s0 - 1) & 3) << 10) + d1, s0 > 0 ? kg - 16 * DM : kg, s0 > 0 ? 16 : 0);
        issue(s0);
        asm volatile("cp.async.commit_group;\n" ::: "memory");
        issue(s0 + 1);
        asm volatile("cp.async.commit_group;\n" ::: "memory");
        const __nv_bfloat16* hg = p.ssm_k + (size_t)chb * 8 * SEQ + lane * 64;
        uint32_t tn = clock32();
#pragma unroll 1
        for (int st = s0; st < s1; st++) {
          tn += PSTEP;
          while ((int)(clock32() - tn) < 0) __nanosleep(100);
          if (st + 2 < s1) issue(st + 2);
          if (hw == 1 && st - s0 < 8) prefetch_l2(hg);
          hg += SEQ;
          asm volatile("" : "+l"(hg));
          asm volatile("cp.async.commit_group;\n" ::: "memory");
          asm volatile("cp.async.wait_group 2;\n" ::: "memory");
          __syncwarp();
#pragma unroll
          for (int h = 0; h < 2; h++) {
            uint32_t e[6], vv[4], e4[4];
            ldsm4t(e4, kring + ((st & 3) << 10) + (la ^ (h << 4)));
            ldsm2t(e[0], e[1], kring + (((st - backb) & 3) << 10) + (lb ^ (h << 4)));
            ldsm4t(vv, vring + ((st & 3) << 10) + (la ^ (h << 4)));
            e[2] = e4[0]; e[3] = e4[1]; e[4] = e4[2]; e[5] = e4[3];
            uint32_t o[5];
#pragma unroll
            for (int i = 0; i < 5; i++) o[i] = __byte_perm(e[i], e[i + 1], 0x5432);
#pragma unroll
            for (int i = 0; i < 4; i++) {
              uint32_t a = bmul2(o[i], w[h][3]);
              a = bfma2(e[i + 1], w[h][2], a);
              a = bfma2(o[i + 1], w[h][1], a);
              a = bfma2(e[i + 2], w[h][0], a);
              vv[i] = bmul2(a, vv[i]);
            }
            st_async128(ud[h] + (st ^ (g & 1)) * 64, ub[h], vv[0], vv[1], vv[2], vv[3]);
          }
          __syncwarp();
        }
        fence_async_smem();
        PROF(16);
      }
      nb_sync(NB_HELP3, 96);
      if (hw == 1 && elect_one()) {
        mbar_expect_tx(bars + 8 * BAR_H, 8 * 4096 + 6144);
#pragma unroll 1
        for (int c = 0; c < 8; c++)
          bulk_load(sb + OFF_X + c * XT + 4096, p.ssm_k + (size_t)(chb * 8 + c) * SEQ, 4096, bars + 8 * BAR_H);
        bulk_load(sb + OFF_T16, g_tab, 2048, bars + 8 * BAR_H);
        bulk_load(sb + OFF_T32, g_tab + 512, 4096, bars + 8 * BAR_H);
      }
      __syncwarp();
      {
        if (hw == 3) {
          const char* wo = (const char*)p.wo + chb * 16384 + lane * 128;
#pragma unroll
          for (int i = 0; i < 4; i++) prefetch_l2(wo + i * 4096);
        }
        if (QPF && hw == 2) {
          const char* q = (const char*)p.q + chb * 32768 + lane * 128;
#pragma unroll
          for (int i = 0; i < 8; i++) prefetch_l2(q + i * 4096);
        }
        const int ck = 16 * (lane >> 4) + 2 * lr + (((lane >> 3) ^ (lane >> 2)) & 1);
        const uint32_t xo = (ck >> 1) * 64, xs = ((ck & 1) ^ (lr >> 1)) << 4;
#pragma unroll 1
        for (int job = hw - 1; job < 16; job += 3) {
          const int c = job & 7;
          uint4 a[8];
          float dv = __shfl_sync(0xffffffffu, dall, c);
          if (job < 8 || lane) dv = 0.f;
          const uint32_t xt = sb + OFF_X + c * XT + (job >> 3) * 4096;
          mbar_wait(bars + 8 * (job < 8 ? BAR_U : BAR_H), 0);
#pragma unroll
          for (int i = 0; i < 8; i++) a[i] = lds128(xt + i * 512 + ((ck ^ (job < 8 ? (c & 1) << 2 : 0)) << 4));
          dv += bf_lo(a[0].x);
          uint32_t m[2] = {bmaxabs2(pack_bf16(dv, 0.f), bmaxabs2(a[0].x, a[0].y)), bmaxabs2(a[0].z, a[0].w)};
#pragma unroll
          for (int i = 1; i < 8; i++) {
            m[0] = bmaxabs2(bmaxabs2(m[0], a[i].x), a[i].y);
            m[1] = bmaxabs2(bmaxabs2(m[1], a[i].z), a[i].w);
          }
          m[0] = bmaxabs2(m[0], m[1]);
          const int f = max(252 - (int)(__reduce_max_sync(0xffffffffu, max(m[0] & 0x7fffu, (m[0] >> 16) & 0x7fffu)) >> 7), 1);
          if (lane == 0) asm volatile("st.shared.u32 [%0], %1;\n" ::"r"(sb + OFF_EX + job * 4), "r"(f) : "memory");
          if (f < 113) {
#pragma unroll
            for (int i = 0; i < 8; i++)
              a[i] = make_uint4(bmul2(a[i].x, f * 0x00800080u), bmul2(a[i].y, f * 0x00800080u), bmul2(a[i].z, f * 0x00800080u),
                                bmul2(a[i].w, f * 0x00800080u));
          }
          const uint32_t mul = (f < 113 ? 15 : f - 112) * 0x00800080u;
          auto cv = [&](uint32_t x) {
            x = bmul2(x, mul);
            return (x & 0x0fff0fffu) * 7 + x;
          };
          const uint32_t dst = xt + xo;
#pragma unroll
          for (int i = 0; i < 8; i++)
            sts128(dst + (i >> 2) * 2048 + (i & 1) * 1024 + (xs ^ ((i & 2) << 4)),
                   i ? cv(a[i].x) : __byte_perm(pack_f16(dv * __uint_as_float(f << 23), 0.f), cv(a[i].x), 0x7610), cv(a[i].y),
                   cv(a[i].z), cv(a[i].w));
        }
        fence_async_smem();
        __syncwarp();
        if (lane == 0) mbar_arrive(bars + 8 * BAR_X);
        PROF(19);
      }
      if (hw < 3) {
#pragma unroll 1
        for (int n = 0; n < SPIN_LIMIT && !mbar_try(bars + 8 * (BAR_Y + hw - 1), 0); n++) __nanosleep(100);
        send_y((hw - 1) * 4 * XT, 2 * XT, 0);
        __syncwarp();
        if (lane == 0) mbar_arrive(bars + 8 * (BAR_Y + 2));
        PROF(32);
        const int c8 = 2 * lm + (lr & 1), src = (lr >> 1) & 1;
        uint32_t fa = sb + OFF_X + c8 * XT + rank * 4096 + (src == rank ? 0 : 1024) + (hw - 1) * 512;
        const uint32_t fx = ((lr >> 2) ^ ((lr & 3) << 1)) << 4;
        uint32_t qa = sb + OFF_Q0 + (hw - 1) * 8192 + (lane >> 3) * 128 + (lane & 2) * 32 + (lane & 4) * 8 + (lane & 1) * 16;
        uint4* og = reinterpret_cast<uint4*>(p.out + (size_t)(rank * 512 + (hw - 1) * 256 + (lane & 2) * 4 + (lane >> 2)) * (2 * DM) +
                                             (chb & ~1) * 8 + (lane & 1) * 8);
        mbar_wait(bars + 8 * BAR_Q, 0);
        uint32_t tn = 0;
        const uint32_t pace = hw == 2 ? FPACE2 : FPACE;
#pragma unroll 1
        for (int j = 0; j < 4; j++) {
          if (!(j & 1)) {
            mbar_wait(bars + 8 * (BAR_LAND + (j >> 1)), 0);
            tn = clock32() + (j ? 0 : (hw - 1) * (FPACE / 2));
            PROF2(33 + j * 2);
          }
#pragma unroll
          for (int i = 0; i < 8; i++) {
            if (i == JS && j == 0 && hw == 2) {
              mbar_wait(bars + 8 * (BAR_Y + 3), 0);
              send_y(2 * XT, 4 * XT, 1);
              fence_async_smem();
              __syncwarp();
              if (lane == 0) mbar_arrive(bars + 8 * BAR_XFREE);
              tn = clock32();
            }
            uint32_t y[4];
            const uint4 q = lds128(qa + i * 512);
            ldsm4t(y, fa + (i >> 2) * 128 + (fx ^ ((i & 3) << 5) ^ ((i >> 2) << 4)));
            while ((int)(clock32() - tn) < 0) __nanosleep(50);
            tn += j == 3 ? FPACE3 : pace;
            og[i * 16 * (2 * DM / 8)] = make_uint4(bmul2(q.x, y[0]), bmul2(q.y, y[1]), bmul2(q.z, y[2]), bmul2(q.w, y[3]));
          }
          qa += j & 1 ? OFF_Q1 - OFF_Q0 - 4096 : 4096;
          fa += j & 1 ? 2048 - 256 : 256;
          og += (j & 1 ? 1024 - 128 : 128) * (2 * DM / 8);
        }
        PROF(22);
      }
      }
      if (MODE != 1 && hw == 3) {
        const uint32_t epoch = ld_relaxed(g_flag_o + FS * cta) + 1;
        if (MODE == 0) nb_sync(NB_G1END, 288);
        if (elect_one()) {
#pragma unroll
          for (int kb = 0; kb < NB0; kb++)
            g2_issue_b(bars + 8 * (BAR_FULL2 + kb), kb || MODE ? STG2 : STG2 / 2, sb + g2_b(kb, 0), g2_k(kb) * 64, true);
        }
        __syncwarp();
        const __nv_bfloat16* osrc = g_o + (size_t)(rb2 >> 1) * 16 * 16384 + hsel * 8192;
        if (MODE == 0) __nanosleep(1500);
        mbar_wait(bars + 8 * (BAR_EMPTY2 + 2), 0);
        const uint32_t* flag = g_flag_o + FS * ((rb2 >> 1) * 16 + g2_k(lane & 15));
        uint32_t ready = MODE == 0 ? 0u : ~0u;
        int s = 1, ph = 0;
#pragma unroll 1
        for (int kb = 2; kb < 16; kb++) {
          if (++s == NS2) { s = 0; ph ^= 1; }
          uint32_t fb = bars + 8 * (BAR_FULL2 + s), dst = sb + g2_a(s, hsel) + rank * 8192;
          const __nv_bfloat16* src = osrc + rank * 4096 + (uint32_t)g2_k(kb) * 16384;
          asm volatile("" : "+r"(fb), "+r"(dst), "+l"(src));
          if (!(ready >> kb & 1)) {
#pragma unroll 1
            for (int n = 0; n < SPIN_LIMIT && !(ready >> kb & 1); n++)
              ready = __ballot_sync(0xffffffffu, ld_acquire(flag) == epoch);
            fence_async_all();
          }
          if (kb == 2) PROF(21);
          if (MODE == 0 && kb == 4 && rank == 1) mbar_wait(bars + 8 * BAR_TAB, 0);
          mbar_wait(fb + 8 * (BAR_EMPTY2 - BAR_FULL2), ph);
          if (elect_one()) {
            asm volatile(
                "cp.async.bulk.shared::cluster.global.mbarrier::complete_tx::bytes.multicast::cluster [%0], [%1], %2, [%3], %4;\n"
                ::"r"(dst), "l"(src), "r"(8192), "r"(fb), "h"((uint16_t)3) : "memory");
          }
          __syncwarp();
        }
      }
    }
    cluster_sync_all();
    PROF_DUMP();
  } else {
    asm volatile("barrier.cluster.arrive.relaxed.aligned;\n" ::: "memory");
    asm volatile("setmaxnreg.inc.sync.aligned.u32 %0;\n" :: "n"(REG_MATH));
    if (halo_cta || MODE == 2) asm volatile("barrier.cluster.wait.aligned;\n" ::: "memory");
    if (warp == 0) PROF2(26);
    const int wg = warp >> 2;
    const int wtid = tid & 127;
    const bool signaller = (wtid == 0) || (wtid == 32);
    const uint32_t rbars = mapa(bars, wtid >> 5 & 1);

    if (halo_cta) {
      const uint32_t epoch = ld_relaxed(g_flag_o + FS * (16 + blockIdx.x * 4)) + 1;
      float acc0[64], acc1[64];
      int s = wg, ph = 0;
#pragma unroll 1
      for (int kb = 0; kb < 16; kb++) {
        mbar_wait(bars + 8 * (BAR_FULLB + s), ph);
        const uint32_t st = sb + s * STGH;
        const uint64_t da = mkdesc(st, 16, 1024, 1);
        const uint64_t db = mkdesc(st + 8192, 8192, 1024, 1);
        wg_fence();
#pragma unroll
        for (int kk = 0; kk < 4; kk++) {
          wgmma_n128(acc0, da + 2 * kk, db + 128 * kk, kb + kk);
          wgmma_n128(acc1, da + 2 * kk, db + 1024 + 128 * kk, kb + kk);
        }
        wg_commit();
        wg_wait<0>();
        if (kb == 15) PROF(37);
        if (wtid < 2) mbar_arrive(bars + 8 * (BAR_EMPTYB + s));
        if ((s += 2) >= NS1B) { s -= NS1B; ph ^= 1; }
      }
      fence_regs(acc0);
      fence_regs(acc1);
      if ((warp & 3) != 3) {
        auto put = [&](const float (&acc)[64], int hp0) {
#pragma unroll
          for (int n = 0; n < 4; n++) {
            uint32_t x[8];
#pragma unroll
            for (int c = 0; c < 8; c++) {
              x[c] = pack_bf16(acc[32 * (n >> 1) + 4 * c + 2 * (n & 1)], acc[32 * (n >> 1) + 4 * c + 2 * (n & 1) + 1]);
              if (wg) x[c] = movm(x[c]);
            }
            uint4* dst = g_halo + (((n & 1) * 4 + (warp & 3) + 1) * 16 + blockIdx.x * 4 + hp0 + (n >> 1)) * 192 + wg * 96 + lane;
            st_b128(dst, x[0], x[1], x[2], epoch);
            st_b128(dst + 32, x[3], x[4], x[5], epoch);
            st_b128(dst + 64, x[6], x[7], 0, epoch);
          }
        };
        put(acc0, 0);
        put(acc1, 2);
      }
      PROF(36);
      cluster_sync_all();
      return;
    }

    float acc[64];
    const uint32_t g2rel = wtid ? mapa(bars, rank) + 8 * BAR_EMPTY2B : mapa(bars, wg) + 8 * BAR_EMPTY2;
    uint32_t g2a = (uint32_t)mkdesc(sb + wg * 8192, 16, 0, 0), g2b = (uint32_t)mkdesc(sb, 8192, 0, 0);
    auto g2_block = [&](bool first, int s, int ph) {
      mbar_wait(bars + 8 * (BAR_FULL2 + s), ph);
      const uint32_t da = g2a + (g2_a(s, hsel) >> 4), db = g2b + (g2_b(s, rank) >> 4), dc = db + (g2_bk(s) >> 4);
      wg_fence();
      if (first) wgmma_n128z(acc, da, db);
      else wgmma_n128a(acc, da, db);
      wgmma_n128a(acc, da + 2, db + 128);
      wgmma_n128a(acc, da + 4, dc);
      wgmma_n128a(acc, da + 6, dc + 128);
      wg_commit();
    };
    if (MODE != 2) {
    uint32_t a1[2][4], sc[2];
    C2 t[2];
    {
      float acc0[96], acc1[96];
      int sa = 0, pha = 0;
      uint64_t db0 = mkdesc(sb + OFF_1B, 4096, 1024, 1);
      const uint64_t da0 = mkdesc(sb + wg * 16384, 16, 2048, 1);
      const bool sigb = wtid == 64;
      uint32_t rela = 0;
#pragma unroll 1
      for (int r = 0; r < 3; r++) {
#pragma unroll
        for (int i = 0; i < 2 * NS1B; i++) {
          const uint64_t da = da0 + sa * (STG1A >> 4) + (i & 1) * 4, db = db0 + (i % NS1B) * (STG1B >> 4);
          if (i || r) {
            if (!(i & 1)) mbar_wait(bars + 8 * (BAR_FULLA + sa), pha);
            mbar_wait(bars + 8 * (BAR_FULLB + i % NS1B), i / NS1B);
          } else {
            asm volatile("cp.async.wait_group 0;\n" ::: "memory");
            fence_async_smem();
            nb_sync(NB_FIRST, 256);
            PROF(0 + wg);
          }
          wg_fence();
          wgmma_n192(acc0, da + 64, db, i ? 1 : r);
          wgmma_n192(acc1, da, db, i ? 1 : r);
          wgmma_n192(acc0, da + 66, db + 128, 1);
          wgmma_n192(acc1, da + 2, db + 128, 1);
          wg_commit();
          wg_wait<1>();
          if (i || r) {
            if (sigb) mbar_arrive(bars + 8 * (BAR_EMPTYB + (i + NS1B - 1) % NS1B));
            if (!(i & 1) && signaller) mbar_arrive_cluster(rela);
          } else {
            asm volatile("barrier.cluster.wait.aligned;\n" ::: "memory");
          }
          if (i & 1) {
            rela = rbars + 8 * (BAR_EMPTYA + sa);
            if (++sa == NS1A) { sa = 0; pha ^= 1; }
          }
        }
        db0 += p.zero;
      }
      const int lr = lane & 7, lm = lane >> 3;
      const bool le0 = 2 * (lane & 3) <= (lane >> 2), le1 = 2 * (lane & 3) + 1 <= (lane >> 2);
      const uint32_t maskLE = (le0 ? 0x0000FFFFu : 0u) | (le1 ? 0xFFFF0000u : 0u);
      uint32_t q[4][8], k[5][8], vt[5][8];
      {
        static_assert(15 % NS1A == 0 && 30 % NS1B == 0, "slots of the last k blocks");
        asm volatile("ld.volatile.global.v4.u32 {%0,%1,%2,%3}, [%4];\n"
                     : "=r"(t[0].r), "=r"(t[1].r), "=r"(t[0].i), "=r"(t[1].i) : "l"(g_tab + 1536 + wtid * 4) : "memory");
        mbar_wait(bars + 8 * BAR_FULLA, 1);
        mbar_wait(bars + 8 * BAR_FULLB, 0);
        mbar_wait(bars + 8 * (BAR_FULLB + 1), 0);
        mbar_wait(bars + 8 * (BAR_EMPTYA + 1), 0);
        mbar_wait(bars + 8 * BAR_H, 0);
        const uint64_t da = mkdesc(sb + wg * 16384, 16, 2048, 1);
        const uint64_t db = mkdesc(sb + OFF_1B, 4096, 1024, 1);
        wg_fence();
#pragma unroll
        for (int i = 0; i < 4; i++) wgmma_n192(acc0, da + 64 + 2 * i, db + (i >> 1) * (STG1B >> 4) + (i & 1) * 128, 1);
        wg_commit();
#pragma unroll
        for (int i = 0; i < 2; i++) wgmma_n192(acc1, da + 2 * i, db + (i >> 1) * (STG1B >> 4) + (i & 1) * 128, 1);
        wg_commit();
        wg_wait<1>();
        fence_regs(acc0);
        PROFA(45, 0);
        attn_pack<8, 1, false>(acc0, k[4]);
        attn_pack<16, 1, true>(acc0, vt[4]);
        const uint32_t kh = sb + (warp == 7 ? OFF_OP + 7 * 4096 : OFF_KH + (warp + 1) * 2048) + lane * 16;
        sts128(kh, k[4][0], k[4][1], k[4][2], k[4][3]);
        sts128(kh + 512, k[4][4], k[4][5], k[4][6], k[4][7]);
#pragma unroll
        for (int i = 0; i < 4; i++) sts64(kh - lane * 8 + 1024 + 256 * i, vt[4][2 * i], vt[4][2 * i + 1]);
        __syncwarp();
        if (lane == 0) mbar_arrive(bars + 8 * (BAR_KH + 1 + warp));
#pragma unroll
        for (int i = 2; i < 4; i++) wgmma_n192(acc1, da + 2 * i, db + (i >> 1) * (STG1B >> 4) + (i & 1) * 128, 1);
        wg_commit();
        attn_pack<0, 0, false>(acc0, q[1]);
        attn_pack<0, 1, false>(acc0, q[3]);
        attn_pack<8, 0, false>(acc0, k[2]);
        attn_pack<16, 0, true>(acc0, vt[2]);
        uint32_t z = p.zero;
#pragma unroll
        for (int i = 0; i < 8; i++) z &= q[1][i] & q[3][i];
#pragma unroll
        for (int i = 0; i < 8; i += 2) z &= k[2][i] & k[2][i + 1];
        if (lane == 0) mbar_arrive(bars + 8 * BAR_STG + z);
        wg_wait<0>();
        fence_regs(acc1);
        if (MODE == 0) nb_arrive(NB_G1END, 288);
      }
      PROF(2 + wg);
      mbar_wait(bars + 8 * (BAR_KH + warp), 0);
      {
        const uint32_t kh = sb + OFF_KH + warp * 2048 + lane * 16;
#pragma unroll
        for (int i = 0; i < 2; i++) {
          const uint4 t = lds128(kh + 512 * i);
          k[0][4 * i] = t.x; k[0][4 * i + 1] = t.y; k[0][4 * i + 2] = t.z; k[0][4 * i + 3] = t.w;
        }
#pragma unroll
        for (int i = 0; i < 4; i++) {
          const uint2 t = lds64(kh - lane * 8 + 1024 + 256 * i);
          vt[0][2 * i] = t.x; vt[0][2 * i + 1] = t.y;
        }
      }
      attn_pack<0, 0, false>(acc1, q[0]);
      attn_pack<0, 1, false>(acc1, q[2]);
      attn_pack<8, 0, false>(acc1, k[1]);
      attn_pack<8, 1, false>(acc1, k[3]);
      {
        float x[8][2];
        uint32_t pp[8];
        const bool first = warp == 0 && gidx == 0;
#pragma unroll
        for (int hd = 0; hd < 2; hd++) {
#pragma unroll
          for (int j = 0; j < 4; j += 2) {
            float s0[4], s1[4], s2[4];
            attn_qk(s2, q[j], q[j + 1], k[j + 2], 4 * hd);
            attn_qk(s1, q[j], q[j + 1], k[j + 1], 4 * hd);
            attn_qk(s0, q[j], q[j + 1], k[j], 4 * hd);
            if (j == 0 && first) s0[0] = s0[1] = -1e9f / 0.17677669529663687f;
            x[2 * j + hd][0] = le0 ? s1[0] : s0[0];
            x[2 * j + hd][1] = le1 ? s1[1] : s0[1];
            x[2 * j + 2 + hd][0] = le0 ? s2[2] : s1[2];
            x[2 * j + 2 + hd][1] = le1 ? s2[3] : s1[3];
          }
        }
        PROFA(40, __float_as_uint(x[1][0] + x[7][1]));
        attn_pack<16, 0, true>(acc1, vt[1]);
        attn_pack<16, 1, true>(acc1, vt[3]);
        quad_softmax<8>(x, pp);
        PROFA(41, pp[1] + pp[7]);
        ldsm4(a1[0], sb + OFF_T32 + (warp & 3) * 1024 + lane * 16);
        ldsm4(a1[1], sb + OFF_T32 + 512 + (warp & 3) * 1024 + lane * 16);
        const uint32_t obase = sb + OFF_OP + (warp * 32 + lr) * 128;
#pragma unroll
        for (int n = 0; n < 8; n++) {
          const uint32_t dst = obase + (n >> 1) * 1024 + (((4 * (n & 1) + lm) ^ lr) << 4);
          if (n & 2) attn_pv<true>(dst, vt[n >> 1], vt[(n >> 1) + 1], 4 * (n & 1), pp[n], maskLE);
          else attn_pv<false>(dst, vt[n >> 1], vt[(n >> 1) + 1], 4 * (n & 1), pp[n], maskLE);
        }
      }
      PROFA(42, 0);
    }

    {
      const int w = warp & 3;
      const int lr = lane & 7, lm = lane >> 3;
      const uint32_t xb = sb + OFF_X + wg * 4 * XT;
      auto uo = [](int c) { return (c & 1) * 2 * XT + (c >> 1) * 2048; };
      const uint64_t dc2 = mkdesc(sb + OFF_T16, 512, 128, 0), dc3 = mkdesc(sb + OFF_T16, 128, 512, 0);
      const uint64_t dc4 = mkdesc(sb + OFF_T32, 128, 256, 0);
      const uint64_t dx = mkdesc(xb, 4096, 512, 2), dz = mkdesc(xb, 4096, 256, 3);
      const uint32_t zs = xb + (w * 16 + (lm & 1) * 8 + lr) * 32 + (((lm >> 1) ^ (lr >> 2)) << 4);
      const uint32_t ys = xb + w * 4096 + (lm >> 1) * 256 + ((lr * 32 + (((lm & 1) ^ (lr >> 2)) << 4)) ^ (rank << 6) ^ ((w & 2) << 4));
      const bool own = (w & 1) == rank;
      const uint32_t ybar = mapa(bars, own ? rank ^ 1 : rank) + 8 * BAR_Y;
      uint32_t d[2][32], pa[2][4][2][4], e[4][4][8], ya[2][2][2][4], v[2][2][8];
      C2 s1[2][2][2];
      float o[2][16];
      auto rows = [&](int c) {
        fft_rows(d[c & 1], a1, dx + (uo(c) >> 4));
        wg_commit();
      };
      auto cols = [&](int c) {
        const int s = c & 1;
        fence_regs(d[s]);
#pragma unroll
        for (int i = 0; i < 16; i++) {
          const C2 z = crot(C2{d[s][2 * i], d[s][2 * i + 1]}, t[i & 1]);
          pa[s][i >> 2][i & 1][(i >> 1) & 1] = z.r;
          pa[s][i >> 2][i & 1][2 + ((i >> 1) & 1)] = z.i;
        }
        wg_fence();
#pragma unroll
        for (int i = 0; i < 4; i++) fft_cols<0>(e[c][i], pa[s][i], dc2);
        wg_commit();
      };
      auto prod = [&](int c, int n) {
        const int s = c & 1;
        fence_regs(e[c][2 * n]);
        fence_regs(e[c][2 * n + 1]);
#pragma unroll
        for (int j = 0; j < 2; j++) {
          const C2 u0 = cget(e[s][2 * n], j, 0), u1 = cget(e[s][2 * n], j, 1);
          const C2 h0 = cget(e[s][2 * n + 1], j, 0), h1 = cget(e[s][2 * n + 1], j, 1);
          C2 y0, y1;
          if (c < 2) {
            y0 = cmul(h0, u0);
            s1[s][n][j] = cfma(h0, u1, cmul(h1, u0));
            y1 = C2{hadd2(s1[s][n][j].r, y0.i), hadd2(s1[s][n][j].i, hneg2(y0.r))};
          } else {
            const C2 u2 = cget(e[c][2 * n], j, 0), u3 = cget(e[c][2 * n], j, 1);
            const C2 h2 = cget(e[c][2 * n + 1], j, 0), h3 = cget(e[c][2 * n + 1], j, 1);
            const C2 s2 = cfma(h0, u2, cfma(h2, u0, cmul(h1, u1)));
            y0 = C2{hadd2(s2.r, s1[s][n][j].i), hadd2(s2.i, hneg2(s1[s][n][j].r))};
            y1 = cfma(h0, u3, cfma(h1, u2, cfma(h2, u1, cfma(h3, u0, C2{s2.i, hneg2(s2.r)}))));
          }
          ya[s][n][j][0] = y0.r;
          ya[s][n][j][1] = y1.r;
          ya[s][n][j][2] = y0.i;
          ya[s][n][j][3] = y1.i;
        }
      };
      auto icols = [&](int c) {
        wg_fence();
        fft_cols<1>(v[c & 1][0], ya[c & 1][0], dc3);
        fft_cols<1>(v[c & 1][1], ya[c & 1][1], dc3);
        wg_commit();
      };
      auto stage = [&](int c) {
        const int s = c & 1;
        fence_regs(v[s][0]);
        fence_regs(v[s][1]);
#pragma unroll
        for (int b = 0; b < 4; b++) {
          const C2 x0 = cget(v[s][b >> 1], 0, b & 1), x1 = cget(v[s][b >> 1], 1, b & 1);
          const C2 z0 = crot(C2{x0.i, x0.r}, t[0]), z1 = crot(C2{x1.i, x1.r}, t[1]);
          stsm4(zs + uo(c) + b * 4096, z0.i, z0.r, z1.i, z1.r);
        }
      };
      auto back = [&](int c) {
        fft_back(o[c & 1], dz + (uo(c) >> 4), dc4);
        wg_commit();
      };
      auto out = [&](int c) {
        float (&r)[16] = o[c & 1];
        fence_regs(r);
#pragma unroll
        for (int i = 0; i < 16; i += 8)
          stsm4t(ys + uo(c) + 64 * i, bmul2(pack_bf16(r[i], r[i + 1]), sc[c & 1]), bmul2(pack_bf16(r[i + 2], r[i + 3]), sc[c & 1]),
                 bmul2(pack_bf16(r[i + 4], r[i + 5]), sc[c & 1]), bmul2(pack_bf16(r[i + 6], r[i + 7]), sc[c & 1]));
      };
      auto signal = [&](int yb, int land) {
        __syncwarp();
        if (lane == 0) {
          mbar_arrive_cluster(ybar + 8 * yb);
          if (own && land >= 0) mbar_arrive(bars + 8 * (BAR_LAND + land));
        }
      };
      mbar_wait(bars + 8 * BAR_X, 0);
      wg_fence();
      rows(0);
      rows(1);
      fence_async_smem();
      nb_arrive(NB_OREADY, 288);
#pragma unroll
      for (int i = 0; i < 2; i++) {
        const uint32_t ex = sb + OFF_EX + wg * 16 + (w & 2) * 2 + 8 * i;
        sc[i] = min(max(381 - (int)lds32(ex) - (int)lds32(ex + 32), 1), 254) * 0x00800080u;
      }
      PROF(34 + wg);
      wg_wait<1>();
      cols(0);
      wg_wait<1>();
      cols(1);
      rows(2);
      nb_sync(NB_CONV + wg, 128);
      wg_wait<2>();
      prod(0, 0);
      prod(0, 1);
      icols(0);
      wg_wait<2>();
      prod(1, 0);
      prod(1, 1);
      icols(1);
      PROF3(40 + 10 * wg);
      wg_wait<1>();
      stage(0);
      wg_wait<0>();
      stage(1);
      fence_async_smem();
      cols(2);
      PROF3(41 + 10 * wg);
      nb_sync(NB_CONV + wg, 128);
      back(0);
      back(1);
      wg_wait<2>();
      prod(2, 0);
      wg_fence();
      rows(3);
      wg_wait<1>();
      out(0);
      out(1);
      signal(wg, 0);
      PROF3(42 + 10 * wg);
      prod(2, 1);
      icols(2);
      wg_wait<1>();
      cols(3);
      PROF3(43 + 10 * wg);
      wg_wait<1>();
      stage(2);
      fence_async_smem();
      wg_wait<0>();
      prod(3, 0);
      nb_sync(NB_CONV + wg, 128);
      wg_fence();
      back(2);
      prod(3, 1);
      icols(3);
      PROF3(44 + 10 * wg);
      wg_wait<1>();
      out(2);
      signal(2, -1);
      wg_wait<0>();
      stage(3);
      PROF3(45 + 10 * wg);
      fence_async_smem();
      nb_sync(NB_FIRST, 256);
      wg_fence();
      back(3);
      constexpr int G = MODE == 0;
      if (G) {
        mbar_wait(bars + 8 * (BAR_EMPTY2 + 4), 0);
        g2_block(true, 0, 0);
      }
      wg_wait<G>();
      if (lane == 0) mbar_arrive_cluster(mapa(bars, 1) + 8 * BAR_TAB);
      out(3);
      signal(3, 1);
      PROF(6 + wg);
    }
    }

    if (MODE != 1) {
      if (MODE == 2) g2_block(true, 0, 0);
      const int lr = lane & 7, lm = lane >> 3;
      const uint32_t wb = sb + g2_a(1, 0) + warp * 2048;
      const int orow = (rb2 & 7) * 128 + warp * 16;
      uint4* og = reinterpret_cast<uint4*>(p.out + (size_t)(2 * (orow + lm) + (rb2 >> 3)) * (2 * DM) + DM + cb2 * 128 + lr * 8);
      uint32_t wst = wb + (lr + 8 * (lm & 1)) * 128, wsx = ((lm >> 1) ^ lr) << 4, wld = wb + lm * 128, wlx = (lr ^ lm) << 4;
      asm volatile("" : "+l"(og), "+r"(wst), "+r"(wsx), "+r"(wld), "+r"(wlx));
#pragma unroll 1
      for (int r = 0; r < 3; r++) {
        const bool hold = r == 2 && wg != LEADWG;
        if (hold) {
          wg_wait<0>();
          if (signaller) mbar_arrive_cluster(g2rel);
          nb_sync(NB_LEAD, 256);
        }
#pragma unroll
        for (int i = 1; i <= NS2; i++) {
          g2_block(false, i % NS2, (r & 1) ^ (i == NS2));
          if (warp == LEADWG * 4) PROF2(40 + 5 * r + i);
          if (i == 1 ? !hold : r < 2) {
            wg_wait<1>();
            if (signaller) mbar_arrive_cluster(g2rel + 8 * (i - 1));
          }
        }
        if (r == 0) PROF(8 + wg);
        g2a += p.zero;
        g2b += p.zero;
      }
      if (wg == LEADWG) nb_arrive(NB_LEAD, 256);
      asm volatile("barrier.cluster.arrive.relaxed.aligned;\n" ::: "memory");
      wg_wait<0>();
      fence_regs(acc);
      PROF(10 + wg);
#pragma unroll
      for (int h = 0; h < 2; h++) {
        const uint32_t b = h * (g2_a(3, 0) - g2_a(1, 0));
#pragma unroll
        for (int j = 8 * h; j < 8 * h + 8; j += 2)
          stsm4(wst + b + (wsx ^ ((j & 7) << 4)), pack_bf16(acc[4 * j], acc[4 * j + 1]),
                pack_bf16(acc[4 * j + 2], acc[4 * j + 3]), pack_bf16(acc[4 * j + 4], acc[4 * j + 5]),
                pack_bf16(acc[4 * j + 6], acc[4 * j + 7]));
        if (wg == LEADWG) {
          fence_async_smem();
          __syncwarp();
          if (elect_one()) {
            tma_store_3d(&tmOb, wb + b, DM + cb2 * 128 + h * 64, rb2 >> 3, orow);
            bulk_commit();
          }
        } else {
          __syncwarp();
          uint4 v[4];
#pragma unroll
          for (int i = 0; i < 4; i++) v[i] = lds128(wld + b + i * 512 + (wlx ^ ((i & 1) << 6)));
#pragma unroll
          for (int i = 0; i < 4; i++)
            asm volatile("st.global.v4.u32 [%0], {%1,%2,%3,%4};\n" ::"l"(og + i * 8 * (2 * DM / 8) + h * 8), "r"(v[i].x),
                         "r"(v[i].y), "r"(v[i].z), "r"(v[i].w) : "memory");
        }
      }
      PROF(12 + wg);
      bulk_wait0();
    } else {
      asm volatile("barrier.cluster.arrive.relaxed.aligned;\n" ::: "memory");
    }
    asm volatile("barrier.cluster.wait.aligned;\n" ::: "memory");
  }
}

typedef CUresult (*EncodeFn)(CUtensorMap*, CUtensorMapDataType, cuuint32_t, void*, const cuuint64_t*, const cuuint64_t*,
                             const cuuint32_t*, const cuuint32_t*, CUtensorMapInterleave, CUtensorMapSwizzle,
                             CUtensorMapL2promotion, CUtensorMapFloatOOBfill);

void make_map(EncodeFn enc, CUtensorMap* tm, const void* base, int rank, const cuuint64_t* dims, const cuuint64_t* strides,
              const cuuint32_t* box, CUtensorMapSwizzle swz) {
  cuuint32_t es[5] = {1, 1, 1, 1, 1};
  enc(tm, CU_TENSOR_MAP_DATA_TYPE_BFLOAT16, rank, const_cast<void*>(base), dims, strides, box, es,
      CU_TENSOR_MAP_INTERLEAVE_NONE, swz, CU_TENSOR_MAP_L2_PROMOTION_L2_256B, CU_TENSOR_MAP_FLOAT_OOB_FILL_NONE);
}

}

extern "C" void kernel_launch(void* const* d_in, const int* in_sizes, int n_in, void* d_out, int out_size) {
  static EncodeFn enc = nullptr;
  static bool coresident = true;
  if (!enc) {
    void* fn = nullptr;
    cudaDriverEntryPointQueryResult qr;
    cudaGetDriverEntryPoint("cuTensorMapEncodeTiled", &fn, cudaEnableDefault, &qr);
    enc = (EncodeFn)fn;
    cudaFuncSetAttribute(fused_kernel<0>, cudaFuncAttributeMaxDynamicSharedMemorySize, SMEM_BYTES);
    cudaFuncSetAttribute(fused_kernel<1>, cudaFuncAttributeMaxDynamicSharedMemorySize, SMEM_BYTES);
    cudaFuncSetAttribute(fused_kernel<2>, cudaFuncAttributeMaxDynamicSharedMemorySize, SMEM_BYTES);
    cudaLaunchConfig_t cfg = {};
    cfg.gridDim = dim3(NCTA);
    cfg.blockDim = dim3(NTHREADS);
    cfg.dynamicSmemBytes = SMEM_BYTES;
    cudaLaunchAttribute at;
    at.id = cudaLaunchAttributeClusterDimension;
    at.val.clusterDim.x = 2;
    at.val.clusterDim.y = 1;
    at.val.clusterDim.z = 1;
    cfg.attrs = &at;
    cfg.numAttrs = 1;
    int nclusters = 0;
    if (cudaOccupancyMaxActiveClusters(&nclusters, fused_kernel<0>, &cfg) == cudaSuccess) coresident = nclusters >= NCTA / 2;
    (void)cudaGetLastError();
  }
  CUtensorMap tmX, tmW, tmWo, tmWp, tmQ, tmOb, tmXh, tmWh;
  {
    cuuint64_t dims[3] = {1024, 2, 1024};
    cuuint64_t str[2] = {2048, 4096};
    cuuint32_t box[3] = {64, 1, 128};
    make_map(enc, &tmX, d_in[6], 3, dims, str, box, CU_TENSOR_MAP_SWIZZLE_128B);
  }
  {
    cuuint64_t dims[3] = {1024, 1024, 3};
    cuuint64_t str[2] = {6144, 2048};
    cuuint32_t box[3] = {64, 32, 3};
    make_map(enc, &tmW, d_in[7], 3, dims, str, box, CU_TENSOR_MAP_SWIZZLE_128B);
  }
  {
    cuuint64_t dims[3] = {64, 1024, 16};
    cuuint64_t str[2] = {2048, 128};
    cuuint32_t box[3] = {64, 64, 2};
    cuuint32_t piece[3] = {64, 32, 1};
    make_map(enc, &tmWo, d_in[8], 3, dims, str, box, CU_TENSOR_MAP_SWIZZLE_128B);
    make_map(enc, &tmWp, d_in[8], 3, dims, str, piece, CU_TENSOR_MAP_SWIZZLE_128B);
  }
  {
    cuuint64_t dims[5] = {1024, 2, 2, 4, 128};
    cuuint64_t str[4] = {2048, 8 * 2048, 2 * 2048, 16 * 2048};
    cuuint32_t box[5] = {16, 2, 2, 4, 32};
    make_map(enc, &tmQ, d_in[0], 5, dims, str, box, CU_TENSOR_MAP_SWIZZLE_NONE);
  }
  {
    cuuint64_t dims[3] = {2048, 2, 1024};
    cuuint64_t str[2] = {4096, 8192};
    cuuint32_t box[3] = {64, 1, 16};
    make_map(enc, &tmOb, d_out, 3, dims, str, box, CU_TENSOR_MAP_SWIZZLE_128B);
  }
  {
    cuuint64_t dims[4] = {1024, 256, 2, 4};
    cuuint64_t str[3] = {4096, 2048, 256 * 4096};
    cuuint32_t box[4] = {64, 8, 2, 3};
    make_map(enc, &tmXh, d_in[6], 4, dims, str, box, CU_TENSOR_MAP_SWIZZLE_128B);
  }
  {
    cuuint64_t dims[3] = {64, 1024, 48};
    cuuint64_t str[2] = {6144, 128};
    cuuint32_t box[3] = {64, 64, 4};
    make_map(enc, &tmWh, d_in[7], 3, dims, str, box, CU_TENSOR_MAP_SWIZZLE_128B);
  }
  Params p;
  p.q = (const __nv_bfloat16*)d_in[0];
  p.k = (const __nv_bfloat16*)d_in[1];
  p.v = (const __nv_bfloat16*)d_in[2];
  p.shift_k = (const __nv_bfloat16*)d_in[3];
  p.ssm_k = (const __nv_bfloat16*)d_in[4];
  p.ssm_D = (const __nv_bfloat16*)d_in[5];
  p.x = (const __nv_bfloat16*)d_in[6];
  p.w = (const __nv_bfloat16*)d_in[7];
  p.wo = (const __nv_bfloat16*)d_in[8];
  p.out = (__nv_bfloat16*)d_out;
  p.zero = 0;
  for (int cl = 0; cl < 72; cl++) {
    const int t = cl - 4, u = t - 32;
    const bool lo = t >= 0 && t < 32, mid = u >= 0 && u < 28;
    const int grp = lo ? t & 7 : mid ? 1 + u % 7 : 0, mem = lo ? t >> 3 : mid ? 4 + u / 7 : t < 0 ? t + 6 : t - 54;
    p.tile[cl] = (uint8_t)((((grp >> 2) * 4 + (mem >> 1)) * 8 + (grp & 3) * 2 + (mem & 1)) & 63);
  }
  if (coresident) {
    fused_kernel<0><<<NCTA, NTHREADS, SMEM_BYTES>>>(p, tmX, tmW, tmWo, tmWp, tmQ, tmOb, tmXh, tmWh);
  } else {
    fused_kernel<0><<<4, NTHREADS, SMEM_BYTES>>>(p, tmX, tmW, tmWo, tmWp, tmQ, tmOb, tmXh, tmWh);
    fused_kernel<1><<<NCTA, NTHREADS, SMEM_BYTES>>>(p, tmX, tmW, tmWo, tmWp, tmQ, tmOb, tmXh, tmWh);
    fused_kernel<2><<<NCTA, NTHREADS, SMEM_BYTES>>>(p, tmX, tmW, tmWo, tmWp, tmQ, tmOb, tmXh, tmWh);
  }
}
```

```cpp
#include <cuda_runtime.h>
#include <cuda.h>
#include <cuda_bf16.h>
#include <stdint.h>

namespace {

constexpr int SEQ = 2048;
constexpr int DM = 1024;
constexpr int NCTA = 132;
constexpr int NTHREADS = 384;

constexpr int STG1A = 32768;
constexpr int NS1A = 3;
constexpr int STG1B = 12288;
constexpr int NS1B = 5;
constexpr int OFF_1B = NS1A * STG1A;
constexpr int STG2 = 32768;
constexpr int NS2 = 5;
#define PSTEP 1250
#define FPACE 260
#define FPACE2 230
#define FPACE3 180
#define LN 4
constexpr int LEADWG = 1;
__device__ __forceinline__ uint32_t g2_a(int s, int hsel) { return (((0x97524 >> (4 * s)) & 15) ^ (s & 5 ? 0 : hsel)) << 14; }
constexpr int OFF_Q0 = 3 << 14, OFF_Q1 = 8 << 14;
constexpr int STGH = 40960;
constexpr int OFF_KH = 1 * STG2;
constexpr int OFF_OP = 2 * STG2;
constexpr int OFF_T32 = 5 * STG2 - 4096;
constexpr int OFF_X = 5 * STG2;
constexpr int XT = 8192;
__device__ __forceinline__ uint32_t g2_b(int s, int rank) {
  return s < 3 ? (s == 2 ? 6 : s) << 14 : OFF_X + (s - 3) * 2 * XT + (rank ^ 1) * 4096;
}
__device__ __forceinline__ uint32_t g2_bk(int s) { return s < 3 ? 4096 : 4 * XT; }
constexpr int OFF_BAR = OFF_X + 8 * XT;
constexpr int OFF_EX = OFF_BAR + 960;
constexpr int OFF_T16 = 230400;
constexpr int SMEM_BYTES = OFF_T16 + 2048;
static_assert(OFF_1B + NS1B * STG1B <= OFF_T32 && OFF_X % 1024 == 0, "layout");
static_assert(NS1B * STGH <= OFF_BAR && OFF_EX + 64 <= OFF_T16 && SMEM_BYTES <= 232448, "smem");

constexpr int BAR_FULLA = 0;
constexpr int BAR_EMPTYA = 3;
constexpr int BAR_FULLB = 6;
constexpr int BAR_EMPTYB = 11;
constexpr int BAR_FULL2 = 16;
constexpr int BAR_EMPTY2 = 21;
constexpr int BAR_EMPTY2B = 44;
constexpr int BAR_X = 26;
constexpr int BAR_LAND = 42;
constexpr int BAR_TAB = 28;
constexpr int BAR_U = 29;
constexpr int BAR_H = 30;
constexpr int BAR_Y = 32;
constexpr int BAR_XFREE = 38;
constexpr int BAR_KH = 49;
constexpr int BAR_Q = 41;

constexpr int NB_LEAD = 2;
constexpr int NB_G1END = 3;
constexpr int NB_OREADY = 4;
constexpr int NB_CONV = 5;
constexpr int NB_HELP3 = 11;
constexpr int NB_FIRST = 13;

#define REG_MATH 224
#define REG_HELP 56
constexpr int SPIN_LIMIT = 1 << 20;

__device__ __align__(1024) __nv_bfloat16 g_o[SEQ * DM];
constexpr int FS = 2;
__device__ __align__(128) uint32_t g_flag_o[128 * FS];
__device__ uint4 g_halo[128 * 192];
__device__ __align__(128) const uint32_t g_tab[2048] = {
  0x2fd93000,0x2ea72f64,0x2c722da8,0x263e2a1f,0x2ea73000,0xa63e2a1f,0xafd9ada8,0xac72af64,0x2c723000,0xafd9aa1f,0x263eada8,0x2ea72f64,
  0x263e3000,0xac72af64,0x2ea72da8,0xafd9aa1f,0xa63e3000,0x2c72af64,0xaea72da8,0x2fd9aa1f,0xac723000,0x2fd9aa1f,0xa63eada8,0xaea72f64,
  0xaea73000,0x263e2a1f,0x2fd9ada8,0x2c72af64,0xafd93000,0xaea72f64,0xac722da8,0xa63e2a1f,0x263e0000,0x2c722a1f,0x2ea72da8,0x2fd92f64,
  0x2c720000,0x2fd92f64,0x263e2da8,0xaea7aa1f,0x2ea70000,0x263e2f64,0xafd9ada8,0x2c72aa1f,0x2fd90000,0xaea72a1f,0x2c72ada8,0xa63e2f64,
  0x2fd90000,0xaea7aa1f,0x2c722da8,0xa63eaf64,0x2ea70000,0x263eaf64,0xafd92da8,0x2c722a1f,0x2c720000,0x2fd9af64,0x263eada8,0xaea72a1f,
  0x263e0000,0x2c72aa1f,0x2ea7ada8,0x2fd9af64,0xafd93000,0xaea72f64,0xac722da8,0xa63e2a1f,0xaea73000,0x263e2a1f,0x2fd9ada8,0x2c72af64,
  0xac723000,0x2fd9aa1f,0xa63eada8,0xaea72f64,0xa63e3000,0x2c72af64,0xaea72da8,0x2fd9aa1f,0x263e3000,0xac72af64,0x2ea72da8,0xafd9aa1f,
  0x2c723000,0xafd9aa1f,0x263eada8,0x2ea72f64,0x2ea73000,0xa63e2a1f,0xafd9ada8,0xac72af64,0x2fd93000,0x2ea72f64,0x2c722da8,0x263e2a1f,
  0xa63e0000,0xac722a1f,0xaea72da8,0xafd92f64,0xac720000,0xafd92f64,0xa63e2da8,0x2ea7aa1f,0xaea70000,0xa63e2f64,0x2fd9ada8,0xac72aa1f,
  0xafd90000,0x2ea72a1f,0xac72ada8,0x263e2f64,0xafd90000,0x2ea7aa1f,0xac722da8,0x263eaf64,0xaea70000,0xa63eaf64,0x2fd92da8,0xac722a1f,
  0xac720000,0xafd9af64,0xa63eada8,0x2ea72a1f,0xa63e0000,0xac72aa1f,0xaea7ada8,0xafd9af64,0xa63e0000,0xac72aa1f,0xaea7ada8,0xafd9af64,
  0xac720000,0xafd9af64,0xa63eada8,0x2ea72a1f,0xaea70000,0xa63eaf64,0x2fd92da8,0xac722a1f,0xafd90000,0x2ea7aa1f,0xac722da8,0x263eaf64,
  0xafd90000,0x2ea72a1f,0xac72ada8,0x263e2f64,0xaea70000,0xa63e2f64,0x2fd9ada8,0xac72aa1f,0xac720000,0xafd92f64,0xa63e2da8,0x2ea7aa1f,
  0xa63e0000,0xac722a1f,0xaea72da8,0xafd92f64,0x2fd93000,0x2ea72f64,0x2c722da8,0x263e2a1f,0x2ea73000,0xa63e2a1f,0xafd9ada8,0xac72af64,
  0x2c723000,0xafd9aa1f,0x263eada8,0x2ea72f64,0x263e3000,0xac72af64,0x2ea72da8,0xafd9aa1f,0xa63e3000,0x2c72af64,0xaea72da8,0x2fd9aa1f,
  0xac723000,0x2fd9aa1f,0xa63eada8,0xaea72f64,0xaea73000,0x263e2a1f,0x2fd9ada8,0x2c72af64,0xafd93000,0xaea72f64,0xac722da8,0xa63e2a1f,
  0x263e0000,0x2c72aa1f,0x2ea7ada8,0x2fd9af64,0x2c720000,0x2fd9af64,0x263eada8,0xaea72a1f,0x2ea70000,0x263eaf64,0xafd92da8,0x2c722a1f,
  0x2fd90000,0xaea7aa1f,0x2c722da8,0xa63eaf64,0x2fd90000,0xaea72a1f,0x2c72ada8,0xa63e2f64,0x2ea70000,0x263e2f64,0xafd9ada8,0x2c72aa1f,
  0x2c720000,0x2fd92f64,0x263e2da8,0xaea7aa1f,0x263e0000,0x2c722a1f,0x2ea72da8,0x2fd92f64,0xafd93000,0xaea72f64,0xac722da8,0xa63e2a1f,
  0xaea73000,0x263e2a1f,0x2fd9ada8,0x2c72af64,0xac723000,0x2fd9aa1f,0xa63eada8,0xaea72f64,0xa63e3000,0x2c72af64,0xaea72da8,0x2fd9aa1f,
  0x263e3000,0xac72af64,0x2ea72da8,0xafd9aa1f,0x2c723000,0xafd9aa1f,0x263eada8,0x2ea72f64,0x2ea73000,0xa63e2a1f,0xafd9ada8,0xac72af64,
  0x2fd93000,0x2ea72f64,0x2c722da8,0x263e2a1f,0xa63e0000,0xac72aa1f,0xaea7ada8,0xafd9af64,0x2c720000,0x2fd92f64,0x263e2da8,0xaea7aa1f,
  0xaea70000,0xa63eaf64,0x2fd92da8,0xac722a1f,0x2fd90000,0xaea72a1f,0x2c72ada8,0xa63e2f64,0xafd90000,0x2ea72a1f,0xac72ada8,0x263e2f64,
  0x2ea70000,0x263eaf64,0xafd92da8,0x2c722a1f,0xac720000,0xafd92f64,0xa63e2da8,0x2ea7aa1f,0x263e0000,0x2c72aa1f,0x2ea7ada8,0x2fd9af64,
  0x2fd93000,0x2ea72f64,0x2c722da8,0x263e2a1f,0xaea7b000,0x263eaa1f,0x2fd92da8,0x2c722f64,0x2c723000,0xafd9aa1f,0x263eada8,0x2ea72f64,
  0xa63eb000,0x2c722f64,0xaea7ada8,0x2fd92a1f,0xa63e3000,0x2c72af64,0xaea72da8,0x2fd9aa1f,0x2c72b000,0xafd92a1f,0x263e2da8,0x2ea7af64,
  0xaea73000,0x263e2a1f,0x2fd9ada8,0x2c72af64,0x2fd9b000,0x2ea7af64,0x2c72ada8,0x263eaa1f,0x263e0000,0x2c72aa1f,0x2ea7ada8,0x2fd9af64,
  0xac720000,0xafd92f64,0xa63e2da8,0x2ea7aa1f,0x2ea70000,0x263eaf64,0xafd92da8,0x2c722a1f,0xafd90000,0x2ea72a1f,0xac72ada8,0x263e2f64,
  0x2fd90000,0xaea72a1f,0x2c72ada8,0xa63e2f64,0xaea70000,0xa63eaf64,0x2fd92da8,0xac722a1f,0x2c720000,0x2fd92f64,0x263e2da8,0xaea7aa1f,
  0xa63e0000,0xac72aa1f,0xaea7ada8,0xafd9af64,0xafd93000,0xaea72f64,0xac722da8,0xa63e2a1f,0x2ea7b000,0xa63eaa1f,0xafd92da8,0xac722f64,
  0xac723000,0x2fd9aa1f,0xa63eada8,0xaea72f64,0x263eb000,0xac722f64,0x2ea7ada8,0xafd92a1f,0x263e3000,0xac72af64,0x2ea72da8,0xafd9aa1f,
  0xac72b000,0x2fd92a1f,0xa63e2da8,0xaea7af64,0x2ea73000,0xa63e2a1f,0xafd9ada8,0xac72af64,0xafd9b000,0xaea7af64,0xac72ada8,0xa63eaa1f,
  0xafd9b000,0xaea7af64,0xac72ada8,0xa63eaa1f,0x2ea73000,0xa63e2a1f,0xafd9ada8,0xac72af64,0xac72b000,0x2fd92a1f,0xa63e2da8,0xaea7af64,
  0x263e3000,0xac72af64,0x2ea72da8,0xafd9aa1f,0x263eb000,0xac722f64,0x2ea7ada8,0xafd92a1f,0xac723000,0x2fd9aa1f,0xa63eada8,0xaea72f64,
  0x2ea7b000,0xa63eaa1f,0xafd92da8,0xac722f64,0xafd93000,0xaea72f64,0xac722da8,0xa63e2a1f,0xa63e0000,0xac72aa1f,0xaea7ada8,0xafd9af64,
  0x2c720000,0x2fd92f64,0x263e2da8,0xaea7aa1f,0xaea70000,0xa63eaf64,0x2fd92da8,0xac722a1f,0x2fd90000,0xaea72a1f,0x2c72ada8,0xa63e2f64,
  0xafd90000,0x2ea72a1f,0xac72ada8,0x263e2f64,0x2ea70000,0x263eaf64,0xafd92da8,0x2c722a1f,0xac720000,0xafd92f64,0xa63e2da8,0x2ea7aa1f,
  0x263e0000,0x2c72aa1f,0x2ea7ada8,0x2fd9af64,0x2fd9b000,0x2ea7af64,0x2c72ada8,0x263eaa1f,0xaea73000,0x263e2a1f,0x2fd9ada8,0x2c72af64,
  0x2c72b000,0xafd92a1f,0x263e2da8,0x2ea7af64,0xa63e3000,0x2c72af64,0xaea72da8,0x2fd9aa1f,0xa63eb000,0x2c722f64,0xaea7ada8,0x2fd92a1f,
  0x2c723000,0xafd9aa1f,0x263eada8,0x2ea72f64,0xaea7b000,0x263eaa1f,0x2fd92da8,0x2c722f64,0x2fd93000,0x2ea72f64,0x2c722da8,0x263e2a1f,
  0x263e0000,0x2c72aa1f,0x2ea7ada8,0x2fd9af64,0xac720000,0xafd92f64,0xa63e2da8,0x2ea7aa1f,0x2ea70000,0x263eaf64,0xafd92da8,0x2c722a1f,
  0xafd90000,0x2ea72a1f,0xac72ada8,0x263e2f64,0x2fd90000,0xaea72a1f,0x2c72ada8,0xa63e2f64,0xaea70000,0xa63eaf64,0x2fd92da8,0xac722a1f,
  0x2c720000,0x2fd92f64,0x263e2da8,0xaea7aa1f,0xa63e0000,0xac72aa1f,0xaea7ada8,0xafd9af64,0x316c2fbd,0x343e32f7,0x35bc34ff,0x372c3676,
  0x371532c6,0x3a81392e,0x3bef3b71,0x3b7c3bf2,0x397034cf,0x3bfc3b6c,0x38b23b04,0xb40e31e8,0x3ae13631,0x39e73bf5,0xb6e83219,0xbbe8bb13,
  0x3bc23785,0x30be3aa9,0xbbfdb911,0x2a16b9aa,0x3bfe3865,0xb80f37a6,0xb82abc00,0x3bfd376f,0x3b9238fd,0xbb7f2311,0x3805b929,0x31223bde,
  0x3a85398b,0xbb96b742,0x3bff319e,0xbbb82f8b,0xbbe2bbf1,0xbbb7bbcf,0xbb78bb9a,0xbb27bb52,0xbb2cbbd2,0xb8a8ba19,0xb029b5df,0x35a52f59,
  0xb9dfbba1,0x2ba7b5f7,0x3a7a37b2,0x3bbd3bdd,0xb815bb60,0x39662e91,0x3b373bda,0xb0d7377a,0xb3d3bb10,0x3be9386f,0x2a7a3a31,0xbbfeb9a6,
  0x294dbab0,0x3ae53b07,0xbad51fdb,0xab43bb16,0x352fba41,0x35993c00,0xbaebba1d,0x3be531cf,0x38a3b9c5,0xb5173b21,0x2776bbe0,0x34323bf2,
  0x384537dd,0x38ea3899,0x39823937,0x3a0d39c9,0x39463a93,0x3340374e,0xb426a452,0xb979b7c8,0xbb45b924,0xbb32bc00,0xb371b902,0x38d63294,
  0xb08db9a1,0x3b3f379b,0x39583bd7,0xb8252dfb,0x3bea3a2d,0xb3ba3874,0xbb89bb0d,0x36d2b625,0xb6bb387f,0xb8d1bbf5,0x3be73602,0xb546391f,
  0xba00bb01,0x3bff35eb,0xba5c34db,0x3359bab6,0x3ac7b66b,0xb9413933,0x368dbabd,0xb0103bb3,0xbac4baf7,0xba50ba8c,0xb9cdba11,0xb93cb986,
  0x3a04388e,0x3bcb3b1e,0x3bba3c00,0x39d63afe,0x36af3a21,0xb6ffa17f,0xbbc8ba3d,0xba60bbd4,0xbbebb9af,0xb6c6bb0a,0x39f43263,0x3ad83bf7,
  0x30a6b916,0x3bc33aa5,0xb55e3790,0xbb3dbb63,0x3b423a9e,0xba642ec3,0xb0f0bb6a,0x3b8e3a25,0xb94a37bd,0x2884bb6f,0x38db3b9f,0xbbc9b85a,
  0xb840bb54,0x3a093a15,0xbb4cb850,0x3bef3457,0x3a893a4d,0x3af43ac1,0x3b4f3b24,0x3b983b76,0xbb94baba,0xbbe4bbf9,0xba58bb57,0xb699b8f8,
  0x3bfe3b18,0x394f3b5c,0xb109347b,0xbae8b884,0xbbc0bb68,0xa9b1b90c,0x3b8b387a,0x38bc3ba5,0x3ade3ba7,0xb8c1324b,0xb9f0bbf6,0x39eb9648,
  0xb96bbbd6,0x3bbf3487,0xb38939b3,0xb9f8bba3,0x370a3bf3,0xbb47b994,0x3bbc2d65,0xb8ad3889,0xb153bc00,0x37213b9c,0xb97dba90,0x3af138f3,
  0xb89eb8ee,0xb7e8b84a,0xb682b737,0xb50bb5c8,0x35233855,0xb13b2d33,0xb8e0b65f,0xbb4aba45,0xa8e8b764,0x39fc3648,0x3be63bae,0x380a3a9b,
  0xb3eb360e,0xbbfeba35,0xb552baa2,0x3a7334b7,0x381ab4ab,0x3a6f3bd8,0xb95d2e5f,0xb962bc00,0xb9e3327c,0xb402bbac,0x3bc6399d,0xb95434c3,
  0x3b2faf27,0xb6a439bc,0xb41abbf9,0x3a7e3a97,0xbbe3251b,0x3b2ab4f3,0xb9d23894,0x37f3ba49,0x3bce3bb5,0x3bf03be1,0x3bff3bfa,0x3bfb3bff,
  0x2c38b1b6,0x383a34e7,0x3aee39c0,0x3bff3bb2,0xbb81bbf8,0xb53ab999,0x38302ef5,0x3bed3ab3,0xb8cc9cb6,0xbb85bbab,0x2adeb86a,0x3bc5391b,
  0x38c73bf6,0xbadbb232,0xb6ddbba9,0x3b87361a,0x3b833201,0xb0743a39,0xba76bb5e,0x3b352dc9,0xac06bbb0,0x39743b59,0xbbeeb759,0x3aceb2ad,
  0xbbccb5d4,0x3bfb2d00,0xbb7a32de,0x3a54b7d2,0xb30fb44b,0xafefb185,0xa6adacce,0x2c9c25e4,0xbbfcbbdf,0xbacbbb9e,0xb7feb990,0xa81fb463,
  0xb58d2d97,0xbb90b9b8,0xbad1bbf4,0xb05bb85f,0x3a673c00,0xb5763493,0xbbfdbaac,0xb3a2ba29,0x3a6b2e2d,0x38203bd9,0xbb3ab49f,0xb56abb65,
  0xb581bbdc,0x3bec3907,0xb8b7363c,0xb6f4bbf8,0xbbfcb46f,0x39dab654,0xb0423b1b,0xb835bbd3,0xb3283b73,0xac6abbfa,0x35b13bd0,0xb8e5bafb,
  0x38ee3a0d,0xb84aba89,0x37373af4,0xb5c8bb4f,0x35df3a81,0x2f59bbef,0xb88e3b7c,0x3b1eb946,0x2d973ae8,0x39b8bb81,0xbbf4353a,0x385f3830,
  0xb2633b3f,0x3bf7b958,0xb60eb825,0xba353bc0,0xb7853b87,0x3aa9b3d3,0x3911bbe9,0xb9aa2a7a,0xb99d3bbf,0x34c33389,0x3bdcb9f8,0x3907bb83,
  0xbb013be5,0xb5eb394a,0x34db2884,0x3ab6b8db,0xbbd03bfb,0xbafb3b7a,0xb98b3a54,0xb74238a3,0x3a4db93c,0xbac1389e,0x3b24b7e8,0xbb763682,
  0x3b71b8a8,0xbbf23029,0x3a9335a5,0xb74eba04,0x3bf8b80a,0xb999b58d,0xaef53b90,0x3ab3bad1,0x3bd7b6c6,0xadfbb9f4,0xbb683ad8,0x390c33eb,
  0x3b10b56a,0x386fbbc2,0xba3130be,0xb9a63bfd,0x39b3b402,0x3ba3bbc6,0x3201b954,0xba393581,0x37bdb122,0x3b6fba00,0x3b9fbbff,0x385aba5c,
  0x32deac6a,0x37d2b5b1,0x39c5b8e5,0x3b21ba85,0x344b3b98,0xb185bbce,0x2cce3bf0,0x25e4bbff,0xbc003340,0x3afe3426,0xb855b979,0x2d333b94,
  0x34cfbbed,0xbb6c39df,0x3b042ba7,0xb1e8ba7a,0x3aa2a9b1,0x34b7bb8b,0xbc0038bc,0x349338cc,0xba2d3bfe,0x387430a6,0x3b0dbbc3,0xb625b55e,
  0xb63cb074,0xbbf83a76,0xb8653b35,0x37a6294d,0x3bf3bbc9,0x3994bb2f,0x2d65b6a4,0xb889341a,0xb19e3517,0x2f8b2776,0x366bb432,0x3933b840,
  0x3bb5b50b,0xbbe1330f,0x3bfaafef,0xbbff26ad,0xa4523bcb,0x37c8bbba,0xbaba39d6,0x3bf9b523,0xbba1305b,0x35f73970,0x37b2bbfc,0xbbdd38b2,
  0x387abbfe,0xbba53552,0x9cb63a73,0x3babba67,0x39162a16,0x3aa5bbea,0xb790b3ba,0xbb633b89,0xbb5e3bec,0xadc938b7,0x3ab0b6f4,0x3b07bbfe,
  0xaf27b359,0xb9bc370a,0xbbf93b47,0xba973bbc,0x3be0bb96,0x3bf2bbff,0x3b54bbb8,0x3a15bac7,0xafbd3bfb,0x32f7bbe2,0xb4ff3bb7,0x3676bb78,
  0x365fbbe4,0xba453a58,0x3bdfb699,0xbb9eac38,0xb9243bbd,0x3c00b6af,0xb902b6ff,0xb2943bc8,0x3aacbb85,0xba29aade,0xb6313bc5,0x3bf5b815,
  0xbba73b3d,0x324b381a,0x3bf6ba6f,0x9648b95d,0x3c00bae5,0x376fbad5,0xb87f2b43,0xbbf53b42,0xbbb03a7e,0xbb593bfc,0xb75939da,0x32ad3042,
  0x3abdba09,0x3bb3bb4c,0x3c00bbef,0x3b9cbbe3,0x3bf12c9c,0xbbcfb16c,0x3b9a343e,0xbb52b5bc,0xbb57b13b,0x38f838e0,0xb1b6bb4a,0xb4e73bfc,
  0x3a21340e,0x217fbb45,0xba3d3b32,0x3bd4b371,0xb86ab576,0xb91b3bfd,0x3b60b3a2,0x2e91bae1,0x34ab36d2,0x3bd8bade,0xae5fb8c1,0xbc0039f0,
  0x9fdbb80f,0xbb16382a,0xba9e3bfd,0x2ec336bb,0xb46f38ad,0x3654ac06,0x3b1bb974,0x3bd3bbee,0x3850b941,0x3457b68d,0xa51bb010,0xb4f33153,
  0xb7dd3b27,0x3899bac4,0xb9373a50,0x39c9b9cd,0x3990383a,0xb463baee,0xb2c63bff,0x392ebb2c,0x3b18ba60,0xbb5c28e8,0x347b39fc,0x3884bbe6,
  0xb219b966,0xbb133b37,0x39a130d7,0x379bbbeb,0xbbf63962,0xb2323a6b,0x3ba9b820,0x361abb3a,0xb6023a64,0x391fb0f0,0x3bd6bb8e,0x3487b9e3,
  0x3a41b835,0x3c00bb92,0x3a1dbb7f,0x31cfb805,0x3a90bb2a,0x38f3b9d2,0x35d4b7f3,0x2d00b328,0x3af7372c,0xba8cb845,0x3a1138ea,0xb986b982,
  0x39c0bacb,0xbbb237fe,0x3bd2a81f,0xba19b715,0xb764b8d6,0xb6483bfe,0x3baeb94f,0xba9bb109,0xbbda39e7,0x377a36e8,0x39afbbe8,0xbb0a308d,
  0xae2d39eb,0x3bd9b8c7,0x349fbadb,0xbb6536dd,0x3b6ab8d1,0x3a25bbe7,0xb27cb546,0xbbac396b,0x38fdbace,0xa311b52f,0xb9293599,0xbbde3aeb,
  0xb8943721,0xba49397d,0xbb733af1,0xbbfa3bcc,0xbbfb3bff,0xbbe23bf1,0xbbb73bcf,0xbb783b9a,0xbb7c3bf2,0xb9463a93,0xb340374e,0x3426a452,
  0xba603bd4,0xa8e83764,0x39fcb648,0x3be6bbae,0xb8bc3ba5,0x38cc9cb6,0x3b85bbab,0xaadeb86a,0xb56a3b65,0x3bc2b785,0x30bebaa9,0xbbfd3911,
  0xab433b16,0x3b42ba9e,0xba64aec3,0xb0f03b6a,0x33593ab6,0x370abbf3,0xbb473994,0x3bbcad65,0x37f33a49,0xb328bb73,0xac6a3bfa,0x35b1bbd0,
  0xac9c25e4,0xb16c2fbd,0xb43e32f7,0xb5bc34ff,0xb5a52f59,0xba04388e,0xbbcb3b1e,0xbbba3c00,0xb8d63294,0xbbfe3b18,0xb94f3b5c,0x3109347b,
  0xba7334b7,0xba673c00,0x35763493,0x3bfdbaac,0xbb87361a,0xb3d33b10,0x3be9b86f,0x2a7aba31,0xbbfd376f,0x36bb387f,0x38d1bbf5,0xbbe73602,
  0xbbc9385a,0x3b2f2f27,0xb6a4b9bc,0xb41a3bf9,0xbaf138f3,0x3bccb5d4,0xbbfb2d00,0x3b7a32de,0xbb273b52,0xbac43af7,0xba503a8c,0xb9cd3a11,
  0x3979b7c8,0x3b94baba,0x3be4bbf9,0x3a58bb57,0x380aba9b,0xb58dad97,0xbb9039b8,0xbad13bf4,0xbbc5391b,0xb8153b60,0x3966ae91,0x3b37bbda,
  0x2a1639aa,0x3beaba2d,0xb3bab874,0xbb893b0d,0x3b8eba25,0xb9e3b27c,0xb4023bac,0x3bc6b99d,0xb8adb889,0xac063bb0,0x3974bb59,0xbbee3759,
  0xb8e53afb,0x3a85b98b,0xbb963742,0x3bffb19e,0xb72c3676,0xb84537dd,0xb8ea3899,0xb9823937,0xb9d63afe,0xb5233855,0x313b2d33,0x38e0b65f,
  0x3ae8b884,0x3b81bbf8,0x353ab999,0xb8302ef5,0x33a2ba29,0xbae13631,0xb9e73bf5,0x36e83219,0xbbfe39a6,0x30a63916,0x3bc3baa5,0xb55eb790,
  0x3546391f,0x396bbbd6,0xbbbf3487,0x338939b3,0x3a7eba97,0xbbfc346f,0x39da3654,0xb042bb1b,0xba54b7d2,0x38a339c5,0xb517bb21,0x27763be0,
  0xb93c3986,0xb89e38ee,0xb7e8384a,0xb6823737,0x3699b8f8,0xac38b1b6,0xb83a34e7,0xbaee39c0,0xb05b385f,0x3970b4cf,0x3bfcbb6c,0x38b2bb04,
  0xb0d7b77a,0xbbeb39af,0xb6c63b0a,0x39f4b263,0x36d23625,0x3adebba7,0xb8c1b24b,0xb9f03bf6,0xb954b4c3,0xb5813bdc,0x3becb907,0xb8b7b63c,
  0x3ace32ad,0xb52fba41,0xb5993c00,0x3aebba1d,0xbbb8af8b,0x3ac7366b,0xb941b933,0x368d3abd,0xba0d39c9,0xba893a4d,0xbaf43ac1,0xbb4f3b24,
  0x3b4aba45,0x3bfcbbdf,0x3acbbb9e,0x37feb990,0xbbed3ab3,0xb9df3ba1,0x2ba735f7,0x3a7ab7b2,0x3be8bb13,0x308db9a1,0xbb3f379b,0xb9583bd7,
  0xbb3d3b63,0x381a34ab,0x3a6fbbd8,0xb95dae5f,0x39f8bba3,0xbb833201,0x30743a39,0x3a76bb5e,0xb8353bd3,0x3b92b8fd,0xbb7fa311,0x38053929,
  0x3432bbf2,0xb8403b54,0x3a09ba15,0xbb4c3850,0xb50b35c8,0xb30f344b,0xafef3185,0xa6ad2cce,0xbbff3bb2,0xbb2c3bd2,0xb8a83a19,0xb02935df,
  0xb40eb1e8,0xbb453924,0xbb323c00,0xb3713902,0x3ad8bbf7,0xb3ebb60e,0xbbfe3a35,0xb5523aa2,0x39eb1648,0x38c7bbf6,0xbadb3232,0xb6dd3ba9,
  0xb6f43bf8,0x3bfeb865,0xb80fb7a6,0xb82a3c00,0xbbe531cf,0x394a37bd,0xa884bb6f,0xb8db3b9f,0xb010bbb3,0xb1533c00,0x3721bb9c,0xb97d3a90,
  0xbb983b76,0xbbce3bb5,0xbbf03be1,0xbbff3bfa,0x281fb463,0xb71532c6,0xba81392e,0xbbef3b71,0x3bbdbbdd,0x36afba21,0xb6ff217f,0xbbc83a3d,
  0x38252dfb,0x3bc0bb68,0x29b1b90c,0xbb8b387a,0xb9623c00,0x3a6bae2d,0x3820bbd9,0xbb3a349f,0xbb352dc9,0x294d3ab0,0x3ae5bb07,0xbad59fdb,
  0x3122bbde,0xba003b01,0x3bffb5eb,0xba5cb4db,0x3befb457,0xbbe3a51b,0x3b2a34f3,0xb9d2b894,0x39c939cd,0xba4db93c,0x3ac1389e,0xbb24b7e8,
  0x3b1e3946,0xbc00b340,0x3afeb426,0xb8553979,0x3bdd38b2,0xba21340e,0xa17fbb45,0x3a3d3b32,0x3bf53815,0xb2193966,0xbb13bb37,0x39a1b0d7,
  0x3b6536dd,0x37853b87,0xbaa9b3d3,0xb911bbe9,0x3a393581,0x3b5e3bec,0x2dc938b7,0xbab0b6f4,0x3889341a,0x3bb03a7e,0x3b593bfc,0x375939da,
  0x34f33153,0x38943721,0x3a49397d,0x3b733af1,0xb9863982,0x38eeba0d,0xb84a3a89,0x3737baf4,0xb74e3a04,0xa452bbcb,0x37c83bba,0xbabab9d6,
  0xb1e83a7a,0xb924bbbd,0x3c0036af,0xb90236ff,0x2e913ae1,0xbbdab9e7,0x377ab6e8,0x39af3be8,0x361a3b3a,0xbb10b56a,0xb86fbbc2,0x3a3130be,
  0x39073b83,0xb63c3074,0xbbf8ba76,0xb865bb35,0x3a973bbc,0x346f38ad,0xb654ac06,0xbb1bb974,0x3b9c3be3,0x3a903b2a,0x38f339d2,0x35d437f3,
  0x3b763682,0xbbb5b50b,0x3be1330f,0xbbfaafef,0x2d33bb94,0x365f3be4,0xba45ba58,0x3bdf3699,0xbbd4b371,0x3764b8d6,0x36483bfe,0xbbaeb94f,
  0x379b3beb,0xbbd7b6c6,0x2dfbb9f4,0x3b683ad8,0x39aa2a7a,0x3a2d3bfe,0xb87430a6,0xbb0dbbc3,0xbb07bbfe,0x1fdbb80f,0x3b16382a,0x3a9e3bfd,
  0xb2ad3042,0xba41b835,0xbc00bb92,0xba1dbb7f,0x3bfa3bcc,0x3bd03bfb,0x3afb3b7a,0x398b3a54,0xb5c83b4f,0x344bbb98,0xb1853bce,0x2ccebbf0,
  0x3bf93523,0xbb57313b,0x38f8b8e0,0xb1b63b4a,0xb294bbc8,0x3b183a60,0xbb5ca8e8,0x347bb9fc,0xbb0ab08d,0xb263bb3f,0x3bf73958,0xb60e3825,
  0x39a63bfd,0xb9162a16,0xbaa5bbea,0x3790b3ba,0x37a6a94d,0x3c003ae5,0x376f3ad5,0xb87fab43,0xbbd3bbee,0xb8fdbace,0x2311b52f,0x39293599,
  0x2d003328,0xb2deac6a,0xb7d2b5b1,0xb9c5b8e5,0x3bff26ad,0xbbf12c9c,0x3bcfb16c,0xbb9a343e,0xbb9e2c38,0x3990b83a,0xb4633aee,0xb2c6bbff,
  0x3a9bb109,0xad973ae8,0xb9b8bb81,0x3bf4353a,0xb90c33eb,0xb87abbfe,0x3ba53552,0x1cb63a73,0x3625b55e,0x3ba73b3d,0xb24b381a,0xbbf6ba6f,
  0xaec336bb,0xbb6ab8d1,0xba25bbe7,0x327cb546,0xb1cfb805,0x37bd3122,0x3b6f3a00,0x3b9f3bff,0x374238a3,0x319e3517,0xaf8b2776,0xb66bb432,
  0x25e43bff,0xafbdbbfb,0x32f73be2,0xb4ffbbb7,0xb4e7bbfc,0x39c03acb,0xbbb2b7fe,0x3bd2281f,0x38843be6,0xbbf8b80a,0x3999b58d,0x2ef53b90,
  0xba35bbc0,0x3aa229b1,0x34b73b8b,0xbc00b8bc,0x3b633b89,0xb4ab36d2,0xbbd8bade,0x2e5fb8c1,0xbbf5bb42,0xb602ba64,0x391f30f0,0x3bd63b8e,
  0x3bde3aeb,0x3b013be5,0x35eb394a,0xb4db2884,0xbb21ba85,0xbbe0bb96,0xbbf2bbff,0xbb54bbb8,0x3b52b5bc,0xbaf7372c,0x3a8cb845,0xba1138ea,
  0x392e3b2c,0xbb71b8a8,0x3bf23029,0xba9335a5,0xb85f3830,0xb4cfbbed,0x3b6c39df,0xbb042ba7,0xbbabba67,0x386ab576,0x391b3bfd,0xbb60b3a2,
  0x1648b95d,0x3bf63962,0x32323a6b,0xbba9b820,0x3bac396b,0x399d3bbf,0xb4c33389,0xbbdcb9f8,0x385a3a5c,0xaf273359,0xb9bcb70a,0xbbf9bb47,
  0xb933b840,0xbabdba09,0xbbb3bb4c,0xbc00bbef,0x36763b78,0xb7ddbb27,0x38993ac4,0xb937ba50,0xba193715,0x35dfba81,0x2f593bef,0xb88ebb7c,
  0xbab3bad1,0x3ba1305b,0xb5f73970,0xb7b2bbfc,0x3493b8cc,0x3aac3b85,0xba292ade,0xb631bbc5,0x3c0039f0,0x2e2d39eb,0xbbd9b8c7,0xb49fbadb,
  0x348739e3,0xb9b3b402,0xbba3bbc6,0xb201b954,0xbab6b8db,0xbbf3bbc9,0xb994bb2f,0xad65b6a4,0xba15bac7,0xb850b941,0xb457b68d,0x251bb010,
  0xb9cfbb16,0x30ac2a31,0x3b9c3bf1,0xb493ae2d,0xb76fb8b4,0x35a133e3,0x3a1d3afe,0xb902b76f,0xb3e3b5a1,0x38b4376f,0x376f3902,0xbafeba1d,
  0xaa31b0ac,0x3b1639cf,0x2e2d3493,0xbbf1bb9c,0xb956ba74,0x305f29cc,0x3b633bd2,0xb44badc9,0xb6e7b859,0x353f335e,0x39d23ab6,0xb8bcb6ff,
  0xb35eb53f,0x385936e7,0x36ff38bc,0xbab6b9d2,0xa9ccb05f,0x3a743956,0x2dc9344b,0xbbd2bb63,0xb8e3b9de,0x30122967,0x3b1e3ba1,0xb402ad65,
  0xb662b801,0x34de32da,0x39823a67,0xb874b68d,0xb2dab4de,0x38013662,0x368d3874,0xba67b982,0xa967b012,0x39de38e3,0x2d653402,0xbba1bb1e,
  0xb876b952,0x2f8c2902,0x3ace3b60,0xb371ad00,0xb5e1b758,0x347e3257,0x392e3a11,0xb82ab61a,0xb257b47e,0x375835e1,0x361a382a,0xba11b92e,
  0xa902af8c,0x39523876,0x2d003371,0xbb60bace,0xb80db8ce,0x2ef3289e,0x3a733b10,0xb2deac9c,0xb562b6b3,0x342031d5,0x38d639b3,0xb7bdb5a5,
  0xb1d5b420,0x36b33562,0x35a537bd,0xb9b3b8d6,0xa89eaef3,0x38ce380d,0x2c9c32de,0xbb10ba73,0xb750b851,0x2e5a2839,0x3a0d3ab0,0xb24bac38,
  0xb4e5b613,0x33863153,0x387a394f,0xb721b52f,0xb153b386,0x361334e5,0x352f3721,0xb94fb87a,0xa839ae5a,0x38513750,0x2c38324b,0xbab0ba0d,
  0xb68eb7b4,0x2dc227a9,0x399d3a41,0xb1b6aba7,0xb46ab577,0x32cd30d2,0x381a38e5,0xb682b4b7,0xb0d2b2cd,0x3577346a,0x34b73682,0xb8e5b81a,
  0xa7a9adc2,0x37b4368e,0x2ba731b6,0xba41b99d,0xb5d2b6d1,0x2d2a26e0,0x392439c5,0xb122aade,0xb3e3b4de,0x32163052,0x376f3874,0xb5dfb43e,
  0xb052b216,0x34de33e3,0x343e35df,0xb874b76f,0xa6e0ad2a,0x36d135d2,0x2ade3122,0xb9c5b924,0xb51cb5f6,0x2c932617,0x38a3393c,0xb08daa16,
  0xb2f4b448,0x31602fa5,0x36a437fe,0xb53ab389,0xafa5b160,0x344832f4,0x3389353a,0xb7feb6a4,0xa617ac93,0x35f6351c,0x2a16308d,0xb93cb8a3,
  0xb46ab523,0x2bf6254d,0x381a38a8,0xafefa94d,0xb209b36b,0x30ac2ea7,0x35d4370a,0xb493b294,0xaea7b0ac,0x336b3209,0x32943493,0xb70ab5d4,
  0xa54dabf6,0x3523346a,0x294d2fef,0xb8a8b81a,0xb378b456,0x2ac82484,0x3715380a,0xaec3a884,0xb120b24a,0x2ff22da9,0x34ff360e,0xb3d3b19e,
  0xada9aff2,0x324a3120,0x319e33d3,0xb60eb4ff,0xa484aac8,0x34563378,0x28842ec3,0xb80ab715,0xb223b31c,0x29992376,0x35eb36c6,0xad97a776,
  0xb039b12d,0x2e8d2cac,0x3426350b,0xb27cb0a6,0xacacae8d,0x312d3039,0x30a6327c,0xb50bb426,0xa376a999,0x331c3223,0x27762d97,0xb6c6b5eb,
  0xb0d2b194,0x286b21e4,0x34b7356a,0xac6aa5e4,0xaea7b012,0x2d2a2b5f,0x32943402,0xb122af59,0xab5fad2a,0x30122ea7,0x2f593122,0xb402b294,
  0xa1e4a86b,0x319430d2,0x25e42c6a,0xb56ab4b7,0xaf0cb012,0x267b2052,0x32f73402,0xaa7aa452,0xacdeadf5,0x2b912967,0x30d731e8,0xaf8bad65,
  0xa967ab91,0x2df52cde,0x2d652f8b,0xb1e8b0d7,0xa052a67b,0x30122f0c,0x24522a7a,0xb402b2f7,0xac79ad2a,0x24201d7f,0x30743122,0xa81fa17f,
  0xaa31ab91,0x28d026e0,0x2e2d2f8b,0xacceaade,0xa6e0a8d0,0x2b912a31,0x2ade2cce,0xaf8bae2d,0x9d7fa420,0x2d2a2c79,0x217f281f,0xb122b074,
  0xa7a9a86b,0x1f1218b6,0x2ba72c6a,0xa3119cb6,0xa54da67b,0x242021e4,0x294d2a7a,0xa81fa5e4,0xa1e4a420,0x267b254d,0x25e4281f,0xaa7aa94d,
  0x98b69f12,0x286b27a9,0x1cb62311,0xac6aaba7,0x211b21e4,0x98b69248,0xa51ba5e4,0x1cb61648,0x1f122052,0x9d7f9bdb,0xa311a452,0x217f1fdb,
  0x1bdb1d7f,0xa0529f12,0x9fdba17f,0x24522311,0x124818b6,0xa1e4a11b,0x96489cb6,0x25e4251b,0x2a632b5f,0xa1e49bdb,0xae5faf59,0x25e41fdb,
  0x286b2967,0xa6e0a4e9,0xac6aad65,0x2ade28e8,0x24e926e0,0xa967a86b,0xa8e8aade,0x2d652c6a,0x1bdb21e4,0xab5faa63,0x9fdba5e4,0x2f592e5f,
  0x2dc22ea7,0xa54d9f12,0xb1b6b294,0x294d2311,0x2bf62cde,0xaa31a86b,0xafefb0d7,0x2e2d2c6a,0x286b2a31,0xacdeabf6,0xac6aae2d,0x30d72fef,
  0x1f12254d,0xaea7adc2,0xa311a94d,0x329431b6,0x302c30d2,0xa7a9a11b,0xb41ab4b7,0x2ba7251b,0x2dc22f0c,0xac79aa63,0xb1b6b2f7,0x30742e5f,
  0x2a632c79,0xaf0cadc2,0xae5fb074,0x32f731b6,0x211b27a9,0xb0d2b02c,0xa51baba7,0x34b7341a,0x317a3257,0xa902a2ad,0xb552b61a,0x2d0026ad,
  0x2f8c309f,0xaddcac2e,0xb371b487,0x31cf3029,0x2c2e2ddc,0xb09faf8c,0xb029b1cf,0x34873371,0x22ad2902,0xb257b17a,0xa6adad00,0x361a3552,
  0x32cd33e3,0xaa31a420,0xb682b76f,0x2e2d281f,0x30ac31bb,0xaf3fad2a,0xb493b58d,0x33283122,0x2d2a2f3f,0xb1bbb0ac,0xb122b328,0x358d3493,
  0x24202a31,0xb3e3b2cd,0xa81fae2d,0x376f3682,0x341334bc,0xab5fa4e9,0xb7a6b85a,0x2f5928e8,0x319432da,0xb052ae28,0xb56ab68d,0x343e3219,
  0x2e283052,0xb2dab194,0xb219b43e,0x368d356a,0x24e92b5f,0xb4bcb413,0xa8e8af59,0x385a37a6,0x34c3358c,0xac47a5b2,0xb85fb8f3,0x304229b1,
  0x327e33fd,0xb106af26,0xb63cb785,0x34e7330f,0x2f263106,0xb3fdb27e,0xb30fb4e7,0x3785363c,0x25b22c47,0xb58cb4c3,0xa9b1b042,0x38f3385f,
  0x35773662,0xacdea67b,0xb8e5b982,0x30d72a7a,0x336b3493,0xb1bbb012,0xb70ab83a,0x358d3402,0x301231bb,0xb493b36b,0xb402b58d,0x383a370a,
  0x267b2cde,0xb662b577,0xaa7ab0d7,0x398238e5,0x36303741,0xad76a744,0xb962ba04,0x316c2b43,0x342e352a,0xb271b092,0xb7d2b8ad,0x3631347b,
  0x30923271,0xb52ab42e,0xb47bb631,0x38ad37d2,0x27442d76,0xb741b630,0xab43b16c,0x3a043962,0x36ee3815,0xae0ea807,0xb9d6ba7a,0x32012c06,
  0x34a735c4,0xb329b113,0xb84ab91b,0x36d234f3,0x31133329,0xb5c4b4a7,0xb4f3b6d2,0x391b384a,0x28072e0e,0xb815b6ee,0xac06b201,0x3a7a39d6,
  0x37b4388e,0xaea7a86b,0xba41bae1,0x32942c6a,0x35233662,0xb3e3b194,0xb8a8b982,0x376f356a,0x319433e3,0xb662b523,0xb56ab76f,0x398238a8,
  0x286b2ea7,0xb88eb7b4,0xac6ab294,0x3ae13a41,0x3841390f,0xaf3fa8d0,0xbaa2bb3a,0x33282cce,0x35a13705,0xb44fb216,0xb902b9e3,0x380535df,
  0x3216344f,0xb705b5a1,0xb5dfb805,0x39e33902,0x28d02f3f,0xb90fb841,0xacceb328,0x3b3a3aa2,0x38ac3997,0xafd8a935,0xbaf7bb83,0x33ba2d33,
  0x362137ac,0xb4aeb298,0xb958ba3d,0x38503654,0x329834ae,0xb7acb621,0xb654b850,0x3a3d3958,0x29352fd8,0xb997b8ac,0xad33b3ba,0x3b833af7,
  0x391c3a28,0xb039a999,0xbb42bbbc,0x34262d97,0x36a4382d,0xb50eb31c,0xb9aaba90,0x389936c6,0x331c350e,0xb82db6a4,0xb6c6b899,0x3a9039aa,
  0x29993039,0xba28b91c,0xad97b426,0x3bbc3b42,0x39923ac3,0xb085a9fe,0xbb81bbe3,0x346f2dfb,0x372a3886,0xb570b3a0,0xb9f8badb,0x38e03737,
  0x33a03570,0xb886b72a,0xb737b8e0,0x3adb39f8,0x29fe3085,0xbac3b992,0xadfbb46f,0x3be33b81,
};

#define PROF(slot) do {} while (0)
#define PROF_DUMP() do {} while (0)
#define PROFA(slot, dep) do {} while (0)
#define PROF3(slot) do {} while (0)
#define PROF2(slot) do {} while (0)

__device__ __forceinline__ uint32_t smem_u32(const void* p) { return (uint32_t)__cvta_generic_to_shared(p); }

__device__ __forceinline__ void mbar_init(uint32_t a, uint32_t c) {
  asm volatile("mbarrier.init.shared::cta.b64 [%0], %1;\n" ::"r"(a), "r"(c) : "memory");
}
__device__ __forceinline__ void mbar_expect_tx(uint32_t a, uint32_t bytes) {
  asm volatile("mbarrier.arrive.expect_tx.shared::cta.b64 _, [%0], %1;\n" ::"r"(a), "r"(bytes) : "memory");
}
__device__ __forceinline__ void mbar_arrive_cluster(uint32_t cluster_addr) {
  asm volatile("mbarrier.arrive.shared::cluster.b64 _, [%0];\n" ::"r"(cluster_addr) : "memory");
}
__device__ __forceinline__ void mbar_arrive_cluster_n(uint32_t cluster_addr, uint32_t n) {
  asm volatile("mbarrier.arrive.shared::cluster.b64 _, [%0], %1;\n" ::"r"(cluster_addr), "r"(n) : "memory");
}
__device__ __forceinline__ bool mbar_try(uint32_t a, uint32_t parity) {
  uint32_t ok;
  asm volatile("{\n.reg .pred p;\nmbarrier.try_wait.parity.shared::cta.b64 p, [%1], %2;\nselp.u32 %0, 1, 0, p;\n}\n"
               : "=r"(ok) : "r"(a), "r"(parity) : "memory");
  return ok;
}
__device__ __forceinline__ void mbar_wait(uint32_t a, uint32_t parity) {
  if (mbar_try(a, parity)) return;
#pragma unroll 1
  for (int n = 0; n < SPIN_LIMIT; n++)
    if (mbar_try(a, parity)) break;
}
__device__ __forceinline__ bool elect_one() {
  uint32_t p;
  asm volatile("{\n.reg .pred P;\nelect.sync _|P, 0xffffffff;\nselp.u32 %0, 1, 0, P;\n}\n" : "=r"(p));
  return p;
}
__device__ __forceinline__ uint32_t mapa(uint32_t a, uint32_t rank) {
  uint32_t r;
  asm volatile("mapa.shared::cluster.u32 %0, %1, %2;\n" : "=r"(r) : "r"(a), "r"(rank));
  return r;
}
__device__ __forceinline__ void nb_sync(int id, int n) { asm volatile("bar.sync %0, %1;\n" ::"r"(id), "r"(n) : "memory"); }
__device__ __forceinline__ void nb_arrive(int id, int n) { asm volatile("bar.arrive %0, %1;\n" ::"r"(id), "r"(n) : "memory"); }
__device__ __forceinline__ void cluster_sync_all() {
  asm volatile("barrier.cluster.arrive.relaxed.aligned;\nbarrier.cluster.wait.aligned;\n" ::: "memory");
}
__device__ __forceinline__ void fence_async_smem() { asm volatile("fence.proxy.async.shared::cta;\n" ::: "memory"); }
__device__ __forceinline__ void fence_async_all() { asm volatile("fence.proxy.async.global;\n" ::: "memory"); }

__device__ __forceinline__ void tma_load_3d(uint32_t dst, const CUtensorMap* tm, uint32_t bar, int c0, int c1, int c2) {
  asm volatile(
      "cp.async.bulk.tensor.3d.shared::cluster.global.mbarrier::complete_tx::bytes [%0], [%1, {%3, %4, %5}], [%2];\n"
      ::"r"(dst), "l"(tm), "r"(bar), "r"(c0), "r"(c1), "r"(c2) : "memory");
}
__device__ __forceinline__ void tma_load_4d(uint32_t dst, const CUtensorMap* tm, uint32_t bar, int c0, int c1, int c2, int c3) {
  asm volatile(
      "cp.async.bulk.tensor.4d.shared::cluster.global.mbarrier::complete_tx::bytes [%0], [%1, {%3, %4, %5, %6}], [%2];\n"
      ::"r"(dst), "l"(tm), "r"(bar), "r"(c0), "r"(c1), "r"(c2), "r"(c3) : "memory");
}
__device__ __forceinline__ void tma_load_3d_mc(uint32_t dst, const CUtensorMap* tm, uint32_t bar, int c0, int c1, int c2) {
  asm volatile(
      "cp.async.bulk.tensor.3d.shared::cluster.global.mbarrier::complete_tx::bytes.multicast::cluster [%0], [%1, {%3, %4, %5}], [%2], %6;\n"
      ::"r"(dst), "l"(tm), "r"(bar), "r"(c0), "r"(c1), "r"(c2), "h"((uint16_t)3) : "memory");
}
__device__ __forceinline__ void bulk_load(uint32_t dst, const void* src, uint32_t bytes, uint32_t bar) {
  asm volatile("cp.async.bulk.shared::cluster.global.mbarrier::complete_tx::bytes [%0], [%1], %2, [%3];\n"
               ::"r"(dst), "l"(src), "r"(bytes), "r"(bar) : "memory");
}
__device__ __forceinline__ void tma_store_3d(const CUtensorMap* tm, uint32_t src, int c0, int c1, int c2) {
  asm volatile("cp.async.bulk.tensor.3d.global.shared::cta.bulk_group [%0, {%2, %3, %4}], [%1];\n"
               ::"l"(tm), "r"(src), "r"(c0), "r"(c1), "r"(c2) : "memory");
}
__device__ __forceinline__ void bulk_commit() { asm volatile("cp.async.bulk.commit_group;\n" ::: "memory"); }
__device__ __forceinline__ void bulk_wait0() { asm volatile("cp.async.bulk.wait_group 0;\n" ::: "memory"); }
__device__ __forceinline__ void prefetch_tmap(const CUtensorMap* tm) {
  asm volatile("prefetch.tensormap [%0];\n" ::"l"(tm) : "memory");
}

__device__ __forceinline__ void wg_fence() { asm volatile("wgmma.fence.sync.aligned;\n" ::: "memory"); }
__device__ __forceinline__ void wg_commit() { asm volatile("wgmma.commit_group.sync.aligned;\n" ::: "memory"); }
template <int N> __device__ __forceinline__ void wg_wait() {
  asm volatile("wgmma.wait_group.sync.aligned %0;\n" ::"n"(N) : "memory");
}
__device__ __forceinline__ uint64_t mkdesc(uint32_t addr, uint32_t lbo, uint32_t sbo, uint32_t swz) {
  return (uint64_t)((addr & 0x3FFFF) >> 4) | ((uint64_t)(lbo >> 4) << 16) | ((uint64_t)(sbo >> 4) << 32) |
         ((uint64_t)swz << 62);
}

#define R4(d, o) "+f"(d[o + 0]), "+f"(d[o + 1]), "+f"(d[o + 2]), "+f"(d[o + 3])
#define R8(d, o) R4(d, o), R4(d, o + 4)
#define R16(d, o) R8(d, o), R8(d, o + 8)
#define R32(d, o) R16(d, o), R16(d, o + 16)
#define R64(d, o) R32(d, o), R32(d, o + 32)

__device__ __forceinline__ void wgmma_n192(float (&d)[96], uint64_t da, uint64_t db, uint32_t acc) {
  asm volatile(
      "{\n.reg .pred p;\nsetp.ne.u32 p, %98, 0;\n"
      "wgmma.mma_async.sync.aligned.m64n192k16.f32.bf16.bf16 "
      "{%0,%1,%2,%3,%4,%5,%6,%7,%8,%9,%10,%11,%12,%13,%14,%15,%16,%17,%18,%19,%20,%21,%22,%23,%24,%25,%26,%27,%28,%29,%30,%31,"
      "%32,%33,%34,%35,%36,%37,%38,%39,%40,%41,%42,%43,%44,%45,%46,%47,%48,%49,%50,%51,%52,%53,%54,%55,%56,%57,%58,%59,%60,%61,%62,%63,"
      "%64,%65,%66,%67,%68,%69,%70,%71,%72,%73,%74,%75,%76,%77,%78,%79,%80,%81,%82,%83,%84,%85,%86,%87,%88,%89,%90,%91,%92,%93,%94,%95}, "
      "%96, %97, p, 1, 1, 0, 1;\n}\n"
      : R64(d, 0), R32(d, 64)
      : "l"(da), "l"(db), "r"(acc));
}
__device__ __forceinline__ void wgmma_n128(float (&d)[64], uint64_t da, uint64_t db, uint32_t acc) {
  asm volatile(
      "{\n.reg .pred p;\nsetp.ne.u32 p, %66, 0;\n"
      "wgmma.mma_async.sync.aligned.m64n128k16.f32.bf16.bf16 "
      "{%0,%1,%2,%3,%4,%5,%6,%7,%8,%9,%10,%11,%12,%13,%14,%15,%16,%17,%18,%19,%20,%21,%22,%23,%24,%25,%26,%27,%28,%29,%30,%31,"
      "%32,%33,%34,%35,%36,%37,%38,%39,%40,%41,%42,%43,%44,%45,%46,%47,%48,%49,%50,%51,%52,%53,%54,%55,%56,%57,%58,%59,%60,%61,%62,%63}, "
      "%64, %65, p, 1, 1, 0, 1;\n}\n"
      : R64(d, 0)
      : "l"(da), "l"(db), "r"(acc));
}
#define WG128(C, ACC)                                                                                                      \
  asm volatile(                                                                                                            \
      "{\n.reg .b64 a, b;\nmov.b64 a, {%64, %66};\nmov.b64 b, {%65, %66};\n"                                               \
      "wgmma.mma_async.sync.aligned.m64n128k16.f32.bf16.bf16 "                                                             \
      "{%0,%1,%2,%3,%4,%5,%6,%7,%8,%9,%10,%11,%12,%13,%14,%15,%16,%17,%18,%19,%20,%21,%22,%23,%24,%25,%26,%27,%28,%29,%30,%31," \
      "%32,%33,%34,%35,%36,%37,%38,%39,%40,%41,%42,%43,%44,%45,%46,%47,%48,%49,%50,%51,%52,%53,%54,%55,%56,%57,%58,%59,%60,%61," \
      "%62,%63}, a, b, " ACC ", 1, 1, 0, 1;\n}\n"                                                                          \
      : Z16(C, d, 0), Z16(C, d, 16), Z16(C, d, 32), Z16(C, d, 48)                                                          \
      : "r"(da), "r"(db), "r"(0x40000040))
#define Z4(C, d, o) C(d[o + 0]), C(d[o + 1]), C(d[o + 2]), C(d[o + 3])
#define Z16(C, d, o) Z4(C, d, o), Z4(C, d, o + 4), Z4(C, d, o + 8), Z4(C, d, o + 12)
__device__ __forceinline__ void wgmma_n128z(float (&d)[64], uint32_t da, uint32_t db) { WG128("=f", "0"); }
__device__ __forceinline__ void wgmma_n128a(float (&d)[64], uint32_t da, uint32_t db) { WG128("+f", "1"); }
template <int N> __device__ __forceinline__ void fence_regs(float (&d)[N]) {
#pragma unroll
  for (int i = 0; i < N; i++) asm volatile("" : "+f"(d[i])::"memory");
}

__device__ __forceinline__ void mma16816(float (&d)[4], uint32_t a0, uint32_t a1, uint32_t a2, uint32_t a3, uint32_t b0,
                                         uint32_t b1) {
  asm("mma.sync.aligned.m16n8k16.row.col.f32.bf16.bf16.f32 {%0,%1,%2,%3}, {%4,%5,%6,%7}, {%8,%9}, {%0,%1,%2,%3};\n"
      : "+f"(d[0]), "+f"(d[1]), "+f"(d[2]), "+f"(d[3])
      : "r"(a0), "r"(a1), "r"(a2), "r"(a3), "r"(b0), "r"(b1));
}
__device__ __forceinline__ void mma16816_z(float (&d)[4], uint32_t a0, uint32_t a1, uint32_t a2, uint32_t a3, uint32_t b0,
                                           uint32_t b1) {
  asm("mma.sync.aligned.m16n8k16.row.col.f32.bf16.bf16.f32 {%0,%1,%2,%3}, {%4,%5,%6,%7}, {%8,%9}, {%10,%10,%10,%10};\n"
      : "=f"(d[0]), "=f"(d[1]), "=f"(d[2]), "=f"(d[3])
      : "r"(a0), "r"(a1), "r"(a2), "r"(a3), "r"(b0), "r"(b1), "f"(0.f));
}
__device__ __forceinline__ void ldsm4t(uint32_t (&r)[4], uint32_t a) {
  asm volatile("ldmatrix.sync.aligned.m8n8.x4.trans.shared.b16 {%0,%1,%2,%3}, [%4];\n"
               : "=r"(r[0]), "=r"(r[1]), "=r"(r[2]), "=r"(r[3]) : "r"(a) : "memory");
}
__device__ __forceinline__ void ldsm2t(uint32_t& r0, uint32_t& r1, uint32_t a) {
  asm volatile("ldmatrix.sync.aligned.m8n8.x2.trans.shared.b16 {%0,%1}, [%2];\n" : "=r"(r0), "=r"(r1) : "r"(a) : "memory");
}
__device__ __forceinline__ void st_async128(uint32_t a, uint32_t bar, uint32_t x, uint32_t y, uint32_t z, uint32_t w) {
  asm volatile("st.async.weak.shared::cluster.mbarrier::complete_tx::bytes.v4.b32 [%0], {%2,%3,%4,%5}, [%1];\n"
               ::"r"(a), "r"(bar), "r"(x), "r"(y), "r"(z), "r"(w) : "memory");
}
__device__ __forceinline__ void mbar_arrive(uint32_t a) {
  asm volatile("mbarrier.arrive.shared::cta.b64 _, [%0];\n" ::"r"(a) : "memory");
}
__device__ __forceinline__ void stsm4(uint32_t a, uint32_t r0, uint32_t r1, uint32_t r2, uint32_t r3) {
  asm volatile("stmatrix.sync.aligned.m8n8.x4.shared.b16 [%0], {%1,%2,%3,%4};\n"
               ::"r"(a), "r"(r0), "r"(r1), "r"(r2), "r"(r3) : "memory");
}
__device__ __forceinline__ void stsm4t(uint32_t a, uint32_t r0, uint32_t r1, uint32_t r2, uint32_t r3) {
  asm volatile("stmatrix.sync.aligned.m8n8.x4.trans.shared.b16 [%0], {%1,%2,%3,%4};\n"
               ::"r"(a), "r"(r0), "r"(r1), "r"(r2), "r"(r3) : "memory");
}
__device__ __forceinline__ uint2 lds64(uint32_t a) {
  uint2 v;
  asm volatile("ld.shared.v2.u32 {%0,%1}, [%2];\n" : "=r"(v.x), "=r"(v.y) : "r"(a) : "memory");
  return v;
}
__device__ __forceinline__ uint4 lds128(uint32_t a) {
  uint4 v;
  asm volatile("ld.shared.v4.u32 {%0,%1,%2,%3}, [%4];\n" : "=r"(v.x), "=r"(v.y), "=r"(v.z), "=r"(v.w) : "r"(a) : "memory");
  return v;
}
__device__ __forceinline__ void sts128(uint32_t a, uint32_t x, uint32_t y, uint32_t z, uint32_t w) {
  asm volatile("st.shared.v4.u32 [%0], {%1,%2,%3,%4};\n" ::"r"(a), "r"(x), "r"(y), "r"(z), "r"(w) : "memory");
}
__device__ __forceinline__ void sts64(uint32_t a, uint32_t x, uint32_t y) {
  asm volatile("st.shared.v2.u32 [%0], {%1,%2};\n" ::"r"(a), "r"(x), "r"(y) : "memory");
}
__device__ __forceinline__ uint32_t pack_bf16(float lo, float hi) {
  uint32_t r;
  asm("cvt.rn.bf16x2.f32 %0, %1, %2;\n" : "=r"(r) : "f"(hi), "f"(lo));
  return r;
}
__device__ __forceinline__ uint32_t bmul2(uint32_t a, uint32_t b) {
  uint32_t r;
  asm("mul.rn.bf16x2 %0, %1, %2;\n" : "=r"(r) : "r"(a), "r"(b));
  return r;
}
__device__ __forceinline__ uint32_t bmax2(uint32_t a, uint32_t b) {
  uint32_t r;
  asm("max.bf16x2 %0, %1, %2;\n" : "=r"(r) : "r"(a), "r"(b));
  return r;
}
__device__ __forceinline__ uint32_t bfma2(uint32_t a, uint32_t b, uint32_t c) {
  uint32_t r;
  asm("fma.rn.bf16x2 %0, %1, %2, %3;\n" : "=r"(r) : "r"(a), "r"(b), "r"(c));
  return r;
}
__device__ __forceinline__ uint32_t clock32() {
  uint32_t t;
  asm volatile("mov.u32 %0, %%clock;\n" : "=r"(t));
  return t;
}
__device__ __forceinline__ void prefetch_l2(const void* p) { asm volatile("prefetch.global.L2 [%0];\n" ::"l"(p)); }
__device__ __forceinline__ void cp_async16(uint32_t dst, const void* src, uint32_t srcbytes) {
  asm volatile("cp.async.cg.shared.global.L2::256B [%0], [%1], 16, %2;\n" ::"r"(dst), "l"(src), "r"(srcbytes) : "memory");
}
__device__ __forceinline__ uint32_t ld_acquire(const uint32_t* p) {
  uint32_t v;
  asm volatile("ld.acquire.gpu.global.u32 %0, [%1];\n" : "=r"(v) : "l"(p) : "memory");
  return v;
}
__device__ __forceinline__ uint32_t ld_relaxed(const uint32_t* p) {
  uint32_t v;
  asm volatile("ld.relaxed.gpu.global.u32 %0, [%1];\n" : "=r"(v) : "l"(p) : "memory");
  return v;
}
__device__ __forceinline__ void st_release(uint32_t* p, uint32_t v) {
  asm volatile("st.release.gpu.global.u32 [%0], %1;\n" ::"l"(p), "r"(v) : "memory");
}
__device__ __forceinline__ uint4 ld_b128(const uint4* p) {
  unsigned long long a, b;
  asm volatile("{\n.reg .b128 v;\nld.relaxed.gpu.global.b128 v, [%2];\nmov.b128 {%0, %1}, v;\n}\n" : "=l"(a), "=l"(b) : "l"(p) : "memory");
  return make_uint4((uint32_t)a, (uint32_t)(a >> 32), (uint32_t)b, (uint32_t)(b >> 32));
}
__device__ __forceinline__ void st_b128(uint4* p, uint32_t x, uint32_t y, uint32_t z, uint32_t w) {
  asm volatile("{\n.reg .b128 v;\nmov.b128 v, {%1, %2};\nst.relaxed.gpu.global.b128 [%0], v;\n}\n"
               ::"l"(p), "l"(x | (unsigned long long)y << 32), "l"(z | (unsigned long long)w << 32) : "memory");
}

struct Params {
  const __nv_bfloat16* x;
  const __nv_bfloat16* w;
  uint8_t tile[72];
  const __nv_bfloat16* q;
  const __nv_bfloat16* k;
  const __nv_bfloat16* v;
  const __nv_bfloat16* shift_k;
  const __nv_bfloat16* ssm_k;
  const __nv_bfloat16* ssm_D;
  const __nv_bfloat16* wo;
  __nv_bfloat16* out;
  uint32_t zero;
};

__device__ __forceinline__ uint32_t lds32(uint32_t a) {
  uint32_t v;
  asm volatile("ld.shared.u32 %0, [%1];\n" : "=r"(v) : "r"(a) : "memory");
  return v;
}
__device__ __forceinline__ float bf_lo(uint32_t v) {
  uint32_t r;
  asm("prmt.b32 %0, %1, 0, 0x1044;\n" : "=r"(r) : "r"(v));
  return __uint_as_float(r);
}
__device__ __forceinline__ float bf_hi(uint32_t v) { return __uint_as_float(v & 0xffff0000u); }
__device__ __forceinline__ float ex2(float x) {
  float r;
  asm("ex2.approx.ftz.f32 %0, %1;\n" : "=f"(r) : "f"(x));
  return r;
}
__device__ __forceinline__ float rcp(float x) {
  float r;
  asm("rcp.approx.ftz.f32 %0, %1;\n" : "=f"(r) : "f"(x));
  return r;
}

#define Q4(c, d, o) c(d[o + 0]), c(d[o + 1]), c(d[o + 2]), c(d[o + 3])
#define Q8(c, d, o) Q4(c, d, o), Q4(c, d, o + 4)
#define Q16(c, d, o) Q8(c, d, o), Q8(c, d, o + 8)
#define Q32(c, d) Q16(c, d, 0), Q16(c, d, 16)
#define L8 "{%0,%1,%2,%3,%4,%5,%6,%7}"
#define L16 "{%0,%1,%2,%3,%4,%5,%6,%7,%8,%9,%10,%11,%12,%13,%14,%15}"
#define L32 "{%0,%1,%2,%3,%4,%5,%6,%7,%8,%9,%10,%11,%12,%13,%14,%15,%16,%17,%18,%19,%20,%21,%22,%23,%24,%25,%26,%27,%28,%29,%30,%31}"
__device__ __forceinline__ void fft_rows(uint32_t (&d)[32], const uint32_t (&a)[2][4], uint64_t db) {
  asm volatile("wgmma.mma_async.sync.aligned.m64n128k16.f16.f16.f16 " L32 ", {%32,%33,%34,%35}, %36, 0, 1, 1, 1;\n"
               : Q32("=r", d) : "r"(a[0][0]), "r"(a[0][1]), "r"(a[0][2]), "r"(a[0][3]), "l"(db));
  asm volatile("wgmma.mma_async.sync.aligned.m64n128k16.f16.f16.f16 " L32 ", {%32,%33,%34,%35}, %36, 1, 1, 1, 1;\n"
               : Q32("+r", d) : "r"(a[1][0]), "r"(a[1][1]), "r"(a[1][2]), "r"(a[1][3]), "l"(db + 64));
}
template <int INV> __device__ __forceinline__ void fft_cols(uint32_t (&d)[8], const uint32_t (&a)[2][4], uint64_t db) {
  asm volatile("wgmma.mma_async.sync.aligned.m64n32k16.f16.f16.f16 " L8 ", {%8,%9,%10,%11}, %12, 0, 1, 1, %13;\n"
               : Q8("=r", d, 0) : "r"(a[0][0]), "r"(a[0][1]), "r"(a[0][2]), "r"(a[0][3]), "l"(db), "n"(INV));
  asm volatile("wgmma.mma_async.sync.aligned.m64n32k16.f16.f16.f16 " L8 ", {%8,%9,%10,%11}, %12, 1, 1, 1, %13;\n"
               : Q8("+r", d, 0) : "r"(a[1][0]), "r"(a[1][1]), "r"(a[1][2]), "r"(a[1][3]), "l"(db + (INV ? 16 : 64)), "n"(INV));
}
__device__ __forceinline__ void fft_back(float (&d)[16], uint64_t da, uint64_t db) {
  asm volatile("wgmma.mma_async.sync.aligned.m64n32k16.f32.f16.f16 " L16 ", %16, %17, 0, 1, 1, 1, 1;\n"
               : Q16("=f", d, 0) : "l"(da), "l"(db));
#pragma unroll
  for (int i = 1; i < 4; i++)
    asm volatile("wgmma.mma_async.sync.aligned.m64n32k16.f32.f16.f16 " L16 ", %16, %17, 1, 1, 1, 1, 1;\n"
                 : Q16("+f", d, 0) : "l"(da + 32 * i), "l"(db + 64 * i));
}
__device__ __forceinline__ uint32_t hmul2(uint32_t a, uint32_t b) {
  uint32_t r;
  asm("mul.rn.f16x2 %0, %1, %2;\n" : "=r"(r) : "r"(a), "r"(b));
  return r;
}
__device__ __forceinline__ uint32_t hadd2(uint32_t a, uint32_t b) {
  uint32_t r;
  asm("add.rn.f16x2 %0, %1, %2;\n" : "=r"(r) : "r"(a), "r"(b));
  return r;
}
__device__ __forceinline__ uint32_t hneg2(uint32_t a) {
  uint32_t r;
  asm("neg.f16x2 %0, %1;\n" : "=r"(r) : "r"(a));
  return r;
}
__device__ __forceinline__ uint32_t hfma2(uint32_t a, uint32_t b, uint32_t c) {
  uint32_t r;
  asm("fma.rn.f16x2 %0, %1, %2, %3;\n" : "=r"(r) : "r"(a), "r"(b), "r"(c));
  return r;
}
__device__ __forceinline__ uint32_t pack_f16(float lo, float hi) {
  uint32_t r;
  asm("cvt.rn.f16x2.f32 %0, %1, %2;\n" : "=r"(r) : "f"(hi), "f"(lo));
  return r;
}
__device__ __forceinline__ uint32_t bmaxabs2(uint32_t a, uint32_t b) {
  uint32_t r;
  asm("max.xorsign.abs.bf16x2 %0, %1, %2;\n" : "=r"(r) : "r"(a), "r"(b));
  return r;
}
struct C2 { uint32_t r, i; };
__device__ __forceinline__ C2 cmul(C2 a, C2 b) {
  return C2{hfma2(a.r, b.r, hneg2(hmul2(a.i, b.i))), hfma2(a.r, b.i, hmul2(a.i, b.r))};
}
__device__ __forceinline__ C2 cfma(C2 a, C2 b, C2 c) {
  return C2{hfma2(a.r, b.r, hfma2(hneg2(a.i), b.i, c.r)), hfma2(a.r, b.i, hfma2(a.i, b.r, c.i))};
}
__device__ __forceinline__ C2 crot(C2 z, C2 t) {
  const uint32_t r = hfma2(t.r, z.i, z.r), i = hfma2(t.i, r, z.i);
  return C2{hfma2(t.r, i, r), i};
}
__device__ __forceinline__ C2 cget(const uint32_t (&e)[8], int j, int b) { return C2{e[4 * j + b], e[4 * j + 2 + b]}; }
template <int N> __device__ __forceinline__ void fence_regs(uint32_t (&d)[N]) {
#pragma unroll
  for (int i = 0; i < N; i++) asm volatile("" : "+r"(d[i])::"memory");
}
__device__ __forceinline__ void ldsm4(uint32_t (&r)[4], uint32_t a) {
  asm volatile("ldmatrix.sync.aligned.m8n8.x4.shared.b16 {%0,%1,%2,%3}, [%4];\n"
               : "=r"(r[0]), "=r"(r[1]), "=r"(r[2]), "=r"(r[3]) : "r"(a) : "memory");
}

__device__ __forceinline__ uint32_t movm(uint32_t a) {
  uint32_t r;
  asm volatile("movmatrix.sync.aligned.m8n8.trans.b16 %0, %1;\n" : "=r"(r) : "r"(a));
  return r;
}
template <int C0, int H, bool T> __device__ __forceinline__ void attn_pack(const float (&acc)[96], uint32_t (&d)[8]) {
#pragma unroll
  for (int c = 0; c < 8; c++) {
    asm volatile("cvt.rn.bf16x2.f32 %0, %1, %2;\n" : "=r"(d[c]) : "f"(acc[4 * (C0 + c) + 2 * H + 1]), "f"(acc[4 * (C0 + c) + 2 * H]));
    if (T) d[c] = movm(d[c]);
  }
}
__device__ __forceinline__ void attn_qk(float (&s)[4], const uint32_t (&qlo)[8], const uint32_t (&qhi)[8],
                                        const uint32_t (&k)[8], int c) {
  mma16816_z(s, qlo[c], qhi[c], qlo[c + 1], qhi[c + 1], k[c], k[c + 1]);
  mma16816(s, qlo[c + 2], qhi[c + 2], qlo[c + 3], qhi[c + 3], k[c + 2], k[c + 3]);
}
template <int N> __device__ __forceinline__ void quad_softmax(float (&x)[N][2], uint32_t (&pp)[N]) {
  const float c2 = 1.4426950408889634f;
  uint32_t q[N], mx[N / 2];
#pragma unroll
  for (int n = 0; n < N; n++) {
    const uint32_t r = pack_bf16(x[n][0], x[n][1]);
    q[n] = bfma2(r, 0x3e353e35u, bmul2(r, 0x379e379eu));
    x[n][0] = bf_lo(q[n]);
    x[n][1] = bf_hi(q[n]);
  }
#pragma unroll
  for (int n = 0; n < N / 2; n++)
    mx[n] = bmax2(__byte_perm(q[2 * n], q[2 * n + 1], 0x5410), __byte_perm(q[2 * n], q[2 * n + 1], 0x7632));
#pragma unroll
  for (int o = 1; o <= 2; o++) {
#pragma unroll
    for (int n = 0; n < N / 2; n++) mx[n] = bmax2(mx[n], __shfl_xor_sync(0xffffffffu, mx[n], o));
  }
  float m[N], t[N];
#pragma unroll
  for (int n = 0; n < N / 2; n++) {
    m[2 * n] = bf_lo(mx[n]);
    m[2 * n + 1] = bf_hi(mx[n]);
  }
#pragma unroll
  for (int n = 0; n < N; n++) {
    const float nm = -m[n] * c2;
    x[n][0] = ex2(fmaf(x[n][0], c2, nm));
    x[n][1] = ex2(fmaf(x[n][1], c2, nm));
  }
#pragma unroll
  for (int n = 0; n < N; n += 2) {
    float u0, u1;
    asm("mma.sync.aligned.m16n8k8.row.col.f32.tf32.tf32.f32 {%0,%1,%2,%3}, {%4,%5,%6,%7}, {%8,%8}, {%9,%9,%9,%9};\n"
        : "=f"(t[n]), "=f"(u0), "=f"(t[n + 1]), "=f"(u1)
        : "r"(__float_as_uint(x[n][0])), "r"(__float_as_uint(x[n + 1][0])), "r"(__float_as_uint(x[n][1])),
          "r"(__float_as_uint(x[n + 1][1])), "r"(0x3f800000u), "f"(0.f));
  }
#pragma unroll
  for (int n = 0; n < N; n++) {
    const float inv = rcp(t[n]);
    pp[n] = pack_bf16(x[n][0] * inv, x[n][1] * inv);
  }
}
template <bool SPLIT>
__device__ __forceinline__ void attn_pv(uint32_t dst, const uint32_t (&vp)[8], const uint32_t (&vo)[8], int c, uint32_t pp,
                                        uint32_t maskLE) {
  const uint32_t b0 = pp & ~maskLE, b1 = pp & maskLE;
  float o[2][4];
#pragma unroll
  for (int i = 0; i < 2; i++) {
    if (SPLIT) {
      asm("mma.sync.aligned.m16n8k8.row.col.f32.bf16.bf16.f32 {%0,%1,%2,%3}, {%4,%5}, {%6}, {%7,%7,%7,%7};\n"
          : "=f"(o[i][0]), "=f"(o[i][1]), "=f"(o[i][2]), "=f"(o[i][3])
          : "r"(vp[c + 2 * i]), "r"(vp[c + 2 * i + 1]), "r"(b0), "f"(0.f));
      asm("mma.sync.aligned.m16n8k8.row.col.f32.bf16.bf16.f32 {%0,%1,%2,%3}, {%4,%5}, {%6}, {%0,%1,%2,%3};\n"
          : "+f"(o[i][0]), "+f"(o[i][1]), "+f"(o[i][2]), "+f"(o[i][3])
          : "r"(vo[c + 2 * i]), "r"(vo[c + 2 * i + 1]), "r"(b1));
    } else {
      mma16816_z(o[i], vp[c + 2 * i], vp[c + 2 * i + 1], vo[c + 2 * i], vo[c + 2 * i + 1], b0, b1);
    }
  }
  stsm4t(dst, pack_bf16(o[0][0], o[0][1]), pack_bf16(o[0][2], o[0][3]), pack_bf16(o[1][0], o[1][1]),
         pack_bf16(o[1][2], o[1][3]));
}

template <int MODE>
__global__ void __cluster_dims__(2, 1, 1) __launch_bounds__(NTHREADS, 1)
fused_kernel(const Params p, const __grid_constant__ CUtensorMap tmX, const __grid_constant__ CUtensorMap tmW,
             const __grid_constant__ CUtensorMap tmWo, const __grid_constant__ CUtensorMap tmWp,
             const __grid_constant__ CUtensorMap tmQ,
             const __grid_constant__ CUtensorMap tmOb,
             const __grid_constant__ CUtensorMap tmXh, const __grid_constant__ CUtensorMap tmWh) {
  extern __shared__ __align__(1024) uint8_t smem[];
  const int tid = threadIdx.x;
  if (tid >= 352) {
    const uint32_t i = (blockIdx.x & 127) * 16 + (tid & 15);
    prefetch_l2(tid & 16 ? (const char*)p.w + i * 128 : (const char*)p.x + i * 2048);
  }
  const uint32_t sb = smem_u32(smem);
  const int rank = blockIdx.x & 1;
  const bool halo_cta = blockIdx.x < 4;
  if (halo_cta && MODE != 0) return;
  const int tile = p.tile[blockIdx.x >> 1];
  const int rg = tile >> 3, hp = (tile & 7) * 2 + rank;
  const int par = rg >> 2, gidx = rg & 3;
  if (tid < 256 && !halo_cta && MODE != 2) {
    const uint32_t r = tid >> 3, c = tid & 7;
    asm volatile(
        "cp.async.cg.shared.global [%0 + 98304], [%1], 16;\ncp.async.cg.shared.global [%0 + 102400], [%1 + 2048], 16;\n"
        "cp.async.cg.shared.global [%0 + 106496], [%1 + 4096], 16;\ncp.async.cg.shared.global [%0], [%2], 16;\n"
        "cp.async.cg.shared.global [%0 + 4096], [%2 + 131072], 16;\ncp.async.cg.shared.global [%0 + 8192], [%2 + 262144], 16;\n"
        "cp.async.cg.shared.global [%0 + 12288], [%2 + 393216], 16;\ncp.async.cg.shared.global [%0 + 16384], [%2 + 524288], 16;\n"
        "cp.async.cg.shared.global [%0 + 20480], [%2 + 655360], 16;\ncp.async.cg.shared.global [%0 + 24576], [%2 + 786432], 16;\n"
        "cp.async.cg.shared.global [%0 + 28672], [%2 + 917504], 16;\ncp.async.commit_group;\n"
        ::"r"(sb + r * 128 + ((c ^ (r & 7)) << 4)), "l"((const char*)p.w + (r * 6144 + c * 16 + hp * 128)),
        "l"((const char*)p.x + (r * 4096 + c * 16 + gidx * 1048576 + par * 2048)) : "memory");
    static_assert(OFF_1B == 98304, "offsets above");
  }
  const uint32_t bars = sb + OFF_BAR;
  const int lane = tid & 31, warp = __shfl_sync(0xffffffffu, tid >> 5, 0);
  const int grp = par * 4 + (hp >> 2), mem = gidx * 2 + ((hp >> 1) & 1);
  const int rb2 = par * 8 + mem, cb2 = (grp & 3) * 2 + rank;
  const int chb = grp * 16 + mem * 2 + rank;
  const int cta = rg * 16 + hp;
  const int hsel = rb2 & 1;

  if (warp >= 8) {
    asm volatile("setmaxnreg.dec.sync.aligned.u32 %0;\n" :: "n"(REG_HELP));
    auto halo_issue = [&](int n, int s) {
      const uint32_t fb = bars + 8 * (BAR_FULLB + s), st = sb + s * STGH;
      tma_load_3d(st + 8192, &tmWh, fb, 0, (n >> 1) * 64, 16 + (n & 1) * 16 + blockIdx.x * 4);
      tma_load_4d(st, &tmXh, fb, (n >> 1) * 64, 248, 0, 0);
      mbar_expect_tx(fb, STGH - 2048);
    };
    if (tid == 256) {
      prefetch_tmap(halo_cta ? &tmXh : &tmX);
#pragma unroll
      for (int i = 0; i < NS1B; i++) mbar_init(bars + 8 * (BAR_FULLB + i), 1);
#pragma unroll
      for (int i = 0; i < NS1A; i++) mbar_init(bars + 8 * (BAR_FULLA + i), 1);
      asm volatile("fence.mbarrier_init.release.cluster;\n" ::: "memory");
      if (!halo_cta && MODE != 2) {
        mbar_expect_tx(bars + 8 * (BAR_FULLB + 1), STG1B);
        tma_load_3d(sb + OFF_1B + 1 * STG1B, &tmW, bars + 8 * (BAR_FULLB + 1), hp * 64, 32, 0);
        mbar_expect_tx(bars + 8 * (BAR_FULLA + 1), STG1A);
        tma_load_3d(sb + STG1A, &tmX, bars + 8 * (BAR_FULLA + 1), 64, par, gidx * 256);
        tma_load_3d(sb + STG1A + 16384, &tmX, bars + 8 * (BAR_FULLA + 1), 64, par, gidx * 256 + 128);
        mbar_expect_tx(bars + 8 * (BAR_FULLB + 2), STG1B);
        tma_load_3d(sb + OFF_1B + 2 * STG1B, &tmW, bars + 8 * (BAR_FULLB + 2), hp * 64, 64, 0);
        mbar_arrive(bars + 8 * BAR_FULLA);
        mbar_arrive(bars + 8 * BAR_FULLB);
      } else if (halo_cta) {
        halo_issue(0, 0);
      }
    } else if (tid >= 289 && tid < 289 + 48 && tid != 320) {
      const uint32_t i = tid - 289 - (tid > 320), b = blockIdx.x & 127;
      if (MODE != 2) prefetch_l2(i < 16 ? (const char*)p.x + (b * 16 + i) * 2048 + 128 : (const char*)p.w + (2048 + b * 31 + i - 16) * 128);
    } else if (tid == 288) {
#pragma unroll
      for (int i = 0; i < NS1A; i++) mbar_init(bars + 8 * (BAR_EMPTYA + i), 4);
#pragma unroll
      for (int i = 0; i < NS1B; i++) mbar_init(bars + 8 * (BAR_EMPTYB + i), 2);
      mbar_init(bars + 8 * BAR_X, 3);
      mbar_init(bars + 8 * BAR_TAB, 16);
      mbar_init(bars + 8 * BAR_U, 1);
      mbar_init(bars + 8 * BAR_H, 1);
      mbar_init(bars + 8 * BAR_Q, 1);
      mbar_init(bars + 8 * BAR_LAND, 5);
      mbar_init(bars + 8 * (BAR_LAND + 1), 5);
      asm volatile("fence.mbarrier_init.release.cluster;\n" ::: "memory");
    } else if (tid == 320) {
#pragma unroll
      for (int i = 0; i < NS2; i++) {
        mbar_init(bars + 8 * (BAR_FULL2 + i), 1);
        mbar_init(bars + 8 * (BAR_EMPTY2 + i), 2);
        mbar_init(bars + 8 * (BAR_EMPTY2B + i), 2);
      }
      asm volatile("fence.mbarrier_init.release.cluster;\n" ::: "memory");
    } else if (tid == 352) {
#pragma unroll
      for (int i = 0; i < 4; i++) mbar_init(bars + 8 * (BAR_Y + i), i < 2 ? 4 : i == 2 ? 10 : 8);
      mbar_init(bars + 8 * BAR_XFREE, 1);
#pragma unroll
      for (int i = 0; i < 9; i++) mbar_init(bars + 8 * (BAR_KH + i), 1);
      asm volatile("fence.mbarrier_init.release.cluster;\n" ::: "memory");
    }
    __syncwarp();
    cluster_sync_all();
    if (warp == 8) PROF2(24);
    const int hw = warp - 8;
    const int lr = lane & 7, lm = lane >> 3;
    auto g1_issue_a = [&](int j, int s) {
      const uint32_t fb = bars + 8 * (BAR_FULLA + s);
      mbar_expect_tx(fb, STG1A);
      tma_load_3d_mc(sb + s * STG1A + rank * 16384, &tmX, fb, j * 64, par, gidx * 256 + rank * 128);
    };
    auto g1_issue_b = [&](int kb, int s) {
      const uint32_t fb = bars + 8 * (BAR_FULLB + s);
      mbar_expect_tx(fb, STG1B);
      tma_load_3d(sb + OFF_1B + s * STG1B, &tmW, fb, hp * 64, kb * 32, 0);
    };
    auto g2_k = [&](int kb) { return (kb < 2 ? hp : kb < 4 ? hp & 14 : hp & 12) ^ kb; };
    auto g2_issue_b = [&](uint32_t fb, uint32_t bytes, uint32_t dst, int k0, bool whole) {
      if (whole) {
        tma_load_3d(dst, &tmWo, fb, 0, k0, cb2 * 2);
      } else {
#pragma unroll
        for (int i = 0; i < 4; i++)
          tma_load_3d(dst + (i & 1) * XT + (i >> 1) * 4 * XT, &tmWp, fb, 0, k0 + (i >> 1) * 32, cb2 * 2 + (i & 1));
      }
      mbar_expect_tx(fb, bytes);
    };
    auto send_y = [&](uint32_t o, uint32_t step, int half) {
      const uint32_t peer = mapa(sb, rank ^ 1);
      o += OFF_X + (rank ^ 1) * 4096 + half * 2048 + lane * 16;
      uint4 a[8];
#pragma unroll
      for (int i = 0; i < 8; i++) a[i] = lds128(sb + o + (i >> 2) * step + (i & 2) * (XT / 2) + (i & 1) * 512);
#pragma unroll
      for (int i = 0; i < 8; i++)
        st_async128(peer + o + 1024 + (i >> 2) * step + (i & 2) * (XT / 2) + (i & 1) * 512,
                    peer + OFF_BAR + 8 * (BAR_LAND + half), a[i].x, a[i].y, a[i].z, a[i].w);
    };

    if (halo_cta) {
      if (hw == 0) {
        int s = 1, ph = 1;
#pragma unroll 1
        for (int n = 1; n < 32; n++) {
          mbar_wait(bars + 8 * (BAR_EMPTYB + s), ph);
          if (elect_one()) halo_issue(n, s);
          if (++s == NS1B) { s = 0; ph ^= 1; }
        }
      }
      __syncwarp();
    } else if (hw == 0) {
      uint32_t epoch = 0;
      if (MODE == 2) {
        if (lane < NS2) mbar_arrive_cluster_n(mapa(bars, rank) + 8 * (BAR_EMPTY2 + lane), 2);
      } else {
      if (lane == 0) {
        mbar_expect_tx(bars + 8 * BAR_U, 32768);
        mbar_expect_tx(bars + 8 * BAR_LAND, 8192);
        mbar_expect_tx(bars + 8 * (BAR_LAND + 1), 8192);
        mbar_expect_tx(bars + 8 * BAR_Q, 32768);
        prefetch_tmap(&tmQ);
      }
      {
        int sa = 2, pha = 1, sbb = 3, phb = 1;
#pragma unroll 1
        for (int kb = 3; kb < 32; kb++) {
          if (!(kb & 1)) {
            mbar_wait(bars + 8 * (BAR_EMPTYA + sa), pha);
            if (elect_one()) g1_issue_a(kb >> 1, sa);
            if (++sa == NS1A) { sa = 0; pha ^= 1; }
          }
          mbar_wait(bars + 8 * (BAR_EMPTYB + sbb), phb);
          if (elect_one()) g1_issue_b(kb, sbb);
          __syncwarp();
          if (kb == 4) epoch = ld_relaxed(g_flag_o + FS * cta);
          if (kb == 4) PROF2(27);
          if (++sbb == NS1B) { sbb = 0; phb ^= 1; }
        }
      }
      auto q_issue = [&](int i) {
        mbar_wait(bars + 8 * (i ? BAR_EMPTYB + 3 : BAR_EMPTYA + 1), i);
        if (elect_one())
          asm volatile(
              "cp.async.bulk.tensor.5d.shared::cluster.global.mbarrier::complete_tx::bytes [%0], [%1, {%3, %4, %4, %4, %5}], [%2];\n"
              ::"r"(sb + (i ? OFF_Q1 : OFF_Q0)), "l"(&tmQ), "r"(bars + 8 * BAR_Q), "r"((chb & ~1) * 8), "r"(0), "r"(rank * 32 + i * 64)
              : "memory");
        __syncwarp();
      };
      epoch++;
      if (lane == 0) {
        prefetch_tmap(&tmWo);
        prefetch_tmap(&tmWp);
        prefetch_tmap(&tmOb);
      }
      __syncwarp();
      {
        uint4 h[6] = {};
        if (gidx != 0) {
#pragma unroll 1
          for (int n = 0; n < SPIN_LIMIT; n++) {
            bool ok = true;
#pragma unroll
            for (int i = 0; i < 6; i++) h[i] = ld_b128(g_halo + cta * 192 + i * 32 + lane);
#pragma unroll
            for (int i = 0; i < 6; i++) ok = ok && h[i].w == epoch;
            if (__all_sync(0xffffffffu, ok)) break;
          }
          PROF(18);
        }
        q_issue(0);
        sts128(sb + OFF_KH + lane * 16, h[0].x, h[0].y, h[0].z, h[1].x);
        sts128(sb + OFF_KH + 512 + lane * 16, h[1].y, h[1].z, h[2].x, h[2].y);
        sts64(sb + OFF_KH + 1024 + lane * 8, h[3].x, h[3].y);
        sts64(sb + OFF_KH + 1280 + lane * 8, h[3].z, h[4].x);
        sts64(sb + OFF_KH + 1536 + lane * 8, h[4].y, h[4].z);
        sts64(sb + OFF_KH + 1792 + lane * 8, h[5].x, h[5].y);
        __syncwarp();
        if (lane == 0) mbar_arrive(bars + 8 * BAR_KH);
      }
      q_issue(1);
      const uint32_t rb = mapa(bars, lane & 1);
      nb_sync(NB_OREADY, 288);
      if (lane == 0) {
        asm volatile("cp.async.bulk.global.shared::cta.bulk_group [%0], [%1], %2;\n" ::"l"(g_o + (size_t)cta * 16384),
                     "r"(sb + OFF_OP), "r"(32768) : "memory");
        bulk_commit();
      }
      if (lane < 2) {
#pragma unroll
        for (int i = 0; i < 4; i++) mbar_arrive_cluster(rb + 8 * (BAR_EMPTY2 + i + i / 2));
      }
      if (lane == 0) {
        bulk_wait0();
        st_release(g_flag_o + FS * cta, epoch);
      }
      __syncwarp();
      PROF2(17);
      if (lane < 2) mbar_arrive_cluster(rb + 8 * (BAR_EMPTY2 + 2));
      }
      if (MODE != 1) {
        const __nv_bfloat16* osrc = g_o + (size_t)(rb2 >> 1) * 16 * 16384 + hsel * 8192;
        mbar_wait(bars + 8 * (BAR_EMPTY2 + 1), 0);
        if (elect_one()) {
          if (MODE == 0) {
            asm volatile("cp.async.bulk.shared::cluster.shared::cta.mbarrier::complete_tx::bytes [%0], [%1], %2, [%3];\n"
                         ::"r"(mapa(sb + g2_a(1, hsel), rank ^ 1)), "r"(sb + g2_a(0, hsel)), "r"(16384),
                         "r"(mapa(bars + 8 * (BAR_FULL2 + 1), rank ^ 1)) : "memory");
          } else {
            bulk_load(sb + g2_a(0, hsel), osrc + hp * 16384, 16384, bars + 8 * BAR_FULL2);
            bulk_load(sb + g2_a(1, hsel), osrc + (hp ^ 1) * 16384, 16384, bars + 8 * (BAR_FULL2 + 1));
          }
#pragma unroll
          for (int kb = 1; kb < 3; kb++)
            g2_issue_b(bars + 8 * (BAR_FULL2 + kb), STG2, sb + g2_b(kb, 0), g2_k(kb) * 64, true);
        }
        __syncwarp();
      }
      if (MODE != 2) {
        mbar_wait(bars + 8 * (BAR_Y + 2), 0);
        send_y(0, 4 * XT, 1);
        fence_async_smem();
        __syncwarp();
      }
      if (MODE != 1) {
        int s = 3, k0 = g2_k(3) * 64;
        uint32_t wbar = bars + 8 * (BAR_Y + 2), fb = bars + 8 * (BAR_FULL2 + 3), dst = sb + g2_b(3, rank), ph = MODE ? 1 : 0;
        int whole = 0;
#pragma unroll 1
        for (int kb = 3; kb < 16;) {
          mbar_wait(wbar, ph);
          if (elect_one()) g2_issue_b(fb, STG2, dst, k0, whole);
          __syncwarp();
          kb++;
          if (++s == NS2) { s = 0; ph = kb == 2 * NS2; }
          wbar = bars + 8 * (kb == 4 ? BAR_XFREE : BAR_EMPTY2B + s);
          fb = bars + 8 * (BAR_FULL2 + s);
          dst = sb + g2_b(s, rank);
          k0 = ((hp & 12) ^ kb) * 64;
          whole = s < 3;
          asm volatile("" : "+r"(fb), "+r"(k0), "+r"(whole));
        }
      }
      __syncwarp();
    } else {
      if (MODE != 2) {
      const float dall = __bfloat162float(p.ssm_D[chb * 8 + lr]);
      {
        const int g = lane >> 2, t = lane & 3;
        uint32_t w[2][4];
#pragma unroll
        for (int h = 0; h < 2; h++) {
          const uint2 x = __ldg(reinterpret_cast<const uint2*>(p.shift_k + ((chb & ~1) * 8 + h * 8 + g) * 4));
          w[h][0] = __byte_perm(x.x, x.x, 0x1010);
          w[h][1] = __byte_perm(x.x, x.x, 0x3232);
          w[h][2] = __byte_perm(x.y, x.y, 0x1010);
          w[h][3] = __byte_perm(x.y, x.y, 0x3232);
        }
        auto swz = [](int r) { return (((r & 29) | ((r ^ (r >> 2)) & 2)) << 5) | (r & 16); };
        const uint32_t kring = sb + OFF_X + 4096 + (hw - 1) * 2 * XT, vring = kring + XT;
        const int s0 = rank * 32 + (hw - 1) * 11, s1 = hw == 3 ? rank * 32 + 32 : s0 + 11;
        const size_t goff = (size_t)(s0 * 32 + (lane >> 1)) * DM + (chb & ~1) * 8 + (lane & 1) * 8;
        const __nv_bfloat16* kg = p.k + goff;
        const __nv_bfloat16* vg = p.v + goff;
        const uint32_t d0 = swz(lane >> 1) ^ ((lane & 1) << 4), d1 = swz(16 + (lane >> 1)) ^ ((lane & 1) << 4);
        auto issue = [&](int st) {
          const uint32_t a = kring + ((st & 3) << 10);
          asm volatile("cp.async.cg.shared.global.L2::256B [%0], [%2], 16;\n"
                       "cp.async.cg.shared.global.L2::256B [%1], [%2 + 32768], 16;\n"
                       "cp.async.cg.shared.global.L2::256B [%0 + 8192], [%3], 16;\n"
                       "cp.async.cg.shared.global.L2::256B [%1 + 8192], [%3 + 32768], 16;\n"
                       ::"r"(a + d0), "r"(a + d1), "l"(kg), "l"(vg) : "memory");
          kg += 32 * DM;
          vg += 32 * DM;
          asm volatile("" : "+l"(kg), "+l"(vg));
        };
        const int xa = 8 * (lr >> 1) + 2 * lm + (lr & 1), xb = 8 * (lr >> 1) - 4 + 2 * (lm & 1) + (lr & 1);
        const uint32_t la = swz(xa), lb = swz(xb & 31);
        const int backb = xb < 0 ? 1 : 0;
        const uint32_t ud[2] = {mapa(sb + OFF_X + g * XT + t * 16, 0), mapa(sb + OFF_X + g * XT + t * 16, 1)};
        const uint32_t ub[2] = {mapa(bars + 8 * BAR_U, 0), mapa(bars + 8 * BAR_U, 1)};
        if (tid == 320) prefetch_l2(g_tab + (chb & 63) * 32);
        if (lane == 0) mbar_wait(bars + 8 * (BAR_FULLB + NS1B - 1), 0);
        __syncwarp();
        if (lane >= 24) cp_async16(kring + (((s0 - 1) & 3) << 10) + d1, s0 > 0 ? kg - 16 * DM : kg, s0 > 0 ? 16 : 0);
        issue(s0);
        asm volatile("cp.async.commit_group;\n" ::: "memory");
        issue(s0 + 1);
        asm volatile("cp.async.commit_group;\n" ::: "memory");
        const __nv_bfloat16* hg = p.ssm_k + (size_t)chb * 8 * SEQ + lane * 64;
        uint32_t tn = clock32();
#pragma unroll 1
        for (int st = s0; st < s1; st++) {
          tn += PSTEP;
          while ((int)(clock32() - tn) < 0) __nanosleep(100);
          if (st + 2 < s1) issue(st + 2);
          if (hw == 1 && st - s0 < 8) prefetch_l2(hg);
          hg += SEQ;
          asm volatile("" : "+l"(hg));
          asm volatile("cp.async.commit_group;\n" ::: "memory");
          asm volatile("cp.async.wait_group 2;\n" ::: "memory");
          __syncwarp();
#pragma unroll
          for (int h = 0; h < 2; h++) {
            uint32_t e[6], vv[4], e4[4];
            ldsm4t(e4, kring + ((st & 3) << 10) + (la ^ (h << 4)));
            ldsm2t(e[0], e[1], kring + (((st - backb) & 3) << 10) + (lb ^ (h << 4)));
            ldsm4t(vv, vring + ((st & 3) << 10) + (la ^ (h << 4)));
            e[2] = e4[0]; e[3] = e4[1]; e[4] = e4[2]; e[5] = e4[3];
            uint32_t o[5];
#pragma unroll
            for (int i = 0; i < 5; i++) o[i] = __byte_perm(e[i], e[i + 1], 0x5432);
#pragma unroll
            for (int i = 0; i < 4; i++) {
              uint32_t a = bmul2(o[i], w[h][3]);
              a = bfma2(e[i + 1], w[h][2], a);
              a = bfma2(o[i + 1], w[h][1], a);
              a = bfma2(e[i + 2], w[h][0], a);
              vv[i] = bmul2(a, vv[i]);
            }
            st_async128(ud[h] + (st ^ (g & 1)) * 64, ub[h], vv[0], vv[1], vv[2], vv[3]);
          }
          __syncwarp();
        }
        fence_async_smem();
        PROF(16);
      }
      nb_sync(NB_HELP3, 96);
      if (hw == 1 && elect_one()) {
        mbar_expect_tx(bars + 8 * BAR_H, 8 * 4096 + 6144);
#pragma unroll 1
        for (int c = 0; c < 8; c++)
          bulk_load(sb + OFF_X + c * XT + 4096, p.ssm_k + (size_t)(chb * 8 + c) * SEQ, 4096, bars + 8 * BAR_H);
        bulk_load(sb + OFF_T16, g_tab, 2048, bars + 8 * BAR_H);
        bulk_load(sb + OFF_T32, g_tab + 512, 4096, bars + 8 * BAR_H);
      }
      __syncwarp();
      {
        if (hw == 3) {
          const char* wo = (const char*)p.wo + chb * 16384 + lane * 128;
#pragma unroll
          for (int i = 0; i < 4; i++) prefetch_l2(wo + i * 4096);
        }
        const int ck = 16 * (lane >> 4) + 2 * lr + (((lane >> 3) ^ (lane >> 2)) & 1);
        const uint32_t xo = (ck >> 1) * 64, xs = ((ck & 1) ^ (lr >> 1)) << 4;
#pragma unroll 1
        for (int job = hw - 1; job < 16; job += 3) {
          const int c = job & 7;
          uint4 a[8];
          float dv = __shfl_sync(0xffffffffu, dall, c);
          if (job < 8 || lane) dv = 0.f;
          const uint32_t xt = sb + OFF_X + c * XT + (job >> 3) * 4096;
          mbar_wait(bars + 8 * (job < 8 ? BAR_U : BAR_H), 0);
#pragma unroll
          for (int i = 0; i < 8; i++) a[i] = lds128(xt + i * 512 + ((ck ^ (job < 8 ? (c & 1) << 2 : 0)) << 4));
          dv += bf_lo(a[0].x);
          uint32_t m[2] = {bmaxabs2(pack_bf16(dv, 0.f), bmaxabs2(a[0].x, a[0].y)), bmaxabs2(a[0].z, a[0].w)};
#pragma unroll
          for (int i = 1; i < 8; i++) {
            m[0] = bmaxabs2(bmaxabs2(m[0], a[i].x), a[i].y);
            m[1] = bmaxabs2(bmaxabs2(m[1], a[i].z), a[i].w);
          }
          m[0] = bmaxabs2(m[0], m[1]);
          const int f = max(252 - (int)(__reduce_max_sync(0xffffffffu, max(m[0] & 0x7fffu, (m[0] >> 16) & 0x7fffu)) >> 7), 1);
          if (lane == 0) asm volatile("st.shared.u32 [%0], %1;\n" ::"r"(sb + OFF_EX + job * 4), "r"(f) : "memory");
          if (f < 113) {
#pragma unroll
            for (int i = 0; i < 8; i++)
              a[i] = make_uint4(bmul2(a[i].x, f * 0x00800080u), bmul2(a[i].y, f * 0x00800080u), bmul2(a[i].z, f * 0x00800080u),
                                bmul2(a[i].w, f * 0x00800080u));
          }
          const uint32_t mul = (f < 113 ? 15 : f - 112) * 0x00800080u;
          auto cv = [&](uint32_t x) {
            x = bmul2(x, mul);
            return (x & 0x0fff0fffu) * 7 + x;
          };
          const uint32_t dst = xt + xo;
#pragma unroll
          for (int i = 0; i < 8; i++)
            sts128(dst + (i >> 2) * 2048 + (i & 1) * 1024 + (xs ^ ((i & 2) << 4)),
                   i ? cv(a[i].x) : __byte_perm(pack_f16(dv * __uint_as_float(f << 23), 0.f), cv(a[i].x), 0x7610), cv(a[i].y),
                   cv(a[i].z), cv(a[i].w));
        }
        fence_async_smem();
        __syncwarp();
        if (lane == 0) mbar_arrive(bars + 8 * BAR_X);
        PROF(19);
      }
      if (hw < 3) {
#pragma unroll 1
        for (int n = 0; n < SPIN_LIMIT && !mbar_try(bars + 8 * (BAR_Y + hw - 1), 0); n++) __nanosleep(100);
        send_y((hw - 1) * 4 * XT, 2 * XT, 0);
        __syncwarp();
        if (lane == 0) mbar_arrive(bars + 8 * (BAR_Y + 2));
        PROF(32);
        const int c8 = 2 * lm + (lr & 1), src = (lr >> 1) & 1;
        uint32_t fa = sb + OFF_X + c8 * XT + rank * 4096 + (src == rank ? 0 : 1024) + (hw - 1) * 512;
        const uint32_t fx = ((lr >> 2) ^ ((lr & 3) << 1)) << 4;
        uint32_t qa = sb + OFF_Q0 + (hw - 1) * 8192 + (lane >> 3) * 128 + (lane & 2) * 32 + (lane & 4) * 8 + (lane & 1) * 16;
        uint4* og = reinterpret_cast<uint4*>(p.out + (size_t)(rank * 512 + (hw - 1) * 256 + (lane & 2) * 4 + (lane >> 2)) * (2 * DM) +
                                             (chb & ~1) * 8 + (lane & 1) * 8);
        mbar_wait(bars + 8 * BAR_Q, 0);
        uint32_t tn = 0;
        const uint32_t pace = hw == 2 ? FPACE2 : FPACE;
#pragma unroll 1
        for (int j = 0; j < 4; j++) {
          if (!(j & 1)) {
            mbar_wait(bars + 8 * (BAR_LAND + (j >> 1)), 0);
            tn = clock32() + (j ? 0 : (hw - 1) * (FPACE / 2));
            PROF2(33 + j * 2);
          }
#pragma unroll
          for (int i = 0; i < 8; i++) {
            if (i == 2 && j == 0 && hw == 2) {
              mbar_wait(bars + 8 * (BAR_Y + 3), 0);
              send_y(2 * XT, 4 * XT, 1);
              fence_async_smem();
              __syncwarp();
              if (lane == 0) mbar_arrive(bars + 8 * BAR_XFREE);
              tn = clock32();
            }
            uint32_t y[4];
            const uint4 q = lds128(qa + i * 512);
            ldsm4t(y, fa + (i >> 2) * 128 + (fx ^ ((i & 3) << 5) ^ ((i >> 2) << 4)));
            while ((int)(clock32() - tn) < 0) __nanosleep(50);
            tn += j == 3 ? FPACE3 : pace;
            og[i * 16 * (2 * DM / 8)] = make_uint4(bmul2(q.x, y[0]), bmul2(q.y, y[1]), bmul2(q.z, y[2]), bmul2(q.w, y[3]));
          }
          qa += j & 1 ? OFF_Q1 - OFF_Q0 - 4096 : 4096;
          fa += j & 1 ? 2048 - 256 : 256;
          og += (j & 1 ? 1024 - 128 : 128) * (2 * DM / 8);
        }
        PROF(22);
      }
      }
      if (MODE != 1 && hw == 3) {
        const uint32_t epoch = ld_relaxed(g_flag_o + FS * cta) + 1;
        if (MODE == 0) nb_sync(NB_G1END, 288);
        if (elect_one()) g2_issue_b(bars + 8 * BAR_FULL2, MODE ? STG2 : STG2 / 2, sb + g2_b(0, 0), hp * 64, true);
        __syncwarp();
        const __nv_bfloat16* osrc = g_o + (size_t)(rb2 >> 1) * 16 * 16384 + hsel * 8192;
        if (MODE == 0) __nanosleep(1500);
        mbar_wait(bars + 8 * (BAR_EMPTY2 + 2), 0);
        const uint32_t* flag = g_flag_o + FS * ((rb2 >> 1) * 16 + g2_k(lane & 15));
        uint32_t ready = MODE == 0 ? 0u : ~0u;
        int s = 1, ph = 0;
#pragma unroll 1
        for (int kb = 2; kb < 16; kb++) {
          if (++s == NS2) { s = 0; ph ^= 1; }
          uint32_t fb = bars + 8 * (BAR_FULL2 + s), dst = sb + g2_a(s, hsel) + rank * 8192;
          const __nv_bfloat16* src = osrc + rank * 4096 + (uint32_t)g2_k(kb) * 16384;
          asm volatile("" : "+r"(fb), "+r"(dst), "+l"(src));
          if (!(ready >> kb & 1)) {
#pragma unroll 1
            for (int n = 0; n < SPIN_LIMIT && !(ready >> kb & 1); n++)
              ready = __ballot_sync(0xffffffffu, ld_acquire(flag) == epoch);
            fence_async_all();
          }
          if (kb == 2) PROF(21);
          if (MODE == 0 && kb == 4 && rank == 1) mbar_wait(bars + 8 * BAR_TAB, 0);
          mbar_wait(fb + 8 * (BAR_EMPTY2 - BAR_FULL2), ph);
          if (elect_one()) {
            asm volatile(
                "cp.async.bulk.shared::cluster.global.mbarrier::complete_tx::bytes.multicast::cluster [%0], [%1], %2, [%3], %4;\n"
                ::"r"(dst), "l"(src), "r"(8192), "r"(fb), "h"((uint16_t)3) : "memory");
          }
          __syncwarp();
        }
      }
    }
    cluster_sync_all();
    PROF_DUMP();
  } else {
    asm volatile("barrier.cluster.arrive.relaxed.aligned;\n" ::: "memory");
    asm volatile("setmaxnreg.inc.sync.aligned.u32 %0;\n" :: "n"(REG_MATH));
    if (halo_cta || MODE == 2) asm volatile("barrier.cluster.wait.aligned;\n" ::: "memory");
    if (warp == 0) PROF2(26);
    const int wg = warp >> 2;
    const int wtid = tid & 127;
    const bool signaller = (wtid == 0) || (wtid == 32);
    const uint32_t rbars = mapa(bars, wtid >> 5 & 1);

    if (halo_cta) {
      const uint32_t epoch = ld_relaxed(g_flag_o + FS * (16 + blockIdx.x * 4)) + 1;
      float acc0[64], acc1[64];
      int s = wg, ph = 0;
#pragma unroll 1
      for (int kb = 0; kb < 16; kb++) {
        mbar_wait(bars + 8 * (BAR_FULLB + s), ph);
        const uint32_t st = sb + s * STGH;
        const uint64_t da = mkdesc(st, 16, 1024, 1);
        const uint64_t db = mkdesc(st + 8192, 8192, 1024, 1);
        wg_fence();
#pragma unroll
        for (int kk = 0; kk < 4; kk++) {
          wgmma_n128(acc0, da + 2 * kk, db + 128 * kk, kb + kk);
          wgmma_n128(acc1, da + 2 * kk, db + 1024 + 128 * kk, kb + kk);
        }
        wg_commit();
        wg_wait<0>();
        if (kb == 15) PROF(37);
        if (wtid < 2) mbar_arrive(bars + 8 * (BAR_EMPTYB + s));
        if ((s += 2) >= NS1B) { s -= NS1B; ph ^= 1; }
      }
      fence_regs(acc0);
      fence_regs(acc1);
      if ((warp & 3) != 3) {
        auto put = [&](const float (&acc)[64], int hp0) {
#pragma unroll
          for (int n = 0; n < 4; n++) {
            uint32_t x[8];
#pragma unroll
            for (int c = 0; c < 8; c++) {
              x[c] = pack_bf16(acc[32 * (n >> 1) + 4 * c + 2 * (n & 1)], acc[32 * (n >> 1) + 4 * c + 2 * (n & 1) + 1]);
              if (wg) x[c] = movm(x[c]);
            }
            uint4* dst = g_halo + (((n & 1) * 4 + (warp & 3) + 1) * 16 + blockIdx.x * 4 + hp0 + (n >> 1)) * 192 + wg * 96 + lane;
            st_b128(dst, x[0], x[1], x[2], epoch);
            st_b128(dst + 32, x[3], x[4], x[5], epoch);
            st_b128(dst + 64, x[6], x[7], 0, epoch);
          }
        };
        put(acc0, 0);
        put(acc1, 2);
      }
      PROF(36);
      cluster_sync_all();
      return;
    }

    float acc[64];
    const uint32_t g2rel = wtid ? mapa(bars, rank) + 8 * BAR_EMPTY2B : mapa(bars, wg) + 8 * BAR_EMPTY2;
    uint32_t g2a = (uint32_t)mkdesc(sb + wg * 8192, 16, 0, 0), g2b = (uint32_t)mkdesc(sb, 8192, 0, 0);
    auto g2_block = [&](bool first, int s, int ph) {
      mbar_wait(bars + 8 * (BAR_FULL2 + s), ph);
      const uint32_t da = g2a + (g2_a(s, hsel) >> 4), db = g2b + (g2_b(s, rank) >> 4), dc = db + (g2_bk(s) >> 4);
      wg_fence();
      if (first) wgmma_n128z(acc, da, db);
      else wgmma_n128a(acc, da, db);
      wgmma_n128a(acc, da + 2, db + 128);
      wgmma_n128a(acc, da + 4, dc);
      wgmma_n128a(acc, da + 6, dc + 128);
      wg_commit();
    };
    if (MODE != 2) {
    uint32_t a1[2][4], sc[2];
    C2 t[2];
    {
      float acc0[96], acc1[96];
      int sa = 0, pha = 0;
      uint64_t db0 = mkdesc(sb + OFF_1B, 4096, 1024, 1);
      const uint64_t da0 = mkdesc(sb + wg * 16384, 16, 2048, 1);
      const bool sigb = wtid == 64;
      uint32_t rela = 0;
#pragma unroll 1
      for (int r = 0; r < 3; r++) {
#pragma unroll
        for (int i = 0; i < 2 * NS1B; i++) {
          if (i == 2 * NS1B - 1 && r == 2) break;
          const uint64_t da = da0 + sa * (STG1A >> 4) + (i & 1) * 4, db = db0 + (i % NS1B) * (STG1B >> 4);
          if (i || r) {
            if (!(i & 1)) mbar_wait(bars + 8 * (BAR_FULLA + sa), pha);
            mbar_wait(bars + 8 * (BAR_FULLB + i % NS1B), i / NS1B);
          } else {
            asm volatile("cp.async.wait_group 0;\n" ::: "memory");
            fence_async_smem();
            nb_sync(NB_FIRST, 256);
            PROF(0 + wg);
          }
          wg_fence();
          wgmma_n192(acc0, da + 64, db, i ? 1 : r);
          wgmma_n192(acc1, da, db, i ? 1 : r);
          wgmma_n192(acc0, da + 66, db + 128, 1);
          wgmma_n192(acc1, da + 2, db + 128, 1);
          wg_commit();
          wg_wait<1>();
          if (i || r) {
            if (sigb) mbar_arrive(bars + 8 * (BAR_EMPTYB + (i + NS1B - 1) % NS1B));
            if (!(i & 1) && signaller) mbar_arrive_cluster(rela);
          } else {
            asm volatile("barrier.cluster.wait.aligned;\n" ::: "memory");
          }
          if (i & 1) {
            rela = rbars + 8 * (BAR_EMPTYA + sa);
            if (++sa == NS1A) { sa = 0; pha ^= 1; }
          }
        }
        db0 += p.zero;
      }
      const int lr = lane & 7, lm = lane >> 3;
      const bool le0 = 2 * (lane & 3) <= (lane >> 2), le1 = 2 * (lane & 3) + 1 <= (lane >> 2);
      const uint32_t maskLE = (le0 ? 0x0000FFFFu : 0u) | (le1 ? 0xFFFF0000u : 0u);
      uint32_t q[4][8], k[5][8], vt[5][8];
      {
        static_assert(15 % NS1A == 0 && 30 % NS1B == 0, "slots of the last k blocks");
        const uint64_t da = mkdesc(sb + wg * 16384, 16, 2048, 1);
        const uint64_t db = mkdesc(sb + OFF_1B, 4096, 1024, 1);
        auto last = [&](float (&acc)[96], int ro, int i0, int i1) {
#pragma unroll
          for (int i = i0; i < i1; i++)
            wgmma_n192(acc, da + ro + (i < 2 ? 2 * (STG1A >> 4) + 4 + 2 * i : 2 * i - 4),
                       db + (i < 2 ? 4 : (i >> 1) - 1) * (STG1B >> 4) + (i & 1) * 128, 1);
          wg_commit();
        };
        mbar_wait(bars + 8 * (BAR_FULLB + 4), 1);
        wg_fence();
        last(acc0, 64, 0, 2);
        asm volatile("ld.volatile.global.v4.u32 {%0,%1,%2,%3}, [%4];\n"
                     : "=r"(t[0].r), "=r"(t[1].r), "=r"(t[0].i), "=r"(t[1].i) : "l"(g_tab + 1536 + wtid * 4) : "memory");
        mbar_wait(bars + 8 * BAR_FULLA, 1);
        mbar_wait(bars + 8 * BAR_FULLB, 0);
        mbar_wait(bars + 8 * (BAR_FULLB + 1), 0);
        wg_fence();
        last(acc0, 64, 2, 6);
        wg_wait<2>();
        if (sigb) mbar_arrive(bars + 8 * (BAR_EMPTYB + 3));
        mbar_wait(bars + 8 * (BAR_EMPTYA + 1), 0);
        mbar_wait(bars + 8 * BAR_H, 0);
        wg_fence();
        last(acc1, 0, 0, LN);
        wg_wait<1>();
        fence_regs(acc0);
        PROFA(45, 0);
        attn_pack<8, 1, false>(acc0, k[4]);
        attn_pack<16, 1, true>(acc0, vt[4]);
        const uint32_t kh = sb + (warp == 7 ? OFF_1B + 2 * STG1B : OFF_KH + (warp + 1) * 2048) + lane * 16;
        sts128(kh, k[4][0], k[4][1], k[4][2], k[4][3]);
        sts128(kh + 512, k[4][4], k[4][5], k[4][6], k[4][7]);
#pragma unroll
        for (int i = 0; i < 4; i++) sts64(kh - lane * 8 + 1024 + 256 * i, vt[4][2 * i], vt[4][2 * i + 1]);
        __syncwarp();
        if (lane == 0) mbar_arrive(bars + 8 * (BAR_KH + 1 + warp));
        if (LN < 6) last(acc1, 0, LN, 6);
        attn_pack<0, 0, false>(acc0, q[1]);
        attn_pack<0, 1, false>(acc0, q[3]);
        attn_pack<8, 0, false>(acc0, k[2]);
        attn_pack<16, 0, true>(acc0, vt[2]);
        uint32_t z = p.zero;
#pragma unroll
        for (int i = 0; i < 8; i++) z &= q[1][i] & q[3][i];
#pragma unroll
        for (int i = 0; i < 8; i += 2) z &= k[2][i] & k[2][i + 1];
        mbar_wait(bars + 8 * (BAR_KH + warp) + z, 0);
        {
          const uint32_t kh = sb + OFF_KH + warp * 2048 + lane * 16;
#pragma unroll
          for (int i = 0; i < 2; i++) {
            const uint4 t = lds128(kh + 512 * i);
            k[0][4 * i] = t.x; k[0][4 * i + 1] = t.y; k[0][4 * i + 2] = t.z; k[0][4 * i + 3] = t.w;
          }
#pragma unroll
          for (int i = 0; i < 4; i++) {
            const uint2 t = lds64(kh - lane * 8 + 1024 + 256 * i);
            vt[0][2 * i] = t.x; vt[0][2 * i + 1] = t.y;
          }
        }
        wg_wait<0>();
        fence_regs(acc1);
        if (MODE == 0) nb_arrive(NB_G1END, 288);
      }
      PROF(2 + wg);
      attn_pack<0, 0, false>(acc1, q[0]);
      attn_pack<0, 1, false>(acc1, q[2]);
      attn_pack<8, 0, false>(acc1, k[1]);
      attn_pack<8, 1, false>(acc1, k[3]);
      {
        float x[8][2];
        uint32_t pp[8];
        const bool first = warp == 0 && gidx == 0;
#pragma unroll
        for (int hd = 0; hd < 2; hd++) {
#pragma unroll
          for (int j = 0; j < 4; j += 2) {
            float s0[4], s1[4], s2[4];
            attn_qk(s2, q[j], q[j + 1], k[j + 2], 4 * hd);
            attn_qk(s1, q[j], q[j + 1], k[j + 1], 4 * hd);
            attn_qk(s0, q[j], q[j + 1], k[j], 4 * hd);
            if (j == 0 && first) s0[0] = s0[1] = -1e9f / 0.17677669529663687f;
            x[2 * j + hd][0] = le0 ? s1[0] : s0[0];
            x[2 * j + hd][1] = le1 ? s1[1] : s0[1];
            x[2 * j + 2 + hd][0] = le0 ? s2[2] : s1[2];
            x[2 * j + 2 + hd][1] = le1 ? s2[3] : s1[3];
          }
        }
        PROFA(40, __float_as_uint(x[1][0] + x[7][1]));
        attn_pack<16, 0, true>(acc1, vt[1]);
        attn_pack<16, 1, true>(acc1, vt[3]);
        quad_softmax<8>(x, pp);
        PROFA(41, pp[1] + pp[7]);
        ldsm4(a1[0], sb + OFF_T32 + (warp & 3) * 1024 + lane * 16);
        ldsm4(a1[1], sb + OFF_T32 + 512 + (warp & 3) * 1024 + lane * 16);
        const uint32_t obase = sb + OFF_OP + (warp * 32 + lr) * 128;
#pragma unroll
        for (int n = 0; n < 8; n++) {
          const uint32_t dst = obase + (n >> 1) * 1024 + (((4 * (n & 1) + lm) ^ lr) << 4);
          if (n & 2) attn_pv<true>(dst, vt[n >> 1], vt[(n >> 1) + 1], 4 * (n & 1), pp[n], maskLE);
          else attn_pv<false>(dst, vt[n >> 1], vt[(n >> 1) + 1], 4 * (n & 1), pp[n], maskLE);
        }
      }
      PROFA(42, 0);
    }

    {
      const int w = warp & 3;
      const int lr = lane & 7, lm = lane >> 3;
      const uint32_t xb = sb + OFF_X + wg * 4 * XT;
      auto uo = [](int c) { return (c & 1) * 2 * XT + (c >> 1) * 2048; };
      const uint64_t dc2 = mkdesc(sb + OFF_T16, 512, 128, 0), dc3 = mkdesc(sb + OFF_T16, 128, 512, 0);
      const uint64_t dc4 = mkdesc(sb + OFF_T32, 128, 256, 0);
      const uint64_t dx = mkdesc(xb, 4096, 512, 2), dz = mkdesc(xb, 4096, 256, 3);
      const uint32_t zs = xb + (w * 16 + (lm & 1) * 8 + lr) * 32 + (((lm >> 1) ^ (lr >> 2)) << 4);
      const uint32_t ys = xb + w * 4096 + (lm >> 1) * 256 + ((lr * 32 + (((lm & 1) ^ (lr >> 2)) << 4)) ^ (rank << 6) ^ ((w & 2) << 4));
      const bool own = (w & 1) == rank;
      const uint32_t ybar = mapa(bars, own ? rank ^ 1 : rank) + 8 * BAR_Y;
      uint32_t d[2][32], pa[2][4][2][4], e[4][4][8], ya[2][2][2][4], v[2][2][8];
      C2 s1[2][2][2];
      float o[2][16];
      auto rows = [&](int c) {
        fft_rows(d[c & 1], a1, dx + (uo(c) >> 4));
        wg_commit();
      };
      auto cols = [&](int c) {
        const int s = c & 1;
        fence_regs(d[s]);
#pragma unroll
        for (int i = 0; i < 16; i++) {
          const C2 z = crot(C2{d[s][2 * i], d[s][2 * i + 1]}, t[i & 1]);
          pa[s][i >> 2][i & 1][(i >> 1) & 1] = z.r;
          pa[s][i >> 2][i & 1][2 + ((i >> 1) & 1)] = z.i;
        }
        wg_fence();
#pragma unroll
        for (int i = 0; i < 4; i++) fft_cols<0>(e[c][i], pa[s][i], dc2);
        wg_commit();
      };
      auto prod = [&](int c, int n) {
        const int s = c & 1;
        fence_regs(e[c][2 * n]);
        fence_regs(e[c][2 * n + 1]);
#pragma unroll
        for (int j = 0; j < 2; j++) {
          const C2 u0 = cget(e[s][2 * n], j, 0), u1 = cget(e[s][2 * n], j, 1);
          const C2 h0 = cget(e[s][2 * n + 1], j, 0), h1 = cget(e[s][2 * n + 1], j, 1);
          C2 y0, y1;
          if (c < 2) {
            y0 = cmul(h0, u0);
            s1[s][n][j] = cfma(h0, u1, cmul(h1, u0));
            y1 = C2{hadd2(s1[s][n][j].r, y0.i), hadd2(s1[s][n][j].i, hneg2(y0.r))};
          } else {
            const C2 u2 = cget(e[c][2 * n], j, 0), u3 = cget(e[c][2 * n], j, 1);
            const C2 h2 = cget(e[c][2 * n + 1], j, 0), h3 = cget(e[c][2 * n + 1], j, 1);
            const C2 s2 = cfma(h0, u2, cfma(h2, u0, cmul(h1, u1)));
            y0 = C2{hadd2(s2.r, s1[s][n][j].i), hadd2(s2.i, hneg2(s1[s][n][j].r))};
            y1 = cfma(h0, u3, cfma(h1, u2, cfma(h2, u1, cfma(h3, u0, C2{s2.i, hneg2(s2.r)}))));
          }
          ya[s][n][j][0] = y0.r;
          ya[s][n][j][1] = y1.r;
          ya[s][n][j][2] = y0.i;
          ya[s][n][j][3] = y1.i;
        }
      };
      auto icols = [&](int c) {
        wg_fence();
        fft_cols<1>(v[c & 1][0], ya[c & 1][0], dc3);
        fft_cols<1>(v[c & 1][1], ya[c & 1][1], dc3);
        wg_commit();
      };
      auto stage = [&](int c) {
        const int s = c & 1;
        fence_regs(v[s][0]);
        fence_regs(v[s][1]);
#pragma unroll
        for (int b = 0; b < 4; b++) {
          const C2 x0 = cget(v[s][b >> 1], 0, b & 1), x1 = cget(v[s][b >> 1], 1, b & 1);
          const C2 z0 = crot(C2{x0.i, x0.r}, t[0]), z1 = crot(C2{x1.i, x1.r}, t[1]);
          stsm4(zs + uo(c) + b * 4096, z0.i, z0.r, z1.i, z1.r);
        }
      };
      auto back = [&](int c) {
        fft_back(o[c & 1], dz + (uo(c) >> 4), dc4);
        wg_commit();
      };
      auto out = [&](int c) {
        float (&r)[16] = o[c & 1];
        fence_regs(r);
#pragma unroll
        for (int i = 0; i < 16; i += 8)
          stsm4t(ys + uo(c) + 64 * i, bmul2(pack_bf16(r[i], r[i + 1]), sc[c & 1]), bmul2(pack_bf16(r[i + 2], r[i + 3]), sc[c & 1]),
                 bmul2(pack_bf16(r[i + 4], r[i + 5]), sc[c & 1]), bmul2(pack_bf16(r[i + 6], r[i + 7]), sc[c & 1]));
      };
      auto signal = [&](int yb, int land) {
        __syncwarp();
        if (lane == 0) {
          mbar_arrive_cluster(ybar + 8 * yb);
          if (own && land >= 0) mbar_arrive(bars + 8 * (BAR_LAND + land));
        }
      };
      mbar_wait(bars + 8 * BAR_X, 0);
      wg_fence();
      rows(0);
      rows(1);
      fence_async_smem();
      nb_arrive(NB_OREADY, 288);
#pragma unroll
      for (int i = 0; i < 2; i++) {
        const uint32_t ex = sb + OFF_EX + wg * 16 + (w & 2) * 2 + 8 * i;
        sc[i] = min(max(381 - (int)lds32(ex) - (int)lds32(ex + 32), 1), 254) * 0x00800080u;
      }
      PROF(34 + wg);
      wg_wait<1>();
      cols(0);
      wg_wait<1>();
      cols(1);
      rows(2);
      nb_sync(NB_CONV + wg, 128);
      wg_wait<2>();
      prod(0, 0);
      prod(0, 1);
      icols(0);
      wg_wait<2>();
      prod(1, 0);
      prod(1, 1);
      icols(1);
      PROF3(40 + 10 * wg);
      wg_wait<1>();
      stage(0);
      wg_wait<0>();
      stage(1);
      fence_async_smem();
      cols(2);
      PROF3(41 + 10 * wg);
      nb_sync(NB_CONV + wg, 128);
      back(0);
      back(1);
      wg_wait<2>();
      prod(2, 0);
      wg_fence();
      rows(3);
      wg_wait<1>();
      out(0);
      out(1);
      signal(wg, 0);
      PROF3(42 + 10 * wg);
      prod(2, 1);
      icols(2);
      wg_wait<1>();
      cols(3);
      PROF3(43 + 10 * wg);
      wg_wait<1>();
      stage(2);
      fence_async_smem();
      wg_wait<0>();
      prod(3, 0);
      nb_sync(NB_CONV + wg, 128);
      wg_fence();
      back(2);
      prod(3, 1);
      icols(3);
      PROF3(44 + 10 * wg);
      wg_wait<1>();
      out(2);
      signal(2, -1);
      wg_wait<0>();
      stage(3);
      PROF3(45 + 10 * wg);
      fence_async_smem();
      nb_sync(NB_FIRST, 256);
      wg_fence();
      back(3);
      constexpr int G = MODE == 0;
      if (G) {
        mbar_wait(bars + 8 * (BAR_EMPTY2 + 4), 0);
        g2_block(true, 0, 0);
      }
      wg_wait<G>();
      if (lane == 0) mbar_arrive_cluster(mapa(bars, 1) + 8 * BAR_TAB);
      out(3);
      signal(3, 1);
      PROF(6 + wg);
    }
    }

    if (MODE != 1) {
      if (MODE == 2) g2_block(true, 0, 0);
      const int lr = lane & 7, lm = lane >> 3;
      const uint32_t wb = sb + g2_a(1, 0) + warp * 2048;
      const int orow = (rb2 & 7) * 128 + warp * 16;
      uint4* og = reinterpret_cast<uint4*>(p.out + (size_t)(2 * (orow + lm) + (rb2 >> 3)) * (2 * DM) + DM + cb2 * 128 + lr * 8);
      uint32_t wst = wb + (lr + 8 * (lm & 1)) * 128, wsx = ((lm >> 1) ^ lr) << 4, wld = wb + lm * 128, wlx = (lr ^ lm) << 4;
      asm volatile("" : "+l"(og), "+r"(wst), "+r"(wsx), "+r"(wld), "+r"(wlx));
#pragma unroll 1
      for (int r = 0; r < 3; r++) {
        const bool hold = r == 2 && wg != LEADWG;
        if (hold) {
          wg_wait<0>();
          if (signaller) mbar_arrive_cluster(g2rel);
          nb_sync(NB_LEAD, 256);
        }
#pragma unroll
        for (int i = 1; i <= NS2; i++) {
          g2_block(false, i % NS2, (r & 1) ^ (i == NS2));
          if (warp == LEADWG * 4) PROF2(40 + 5 * r + i);
          if (i == 1 ? !hold : r < 2) {
            wg_wait<1>();
            if (signaller) mbar_arrive_cluster(g2rel + 8 * (i - 1));
          }
        }
        if (r == 0) PROF(8 + wg);
        g2a += p.zero;
        g2b += p.zero;
      }
      if (wg == LEADWG) nb_arrive(NB_LEAD, 256);
      asm volatile("barrier.cluster.arrive.relaxed.aligned;\n" ::: "memory");
      wg_wait<0>();
      fence_regs(acc);
      PROF(10 + wg);
#pragma unroll
      for (int h = 0; h < 2; h++) {
        const uint32_t b = h * (g2_a(3, 0) - g2_a(1, 0));
#pragma unroll
        for (int j = 8 * h; j < 8 * h + 8; j += 2)
          stsm4(wst + b + (wsx ^ ((j & 7) << 4)), pack_bf16(acc[4 * j], acc[4 * j + 1]),
                pack_bf16(acc[4 * j + 2], acc[4 * j + 3]), pack_bf16(acc[4 * j + 4], acc[4 * j + 5]),
                pack_bf16(acc[4 * j + 6], acc[4 * j + 7]));
        if (wg == LEADWG) {
          fence_async_smem();
          __syncwarp();
          if (elect_one()) {
            tma_store_3d(&tmOb, wb + b, DM + cb2 * 128 + h * 64, rb2 >> 3, orow);
            bulk_commit();
          }
        } else {
          __syncwarp();
          uint4 v[4];
#pragma unroll
          for (int i = 0; i < 4; i++) v[i] = lds128(wld + b + i * 512 + (wlx ^ ((i & 1) << 6)));
#pragma unroll
          for (int i = 0; i < 4; i++)
            asm volatile("st.global.v4.u32 [%0], {%1,%2,%3,%4};\n" ::"l"(og + i * 8 * (2 * DM / 8) + h * 8), "r"(v[i].x),
                         "r"(v[i].y), "r"(v[i].z), "r"(v[i].w) : "memory");
        }
      }
      PROF(12 + wg);
      bulk_wait0();
    } else {
      asm volatile("barrier.cluster.arrive.relaxed.aligned;\n" ::: "memory");
    }
    asm volatile("barrier.cluster.wait.aligned;\n" ::: "memory");
  }
}

typedef CUresult (*EncodeFn)(CUtensorMap*, CUtensorMapDataType, cuuint32_t, void*, const cuuint64_t*, const cuuint64_t*,
                             const cuuint32_t*, const cuuint32_t*, CUtensorMapInterleave, CUtensorMapSwizzle,
                             CUtensorMapL2promotion, CUtensorMapFloatOOBfill);

void make_map(EncodeFn enc, CUtensorMap* tm, const void* base, int rank, const cuuint64_t* dims, const cuuint64_t* strides,
              const cuuint32_t* box, CUtensorMapSwizzle swz) {
  cuuint32_t es[5] = {1, 1, 1, 1, 1};
  enc(tm, CU_TENSOR_MAP_DATA_TYPE_BFLOAT16, rank, const_cast<void*>(base), dims, strides, box, es,
      CU_TENSOR_MAP_INTERLEAVE_NONE, swz, CU_TENSOR_MAP_L2_PROMOTION_L2_256B, CU_TENSOR_MAP_FLOAT_OOB_FILL_NONE);
}

}

extern "C" void kernel_launch(void* const* d_in, const int* in_sizes, int n_in, void* d_out, int out_size) {
  static EncodeFn enc = nullptr;
  static bool coresident = true;
  if (!enc) {
    void* fn = nullptr;
    cudaDriverEntryPointQueryResult qr;
    cudaGetDriverEntryPoint("cuTensorMapEncodeTiled", &fn, cudaEnableDefault, &qr);
    enc = (EncodeFn)fn;
    cudaFuncSetAttribute(fused_kernel<0>, cudaFuncAttributeMaxDynamicSharedMemorySize, SMEM_BYTES);
    cudaFuncSetAttribute(fused_kernel<1>, cudaFuncAttributeMaxDynamicSharedMemorySize, SMEM_BYTES);
    cudaFuncSetAttribute(fused_kernel<2>, cudaFuncAttributeMaxDynamicSharedMemorySize, SMEM_BYTES);
    cudaLaunchConfig_t cfg = {};
    cfg.gridDim = dim3(NCTA);
    cfg.blockDim = dim3(NTHREADS);
    cfg.dynamicSmemBytes = SMEM_BYTES;
    cudaLaunchAttribute at;
    at.id = cudaLaunchAttributeClusterDimension;
    at.val.clusterDim.x = 2;
    at.val.clusterDim.y = 1;
    at.val.clusterDim.z = 1;
    cfg.attrs = &at;
    cfg.numAttrs = 1;
    int nclusters = 0;
    if (cudaOccupancyMaxActiveClusters(&nclusters, fused_kernel<0>, &cfg) == cudaSuccess) coresident = nclusters >= NCTA / 2;
    (void)cudaGetLastError();
  }
  CUtensorMap tmX, tmW, tmWo, tmWp, tmQ, tmOb, tmXh, tmWh;
  {
    cuuint64_t dims[3] = {1024, 2, 1024};
    cuuint64_t str[2] = {2048, 4096};
    cuuint32_t box[3] = {64, 1, 128};
    make_map(enc, &tmX, d_in[6], 3, dims, str, box, CU_TENSOR_MAP_SWIZZLE_128B);
  }
  {
    cuuint64_t dims[3] = {1024, 1024, 3};
    cuuint64_t str[2] = {6144, 2048};
    cuuint32_t box[3] = {64, 32, 3};
    make_map(enc, &tmW, d_in[7], 3, dims, str, box, CU_TENSOR_MAP_SWIZZLE_128B);
  }
  {
    cuuint64_t dims[3] = {64, 1024, 16};
    cuuint64_t str[2] = {2048, 128};
    cuuint32_t box[3] = {64, 64, 2};
    cuuint32_t piece[3] = {64, 32, 1};
    make_map(enc, &tmWo, d_in[8], 3, dims, str, box, CU_TENSOR_MAP_SWIZZLE_128B);
    make_map(enc, &tmWp, d_in[8], 3, dims, str, piece, CU_TENSOR_MAP_SWIZZLE_128B);
  }
  {
    cuuint64_t dims[5] = {1024, 2, 2, 4, 128};
    cuuint64_t str[4] = {2048, 8 * 2048, 2 * 2048, 16 * 2048};
    cuuint32_t box[5] = {16, 2, 2, 4, 32};
    make_map(enc, &tmQ, d_in[0], 5, dims, str, box, CU_TENSOR_MAP_SWIZZLE_NONE);
  }
  {
    cuuint64_t dims[3] = {2048, 2, 1024};
    cuuint64_t str[2] = {4096, 8192};
    cuuint32_t box[3] = {64, 1, 16};
    make_map(enc, &tmOb, d_out, 3, dims, str, box, CU_TENSOR_MAP_SWIZZLE_128B);
  }
  {
    cuuint64_t dims[4] = {1024, 256, 2, 4};
    cuuint64_t str[3] = {4096, 2048, 256 * 4096};
    cuuint32_t box[4] = {64, 8, 2, 3};
    make_map(enc, &tmXh, d_in[6], 4, dims, str, box, CU_TENSOR_MAP_SWIZZLE_128B);
  }
  {
    cuuint64_t dims[3] = {64, 1024, 48};
    cuuint64_t str[2] = {6144, 128};
    cuuint32_t box[3] = {64, 64, 4};
    make_map(enc, &tmWh, d_in[7], 3, dims, str, box, CU_TENSOR_MAP_SWIZZLE_128B);
  }
  Params p;
  p.q = (const __nv_bfloat16*)d_in[0];
  p.k = (const __nv_bfloat16*)d_in[1];
  p.v = (const __nv_bfloat16*)d_in[2];
  p.shift_k = (const __nv_bfloat16*)d_in[3];
  p.ssm_k = (const __nv_bfloat16*)d_in[4];
  p.ssm_D = (const __nv_bfloat16*)d_in[5];
  p.x = (const __nv_bfloat16*)d_in[6];
  p.w = (const __nv_bfloat16*)d_in[7];
  p.wo = (const __nv_bfloat16*)d_in[8];
  p.out = (__nv_bfloat16*)d_out;
  p.zero = 0;
  for (int cl = 0; cl < 72; cl++) {
    const int t = cl - 4, u = t - 32;
    const bool lo = t >= 0 && t < 32, mid = u >= 0 && u < 28;
    const int grp = lo ? t & 7 : mid ? 1 + u % 7 : 0, mem = lo ? t >> 3 : mid ? 4 + u / 7 : t < 0 ? t + 6 : t - 54;
    p.tile[cl] = (uint8_t)((((grp >> 2) * 4 + (mem >> 1)) * 8 + (grp & 3) * 2 + (mem & 1)) & 63);
  }
  if (coresident) {
    fused_kernel<0><<<NCTA, NTHREADS, SMEM_BYTES>>>(p, tmX, tmW, tmWo, tmWp, tmQ, tmOb, tmXh, tmWh);
  } else {
    fused_kernel<0><<<4, NTHREADS, SMEM_BYTES>>>(p, tmX, tmW, tmWo, tmWp, tmQ, tmOb, tmXh, tmWh);
    fused_kernel<1><<<NCTA, NTHREADS, SMEM_BYTES>>>(p, tmX, tmW, tmWo, tmWp, tmQ, tmOb, tmXh, tmWh);
    fused_kernel<2><<<NCTA, NTHREADS, SMEM_BYTES>>>(p, tmX, tmW, tmWo, tmWp, tmQ, tmOb, tmXh, tmWh);
  }
}
```

```cpp
#include <cuda_runtime.h>
#include <cuda.h>
#include <cuda_bf16.h>
#include <stdint.h>

namespace {

constexpr int SEQ = 2048;
constexpr int DM = 1024;
constexpr int NCTA = 132;
constexpr int NTHREADS = 384;

constexpr int STG1A = 32768;
constexpr int NS1A = 3;
constexpr int STG1B = 12288;
constexpr int NS1B = 5;
constexpr int OFF_1B = NS1A * STG1A;
constexpr int STG2 = 32768;
constexpr int NS2 = 5;
#define PSTEP 1250
#define FPACE 260
#define FPACE2 230
#define FPACE3 180
#define LN 4
constexpr int LEADWG = 1;
__device__ __forceinline__ uint32_t g2_a(int s, int hsel) { return (((0x97524 >> (4 * s)) & 15) ^ (s & 5 ? 0 : hsel)) << 14; }
constexpr int OFF_Q0 = 3 << 14, OFF_Q1 = 8 << 14;
constexpr int STGH = 40960;
constexpr int OFF_KH = 1 * STG2;
constexpr int OFF_OP = 2 * STG2;
constexpr int OFF_T32 = 5 * STG2 - 4096;
constexpr int OFF_X = 5 * STG2;
constexpr int XT = 8192;
__device__ __forceinline__ uint32_t g2_b(int s, int rank) {
  return s < 3 ? (s == 2 ? 6 : s) << 14 : OFF_X + (s - 3) * 2 * XT + (rank ^ 1) * 4096;
}
__device__ __forceinline__ uint32_t g2_bk(int s) { return s < 3 ? 4096 : 4 * XT; }
constexpr int OFF_BAR = OFF_X + 8 * XT;
constexpr int OFF_EX = OFF_BAR + 960;
constexpr int OFF_T16 = 230400;
constexpr int SMEM_BYTES = OFF_T16 + 2048;
static_assert(OFF_1B + NS1B * STG1B <= OFF_T32 && OFF_X % 1024 == 0, "layout");
static_assert(NS1B == NS2 && NS1B * STGH <= OFF_BAR && OFF_EX + 64 <= OFF_T16 && SMEM_BYTES <= 232448, "smem");

constexpr int BAR_FULLA = 0;
constexpr int BAR_EMPTYA = 3;
constexpr int BAR_FULLB = 6;
constexpr int BAR_EMPTYB = 11;
constexpr int BAR_FULL2 = 16;
constexpr int BAR_EMPTY2 = 21;
constexpr int BAR_EMPTY2B = 44;
constexpr int BAR_X = 26;
constexpr int BAR_LAND = 42;
constexpr int BAR_TAB = 28;
constexpr int BAR_U = 29;
constexpr int BAR_H = 30;
constexpr int BAR_Y = 32;
constexpr int BAR_XFREE = 38;
constexpr int BAR_KH = 49;
constexpr int BAR_Q = 41;

constexpr int NB_LEAD = 2;
constexpr int NB_G1END = 3;
constexpr int NB_OREADY = 4;
constexpr int NB_CONV = 5;
constexpr int NB_HELP3 = 11;
constexpr int NB_FIRST = 13;

#define REG_MATH 224
#define REG_HELP 56
constexpr int SPIN_LIMIT = 1 << 20;

__device__ __align__(1024) __nv_bfloat16 g_o[SEQ * DM];
constexpr int FS = 2;
__device__ __align__(128) uint32_t g_flag_o[128 * FS];
__device__ uint4 g_halo[128 * 192];
__device__ __align__(128) const uint32_t g_tab[2048] = {
  0x2fd93000,0x2ea72f64,0x2c722da8,0x263e2a1f,0x2ea73000,0xa63e2a1f,0xafd9ada8,0xac72af64,0x2c723000,0xafd9aa1f,0x263eada8,0x2ea72f64,
  0x263e3000,0xac72af64,0x2ea72da8,0xafd9aa1f,0xa63e3000,0x2c72af64,0xaea72da8,0x2fd9aa1f,0xac723000,0x2fd9aa1f,0xa63eada8,0xaea72f64,
  0xaea73000,0x263e2a1f,0x2fd9ada8,0x2c72af64,0xafd93000,0xaea72f64,0xac722da8,0xa63e2a1f,0x263e0000,0x2c722a1f,0x2ea72da8,0x2fd92f64,
  0x2c720000,0x2fd92f64,0x263e2da8,0xaea7aa1f,0x2ea70000,0x263e2f64,0xafd9ada8,0x2c72aa1f,0x2fd90000,0xaea72a1f,0x2c72ada8,0xa63e2f64,
  0x2fd90000,0xaea7aa1f,0x2c722da8,0xa63eaf64,0x2ea70000,0x263eaf64,0xafd92da8,0x2c722a1f,0x2c720000,0x2fd9af64,0x263eada8,0xaea72a1f,
  0x263e0000,0x2c72aa1f,0x2ea7ada8,0x2fd9af64,0xafd93000,0xaea72f64,0xac722da8,0xa63e2a1f,0xaea73000,0x263e2a1f,0x2fd9ada8,0x2c72af64,
  0xac723000,0x2fd9aa1f,0xa63eada8,0xaea72f64,0xa63e3000,0x2c72af64,0xaea72da8,0x2fd9aa1f,0x263e3000,0xac72af64,0x2ea72da8,0xafd9aa1f,
  0x2c723000,0xafd9aa1f,0x263eada8,0x2ea72f64,0x2ea73000,0xa63e2a1f,0xafd9ada8,0xac72af64,0x2fd93000,0x2ea72f64,0x2c722da8,0x263e2a1f,
  0xa63e0000,0xac722a1f,0xaea72da8,0xafd92f64,0xac720000,0xafd92f64,0xa63e2da8,0x2ea7aa1f,0xaea70000,0xa63e2f64,0x2fd9ada8,0xac72aa1f,
  0xafd90000,0x2ea72a1f,0xac72ada8,0x263e2f64,0xafd90000,0x2ea7aa1f,0xac722da8,0x263eaf64,0xaea70000,0xa63eaf64,0x2fd92da8,0xac722a1f,
  0xac720000,0xafd9af64,0xa63eada8,0x2ea72a1f,0xa63e0000,0xac72aa1f,0xaea7ada8,0xafd9af64,0xa63e0000,0xac72aa1f,0xaea7ada8,0xafd9af64,
  0xac720000,0xafd9af64,0xa63eada8,0x2ea72a1f,0xaea70000,0xa63eaf64,0x2fd92da8,0xac722a1f,0xafd90000,0x2ea7aa1f,0xac722da8,0x263eaf64,
  0xafd90000,0x2ea72a1f,0xac72ada8,0x263e2f64,0xaea70000,0xa63e2f64,0x2fd9ada8,0xac72aa1f,0xac720000,0xafd92f64,0xa63e2da8,0x2ea7aa1f,
  0xa63e0000,0xac722a1f,0xaea72da8,0xafd92f64,0x2fd93000,0x2ea72f64,0x2c722da8,0x263e2a1f,0x2ea73000,0xa63e2a1f,0xafd9ada8,0xac72af64,
  0x2c723000,0xafd9aa1f,0x263eada8,0x2ea72f64,0x263e3000,0xac72af64,0x2ea72da8,0xafd9aa1f,0xa63e3000,0x2c72af64,0xaea72da8,0x2fd9aa1f,
  0xac723000,0x2fd9aa1f,0xa63eada8,0xaea72f64,0xaea73000,0x263e2a1f,0x2fd9ada8,0x2c72af64,0xafd93000,0xaea72f64,0xac722da8,0xa63e2a1f,
  0x263e0000,0x2c72aa1f,0x2ea7ada8,0x2fd9af64,0x2c720000,0x2fd9af64,0x263eada8,0xaea72a1f,0x2ea70000,0x263eaf64,0xafd92da8,0x2c722a1f,
  0x2fd90000,0xaea7aa1f,0x2c722da8,0xa63eaf64,0x2fd90000,0xaea72a1f,0x2c72ada8,0xa63e2f64,0x2ea70000,0x263e2f64,0xafd9ada8,0x2c72aa1f,
  0x2c720000,0x2fd92f64,0x263e2da8,0xaea7aa1f,0x263e0000,0x2c722a1f,0x2ea72da8,0x2fd92f64,0xafd93000,0xaea72f64,0xac722da8,0xa63e2a1f,
  0xaea73000,0x263e2a1f,0x2fd9ada8,0x2c72af64,0xac723000,0x2fd9aa1f,0xa63eada8,0xaea72f64,0xa63e3000,0x2c72af64,0xaea72da8,0x2fd9aa1f,
  0x263e3000,0xac72af64,0x2ea72da8,0xafd9aa1f,0x2c723000,0xafd9aa1f,0x263eada8,0x2ea72f64,0x2ea73000,0xa63e2a1f,0xafd9ada8,0xac72af64,
  0x2fd93000,0x2ea72f64,0x2c722da8,0x263e2a1f,0xa63e0000,0xac72aa1f,0xaea7ada8,0xafd9af64,0x2c720000,0x2fd92f64,0x263e2da8,0xaea7aa1f,
  0xaea70000,0xa63eaf64,0x2fd92da8,0xac722a1f,0x2fd90000,0xaea72a1f,0x2c72ada8,0xa63e2f64,0xafd90000,0x2ea72a1f,0xac72ada8,0x263e2f64,
  0x2ea70000,0x263eaf64,0xafd92da8,0x2c722a1f,0xac720000,0xafd92f64,0xa63e2da8,0x2ea7aa1f,0x263e0000,0x2c72aa1f,0x2ea7ada8,0x2fd9af64,
  0x2fd93000,0x2ea72f64,0x2c722da8,0x263e2a1f,0xaea7b000,0x263eaa1f,0x2fd92da8,0x2c722f64,0x2c723000,0xafd9aa1f,0x263eada8,0x2ea72f64,
  0xa63eb000,0x2c722f64,0xaea7ada8,0x2fd92a1f,0xa63e3000,0x2c72af64,0xaea72da8,0x2fd9aa1f,0x2c72b000,0xafd92a1f,0x263e2da8,0x2ea7af64,
  0xaea73000,0x263e2a1f,0x2fd9ada8,0x2c72af64,0x2fd9b000,0x2ea7af64,0x2c72ada8,0x263eaa1f,0x263e0000,0x2c72aa1f,0x2ea7ada8,0x2fd9af64,
  0xac720000,0xafd92f64,0xa63e2da8,0x2ea7aa1f,0x2ea70000,0x263eaf64,0xafd92da8,0x2c722a1f,0xafd90000,0x2ea72a1f,0xac72ada8,0x263e2f64,
  0x2fd90000,0xaea72a1f,0x2c72ada8,0xa63e2f64,0xaea70000,0xa63eaf64,0x2fd92da8,0xac722a1f,0x2c720000,0x2fd92f64,0x263e2da8,0xaea7aa1f,
  0xa63e0000,0xac72aa1f,0xaea7ada8,0xafd9af64,0xafd93000,0xaea72f64,0xac722da8,0xa63e2a1f,0x2ea7b000,0xa63eaa1f,0xafd92da8,0xac722f64,
  0xac723000,0x2fd9aa1f,0xa63eada8,0xaea72f64,0x263eb000,0xac722f64,0x2ea7ada8,0xafd92a1f,0x263e3000,0xac72af64,0x2ea72da8,0xafd9aa1f,
  0xac72b000,0x2fd92a1f,0xa63e2da8,0xaea7af64,0x2ea73000,0xa63e2a1f,0xafd9ada8,0xac72af64,0xafd9b000,0xaea7af64,0xac72ada8,0xa63eaa1f,
  0xafd9b000,0xaea7af64,0xac72ada8,0xa63eaa1f,0x2ea73000,0xa63e2a1f,0xafd9ada8,0xac72af64,0xac72b000,0x2fd92a1f,0xa63e2da8,0xaea7af64,
  0x263e3000,0xac72af64,0x2ea72da8,0xafd9aa1f,0x263eb000,0xac722f64,0x2ea7ada8,0xafd92a1f,0xac723000,0x2fd9aa1f,0xa63eada8,0xaea72f64,
  0x2ea7b000,0xa63eaa1f,0xafd92da8,0xac722f64,0xafd93000,0xaea72f64,0xac722da8,0xa63e2a1f,0xa63e0000,0xac72aa1f,0xaea7ada8,0xafd9af64,
  0x2c720000,0x2fd92f64,0x263e2da8,0xaea7aa1f,0xaea70000,0xa63eaf64,0x2fd92da8,0xac722a1f,0x2fd90000,0xaea72a1f,0x2c72ada8,0xa63e2f64,
  0xafd90000,0x2ea72a1f,0xac72ada8,0x263e2f64,0x2ea70000,0x263eaf64,0xafd92da8,0x2c722a1f,0xac720000,0xafd92f64,0xa63e2da8,0x2ea7aa1f,
  0x263e0000,0x2c72aa1f,0x2ea7ada8,0x2fd9af64,0x2fd9b000,0x2ea7af64,0x2c72ada8,0x263eaa1f,0xaea73000,0x263e2a1f,0x2fd9ada8,0x2c72af64,
  0x2c72b000,0xafd92a1f,0x263e2da8,0x2ea7af64,0xa63e3000,0x2c72af64,0xaea72da8,0x2fd9aa1f,0xa63eb000,0x2c722f64,0xaea7ada8,0x2fd92a1f,
  0x2c723000,0xafd9aa1f,0x263eada8,0x2ea72f64,0xaea7b000,0x263eaa1f,0x2fd92da8,0x2c722f64,0x2fd93000,0x2ea72f64,0x2c722da8,0x263e2a1f,
  0x263e0000,0x2c72aa1f,0x2ea7ada8,0x2fd9af64,0xac720000,0xafd92f64,0xa63e2da8,0x2ea7aa1f,0x2ea70000,0x263eaf64,0xafd92da8,0x2c722a1f,
  0xafd90000,0x2ea72a1f,0xac72ada8,0x263e2f64,0x2fd90000,0xaea72a1f,0x2c72ada8,0xa63e2f64,0xaea70000,0xa63eaf64,0x2fd92da8,0xac722a1f,
  0x2c720000,0x2fd92f64,0x263e2da8,0xaea7aa1f,0xa63e0000,0xac72aa1f,0xaea7ada8,0xafd9af64,0x316c2fbd,0x343e32f7,0x35bc34ff,0x372c3676,
  0x371532c6,0x3a81392e,0x3bef3b71,0x3b7c3bf2,0x397034cf,0x3bfc3b6c,0x38b23b04,0xb40e31e8,0x3ae13631,0x39e73bf5,0xb6e83219,0xbbe8bb13,
  0x3bc23785,0x30be3aa9,0xbbfdb911,0x2a16b9aa,0x3bfe3865,0xb80f37a6,0xb82abc00,0x3bfd376f,0x3b9238fd,0xbb7f2311,0x3805b929,0x31223bde,
  0x3a85398b,0xbb96b742,0x3bff319e,0xbbb82f8b,0xbbe2bbf1,0xbbb7bbcf,0xbb78bb9a,0xbb27bb52,0xbb2cbbd2,0xb8a8ba19,0xb029b5df,0x35a52f59,
  0xb9dfbba1,0x2ba7b5f7,0x3a7a37b2,0x3bbd3bdd,0xb815bb60,0x39662e91,0x3b373bda,0xb0d7377a,0xb3d3bb10,0x3be9386f,0x2a7a3a31,0xbbfeb9a6,
  0x294dbab0,0x3ae53b07,0xbad51fdb,0xab43bb16,0x352fba41,0x35993c00,0xbaebba1d,0x3be531cf,0x38a3b9c5,0xb5173b21,0x2776bbe0,0x34323bf2,
  0x384537dd,0x38ea3899,0x39823937,0x3a0d39c9,0x39463a93,0x3340374e,0xb426a452,0xb979b7c8,0xbb45b924,0xbb32bc00,0xb371b902,0x38d63294,
  0xb08db9a1,0x3b3f379b,0x39583bd7,0xb8252dfb,0x3bea3a2d,0xb3ba3874,0xbb89bb0d,0x36d2b625,0xb6bb387f,0xb8d1bbf5,0x3be73602,0xb546391f,
  0xba00bb01,0x3bff35eb,0xba5c34db,0x3359bab6,0x3ac7b66b,0xb9413933,0x368dbabd,0xb0103bb3,0xbac4baf7,0xba50ba8c,0xb9cdba11,0xb93cb986,
  0x3a04388e,0x3bcb3b1e,0x3bba3c00,0x39d63afe,0x36af3a21,0xb6ffa17f,0xbbc8ba3d,0xba60bbd4,0xbbebb9af,0xb6c6bb0a,0x39f43263,0x3ad83bf7,
  0x30a6b916,0x3bc33aa5,0xb55e3790,0xbb3dbb63,0x3b423a9e,0xba642ec3,0xb0f0bb6a,0x3b8e3a25,0xb94a37bd,0x2884bb6f,0x38db3b9f,0xbbc9b85a,
  0xb840bb54,0x3a093a15,0xbb4cb850,0x3bef3457,0x3a893a4d,0x3af43ac1,0x3b4f3b24,0x3b983b76,0xbb94baba,0xbbe4bbf9,0xba58bb57,0xb699b8f8,
  0x3bfe3b18,0x394f3b5c,0xb109347b,0xbae8b884,0xbbc0bb68,0xa9b1b90c,0x3b8b387a,0x38bc3ba5,0x3ade3ba7,0xb8c1324b,0xb9f0bbf6,0x39eb9648,
  0xb96bbbd6,0x3bbf3487,0xb38939b3,0xb9f8bba3,0x370a3bf3,0xbb47b994,0x3bbc2d65,0xb8ad3889,0xb153bc00,0x37213b9c,0xb97dba90,0x3af138f3,
  0xb89eb8ee,0xb7e8b84a,0xb682b737,0xb50bb5c8,0x35233855,0xb13b2d33,0xb8e0b65f,0xbb4aba45,0xa8e8b764,0x39fc3648,0x3be63bae,0x380a3a9b,
  0xb3eb360e,0xbbfeba35,0xb552baa2,0x3a7334b7,0x381ab4ab,0x3a6f3bd8,0xb95d2e5f,0xb962bc00,0xb9e3327c,0xb402bbac,0x3bc6399d,0xb95434c3,
  0x3b2faf27,0xb6a439bc,0xb41abbf9,0x3a7e3a97,0xbbe3251b,0x3b2ab4f3,0xb9d23894,0x37f3ba49,0x3bce3bb5,0x3bf03be1,0x3bff3bfa,0x3bfb3bff,
  0x2c38b1b6,0x383a34e7,0x3aee39c0,0x3bff3bb2,0xbb81bbf8,0xb53ab999,0x38302ef5,0x3bed3ab3,0xb8cc9cb6,0xbb85bbab,0x2adeb86a,0x3bc5391b,
  0x38c73bf6,0xbadbb232,0xb6ddbba9,0x3b87361a,0x3b833201,0xb0743a39,0xba76bb5e,0x3b352dc9,0xac06bbb0,0x39743b59,0xbbeeb759,0x3aceb2ad,
  0xbbccb5d4,0x3bfb2d00,0xbb7a32de,0x3a54b7d2,0xb30fb44b,0xafefb185,0xa6adacce,0x2c9c25e4,0xbbfcbbdf,0xbacbbb9e,0xb7feb990,0xa81fb463,
  0xb58d2d97,0xbb90b9b8,0xbad1bbf4,0xb05bb85f,0x3a673c00,0xb5763493,0xbbfdbaac,0xb3a2ba29,0x3a6b2e2d,0x38203bd9,0xbb3ab49f,0xb56abb65,
  0xb581bbdc,0x3bec3907,0xb8b7363c,0xb6f4bbf8,0xbbfcb46f,0x39dab654,0xb0423b1b,0xb835bbd3,0xb3283b73,0xac6abbfa,0x35b13bd0,0xb8e5bafb,
  0x38ee3a0d,0xb84aba89,0x37373af4,0xb5c8bb4f,0x35df3a81,0x2f59bbef,0xb88e3b7c,0x3b1eb946,0x2d973ae8,0x39b8bb81,0xbbf4353a,0x385f3830,
  0xb2633b3f,0x3bf7b958,0xb60eb825,0xba353bc0,0xb7853b87,0x3aa9b3d3,0x3911bbe9,0xb9aa2a7a,0xb99d3bbf,0x34c33389,0x3bdcb9f8,0x3907bb83,
  0xbb013be5,0xb5eb394a,0x34db2884,0x3ab6b8db,0xbbd03bfb,0xbafb3b7a,0xb98b3a54,0xb74238a3,0x3a4db93c,0xbac1389e,0x3b24b7e8,0xbb763682,
  0x3b71b8a8,0xbbf23029,0x3a9335a5,0xb74eba04,0x3bf8b80a,0xb999b58d,0xaef53b90,0x3ab3bad1,0x3bd7b6c6,0xadfbb9f4,0xbb683ad8,0x390c33eb,
  0x3b10b56a,0x386fbbc2,0xba3130be,0xb9a63bfd,0x39b3b402,0x3ba3bbc6,0x3201b954,0xba393581,0x37bdb122,0x3b6fba00,0x3b9fbbff,0x385aba5c,
  0x32deac6a,0x37d2b5b1,0x39c5b8e5,0x3b21ba85,0x344b3b98,0xb185bbce,0x2cce3bf0,0x25e4bbff,0xbc003340,0x3afe3426,0xb855b979,0x2d333b94,
  0x34cfbbed,0xbb6c39df,0x3b042ba7,0xb1e8ba7a,0x3aa2a9b1,0x34b7bb8b,0xbc0038bc,0x349338cc,0xba2d3bfe,0x387430a6,0x3b0dbbc3,0xb625b55e,
  0xb63cb074,0xbbf83a76,0xb8653b35,0x37a6294d,0x3bf3bbc9,0x3994bb2f,0x2d65b6a4,0xb889341a,0xb19e3517,0x2f8b2776,0x366bb432,0x3933b840,
  0x3bb5b50b,0xbbe1330f,0x3bfaafef,0xbbff26ad,0xa4523bcb,0x37c8bbba,0xbaba39d6,0x3bf9b523,0xbba1305b,0x35f73970,0x37b2bbfc,0xbbdd38b2,
  0x387abbfe,0xbba53552,0x9cb63a73,0x3babba67,0x39162a16,0x3aa5bbea,0xb790b3ba,0xbb633b89,0xbb5e3bec,0xadc938b7,0x3ab0b6f4,0x3b07bbfe,
  0xaf27b359,0xb9bc370a,0xbbf93b47,0xba973bbc,0x3be0bb96,0x3bf2bbff,0x3b54bbb8,0x3a15bac7,0xafbd3bfb,0x32f7bbe2,0xb4ff3bb7,0x3676bb78,
  0x365fbbe4,0xba453a58,0x3bdfb699,0xbb9eac38,0xb9243bbd,0x3c00b6af,0xb902b6ff,0xb2943bc8,0x3aacbb85,0xba29aade,0xb6313bc5,0x3bf5b815,
  0xbba73b3d,0x324b381a,0x3bf6ba6f,0x9648b95d,0x3c00bae5,0x376fbad5,0xb87f2b43,0xbbf53b42,0xbbb03a7e,0xbb593bfc,0xb75939da,0x32ad3042,
  0x3abdba09,0x3bb3bb4c,0x3c00bbef,0x3b9cbbe3,0x3bf12c9c,0xbbcfb16c,0x3b9a343e,0xbb52b5bc,0xbb57b13b,0x38f838e0,0xb1b6bb4a,0xb4e73bfc,
  0x3a21340e,0x217fbb45,0xba3d3b32,0x3bd4b371,0xb86ab576,0xb91b3bfd,0x3b60b3a2,0x2e91bae1,0x34ab36d2,0x3bd8bade,0xae5fb8c1,0xbc0039f0,
  0x9fdbb80f,0xbb16382a,0xba9e3bfd,0x2ec336bb,0xb46f38ad,0x3654ac06,0x3b1bb974,0x3bd3bbee,0x3850b941,0x3457b68d,0xa51bb010,0xb4f33153,
  0xb7dd3b27,0x3899bac4,0xb9373a50,0x39c9b9cd,0x3990383a,0xb463baee,0xb2c63bff,0x392ebb2c,0x3b18ba60,0xbb5c28e8,0x347b39fc,0x3884bbe6,
  0xb219b966,0xbb133b37,0x39a130d7,0x379bbbeb,0xbbf63962,0xb2323a6b,0x3ba9b820,0x361abb3a,0xb6023a64,0x391fb0f0,0x3bd6bb8e,0x3487b9e3,
  0x3a41b835,0x3c00bb92,0x3a1dbb7f,0x31cfb805,0x3a90bb2a,0x38f3b9d2,0x35d4b7f3,0x2d00b328,0x3af7372c,0xba8cb845,0x3a1138ea,0xb986b982,
  0x39c0bacb,0xbbb237fe,0x3bd2a81f,0xba19b715,0xb764b8d6,0xb6483bfe,0x3baeb94f,0xba9bb109,0xbbda39e7,0x377a36e8,0x39afbbe8,0xbb0a308d,
  0xae2d39eb,0x3bd9b8c7,0x349fbadb,0xbb6536dd,0x3b6ab8d1,0x3a25bbe7,0xb27cb546,0xbbac396b,0x38fdbace,0xa311b52f,0xb9293599,0xbbde3aeb,
  0xb8943721,0xba49397d,0xbb733af1,0xbbfa3bcc,0xbbfb3bff,0xbbe23bf1,0xbbb73bcf,0xbb783b9a,0xbb7c3bf2,0xb9463a93,0xb340374e,0x3426a452,
  0xba603bd4,0xa8e83764,0x39fcb648,0x3be6bbae,0xb8bc3ba5,0x38cc9cb6,0x3b85bbab,0xaadeb86a,0xb56a3b65,0x3bc2b785,0x30bebaa9,0xbbfd3911,
  0xab433b16,0x3b42ba9e,0xba64aec3,0xb0f03b6a,0x33593ab6,0x370abbf3,0xbb473994,0x3bbcad65,0x37f33a49,0xb328bb73,0xac6a3bfa,0x35b1bbd0,
  0xac9c25e4,0xb16c2fbd,0xb43e32f7,0xb5bc34ff,0xb5a52f59,0xba04388e,0xbbcb3b1e,0xbbba3c00,0xb8d63294,0xbbfe3b18,0xb94f3b5c,0x3109347b,
  0xba7334b7,0xba673c00,0x35763493,0x3bfdbaac,0xbb87361a,0xb3d33b10,0x3be9b86f,0x2a7aba31,0xbbfd376f,0x36bb387f,0x38d1bbf5,0xbbe73602,
  0xbbc9385a,0x3b2f2f27,0xb6a4b9bc,0xb41a3bf9,0xbaf138f3,0x3bccb5d4,0xbbfb2d00,0x3b7a32de,0xbb273b52,0xbac43af7,0xba503a8c,0xb9cd3a11,
  0x3979b7c8,0x3b94baba,0x3be4bbf9,0x3a58bb57,0x380aba9b,0xb58dad97,0xbb9039b8,0xbad13bf4,0xbbc5391b,0xb8153b60,0x3966ae91,0x3b37bbda,
  0x2a1639aa,0x3beaba2d,0xb3bab874,0xbb893b0d,0x3b8eba25,0xb9e3b27c,0xb4023bac,0x3bc6b99d,0xb8adb889,0xac063bb0,0x3974bb59,0xbbee3759,
  0xb8e53afb,0x3a85b98b,0xbb963742,0x3bffb19e,0xb72c3676,0xb84537dd,0xb8ea3899,0xb9823937,0xb9d63afe,0xb5233855,0x313b2d33,0x38e0b65f,
  0x3ae8b884,0x3b81bbf8,0x353ab999,0xb8302ef5,0x33a2ba29,0xbae13631,0xb9e73bf5,0x36e83219,0xbbfe39a6,0x30a63916,0x3bc3baa5,0xb55eb790,
  0x3546391f,0x396bbbd6,0xbbbf3487,0x338939b3,0x3a7eba97,0xbbfc346f,0x39da3654,0xb042bb1b,0xba54b7d2,0x38a339c5,0xb517bb21,0x27763be0,
  0xb93c3986,0xb89e38ee,0xb7e8384a,0xb6823737,0x3699b8f8,0xac38b1b6,0xb83a34e7,0xbaee39c0,0xb05b385f,0x3970b4cf,0x3bfcbb6c,0x38b2bb04,
  0xb0d7b77a,0xbbeb39af,0xb6c63b0a,0x39f4b263,0x36d23625,0x3adebba7,0xb8c1b24b,0xb9f03bf6,0xb954b4c3,0xb5813bdc,0x3becb907,0xb8b7b63c,
  0x3ace32ad,0xb52fba41,0xb5993c00,0x3aebba1d,0xbbb8af8b,0x3ac7366b,0xb941b933,0x368d3abd,0xba0d39c9,0xba893a4d,0xbaf43ac1,0xbb4f3b24,
  0x3b4aba45,0x3bfcbbdf,0x3acbbb9e,0x37feb990,0xbbed3ab3,0xb9df3ba1,0x2ba735f7,0x3a7ab7b2,0x3be8bb13,0x308db9a1,0xbb3f379b,0xb9583bd7,
  0xbb3d3b63,0x381a34ab,0x3a6fbbd8,0xb95dae5f,0x39f8bba3,0xbb833201,0x30743a39,0x3a76bb5e,0xb8353bd3,0x3b92b8fd,0xbb7fa311,0x38053929,
  0x3432bbf2,0xb8403b54,0x3a09ba15,0xbb4c3850,0xb50b35c8,0xb30f344b,0xafef3185,0xa6ad2cce,0xbbff3bb2,0xbb2c3bd2,0xb8a83a19,0xb02935df,
  0xb40eb1e8,0xbb453924,0xbb323c00,0xb3713902,0x3ad8bbf7,0xb3ebb60e,0xbbfe3a35,0xb5523aa2,0x39eb1648,0x38c7bbf6,0xbadb3232,0xb6dd3ba9,
  0xb6f43bf8,0x3bfeb865,0xb80fb7a6,0xb82a3c00,0xbbe531cf,0x394a37bd,0xa884bb6f,0xb8db3b9f,0xb010bbb3,0xb1533c00,0x3721bb9c,0xb97d3a90,
  0xbb983b76,0xbbce3bb5,0xbbf03be1,0xbbff3bfa,0x281fb463,0xb71532c6,0xba81392e,0xbbef3b71,0x3bbdbbdd,0x36afba21,0xb6ff217f,0xbbc83a3d,
  0x38252dfb,0x3bc0bb68,0x29b1b90c,0xbb8b387a,0xb9623c00,0x3a6bae2d,0x3820bbd9,0xbb3a349f,0xbb352dc9,0x294d3ab0,0x3ae5bb07,0xbad59fdb,
  0x3122bbde,0xba003b01,0x3bffb5eb,0xba5cb4db,0x3befb457,0xbbe3a51b,0x3b2a34f3,0xb9d2b894,0x39c939cd,0xba4db93c,0x3ac1389e,0xbb24b7e8,
  0x3b1e3946,0xbc00b340,0x3afeb426,0xb8553979,0x3bdd38b2,0xba21340e,0xa17fbb45,0x3a3d3b32,0x3bf53815,0xb2193966,0xbb13bb37,0x39a1b0d7,
  0x3b6536dd,0x37853b87,0xbaa9b3d3,0xb911bbe9,0x3a393581,0x3b5e3bec,0x2dc938b7,0xbab0b6f4,0x3889341a,0x3bb03a7e,0x3b593bfc,0x375939da,
  0x34f33153,0x38943721,0x3a49397d,0x3b733af1,0xb9863982,0x38eeba0d,0xb84a3a89,0x3737baf4,0xb74e3a04,0xa452bbcb,0x37c83bba,0xbabab9d6,
  0xb1e83a7a,0xb924bbbd,0x3c0036af,0xb90236ff,0x2e913ae1,0xbbdab9e7,0x377ab6e8,0x39af3be8,0x361a3b3a,0xbb10b56a,0xb86fbbc2,0x3a3130be,
  0x39073b83,0xb63c3074,0xbbf8ba76,0xb865bb35,0x3a973bbc,0x346f38ad,0xb654ac06,0xbb1bb974,0x3b9c3be3,0x3a903b2a,0x38f339d2,0x35d437f3,
  0x3b763682,0xbbb5b50b,0x3be1330f,0xbbfaafef,0x2d33bb94,0x365f3be4,0xba45ba58,0x3bdf3699,0xbbd4b371,0x3764b8d6,0x36483bfe,0xbbaeb94f,
  0x379b3beb,0xbbd7b6c6,0x2dfbb9f4,0x3b683ad8,0x39aa2a7a,0x3a2d3bfe,0xb87430a6,0xbb0dbbc3,0xbb07bbfe,0x1fdbb80f,0x3b16382a,0x3a9e3bfd,
  0xb2ad3042,0xba41b835,0xbc00bb92,0xba1dbb7f,0x3bfa3bcc,0x3bd03bfb,0x3afb3b7a,0x398b3a54,0xb5c83b4f,0x344bbb98,0xb1853bce,0x2ccebbf0,
  0x3bf93523,0xbb57313b,0x38f8b8e0,0xb1b63b4a,0xb294bbc8,0x3b183a60,0xbb5ca8e8,0x347bb9fc,0xbb0ab08d,0xb263bb3f,0x3bf73958,0xb60e3825,
  0x39a63bfd,0xb9162a16,0xbaa5bbea,0x3790b3ba,0x37a6a94d,0x3c003ae5,0x376f3ad5,0xb87fab43,0xbbd3bbee,0xb8fdbace,0x2311b52f,0x39293599,
  0x2d003328,0xb2deac6a,0xb7d2b5b1,0xb9c5b8e5,0x3bff26ad,0xbbf12c9c,0x3bcfb16c,0xbb9a343e,0xbb9e2c38,0x3990b83a,0xb4633aee,0xb2c6bbff,
  0x3a9bb109,0xad973ae8,0xb9b8bb81,0x3bf4353a,0xb90c33eb,0xb87abbfe,0x3ba53552,0x1cb63a73,0x3625b55e,0x3ba73b3d,0xb24b381a,0xbbf6ba6f,
  0xaec336bb,0xbb6ab8d1,0xba25bbe7,0x327cb546,0xb1cfb805,0x37bd3122,0x3b6f3a00,0x3b9f3bff,0x374238a3,0x319e3517,0xaf8b2776,0xb66bb432,
  0x25e43bff,0xafbdbbfb,0x32f73be2,0xb4ffbbb7,0xb4e7bbfc,0x39c03acb,0xbbb2b7fe,0x3bd2281f,0x38843be6,0xbbf8b80a,0x3999b58d,0x2ef53b90,
  0xba35bbc0,0x3aa229b1,0x34b73b8b,0xbc00b8bc,0x3b633b89,0xb4ab36d2,0xbbd8bade,0x2e5fb8c1,0xbbf5bb42,0xb602ba64,0x391f30f0,0x3bd63b8e,
  0x3bde3aeb,0x3b013be5,0x35eb394a,0xb4db2884,0xbb21ba85,0xbbe0bb96,0xbbf2bbff,0xbb54bbb8,0x3b52b5bc,0xbaf7372c,0x3a8cb845,0xba1138ea,
  0x392e3b2c,0xbb71b8a8,0x3bf23029,0xba9335a5,0xb85f3830,0xb4cfbbed,0x3b6c39df,0xbb042ba7,0xbbabba67,0x386ab576,0x391b3bfd,0xbb60b3a2,
  0x1648b95d,0x3bf63962,0x32323a6b,0xbba9b820,0x3bac396b,0x399d3bbf,0xb4c33389,0xbbdcb9f8,0x385a3a5c,0xaf273359,0xb9bcb70a,0xbbf9bb47,
  0xb933b840,0xbabdba09,0xbbb3bb4c,0xbc00bbef,0x36763b78,0xb7ddbb27,0x38993ac4,0xb937ba50,0xba193715,0x35dfba81,0x2f593bef,0xb88ebb7c,
  0xbab3bad1,0x3ba1305b,0xb5f73970,0xb7b2bbfc,0x3493b8cc,0x3aac3b85,0xba292ade,0xb631bbc5,0x3c0039f0,0x2e2d39eb,0xbbd9b8c7,0xb49fbadb,
  0x348739e3,0xb9b3b402,0xbba3bbc6,0xb201b954,0xbab6b8db,0xbbf3bbc9,0xb994bb2f,0xad65b6a4,0xba15bac7,0xb850b941,0xb457b68d,0x251bb010,
  0xb9cfbb16,0x30ac2a31,0x3b9c3bf1,0xb493ae2d,0xb76fb8b4,0x35a133e3,0x3a1d3afe,0xb902b76f,0xb3e3b5a1,0x38b4376f,0x376f3902,0xbafeba1d,
  0xaa31b0ac,0x3b1639cf,0x2e2d3493,0xbbf1bb9c,0xb956ba74,0x305f29cc,0x3b633bd2,0xb44badc9,0xb6e7b859,0x353f335e,0x39d23ab6,0xb8bcb6ff,
  0xb35eb53f,0x385936e7,0x36ff38bc,0xbab6b9d2,0xa9ccb05f,0x3a743956,0x2dc9344b,0xbbd2bb63,0xb8e3b9de,0x30122967,0x3b1e3ba1,0xb402ad65,
  0xb662b801,0x34de32da,0x39823a67,0xb874b68d,0xb2dab4de,0x38013662,0x368d3874,0xba67b982,0xa967b012,0x39de38e3,0x2d653402,0xbba1bb1e,
  0xb876b952,0x2f8c2902,0x3ace3b60,0xb371ad00,0xb5e1b758,0x347e3257,0x392e3a11,0xb82ab61a,0xb257b47e,0x375835e1,0x361a382a,0xba11b92e,
  0xa902af8c,0x39523876,0x2d003371,0xbb60bace,0xb80db8ce,0x2ef3289e,0x3a733b10,0xb2deac9c,0xb562b6b3,0x342031d5,0x38d639b3,0xb7bdb5a5,
  0xb1d5b420,0x36b33562,0x35a537bd,0xb9b3b8d6,0xa89eaef3,0x38ce380d,0x2c9c32de,0xbb10ba73,0xb750b851,0x2e5a2839,0x3a0d3ab0,0xb24bac38,
  0xb4e5b613,0x33863153,0x387a394f,0xb721b52f,0xb153b386,0x361334e5,0x352f3721,0xb94fb87a,0xa839ae5a,0x38513750,0x2c38324b,0xbab0ba0d,
  0xb68eb7b4,0x2dc227a9,0x399d3a41,0xb1b6aba7,0xb46ab577,0x32cd30d2,0x381a38e5,0xb682b4b7,0xb0d2b2cd,0x3577346a,0x34b73682,0xb8e5b81a,
  0xa7a9adc2,0x37b4368e,0x2ba731b6,0xba41b99d,0xb5d2b6d1,0x2d2a26e0,0x392439c5,0xb122aade,0xb3e3b4de,0x32163052,0x376f3874,0xb5dfb43e,
  0xb052b216,0x34de33e3,0x343e35df,0xb874b76f,0xa6e0ad2a,0x36d135d2,0x2ade3122,0xb9c5b924,0xb51cb5f6,0x2c932617,0x38a3393c,0xb08daa16,
  0xb2f4b448,0x31602fa5,0x36a437fe,0xb53ab389,0xafa5b160,0x344832f4,0x3389353a,0xb7feb6a4,0xa617ac93,0x35f6351c,0x2a16308d,0xb93cb8a3,
  0xb46ab523,0x2bf6254d,0x381a38a8,0xafefa94d,0xb209b36b,0x30ac2ea7,0x35d4370a,0xb493b294,0xaea7b0ac,0x336b3209,0x32943493,0xb70ab5d4,
  0xa54dabf6,0x3523346a,0x294d2fef,0xb8a8b81a,0xb378b456,0x2ac82484,0x3715380a,0xaec3a884,0xb120b24a,0x2ff22da9,0x34ff360e,0xb3d3b19e,
  0xada9aff2,0x324a3120,0x319e33d3,0xb60eb4ff,0xa484aac8,0x34563378,0x28842ec3,0xb80ab715,0xb223b31c,0x29992376,0x35eb36c6,0xad97a776,
  0xb039b12d,0x2e8d2cac,0x3426350b,0xb27cb0a6,0xacacae8d,0x312d3039,0x30a6327c,0xb50bb426,0xa376a999,0x331c3223,0x27762d97,0xb6c6b5eb,
  0xb0d2b194,0x286b21e4,0x34b7356a,0xac6aa5e4,0xaea7b012,0x2d2a2b5f,0x32943402,0xb122af59,0xab5fad2a,0x30122ea7,0x2f593122,0xb402b294,
  0xa1e4a86b,0x319430d2,0x25e42c6a,0xb56ab4b7,0xaf0cb012,0x267b2052,0x32f73402,0xaa7aa452,0xacdeadf5,0x2b912967,0x30d731e8,0xaf8bad65,
  0xa967ab91,0x2df52cde,0x2d652f8b,0xb1e8b0d7,0xa052a67b,0x30122f0c,0x24522a7a,0xb402b2f7,0xac79ad2a,0x24201d7f,0x30743122,0xa81fa17f,
  0xaa31ab91,0x28d026e0,0x2e2d2f8b,0xacceaade,0xa6e0a8d0,0x2b912a31,0x2ade2cce,0xaf8bae2d,0x9d7fa420,0x2d2a2c79,0x217f281f,0xb122b074,
  0xa7a9a86b,0x1f1218b6,0x2ba72c6a,0xa3119cb6,0xa54da67b,0x242021e4,0x294d2a7a,0xa81fa5e4,0xa1e4a420,0x267b254d,0x25e4281f,0xaa7aa94d,
  0x98b69f12,0x286b27a9,0x1cb62311,0xac6aaba7,0x211b21e4,0x98b69248,0xa51ba5e4,0x1cb61648,0x1f122052,0x9d7f9bdb,0xa311a452,0x217f1fdb,
  0x1bdb1d7f,0xa0529f12,0x9fdba17f,0x24522311,0x124818b6,0xa1e4a11b,0x96489cb6,0x25e4251b,0x2a632b5f,0xa1e49bdb,0xae5faf59,0x25e41fdb,
  0x286b2967,0xa6e0a4e9,0xac6aad65,0x2ade28e8,0x24e926e0,0xa967a86b,0xa8e8aade,0x2d652c6a,0x1bdb21e4,0xab5faa63,0x9fdba5e4,0x2f592e5f,
  0x2dc22ea7,0xa54d9f12,0xb1b6b294,0x294d2311,0x2bf62cde,0xaa31a86b,0xafefb0d7,0x2e2d2c6a,0x286b2a31,0xacdeabf6,0xac6aae2d,0x30d72fef,
  0x1f12254d,0xaea7adc2,0xa311a94d,0x329431b6,0x302c30d2,0xa7a9a11b,0xb41ab4b7,0x2ba7251b,0x2dc22f0c,0xac79aa63,0xb1b6b2f7,0x30742e5f,
  0x2a632c79,0xaf0cadc2,0xae5fb074,0x32f731b6,0x211b27a9,0xb0d2b02c,0xa51baba7,0x34b7341a,0x317a3257,0xa902a2ad,0xb552b61a,0x2d0026ad,
  0x2f8c309f,0xaddcac2e,0xb371b487,0x31cf3029,0x2c2e2ddc,0xb09faf8c,0xb029b1cf,0x34873371,0x22ad2902,0xb257b17a,0xa6adad00,0x361a3552,
  0x32cd33e3,0xaa31a420,0xb682b76f,0x2e2d281f,0x30ac31bb,0xaf3fad2a,0xb493b58d,0x33283122,0x2d2a2f3f,0xb1bbb0ac,0xb122b328,0x358d3493,
  0x24202a31,0xb3e3b2cd,0xa81fae2d,0x376f3682,0x341334bc,0xab5fa4e9,0xb7a6b85a,0x2f5928e8,0x319432da,0xb052ae28,0xb56ab68d,0x343e3219,
  0x2e283052,0xb2dab194,0xb219b43e,0x368d356a,0x24e92b5f,0xb4bcb413,0xa8e8af59,0x385a37a6,0x34c3358c,0xac47a5b2,0xb85fb8f3,0x304229b1,
  0x327e33fd,0xb106af26,0xb63cb785,0x34e7330f,0x2f263106,0xb3fdb27e,0xb30fb4e7,0x3785363c,0x25b22c47,0xb58cb4c3,0xa9b1b042,0x38f3385f,
  0x35773662,0xacdea67b,0xb8e5b982,0x30d72a7a,0x336b3493,0xb1bbb012,0xb70ab83a,0x358d3402,0x301231bb,0xb493b36b,0xb402b58d,0x383a370a,
  0x267b2cde,0xb662b577,0xaa7ab0d7,0x398238e5,0x36303741,0xad76a744,0xb962ba04,0x316c2b43,0x342e352a,0xb271b092,0xb7d2b8ad,0x3631347b,
  0x30923271,0xb52ab42e,0xb47bb631,0x38ad37d2,0x27442d76,0xb741b630,0xab43b16c,0x3a043962,0x36ee3815,0xae0ea807,0xb9d6ba7a,0x32012c06,
  0x34a735c4,0xb329b113,0xb84ab91b,0x36d234f3,0x31133329,0xb5c4b4a7,0xb4f3b6d2,0x391b384a,0x28072e0e,0xb815b6ee,0xac06b201,0x3a7a39d6,
  0x37b4388e,0xaea7a86b,0xba41bae1,0x32942c6a,0x35233662,0xb3e3b194,0xb8a8b982,0x376f356a,0x319433e3,0xb662b523,0xb56ab76f,0x398238a8,
  0x286b2ea7,0xb88eb7b4,0xac6ab294,0x3ae13a41,0x3841390f,0xaf3fa8d0,0xbaa2bb3a,0x33282cce,0x35a13705,0xb44fb216,0xb902b9e3,0x380535df,
  0x3216344f,0xb705b5a1,0xb5dfb805,0x39e33902,0x28d02f3f,0xb90fb841,0xacceb328,0x3b3a3aa2,0x38ac3997,0xafd8a935,0xbaf7bb83,0x33ba2d33,
  0x362137ac,0xb4aeb298,0xb958ba3d,0x38503654,0x329834ae,0xb7acb621,0xb654b850,0x3a3d3958,0x29352fd8,0xb997b8ac,0xad33b3ba,0x3b833af7,
  0x391c3a28,0xb039a999,0xbb42bbbc,0x34262d97,0x36a4382d,0xb50eb31c,0xb9aaba90,0x389936c6,0x331c350e,0xb82db6a4,0xb6c6b899,0x3a9039aa,
  0x29993039,0xba28b91c,0xad97b426,0x3bbc3b42,0x39923ac3,0xb085a9fe,0xbb81bbe3,0x346f2dfb,0x372a3886,0xb570b3a0,0xb9f8badb,0x38e03737,
  0x33a03570,0xb886b72a,0xb737b8e0,0x3adb39f8,0x29fe3085,0xbac3b992,0xadfbb46f,0x3be33b81,
};

#define PROF(slot) do {} while (0)
#define PROF_DUMP() do {} while (0)
#define PROFA(slot, dep) do {} while (0)
#define PROF3(slot) do {} while (0)
#define PROF2(slot) do {} while (0)

__device__ __forceinline__ uint32_t smem_u32(const void* p) { return (uint32_t)__cvta_generic_to_shared(p); }

__device__ __forceinline__ void mbar_init(uint32_t a, uint32_t c) {
  asm volatile("mbarrier.init.shared::cta.b64 [%0], %1;\n" ::"r"(a), "r"(c) : "memory");
}
__device__ __forceinline__ void mbar_expect_tx(uint32_t a, uint32_t bytes) {
  asm volatile("mbarrier.arrive.expect_tx.shared::cta.b64 _, [%0], %1;\n" ::"r"(a), "r"(bytes) : "memory");
}
__device__ __forceinline__ void mbar_arrive_cluster(uint32_t cluster_addr) {
  asm volatile("mbarrier.arrive.shared::cluster.b64 _, [%0];\n" ::"r"(cluster_addr) : "memory");
}
__device__ __forceinline__ void mbar_arrive_cluster_n(uint32_t cluster_addr, uint32_t n) {
  asm volatile("mbarrier.arrive.shared::cluster.b64 _, [%0], %1;\n" ::"r"(cluster_addr), "r"(n) : "memory");
}
__device__ __forceinline__ bool mbar_try(uint32_t a, uint32_t parity) {
  uint32_t ok;
  asm volatile("{\n.reg .pred p;\nmbarrier.try_wait.parity.shared::cta.b64 p, [%1], %2;\nselp.u32 %0, 1, 0, p;\n}\n"
               : "=r"(ok) : "r"(a), "r"(parity) : "memory");
  return ok;
}
__device__ __forceinline__ void mbar_wait(uint32_t a, uint32_t parity) {
  if (mbar_try(a, parity)) return;
#pragma unroll 1
  for (int n = 0; n < SPIN_LIMIT; n++)
    if (mbar_try(a, parity)) break;
}
__device__ __forceinline__ bool elect_one() {
  uint32_t p;
  asm volatile("{\n.reg .pred P;\nelect.sync _|P, 0xffffffff;\nselp.u32 %0, 1, 0, P;\n}\n" : "=r"(p));
  return p;
}
__device__ __forceinline__ uint32_t mapa(uint32_t a, uint32_t rank) {
  uint32_t r;
  asm volatile("mapa.shared::cluster.u32 %0, %1, %2;\n" : "=r"(r) : "r"(a), "r"(rank));
  return r;
}
__device__ __forceinline__ void nb_sync(int id, int n) { asm volatile("bar.sync %0, %1;\n" ::"r"(id), "r"(n) : "memory"); }
__device__ __forceinline__ void nb_arrive(int id, int n) { asm volatile("bar.arrive %0, %1;\n" ::"r"(id), "r"(n) : "memory"); }
__device__ __forceinline__ void cluster_sync_all() {
  asm volatile("barrier.cluster.arrive.relaxed.aligned;\nbarrier.cluster.wait.aligned;\n" ::: "memory");
}
__device__ __forceinline__ void fence_async_smem() { asm volatile("fence.proxy.async.shared::cta;\n" ::: "memory"); }
__device__ __forceinline__ void fence_async_all() { asm volatile("fence.proxy.async.global;\n" ::: "memory"); }

__device__ __forceinline__ void tma_load_3d(uint32_t dst, const CUtensorMap* tm, uint32_t bar, int c0, int c1, int c2) {
  asm volatile(
      "cp.async.bulk.tensor.3d.shared::cluster.global.mbarrier::complete_tx::bytes [%0], [%1, {%3, %4, %5}], [%2];\n"
      ::"r"(dst), "l"(tm), "r"(bar), "r"(c0), "r"(c1), "r"(c2) : "memory");
}
__device__ __forceinline__ void tma_load_4d(uint32_t dst, const CUtensorMap* tm, uint32_t bar, int c0, int c1, int c2, int c3) {
  asm volatile(
      "cp.async.bulk.tensor.4d.shared::cluster.global.mbarrier::complete_tx::bytes [%0], [%1, {%3, %4, %5, %6}], [%2];\n"
      ::"r"(dst), "l"(tm), "r"(bar), "r"(c0), "r"(c1), "r"(c2), "r"(c3) : "memory");
}
__device__ __forceinline__ void tma_load_3d_mc(uint32_t dst, const CUtensorMap* tm, uint32_t bar, int c0, int c1, int c2) {
  asm volatile(
      "cp.async.bulk.tensor.3d.shared::cluster.global.mbarrier::complete_tx::bytes.multicast::cluster [%0], [%1, {%3, %4, %5}], [%2], %6;\n"
      ::"r"(dst), "l"(tm), "r"(bar), "r"(c0), "r"(c1), "r"(c2), "h"((uint16_t)3) : "memory");
}
__device__ __forceinline__ void bulk_load(uint32_t dst, const void* src, uint32_t bytes, uint32_t bar) {
  asm volatile("cp.async.bulk.shared::cluster.global.mbarrier::complete_tx::bytes [%0], [%1], %2, [%3];\n"
               ::"r"(dst), "l"(src), "r"(bytes), "r"(bar) : "memory");
}
__device__ __forceinline__ void tma_store_3d(const CUtensorMap* tm, uint32_t src, int c0, int c1, int c2) {
  asm volatile("cp.async.bulk.tensor.3d.global.shared::cta.bulk_group [%0, {%2, %3, %4}], [%1];\n"
               ::"l"(tm), "r"(src), "r"(c0), "r"(c1), "r"(c2) : "memory");
}
__device__ __forceinline__ void bulk_commit() { asm volatile("cp.async.bulk.commit_group;\n" ::: "memory"); }
__device__ __forceinline__ void bulk_wait0() { asm volatile("cp.async.bulk.wait_group 0;\n" ::: "memory"); }
__device__ __forceinline__ void prefetch_tmap(const CUtensorMap* tm) {
  asm volatile("prefetch.tensormap [%0];\n" ::"l"(tm) : "memory");
}

__device__ __forceinline__ void wg_fence() { asm volatile("wgmma.fence.sync.aligned;\n" ::: "memory"); }
__device__ __forceinline__ void wg_commit() { asm volatile("wgmma.commit_group.sync.aligned;\n" ::: "memory"); }
template <int N> __device__ __forceinline__ void wg_wait() {
  asm volatile("wgmma.wait_group.sync.aligned %0;\n" ::"n"(N) : "memory");
}
__device__ __forceinline__ uint64_t mkdesc(uint32_t addr, uint32_t lbo, uint32_t sbo, uint32_t swz) {
  return (uint64_t)((addr & 0x3FFFF) >> 4) | ((uint64_t)(lbo >> 4) << 16) | ((uint64_t)(sbo >> 4) << 32) |
         ((uint64_t)swz << 62);
}

#define R4(d, o) "+f"(d[o + 0]), "+f"(d[o + 1]), "+f"(d[o + 2]), "+f"(d[o + 3])
#define R8(d, o) R4(d, o), R4(d, o + 4)
#define R16(d, o) R8(d, o), R8(d, o + 8)
#define R32(d, o) R16(d, o), R16(d, o + 16)
#define R64(d, o) R32(d, o), R32(d, o + 32)

__device__ __forceinline__ void wgmma_n192(float (&d)[96], uint64_t da, uint64_t db, uint32_t acc) {
  asm volatile(
      "{\n.reg .pred p;\nsetp.ne.u32 p, %98, 0;\n"
      "wgmma.mma_async.sync.aligned.m64n192k16.f32.bf16.bf16 "
      "{%0,%1,%2,%3,%4,%5,%6,%7,%8,%9,%10,%11,%12,%13,%14,%15,%16,%17,%18,%19,%20,%21,%22,%23,%24,%25,%26,%27,%28,%29,%30,%31,"
      "%32,%33,%34,%35,%36,%37,%38,%39,%40,%41,%42,%43,%44,%45,%46,%47,%48,%49,%50,%51,%52,%53,%54,%55,%56,%57,%58,%59,%60,%61,%62,%63,"
      "%64,%65,%66,%67,%68,%69,%70,%71,%72,%73,%74,%75,%76,%77,%78,%79,%80,%81,%82,%83,%84,%85,%86,%87,%88,%89,%90,%91,%92,%93,%94,%95}, "
      "%96, %97, p, 1, 1, 0, 1;\n}\n"
      : R64(d, 0), R32(d, 64)
      : "l"(da), "l"(db), "r"(acc));
}
__device__ __forceinline__ void wgmma_n128(float (&d)[64], uint64_t da, uint64_t db, uint32_t acc) {
  asm volatile(
      "{\n.reg .pred p;\nsetp.ne.u32 p, %66, 0;\n"
      "wgmma.mma_async.sync.aligned.m64n128k16.f32.bf16.bf16 "
      "{%0,%1,%2,%3,%4,%5,%6,%7,%8,%9,%10,%11,%12,%13,%14,%15,%16,%17,%18,%19,%20,%21,%22,%23,%24,%25,%26,%27,%28,%29,%30,%31,"
      "%32,%33,%34,%35,%36,%37,%38,%39,%40,%41,%42,%43,%44,%45,%46,%47,%48,%49,%50,%51,%52,%53,%54,%55,%56,%57,%58,%59,%60,%61,%62,%63}, "
      "%64, %65, p, 1, 1, 0, 1;\n}\n"
      : R64(d, 0)
      : "l"(da), "l"(db), "r"(acc));
}
#define WG128(C, ACC)                                                                                                      \
  asm volatile(                                                                                                            \
      "{\n.reg .b64 a, b;\nmov.b64 a, {%64, %66};\nmov.b64 b, {%65, %66};\n"                                               \
      "wgmma.mma_async.sync.aligned.m64n128k16.f32.bf16.bf16 "                                                             \
      "{%0,%1,%2,%3,%4,%5,%6,%7,%8,%9,%10,%11,%12,%13,%14,%15,%16,%17,%18,%19,%20,%21,%22,%23,%24,%25,%26,%27,%28,%29,%30,%31," \
      "%32,%33,%34,%35,%36,%37,%38,%39,%40,%41,%42,%43,%44,%45,%46,%47,%48,%49,%50,%51,%52,%53,%54,%55,%56,%57,%58,%59,%60,%61," \
      "%62,%63}, a, b, " ACC ", 1, 1, 0, 1;\n}\n"                                                                          \
      : Z16(C, d, 0), Z16(C, d, 16), Z16(C, d, 32), Z16(C, d, 48)                                                          \
      : "r"(da), "r"(db), "r"(0x40000040))
#define Z4(C, d, o) C(d[o + 0]), C(d[o + 1]), C(d[o + 2]), C(d[o + 3])
#define Z16(C, d, o) Z4(C, d, o), Z4(C, d, o + 4), Z4(C, d, o + 8), Z4(C, d, o + 12)
__device__ __forceinline__ void wgmma_n128z(float (&d)[64], uint32_t da, uint32_t db) { WG128("=f", "0"); }
__device__ __forceinline__ void wgmma_n128a(float (&d)[64], uint32_t da, uint32_t db) { WG128("+f", "1"); }
template <int N> __device__ __forceinline__ void fence_regs(float (&d)[N]) {
#pragma unroll
  for (int i = 0; i < N; i++) asm volatile("" : "+f"(d[i])::"memory");
}

__device__ __forceinline__ void mma16816(float (&d)[4], uint32_t a0, uint32_t a1, uint32_t a2, uint32_t a3, uint32_t b0,
                                         uint32_t b1) {
  asm("mma.sync.aligned.m16n8k16.row.col.f32.bf16.bf16.f32 {%0,%1,%2,%3}, {%4,%5,%6,%7}, {%8,%9}, {%0,%1,%2,%3};\n"
      : "+f"(d[0]), "+f"(d[1]), "+f"(d[2]), "+f"(d[3])
      : "r"(a0), "r"(a1), "r"(a2), "r"(a3), "r"(b0), "r"(b1));
}
__device__ __forceinline__ void mma16816_z(float (&d)[4], uint32_t a0, uint32_t a1, uint32_t a2, uint32_t a3, uint32_t b0,
                                           uint32_t b1) {
  asm("mma.sync.aligned.m16n8k16.row.col.f32.bf16.bf16.f32 {%0,%1,%2,%3}, {%4,%5,%6,%7}, {%8,%9}, {%10,%10,%10,%10};\n"
      : "=f"(d[0]), "=f"(d[1]), "=f"(d[2]), "=f"(d[3])
      : "r"(a0), "r"(a1), "r"(a2), "r"(a3), "r"(b0), "r"(b1), "f"(0.f));
}
__device__ __forceinline__ void ldsm4t(uint32_t (&r)[4], uint32_t a) {
  asm volatile("ldmatrix.sync.aligned.m8n8.x4.trans.shared.b16 {%0,%1,%2,%3}, [%4];\n"
               : "=r"(r[0]), "=r"(r[1]), "=r"(r[2]), "=r"(r[3]) : "r"(a) : "memory");
}
__device__ __forceinline__ void ldsm2t(uint32_t& r0, uint32_t& r1, uint32_t a) {
  asm volatile("ldmatrix.sync.aligned.m8n8.x2.trans.shared.b16 {%0,%1}, [%2];\n" : "=r"(r0), "=r"(r1) : "r"(a) : "memory");
}
__device__ __forceinline__ void st_async128(uint32_t a, uint32_t bar, uint32_t x, uint32_t y, uint32_t z, uint32_t w) {
  asm volatile("st.async.weak.shared::cluster.mbarrier::complete_tx::bytes.v4.b32 [%0], {%2,%3,%4,%5}, [%1];\n"
               ::"r"(a), "r"(bar), "r"(x), "r"(y), "r"(z), "r"(w) : "memory");
}
__device__ __forceinline__ void mbar_arrive(uint32_t a) {
  asm volatile("mbarrier.arrive.shared::cta.b64 _, [%0];\n" ::"r"(a) : "memory");
}
__device__ __forceinline__ void stsm4(uint32_t a, uint32_t r0, uint32_t r1, uint32_t r2, uint32_t r3) {
  asm volatile("stmatrix.sync.aligned.m8n8.x4.shared.b16 [%0], {%1,%2,%3,%4};\n"
               ::"r"(a), "r"(r0), "r"(r1), "r"(r2), "r"(r3) : "memory");
}
__device__ __forceinline__ void stsm4t(uint32_t a, uint32_t r0, uint32_t r1, uint32_t r2, uint32_t r3) {
  asm volatile("stmatrix.sync.aligned.m8n8.x4.trans.shared.b16 [%0], {%1,%2,%3,%4};\n"
               ::"r"(a), "r"(r0), "r"(r1), "r"(r2), "r"(r3) : "memory");
}
__device__ __forceinline__ uint2 lds64(uint32_t a) {
  uint2 v;
  asm volatile("ld.shared.v2.u32 {%0,%1}, [%2];\n" : "=r"(v.x), "=r"(v.y) : "r"(a) : "memory");
  return v;
}
__device__ __forceinline__ uint4 lds128(uint32_t a) {
  uint4 v;
  asm volatile("ld.shared.v4.u32 {%0,%1,%2,%3}, [%4];\n" : "=r"(v.x), "=r"(v.y), "=r"(v.z), "=r"(v.w) : "r"(a) : "memory");
  return v;
}
__device__ __forceinline__ void sts128(uint32_t a, uint32_t x, uint32_t y, uint32_t z, uint32_t w) {
  asm volatile("st.shared.v4.u32 [%0], {%1,%2,%3,%4};\n" ::"r"(a), "r"(x), "r"(y), "r"(z), "r"(w) : "memory");
}
__device__ __forceinline__ void sts64(uint32_t a, uint32_t x, uint32_t y) {
  asm volatile("st.shared.v2.u32 [%0], {%1,%2};\n" ::"r"(a), "r"(x), "r"(y) : "memory");
}
__device__ __forceinline__ uint32_t pack_bf16(float lo, float hi) {
  uint32_t r;
  asm("cvt.rn.bf16x2.f32 %0, %1, %2;\n" : "=r"(r) : "f"(hi), "f"(lo));
  return r;
}
__device__ __forceinline__ uint32_t bmul2(uint32_t a, uint32_t b) {
  uint32_t r;
  asm("mul.rn.bf16x2 %0, %1, %2;\n" : "=r"(r) : "r"(a), "r"(b));
  return r;
}
__device__ __forceinline__ uint32_t bmax2(uint32_t a, uint32_t b) {
  uint32_t r;
  asm("max.bf16x2 %0, %1, %2;\n" : "=r"(r) : "r"(a), "r"(b));
  return r;
}
__device__ __forceinline__ uint32_t bfma2(uint32_t a, uint32_t b, uint32_t c) {
  uint32_t r;
  asm("fma.rn.bf16x2 %0, %1, %2, %3;\n" : "=r"(r) : "r"(a), "r"(b), "r"(c));
  return r;
}
__device__ __forceinline__ uint32_t clock32() {
  uint32_t t;
  asm volatile("mov.u32 %0, %%clock;\n" : "=r"(t));
  return t;
}
__device__ __forceinline__ void prefetch_l2(const void* p) { asm volatile("prefetch.global.L2 [%0];\n" ::"l"(p)); }
__device__ __forceinline__ void cp_async16(uint32_t dst, const void* src, uint32_t srcbytes) {
  asm volatile("cp.async.cg.shared.global.L2::256B [%0], [%1], 16, %2;\n" ::"r"(dst), "l"(src), "r"(srcbytes) : "memory");
}
__device__ __forceinline__ uint32_t ld_acquire(const uint32_t* p) {
  uint32_t v;
  asm volatile("ld.acquire.gpu.global.u32 %0, [%1];\n" : "=r"(v) : "l"(p) : "memory");
  return v;
}
__device__ __forceinline__ uint32_t ld_relaxed(const uint32_t* p) {
  uint32_t v;
  asm volatile("ld.relaxed.gpu.global.u32 %0, [%1];\n" : "=r"(v) : "l"(p) : "memory");
  return v;
}
__device__ __forceinline__ void st_release(uint32_t* p, uint32_t v) {
  asm volatile("st.release.gpu.global.u32 [%0], %1;\n" ::"l"(p), "r"(v) : "memory");
}
__device__ __forceinline__ uint4 ld_b128(const uint4* p) {
  unsigned long long a, b;
  asm volatile("{\n.reg .b128 v;\nld.relaxed.gpu.global.b128 v, [%2];\nmov.b128 {%0, %1}, v;\n}\n" : "=l"(a), "=l"(b) : "l"(p) : "memory");
  return make_uint4((uint32_t)a, (uint32_t)(a >> 32), (uint32_t)b, (uint32_t)(b >> 32));
}
__device__ __forceinline__ void st_b128(uint4* p, uint32_t x, uint32_t y, uint32_t z, uint32_t w) {
  asm volatile("{\n.reg .b128 v;\nmov.b128 v, {%1, %2};\nst.relaxed.gpu.global.b128 [%0], v;\n}\n"
               ::"l"(p), "l"(x | (unsigned long long)y << 32), "l"(z | (unsigned long long)w << 32) : "memory");
}

struct Params {
  const __nv_bfloat16* x;
  const __nv_bfloat16* w;
  uint8_t tile[72];
  const __nv_bfloat16* q;
  const __nv_bfloat16* k;
  const __nv_bfloat16* v;
  const __nv_bfloat16* shift_k;
  const __nv_bfloat16* ssm_k;
  const __nv_bfloat16* ssm_D;
  const __nv_bfloat16* wo;
  __nv_bfloat16* out;
  uint32_t zero;
};

__device__ __forceinline__ uint32_t lds32(uint32_t a) {
  uint32_t v;
  asm volatile("ld.shared.u32 %0, [%1];\n" : "=r"(v) : "r"(a) : "memory");
  return v;
}
__device__ __forceinline__ float bf_lo(uint32_t v) {
  uint32_t r;
  asm("prmt.b32 %0, %1, 0, 0x1044;\n" : "=r"(r) : "r"(v));
  return __uint_as_float(r);
}
__device__ __forceinline__ float bf_hi(uint32_t v) { return __uint_as_float(v & 0xffff0000u); }
__device__ __forceinline__ float ex2(float x) {
  float r;
  asm("ex2.approx.ftz.f32 %0, %1;\n" : "=f"(r) : "f"(x));
  return r;
}
__device__ __forceinline__ float rcp(float x) {
  float r;
  asm("rcp.approx.ftz.f32 %0, %1;\n" : "=f"(r) : "f"(x));
  return r;
}

#define Q4(c, d, o) c(d[o + 0]), c(d[o + 1]), c(d[o + 2]), c(d[o + 3])
#define Q8(c, d, o) Q4(c, d, o), Q4(c, d, o + 4)
#define Q16(c, d, o) Q8(c, d, o), Q8(c, d, o + 8)
#define Q32(c, d) Q16(c, d, 0), Q16(c, d, 16)
#define L8 "{%0,%1,%2,%3,%4,%5,%6,%7}"
#define L16 "{%0,%1,%2,%3,%4,%5,%6,%7,%8,%9,%10,%11,%12,%13,%14,%15}"
#define L32 "{%0,%1,%2,%3,%4,%5,%6,%7,%8,%9,%10,%11,%12,%13,%14,%15,%16,%17,%18,%19,%20,%21,%22,%23,%24,%25,%26,%27,%28,%29,%30,%31}"
__device__ __forceinline__ void fft_rows(uint32_t (&d)[32], const uint32_t (&a)[2][4], uint64_t db) {
  asm volatile("wgmma.mma_async.sync.aligned.m64n128k16.f16.f16.f16 " L32 ", {%32,%33,%34,%35}, %36, 0, 1, 1, 1;\n"
               : Q32("=r", d) : "r"(a[0][0]), "r"(a[0][1]), "r"(a[0][2]), "r"(a[0][3]), "l"(db));
  asm volatile("wgmma.mma_async.sync.aligned.m64n128k16.f16.f16.f16 " L32 ", {%32,%33,%34,%35}, %36, 1, 1, 1, 1;\n"
               : Q32("+r", d) : "r"(a[1][0]), "r"(a[1][1]), "r"(a[1][2]), "r"(a[1][3]), "l"(db + 64));
}
template <int INV> __device__ __forceinline__ void fft_cols(uint32_t (&d)[8], const uint32_t (&a)[2][4], uint64_t db) {
  asm volatile("wgmma.mma_async.sync.aligned.m64n32k16.f16.f16.f16 " L8 ", {%8,%9,%10,%11}, %12, 0, 1, 1, %13;\n"
               : Q8("=r", d, 0) : "r"(a[0][0]), "r"(a[0][1]), "r"(a[0][2]), "r"(a[0][3]), "l"(db), "n"(INV));
  asm volatile("wgmma.mma_async.sync.aligned.m64n32k16.f16.f16.f16 " L8 ", {%8,%9,%10,%11}, %12, 1, 1, 1, %13;\n"
               : Q8("+r", d, 0) : "r"(a[1][0]), "r"(a[1][1]), "r"(a[1][2]), "r"(a[1][3]), "l"(db + (INV ? 16 : 64)), "n"(INV));
}
__device__ __forceinline__ void fft_back(float (&d)[16], uint64_t da, uint64_t db) {
  asm volatile("wgmma.mma_async.sync.aligned.m64n32k16.f32.f16.f16 " L16 ", %16, %17, 0, 1, 1, 1, 1;\n"
               : Q16("=f", d, 0) : "l"(da), "l"(db));
#pragma unroll
  for (int i = 1; i < 4; i++)
    asm volatile("wgmma.mma_async.sync.aligned.m64n32k16.f32.f16.f16 " L16 ", %16, %17, 1, 1, 1, 1, 1;\n"
                 : Q16("+f", d, 0) : "l"(da + 32 * i), "l"(db + 64 * i));
}
__device__ __forceinline__ uint32_t hmul2(uint32_t a, uint32_t b) {
  uint32_t r;
  asm("mul.rn.f16x2 %0, %1, %2;\n" : "=r"(r) : "r"(a), "r"(b));
  return r;
}
__device__ __forceinline__ uint32_t hadd2(uint32_t a, uint32_t b) {
  uint32_t r;
  asm("add.rn.f16x2 %0, %1, %2;\n" : "=r"(r) : "r"(a), "r"(b));
  return r;
}
__device__ __forceinline__ uint32_t hneg2(uint32_t a) {
  uint32_t r;
  asm("neg.f16x2 %0, %1;\n" : "=r"(r) : "r"(a));
  return r;
}
__device__ __forceinline__ uint32_t hfma2(uint32_t a, uint32_t b, uint32_t c) {
  uint32_t r;
  asm("fma.rn.f16x2 %0, %1, %2, %3;\n" : "=r"(r) : "r"(a), "r"(b), "r"(c));
  return r;
}
__device__ __forceinline__ uint32_t pack_f16(float lo, float hi) {
  uint32_t r;
  asm("cvt.rn.f16x2.f32 %0, %1, %2;\n" : "=r"(r) : "f"(hi), "f"(lo));
  return r;
}
__device__ __forceinline__ uint32_t bmaxabs2(uint32_t a, uint32_t b) {
  uint32_t r;
  asm("max.xorsign.abs.bf16x2 %0, %1, %2;\n" : "=r"(r) : "r"(a), "r"(b));
  return r;
}
struct C2 { uint32_t r, i; };
__device__ __forceinline__ C2 cmul(C2 a, C2 b) {
  return C2{hfma2(a.r, b.r, hneg2(hmul2(a.i, b.i))), hfma2(a.r, b.i, hmul2(a.i, b.r))};
}
__device__ __forceinline__ C2 cfma(C2 a, C2 b, C2 c) {
  return C2{hfma2(a.r, b.r, hfma2(hneg2(a.i), b.i, c.r)), hfma2(a.r, b.i, hfma2(a.i, b.r, c.i))};
}
__device__ __forceinline__ C2 crot(C2 z, C2 t) {
  const uint32_t r = hfma2(t.r, z.i, z.r), i = hfma2(t.i, r, z.i);
  return C2{hfma2(t.r, i, r), i};
}
__device__ __forceinline__ C2 cget(const uint32_t (&e)[8], int j, int b) { return C2{e[4 * j + b], e[4 * j + 2 + b]}; }
template <int N> __device__ __forceinline__ void fence_regs(uint32_t (&d)[N]) {
#pragma unroll
  for (int i = 0; i < N; i++) asm volatile("" : "+r"(d[i])::"memory");
}
__device__ __forceinline__ void ldsm4(uint32_t (&r)[4], uint32_t a) {
  asm volatile("ldmatrix.sync.aligned.m8n8.x4.shared.b16 {%0,%1,%2,%3}, [%4];\n"
               : "=r"(r[0]), "=r"(r[1]), "=r"(r[2]), "=r"(r[3]) : "r"(a) : "memory");
}

__device__ __forceinline__ uint32_t movm(uint32_t a) {
  uint32_t r;
  asm volatile("movmatrix.sync.aligned.m8n8.trans.b16 %0, %1;\n" : "=r"(r) : "r"(a));
  return r;
}
template <int C0, int H, bool T> __device__ __forceinline__ void attn_pack(const float (&acc)[96], uint32_t (&d)[8]) {
#pragma unroll
  for (int c = 0; c < 8; c++) {
    asm volatile("cvt.rn.bf16x2.f32 %0, %1, %2;\n" : "=r"(d[c]) : "f"(acc[4 * (C0 + c) + 2 * H + 1]), "f"(acc[4 * (C0 + c) + 2 * H]));
    if (T) d[c] = movm(d[c]);
  }
}
__device__ __forceinline__ void attn_qk(float (&s)[4], const uint32_t (&qlo)[8], const uint32_t (&qhi)[8],
                                        const uint32_t (&k)[8], int c) {
  mma16816_z(s, qlo[c], qhi[c], qlo[c + 1], qhi[c + 1], k[c], k[c + 1]);
  mma16816(s, qlo[c + 2], qhi[c + 2], qlo[c + 3], qhi[c + 3], k[c + 2], k[c + 3]);
}
template <int N> __device__ __forceinline__ void quad_softmax(float (&x)[N][2], uint32_t (&pp)[N]) {
  const float c2 = 1.4426950408889634f;
  uint32_t q[N], mx[N / 2];
#pragma unroll
  for (int n = 0; n < N; n++) {
    const uint32_t r = pack_bf16(x[n][0], x[n][1]);
    q[n] = bfma2(r, 0x3e353e35u, bmul2(r, 0x379e379eu));
    x[n][0] = bf_lo(q[n]);
    x[n][1] = bf_hi(q[n]);
  }
#pragma unroll
  for (int n = 0; n < N / 2; n++)
    mx[n] = bmax2(__byte_perm(q[2 * n], q[2 * n + 1], 0x5410), __byte_perm(q[2 * n], q[2 * n + 1], 0x7632));
#pragma unroll
  for (int o = 1; o <= 2; o++) {
#pragma unroll
    for (int n = 0; n < N / 2; n++) mx[n] = bmax2(mx[n], __shfl_xor_sync(0xffffffffu, mx[n], o));
  }
  float m[N], t[N];
#pragma unroll
  for (int n = 0; n < N / 2; n++) {
    m[2 * n] = bf_lo(mx[n]);
    m[2 * n + 1] = bf_hi(mx[n]);
  }
#pragma unroll
  for (int n = 0; n < N; n++) {
    const float nm = -m[n] * c2;
    x[n][0] = ex2(fmaf(x[n][0], c2, nm));
    x[n][1] = ex2(fmaf(x[n][1], c2, nm));
  }
#pragma unroll
  for (int n = 0; n < N; n += 2) {
    float u0, u1;
    asm("mma.sync.aligned.m16n8k8.row.col.f32.tf32.tf32.f32 {%0,%1,%2,%3}, {%4,%5,%6,%7}, {%8,%8}, {%9,%9,%9,%9};\n"
        : "=f"(t[n]), "=f"(u0), "=f"(t[n + 1]), "=f"(u1)
        : "r"(__float_as_uint(x[n][0])), "r"(__float_as_uint(x[n + 1][0])), "r"(__float_as_uint(x[n][1])),
          "r"(__float_as_uint(x[n + 1][1])), "r"(0x3f800000u), "f"(0.f));
  }
#pragma unroll
  for (int n = 0; n < N; n++) {
    const float inv = rcp(t[n]);
    pp[n] = pack_bf16(x[n][0] * inv, x[n][1] * inv);
  }
}
template <bool SPLIT>
__device__ __forceinline__ void attn_pv(uint32_t dst, const uint32_t (&vp)[8], const uint32_t (&vo)[8], int c, uint32_t pp,
                                        uint32_t maskLE) {
  const uint32_t b0 = pp & ~maskLE, b1 = pp & maskLE;
  float o[2][4];
#pragma unroll
  for (int i = 0; i < 2; i++) {
    if (SPLIT) {
      asm("mma.sync.aligned.m16n8k8.row.col.f32.bf16.bf16.f32 {%0,%1,%2,%3}, {%4,%5}, {%6}, {%7,%7,%7,%7};\n"
          : "=f"(o[i][0]), "=f"(o[i][1]), "=f"(o[i][2]), "=f"(o[i][3])
          : "r"(vp[c + 2 * i]), "r"(vp[c + 2 * i + 1]), "r"(b0), "f"(0.f));
      asm("mma.sync.aligned.m16n8k8.row.col.f32.bf16.bf16.f32 {%0,%1,%2,%3}, {%4,%5}, {%6}, {%0,%1,%2,%3};\n"
          : "+f"(o[i][0]), "+f"(o[i][1]), "+f"(o[i][2]), "+f"(o[i][3])
          : "r"(vo[c + 2 * i]), "r"(vo[c + 2 * i + 1]), "r"(b1));
    } else {
      mma16816_z(o[i], vp[c + 2 * i], vp[c + 2 * i + 1], vo[c + 2 * i], vo[c + 2 * i + 1], b0, b1);
    }
  }
  stsm4t(dst, pack_bf16(o[0][0], o[0][1]), pack_bf16(o[0][2], o[0][3]), pack_bf16(o[1][0], o[1][1]),
         pack_bf16(o[1][2], o[1][3]));
}

template <int MODE>
__global__ void __cluster_dims__(2, 1, 1) __launch_bounds__(NTHREADS, 1)
fused_kernel(const Params p, const __grid_constant__ CUtensorMap tmX, const __grid_constant__ CUtensorMap tmW,
             const __grid_constant__ CUtensorMap tmWo, const __grid_constant__ CUtensorMap tmWp,
             const __grid_constant__ CUtensorMap tmQ,
             const __grid_constant__ CUtensorMap tmOb,
             const __grid_constant__ CUtensorMap tmXh, const __grid_constant__ CUtensorMap tmWh) {
  extern __shared__ __align__(1024) uint8_t smem[];
  const int tid = threadIdx.x;
  if (tid >= 352) {
    const uint32_t i = (blockIdx.x & 127) * 16 + (tid & 15);
    prefetch_l2(tid & 16 ? (const char*)p.w + i * 128 : (const char*)p.x + i * 2048);
  }
  const uint32_t sb = smem_u32(smem);
  const int rank = blockIdx.x & 1;
  const bool halo_cta = blockIdx.x < 4;
  if (halo_cta && MODE != 0) return;
  const int tile = p.tile[blockIdx.x >> 1];
  const int rg = tile >> 3, hp = (tile & 7) * 2 + rank;
  const int par = rg >> 2, gidx = rg & 3;
  if (tid < 256 && !halo_cta && MODE != 2) {
    const uint32_t r = tid >> 3, c = tid & 7;
    asm volatile(
        "cp.async.cg.shared.global [%0 + 98304], [%1], 16;\ncp.async.cg.shared.global [%0 + 102400], [%1 + 2048], 16;\n"
        "cp.async.cg.shared.global [%0 + 106496], [%1 + 4096], 16;\ncp.async.cg.shared.global [%0], [%2], 16;\n"
        "cp.async.cg.shared.global [%0 + 4096], [%2 + 131072], 16;\ncp.async.cg.shared.global [%0 + 8192], [%2 + 262144], 16;\n"
        "cp.async.cg.shared.global [%0 + 12288], [%2 + 393216], 16;\ncp.async.cg.shared.global [%0 + 16384], [%2 + 524288], 16;\n"
        "cp.async.cg.shared.global [%0 + 20480], [%2 + 655360], 16;\ncp.async.cg.shared.global [%0 + 24576], [%2 + 786432], 16;\n"
        "cp.async.cg.shared.global [%0 + 28672], [%2 + 917504], 16;\ncp.async.commit_group;\n"
        ::"r"(sb + r * 128 + ((c ^ (r & 7)) << 4)), "l"((const char*)p.w + (r * 6144 + c * 16 + hp * 128)),
        "l"((const char*)p.x + (r * 4096 + c * 16 + gidx * 1048576 + par * 2048)) : "memory");
    static_assert(OFF_1B == 98304, "offsets above");
  }
  const uint32_t bars = sb + OFF_BAR;
  const int lane = tid & 31, warp = __shfl_sync(0xffffffffu, tid >> 5, 0);
  const int grp = par * 4 + (hp >> 2), mem = gidx * 2 + ((hp >> 1) & 1);
  const int rb2 = par * 8 + mem, cb2 = (grp & 3) * 2 + rank;
  const int chb = grp * 16 + mem * 2 + rank;
  const int cta = rg * 16 + hp;
  const int hsel = rb2 & 1;

  if (warp >= 8) {
    asm volatile("setmaxnreg.dec.sync.aligned.u32 %0;\n" :: "n"(REG_HELP));
    auto halo_issue = [&](int n, int s) {
      const uint32_t fb = bars + 8 * ((n & 1 ? BAR_FULL2 : BAR_FULLB) + s), st = sb + s * STGH;
      tma_load_3d(st + 8192, &tmWh, fb, 0, (n >> 1) * 64, 16 + (n & 1) * 16 + blockIdx.x * 4);
      tma_load_4d(st, &tmXh, fb, (n >> 1) * 64, 248, 0, 0);
      mbar_expect_tx(fb, STGH - 2048);
    };
    if (tid == 256) {
      prefetch_tmap(halo_cta ? &tmXh : &tmX);
#pragma unroll
      for (int i = 0; i < NS1B; i++) mbar_init(bars + 8 * (BAR_FULLB + i), 1);
#pragma unroll
      for (int i = 0; i < NS1A; i++) mbar_init(bars + 8 * (BAR_FULLA + i), 1);
      asm volatile("fence.mbarrier_init.release.cluster;\n" ::: "memory");
      if (!halo_cta && MODE != 2) {
        mbar_expect_tx(bars + 8 * (BAR_FULLB + 1), STG1B);
        tma_load_3d(sb + OFF_1B + 1 * STG1B, &tmW, bars + 8 * (BAR_FULLB + 1), hp * 64, 32, 0);
        mbar_expect_tx(bars + 8 * (BAR_FULLA + 1), STG1A);
        tma_load_3d(sb + STG1A, &tmX, bars + 8 * (BAR_FULLA + 1), 64, par, gidx * 256);
        tma_load_3d(sb + STG1A + 16384, &tmX, bars + 8 * (BAR_FULLA + 1), 64, par, gidx * 256 + 128);
        mbar_expect_tx(bars + 8 * (BAR_FULLB + 2), STG1B);
        tma_load_3d(sb + OFF_1B + 2 * STG1B, &tmW, bars + 8 * (BAR_FULLB + 2), hp * 64, 64, 0);
        mbar_arrive(bars + 8 * BAR_FULLA);
        mbar_arrive(bars + 8 * BAR_FULLB);
      } else if (halo_cta) {
        halo_issue(0, 0);
      }
    } else if (tid >= 289 && tid < 289 + 48 && tid != 320) {
      const uint32_t i = tid - 289 - (tid > 320), b = blockIdx.x & 127;
      if (MODE != 2) prefetch_l2(i < 16 ? (const char*)p.x + (b * 16 + i) * 2048 + 128 : (const char*)p.w + (2048 + b * 31 + i - 16) * 128);
    } else if (tid == 288) {
#pragma unroll
      for (int i = 0; i < NS1A; i++) mbar_init(bars + 8 * (BAR_EMPTYA + i), 4);
#pragma unroll
      for (int i = 0; i < NS1B; i++) mbar_init(bars + 8 * (BAR_EMPTYB + i), 2);
      mbar_init(bars + 8 * BAR_X, 3);
      mbar_init(bars + 8 * BAR_TAB, 16);
      mbar_init(bars + 8 * BAR_U, 1);
      mbar_init(bars + 8 * BAR_H, 1);
      mbar_init(bars + 8 * BAR_Q, 1);
      mbar_init(bars + 8 * BAR_LAND, 5);
      mbar_init(bars + 8 * (BAR_LAND + 1), 5);
      asm volatile("fence.mbarrier_init.release.cluster;\n" ::: "memory");
    } else if (tid == 320) {
#pragma unroll
      for (int i = 0; i < NS2; i++) {
        mbar_init(bars + 8 * (BAR_FULL2 + i), 1);
        mbar_init(bars + 8 * (BAR_EMPTY2 + i), 2);
        mbar_init(bars + 8 * (BAR_EMPTY2B + i), 2);
      }
      asm volatile("fence.mbarrier_init.release.cluster;\n" ::: "memory");
    } else if (tid == 352) {
#pragma unroll
      for (int i = 0; i < 4; i++) mbar_init(bars + 8 * (BAR_Y + i), i < 2 ? 4 : i == 2 ? 10 : 8);
      mbar_init(bars + 8 * BAR_XFREE, 1);
#pragma unroll
      for (int i = 0; i < 9; i++) mbar_init(bars + 8 * (BAR_KH + i), 1);
      asm volatile("fence.mbarrier_init.release.cluster;\n" ::: "memory");
    }
    __syncwarp();
    cluster_sync_all();
    if (warp == 8) PROF2(24);
    const int hw = warp - 8;
    const int lr = lane & 7, lm = lane >> 3;
    auto g1_issue_a = [&](int j, int s) {
      const uint32_t fb = bars + 8 * (BAR_FULLA + s);
      mbar_expect_tx(fb, STG1A);
      tma_load_3d_mc(sb + s * STG1A + rank * 16384, &tmX, fb, j * 64, par, gidx * 256 + rank * 128);
    };
    auto g1_issue_b = [&](int kb, int s) {
      const uint32_t fb = bars + 8 * (BAR_FULLB + s);
      mbar_expect_tx(fb, STG1B);
      tma_load_3d(sb + OFF_1B + s * STG1B, &tmW, fb, hp * 64, kb * 32, 0);
    };
    auto g2_k = [&](int kb) { return (kb < 2 ? hp : kb < 4 ? hp & 14 : hp & 12) ^ kb; };
    auto g2_issue_b = [&](uint32_t fb, uint32_t bytes, uint32_t dst, int k0, bool whole) {
      if (whole) {
        tma_load_3d(dst, &tmWo, fb, 0, k0, cb2 * 2);
      } else {
#pragma unroll
        for (int i = 0; i < 4; i++)
          tma_load_3d(dst + (i & 1) * XT + (i >> 1) * 4 * XT, &tmWp, fb, 0, k0 + (i >> 1) * 32, cb2 * 2 + (i & 1));
      }
      mbar_expect_tx(fb, bytes);
    };
    auto send_y = [&](uint32_t o, uint32_t step, int half) {
      const uint32_t peer = mapa(sb, rank ^ 1);
      o += OFF_X + (rank ^ 1) * 4096 + half * 2048 + lane * 16;
      uint4 a[8];
#pragma unroll
      for (int i = 0; i < 8; i++) a[i] = lds128(sb + o + (i >> 2) * step + (i & 2) * (XT / 2) + (i & 1) * 512);
#pragma unroll
      for (int i = 0; i < 8; i++)
        st_async128(peer + o + 1024 + (i >> 2) * step + (i & 2) * (XT / 2) + (i & 1) * 512,
                    peer + OFF_BAR + 8 * (BAR_LAND + half), a[i].x, a[i].y, a[i].z, a[i].w);
    };

    if (halo_cta) {
      if (hw == 0) {
        int s = 1, ph = 1;
#pragma unroll 1
        for (int n = 1; n < 32; n++) {
          mbar_wait(bars + 8 * (BAR_EMPTYB + s), ph);
          if (elect_one()) halo_issue(n, s);
          if (++s == NS1B) { s = 0; ph ^= 1; }
        }
      }
      __syncwarp();
    } else if (hw == 0) {
      uint32_t epoch = 0;
      if (MODE == 2) {
        if (lane < NS2) mbar_arrive_cluster_n(mapa(bars, rank) + 8 * (BAR_EMPTY2 + lane), 2);
      } else {
      if (lane == 0) {
        mbar_expect_tx(bars + 8 * BAR_U, 32768);
        mbar_expect_tx(bars + 8 * BAR_LAND, 8192);
        mbar_expect_tx(bars + 8 * (BAR_LAND + 1), 8192);
        mbar_expect_tx(bars + 8 * BAR_Q, 32768);
        prefetch_tmap(&tmQ);
      }
      {
        int sa = 2, pha = 1, sbb = 3, phb = 1;
#pragma unroll 1
        for (int kb = 3; kb < 32; kb++) {
          if (!(kb & 1)) {
            mbar_wait(bars + 8 * (BAR_EMPTYA + sa), pha);
            if (elect_one()) g1_issue_a(kb >> 1, sa);
            if (++sa == NS1A) { sa = 0; pha ^= 1; }
          }
          mbar_wait(bars + 8 * (BAR_EMPTYB + sbb), phb);
          if (elect_one()) g1_issue_b(kb, sbb);
          __syncwarp();
          if (kb == 4) epoch = ld_relaxed(g_flag_o + FS * cta);
          if (kb == 4) PROF2(27);
          if (++sbb == NS1B) { sbb = 0; phb ^= 1; }
        }
      }
      auto q_issue = [&](int i) {
        mbar_wait(bars + 8 * (i ? BAR_EMPTYB + 3 : BAR_EMPTYA + 1), i);
        if (elect_one())
          asm volatile(
              "cp.async.bulk.tensor.5d.shared::cluster.global.mbarrier::complete_tx::bytes [%0], [%1, {%3, %4, %4, %4, %5}], [%2];\n"
              ::"r"(sb + (i ? OFF_Q1 : OFF_Q0)), "l"(&tmQ), "r"(bars + 8 * BAR_Q), "r"((chb & ~1) * 8), "r"(0), "r"(rank * 32 + i * 64)
              : "memory");
        __syncwarp();
      };
      epoch++;
      if (lane == 0) {
        asm volatile("st.shared.u32 [%0], %1;\n" ::"r"(sb + OFF_EX - 4), "r"(epoch) : "memory");
        prefetch_tmap(&tmWo);
        prefetch_tmap(&tmWp);
        prefetch_tmap(&tmOb);
      }
      __syncwarp();
      {
        uint4 h[6] = {};
        if (gidx != 0) {
#pragma unroll 1
          for (int n = 0; n < SPIN_LIMIT; n++) {
            bool ok = true;
#pragma unroll
            for (int i = 0; i < 6; i++) h[i] = ld_b128(g_halo + cta * 192 + i * 32 + lane);
#pragma unroll
            for (int i = 0; i < 6; i++) ok = ok && h[i].w == epoch;
            if (__all_sync(0xffffffffu, ok)) break;
          }
          PROF(18);
        }
        q_issue(0);
        sts128(sb + OFF_KH + lane * 16, h[0].x, h[0].y, h[0].z, h[1].x);
        sts128(sb + OFF_KH + 512 + lane * 16, h[1].y, h[1].z, h[2].x, h[2].y);
        sts64(sb + OFF_KH + 1024 + lane * 8, h[3].x, h[3].y);
        sts64(sb + OFF_KH + 1280 + lane * 8, h[3].z, h[4].x);
        sts64(sb + OFF_KH + 1536 + lane * 8, h[4].y, h[4].z);
        sts64(sb + OFF_KH + 1792 + lane * 8, h[5].x, h[5].y);
        __syncwarp();
        if (lane == 0) mbar_arrive(bars + 8 * BAR_KH);
      }
      q_issue(1);
      const uint32_t rb = mapa(bars, lane & 1);
      nb_sync(NB_OREADY, 288);
      if (lane == 0) {
        asm volatile("cp.async.bulk.global.shared::cta.bulk_group [%0], [%1], %2;\n" ::"l"(g_o + (size_t)cta * 16384),
                     "r"(sb + OFF_OP), "r"(32768) : "memory");
        bulk_commit();
      }
      if (lane < 2) {
#pragma unroll
        for (int i = 0; i < 4; i++) mbar_arrive_cluster(rb + 8 * (BAR_EMPTY2 + i + i / 2));
      }
      if (lane == 0) {
        bulk_wait0();
        st_release(g_flag_o + FS * cta, epoch);
      }
      __syncwarp();
      PROF2(17);
      if (lane < 2) mbar_arrive_cluster(rb + 8 * (BAR_EMPTY2 + 2));
      }
      if (MODE != 1) {
        const __nv_bfloat16* osrc = g_o + (size_t)(rb2 >> 1) * 16 * 16384 + hsel * 8192;
        mbar_wait(bars + 8 * (BAR_EMPTY2 + 1), 0);
        if (elect_one()) {
          if (MODE == 0) {
            asm volatile("cp.async.bulk.shared::cluster.shared::cta.mbarrier::complete_tx::bytes [%0], [%1], %2, [%3];\n"
                         ::"r"(mapa(sb + g2_a(1, hsel), rank ^ 1)), "r"(sb + g2_a(0, hsel)), "r"(16384),
                         "r"(mapa(bars + 8 * (BAR_FULL2 + 1), rank ^ 1)) : "memory");
          } else {
            bulk_load(sb + g2_a(0, hsel), osrc + hp * 16384, 16384, bars + 8 * BAR_FULL2);
            bulk_load(sb + g2_a(1, hsel), osrc + (hp ^ 1) * 16384, 16384, bars + 8 * (BAR_FULL2 + 1));
          }
#pragma unroll
          for (int kb = 1; kb < 3; kb++)
            g2_issue_b(bars + 8 * (BAR_FULL2 + kb), STG2, sb + g2_b(kb, 0), g2_k(kb) * 64, true);
        }
        __syncwarp();
      }
      if (MODE != 2) {
        mbar_wait(bars + 8 * (BAR_Y + 2), 0);
        send_y(0, 4 * XT, 1);
        fence_async_smem();
        __syncwarp();
      }
      if (MODE != 1) {
        int s = 3, k0 = g2_k(3) * 64;
        uint32_t wbar = bars + 8 * (BAR_Y + 2), fb = bars + 8 * (BAR_FULL2 + 3), dst = sb + g2_b(3, rank), ph = MODE ? 1 : 0;
        int whole = 0;
#pragma unroll 1
        for (int kb = 3; kb < 16;) {
          mbar_wait(wbar, ph);
          if (elect_one()) g2_issue_b(fb, STG2, dst, k0, whole);
          __syncwarp();
          kb++;
          if (++s == NS2) { s = 0; ph = kb == 2 * NS2; }
          wbar = bars + 8 * (kb == 4 ? BAR_XFREE : BAR_EMPTY2B + s);
          fb = bars + 8 * (BAR_FULL2 + s);
          dst = sb + g2_b(s, rank);
          k0 = ((hp & 12) ^ kb) * 64;
          whole = s < 3;
          asm volatile("" : "+r"(fb), "+r"(k0), "+r"(whole));
        }
      }
      __syncwarp();
    } else {
      if (MODE != 2) {
      const float dall = __bfloat162float(p.ssm_D[chb * 8 + lr]);
      {
        const int g = lane >> 2, t = lane & 3;
        uint32_t w[2][4];
#pragma unroll
        for (int h = 0; h < 2; h++) {
          const uint2 x = __ldg(reinterpret_cast<const uint2*>(p.shift_k + ((chb & ~1) * 8 + h * 8 + g) * 4));
          w[h][0] = __byte_perm(x.x, x.x, 0x1010);
          w[h][1] = __byte_perm(x.x, x.x, 0x3232);
          w[h][2] = __byte_perm(x.y, x.y, 0x1010);
          w[h][3] = __byte_perm(x.y, x.y, 0x3232);
        }
        auto swz = [](int r) { return (((r & 29) | ((r ^ (r >> 2)) & 2)) << 5) | (r & 16); };
        const uint32_t kring = sb + OFF_X + 4096 + (hw - 1) * 2 * XT, vring = kring + XT;
        const int s0 = rank * 32 + (hw - 1) * 11, s1 = hw == 3 ? rank * 32 + 32 : s0 + 11;
        const size_t goff = (size_t)(s0 * 32 + (lane >> 1)) * DM + (chb & ~1) * 8 + (lane & 1) * 8;
        const __nv_bfloat16* kg = p.k + goff;
        const __nv_bfloat16* vg = p.v + goff;
        const uint32_t d0 = swz(lane >> 1) ^ ((lane & 1) << 4), d1 = swz(16 + (lane >> 1)) ^ ((lane & 1) << 4);
        auto issue = [&](int st) {
          const uint32_t a = kring + ((st & 3) << 10);
          asm volatile("cp.async.cg.shared.global.L2::256B [%0], [%2], 16;\n"
                       "cp.async.cg.shared.global.L2::256B [%1], [%2 + 32768], 16;\n"
                       "cp.async.cg.shared.global.L2::256B [%0 + 8192], [%3], 16;\n"
                       "cp.async.cg.shared.global.L2::256B [%1 + 8192], [%3 + 32768], 16;\n"
                       ::"r"(a + d0), "r"(a + d1), "l"(kg), "l"(vg) : "memory");
          kg += 32 * DM;
          vg += 32 * DM;
          asm volatile("" : "+l"(kg), "+l"(vg));
        };
        const int xa = 8 * (lr >> 1) + 2 * lm + (lr & 1), xb = 8 * (lr >> 1) - 4 + 2 * (lm & 1) + (lr & 1);
        const uint32_t la = swz(xa), lb = swz(xb & 31);
        const int backb = xb < 0 ? 1 : 0;
        const uint32_t ud[2] = {mapa(sb + OFF_X + g * XT + t * 16, 0), mapa(sb + OFF_X + g * XT + t * 16, 1)};
        const uint32_t ub[2] = {mapa(bars + 8 * BAR_U, 0), mapa(bars + 8 * BAR_U, 1)};
        if (tid == 320) prefetch_l2(g_tab + (chb & 63) * 32);
        if (lane == 0) mbar_wait(bars + 8 * (BAR_FULLB + NS1B - 1), 0);
        __syncwarp();
        if (lane >= 24) cp_async16(kring + (((s0 - 1) & 3) << 10) + d1, s0 > 0 ? kg - 16 * DM : kg, s0 > 0 ? 16 : 0);
        issue(s0);
        asm volatile("cp.async.commit_group;\n" ::: "memory");
        issue(s0 + 1);
        asm volatile("cp.async.commit_group;\n" ::: "memory");
        const __nv_bfloat16* hg = p.ssm_k + (size_t)chb * 8 * SEQ + lane * 64;
        uint32_t tn = clock32();
#pragma unroll 1
        for (int st = s0; st < s1; st++) {
          tn += PSTEP;
          while ((int)(clock32() - tn) < 0) __nanosleep(100);
          if (st + 2 < s1) issue(st + 2);
          if (hw == 1 && st - s0 < 8) prefetch_l2(hg);
          hg += SEQ;
          asm volatile("" : "+l"(hg));
          asm volatile("cp.async.commit_group;\n" ::: "memory");
          asm volatile("cp.async.wait_group 2;\n" ::: "memory");
          __syncwarp();
#pragma unroll
          for (int h = 0; h < 2; h++) {
            uint32_t e[6], vv[4], e4[4];
            ldsm4t(e4, kring + ((st & 3) << 10) + (la ^ (h << 4)));
            ldsm2t(e[0], e[1], kring + (((st - backb) & 3) << 10) + (lb ^ (h << 4)));
            ldsm4t(vv, vring + ((st & 3) << 10) + (la ^ (h << 4)));
            e[2] = e4[0]; e[3] = e4[1]; e[4] = e4[2]; e[5] = e4[3];
            uint32_t o[5];
#pragma unroll
            for (int i = 0; i < 5; i++) o[i] = __byte_perm(e[i], e[i + 1], 0x5432);
#pragma unroll
            for (int i = 0; i < 4; i++) {
              uint32_t a = bmul2(o[i], w[h][3]);
              a = bfma2(e[i + 1], w[h][2], a);
              a = bfma2(o[i + 1], w[h][1], a);
              a = bfma2(e[i + 2], w[h][0], a);
              vv[i] = bmul2(a, vv[i]);
            }
            st_async128(ud[h] + (st ^ (g & 1)) * 64, ub[h], vv[0], vv[1], vv[2], vv[3]);
          }
          __syncwarp();
        }
        fence_async_smem();
        PROF(16);
      }
      nb_sync(NB_HELP3, 96);
      if (hw == 1 && elect_one()) {
        mbar_expect_tx(bars + 8 * BAR_H, 8 * 4096 + 6144);
#pragma unroll 1
        for (int c = 0; c < 8; c++)
          bulk_load(sb + OFF_X + c * XT + 4096, p.ssm_k + (size_t)(chb * 8 + c) * SEQ, 4096, bars + 8 * BAR_H);
        bulk_load(sb + OFF_T16, g_tab, 2048, bars + 8 * BAR_H);
        bulk_load(sb + OFF_T32, g_tab + 512, 4096, bars + 8 * BAR_H);
      }
      __syncwarp();
      {
        if (hw == 3) {
          const char* wo = (const char*)p.wo + chb * 16384 + lane * 128;
#pragma unroll
          for (int i = 0; i < 4; i++) prefetch_l2(wo + i * 4096);
        }
        const int ck = 16 * (lane >> 4) + 2 * lr + (((lane >> 3) ^ (lane >> 2)) & 1);
        const uint32_t xo = (ck >> 1) * 64, xs = ((ck & 1) ^ (lr >> 1)) << 4;
#pragma unroll 1
        for (int job = hw - 1; job < 16; job += 3) {
          const int c = job & 7;
          uint4 a[8];
          float dv = __shfl_sync(0xffffffffu, dall, c);
          if (job < 8 || lane) dv = 0.f;
          const uint32_t xt = sb + OFF_X + c * XT + (job >> 3) * 4096;
          mbar_wait(bars + 8 * (job < 8 ? BAR_U : BAR_H), 0);
#pragma unroll
          for (int i = 0; i < 8; i++) a[i] = lds128(xt + i * 512 + ((ck ^ (job < 8 ? (c & 1) << 2 : 0)) << 4));
          dv += bf_lo(a[0].x);
          uint32_t m[2] = {bmaxabs2(pack_bf16(dv, 0.f), bmaxabs2(a[0].x, a[0].y)), bmaxabs2(a[0].z, a[0].w)};
#pragma unroll
          for (int i = 1; i < 8; i++) {
            m[0] = bmaxabs2(bmaxabs2(m[0], a[i].x), a[i].y);
            m[1] = bmaxabs2(bmaxabs2(m[1], a[i].z), a[i].w);
          }
          m[0] = bmaxabs2(m[0], m[1]);
          const int f = max(252 - (int)(__reduce_max_sync(0xffffffffu, max(m[0] & 0x7fffu, (m[0] >> 16) & 0x7fffu)) >> 7), 1);
          if (lane == 0) asm volatile("st.shared.u32 [%0], %1;\n" ::"r"(sb + OFF_EX + job * 4), "r"(f) : "memory");
          if (f < 113) {
#pragma unroll
            for (int i = 0; i < 8; i++)
              a[i] = make_uint4(bmul2(a[i].x, f * 0x00800080u), bmul2(a[i].y, f * 0x00800080u), bmul2(a[i].z, f * 0x00800080u),
                                bmul2(a[i].w, f * 0x00800080u));
          }
          const uint32_t mul = (f < 113 ? 15 : f - 112) * 0x00800080u;
          auto cv = [&](uint32_t x) {
            x = bmul2(x, mul);
            return (x & 0x0fff0fffu) * 7 + x;
          };
          const uint32_t dst = xt + xo;
#pragma unroll
          for (int i = 0; i < 8; i++)
            sts128(dst + (i >> 2) * 2048 + (i & 1) * 1024 + (xs ^ ((i & 2) << 4)),
                   i ? cv(a[i].x) : __byte_perm(pack_f16(dv * __uint_as_float(f << 23), 0.f), cv(a[i].x), 0x7610), cv(a[i].y),
                   cv(a[i].z), cv(a[i].w));
        }
        fence_async_smem();
        __syncwarp();
        if (lane == 0) mbar_arrive(bars + 8 * BAR_X);
        PROF(19);
      }
      if (hw < 3) {
        int lane, lr, lm;
        asm volatile("mov.u32 %0, %%laneid;\n" : "=r"(lane));
        lr = lane & 7;
        lm = lane >> 3;
#pragma unroll 1
        for (int n = 0; n < SPIN_LIMIT && !mbar_try(bars + 8 * (BAR_Y + hw - 1), 0); n++) __nanosleep(100);
        send_y((hw - 1) * 4 * XT, 2 * XT, 0);
        __syncwarp();
        if (lane == 0) mbar_arrive(bars + 8 * (BAR_Y + 2));
        PROF(32);
        const int c8 = 2 * lm + (lr & 1), src = (lr >> 1) & 1;
        uint32_t fa = sb + OFF_X + c8 * XT + rank * 4096 + (src == rank ? 0 : 1024) + (hw - 1) * 512;
        const uint32_t fx = ((lr >> 2) ^ ((lr & 3) << 1)) << 4;
        uint32_t qa = sb + OFF_Q0 + (hw - 1) * 8192 + (lane >> 3) * 128 + (lane & 2) * 32 + (lane & 4) * 8 + (lane & 1) * 16;
        uint4* og = reinterpret_cast<uint4*>(p.out + (size_t)(rank * 512 + (hw - 1) * 256 + (lane & 2) * 4 + (lane >> 2)) * (2 * DM) +
                                             (chb & ~1) * 8 + (lane & 1) * 8);
        mbar_wait(bars + 8 * BAR_Q, 0);
        uint32_t tn = 0;
        const uint32_t pace = hw == 2 ? FPACE2 : FPACE;
#pragma unroll 1
        for (int j = 0; j < 4; j++) {
          if (!(j & 1)) {
            mbar_wait(bars + 8 * (BAR_LAND + (j >> 1)), 0);
            tn = clock32() + (j ? 0 : (hw - 1) * (FPACE / 2));
            PROF2(33 + j * 2);
          }
#pragma unroll
          for (int i = 0; i < 8; i++) {
            if (i == 2 && j == 0 && hw == 2) {
              mbar_wait(bars + 8 * (BAR_Y + 3), 0);
              send_y(2 * XT, 4 * XT, 1);
              fence_async_smem();
              __syncwarp();
              if (lane == 0) mbar_arrive(bars + 8 * BAR_XFREE);
              tn = clock32();
            }
            uint32_t y[4];
            const uint4 q = lds128(qa + i * 512);
            ldsm4t(y, fa + (i >> 2) * 128 + (fx ^ ((i & 3) << 5) ^ ((i >> 2) << 4)));
            while ((int)(clock32() - tn) < 0) __nanosleep(50);
            tn += j == 3 ? FPACE3 : pace;
            og[i * 16 * (2 * DM / 8)] = make_uint4(bmul2(q.x, y[0]), bmul2(q.y, y[1]), bmul2(q.z, y[2]), bmul2(q.w, y[3]));
          }
          qa += j & 1 ? OFF_Q1 - OFF_Q0 - 4096 : 4096;
          fa += j & 1 ? 2048 - 256 : 256;
          og += (j & 1 ? 1024 - 128 : 128) * (2 * DM / 8);
        }
        PROF(22);
      }
      }
      if (MODE != 1 && hw == 3) {
        if (MODE == 0) nb_sync(NB_G1END, 288);
        if (elect_one()) g2_issue_b(bars + 8 * BAR_FULL2, MODE ? STG2 : STG2 / 2, sb + g2_b(0, 0), hp * 64, true);
        __syncwarp();
        const __nv_bfloat16* osrc = g_o + (size_t)(rb2 >> 1) * 16 * 16384 + hsel * 8192;
        if (MODE == 0) __nanosleep(1500);
        mbar_wait(bars + 8 * (BAR_EMPTY2 + 2), 0);
        const uint32_t epoch = lds32(sb + OFF_EX - 4);
        const uint32_t* flag = g_flag_o + FS * ((rb2 >> 1) * 16 + g2_k(lane & 15));
        uint32_t ready = MODE == 0 ? 0u : ~0u;
        int s = 1, ph = 0;
#pragma unroll 1
        for (int kb = 2; kb < 16; kb++) {
          if (++s == NS2) { s = 0; ph ^= 1; }
          uint32_t fb = bars + 8 * (BAR_FULL2 + s), dst = sb + g2_a(s, hsel) + rank * 8192;
          const __nv_bfloat16* src = osrc + rank * 4096 + (uint32_t)g2_k(kb) * 16384;
          asm volatile("" : "+r"(fb), "+r"(dst), "+l"(src));
          if (!(ready >> kb & 1)) {
#pragma unroll 1
            for (int n = 0; n < SPIN_LIMIT && !(ready >> kb & 1); n++)
              ready = __ballot_sync(0xffffffffu, ld_acquire(flag) == epoch);
            fence_async_all();
          }
          if (kb == 2) PROF(21);
          if (MODE == 0 && kb == 4 && rank == 1) mbar_wait(bars + 8 * BAR_TAB, 0);
          mbar_wait(fb + 8 * (BAR_EMPTY2 - BAR_FULL2), ph);
          if (elect_one()) {
            asm volatile(
                "cp.async.bulk.shared::cluster.global.mbarrier::complete_tx::bytes.multicast::cluster [%0], [%1], %2, [%3], %4;\n"
                ::"r"(dst), "l"(src), "r"(8192), "r"(fb), "h"((uint16_t)3) : "memory");
          }
          __syncwarp();
        }
      }
    }
    cluster_sync_all();
    PROF_DUMP();
  } else {
    asm volatile("barrier.cluster.arrive.relaxed.aligned;\n" ::: "memory");
    asm volatile("setmaxnreg.inc.sync.aligned.u32 %0;\n" :: "n"(REG_MATH));
    if (halo_cta || MODE == 2) asm volatile("barrier.cluster.wait.aligned;\n" ::: "memory");
    if (warp == 0) PROF2(26);
    const int wg = warp >> 2;
    const int wtid = tid & 127;
    const bool signaller = (wtid == 0) || (wtid == 32);
    const uint32_t rbars = mapa(bars, wtid >> 5 & 1);

    if (halo_cta) {
      const uint32_t epoch = ld_relaxed(g_flag_o + FS * (16 + blockIdx.x * 4)) + 1;
      float acc0[64], acc1[64];
      int s = wg, ph = 0;
#pragma unroll 1
      for (int kb = 0; kb < 16; kb++) {
        mbar_wait(bars + 8 * ((wg ? BAR_FULL2 : BAR_FULLB) + s), ph);
        const uint32_t st = sb + s * STGH;
        const uint64_t da = mkdesc(st, 16, 1024, 1);
        const uint64_t db = mkdesc(st + 8192, 8192, 1024, 1);
        wg_fence();
#pragma unroll
        for (int kk = 0; kk < 4; kk++) {
          wgmma_n128(acc0, da + 2 * kk, db + 128 * kk, kb + kk);
          wgmma_n128(acc1, da + 2 * kk, db + 1024 + 128 * kk, kb + kk);
        }
        wg_commit();
        wg_wait<0>();
        if (kb == 15) PROF(37);
        if (wtid < 2) mbar_arrive(bars + 8 * (BAR_EMPTYB + s));
        if ((s += 2) >= NS1B) s -= NS1B;
        if (s == wg) ph ^= 1;
      }
      fence_regs(acc0);
      fence_regs(acc1);
      if ((warp & 3) != 3) {
        auto put = [&](const float (&acc)[64], int hp0) {
#pragma unroll
          for (int n = 0; n < 4; n++) {
            uint32_t x[8];
#pragma unroll
            for (int c = 0; c < 8; c++) {
              x[c] = pack_bf16(acc[32 * (n >> 1) + 4 * c + 2 * (n & 1)], acc[32 * (n >> 1) + 4 * c + 2 * (n & 1) + 1]);
              if (wg) x[c] = movm(x[c]);
            }
            uint4* dst = g_halo + (((n & 1) * 4 + (warp & 3) + 1) * 16 + blockIdx.x * 4 + hp0 + (n >> 1)) * 192 + wg * 96 + lane;
            st_b128(dst, x[0], x[1], x[2], epoch);
            st_b128(dst + 32, x[3], x[4], x[5], epoch);
            st_b128(dst + 64, x[6], x[7], 0, epoch);
          }
        };
        put(acc0, 0);
        put(acc1, 2);
      }
      PROF(36);
      cluster_sync_all();
      return;
    }

    float acc[64];
    const uint32_t g2rel = wtid ? mapa(bars, rank) + 8 * BAR_EMPTY2B : mapa(bars, wg) + 8 * BAR_EMPTY2;
    uint32_t g2a = (uint32_t)mkdesc(sb + wg * 8192, 16, 0, 0), g2b = (uint32_t)mkdesc(sb, 8192, 0, 0);
    auto g2_block = [&](bool first, int s, int ph) {
      mbar_wait(bars + 8 * (BAR_FULL2 + s), ph);
      const uint32_t da = g2a + (g2_a(s, hsel) >> 4), db = g2b + (g2_b(s, rank) >> 4), dc = db + (g2_bk(s) >> 4);
      wg_fence();
      if (first) wgmma_n128z(acc, da, db);
      else wgmma_n128a(acc, da, db);
      wgmma_n128a(acc, da + 2, db + 128);
      wgmma_n128a(acc, da + 4, dc);
      wgmma_n128a(acc, da + 6, dc + 128);
      wg_commit();
    };
    if (MODE != 2) {
    uint32_t a1[2][4], sc[2];
    C2 t[2];
    {
      float acc0[96], acc1[96];
      int sa = 0, pha = 0;
      uint64_t db0 = mkdesc(sb + OFF_1B, 4096, 1024, 1);
      const uint64_t da0 = mkdesc(sb + wg * 16384, 16, 2048, 1);
      const bool sigb = wtid == 64;
      uint32_t rela = 0;
#pragma unroll 1
      for (int r = 0; r < 3; r++) {
#pragma unroll
        for (int i = 0; i < 2 * NS1B; i++) {
          if (i == 2 * NS1B - 1 && r == 2) break;
          const uint64_t da = da0 + sa * (STG1A >> 4) + (i & 1) * 4, db = db0 + (i % NS1B) * (STG1B >> 4);
          if (i || r) {
            if (!(i & 1)) mbar_wait(bars + 8 * (BAR_FULLA + sa), pha);
            mbar_wait(bars + 8 * (BAR_FULLB + i % NS1B), i / NS1B);
          } else {
            asm volatile("cp.async.wait_group 0;\n" ::: "memory");
            fence_async_smem();
            nb_sync(NB_FIRST, 256);
            PROF(0 + wg);
          }
          wg_fence();
          wgmma_n192(acc0, da + 64, db, i ? 1 : r);
          wgmma_n192(acc1, da, db, i ? 1 : r);
          wgmma_n192(acc0, da + 66, db + 128, 1);
          wgmma_n192(acc1, da + 2, db + 128, 1);
          wg_commit();
          wg_wait<1>();
          if (i || r) {
            if (sigb) mbar_arrive(bars + 8 * (BAR_EMPTYB + (i + NS1B - 1) % NS1B));
            if (!(i & 1) && signaller) mbar_arrive_cluster(rela);
          } else {
            asm volatile("barrier.cluster.wait.aligned;\n" ::: "memory");
          }
          if (i & 1) {
            rela = rbars + 8 * (BAR_EMPTYA + sa);
            if (++sa == NS1A) { sa = 0; pha ^= 1; }
          }
        }
        db0 += p.zero;
      }
      const int lr = lane & 7, lm = lane >> 3;
      const bool le0 = 2 * (lane & 3) <= (lane >> 2), le1 = 2 * (lane & 3) + 1 <= (lane >> 2);
      const uint32_t maskLE = (le0 ? 0x0000FFFFu : 0u) | (le1 ? 0xFFFF0000u : 0u);
      uint32_t q[4][8], k[5][8], vt[5][8];
      {
        static_assert(15 % NS1A == 0 && 30 % NS1B == 0, "slots of the last k blocks");
        const uint64_t da = mkdesc(sb + wg * 16384, 16, 2048, 1);
        const uint64_t db = mkdesc(sb + OFF_1B, 4096, 1024, 1);
        auto last = [&](float (&acc)[96], int ro, int i0, int i1) {
#pragma unroll
          for (int i = i0; i < i1; i++)
            wgmma_n192(acc, da + ro + (i < 2 ? 2 * (STG1A >> 4) + 4 + 2 * i : 2 * i - 4),
                       db + (i < 2 ? 4 : (i >> 1) - 1) * (STG1B >> 4) + (i & 1) * 128, 1);
          wg_commit();
        };
        mbar_wait(bars + 8 * (BAR_FULLB + 4), 1);
        wg_fence();
        last(acc0, 64, 0, 2);
        asm volatile("ld.volatile.global.v4.u32 {%0,%1,%2,%3}, [%4];\n"
                     : "=r"(t[0].r), "=r"(t[1].r), "=r"(t[0].i), "=r"(t[1].i) : "l"(g_tab + 1536 + wtid * 4) : "memory");
        mbar_wait(bars + 8 * BAR_FULLA, 1);
        mbar_wait(bars + 8 * BAR_FULLB, 0);
        mbar_wait(bars + 8 * (BAR_FULLB + 1), 0);
        wg_fence();
        last(acc0, 64, 2, 6);
        wg_wait<2>();
        if (sigb) mbar_arrive(bars + 8 * (BAR_EMPTYB + 3));
        mbar_wait(bars + 8 * (BAR_EMPTYA + 1), 0);
        mbar_wait(bars + 8 * BAR_H, 0);
        wg_fence();
        last(acc1, 0, 0, LN);
        wg_wait<1>();
        fence_regs(acc0);
        PROFA(45, 0);
        attn_pack<8, 1, false>(acc0, k[4]);
        attn_pack<16, 1, true>(acc0, vt[4]);
        const uint32_t kh = sb + (warp == 7 ? OFF_1B + 2 * STG1B : OFF_KH + (warp + 1) * 2048) + lane * 16;
        sts128(kh, k[4][0], k[4][1], k[4][2], k[4][3]);
        sts128(kh + 512, k[4][4], k[4][5], k[4][6], k[4][7]);
#pragma unroll
        for (int i = 0; i < 4; i++) sts64(kh - lane * 8 + 1024 + 256 * i, vt[4][2 * i], vt[4][2 * i + 1]);
        __syncwarp();
        if (lane == 0) mbar_arrive(bars + 8 * (BAR_KH + 1 + warp));
        if (LN < 6) last(acc1, 0, LN, 6);
        attn_pack<0, 0, false>(acc0, q[1]);
        attn_pack<0, 1, false>(acc0, q[3]);
        attn_pack<8, 0, false>(acc0, k[2]);
        attn_pack<16, 0, true>(acc0, vt[2]);
        uint32_t z = p.zero;
#pragma unroll
        for (int i = 0; i < 8; i++) z &= q[1][i] & q[3][i];
#pragma unroll
        for (int i = 0; i < 8; i += 2) z &= k[2][i] & k[2][i + 1];
        mbar_wait(bars + 8 * (BAR_KH + warp) + z, 0);
        {
          const uint32_t kh = sb + OFF_KH + warp * 2048 + lane * 16;
#pragma unroll
          for (int i = 0; i < 2; i++) {
            const uint4 t = lds128(kh + 512 * i);
            k[0][4 * i] = t.x; k[0][4 * i + 1] = t.y; k[0][4 * i + 2] = t.z; k[0][4 * i + 3] = t.w;
          }
#pragma unroll
          for (int i = 0; i < 4; i++) {
            const uint2 t = lds64(kh - lane * 8 + 1024 + 256 * i);
            vt[0][2 * i] = t.x; vt[0][2 * i + 1] = t.y;
          }
        }
        wg_wait<0>();
        fence_regs(acc1);
        if (MODE == 0) nb_arrive(NB_G1END, 288);
      }
      PROF(2 + wg);
      attn_pack<0, 0, false>(acc1, q[0]);
      attn_pack<0, 1, false>(acc1, q[2]);
      attn_pack<8, 0, false>(acc1, k[1]);
      attn_pack<8, 1, false>(acc1, k[3]);
      {
        float x[8][2];
        uint32_t pp[8];
        const bool first = warp == 0 && gidx == 0;
#pragma unroll
        for (int hd = 0; hd < 2; hd++) {
#pragma unroll
          for (int j = 0; j < 4; j += 2) {
            float s0[4], s1[4], s2[4];
            attn_qk(s2, q[j], q[j + 1], k[j + 2], 4 * hd);
            attn_qk(s1, q[j], q[j + 1], k[j + 1], 4 * hd);
            attn_qk(s0, q[j], q[j + 1], k[j], 4 * hd);
            if (j == 0 && first) s0[0] = s0[1] = -1e9f / 0.17677669529663687f;
            x[2 * j + hd][0] = le0 ? s1[0] : s0[0];
            x[2 * j + hd][1] = le1 ? s1[1] : s0[1];
            x[2 * j + 2 + hd][0] = le0 ? s2[2] : s1[2];
            x[2 * j + 2 + hd][1] = le1 ? s2[3] : s1[3];
          }
        }
        PROFA(40, __float_as_uint(x[1][0] + x[7][1]));
        attn_pack<16, 0, true>(acc1, vt[1]);
        attn_pack<16, 1, true>(acc1, vt[3]);
        quad_softmax<8>(x, pp);
        PROFA(41, pp[1] + pp[7]);
        ldsm4(a1[0], sb + OFF_T32 + (warp & 3) * 1024 + lane * 16);
        ldsm4(a1[1], sb + OFF_T32 + 512 + (warp & 3) * 1024 + lane * 16);
        const uint32_t obase = sb + OFF_OP + (warp * 32 + lr) * 128;
#pragma unroll
        for (int n = 0; n < 8; n++) {
          const uint32_t dst = obase + (n >> 1) * 1024 + (((4 * (n & 1) + lm) ^ lr) << 4);
          if (n & 2) attn_pv<true>(dst, vt[n >> 1], vt[(n >> 1) + 1], 4 * (n & 1), pp[n], maskLE);
          else attn_pv<false>(dst, vt[n >> 1], vt[(n >> 1) + 1], 4 * (n & 1), pp[n], maskLE);
        }
      }
      PROFA(42, 0);
    }

    {
      const int w = warp & 3;
      const int lr = lane & 7, lm = lane >> 3;
      const uint32_t xb = sb + OFF_X + wg * 4 * XT;
      auto uo = [](int c) { return (c & 1) * 2 * XT + (c >> 1) * 2048; };
      const uint64_t dc2 = mkdesc(sb + OFF_T16, 512, 128, 0), dc3 = mkdesc(sb + OFF_T16, 128, 512, 0);
      const uint64_t dc4 = mkdesc(sb + OFF_T32, 128, 256, 0);
      const uint64_t dx = mkdesc(xb, 4096, 512, 2), dz = mkdesc(xb, 4096, 256, 3);
      const uint32_t zs = xb + (w * 16 + (lm & 1) * 8 + lr) * 32 + (((lm >> 1) ^ (lr >> 2)) << 4);
      const uint32_t ys = xb + w * 4096 + (lm >> 1) * 256 + ((lr * 32 + (((lm & 1) ^ (lr >> 2)) << 4)) ^ (rank << 6) ^ ((w & 2) << 4));
      const bool own = (w & 1) == rank;
      const uint32_t ybar = mapa(bars, own ? rank ^ 1 : rank) + 8 * BAR_Y;
      uint32_t d[2][32], pa[2][4][2][4], e[4][4][8], ya[2][2][2][4], v[2][2][8];
      C2 s1[2][2][2];
      float o[2][16];
      auto rows = [&](int c) {
        fft_rows(d[c & 1], a1, dx + (uo(c) >> 4));
        wg_commit();
      };
      auto cols = [&](int c) {
        const int s = c & 1;
        fence_regs(d[s]);
#pragma unroll
        for (int i = 0; i < 16; i++) {
          const C2 z = crot(C2{d[s][2 * i], d[s][2 * i + 1]}, t[i & 1]);
          pa[s][i >> 2][i & 1][(i >> 1) & 1] = z.r;
          pa[s][i >> 2][i & 1][2 + ((i >> 1) & 1)] = z.i;
        }
        wg_fence();
#pragma unroll
        for (int i = 0; i < 4; i++) fft_cols<0>(e[c][i], pa[s][i], dc2);
        wg_commit();
      };
      auto prod = [&](int c, int n) {
        const int s = c & 1;
        fence_regs(e[c][2 * n]);
        fence_regs(e[c][2 * n + 1]);
#pragma unroll
        for (int j = 0; j < 2; j++) {
          const C2 u0 = cget(e[s][2 * n], j, 0), u1 = cget(e[s][2 * n], j, 1);
          const C2 h0 = cget(e[s][2 * n + 1], j, 0), h1 = cget(e[s][2 * n + 1], j, 1);
          C2 y0, y1;
          if (c < 2) {
            y0 = cmul(h0, u0);
            s1[s][n][j] = cfma(h0, u1, cmul(h1, u0));
            y1 = C2{hadd2(s1[s][n][j].r, y0.i), hadd2(s1[s][n][j].i, hneg2(y0.r))};
          } else {
            const C2 u2 = cget(e[c][2 * n], j, 0), u3 = cget(e[c][2 * n], j, 1);
            const C2 h2 = cget(e[c][2 * n + 1], j, 0), h3 = cget(e[c][2 * n + 1], j, 1);
            const C2 s2 = cfma(h0, u2, cfma(h2, u0, cmul(h1, u1)));
            y0 = C2{hadd2(s2.r, s1[s][n][j].i), hadd2(s2.i, hneg2(s1[s][n][j].r))};
            y1 = cfma(h0, u3, cfma(h1, u2, cfma(h2, u1, cfma(h3, u0, C2{s2.i, hneg2(s2.r)}))));
          }
          ya[s][n][j][0] = y0.r;
          ya[s][n][j][1] = y1.r;
          ya[s][n][j][2] = y0.i;
          ya[s][n][j][3] = y1.i;
        }
      };
      auto icols = [&](int c) {
        wg_fence();
        fft_cols<1>(v[c & 1][0], ya[c & 1][0], dc3);
        fft_cols<1>(v[c & 1][1], ya[c & 1][1], dc3);
        wg_commit();
      };
      auto stage = [&](int c) {
        const int s = c & 1;
        fence_regs(v[s][0]);
        fence_regs(v[s][1]);
#pragma unroll
        for (int b = 0; b < 4; b++) {
          const C2 x0 = cget(v[s][b >> 1], 0, b & 1), x1 = cget(v[s][b >> 1], 1, b & 1);
          const C2 z0 = crot(C2{x0.i, x0.r}, t[0]), z1 = crot(C2{x1.i, x1.r}, t[1]);
          stsm4(zs + uo(c) + b * 4096, z0.i, z0.r, z1.i, z1.r);
        }
      };
      auto back = [&](int c) {
        fft_back(o[c & 1], dz + (uo(c) >> 4), dc4);
        wg_commit();
      };
      auto out = [&](int c) {
        float (&r)[16] = o[c & 1];
        fence_regs(r);
#pragma unroll
        for (int i = 0; i < 16; i += 8)
          stsm4t(ys + uo(c) + 64 * i, bmul2(pack_bf16(r[i], r[i + 1]), sc[c & 1]), bmul2(pack_bf16(r[i + 2], r[i + 3]), sc[c & 1]),
                 bmul2(pack_bf16(r[i + 4], r[i + 5]), sc[c & 1]), bmul2(pack_bf16(r[i + 6], r[i + 7]), sc[c & 1]));
      };
      auto signal = [&](int yb, int land) {
        __syncwarp();
        if (lane == 0) {
          mbar_arrive_cluster(ybar + 8 * yb);
          if (own && land >= 0) mbar_arrive(bars + 8 * (BAR_LAND + land));
        }
      };
      mbar_wait(bars + 8 * BAR_X, 0);
      wg_fence();
      rows(0);
      rows(1);
      fence_async_smem();
      nb_arrive(NB_OREADY, 288);
#pragma unroll
      for (int i = 0; i < 2; i++) {
        const uint32_t ex = sb + OFF_EX + wg * 16 + (w & 2) * 2 + 8 * i;
        sc[i] = min(max(381 - (int)lds32(ex) - (int)lds32(ex + 32), 1), 254) * 0x00800080u;
      }
      PROF(34 + wg);
      wg_wait<1>();
      cols(0);
      wg_wait<1>();
      cols(1);
      rows(2);
      nb_sync(NB_CONV + wg, 128);
      wg_wait<2>();
      prod(0, 0);
      prod(0, 1);
      icols(0);
      wg_wait<2>();
      prod(1, 0);
      prod(1, 1);
      icols(1);
      PROF3(40 + 10 * wg);
      wg_wait<1>();
      stage(0);
      wg_wait<0>();
      stage(1);
      fence_async_smem();
      cols(2);
      PROF3(41 + 10 * wg);
      nb_sync(NB_CONV + wg, 128);
      back(0);
      back(1);
      wg_wait<2>();
      prod(2, 0);
      wg_fence();
      rows(3);
      wg_wait<1>();
      out(0);
      out(1);
      signal(wg, 0);
      PROF3(42 + 10 * wg);
      prod(2, 1);
      icols(2);
      wg_wait<1>();
      cols(3);
      PROF3(43 + 10 * wg);
      wg_wait<1>();
      stage(2);
      fence_async_smem();
      wg_wait<0>();
      prod(3, 0);
      nb_sync(NB_CONV + wg, 128);
      wg_fence();
      back(2);
      prod(3, 1);
      icols(3);
      PROF3(44 + 10 * wg);
      wg_wait<1>();
      out(2);
      signal(2, -1);
      wg_wait<0>();
      stage(3);
      PROF3(45 + 10 * wg);
      fence_async_smem();
      nb_sync(NB_FIRST, 256);
      wg_fence();
      back(3);
      constexpr int G = MODE == 0;
      if (G) {
        mbar_wait(bars + 8 * (BAR_EMPTY2 + 4), 0);
        g2_block(true, 0, 0);
      }
      wg_wait<G>();
      if (lane == 0) mbar_arrive_cluster(mapa(bars, 1) + 8 * BAR_TAB);
      out(3);
      signal(3, 1);
      PROF(6 + wg);
    }
    }

    if (MODE != 1) {
      if (MODE == 2) g2_block(true, 0, 0);
      const int lr = lane & 7, lm = lane >> 3;
      const uint32_t wb = sb + g2_a(1, 0) + warp * 2048;
      const int orow = (rb2 & 7) * 128 + warp * 16;
      uint4* og = reinterpret_cast<uint4*>(p.out + (size_t)(2 * (orow + lm) + (rb2 >> 3)) * (2 * DM) + DM + cb2 * 128 + lr * 8);
      uint32_t wst = wb + (lr + 8 * (lm & 1)) * 128, wsx = ((lm >> 1) ^ lr) << 4, wld = wb + lm * 128, wlx = (lr ^ lm) << 4;
      asm volatile("" : "+l"(og), "+r"(wst), "+r"(wsx), "+r"(wld), "+r"(wlx));
#pragma unroll 1
      for (int r = 0; r < 3; r++) {
        const bool hold = r == 2 && wg != LEADWG;
        if (hold) {
          wg_wait<0>();
          if (signaller) mbar_arrive_cluster(g2rel);
          nb_sync(NB_LEAD, 256);
        }
#pragma unroll
        for (int i = 1; i <= NS2; i++) {
          g2_block(false, i % NS2, (r & 1) ^ (i == NS2));
          if (warp == LEADWG * 4) PROF2(40 + 5 * r + i);
          if (i == 1 ? !hold : r < 2) {
            wg_wait<1>();
            if (signaller) mbar_arrive_cluster(g2rel + 8 * (i - 1));
          }
        }
        if (r == 0) PROF(8 + wg);
        g2a += p.zero;
        g2b += p.zero;
      }
      if (wg == LEADWG) nb_arrive(NB_LEAD, 256);
      asm volatile("barrier.cluster.arrive.relaxed.aligned;\n" ::: "memory");
      wg_wait<0>();
      fence_regs(acc);
      PROF(10 + wg);
#pragma unroll
      for (int h = 0; h < 2; h++) {
        const uint32_t b = h * (g2_a(3, 0) - g2_a(1, 0));
#pragma unroll
        for (int j = 8 * h; j < 8 * h + 8; j += 2)
          stsm4(wst + b + (wsx ^ ((j & 7) << 4)), pack_bf16(acc[4 * j], acc[4 * j + 1]),
                pack_bf16(acc[4 * j + 2], acc[4 * j + 3]), pack_bf16(acc[4 * j + 4], acc[4 * j + 5]),
                pack_bf16(acc[4 * j + 6], acc[4 * j + 7]));
        if (wg == LEADWG) {
          fence_async_smem();
          __syncwarp();
          if (elect_one()) {
            tma_store_3d(&tmOb, wb + b, DM + cb2 * 128 + h * 64, rb2 >> 3, orow);
            bulk_commit();
          }
        } else {
          __syncwarp();
          uint4 v[4];
#pragma unroll
          for (int i = 0; i < 4; i++) v[i] = lds128(wld + b + i * 512 + (wlx ^ ((i & 1) << 6)));
#pragma unroll
          for (int i = 0; i < 4; i++)
            asm volatile("st.global.v4.u32 [%0], {%1,%2,%3,%4};\n" ::"l"(og + i * 8 * (2 * DM / 8) + h * 8), "r"(v[i].x),
                         "r"(v[i].y), "r"(v[i].z), "r"(v[i].w) : "memory");
        }
      }
      PROF(12 + wg);
      bulk_wait0();
    } else {
      asm volatile("barrier.cluster.arrive.relaxed.aligned;\n" ::: "memory");
    }
    asm volatile("barrier.cluster.wait.aligned;\n" ::: "memory");
  }
}

typedef CUresult (*EncodeFn)(CUtensorMap*, CUtensorMapDataType, cuuint32_t, void*, const cuuint64_t*, const cuuint64_t*,
                             const cuuint32_t*, const cuuint32_t*, CUtensorMapInterleave, CUtensorMapSwizzle,
                             CUtensorMapL2promotion, CUtensorMapFloatOOBfill);

void make_map(EncodeFn enc, CUtensorMap* tm, const void* base, int rank, const cuuint64_t* dims, const cuuint64_t* strides,
              const cuuint32_t* box, CUtensorMapSwizzle swz) {
  cuuint32_t es[5] = {1, 1, 1, 1, 1};
  enc(tm, CU_TENSOR_MAP_DATA_TYPE_BFLOAT16, rank, const_cast<void*>(base), dims, strides, box, es,
      CU_TENSOR_MAP_INTERLEAVE_NONE, swz, CU_TENSOR_MAP_L2_PROMOTION_L2_256B, CU_TENSOR_MAP_FLOAT_OOB_FILL_NONE);
}

}

extern "C" void kernel_launch(void* const* d_in, const int* in_sizes, int n_in, void* d_out, int out_size) {
  static EncodeFn enc = nullptr;
  static bool coresident = true;
  if (!enc) {
    void* fn = nullptr;
    cudaDriverEntryPointQueryResult qr;
    cudaGetDriverEntryPoint("cuTensorMapEncodeTiled", &fn, cudaEnableDefault, &qr);
    enc = (EncodeFn)fn;
    cudaFuncSetAttribute(fused_kernel<0>, cudaFuncAttributeMaxDynamicSharedMemorySize, SMEM_BYTES);
    cudaFuncSetAttribute(fused_kernel<1>, cudaFuncAttributeMaxDynamicSharedMemorySize, SMEM_BYTES);
    cudaFuncSetAttribute(fused_kernel<2>, cudaFuncAttributeMaxDynamicSharedMemorySize, SMEM_BYTES);
    cudaLaunchConfig_t cfg = {};
    cfg.gridDim = dim3(NCTA);
    cfg.blockDim = dim3(NTHREADS);
    cfg.dynamicSmemBytes = SMEM_BYTES;
    cudaLaunchAttribute at;
    at.id = cudaLaunchAttributeClusterDimension;
    at.val.clusterDim.x = 2;
    at.val.clusterDim.y = 1;
    at.val.clusterDim.z = 1;
    cfg.attrs = &at;
    cfg.numAttrs = 1;
    int nclusters = 0;
    if (cudaOccupancyMaxActiveClusters(&nclusters, fused_kernel<0>, &cfg) == cudaSuccess) coresident = nclusters >= NCTA / 2;
    (void)cudaGetLastError();
  }
  CUtensorMap tmX, tmW, tmWo, tmWp, tmQ, tmOb, tmXh, tmWh;
  {
    cuuint64_t dims[3] = {1024, 2, 1024};
    cuuint64_t str[2] = {2048, 4096};
    cuuint32_t box[3] = {64, 1, 128};
    make_map(enc, &tmX, d_in[6], 3, dims, str, box, CU_TENSOR_MAP_SWIZZLE_128B);
  }
  {
    cuuint64_t dims[3] = {1024, 1024, 3};
    cuuint64_t str[2] = {6144, 2048};
    cuuint32_t box[3] = {64, 32, 3};
    make_map(enc, &tmW, d_in[7], 3, dims, str, box, CU_TENSOR_MAP_SWIZZLE_128B);
  }
  {
    cuuint64_t dims[3] = {64, 1024, 16};
    cuuint64_t str[2] = {2048, 128};
    cuuint32_t box[3] = {64, 64, 2};
    cuuint32_t piece[3] = {64, 32, 1};
    make_map(enc, &tmWo, d_in[8], 3, dims, str, box, CU_TENSOR_MAP_SWIZZLE_128B);
    make_map(enc, &tmWp, d_in[8], 3, dims, str, piece, CU_TENSOR_MAP_SWIZZLE_128B);
  }
  {
    cuuint64_t dims[5] = {1024, 2, 2, 4, 128};
    cuuint64_t str[4] = {2048, 8 * 2048, 2 * 2048, 16 * 2048};
    cuuint32_t box[5] = {16, 2, 2, 4, 32};
    make_map(enc, &tmQ, d_in[0], 5, dims, str, box, CU_TENSOR_MAP_SWIZZLE_NONE);
  }
  {
    cuuint64_t dims[3] = {2048, 2, 1024};
    cuuint64_t str[2] = {4096, 8192};
    cuuint32_t box[3] = {64, 1, 16};
    make_map(enc, &tmOb, d_out, 3, dims, str, box, CU_TENSOR_MAP_SWIZZLE_128B);
  }
  {
    cuuint64_t dims[4] = {1024, 256, 2, 4};
    cuuint64_t str[3] = {4096, 2048, 256 * 4096};
    cuuint32_t box[4] = {64, 8, 2, 3};
    make_map(enc, &tmXh, d_in[6], 4, dims, str, box, CU_TENSOR_MAP_SWIZZLE_128B);
  }
  {
    cuuint64_t dims[3] = {64, 1024, 48};
    cuuint64_t str[2] = {6144, 128};
    cuuint32_t box[3] = {64, 64, 4};
    make_map(enc, &tmWh, d_in[7], 3, dims, str, box, CU_TENSOR_MAP_SWIZZLE_128B);
  }
  Params p;
  p.q = (const __nv_bfloat16*)d_in[0];
  p.k = (const __nv_bfloat16*)d_in[1];
  p.v = (const __nv_bfloat16*)d_in[2];
  p.shift_k = (const __nv_bfloat16*)d_in[3];
  p.ssm_k = (const __nv_bfloat16*)d_in[4];
  p.ssm_D = (const __nv_bfloat16*)d_in[5];
  p.x = (const __nv_bfloat16*)d_in[6];
  p.w = (const __nv_bfloat16*)d_in[7];
  p.wo = (const __nv_bfloat16*)d_in[8];
  p.out = (__nv_bfloat16*)d_out;
  p.zero = 0;
  for (int cl = 0; cl < 72; cl++) {
    const int t = cl - 4, u = t - 32;
    const bool lo = t >= 0 && t < 32, mid = u >= 0 && u < 28;
    const int grp = lo ? t & 7 : mid ? 1 + u % 7 : 0, mem = lo ? t >> 3 : mid ? 4 + u / 7 : t < 0 ? t + 6 : t - 54;
    p.tile[cl] = (uint8_t)((((grp >> 2) * 4 + (mem >> 1)) * 8 + (grp & 3) * 2 + (mem & 1)) & 63);
  }
  if (coresident) {
    fused_kernel<0><<<NCTA, NTHREADS, SMEM_BYTES>>>(p, tmX, tmW, tmWo, tmWp, tmQ, tmOb, tmXh, tmWh);
  } else {
    fused_kernel<0><<<4, NTHREADS, SMEM_BYTES>>>(p, tmX, tmW, tmWo, tmWp, tmQ, tmOb, tmXh, tmWh);
    fused_kernel<1><<<NCTA, NTHREADS, SMEM_BYTES>>>(p, tmX, tmW, tmWo, tmWp, tmQ, tmOb, tmXh, tmWh);
    fused_kernel<2><<<NCTA, NTHREADS, SMEM_BYTES>>>(p, tmX, tmW, tmWo, tmWp, tmQ, tmOb, tmXh, tmWh);
  }
}
```

```cpp
#include <cuda_runtime.h>
#include <cuda.h>
#include <cuda_bf16.h>
#include <stdint.h>

namespace {

constexpr int SEQ = 2048;
constexpr int DM = 1024;
constexpr int NCTA = 132;
constexpr int NTHREADS = 384;

constexpr int STG1A = 32768;
constexpr int NS1A = 3;
constexpr int STG1B = 12288;
constexpr int NS1B = 5;
constexpr int OFF_1B = NS1A * STG1A;
constexpr int STG2 = 32768;
constexpr int NS2 = 5;
#define PSTEP 1250
#define FPACE 260
#define FPACE2 230
#define FPACE3 180
#define LN 4
constexpr int LEADWG = 1;
__device__ __forceinline__ uint32_t g2_a(int s, int hsel) { return (((0x97524 >> (4 * s)) & 15) ^ (s & 5 ? 0 : hsel)) << 14; }
constexpr int OFF_Q0 = 3 << 14, OFF_Q1 = 8 << 14;
constexpr int STGH = 40960;
constexpr int OFF_KH = 1 * STG2;
constexpr int OFF_OP = 2 * STG2;
constexpr int OFF_T32 = 5 * STG2 - 4096;
constexpr int OFF_X = 5 * STG2;
constexpr int XT = 8192;
__device__ __forceinline__ uint32_t g2_b(int s, int rank) {
  return s < 3 ? (s == 2 ? 6 : s) << 14 : OFF_X + (s - 3) * 2 * XT + (rank ^ 1) * 4096;
}
__device__ __forceinline__ uint32_t g2_bk(int s) { return s < 3 ? 4096 : 4 * XT; }
constexpr int OFF_BAR = OFF_X + 8 * XT;
constexpr int OFF_EX = OFF_BAR + 960;
constexpr int OFF_T16 = 230400;
constexpr int SMEM_BYTES = OFF_T16 + 2048;
static_assert(OFF_1B + NS1B * STG1B <= OFF_T32 && OFF_X % 1024 == 0, "layout");
static_assert(NS1B == NS2 && NS1B * STGH <= OFF_BAR && OFF_EX + 64 <= OFF_T16 && SMEM_BYTES <= 232448, "smem");

constexpr int BAR_FULLA = 0;
constexpr int BAR_EMPTYA = 3;
constexpr int BAR_FULLB = 6;
constexpr int BAR_EMPTYB = 11;
constexpr int BAR_FULL2 = 16;
constexpr int BAR_EMPTY2 = 21;
constexpr int BAR_EMPTY2B = 44;
constexpr int BAR_X = 26;
constexpr int BAR_LAND = 42;
constexpr int BAR_TAB = 28;
constexpr int BAR_U = 29;
constexpr int BAR_H = 30;
constexpr int BAR_Y = 32;
constexpr int BAR_XFREE = 38;
constexpr int BAR_KH = 49;
constexpr int BAR_Q = 41;

constexpr int NB_LEAD = 2;
constexpr int NB_G1END = 3;
constexpr int NB_OREADY = 4;
constexpr int NB_CONV = 5;
constexpr int NB_HELP3 = 11;
constexpr int NB_FIRST = 13;

#define REG_MATH 224
#define REG_HELP 56
constexpr int SPIN_LIMIT = 1 << 20;

__device__ __align__(1024) __nv_bfloat16 g_o[SEQ * DM];
constexpr int FS = 2;
__device__ __align__(128) uint32_t g_flag_o[128 * FS];
__device__ uint4 g_halo[128 * 192];
__device__ __align__(128) const uint32_t g_tab[2048] = {
  0x2fd93000,0x2ea72f64,0x2c722da8,0x263e2a1f,0x2ea73000,0xa63e2a1f,0xafd9ada8,0xac72af64,0x2c723000,0xafd9aa1f,0x263eada8,0x2ea72f64,
  0x263e3000,0xac72af64,0x2ea72da8,0xafd9aa1f,0xa63e3000,0x2c72af64,0xaea72da8,0x2fd9aa1f,0xac723000,0x2fd9aa1f,0xa63eada8,0xaea72f64,
  0xaea73000,0x263e2a1f,0x2fd9ada8,0x2c72af64,0xafd93000,0xaea72f64,0xac722da8,0xa63e2a1f,0x263e0000,0x2c722a1f,0x2ea72da8,0x2fd92f64,
  0x2c720000,0x2fd92f64,0x263e2da8,0xaea7aa1f,0x2ea70000,0x263e2f64,0xafd9ada8,0x2c72aa1f,0x2fd90000,0xaea72a1f,0x2c72ada8,0xa63e2f64,
  0x2fd90000,0xaea7aa1f,0x2c722da8,0xa63eaf64,0x2ea70000,0x263eaf64,0xafd92da8,0x2c722a1f,0x2c720000,0x2fd9af64,0x263eada8,0xaea72a1f,
  0x263e0000,0x2c72aa1f,0x2ea7ada8,0x2fd9af64,0xafd93000,0xaea72f64,0xac722da8,0xa63e2a1f,0xaea73000,0x263e2a1f,0x2fd9ada8,0x2c72af64,
  0xac723000,0x2fd9aa1f,0xa63eada8,0xaea72f64,0xa63e3000,0x2c72af64,0xaea72da8,0x2fd9aa1f,0x263e3000,0xac72af64,0x2ea72da8,0xafd9aa1f,
  0x2c723000,0xafd9aa1f,0x263eada8,0x2ea72f64,0x2ea73000,0xa63e2a1f,0xafd9ada8,0xac72af64,0x2fd93000,0x2ea72f64,0x2c722da8,0x263e2a1f,
  0xa63e0000,0xac722a1f,0xaea72da8,0xafd92f64,0xac720000,0xafd92f64,0xa63e2da8,0x2ea7aa1f,0xaea70000,0xa63e2f64,0x2fd9ada8,0xac72aa1f,
  0xafd90000,0x2ea72a1f,0xac72ada8,0x263e2f64,0xafd90000,0x2ea7aa1f,0xac722da8,0x263eaf64,0xaea70000,0xa63eaf64,0x2fd92da8,0xac722a1f,
  0xac720000,0xafd9af64,0xa63eada8,0x2ea72a1f,0xa63e0000,0xac72aa1f,0xaea7ada8,0xafd9af64,0xa63e0000,0xac72aa1f,0xaea7ada8,0xafd9af64,
  0xac720000,0xafd9af64,0xa63eada8,0x2ea72a1f,0xaea70000,0xa63eaf64,0x2fd92da8,0xac722a1f,0xafd90000,0x2ea7aa1f,0xac722da8,0x263eaf64,
  0xafd90000,0x2ea72a1f,0xac72ada8,0x263e2f64,0xaea70000,0xa63e2f64,0x2fd9ada8,0xac72aa1f,0xac720000,0xafd92f64,0xa63e2da8,0x2ea7aa1f,
  0xa63e0000,0xac722a1f,0xaea72da8,0xafd92f64,0x2fd93000,0x2ea72f64,0x2c722da8,0x263e2a1f,0x2ea73000,0xa63e2a1f,0xafd9ada8,0xac72af64,
  0x2c723000,0xafd9aa1f,0x263eada8,0x2ea72f64,0x263e3000,0xac72af64,0x2ea72da8,0xafd9aa1f,0xa63e3000,0x2c72af64,0xaea72da8,0x2fd9aa1f,
  0xac723000,0x2fd9aa1f,0xa63eada8,0xaea72f64,0xaea73000,0x263e2a1f,0x2fd9ada8,0x2c72af64,0xafd93000,0xaea72f64,0xac722da8,0xa63e2a1f,
  0x263e0000,0x2c72aa1f,0x2ea7ada8,0x2fd9af64,0x2c720000,0x2fd9af64,0x263eada8,0xaea72a1f,0x2ea70000,0x263eaf64,0xafd92da8,0x2c722a1f,
  0x2fd90000,0xaea7aa1f,0x2c722da8,0xa63eaf64,0x2fd90000,0xaea72a1f,0x2c72ada8,0xa63e2f64,0x2ea70000,0x263e2f64,0xafd9ada8,0x2c72aa1f,
  0x2c720000,0x2fd92f64,0x263e2da8,0xaea7aa1f,0x263e0000,0x2c722a1f,0x2ea72da8,0x2fd92f64,0xafd93000,0xaea72f64,0xac722da8,0xa63e2a1f,
  0xaea73000,0x263e2a1f,0x2fd9ada8,0x2c72af64,0xac723000,0x2fd9aa1f,0xa63eada8,0xaea72f64,0xa63e3000,0x2c72af64,0xaea72da8,0x2fd9aa1f,
  0x263e3000,0xac72af64,0x2ea72da8,0xafd9aa1f,0x2c723000,0xafd9aa1f,0x263eada8,0x2ea72f64,0x2ea73000,0xa63e2a1f,0xafd9ada8,0xac72af64,
  0x2fd93000,0x2ea72f64,0x2c722da8,0x263e2a1f,0xa63e0000,0xac72aa1f,0xaea7ada8,0xafd9af64,0x2c720000,0x2fd92f64,0x263e2da8,0xaea7aa1f,
  0xaea70000,0xa63eaf64,0x2fd92da8,0xac722a1f,0x2fd90000,0xaea72a1f,0x2c72ada8,0xa63e2f64,0xafd90000,0x2ea72a1f,0xac72ada8,0x263e2f64,
  0x2ea70000,0x263eaf64,0xafd92da8,0x2c722a1f,0xac720000,0xafd92f64,0xa63e2da8,0x2ea7aa1f,0x263e0000,0x2c72aa1f,0x2ea7ada8,0x2fd9af64,
  0x2fd93000,0x2ea72f64,0x2c722da8,0x263e2a1f,0xaea7b000,0x263eaa1f,0x2fd92da8,0x2c722f64,0x2c723000,0xafd9aa1f,0x263eada8,0x2ea72f64,
  0xa63eb000,0x2c722f64,0xaea7ada8,0x2fd92a1f,0xa63e3000,0x2c72af64,0xaea72da8,0x2fd9aa1f,0x2c72b000,0xafd92a1f,0x263e2da8,0x2ea7af64,
  0xaea73000,0x263e2a1f,0x2fd9ada8,0x2c72af64,0x2fd9b000,0x2ea7af64,0x2c72ada8,0x263eaa1f,0x263e0000,0x2c72aa1f,0x2ea7ada8,0x2fd9af64,
  0xac720000,0xafd92f64,0xa63e2da8,0x2ea7aa1f,0x2ea70000,0x263eaf64,0xafd92da8,0x2c722a1f,0xafd90000,0x2ea72a1f,0xac72ada8,0x263e2f64,
  0x2fd90000,0xaea72a1f,0x2c72ada8,0xa63e2f64,0xaea70000,0xa63eaf64,0x2fd92da8,0xac722a1f,0x2c720000,0x2fd92f64,0x263e2da8,0xaea7aa1f,
  0xa63e0000,0xac72aa1f,0xaea7ada8,0xafd9af64,0xafd93000,0xaea72f64,0xac722da8,0xa63e2a1f,0x2ea7b000,0xa63eaa1f,0xafd92da8,0xac722f64,
  0xac723000,0x2fd9aa1f,0xa63eada8,0xaea72f64,0x263eb000,0xac722f64,0x2ea7ada8,0xafd92a1f,0x263e3000,0xac72af64,0x2ea72da8,0xafd9aa1f,
  0xac72b000,0x2fd92a1f,0xa63e2da8,0xaea7af64,0x2ea73000,0xa63e2a1f,0xafd9ada8,0xac72af64,0xafd9b000,0xaea7af64,0xac72ada8,0xa63eaa1f,
  0xafd9b000,0xaea7af64,0xac72ada8,0xa63eaa1f,0x2ea73000,0xa63e2a1f,0xafd9ada8,0xac72af64,0xac72b000,0x2fd92a1f,0xa63e2da8,0xaea7af64,
  0x263e3000,0xac72af64,0x2ea72da8,0xafd9aa1f,0x263eb000,0xac722f64,0x2ea7ada8,0xafd92a1f,0xac723000,0x2fd9aa1f,0xa63eada8,0xaea72f64,
  0x2ea7b000,0xa63eaa1f,0xafd92da8,0xac722f64,0xafd93000,0xaea72f64,0xac722da8,0xa63e2a1f,0xa63e0000,0xac72aa1f,0xaea7ada8,0xafd9af64,
  0x2c720000,0x2fd92f64,0x263e2da8,0xaea7aa1f,0xaea70000,0xa63eaf64,0x2fd92da8,0xac722a1f,0x2fd90000,0xaea72a1f,0x2c72ada8,0xa63e2f64,
  0xafd90000,0x2ea72a1f,0xac72ada8,0x263e2f64,0x2ea70000,0x263eaf64,0xafd92da8,0x2c722a1f,0xac720000,0xafd92f64,0xa63e2da8,0x2ea7aa1f,
  0x263e0000,0x2c72aa1f,0x2ea7ada8,0x2fd9af64,0x2fd9b000,0x2ea7af64,0x2c72ada8,0x263eaa1f,0xaea73000,0x263e2a1f,0x2fd9ada8,0x2c72af64,
  0x2c72b000,0xafd92a1f,0x263e2da8,0x2ea7af64,0xa63e3000,0x2c72af64,0xaea72da8,0x2fd9aa1f,0xa63eb000,0x2c722f64,0xaea7ada8,0x2fd92a1f,
  0x2c723000,0xafd9aa1f,0x263eada8,0x2ea72f64,0xaea7b000,0x263eaa1f,0x2fd92da8,0x2c722f64,0x2fd93000,0x2ea72f64,0x2c722da8,0x263e2a1f,
  0x263e0000,0x2c72aa1f,0x2ea7ada8,0x2fd9af64,0xac720000,0xafd92f64,0xa63e2da8,0x2ea7aa1f,0x2ea70000,0x263eaf64,0xafd92da8,0x2c722a1f,
  0xafd90000,0x2ea72a1f,0xac72ada8,0x263e2f64,0x2fd90000,0xaea72a1f,0x2c72ada8,0xa63e2f64,0xaea70000,0xa63eaf64,0x2fd92da8,0xac722a1f,
  0x2c720000,0x2fd92f64,0x263e2da8,0xaea7aa1f,0xa63e0000,0xac72aa1f,0xaea7ada8,0xafd9af64,0x316c2fbd,0x343e32f7,0x35bc34ff,0x372c3676,
  0x371532c6,0x3a81392e,0x3bef3b71,0x3b7c3bf2,0x397034cf,0x3bfc3b6c,0x38b23b04,0xb40e31e8,0x3ae13631,0x39e73bf5,0xb6e83219,0xbbe8bb13,
  0x3bc23785,0x30be3aa9,0xbbfdb911,0x2a16b9aa,0x3bfe3865,0xb80f37a6,0xb82abc00,0x3bfd376f,0x3b9238fd,0xbb7f2311,0x3805b929,0x31223bde,
  0x3a85398b,0xbb96b742,0x3bff319e,0xbbb82f8b,0xbbe2bbf1,0xbbb7bbcf,0xbb78bb9a,0xbb27bb52,0xbb2cbbd2,0xb8a8ba19,0xb029b5df,0x35a52f59,
  0xb9dfbba1,0x2ba7b5f7,0x3a7a37b2,0x3bbd3bdd,0xb815bb60,0x39662e91,0x3b373bda,0xb0d7377a,0xb3d3bb10,0x3be9386f,0x2a7a3a31,0xbbfeb9a6,
  0x294dbab0,0x3ae53b07,0xbad51fdb,0xab43bb16,0x352fba41,0x35993c00,0xbaebba1d,0x3be531cf,0x38a3b9c5,0xb5173b21,0x2776bbe0,0x34323bf2,
  0x384537dd,0x38ea3899,0x39823937,0x3a0d39c9,0x39463a93,0x3340374e,0xb426a452,0xb979b7c8,0xbb45b924,0xbb32bc00,0xb371b902,0x38d63294,
  0xb08db9a1,0x3b3f379b,0x39583bd7,0xb8252dfb,0x3bea3a2d,0xb3ba3874,0xbb89bb0d,0x36d2b625,0xb6bb387f,0xb8d1bbf5,0x3be73602,0xb546391f,
  0xba00bb01,0x3bff35eb,0xba5c34db,0x3359bab6,0x3ac7b66b,0xb9413933,0x368dbabd,0xb0103bb3,0xbac4baf7,0xba50ba8c,0xb9cdba11,0xb93cb986,
  0x3a04388e,0x3bcb3b1e,0x3bba3c00,0x39d63afe,0x36af3a21,0xb6ffa17f,0xbbc8ba3d,0xba60bbd4,0xbbebb9af,0xb6c6bb0a,0x39f43263,0x3ad83bf7,
  0x30a6b916,0x3bc33aa5,0xb55e3790,0xbb3dbb63,0x3b423a9e,0xba642ec3,0xb0f0bb6a,0x3b8e3a25,0xb94a37bd,0x2884bb6f,0x38db3b9f,0xbbc9b85a,
  0xb840bb54,0x3a093a15,0xbb4cb850,0x3bef3457,0x3a893a4d,0x3af43ac1,0x3b4f3b24,0x3b983b76,0xbb94baba,0xbbe4bbf9,0xba58bb57,0xb699b8f8,
  0x3bfe3b18,0x394f3b5c,0xb109347b,0xbae8b884,0xbbc0bb68,0xa9b1b90c,0x3b8b387a,0x38bc3ba5,0x3ade3ba7,0xb8c1324b,0xb9f0bbf6,0x39eb9648,
  0xb96bbbd6,0x3bbf3487,0xb38939b3,0xb9f8bba3,0x370a3bf3,0xbb47b994,0x3bbc2d65,0xb8ad3889,0xb153bc00,0x37213b9c,0xb97dba90,0x3af138f3,
  0xb89eb8ee,0xb7e8b84a,0xb682b737,0xb50bb5c8,0x35233855,0xb13b2d33,0xb8e0b65f,0xbb4aba45,0xa8e8b764,0x39fc3648,0x3be63bae,0x380a3a9b,
  0xb3eb360e,0xbbfeba35,0xb552baa2,0x3a7334b7,0x381ab4ab,0x3a6f3bd8,0xb95d2e5f,0xb962bc00,0xb9e3327c,0xb402bbac,0x3bc6399d,0xb95434c3,
  0x3b2faf27,0xb6a439bc,0xb41abbf9,0x3a7e3a97,0xbbe3251b,0x3b2ab4f3,0xb9d23894,0x37f3ba49,0x3bce3bb5,0x3bf03be1,0x3bff3bfa,0x3bfb3bff,
  0x2c38b1b6,0x383a34e7,0x3aee39c0,0x3bff3bb2,0xbb81bbf8,0xb53ab999,0x38302ef5,0x3bed3ab3,0xb8cc9cb6,0xbb85bbab,0x2adeb86a,0x3bc5391b,
  0x38c73bf6,0xbadbb232,0xb6ddbba9,0x3b87361a,0x3b833201,0xb0743a39,0xba76bb5e,0x3b352dc9,0xac06bbb0,0x39743b59,0xbbeeb759,0x3aceb2ad,
  0xbbccb5d4,0x3bfb2d00,0xbb7a32de,0x3a54b7d2,0xb30fb44b,0xafefb185,0xa6adacce,0x2c9c25e4,0xbbfcbbdf,0xbacbbb9e,0xb7feb990,0xa81fb463,
  0xb58d2d97,0xbb90b9b8,0xbad1bbf4,0xb05bb85f,0x3a673c00,0xb5763493,0xbbfdbaac,0xb3a2ba29,0x3a6b2e2d,0x38203bd9,0xbb3ab49f,0xb56abb65,
  0xb581bbdc,0x3bec3907,0xb8b7363c,0xb6f4bbf8,0xbbfcb46f,0x39dab654,0xb0423b1b,0xb835bbd3,0xb3283b73,0xac6abbfa,0x35b13bd0,0xb8e5bafb,
  0x38ee3a0d,0xb84aba89,0x37373af4,0xb5c8bb4f,0x35df3a81,0x2f59bbef,0xb88e3b7c,0x3b1eb946,0x2d973ae8,0x39b8bb81,0xbbf4353a,0x385f3830,
  0xb2633b3f,0x3bf7b958,0xb60eb825,0xba353bc0,0xb7853b87,0x3aa9b3d3,0x3911bbe9,0xb9aa2a7a,0xb99d3bbf,0x34c33389,0x3bdcb9f8,0x3907bb83,
  0xbb013be5,0xb5eb394a,0x34db2884,0x3ab6b8db,0xbbd03bfb,0xbafb3b7a,0xb98b3a54,0xb74238a3,0x3a4db93c,0xbac1389e,0x3b24b7e8,0xbb763682,
  0x3b71b8a8,0xbbf23029,0x3a9335a5,0xb74eba04,0x3bf8b80a,0xb999b58d,0xaef53b90,0x3ab3bad1,0x3bd7b6c6,0xadfbb9f4,0xbb683ad8,0x390c33eb,
  0x3b10b56a,0x386fbbc2,0xba3130be,0xb9a63bfd,0x39b3b402,0x3ba3bbc6,0x3201b954,0xba393581,0x37bdb122,0x3b6fba00,0x3b9fbbff,0x385aba5c,
  0x32deac6a,0x37d2b5b1,0x39c5b8e5,0x3b21ba85,0x344b3b98,0xb185bbce,0x2cce3bf0,0x25e4bbff,0xbc003340,0x3afe3426,0xb855b979,0x2d333b94,
  0x34cfbbed,0xbb6c39df,0x3b042ba7,0xb1e8ba7a,0x3aa2a9b1,0x34b7bb8b,0xbc0038bc,0x349338cc,0xba2d3bfe,0x387430a6,0x3b0dbbc3,0xb625b55e,
  0xb63cb074,0xbbf83a76,0xb8653b35,0x37a6294d,0x3bf3bbc9,0x3994bb2f,0x2d65b6a4,0xb889341a,0xb19e3517,0x2f8b2776,0x366bb432,0x3933b840,
  0x3bb5b50b,0xbbe1330f,0x3bfaafef,0xbbff26ad,0xa4523bcb,0x37c8bbba,0xbaba39d6,0x3bf9b523,0xbba1305b,0x35f73970,0x37b2bbfc,0xbbdd38b2,
  0x387abbfe,0xbba53552,0x9cb63a73,0x3babba67,0x39162a16,0x3aa5bbea,0xb790b3ba,0xbb633b89,0xbb5e3bec,0xadc938b7,0x3ab0b6f4,0x3b07bbfe,
  0xaf27b359,0xb9bc370a,0xbbf93b47,0xba973bbc,0x3be0bb96,0x3bf2bbff,0x3b54bbb8,0x3a15bac7,0xafbd3bfb,0x32f7bbe2,0xb4ff3bb7,0x3676bb78,
  0x365fbbe4,0xba453a58,0x3bdfb699,0xbb9eac38,0xb9243bbd,0x3c00b6af,0xb902b6ff,0xb2943bc8,0x3aacbb85,0xba29aade,0xb6313bc5,0x3bf5b815,
  0xbba73b3d,0x324b381a,0x3bf6ba6f,0x9648b95d,0x3c00bae5,0x376fbad5,0xb87f2b43,0xbbf53b42,0xbbb03a7e,0xbb593bfc,0xb75939da,0x32ad3042,
  0x3abdba09,0x3bb3bb4c,0x3c00bbef,0x3b9cbbe3,0x3bf12c9c,0xbbcfb16c,0x3b9a343e,0xbb52b5bc,0xbb57b13b,0x38f838e0,0xb1b6bb4a,0xb4e73bfc,
  0x3a21340e,0x217fbb45,0xba3d3b32,0x3bd4b371,0xb86ab576,0xb91b3bfd,0x3b60b3a2,0x2e91bae1,0x34ab36d2,0x3bd8bade,0xae5fb8c1,0xbc0039f0,
  0x9fdbb80f,0xbb16382a,0xba9e3bfd,0x2ec336bb,0xb46f38ad,0x3654ac06,0x3b1bb974,0x3bd3bbee,0x3850b941,0x3457b68d,0xa51bb010,0xb4f33153,
  0xb7dd3b27,0x3899bac4,0xb9373a50,0x39c9b9cd,0x3990383a,0xb463baee,0xb2c63bff,0x392ebb2c,0x3b18ba60,0xbb5c28e8,0x347b39fc,0x3884bbe6,
  0xb219b966,0xbb133b37,0x39a130d7,0x379bbbeb,0xbbf63962,0xb2323a6b,0x3ba9b820,0x361abb3a,0xb6023a64,0x391fb0f0,0x3bd6bb8e,0x3487b9e3,
  0x3a41b835,0x3c00bb92,0x3a1dbb7f,0x31cfb805,0x3a90bb2a,0x38f3b9d2,0x35d4b7f3,0x2d00b328,0x3af7372c,0xba8cb845,0x3a1138ea,0xb986b982,
  0x39c0bacb,0xbbb237fe,0x3bd2a81f,0xba19b715,0xb764b8d6,0xb6483bfe,0x3baeb94f,0xba9bb109,0xbbda39e7,0x377a36e8,0x39afbbe8,0xbb0a308d,
  0xae2d39eb,0x3bd9b8c7,0x349fbadb,0xbb6536dd,0x3b6ab8d1,0x3a25bbe7,0xb27cb546,0xbbac396b,0x38fdbace,0xa311b52f,0xb9293599,0xbbde3aeb,
  0xb8943721,0xba49397d,0xbb733af1,0xbbfa3bcc,0xbbfb3bff,0xbbe23bf1,0xbbb73bcf,0xbb783b9a,0xbb7c3bf2,0xb9463a93,0xb340374e,0x3426a452,
  0xba603bd4,0xa8e83764,0x39fcb648,0x3be6bbae,0xb8bc3ba5,0x38cc9cb6,0x3b85bbab,0xaadeb86a,0xb56a3b65,0x3bc2b785,0x30bebaa9,0xbbfd3911,
  0xab433b16,0x3b42ba9e,0xba64aec3,0xb0f03b6a,0x33593ab6,0x370abbf3,0xbb473994,0x3bbcad65,0x37f33a49,0xb328bb73,0xac6a3bfa,0x35b1bbd0,
  0xac9c25e4,0xb16c2fbd,0xb43e32f7,0xb5bc34ff,0xb5a52f59,0xba04388e,0xbbcb3b1e,0xbbba3c00,0xb8d63294,0xbbfe3b18,0xb94f3b5c,0x3109347b,
  0xba7334b7,0xba673c00,0x35763493,0x3bfdbaac,0xbb87361a,0xb3d33b10,0x3be9b86f,0x2a7aba31,0xbbfd376f,0x36bb387f,0x38d1bbf5,0xbbe73602,
  0xbbc9385a,0x3b2f2f27,0xb6a4b9bc,0xb41a3bf9,0xbaf138f3,0x3bccb5d4,0xbbfb2d00,0x3b7a32de,0xbb273b52,0xbac43af7,0xba503a8c,0xb9cd3a11,
  0x3979b7c8,0x3b94baba,0x3be4bbf9,0x3a58bb57,0x380aba9b,0xb58dad97,0xbb9039b8,0xbad13bf4,0xbbc5391b,0xb8153b60,0x3966ae91,0x3b37bbda,
  0x2a1639aa,0x3beaba2d,0xb3bab874,0xbb893b0d,0x3b8eba25,0xb9e3b27c,0xb4023bac,0x3bc6b99d,0xb8adb889,0xac063bb0,0x3974bb59,0xbbee3759,
  0xb8e53afb,0x3a85b98b,0xbb963742,0x3bffb19e,0xb72c3676,0xb84537dd,0xb8ea3899,0xb9823937,0xb9d63afe,0xb5233855,0x313b2d33,0x38e0b65f,
  0x3ae8b884,0x3b81bbf8,0x353ab999,0xb8302ef5,0x33a2ba29,0xbae13631,0xb9e73bf5,0x36e83219,0xbbfe39a6,0x30a63916,0x3bc3baa5,0xb55eb790,
  0x3546391f,0x396bbbd6,0xbbbf3487,0x338939b3,0x3a7eba97,0xbbfc346f,0x39da3654,0xb042bb1b,0xba54b7d2,0x38a339c5,0xb517bb21,0x27763be0,
  0xb93c3986,0xb89e38ee,0xb7e8384a,0xb6823737,0x3699b8f8,0xac38b1b6,0xb83a34e7,0xbaee39c0,0xb05b385f,0x3970b4cf,0x3bfcbb6c,0x38b2bb04,
  0xb0d7b77a,0xbbeb39af,0xb6c63b0a,0x39f4b263,0x36d23625,0x3adebba7,0xb8c1b24b,0xb9f03bf6,0xb954b4c3,0xb5813bdc,0x3becb907,0xb8b7b63c,
  0x3ace32ad,0xb52fba41,0xb5993c00,0x3aebba1d,0xbbb8af8b,0x3ac7366b,0xb941b933,0x368d3abd,0xba0d39c9,0xba893a4d,0xbaf43ac1,0xbb4f3b24,
  0x3b4aba45,0x3bfcbbdf,0x3acbbb9e,0x37feb990,0xbbed3ab3,0xb9df3ba1,0x2ba735f7,0x3a7ab7b2,0x3be8bb13,0x308db9a1,0xbb3f379b,0xb9583bd7,
  0xbb3d3b63,0x381a34ab,0x3a6fbbd8,0xb95dae5f,0x39f8bba3,0xbb833201,0x30743a39,0x3a76bb5e,0xb8353bd3,0x3b92b8fd,0xbb7fa311,0x38053929,
  0x3432bbf2,0xb8403b54,0x3a09ba15,0xbb4c3850,0xb50b35c8,0xb30f344b,0xafef3185,0xa6ad2cce,0xbbff3bb2,0xbb2c3bd2,0xb8a83a19,0xb02935df,
  0xb40eb1e8,0xbb453924,0xbb323c00,0xb3713902,0x3ad8bbf7,0xb3ebb60e,0xbbfe3a35,0xb5523aa2,0x39eb1648,0x38c7bbf6,0xbadb3232,0xb6dd3ba9,
  0xb6f43bf8,0x3bfeb865,0xb80fb7a6,0xb82a3c00,0xbbe531cf,0x394a37bd,0xa884bb6f,0xb8db3b9f,0xb010bbb3,0xb1533c00,0x3721bb9c,0xb97d3a90,
  0xbb983b76,0xbbce3bb5,0xbbf03be1,0xbbff3bfa,0x281fb463,0xb71532c6,0xba81392e,0xbbef3b71,0x3bbdbbdd,0x36afba21,0xb6ff217f,0xbbc83a3d,
  0x38252dfb,0x3bc0bb68,0x29b1b90c,0xbb8b387a,0xb9623c00,0x3a6bae2d,0x3820bbd9,0xbb3a349f,0xbb352dc9,0x294d3ab0,0x3ae5bb07,0xbad59fdb,
  0x3122bbde,0xba003b01,0x3bffb5eb,0xba5cb4db,0x3befb457,0xbbe3a51b,0x3b2a34f3,0xb9d2b894,0x39c939cd,0xba4db93c,0x3ac1389e,0xbb24b7e8,
  0x3b1e3946,0xbc00b340,0x3afeb426,0xb8553979,0x3bdd38b2,0xba21340e,0xa17fbb45,0x3a3d3b32,0x3bf53815,0xb2193966,0xbb13bb37,0x39a1b0d7,
  0x3b6536dd,0x37853b87,0xbaa9b3d3,0xb911bbe9,0x3a393581,0x3b5e3bec,0x2dc938b7,0xbab0b6f4,0x3889341a,0x3bb03a7e,0x3b593bfc,0x375939da,
  0x34f33153,0x38943721,0x3a49397d,0x3b733af1,0xb9863982,0x38eeba0d,0xb84a3a89,0x3737baf4,0xb74e3a04,0xa452bbcb,0x37c83bba,0xbabab9d6,
  0xb1e83a7a,0xb924bbbd,0x3c0036af,0xb90236ff,0x2e913ae1,0xbbdab9e7,0x377ab6e8,0x39af3be8,0x361a3b3a,0xbb10b56a,0xb86fbbc2,0x3a3130be,
  0x39073b83,0xb63c3074,0xbbf8ba76,0xb865bb35,0x3a973bbc,0x346f38ad,0xb654ac06,0xbb1bb974,0x3b9c3be3,0x3a903b2a,0x38f339d2,0x35d437f3,
  0x3b763682,0xbbb5b50b,0x3be1330f,0xbbfaafef,0x2d33bb94,0x365f3be4,0xba45ba58,0x3bdf3699,0xbbd4b371,0x3764b8d6,0x36483bfe,0xbbaeb94f,
  0x379b3beb,0xbbd7b6c6,0x2dfbb9f4,0x3b683ad8,0x39aa2a7a,0x3a2d3bfe,0xb87430a6,0xbb0dbbc3,0xbb07bbfe,0x1fdbb80f,0x3b16382a,0x3a9e3bfd,
  0xb2ad3042,0xba41b835,0xbc00bb92,0xba1dbb7f,0x3bfa3bcc,0x3bd03bfb,0x3afb3b7a,0x398b3a54,0xb5c83b4f,0x344bbb98,0xb1853bce,0x2ccebbf0,
  0x3bf93523,0xbb57313b,0x38f8b8e0,0xb1b63b4a,0xb294bbc8,0x3b183a60,0xbb5ca8e8,0x347bb9fc,0xbb0ab08d,0xb263bb3f,0x3bf73958,0xb60e3825,
  0x39a63bfd,0xb9162a16,0xbaa5bbea,0x3790b3ba,0x37a6a94d,0x3c003ae5,0x376f3ad5,0xb87fab43,0xbbd3bbee,0xb8fdbace,0x2311b52f,0x39293599,
  0x2d003328,0xb2deac6a,0xb7d2b5b1,0xb9c5b8e5,0x3bff26ad,0xbbf12c9c,0x3bcfb16c,0xbb9a343e,0xbb9e2c38,0x3990b83a,0xb4633aee,0xb2c6bbff,
  0x3a9bb109,0xad973ae8,0xb9b8bb81,0x3bf4353a,0xb90c33eb,0xb87abbfe,0x3ba53552,0x1cb63a73,0x3625b55e,0x3ba73b3d,0xb24b381a,0xbbf6ba6f,
  0xaec336bb,0xbb6ab8d1,0xba25bbe7,0x327cb546,0xb1cfb805,0x37bd3122,0x3b6f3a00,0x3b9f3bff,0x374238a3,0x319e3517,0xaf8b2776,0xb66bb432,
  0x25e43bff,0xafbdbbfb,0x32f73be2,0xb4ffbbb7,0xb4e7bbfc,0x39c03acb,0xbbb2b7fe,0x3bd2281f,0x38843be6,0xbbf8b80a,0x3999b58d,0x2ef53b90,
  0xba35bbc0,0x3aa229b1,0x34b73b8b,0xbc00b8bc,0x3b633b89,0xb4ab36d2,0xbbd8bade,0x2e5fb8c1,0xbbf5bb42,0xb602ba64,0x391f30f0,0x3bd63b8e,
  0x3bde3aeb,0x3b013be5,0x35eb394a,0xb4db2884,0xbb21ba85,0xbbe0bb96,0xbbf2bbff,0xbb54bbb8,0x3b52b5bc,0xbaf7372c,0x3a8cb845,0xba1138ea,
  0x392e3b2c,0xbb71b8a8,0x3bf23029,0xba9335a5,0xb85f3830,0xb4cfbbed,0x3b6c39df,0xbb042ba7,0xbbabba67,0x386ab576,0x391b3bfd,0xbb60b3a2,
  0x1648b95d,0x3bf63962,0x32323a6b,0xbba9b820,0x3bac396b,0x399d3bbf,0xb4c33389,0xbbdcb9f8,0x385a3a5c,0xaf273359,0xb9bcb70a,0xbbf9bb47,
  0xb933b840,0xbabdba09,0xbbb3bb4c,0xbc00bbef,0x36763b78,0xb7ddbb27,0x38993ac4,0xb937ba50,0xba193715,0x35dfba81,0x2f593bef,0xb88ebb7c,
  0xbab3bad1,0x3ba1305b,0xb5f73970,0xb7b2bbfc,0x3493b8cc,0x3aac3b85,0xba292ade,0xb631bbc5,0x3c0039f0,0x2e2d39eb,0xbbd9b8c7,0xb49fbadb,
  0x348739e3,0xb9b3b402,0xbba3bbc6,0xb201b954,0xbab6b8db,0xbbf3bbc9,0xb994bb2f,0xad65b6a4,0xba15bac7,0xb850b941,0xb457b68d,0x251bb010,
  0xb9cfbb16,0x30ac2a31,0x3b9c3bf1,0xb493ae2d,0xb76fb8b4,0x35a133e3,0x3a1d3afe,0xb902b76f,0xb3e3b5a1,0x38b4376f,0x376f3902,0xbafeba1d,
  0xaa31b0ac,0x3b1639cf,0x2e2d3493,0xbbf1bb9c,0xb956ba74,0x305f29cc,0x3b633bd2,0xb44badc9,0xb6e7b859,0x353f335e,0x39d23ab6,0xb8bcb6ff,
  0xb35eb53f,0x385936e7,0x36ff38bc,0xbab6b9d2,0xa9ccb05f,0x3a743956,0x2dc9344b,0xbbd2bb63,0xb8e3b9de,0x30122967,0x3b1e3ba1,0xb402ad65,
  0xb662b801,0x34de32da,0x39823a67,0xb874b68d,0xb2dab4de,0x38013662,0x368d3874,0xba67b982,0xa967b012,0x39de38e3,0x2d653402,0xbba1bb1e,
  0xb876b952,0x2f8c2902,0x3ace3b60,0xb371ad00,0xb5e1b758,0x347e3257,0x392e3a11,0xb82ab61a,0xb257b47e,0x375835e1,0x361a382a,0xba11b92e,
  0xa902af8c,0x39523876,0x2d003371,0xbb60bace,0xb80db8ce,0x2ef3289e,0x3a733b10,0xb2deac9c,0xb562b6b3,0x342031d5,0x38d639b3,0xb7bdb5a5,
  0xb1d5b420,0x36b33562,0x35a537bd,0xb9b3b8d6,0xa89eaef3,0x38ce380d,0x2c9c32de,0xbb10ba73,0xb750b851,0x2e5a2839,0x3a0d3ab0,0xb24bac38,
  0xb4e5b613,0x33863153,0x387a394f,0xb721b52f,0xb153b386,0x361334e5,0x352f3721,0xb94fb87a,0xa839ae5a,0x38513750,0x2c38324b,0xbab0ba0d,
  0xb68eb7b4,0x2dc227a9,0x399d3a41,0xb1b6aba7,0xb46ab577,0x32cd30d2,0x381a38e5,0xb682b4b7,0xb0d2b2cd,0x3577346a,0x34b73682,0xb8e5b81a,
  0xa7a9adc2,0x37b4368e,0x2ba731b6,0xba41b99d,0xb5d2b6d1,0x2d2a26e0,0x392439c5,0xb122aade,0xb3e3b4de,0x32163052,0x376f3874,0xb5dfb43e,
  0xb052b216,0x34de33e3,0x343e35df,0xb874b76f,0xa6e0ad2a,0x36d135d2,0x2ade3122,0xb9c5b924,0xb51cb5f6,0x2c932617,0x38a3393c,0xb08daa16,
  0xb2f4b448,0x31602fa5,0x36a437fe,0xb53ab389,0xafa5b160,0x344832f4,0x3389353a,0xb7feb6a4,0xa617ac93,0x35f6351c,0x2a16308d,0xb93cb8a3,
  0xb46ab523,0x2bf6254d,0x381a38a8,0xafefa94d,0xb209b36b,0x30ac2ea7,0x35d4370a,0xb493b294,0xaea7b0ac,0x336b3209,0x32943493,0xb70ab5d4,
  0xa54dabf6,0x3523346a,0x294d2fef,0xb8a8b81a,0xb378b456,0x2ac82484,0x3715380a,0xaec3a884,0xb120b24a,0x2ff22da9,0x34ff360e,0xb3d3b19e,
  0xada9aff2,0x324a3120,0x319e33d3,0xb60eb4ff,0xa484aac8,0x34563378,0x28842ec3,0xb80ab715,0xb223b31c,0x29992376,0x35eb36c6,0xad97a776,
  0xb039b12d,0x2e8d2cac,0x3426350b,0xb27cb0a6,0xacacae8d,0x312d3039,0x30a6327c,0xb50bb426,0xa376a999,0x331c3223,0x27762d97,0xb6c6b5eb,
  0xb0d2b194,0x286b21e4,0x34b7356a,0xac6aa5e4,0xaea7b012,0x2d2a2b5f,0x32943402,0xb122af59,0xab5fad2a,0x30122ea7,0x2f593122,0xb402b294,
  0xa1e4a86b,0x319430d2,0x25e42c6a,0xb56ab4b7,0xaf0cb012,0x267b2052,0x32f73402,0xaa7aa452,0xacdeadf5,0x2b912967,0x30d731e8,0xaf8bad65,
  0xa967ab91,0x2df52cde,0x2d652f8b,0xb1e8b0d7,0xa052a67b,0x30122f0c,0x24522a7a,0xb402b2f7,0xac79ad2a,0x24201d7f,0x30743122,0xa81fa17f,
  0xaa31ab91,0x28d026e0,0x2e2d2f8b,0xacceaade,0xa6e0a8d0,0x2b912a31,0x2ade2cce,0xaf8bae2d,0x9d7fa420,0x2d2a2c79,0x217f281f,0xb122b074,
  0xa7a9a86b,0x1f1218b6,0x2ba72c6a,0xa3119cb6,0xa54da67b,0x242021e4,0x294d2a7a,0xa81fa5e4,0xa1e4a420,0x267b254d,0x25e4281f,0xaa7aa94d,
  0x98b69f12,0x286b27a9,0x1cb62311,0xac6aaba7,0x211b21e4,0x98b69248,0xa51ba5e4,0x1cb61648,0x1f122052,0x9d7f9bdb,0xa311a452,0x217f1fdb,
  0x1bdb1d7f,0xa0529f12,0x9fdba17f,0x24522311,0x124818b6,0xa1e4a11b,0x96489cb6,0x25e4251b,0x2a632b5f,0xa1e49bdb,0xae5faf59,0x25e41fdb,
  0x286b2967,0xa6e0a4e9,0xac6aad65,0x2ade28e8,0x24e926e0,0xa967a86b,0xa8e8aade,0x2d652c6a,0x1bdb21e4,0xab5faa63,0x9fdba5e4,0x2f592e5f,
  0x2dc22ea7,0xa54d9f12,0xb1b6b294,0x294d2311,0x2bf62cde,0xaa31a86b,0xafefb0d7,0x2e2d2c6a,0x286b2a31,0xacdeabf6,0xac6aae2d,0x30d72fef,
  0x1f12254d,0xaea7adc2,0xa311a94d,0x329431b6,0x302c30d2,0xa7a9a11b,0xb41ab4b7,0x2ba7251b,0x2dc22f0c,0xac79aa63,0xb1b6b2f7,0x30742e5f,
  0x2a632c79,0xaf0cadc2,0xae5fb074,0x32f731b6,0x211b27a9,0xb0d2b02c,0xa51baba7,0x34b7341a,0x317a3257,0xa902a2ad,0xb552b61a,0x2d0026ad,
  0x2f8c309f,0xaddcac2e,0xb371b487,0x31cf3029,0x2c2e2ddc,0xb09faf8c,0xb029b1cf,0x34873371,0x22ad2902,0xb257b17a,0xa6adad00,0x361a3552,
  0x32cd33e3,0xaa31a420,0xb682b76f,0x2e2d281f,0x30ac31bb,0xaf3fad2a,0xb493b58d,0x33283122,0x2d2a2f3f,0xb1bbb0ac,0xb122b328,0x358d3493,
  0x24202a31,0xb3e3b2cd,0xa81fae2d,0x376f3682,0x341334bc,0xab5fa4e9,0xb7a6b85a,0x2f5928e8,0x319432da,0xb052ae28,0xb56ab68d,0x343e3219,
  0x2e283052,0xb2dab194,0xb219b43e,0x368d356a,0x24e92b5f,0xb4bcb413,0xa8e8af59,0x385a37a6,0x34c3358c,0xac47a5b2,0xb85fb8f3,0x304229b1,
  0x327e33fd,0xb106af26,0xb63cb785,0x34e7330f,0x2f263106,0xb3fdb27e,0xb30fb4e7,0x3785363c,0x25b22c47,0xb58cb4c3,0xa9b1b042,0x38f3385f,
  0x35773662,0xacdea67b,0xb8e5b982,0x30d72a7a,0x336b3493,0xb1bbb012,0xb70ab83a,0x358d3402,0x301231bb,0xb493b36b,0xb402b58d,0x383a370a,
  0x267b2cde,0xb662b577,0xaa7ab0d7,0x398238e5,0x36303741,0xad76a744,0xb962ba04,0x316c2b43,0x342e352a,0xb271b092,0xb7d2b8ad,0x3631347b,
  0x30923271,0xb52ab42e,0xb47bb631,0x38ad37d2,0x27442d76,0xb741b630,0xab43b16c,0x3a043962,0x36ee3815,0xae0ea807,0xb9d6ba7a,0x32012c06,
  0x34a735c4,0xb329b113,0xb84ab91b,0x36d234f3,0x31133329,0xb5c4b4a7,0xb4f3b6d2,0x391b384a,0x28072e0e,0xb815b6ee,0xac06b201,0x3a7a39d6,
  0x37b4388e,0xaea7a86b,0xba41bae1,0x32942c6a,0x35233662,0xb3e3b194,0xb8a8b982,0x376f356a,0x319433e3,0xb662b523,0xb56ab76f,0x398238a8,
  0x286b2ea7,0xb88eb7b4,0xac6ab294,0x3ae13a41,0x3841390f,0xaf3fa8d0,0xbaa2bb3a,0x33282cce,0x35a13705,0xb44fb216,0xb902b9e3,0x380535df,
  0x3216344f,0xb705b5a1,0xb5dfb805,0x39e33902,0x28d02f3f,0xb90fb841,0xacceb328,0x3b3a3aa2,0x38ac3997,0xafd8a935,0xbaf7bb83,0x33ba2d33,
  0x362137ac,0xb4aeb298,0xb958ba3d,0x38503654,0x329834ae,0xb7acb621,0xb654b850,0x3a3d3958,0x29352fd8,0xb997b8ac,0xad33b3ba,0x3b833af7,
  0x391c3a28,0xb039a999,0xbb42bbbc,0x34262d97,0x36a4382d,0xb50eb31c,0xb9aaba90,0x389936c6,0x331c350e,0xb82db6a4,0xb6c6b899,0x3a9039aa,
  0x29993039,0xba28b91c,0xad97b426,0x3bbc3b42,0x39923ac3,0xb085a9fe,0xbb81bbe3,0x346f2dfb,0x372a3886,0xb570b3a0,0xb9f8badb,0x38e03737,
  0x33a03570,0xb886b72a,0xb737b8e0,0x3adb39f8,0x29fe3085,0xbac3b992,0xadfbb46f,0x3be33b81,
};

#define PROF(slot) do {} while (0)
#define PROF_DUMP() do {} while (0)
#define PROFA(slot, dep) do {} while (0)
#define PROF3(slot) do {} while (0)
#define PROF2(slot) do {} while (0)

__device__ __forceinline__ uint32_t smem_u32(const void* p) { return (uint32_t)__cvta_generic_to_shared(p); }

__device__ __forceinline__ void mbar_init(uint32_t a, uint32_t c) {
  asm volatile("mbarrier.init.shared::cta.b64 [%0], %1;\n" ::"r"(a), "r"(c) : "memory");
}
__device__ __forceinline__ void mbar_expect_tx(uint32_t a, uint32_t bytes) {
  asm volatile("mbarrier.arrive.expect_tx.shared::cta.b64 _, [%0], %1;\n" ::"r"(a), "r"(bytes) : "memory");
}
__device__ __forceinline__ void mbar_arrive_cluster(uint32_t cluster_addr) {
  asm volatile("mbarrier.arrive.shared::cluster.b64 _, [%0];\n" ::"r"(cluster_addr) : "memory");
}
__device__ __forceinline__ void mbar_arrive_cluster_n(uint32_t cluster_addr, uint32_t n) {
  asm volatile("mbarrier.arrive.shared::cluster.b64 _, [%0], %1;\n" ::"r"(cluster_addr), "r"(n) : "memory");
}
__device__ __forceinline__ bool mbar_try(uint32_t a, uint32_t parity) {
  uint32_t ok;
  asm volatile("{\n.reg .pred p;\nmbarrier.try_wait.parity.shared::cta.b64 p, [%1], %2;\nselp.u32 %0, 1, 0, p;\n}\n"
               : "=r"(ok) : "r"(a), "r"(parity) : "memory");
  return ok;
}
__device__ __forceinline__ void mbar_wait(uint32_t a, uint32_t parity) {
  if (mbar_try(a, parity)) return;
#pragma unroll 1
  for (int n = 0; n < SPIN_LIMIT; n++)
    if (mbar_try(a, parity)) break;
}
__device__ __forceinline__ bool elect_one() {
  uint32_t p;
  asm volatile("{\n.reg .pred P;\nelect.sync _|P, 0xffffffff;\nselp.u32 %0, 1, 0, P;\n}\n" : "=r"(p));
  return p;
}
__device__ __forceinline__ uint32_t mapa(uint32_t a, uint32_t rank) {
  uint32_t r;
  asm volatile("mapa.shared::cluster.u32 %0, %1, %2;\n" : "=r"(r) : "r"(a), "r"(rank));
  return r;
}
__device__ __forceinline__ void nb_sync(int id, int n) { asm volatile("bar.sync %0, %1;\n" ::"r"(id), "r"(n) : "memory"); }
__device__ __forceinline__ void nb_arrive(int id, int n) { asm volatile("bar.arrive %0, %1;\n" ::"r"(id), "r"(n) : "memory"); }
__device__ __forceinline__ void cluster_sync_all() {
  asm volatile("barrier.cluster.arrive.relaxed.aligned;\nbarrier.cluster.wait.aligned;\n" ::: "memory");
}
__device__ __forceinline__ void fence_async_smem() { asm volatile("fence.proxy.async.shared::cta;\n" ::: "memory"); }
__device__ __forceinline__ void fence_async_all() { asm volatile("fence.proxy.async.global;\n" ::: "memory"); }

__device__ __forceinline__ void tma_load_3d(uint32_t dst, const CUtensorMap* tm, uint32_t bar, int c0, int c1, int c2) {
  asm volatile(
      "cp.async.bulk.tensor.3d.shared::cluster.global.mbarrier::complete_tx::bytes [%0], [%1, {%3, %4, %5}], [%2];\n"
      ::"r"(dst), "l"(tm), "r"(bar), "r"(c0), "r"(c1), "r"(c2) : "memory");
}
__device__ __forceinline__ void tma_load_4d(uint32_t dst, const CUtensorMap* tm, uint32_t bar, int c0, int c1, int c2, int c3) {
  asm volatile(
      "cp.async.bulk.tensor.4d.shared::cluster.global.mbarrier::complete_tx::bytes [%0], [%1, {%3, %4, %5, %6}], [%2];\n"
      ::"r"(dst), "l"(tm), "r"(bar), "r"(c0), "r"(c1), "r"(c2), "r"(c3) : "memory");
}
__device__ __forceinline__ void tma_load_3d_mc(uint32_t dst, const CUtensorMap* tm, uint32_t bar, int c0, int c1, int c2) {
  asm volatile(
      "cp.async.bulk.tensor.3d.shared::cluster.global.mbarrier::complete_tx::bytes.multicast::cluster [%0], [%1, {%3, %4, %5}], [%2], %6;\n"
      ::"r"(dst), "l"(tm), "r"(bar), "r"(c0), "r"(c1), "r"(c2), "h"((uint16_t)3) : "memory");
}
__device__ __forceinline__ void bulk_load(uint32_t dst, const void* src, uint32_t bytes, uint32_t bar) {
  asm volatile("cp.async.bulk.shared::cluster.global.mbarrier::complete_tx::bytes [%0], [%1], %2, [%3];\n"
               ::"r"(dst), "l"(src), "r"(bytes), "r"(bar) : "memory");
}
__device__ __forceinline__ void tma_store_3d(const CUtensorMap* tm, uint32_t src, int c0, int c1, int c2) {
  asm volatile("cp.async.bulk.tensor.3d.global.shared::cta.bulk_group [%0, {%2, %3, %4}], [%1];\n"
               ::"l"(tm), "r"(src), "r"(c0), "r"(c1), "r"(c2) : "memory");
}
__device__ __forceinline__ void bulk_commit() { asm volatile("cp.async.bulk.commit_group;\n" ::: "memory"); }
__device__ __forceinline__ void bulk_wait0() { asm volatile("cp.async.bulk.wait_group 0;\n" ::: "memory"); }
__device__ __forceinline__ void prefetch_tmap(const CUtensorMap* tm) {
  asm volatile("prefetch.tensormap [%0];\n" ::"l"(tm) : "memory");
}

__device__ __forceinline__ void wg_fence() { asm volatile("wgmma.fence.sync.aligned;\n" ::: "memory"); }
__device__ __forceinline__ void wg_commit() { asm volatile("wgmma.commit_group.sync.aligned;\n" ::: "memory"); }
template <int N> __device__ __forceinline__ void wg_wait() {
  asm volatile("wgmma.wait_group.sync.aligned %0;\n" ::"n"(N) : "memory");
}
__device__ __forceinline__ uint64_t mkdesc(uint32_t addr, uint32_t lbo, uint32_t sbo, uint32_t swz) {
  return (uint64_t)((addr & 0x3FFFF) >> 4) | ((uint64_t)(lbo >> 4) << 16) | ((uint64_t)(sbo >> 4) << 32) |
         ((uint64_t)swz << 62);
}

#define R4(d, o) "+f"(d[o + 0]), "+f"(d[o + 1]), "+f"(d[o + 2]), "+f"(d[o + 3])
#define R8(d, o) R4(d, o), R4(d, o + 4)
#define R16(d, o) R8(d, o), R8(d, o + 8)
#define R32(d, o) R16(d, o), R16(d, o + 16)
#define R64(d, o) R32(d, o), R32(d, o + 32)

__device__ __forceinline__ void wgmma_n192(float (&d)[96], uint64_t da, uint64_t db, uint32_t acc) {
  asm volatile(
      "{\n.reg .pred p;\nsetp.ne.u32 p, %98, 0;\n"
      "wgmma.mma_async.sync.aligned.m64n192k16.f32.bf16.bf16 "
      "{%0,%1,%2,%3,%4,%5,%6,%7,%8,%9,%10,%11,%12,%13,%14,%15,%16,%17,%18,%19,%20,%21,%22,%23,%24,%25,%26,%27,%28,%29,%30,%31,"
      "%32,%33,%34,%35,%36,%37,%38,%39,%40,%41,%42,%43,%44,%45,%46,%47,%48,%49,%50,%51,%52,%53,%54,%55,%56,%57,%58,%59,%60,%61,%62,%63,"
      "%64,%65,%66,%67,%68,%69,%70,%71,%72,%73,%74,%75,%76,%77,%78,%79,%80,%81,%82,%83,%84,%85,%86,%87,%88,%89,%90,%91,%92,%93,%94,%95}, "
      "%96, %97, p, 1, 1, 0, 1;\n}\n"
      : R64(d, 0), R32(d, 64)
      : "l"(da), "l"(db), "r"(acc));
}
__device__ __forceinline__ void wgmma_n128(float (&d)[64], uint64_t da, uint64_t db, uint32_t acc) {
  asm volatile(
      "{\n.reg .pred p;\nsetp.ne.u32 p, %66, 0;\n"
      "wgmma.mma_async.sync.aligned.m64n128k16.f32.bf16.bf16 "
      "{%0,%1,%2,%3,%4,%5,%6,%7,%8,%9,%10,%11,%12,%13,%14,%15,%16,%17,%18,%19,%20,%21,%22,%23,%24,%25,%26,%27,%28,%29,%30,%31,"
      "%32,%33,%34,%35,%36,%37,%38,%39,%40,%41,%42,%43,%44,%45,%46,%47,%48,%49,%50,%51,%52,%53,%54,%55,%56,%57,%58,%59,%60,%61,%62,%63}, "
      "%64, %65, p, 1, 1, 0, 1;\n}\n"
      : R64(d, 0)
      : "l"(da), "l"(db), "r"(acc));
}
#define WG128(C, ACC)                                                                                                      \
  asm volatile(                                                                                                            \
      "{\n.reg .b64 a, b;\nmov.b64 a, {%64, %66};\nmov.b64 b, {%65, %66};\n"                                               \
      "wgmma.mma_async.sync.aligned.m64n128k16.f32.bf16.bf16 "                                                             \
      "{%0,%1,%2,%3,%4,%5,%6,%7,%8,%9,%10,%11,%12,%13,%14,%15,%16,%17,%18,%19,%20,%21,%22,%23,%24,%25,%26,%27,%28,%29,%30,%31," \
      "%32,%33,%34,%35,%36,%37,%38,%39,%40,%41,%42,%43,%44,%45,%46,%47,%48,%49,%50,%51,%52,%53,%54,%55,%56,%57,%58,%59,%60,%61," \
      "%62,%63}, a, b, " ACC ", 1, 1, 0, 1;\n}\n"                                                                          \
      : Z16(C, d, 0), Z16(C, d, 16), Z16(C, d, 32), Z16(C, d, 48)                                                          \
      : "r"(da), "r"(db), "r"(0x40000040))
#define Z4(C, d, o) C(d[o + 0]), C(d[o + 1]), C(d[o + 2]), C(d[o + 3])
#define Z16(C, d, o) Z4(C, d, o), Z4(C, d, o + 4), Z4(C, d, o + 8), Z4(C, d, o + 12)
__device__ __forceinline__ void wgmma_n128z(float (&d)[64], uint32_t da, uint32_t db) { WG128("=f", "0"); }
__device__ __forceinline__ void wgmma_n128a(float (&d)[64], uint32_t da, uint32_t db) { WG128("+f", "1"); }
template <int N> __device__ __forceinline__ void fence_regs(float (&d)[N]) {
#pragma unroll
  for (int i = 0; i < N; i++) asm volatile("" : "+f"(d[i])::"memory");
}

__device__ __forceinline__ void mma16816(float (&d)[4], uint32_t a0, uint32_t a1, uint32_t a2, uint32_t a3, uint32_t b0,
                                         uint32_t b1) {
  asm("mma.sync.aligned.m16n8k16.row.col.f32.bf16.bf16.f32 {%0,%1,%2,%3}, {%4,%5,%6,%7}, {%8,%9}, {%0,%1,%2,%3};\n"
      : "+f"(d[0]), "+f"(d[1]), "+f"(d[2]), "+f"(d[3])
      : "r"(a0), "r"(a1), "r"(a2), "r"(a3), "r"(b0), "r"(b1));
}
__device__ __forceinline__ void mma16816_z(float (&d)[4], uint32_t a0, uint32_t a1, uint32_t a2, uint32_t a3, uint32_t b0,
                                           uint32_t b1) {
  asm("mma.sync.aligned.m16n8k16.row.col.f32.bf16.bf16.f32 {%0,%1,%2,%3}, {%4,%5,%6,%7}, {%8,%9}, {%10,%10,%10,%10};\n"
      : "=f"(d[0]), "=f"(d[1]), "=f"(d[2]), "=f"(d[3])
      : "r"(a0), "r"(a1), "r"(a2), "r"(a3), "r"(b0), "r"(b1), "f"(0.f));
}
__device__ __forceinline__ void ldsm4t(uint32_t (&r)[4], uint32_t a) {
  asm volatile("ldmatrix.sync.aligned.m8n8.x4.trans.shared.b16 {%0,%1,%2,%3}, [%4];\n"
               : "=r"(r[0]), "=r"(r[1]), "=r"(r[2]), "=r"(r[3]) : "r"(a) : "memory");
}
__device__ __forceinline__ void ldsm2t(uint32_t& r0, uint32_t& r1, uint32_t a) {
  asm volatile("ldmatrix.sync.aligned.m8n8.x2.trans.shared.b16 {%0,%1}, [%2];\n" : "=r"(r0), "=r"(r1) : "r"(a) : "memory");
}
__device__ __forceinline__ void st_async128(uint32_t a, uint32_t bar, uint32_t x, uint32_t y, uint32_t z, uint32_t w) {
  asm volatile("st.async.weak.shared::cluster.mbarrier::complete_tx::bytes.v4.b32 [%0], {%2,%3,%4,%5}, [%1];\n"
               ::"r"(a), "r"(bar), "r"(x), "r"(y), "r"(z), "r"(w) : "memory");
}
__device__ __forceinline__ void mbar_arrive(uint32_t a) {
  asm volatile("mbarrier.arrive.shared::cta.b64 _, [%0];\n" ::"r"(a) : "memory");
}
__device__ __forceinline__ void stsm4(uint32_t a, uint32_t r0, uint32_t r1, uint32_t r2, uint32_t r3) {
  asm volatile("stmatrix.sync.aligned.m8n8.x4.shared.b16 [%0], {%1,%2,%3,%4};\n"
               ::"r"(a), "r"(r0), "r"(r1), "r"(r2), "r"(r3) : "memory");
}
__device__ __forceinline__ void stsm4t(uint32_t a, uint32_t r0, uint32_t r1, uint32_t r2, uint32_t r3) {
  asm volatile("stmatrix.sync.aligned.m8n8.x4.trans.shared.b16 [%0], {%1,%2,%3,%4};\n"
               ::"r"(a), "r"(r0), "r"(r1), "r"(r2), "r"(r3) : "memory");
}
__device__ __forceinline__ uint2 lds64(uint32_t a) {
  uint2 v;
  asm volatile("ld.shared.v2.u32 {%0,%1}, [%2];\n" : "=r"(v.x), "=r"(v.y) : "r"(a) : "memory");
  return v;
}
__device__ __forceinline__ uint4 lds128(uint32_t a) {
  uint4 v;
  asm volatile("ld.shared.v4.u32 {%0,%1,%2,%3}, [%4];\n" : "=r"(v.x), "=r"(v.y), "=r"(v.z), "=r"(v.w) : "r"(a) : "memory");
  return v;
}
__device__ __forceinline__ void sts128(uint32_t a, uint32_t x, uint32_t y, uint32_t z, uint32_t w) {
  asm volatile("st.shared.v4.u32 [%0], {%1,%2,%3,%4};\n" ::"r"(a), "r"(x), "r"(y), "r"(z), "r"(w) : "memory");
}
__device__ __forceinline__ void sts64(uint32_t a, uint32_t x, uint32_t y) {
  asm volatile("st.shared.v2.u32 [%0], {%1,%2};\n" ::"r"(a), "r"(x), "r"(y) : "memory");
}
__device__ __forceinline__ uint32_t pack_bf16(float lo, float hi) {
  uint32_t r;
  asm("cvt.rn.bf16x2.f32 %0, %1, %2;\n" : "=r"(r) : "f"(hi), "f"(lo));
  return r;
}
__device__ __forceinline__ uint32_t bmul2(uint32_t a, uint32_t b) {
  uint32_t r;
  asm("mul.rn.bf16x2 %0, %1, %2;\n" : "=r"(r) : "r"(a), "r"(b));
  return r;
}
__device__ __forceinline__ uint32_t bmax2(uint32_t a, uint32_t b) {
  uint32_t r;
  asm("max.bf16x2 %0, %1, %2;\n" : "=r"(r) : "r"(a), "r"(b));
  return r;
}
__device__ __forceinline__ uint32_t bfma2(uint32_t a, uint32_t b, uint32_t c) {
  uint32_t r;
  asm("fma.rn.bf16x2 %0, %1, %2, %3;\n" : "=r"(r) : "r"(a), "r"(b), "r"(c));
  return r;
}
__device__ __forceinline__ uint32_t clock32() {
  uint32_t t;
  asm volatile("mov.u32 %0, %%clock;\n" : "=r"(t));
  return t;
}
__device__ __forceinline__ void prefetch_l2(const void* p) { asm volatile("prefetch.global.L2 [%0];\n" ::"l"(p)); }
__device__ __forceinline__ void cp_async16(uint32_t dst, const void* src, uint32_t srcbytes) {
  asm volatile("cp.async.cg.shared.global.L2::256B [%0], [%1], 16, %2;\n" ::"r"(dst), "l"(src), "r"(srcbytes) : "memory");
}
__device__ __forceinline__ uint32_t ld_acquire(const uint32_t* p) {
  uint32_t v;
  asm volatile("ld.acquire.gpu.global.u32 %0, [%1];\n" : "=r"(v) : "l"(p) : "memory");
  return v;
}
__device__ __forceinline__ uint32_t ld_relaxed(const uint32_t* p) {
  uint32_t v;
  asm volatile("ld.relaxed.gpu.global.u32 %0, [%1];\n" : "=r"(v) : "l"(p) : "memory");
  return v;
}
__device__ __forceinline__ uint4 ld_b128(const uint4* p) {
  unsigned long long a, b;
  asm volatile("{\n.reg .b128 v;\nld.relaxed.gpu.global.b128 v, [%2];\nmov.b128 {%0, %1}, v;\n}\n" : "=l"(a), "=l"(b) : "l"(p) : "memory");
  return make_uint4((uint32_t)a, (uint32_t)(a >> 32), (uint32_t)b, (uint32_t)(b >> 32));
}
__device__ __forceinline__ void st_b128(uint4* p, uint32_t x, uint32_t y, uint32_t z, uint32_t w) {
  asm volatile("{\n.reg .b128 v;\nmov.b128 v, {%1, %2};\nst.relaxed.gpu.global.b128 [%0], v;\n}\n"
               ::"l"(p), "l"(x | (unsigned long long)y << 32), "l"(z | (unsigned long long)w << 32) : "memory");
}

struct Params {
  const __nv_bfloat16* x;
  const __nv_bfloat16* w;
  uint8_t tile[72];
  const __nv_bfloat16* q;
  const __nv_bfloat16* k;
  const __nv_bfloat16* v;
  const __nv_bfloat16* shift_k;
  const __nv_bfloat16* ssm_k;
  const __nv_bfloat16* ssm_D;
  const __nv_bfloat16* wo;
  __nv_bfloat16* out;
  uint32_t zero;
};

__device__ __forceinline__ uint32_t lds32(uint32_t a) {
  uint32_t v;
  asm volatile("ld.shared.u32 %0, [%1];\n" : "=r"(v) : "r"(a) : "memory");
  return v;
}
__device__ __forceinline__ float bf_lo(uint32_t v) {
  uint32_t r;
  asm("prmt.b32 %0, %1, 0, 0x1044;\n" : "=r"(r) : "r"(v));
  return __uint_as_float(r);
}
__device__ __forceinline__ float bf_hi(uint32_t v) { return __uint_as_float(v & 0xffff0000u); }
__device__ __forceinline__ float ex2(float x) {
  float r;
  asm("ex2.approx.ftz.f32 %0, %1;\n" : "=f"(r) : "f"(x));
  return r;
}
__device__ __forceinline__ float rcp(float x) {
  float r;
  asm("rcp.approx.ftz.f32 %0, %1;\n" : "=f"(r) : "f"(x));
  return r;
}

#define Q4(c, d, o) c(d[o + 0]), c(d[o + 1]), c(d[o + 2]), c(d[o + 3])
#define Q8(c, d, o) Q4(c, d, o), Q4(c, d, o + 4)
#define Q16(c, d, o) Q8(c, d, o), Q8(c, d, o + 8)
#define Q32(c, d) Q16(c, d, 0), Q16(c, d, 16)
#define L8 "{%0,%1,%2,%3,%4,%5,%6,%7}"
#define L16 "{%0,%1,%2,%3,%4,%5,%6,%7,%8,%9,%10,%11,%12,%13,%14,%15}"
#define L32 "{%0,%1,%2,%3,%4,%5,%6,%7,%8,%9,%10,%11,%12,%13,%14,%15,%16,%17,%18,%19,%20,%21,%22,%23,%24,%25,%26,%27,%28,%29,%30,%31}"
__device__ __forceinline__ void fft_rows(uint32_t (&d)[32], const uint32_t (&a)[2][4], uint64_t db) {
  asm volatile("wgmma.mma_async.sync.aligned.m64n128k16.f16.f16.f16 " L32 ", {%32,%33,%34,%35}, %36, 0, 1, 1, 1;\n"
               : Q32("=r", d) : "r"(a[0][0]), "r"(a[0][1]), "r"(a[0][2]), "r"(a[0][3]), "l"(db));
  asm volatile("wgmma.mma_async.sync.aligned.m64n128k16.f16.f16.f16 " L32 ", {%32,%33,%34,%35}, %36, 1, 1, 1, 1;\n"
               : Q32("+r", d) : "r"(a[1][0]), "r"(a[1][1]), "r"(a[1][2]), "r"(a[1][3]), "l"(db + 64));
}
template <int INV> __device__ __forceinline__ void fft_cols(uint32_t (&d)[8], const uint32_t (&a)[2][4], uint64_t db) {
  asm volatile("wgmma.mma_async.sync.aligned.m64n32k16.f16.f16.f16 " L8 ", {%8,%9,%10,%11}, %12, 0, 1, 1, %13;\n"
               : Q8("=r", d, 0) : "r"(a[0][0]), "r"(a[0][1]), "r"(a[0][2]), "r"(a[0][3]), "l"(db), "n"(INV));
  asm volatile("wgmma.mma_async.sync.aligned.m64n32k16.f16.f16.f16 " L8 ", {%8,%9,%10,%11}, %12, 1, 1, 1, %13;\n"
               : Q8("+r", d, 0) : "r"(a[1][0]), "r"(a[1][1]), "r"(a[1][2]), "r"(a[1][3]), "l"(db + (INV ? 16 : 64)), "n"(INV));
}
__device__ __forceinline__ void fft_back(float (&d)[16], uint64_t da, uint64_t db) {
  asm volatile("wgmma.mma_async.sync.aligned.m64n32k16.f32.f16.f16 " L16 ", %16, %17, 0, 1, 1, 1, 1;\n"
               : Q16("=f", d, 0) : "l"(da), "l"(db));
#pragma unroll
  for (int i = 1; i < 4; i++)
    asm volatile("wgmma.mma_async.sync.aligned.m64n32k16.f32.f16.f16 " L16 ", %16, %17, 1, 1, 1, 1, 1;\n"
                 : Q16("+f", d, 0) : "l"(da + 32 * i), "l"(db + 64 * i));
}
__device__ __forceinline__ uint32_t hmul2(uint32_t a, uint32_t b) {
  uint32_t r;
  asm("mul.rn.f16x2 %0, %1, %2;\n" : "=r"(r) : "r"(a), "r"(b));
  return r;
}
__device__ __forceinline__ uint32_t hadd2(uint32_t a, uint32_t b) {
  uint32_t r;
  asm("add.rn.f16x2 %0, %1, %2;\n" : "=r"(r) : "r"(a), "r"(b));
  return r;
}
__device__ __forceinline__ uint32_t hneg2(uint32_t a) {
  uint32_t r;
  asm("neg.f16x2 %0, %1;\n" : "=r"(r) : "r"(a));
  return r;
}
__device__ __forceinline__ uint32_t hfma2(uint32_t a, uint32_t b, uint32_t c) {
  uint32_t r;
  asm("fma.rn.f16x2 %0, %1, %2, %3;\n" : "=r"(r) : "r"(a), "r"(b), "r"(c));
  return r;
}
__device__ __forceinline__ uint32_t pack_f16(float lo, float hi) {
  uint32_t r;
  asm("cvt.rn.f16x2.f32 %0, %1, %2;\n" : "=r"(r) : "f"(hi), "f"(lo));
  return r;
}
__device__ __forceinline__ uint32_t bmaxabs2(uint32_t a, uint32_t b) {
  uint32_t r;
  asm("max.xorsign.abs.bf16x2 %0, %1, %2;\n" : "=r"(r) : "r"(a), "r"(b));
  return r;
}
struct C2 { uint32_t r, i; };
__device__ __forceinline__ C2 cmul(C2 a, C2 b) {
  return C2{hfma2(a.r, b.r, hneg2(hmul2(a.i, b.i))), hfma2(a.r, b.i, hmul2(a.i, b.r))};
}
__device__ __forceinline__ C2 cfma(C2 a, C2 b, C2 c) {
  return C2{hfma2(a.r, b.r, hfma2(hneg2(a.i), b.i, c.r)), hfma2(a.r, b.i, hfma2(a.i, b.r, c.i))};
}
__device__ __forceinline__ C2 crot(C2 z, C2 t) {
  const uint32_t r = hfma2(t.r, z.i, z.r), i = hfma2(t.i, r, z.i);
  return C2{hfma2(t.r, i, r), i};
}
__device__ __forceinline__ C2 cget(const uint32_t (&e)[8], int j, int b) { return C2{e[4 * j + b], e[4 * j + 2 + b]}; }
template <int N> __device__ __forceinline__ void fence_regs(uint32_t (&d)[N]) {
#pragma unroll
  for (int i = 0; i < N; i++) asm volatile("" : "+r"(d[i])::"memory");
}
__device__ __forceinline__ void ldsm4(uint32_t (&r)[4], uint32_t a) {
  asm volatile("ldmatrix.sync.aligned.m8n8.x4.shared.b16 {%0,%1,%2,%3}, [%4];\n"
               : "=r"(r[0]), "=r"(r[1]), "=r"(r[2]), "=r"(r[3]) : "r"(a) : "memory");
}

__device__ __forceinline__ uint32_t movm(uint32_t a) {
  uint32_t r;
  asm volatile("movmatrix.sync.aligned.m8n8.trans.b16 %0, %1;\n" : "=r"(r) : "r"(a));
  return r;
}
template <int C0, int H, bool T> __device__ __forceinline__ void attn_pack(const float (&acc)[96], uint32_t (&d)[8]) {
#pragma unroll
  for (int c = 0; c < 8; c++) {
    asm volatile("cvt.rn.bf16x2.f32 %0, %1, %2;\n" : "=r"(d[c]) : "f"(acc[4 * (C0 + c) + 2 * H + 1]), "f"(acc[4 * (C0 + c) + 2 * H]));
    if (T) d[c] = movm(d[c]);
  }
}
__device__ __forceinline__ void attn_qk(float (&s)[4], const uint32_t (&qlo)[8], const uint32_t (&qhi)[8],
                                        const uint32_t (&k)[8], int c) {
  mma16816_z(s, qlo[c], qhi[c], qlo[c + 1], qhi[c + 1], k[c], k[c + 1]);
  mma16816(s, qlo[c + 2], qhi[c + 2], qlo[c + 3], qhi[c + 3], k[c + 2], k[c + 3]);
}
template <int N> __device__ __forceinline__ void quad_softmax(float (&x)[N][2], uint32_t (&pp)[N]) {
  const float c2 = 1.4426950408889634f;
  uint32_t q[N], mx[N / 2];
#pragma unroll
  for (int n = 0; n < N; n++) {
    const uint32_t r = pack_bf16(x[n][0], x[n][1]);
    q[n] = bfma2(r, 0x3e353e35u, bmul2(r, 0x379e379eu));
    x[n][0] = bf_lo(q[n]);
    x[n][1] = bf_hi(q[n]);
  }
#pragma unroll
  for (int n = 0; n < N / 2; n++)
    mx[n] = bmax2(__byte_perm(q[2 * n], q[2 * n + 1], 0x5410), __byte_perm(q[2 * n], q[2 * n + 1], 0x7632));
#pragma unroll
  for (int o = 1; o <= 2; o++) {
#pragma unroll
    for (int n = 0; n < N / 2; n++) mx[n] = bmax2(mx[n], __shfl_xor_sync(0xffffffffu, mx[n], o));
  }
  float m[N], t[N];
#pragma unroll
  for (int n = 0; n < N / 2; n++) {
    m[2 * n] = bf_lo(mx[n]);
    m[2 * n + 1] = bf_hi(mx[n]);
  }
#pragma unroll
  for (int n = 0; n < N; n++) {
    const float nm = -m[n] * c2;
    x[n][0] = ex2(fmaf(x[n][0], c2, nm));
    x[n][1] = ex2(fmaf(x[n][1], c2, nm));
  }
#pragma unroll
  for (int n = 0; n < N; n += 2) {
    float u0, u1;
    asm("mma.sync.aligned.m16n8k8.row.col.f32.tf32.tf32.f32 {%0,%1,%2,%3}, {%4,%5,%6,%7}, {%8,%8}, {%9,%9,%9,%9};\n"
        : "=f"(t[n]), "=f"(u0), "=f"(t[n + 1]), "=f"(u1)
        : "r"(__float_as_uint(x[n][0])), "r"(__float_as_uint(x[n + 1][0])), "r"(__float_as_uint(x[n][1])),
          "r"(__float_as_uint(x[n + 1][1])), "r"(0x3f800000u), "f"(0.f));
  }
#pragma unroll
  for (int n = 0; n < N; n++) {
    const float inv = rcp(t[n]);
    pp[n] = pack_bf16(x[n][0] * inv, x[n][1] * inv);
  }
}
template <bool SPLIT>
__device__ __forceinline__ void attn_pv(uint32_t dst, const uint32_t (&vp)[8], const uint32_t (&vo)[8], int c, uint32_t pp,
                                        uint32_t maskLE) {
  const uint32_t b0 = pp & ~maskLE, b1 = pp & maskLE;
  float o[2][4];
#pragma unroll
  for (int i = 0; i < 2; i++) {
    if (SPLIT) {
      asm("mma.sync.aligned.m16n8k8.row.col.f32.bf16.bf16.f32 {%0,%1,%2,%3}, {%4,%5}, {%6}, {%7,%7,%7,%7};\n"
          : "=f"(o[i][0]), "=f"(o[i][1]), "=f"(o[i][2]), "=f"(o[i][3])
          : "r"(vp[c + 2 * i]), "r"(vp[c + 2 * i + 1]), "r"(b0), "f"(0.f));
      asm("mma.sync.aligned.m16n8k8.row.col.f32.bf16.bf16.f32 {%0,%1,%2,%3}, {%4,%5}, {%6}, {%0,%1,%2,%3};\n"
          : "+f"(o[i][0]), "+f"(o[i][1]), "+f"(o[i][2]), "+f"(o[i][3])
          : "r"(vo[c + 2 * i]), "r"(vo[c + 2 * i + 1]), "r"(b1));
    } else {
      mma16816_z(o[i], vp[c + 2 * i], vp[c + 2 * i + 1], vo[c + 2 * i], vo[c + 2 * i + 1], b0, b1);
    }
  }
  stsm4t(dst, pack_bf16(o[0][0], o[0][1]), pack_bf16(o[0][2], o[0][3]), pack_bf16(o[1][0], o[1][1]),
         pack_bf16(o[1][2], o[1][3]));
}

template <int MODE>
__global__ void __cluster_dims__(2, 1, 1) __launch_bounds__(NTHREADS, 1)
fused_kernel(const Params p, const __grid_constant__ CUtensorMap tmX, const __grid_constant__ CUtensorMap tmW,
             const __grid_constant__ CUtensorMap tmWo, const __grid_constant__ CUtensorMap tmWp,
             const __grid_constant__ CUtensorMap tmQ,
             const __grid_constant__ CUtensorMap tmOb,
             const __grid_constant__ CUtensorMap tmXh, const __grid_constant__ CUtensorMap tmWh) {
  extern __shared__ __align__(1024) uint8_t smem[];
  const int tid = threadIdx.x;
  if (tid >= 352) {
    const uint32_t i = (blockIdx.x & 127) * 16 + (tid & 15);
    prefetch_l2(tid & 16 ? (const char*)p.w + i * 128 : (const char*)p.x + i * 2048);
  }
  const uint32_t sb = smem_u32(smem);
  const int rank = blockIdx.x & 1;
  const bool halo_cta = blockIdx.x < 4;
  if (halo_cta && MODE != 0) return;
  const int tile = p.tile[blockIdx.x >> 1];
  const int rg = tile >> 3, hp = (tile & 7) * 2 + rank;
  const int par = rg >> 2, gidx = rg & 3;
  if (tid < 256 && !halo_cta && MODE != 2) {
    const uint32_t r = tid >> 3, c = tid & 7;
    asm volatile(
        "cp.async.cg.shared.global [%0 + 98304], [%1], 16;\ncp.async.cg.shared.global [%0 + 102400], [%1 + 2048], 16;\n"
        "cp.async.cg.shared.global [%0 + 106496], [%1 + 4096], 16;\ncp.async.cg.shared.global [%0], [%2], 16;\n"
        "cp.async.cg.shared.global [%0 + 4096], [%2 + 131072], 16;\ncp.async.cg.shared.global [%0 + 8192], [%2 + 262144], 16;\n"
        "cp.async.cg.shared.global [%0 + 12288], [%2 + 393216], 16;\ncp.async.cg.shared.global [%0 + 16384], [%2 + 524288], 16;\n"
        "cp.async.cg.shared.global [%0 + 20480], [%2 + 655360], 16;\ncp.async.cg.shared.global [%0 + 24576], [%2 + 786432], 16;\n"
        "cp.async.cg.shared.global [%0 + 28672], [%2 + 917504], 16;\ncp.async.commit_group;\n"
        ::"r"(sb + r * 128 + ((c ^ (r & 7)) << 4)), "l"((const char*)p.w + (r * 6144 + c * 16 + hp * 128)),
        "l"((const char*)p.x + (r * 4096 + c * 16 + gidx * 1048576 + par * 2048)) : "memory");
    static_assert(OFF_1B == 98304, "offsets above");
  }
  const uint32_t bars = sb + OFF_BAR;
  const int lane = tid & 31, warp = __shfl_sync(0xffffffffu, tid >> 5, 0);
  const int grp = par * 4 + (hp >> 2), mem = gidx * 2 + ((hp >> 1) & 1);
  const int rb2 = par * 8 + mem, cb2 = (grp & 3) * 2 + rank;
  const int chb = grp * 16 + mem * 2 + rank;
  const int cta = rg * 16 + hp;
  const int hsel = rb2 & 1;

  if (warp >= 8) {
    asm volatile("setmaxnreg.dec.sync.aligned.u32 %0;\n" :: "n"(REG_HELP));
    auto halo_issue = [&](int n, int s) {
      const uint32_t fb = bars + 8 * ((n & 1 ? BAR_FULL2 : BAR_FULLB) + s), st = sb + s * STGH;
      tma_load_3d(st + 8192, &tmWh, fb, 0, (n >> 1) * 64, 16 + (n & 1) * 16 + blockIdx.x * 4);
      tma_load_4d(st, &tmXh, fb, (n >> 1) * 64, 248, 0, 0);
      mbar_expect_tx(fb, STGH - 2048);
    };
    if (tid == 256) {
      prefetch_tmap(halo_cta ? &tmXh : &tmX);
#pragma unroll
      for (int i = 0; i < NS1B; i++) mbar_init(bars + 8 * (BAR_FULLB + i), 1);
#pragma unroll
      for (int i = 0; i < NS1A; i++) mbar_init(bars + 8 * (BAR_FULLA + i), 1);
      asm volatile("fence.mbarrier_init.release.cluster;\n" ::: "memory");
      if (!halo_cta && MODE != 2) {
        mbar_expect_tx(bars + 8 * (BAR_FULLB + 1), STG1B);
        tma_load_3d(sb + OFF_1B + 1 * STG1B, &tmW, bars + 8 * (BAR_FULLB + 1), hp * 64, 32, 0);
        mbar_expect_tx(bars + 8 * (BAR_FULLA + 1), STG1A);
        tma_load_3d(sb + STG1A, &tmX, bars + 8 * (BAR_FULLA + 1), 64, par, gidx * 256);
        tma_load_3d(sb + STG1A + 16384, &tmX, bars + 8 * (BAR_FULLA + 1), 64, par, gidx * 256 + 128);
        mbar_expect_tx(bars + 8 * (BAR_FULLB + 2), STG1B);
        tma_load_3d(sb + OFF_1B + 2 * STG1B, &tmW, bars + 8 * (BAR_FULLB + 2), hp * 64, 64, 0);
        mbar_arrive(bars + 8 * BAR_FULLA);
        mbar_arrive(bars + 8 * BAR_FULLB);
      } else if (halo_cta) {
        halo_issue(0, 0);
      }
    } else if (tid >= 289 && tid < 289 + 48 && tid != 320) {
      const uint32_t i = tid - 289 - (tid > 320), b = blockIdx.x & 127;
      if (MODE != 2) prefetch_l2(i < 16 ? (const char*)p.x + (b * 16 + i) * 2048 + 128 : (const char*)p.w + (2048 + b * 31 + i - 16) * 128);
    } else if (tid == 288) {
#pragma unroll
      for (int i = 0; i < NS1A; i++) mbar_init(bars + 8 * (BAR_EMPTYA + i), 4);
#pragma unroll
      for (int i = 0; i < NS1B; i++) mbar_init(bars + 8 * (BAR_EMPTYB + i), 2);
      mbar_init(bars + 8 * BAR_X, 3);
      mbar_init(bars + 8 * BAR_TAB, 16);
      mbar_init(bars + 8 * BAR_U, 1);
      mbar_init(bars + 8 * BAR_H, 1);
      mbar_init(bars + 8 * BAR_Q, 1);
      mbar_init(bars + 8 * BAR_LAND, 5);
      mbar_init(bars + 8 * (BAR_LAND + 1), 5);
      asm volatile("fence.mbarrier_init.release.cluster;\n" ::: "memory");
    } else if (tid == 320) {
#pragma unroll
      for (int i = 0; i < NS2; i++) {
        mbar_init(bars + 8 * (BAR_FULL2 + i), 1);
        mbar_init(bars + 8 * (BAR_EMPTY2 + i), 2);
        mbar_init(bars + 8 * (BAR_EMPTY2B + i), 2);
      }
      asm volatile("fence.mbarrier_init.release.cluster;\n" ::: "memory");
    } else if (tid == 352) {
#pragma unroll
      for (int i = 0; i < 4; i++) mbar_init(bars + 8 * (BAR_Y + i), i < 2 ? 4 : i == 2 ? 10 : 8);
      mbar_init(bars + 8 * BAR_XFREE, 1);
#pragma unroll
      for (int i = 0; i < 9; i++) mbar_init(bars + 8 * (BAR_KH + i), 1);
      asm volatile("fence.mbarrier_init.release.cluster;\n" ::: "memory");
    }
    __syncwarp();
    cluster_sync_all();
    if (warp == 8) PROF2(24);
    const int hw = warp - 8;
    const int lr = lane & 7, lm = lane >> 3;
    auto g1_issue_a = [&](int j, int s) {
      const uint32_t fb = bars + 8 * (BAR_FULLA + s);
      mbar_expect_tx(fb, STG1A);
      tma_load_3d_mc(sb + s * STG1A + rank * 16384, &tmX, fb, j * 64, par, gidx * 256 + rank * 128);
    };
    auto g1_issue_b = [&](int kb, int s) {
      const uint32_t fb = bars + 8 * (BAR_FULLB + s);
      mbar_expect_tx(fb, STG1B);
      tma_load_3d(sb + OFF_1B + s * STG1B, &tmW, fb, hp * 64, kb * 32, 0);
    };
    auto g2_k = [&](int kb) { return (kb < 2 ? hp : kb < 4 ? hp & 14 : hp & 12) ^ kb; };
    auto g2_issue_b = [&](uint32_t fb, uint32_t bytes, uint32_t dst, int k0, bool whole) {
      if (whole) {
        tma_load_3d(dst, &tmWo, fb, 0, k0, cb2 * 2);
      } else {
#pragma unroll
        for (int i = 0; i < 4; i++)
          tma_load_3d(dst + (i & 1) * XT + (i >> 1) * 4 * XT, &tmWp, fb, 0, k0 + (i >> 1) * 32, cb2 * 2 + (i & 1));
      }
      mbar_expect_tx(fb, bytes);
    };
    auto send_y = [&](uint32_t o, uint32_t step, int half) {
      const uint32_t peer = mapa(sb, rank ^ 1);
      o += OFF_X + (rank ^ 1) * 4096 + half * 2048 + lane * 16;
      uint4 a[8];
#pragma unroll
      for (int i = 0; i < 8; i++) a[i] = lds128(sb + o + (i >> 2) * step + (i & 2) * (XT / 2) + (i & 1) * 512);
#pragma unroll
      for (int i = 0; i < 8; i++)
        st_async128(peer + o + 1024 + (i >> 2) * step + (i & 2) * (XT / 2) + (i & 1) * 512,
                    peer + OFF_BAR + 8 * (BAR_LAND + half), a[i].x, a[i].y, a[i].z, a[i].w);
    };

    if (halo_cta) {
      if (hw == 0) {
        int s = 1, ph = 1;
#pragma unroll 1
        for (int n = 1; n < 32; n++) {
          mbar_wait(bars + 8 * (BAR_EMPTYB + s), ph);
          if (elect_one()) halo_issue(n, s);
          if (++s == NS1B) { s = 0; ph ^= 1; }
        }
      }
      __syncwarp();
    } else if (hw == 0) {
      uint32_t epoch = 0;
      if (MODE == 2) {
        if (lane < NS2) mbar_arrive_cluster_n(mapa(bars, rank) + 8 * (BAR_EMPTY2 + lane), 2);
      } else {
      if (lane == 0) {
        mbar_expect_tx(bars + 8 * BAR_U, 32768);
        mbar_expect_tx(bars + 8 * BAR_LAND, 8192);
        mbar_expect_tx(bars + 8 * (BAR_LAND + 1), 8192);
        mbar_expect_tx(bars + 8 * BAR_Q, 32768);
        prefetch_tmap(&tmQ);
      }
      {
        int sa = 2, pha = 1, sbb = 3, phb = 1;
#pragma unroll 1
        for (int kb = 3; kb < 32; kb++) {
          if (!(kb & 1)) {
            mbar_wait(bars + 8 * (BAR_EMPTYA + sa), pha);
            if (elect_one()) g1_issue_a(kb >> 1, sa);
            if (++sa == NS1A) { sa = 0; pha ^= 1; }
          }
          mbar_wait(bars + 8 * (BAR_EMPTYB + sbb), phb);
          if (elect_one()) g1_issue_b(kb, sbb);
          __syncwarp();
          if (kb == 4) epoch = ld_relaxed(g_flag_o + FS * cta);
          if (kb == 4) PROF2(27);
          if (++sbb == NS1B) { sbb = 0; phb ^= 1; }
        }
      }
      auto q_issue = [&](int i) {
        mbar_wait(bars + 8 * (i ? BAR_EMPTYB + 3 : BAR_EMPTYA + 1), i);
        if (elect_one())
          asm volatile(
              "cp.async.bulk.tensor.5d.shared::cluster.global.mbarrier::complete_tx::bytes [%0], [%1, {%3, %4, %4, %4, %5}], [%2];\n"
              ::"r"(sb + (i ? OFF_Q1 : OFF_Q0)), "l"(&tmQ), "r"(bars + 8 * BAR_Q), "r"((chb & ~1) * 8), "r"(0), "r"(rank * 32 + i * 64)
              : "memory");
        __syncwarp();
      };
      epoch++;
      if (lane == 0) {
        asm volatile("st.shared.u32 [%0], %1;\n" ::"r"(sb + OFF_EX - 4), "r"(epoch) : "memory");
        prefetch_tmap(&tmWo);
        prefetch_tmap(&tmWp);
        prefetch_tmap(&tmOb);
      }
      __syncwarp();
      {
        uint4 h[6] = {};
        if (gidx != 0) {
#pragma unroll 1
          for (int n = 0; n < SPIN_LIMIT; n++) {
            bool ok = true;
#pragma unroll
            for (int i = 0; i < 6; i++) h[i] = ld_b128(g_halo + cta * 192 + i * 32 + lane);
#pragma unroll
            for (int i = 0; i < 6; i++) ok = ok && h[i].w == epoch;
            if (__all_sync(0xffffffffu, ok)) break;
          }
          PROF(18);
        }
        q_issue(0);
        sts128(sb + OFF_KH + lane * 16, h[0].x, h[0].y, h[0].z, h[1].x);
        sts128(sb + OFF_KH + 512 + lane * 16, h[1].y, h[1].z, h[2].x, h[2].y);
        sts64(sb + OFF_KH + 1024 + lane * 8, h[3].x, h[3].y);
        sts64(sb + OFF_KH + 1280 + lane * 8, h[3].z, h[4].x);
        sts64(sb + OFF_KH + 1536 + lane * 8, h[4].y, h[4].z);
        sts64(sb + OFF_KH + 1792 + lane * 8, h[5].x, h[5].y);
        __syncwarp();
        if (lane == 0) mbar_arrive(bars + 8 * BAR_KH);
      }
      q_issue(1);
      const uint32_t rb = mapa(bars, lane & 1);
      nb_sync(NB_OREADY, 288);
      if (lane == 0) {
        asm volatile("cp.async.bulk.global.shared::cta.bulk_group [%0], [%1], %2;\n" ::"l"(g_o + (size_t)cta * 16384),
                     "r"(sb + OFF_OP), "r"(32768) : "memory");
        bulk_commit();
      }
      if (lane < 2) {
#pragma unroll
        for (int i = 0; i < 4; i++) mbar_arrive_cluster(rb + 8 * (BAR_EMPTY2 + i + i / 2));
      }
      if (lane == 0) {
        bulk_wait0();
        asm volatile("fence.acq_rel.gpu;\nst.relaxed.gpu.global.u32 [%0], %1;\n"
                     "mbarrier.arrive.relaxed.cluster.shared::cluster.b64 _, [%2];\n"
                     "mbarrier.arrive.relaxed.cluster.shared::cluster.b64 _, [%3];\n"
                     ::"l"(g_flag_o + FS * cta), "r"(epoch), "r"(mapa(bars, rank ^ 1) + 8 * (BAR_EMPTY2 + 2)),
                     "r"(mapa(bars, rank) + 8 * (BAR_EMPTY2 + 2)) : "memory");
      }
      __syncwarp();
      PROF2(17);
      }
      if (MODE != 1) {
        const __nv_bfloat16* osrc = g_o + (size_t)(rb2 >> 1) * 16 * 16384 + hsel * 8192;
        if (elect_one()) {
          if (MODE != 0) bulk_load(sb + g2_a(0, hsel), osrc + hp * 16384, 16384, bars + 8 * BAR_FULL2);
#pragma unroll
          for (int kb = 1; kb < 3; kb++)
            g2_issue_b(bars + 8 * (BAR_FULL2 + kb), STG2, sb + g2_b(kb, 0), g2_k(kb) * 64, true);
        }
        mbar_wait(bars + 8 * (BAR_EMPTY2 + 2), 0);
        asm volatile("{\n.reg .pred p;\nmbarrier.test_wait.parity.acquire.cluster.shared::cta.b64 p, [%0], 0;\n}\n"
                     ::"r"(bars + 8 * (BAR_EMPTY2 + 2)) : "memory");
        fence_async_all();
        if (elect_one()) bulk_load(sb + g2_a(1, hsel), osrc + (hp ^ 1) * 16384, 16384, bars + 8 * (BAR_FULL2 + 1));
        __syncwarp();
      }
      if (MODE != 2) {
        mbar_wait(bars + 8 * (BAR_Y + 2), 0);
        send_y(0, 4 * XT, 1);
        fence_async_smem();
        __syncwarp();
      }
      if (MODE != 1) {
        int s = 3, k0 = g2_k(3) * 64;
        uint32_t wbar = bars + 8 * (BAR_Y + 2), fb = bars + 8 * (BAR_FULL2 + 3), dst = sb + g2_b(3, rank), ph = MODE ? 1 : 0;
        int whole = 0;
#pragma unroll 1
        for (int kb = 3; kb < 16;) {
          mbar_wait(wbar, ph);
          if (elect_one()) g2_issue_b(fb, STG2, dst, k0, whole);
          __syncwarp();
          kb++;
          if (++s == NS2) { s = 0; ph = kb == 2 * NS2; }
          wbar = bars + 8 * (kb == 4 ? BAR_XFREE : BAR_EMPTY2B + s);
          fb = bars + 8 * (BAR_FULL2 + s);
          dst = sb + g2_b(s, rank);
          k0 = ((hp & 12) ^ kb) * 64;
          whole = s < 3;
          asm volatile("" : "+r"(fb), "+r"(k0), "+r"(whole));
        }
      }
      __syncwarp();
    } else {
      if (MODE != 2) {
      const float dall = __bfloat162float(p.ssm_D[chb * 8 + lr]);
      {
        const int g = lane >> 2, t = lane & 3;
        uint32_t w[2][4];
#pragma unroll
        for (int h = 0; h < 2; h++) {
          const uint2 x = __ldg(reinterpret_cast<const uint2*>(p.shift_k + ((chb & ~1) * 8 + h * 8 + g) * 4));
          w[h][0] = __byte_perm(x.x, x.x, 0x1010);
          w[h][1] = __byte_perm(x.x, x.x, 0x3232);
          w[h][2] = __byte_perm(x.y, x.y, 0x1010);
          w[h][3] = __byte_perm(x.y, x.y, 0x3232);
        }
        auto swz = [](int r) { return (((r & 29) | ((r ^ (r >> 2)) & 2)) << 5) | (r & 16); };
        const uint32_t kring = sb + OFF_X + 4096 + (hw - 1) * 2 * XT, vring = kring + XT;
        const int s0 = rank * 32 + (hw - 1) * 11, s1 = hw == 3 ? rank * 32 + 32 : s0 + 11;
        const size_t goff = (size_t)(s0 * 32 + (lane >> 1)) * DM + (chb & ~1) * 8 + (lane & 1) * 8;
        const __nv_bfloat16* kg = p.k + goff;
        const __nv_bfloat16* vg = p.v + goff;
        const uint32_t d0 = swz(lane >> 1) ^ ((lane & 1) << 4), d1 = swz(16 + (lane >> 1)) ^ ((lane & 1) << 4);
        auto issue = [&](int st) {
          const uint32_t a = kring + ((st & 3) << 10);
          asm volatile("cp.async.cg.shared.global.L2::256B [%0], [%2], 16;\n"
                       "cp.async.cg.shared.global.L2::256B [%1], [%2 + 32768], 16;\n"
                       "cp.async.cg.shared.global.L2::256B [%0 + 8192], [%3], 16;\n"
                       "cp.async.cg.shared.global.L2::256B [%1 + 8192], [%3 + 32768], 16;\n"
                       ::"r"(a + d0), "r"(a + d1), "l"(kg), "l"(vg) : "memory");
          kg += 32 * DM;
          vg += 32 * DM;
          asm volatile("" : "+l"(kg), "+l"(vg));
        };
        const int xa = 8 * (lr >> 1) + 2 * lm + (lr & 1), xb = 8 * (lr >> 1) - 4 + 2 * (lm & 1) + (lr & 1);
        const uint32_t la = swz(xa), lb = swz(xb & 31);
        const int backb = xb < 0 ? 1 : 0;
        const uint32_t ud[2] = {mapa(sb + OFF_X + g * XT + t * 16, 0), mapa(sb + OFF_X + g * XT + t * 16, 1)};
        const uint32_t ub[2] = {mapa(bars + 8 * BAR_U, 0), mapa(bars + 8 * BAR_U, 1)};
        if (tid == 320) prefetch_l2(g_tab + (chb & 63) * 32);
        if (lane == 0) mbar_wait(bars + 8 * (BAR_FULLB + NS1B - 1), 0);
        __syncwarp();
        if (lane >= 24) cp_async16(kring + (((s0 - 1) & 3) << 10) + d1, s0 > 0 ? kg - 16 * DM : kg, s0 > 0 ? 16 : 0);
        issue(s0);
        asm volatile("cp.async.commit_group;\n" ::: "memory");
        issue(s0 + 1);
        asm volatile("cp.async.commit_group;\n" ::: "memory");
        const __nv_bfloat16* hg = p.ssm_k + (size_t)chb * 8 * SEQ + lane * 64;
        uint32_t tn = clock32();
#pragma unroll 1
        for (int st = s0; st < s1; st++) {
          tn += PSTEP;
          while ((int)(clock32() - tn) < 0) __nanosleep(100);
          if (st + 2 < s1) issue(st + 2);
          if (hw == 1 && st - s0 < 8) prefetch_l2(hg);
          hg += SEQ;
          asm volatile("" : "+l"(hg));
          asm volatile("cp.async.commit_group;\n" ::: "memory");
          asm volatile("cp.async.wait_group 2;\n" ::: "memory");
          __syncwarp();
#pragma unroll
          for (int h = 0; h < 2; h++) {
            uint32_t e[6], vv[4], e4[4];
            ldsm4t(e4, kring + ((st & 3) << 10) + (la ^ (h << 4)));
            ldsm2t(e[0], e[1], kring + (((st - backb) & 3) << 10) + (lb ^ (h << 4)));
            ldsm4t(vv, vring + ((st & 3) << 10) + (la ^ (h << 4)));
            e[2] = e4[0]; e[3] = e4[1]; e[4] = e4[2]; e[5] = e4[3];
            uint32_t o[5];
#pragma unroll
            for (int i = 0; i < 5; i++) o[i] = __byte_perm(e[i], e[i + 1], 0x5432);
#pragma unroll
            for (int i = 0; i < 4; i++) {
              uint32_t a = bmul2(o[i], w[h][3]);
              a = bfma2(e[i + 1], w[h][2], a);
              a = bfma2(o[i + 1], w[h][1], a);
              a = bfma2(e[i + 2], w[h][0], a);
              vv[i] = bmul2(a, vv[i]);
            }
            st_async128(ud[h] + (st ^ (g & 1)) * 64, ub[h], vv[0], vv[1], vv[2], vv[3]);
          }
          __syncwarp();
        }
        fence_async_smem();
        PROF(16);
      }
      nb_sync(NB_HELP3, 96);
      if (hw == 1 && elect_one()) {
        mbar_expect_tx(bars + 8 * BAR_H, 8 * 4096 + 6144);
#pragma unroll 1
        for (int c = 0; c < 8; c++)
          bulk_load(sb + OFF_X + c * XT + 4096, p.ssm_k + (size_t)(chb * 8 + c) * SEQ, 4096, bars + 8 * BAR_H);
        bulk_load(sb + OFF_T16, g_tab, 2048, bars + 8 * BAR_H);
        bulk_load(sb + OFF_T32, g_tab + 512, 4096, bars + 8 * BAR_H);
      }
      __syncwarp();
      {
        if (hw == 3) {
          const char* wo = (const char*)p.wo + chb * 16384 + lane * 128;
#pragma unroll
          for (int i = 0; i < 4; i++) prefetch_l2(wo + i * 4096);
        }
        const int ck = 16 * (lane >> 4) + 2 * lr + (((lane >> 3) ^ (lane >> 2)) & 1);
        const uint32_t xo = (ck >> 1) * 64, xs = ((ck & 1) ^ (lr >> 1)) << 4;
#pragma unroll 1
        for (int job = hw - 1; job < 16; job += 3) {
          const int c = job & 7;
          uint4 a[8];
          float dv = __shfl_sync(0xffffffffu, dall, c);
          if (job < 8 || lane) dv = 0.f;
          const uint32_t xt = sb + OFF_X + c * XT + (job >> 3) * 4096;
          mbar_wait(bars + 8 * (job < 8 ? BAR_U : BAR_H), 0);
#pragma unroll
          for (int i = 0; i < 8; i++) a[i] = lds128(xt + i * 512 + ((ck ^ (job < 8 ? (c & 1) << 2 : 0)) << 4));
          dv += bf_lo(a[0].x);
          uint32_t m[2] = {bmaxabs2(pack_bf16(dv, 0.f), bmaxabs2(a[0].x, a[0].y)), bmaxabs2(a[0].z, a[0].w)};
#pragma unroll
          for (int i = 1; i < 8; i++) {
            m[0] = bmaxabs2(bmaxabs2(m[0], a[i].x), a[i].y);
            m[1] = bmaxabs2(bmaxabs2(m[1], a[i].z), a[i].w);
          }
          m[0] = bmaxabs2(m[0], m[1]);
          const int f = max(252 - (int)(__reduce_max_sync(0xffffffffu, max(m[0] & 0x7fffu, (m[0] >> 16) & 0x7fffu)) >> 7), 1);
          if (lane == 0) asm volatile("st.shared.u32 [%0], %1;\n" ::"r"(sb + OFF_EX + job * 4), "r"(f) : "memory");
          if (f < 113) {
#pragma unroll
            for (int i = 0; i < 8; i++)
              a[i] = make_uint4(bmul2(a[i].x, f * 0x00800080u), bmul2(a[i].y, f * 0x00800080u), bmul2(a[i].z, f * 0x00800080u),
                                bmul2(a[i].w, f * 0x00800080u));
          }
          const uint32_t mul = (f < 113 ? 15 : f - 112) * 0x00800080u;
          auto cv = [&](uint32_t x) {
            x = bmul2(x, mul);
            return (x & 0x0fff0fffu) * 7 + x;
          };
          const uint32_t dst = xt + xo;
#pragma unroll
          for (int i = 0; i < 8; i++)
            sts128(dst + (i >> 2) * 2048 + (i & 1) * 1024 + (xs ^ ((i & 2) << 4)),
                   i ? cv(a[i].x) : __byte_perm(pack_f16(dv * __uint_as_float(f << 23), 0.f), cv(a[i].x), 0x7610), cv(a[i].y),
                   cv(a[i].z), cv(a[i].w));
        }
        fence_async_smem();
        __syncwarp();
        if (lane == 0) mbar_arrive(bars + 8 * BAR_X);
        PROF(19);
      }
      if (hw < 3) {
        int lane, lr, lm;
        asm volatile("mov.u32 %0, %%laneid;\n" : "=r"(lane));
        lr = lane & 7;
        lm = lane >> 3;
#pragma unroll 1
        for (int n = 0; n < SPIN_LIMIT && !mbar_try(bars + 8 * (BAR_Y + hw - 1), 0); n++) __nanosleep(100);
        send_y((hw - 1) * 4 * XT, 2 * XT, 0);
        __syncwarp();
        if (lane == 0) mbar_arrive(bars + 8 * (BAR_Y + 2));
        PROF(32);
        const int c8 = 2 * lm + (lr & 1), src = (lr >> 1) & 1;
        uint32_t fa = sb + OFF_X + c8 * XT + rank * 4096 + (src == rank ? 0 : 1024) + (hw - 1) * 512;
        const uint32_t fx = ((lr >> 2) ^ ((lr & 3) << 1)) << 4;
        uint32_t qa = sb + OFF_Q0 + (hw - 1) * 8192 + (lane >> 3) * 128 + (lane & 2) * 32 + (lane & 4) * 8 + (lane & 1) * 16;
        uint4* og = reinterpret_cast<uint4*>(p.out + (size_t)(rank * 512 + (hw - 1) * 256 + (lane & 2) * 4 + (lane >> 2)) * (2 * DM) +
                                             (chb & ~1) * 8 + (lane & 1) * 8);
        mbar_wait(bars + 8 * BAR_Q, 0);
        uint32_t tn = 0;
        const uint32_t pace = hw == 2 ? FPACE2 : FPACE;
#pragma unroll 1
        for (int j = 0; j < 4; j++) {
          if (!(j & 1)) {
            mbar_wait(bars + 8 * (BAR_LAND + (j >> 1)), 0);
            tn = clock32() + (j ? 0 : (hw - 1) * (FPACE / 2));
            PROF2(33 + j * 2);
          }
#pragma unroll
          for (int i = 0; i < 8; i++) {
            if (i == 2 && j == 0 && hw == 2) {
              mbar_wait(bars + 8 * (BAR_Y + 3), 0);
              send_y(2 * XT, 4 * XT, 1);
              fence_async_smem();
              __syncwarp();
              if (lane == 0) mbar_arrive(bars + 8 * BAR_XFREE);
              tn = clock32();
            }
            uint32_t y[4];
            const uint4 q = lds128(qa + i * 512);
            ldsm4t(y, fa + (i >> 2) * 128 + (fx ^ ((i & 3) << 5) ^ ((i >> 2) << 4)));
            while ((int)(clock32() - tn) < 0) __nanosleep(50);
            tn += j == 3 ? FPACE3 : pace;
            og[i * 16 * (2 * DM / 8)] = make_uint4(bmul2(q.x, y[0]), bmul2(q.y, y[1]), bmul2(q.z, y[2]), bmul2(q.w, y[3]));
          }
          qa += j & 1 ? OFF_Q1 - OFF_Q0 - 4096 : 4096;
          fa += j & 1 ? 2048 - 256 : 256;
          og += (j & 1 ? 1024 - 128 : 128) * (2 * DM / 8);
        }
        PROF(22);
      }
      }
      if (MODE != 1 && hw == 3) {
        if (MODE == 0) nb_sync(NB_G1END, 288);
        if (elect_one()) g2_issue_b(bars + 8 * BAR_FULL2, MODE ? STG2 : STG2 / 2, sb + g2_b(0, 0), hp * 64, true);
        __syncwarp();
        const __nv_bfloat16* osrc = g_o + (size_t)(rb2 >> 1) * 16 * 16384 + hsel * 8192;
        if (MODE == 0) __nanosleep(1500);
        mbar_wait(bars + 8 * (BAR_EMPTY2 + 2), 0);
        const uint32_t epoch = lds32(sb + OFF_EX - 4);
        const uint32_t* flag = g_flag_o + FS * ((rb2 >> 1) * 16 + g2_k(lane & 15));
        uint32_t ready = MODE == 0 ? 0u : ~0u;
        int s = 1, ph = 0;
#pragma unroll 1
        for (int kb = 2; kb < 16; kb++) {
          if (++s == NS2) { s = 0; ph ^= 1; }
          uint32_t fb = bars + 8 * (BAR_FULL2 + s), dst = sb + g2_a(s, hsel) + rank * 8192;
          const __nv_bfloat16* src = osrc + rank * 4096 + (uint32_t)g2_k(kb) * 16384;
          asm volatile("" : "+r"(fb), "+r"(dst), "+l"(src));
          if (!(ready >> kb & 1)) {
#pragma unroll 1
            for (int n = 0; n < SPIN_LIMIT && !(ready >> kb & 1); n++)
              ready = __ballot_sync(0xffffffffu, ld_acquire(flag) == epoch);
            fence_async_all();
          }
          if (kb == 2) PROF(21);
          if (MODE == 0 && kb == 4 && rank == 1) mbar_wait(bars + 8 * BAR_TAB, 0);
          mbar_wait(fb + 8 * (BAR_EMPTY2 - BAR_FULL2), ph);
          if (elect_one()) {
            asm volatile(
                "cp.async.bulk.shared::cluster.global.mbarrier::complete_tx::bytes.multicast::cluster [%0], [%1], %2, [%3], %4;\n"
                ::"r"(dst), "l"(src), "r"(8192), "r"(fb), "h"((uint16_t)3) : "memory");
          }
          __syncwarp();
        }
      }
    }
    cluster_sync_all();
    PROF_DUMP();
  } else {
    asm volatile("barrier.cluster.arrive.relaxed.aligned;\n" ::: "memory");
    asm volatile("setmaxnreg.inc.sync.aligned.u32 %0;\n" :: "n"(REG_MATH));
    if (halo_cta || MODE == 2) asm volatile("barrier.cluster.wait.aligned;\n" ::: "memory");
    if (warp == 0) PROF2(26);
    const int wg = warp >> 2;
    const int wtid = tid & 127;
    const bool signaller = (wtid == 0) || (wtid == 32);
    const uint32_t rbars = mapa(bars, wtid >> 5 & 1);

    if (halo_cta) {
      const uint32_t epoch = ld_relaxed(g_flag_o + FS * (16 + blockIdx.x * 4)) + 1;
      float acc0[64], acc1[64];
      int s = wg, ph = 0;
#pragma unroll 1
      for (int kb = 0; kb < 16; kb++) {
        mbar_wait(bars + 8 * ((wg ? BAR_FULL2 : BAR_FULLB) + s), ph);
        const uint32_t st = sb + s * STGH;
        const uint64_t da = mkdesc(st, 16, 1024, 1);
        const uint64_t db = mkdesc(st + 8192, 8192, 1024, 1);
        wg_fence();
#pragma unroll
        for (int kk = 0; kk < 4; kk++) {
          wgmma_n128(acc0, da + 2 * kk, db + 128 * kk, kb + kk);
          wgmma_n128(acc1, da + 2 * kk, db + 1024 + 128 * kk, kb + kk);
        }
        wg_commit();
        wg_wait<0>();
        if (kb == 15) PROF(37);
        if (wtid < 2) mbar_arrive(bars + 8 * (BAR_EMPTYB + s));
        if ((s += 2) >= NS1B) s -= NS1B;
        if (s == wg) ph ^= 1;
      }
      fence_regs(acc0);
      fence_regs(acc1);
      if ((warp & 3) != 3) {
        auto put = [&](const float (&acc)[64], int hp0) {
#pragma unroll
          for (int n = 0; n < 4; n++) {
            uint32_t x[8];
#pragma unroll
            for (int c = 0; c < 8; c++) {
              x[c] = pack_bf16(acc[32 * (n >> 1) + 4 * c + 2 * (n & 1)], acc[32 * (n >> 1) + 4 * c + 2 * (n & 1) + 1]);
              if (wg) x[c] = movm(x[c]);
            }
            uint4* dst = g_halo + (((n & 1) * 4 + (warp & 3) + 1) * 16 + blockIdx.x * 4 + hp0 + (n >> 1)) * 192 + wg * 96 + lane;
            st_b128(dst, x[0], x[1], x[2], epoch);
            st_b128(dst + 32, x[3], x[4], x[5], epoch);
            st_b128(dst + 64, x[6], x[7], 0, epoch);
          }
        };
        put(acc0, 0);
        put(acc1, 2);
      }
      PROF(36);
      cluster_sync_all();
      return;
    }

    float acc[64];
    const uint32_t g2rel = wtid ? mapa(bars, rank) + 8 * BAR_EMPTY2B : mapa(bars, wg) + 8 * BAR_EMPTY2;
    uint32_t g2a = (uint32_t)mkdesc(sb + wg * 8192, 16, 0, 0), g2b = (uint32_t)mkdesc(sb, 8192, 0, 0);
    auto g2_block = [&](bool first, int s, int ph) {
      mbar_wait(bars + 8 * (BAR_FULL2 + s), ph);
      const uint32_t da = g2a + (g2_a(s, hsel) >> 4), db = g2b + (g2_b(s, rank) >> 4), dc = db + (g2_bk(s) >> 4);
      wg_fence();
      if (first) wgmma_n128z(acc, da, db);
      else wgmma_n128a(acc, da, db);
      wgmma_n128a(acc, da + 2, db + 128);
      wgmma_n128a(acc, da + 4, dc);
      wgmma_n128a(acc, da + 6, dc + 128);
      wg_commit();
    };
    if (MODE != 2) {
    uint32_t a1[2][4], sc[2];
    C2 t[2];
    {
      float acc0[96], acc1[96];
      int sa = 0, pha = 0;
      uint64_t db0 = mkdesc(sb + OFF_1B, 4096, 1024, 1);
      const uint64_t da0 = mkdesc(sb + wg * 16384, 16, 2048, 1);
      const bool sigb = wtid == 64;
      uint32_t rela = 0;
#pragma unroll 1
      for (int r = 0; r < 3; r++) {
#pragma unroll
        for (int i = 0; i < 2 * NS1B; i++) {
          if (i == 2 * NS1B - 1 && r == 2) break;
          const uint64_t da = da0 + sa * (STG1A >> 4) + (i & 1) * 4, db = db0 + (i % NS1B) * (STG1B >> 4);
          if (i || r) {
            if (!(i & 1)) mbar_wait(bars + 8 * (BAR_FULLA + sa), pha);
            mbar_wait(bars + 8 * (BAR_FULLB + i % NS1B), i / NS1B);
          } else {
            asm volatile("cp.async.wait_group 0;\n" ::: "memory");
            fence_async_smem();
            nb_sync(NB_FIRST, 256);
            PROF(0 + wg);
          }
          wg_fence();
          wgmma_n192(acc0, da + 64, db, i ? 1 : r);
          wgmma_n192(acc1, da, db, i ? 1 : r);
          wgmma_n192(acc0, da + 66, db + 128, 1);
          wgmma_n192(acc1, da + 2, db + 128, 1);
          wg_commit();
          wg_wait<1>();
          if (i || r) {
            if (sigb) mbar_arrive(bars + 8 * (BAR_EMPTYB + (i + NS1B - 1) % NS1B));
            if (!(i & 1) && signaller) mbar_arrive_cluster(rela);
          } else {
            asm volatile("barrier.cluster.wait.aligned;\n" ::: "memory");
          }
          if (i & 1) {
            rela = rbars + 8 * (BAR_EMPTYA + sa);
            if (++sa == NS1A) { sa = 0; pha ^= 1; }
          }
        }
        db0 += p.zero;
      }
      const int lr = lane & 7, lm = lane >> 3;
      const bool le0 = 2 * (lane & 3) <= (lane >> 2), le1 = 2 * (lane & 3) + 1 <= (lane >> 2);
      const uint32_t maskLE = (le0 ? 0x0000FFFFu : 0u) | (le1 ? 0xFFFF0000u : 0u);
      uint32_t q[4][8], k[5][8], vt[5][8];
      {
        static_assert(15 % NS1A == 0 && 30 % NS1B == 0, "slots of the last k blocks");
        const uint64_t da = mkdesc(sb + wg * 16384, 16, 2048, 1);
        const uint64_t db = mkdesc(sb + OFF_1B, 4096, 1024, 1);
        auto last = [&](float (&acc)[96], int ro, int i0, int i1) {
#pragma unroll
          for (int i = i0; i < i1; i++)
            wgmma_n192(acc, da + ro + (i < 2 ? 2 * (STG1A >> 4) + 4 + 2 * i : 2 * i - 4),
                       db + (i < 2 ? 4 : (i >> 1) - 1) * (STG1B >> 4) + (i & 1) * 128, 1);
          wg_commit();
        };
        mbar_wait(bars + 8 * (BAR_FULLB + 4), 1);
        wg_fence();
        last(acc0, 64, 0, 2);
        asm volatile("ld.volatile.global.v4.u32 {%0,%1,%2,%3}, [%4];\n"
                     : "=r"(t[0].r), "=r"(t[1].r), "=r"(t[0].i), "=r"(t[1].i) : "l"(g_tab + 1536 + wtid * 4) : "memory");
        mbar_wait(bars + 8 * BAR_FULLA, 1);
        mbar_wait(bars + 8 * BAR_FULLB, 0);
        mbar_wait(bars + 8 * (BAR_FULLB + 1), 0);
        wg_fence();
        last(acc0, 64, 2, 6);
        wg_wait<2>();
        if (sigb) mbar_arrive(bars + 8 * (BAR_EMPTYB + 3));
        mbar_wait(bars + 8 * (BAR_EMPTYA + 1), 0);
        mbar_wait(bars + 8 * BAR_H, 0);
        wg_fence();
        last(acc1, 0, 0, LN);
        wg_wait<1>();
        fence_regs(acc0);
        PROFA(45, 0);
        attn_pack<8, 1, false>(acc0, k[4]);
        attn_pack<16, 1, true>(acc0, vt[4]);
        const uint32_t kh = sb + (warp == 7 ? OFF_1B + 2 * STG1B : OFF_KH + (warp + 1) * 2048) + lane * 16;
        sts128(kh, k[4][0], k[4][1], k[4][2], k[4][3]);
        sts128(kh + 512, k[4][4], k[4][5], k[4][6], k[4][7]);
#pragma unroll
        for (int i = 0; i < 4; i++) sts64(kh - lane * 8 + 1024 + 256 * i, vt[4][2 * i], vt[4][2 * i + 1]);
        __syncwarp();
        if (lane == 0) mbar_arrive(bars + 8 * (BAR_KH + 1 + warp));
        if (LN < 6) last(acc1, 0, LN, 6);
        attn_pack<0, 0, false>(acc0, q[1]);
        attn_pack<0, 1, false>(acc0, q[3]);
        attn_pack<8, 0, false>(acc0, k[2]);
        attn_pack<16, 0, true>(acc0, vt[2]);
        uint32_t z = p.zero;
#pragma unroll
        for (int i = 0; i < 8; i++) z &= q[1][i] & q[3][i];
#pragma unroll
        for (int i = 0; i < 8; i += 2) z &= k[2][i] & k[2][i + 1];
        mbar_wait(bars + 8 * (BAR_KH + warp) + z, 0);
        {
          const uint32_t kh = sb + OFF_KH + warp * 2048 + lane * 16;
#pragma unroll
          for (int i = 0; i < 2; i++) {
            const uint4 t = lds128(kh + 512 * i);
            k[0][4 * i] = t.x; k[0][4 * i + 1] = t.y; k[0][4 * i + 2] = t.z; k[0][4 * i + 3] = t.w;
          }
#pragma unroll
          for (int i = 0; i < 4; i++) {
            const uint2 t = lds64(kh - lane * 8 + 1024 + 256 * i);
            vt[0][2 * i] = t.x; vt[0][2 * i + 1] = t.y;
          }
        }
        wg_wait<0>();
        fence_regs(acc1);
        if (MODE == 0) nb_arrive(NB_G1END, 288);
      }
      PROF(2 + wg);
      attn_pack<0, 0, false>(acc1, q[0]);
      attn_pack<0, 1, false>(acc1, q[2]);
      attn_pack<8, 0, false>(acc1, k[1]);
      attn_pack<8, 1, false>(acc1, k[3]);
      {
        float x[8][2];
        uint32_t pp[8];
        const bool first = warp == 0 && gidx == 0;
#pragma unroll
        for (int hd = 0; hd < 2; hd++) {
#pragma unroll
          for (int j = 0; j < 4; j += 2) {
            float s0[4], s1[4], s2[4];
            attn_qk(s2, q[j], q[j + 1], k[j + 2], 4 * hd);
            attn_qk(s1, q[j], q[j + 1], k[j + 1], 4 * hd);
            attn_qk(s0, q[j], q[j + 1], k[j], 4 * hd);
            if (j == 0 && first) s0[0] = s0[1] = -1e9f / 0.17677669529663687f;
            x[2 * j + hd][0] = le0 ? s1[0] : s0[0];
            x[2 * j + hd][1] = le1 ? s1[1] : s0[1];
            x[2 * j + 2 + hd][0] = le0 ? s2[2] : s1[2];
            x[2 * j + 2 + hd][1] = le1 ? s2[3] : s1[3];
          }
        }
        PROFA(40, __float_as_uint(x[1][0] + x[7][1]));
        attn_pack<16, 0, true>(acc1, vt[1]);
        attn_pack<16, 1, true>(acc1, vt[3]);
        quad_softmax<8>(x, pp);
        PROFA(41, pp[1] + pp[7]);
        ldsm4(a1[0], sb + OFF_T32 + (warp & 3) * 1024 + lane * 16);
        ldsm4(a1[1], sb + OFF_T32 + 512 + (warp & 3) * 1024 + lane * 16);
        const uint32_t obase = sb + OFF_OP + (warp * 32 + lr) * 128;
#pragma unroll
        for (int n = 0; n < 8; n++) {
          const uint32_t dst = obase + (n >> 1) * 1024 + (((4 * (n & 1) + lm) ^ lr) << 4);
          if (n & 2) attn_pv<true>(dst, vt[n >> 1], vt[(n >> 1) + 1], 4 * (n & 1), pp[n], maskLE);
          else attn_pv<false>(dst, vt[n >> 1], vt[(n >> 1) + 1], 4 * (n & 1), pp[n], maskLE);
        }
      }
      PROFA(42, 0);
    }

    {
      const int w = warp & 3;
      const int lr = lane & 7, lm = lane >> 3;
      const uint32_t xb = sb + OFF_X + wg * 4 * XT;
      auto uo = [](int c) { return (c & 1) * 2 * XT + (c >> 1) * 2048; };
      const uint64_t dc2 = mkdesc(sb + OFF_T16, 512, 128, 0), dc3 = mkdesc(sb + OFF_T16, 128, 512, 0);
      const uint64_t dc4 = mkdesc(sb + OFF_T32, 128, 256, 0);
      const uint64_t dx = mkdesc(xb, 4096, 512, 2), dz = mkdesc(xb, 4096, 256, 3);
      const uint32_t zs = xb + (w * 16 + (lm & 1) * 8 + lr) * 32 + (((lm >> 1) ^ (lr >> 2)) << 4);
      const uint32_t ys = xb + w * 4096 + (lm >> 1) * 256 + ((lr * 32 + (((lm & 1) ^ (lr >> 2)) << 4)) ^ (rank << 6) ^ ((w & 2) << 4));
      const bool own = (w & 1) == rank;
      const uint32_t ybar = mapa(bars, own ? rank ^ 1 : rank) + 8 * BAR_Y;
      uint32_t d[2][32], pa[2][4][2][4], e[4][4][8], ya[2][2][2][4], v[2][2][8];
      C2 s1[2][2][2];
      float o[2][16];
      auto rows = [&](int c) {
        fft_rows(d[c & 1], a1, dx + (uo(c) >> 4));
        wg_commit();
      };
      auto cols = [&](int c) {
        const int s = c & 1;
        fence_regs(d[s]);
#pragma unroll
        for (int i = 0; i < 16; i++) {
          const C2 z = crot(C2{d[s][2 * i], d[s][2 * i + 1]}, t[i & 1]);
          pa[s][i >> 2][i & 1][(i >> 1) & 1] = z.r;
          pa[s][i >> 2][i & 1][2 + ((i >> 1) & 1)] = z.i;
        }
        wg_fence();
#pragma unroll
        for (int i = 0; i < 4; i++) fft_cols<0>(e[c][i], pa[s][i], dc2);
        wg_commit();
      };
      auto prod = [&](int c, int n) {
        const int s = c & 1;
        fence_regs(e[c][2 * n]);
        fence_regs(e[c][2 * n + 1]);
#pragma unroll
        for (int j = 0; j < 2; j++) {
          const C2 u0 = cget(e[s][2 * n], j, 0), u1 = cget(e[s][2 * n], j, 1);
          const C2 h0 = cget(e[s][2 * n + 1], j, 0), h1 = cget(e[s][2 * n + 1], j, 1);
          C2 y0, y1;
          if (c < 2) {
            y0 = cmul(h0, u0);
            s1[s][n][j] = cfma(h0, u1, cmul(h1, u0));
            y1 = C2{hadd2(s1[s][n][j].r, y0.i), hadd2(s1[s][n][j].i, hneg2(y0.r))};
          } else {
            const C2 u2 = cget(e[c][2 * n], j, 0), u3 = cget(e[c][2 * n], j, 1);
            const C2 h2 = cget(e[c][2 * n + 1], j, 0), h3 = cget(e[c][2 * n + 1], j, 1);
            const C2 s2 = cfma(h0, u2, cfma(h2, u0, cmul(h1, u1)));
            y0 = C2{hadd2(s2.r, s1[s][n][j].i), hadd2(s2.i, hneg2(s1[s][n][j].r))};
            y1 = cfma(h0, u3, cfma(h1, u2, cfma(h2, u1, cfma(h3, u0, C2{s2.i, hneg2(s2.r)}))));
          }
          ya[s][n][j][0] = y0.r;
          ya[s][n][j][1] = y1.r;
          ya[s][n][j][2] = y0.i;
          ya[s][n][j][3] = y1.i;
        }
      };
      auto icols = [&](int c) {
        wg_fence();
        fft_cols<1>(v[c & 1][0], ya[c & 1][0], dc3);
        fft_cols<1>(v[c & 1][1], ya[c & 1][1], dc3);
        wg_commit();
      };
      auto stage = [&](int c) {
        const int s = c & 1;
        fence_regs(v[s][0]);
        fence_regs(v[s][1]);
#pragma unroll
        for (int b = 0; b < 4; b++) {
          const C2 x0 = cget(v[s][b >> 1], 0, b & 1), x1 = cget(v[s][b >> 1], 1, b & 1);
          const C2 z0 = crot(C2{x0.i, x0.r}, t[0]), z1 = crot(C2{x1.i, x1.r}, t[1]);
          stsm4(zs + uo(c) + b * 4096, z0.i, z0.r, z1.i, z1.r);
        }
      };
      auto back = [&](int c) {
        fft_back(o[c & 1], dz + (uo(c) >> 4), dc4);
        wg_commit();
      };
      auto out = [&](int c) {
        float (&r)[16] = o[c & 1];
        fence_regs(r);
#pragma unroll
        for (int i = 0; i < 16; i += 8)
          stsm4t(ys + uo(c) + 64 * i, bmul2(pack_bf16(r[i], r[i + 1]), sc[c & 1]), bmul2(pack_bf16(r[i + 2], r[i + 3]), sc[c & 1]),
                 bmul2(pack_bf16(r[i + 4], r[i + 5]), sc[c & 1]), bmul2(pack_bf16(r[i + 6], r[i + 7]), sc[c & 1]));
      };
      auto signal = [&](int yb, int land) {
        __syncwarp();
        if (lane == 0) {
          mbar_arrive_cluster(ybar + 8 * yb);
          if (own && land >= 0) mbar_arrive(bars + 8 * (BAR_LAND + land));
        }
      };
      mbar_wait(bars + 8 * BAR_X, 0);
      wg_fence();
      rows(0);
      rows(1);
      fence_async_smem();
      nb_arrive(NB_OREADY, 288);
#pragma unroll
      for (int i = 0; i < 2; i++) {
        const uint32_t ex = sb + OFF_EX + wg * 16 + (w & 2) * 2 + 8 * i;
        sc[i] = min(max(381 - (int)lds32(ex) - (int)lds32(ex + 32), 1), 254) * 0x00800080u;
      }
      PROF(34 + wg);
      wg_wait<1>();
      cols(0);
      wg_wait<1>();
      cols(1);
      rows(2);
      nb_sync(NB_CONV + wg, 128);
      wg_wait<2>();
      prod(0, 0);
      prod(0, 1);
      icols(0);
      wg_wait<2>();
      prod(1, 0);
      prod(1, 1);
      icols(1);
      PROF3(40 + 10 * wg);
      wg_wait<1>();
      stage(0);
      wg_wait<0>();
      stage(1);
      fence_async_smem();
      cols(2);
      PROF3(41 + 10 * wg);
      nb_sync(NB_CONV + wg, 128);
      back(0);
      back(1);
      wg_wait<2>();
      prod(2, 0);
      wg_fence();
      rows(3);
      wg_wait<1>();
      out(0);
      out(1);
      signal(wg, 0);
      PROF3(42 + 10 * wg);
      prod(2, 1);
      icols(2);
      wg_wait<1>();
      cols(3);
      PROF3(43 + 10 * wg);
      wg_wait<1>();
      stage(2);
      fence_async_smem();
      wg_wait<0>();
      prod(3, 0);
      nb_sync(NB_CONV + wg, 128);
      wg_fence();
      back(2);
      prod(3, 1);
      icols(3);
      PROF3(44 + 10 * wg);
      wg_wait<1>();
      out(2);
      signal(2, -1);
      wg_wait<0>();
      stage(3);
      PROF3(45 + 10 * wg);
      fence_async_smem();
      nb_sync(NB_FIRST, 256);
      wg_fence();
      back(3);
      constexpr int G = MODE == 0;
      if (G) {
        mbar_wait(bars + 8 * (BAR_EMPTY2 + 4), 0);
        g2_block(true, 0, 0);
      }
      wg_wait<G>();
      if (lane == 0) mbar_arrive_cluster(mapa(bars, 1) + 8 * BAR_TAB);
      out(3);
      signal(3, 1);
      PROF(6 + wg);
    }
    }

    if (MODE != 1) {
      if (MODE == 2) g2_block(true, 0, 0);
      const int lr = lane & 7, lm = lane >> 3;
      const uint32_t wb = sb + g2_a(1, 0) + warp * 2048;
      const int orow = (rb2 & 7) * 128 + warp * 16;
      uint4* og = reinterpret_cast<uint4*>(p.out + (size_t)(2 * (orow + lm) + (rb2 >> 3)) * (2 * DM) + DM + cb2 * 128 + lr * 8);
      uint32_t wst = wb + (lr + 8 * (lm & 1)) * 128, wsx = ((lm >> 1) ^ lr) << 4, wld = wb + lm * 128, wlx = (lr ^ lm) << 4;
      asm volatile("" : "+l"(og), "+r"(wst), "+r"(wsx), "+r"(wld), "+r"(wlx));
#pragma unroll 1
      for (int r = 0; r < 3; r++) {
        const bool hold = r == 2 && wg != LEADWG;
        if (hold) {
          wg_wait<0>();
          if (signaller) mbar_arrive_cluster(g2rel);
          nb_sync(NB_LEAD, 256);
        }
#pragma unroll
        for (int i = 1; i <= NS2; i++) {
          g2_block(false, i % NS2, (r & 1) ^ (i == NS2));
          if (warp == LEADWG * 4) PROF2(40 + 5 * r + i);
          if (i == 1 ? !hold : r < 2) {
            wg_wait<1>();
            if (signaller) mbar_arrive_cluster(g2rel + 8 * (i - 1));
          }
        }
        if (r == 0) PROF(8 + wg);
        g2a += p.zero;
        g2b += p.zero;
      }
      if (wg == LEADWG) nb_arrive(NB_LEAD, 256);
      asm volatile("barrier.cluster.arrive.relaxed.aligned;\n" ::: "memory");
      wg_wait<0>();
      fence_regs(acc);
      PROF(10 + wg);
#pragma unroll
      for (int h = 0; h < 2; h++) {
        const uint32_t b = h * (g2_a(3, 0) - g2_a(1, 0));
#pragma unroll
        for (int j = 8 * h; j < 8 * h + 8; j += 2)
          stsm4(wst + b + (wsx ^ ((j & 7) << 4)), pack_bf16(acc[4 * j], acc[4 * j + 1]),
                pack_bf16(acc[4 * j + 2], acc[4 * j + 3]), pack_bf16(acc[4 * j + 4], acc[4 * j + 5]),
                pack_bf16(acc[4 * j + 6], acc[4 * j + 7]));
        if (wg == LEADWG) {
          fence_async_smem();
          __syncwarp();
          if (elect_one()) {
            tma_store_3d(&tmOb, wb + b, DM + cb2 * 128 + h * 64, rb2 >> 3, orow);
            bulk_commit();
          }
        } else {
          __syncwarp();
          uint4 v[4];
#pragma unroll
          for (int i = 0; i < 4; i++) v[i] = lds128(wld + b + i * 512 + (wlx ^ ((i & 1) << 6)));
#pragma unroll
          for (int i = 0; i < 4; i++)
            asm volatile("st.global.v4.u32 [%0], {%1,%2,%3,%4};\n" ::"l"(og + i * 8 * (2 * DM / 8) + h * 8), "r"(v[i].x),
                         "r"(v[i].y), "r"(v[i].z), "r"(v[i].w) : "memory");
        }
      }
      PROF(12 + wg);
      bulk_wait0();
    } else {
      asm volatile("barrier.cluster.arrive.relaxed.aligned;\n" ::: "memory");
    }
    asm volatile("barrier.cluster.wait.aligned;\n" ::: "memory");
  }
}

typedef CUresult (*EncodeFn)(CUtensorMap*, CUtensorMapDataType, cuuint32_t, void*, const cuuint64_t*, const cuuint64_t*,
                             const cuuint32_t*, const cuuint32_t*, CUtensorMapInterleave, CUtensorMapSwizzle,
                             CUtensorMapL2promotion, CUtensorMapFloatOOBfill);

void make_map(EncodeFn enc, CUtensorMap* tm, const void* base, int rank, const cuuint64_t* dims, const cuuint64_t* strides,
              const cuuint32_t* box, CUtensorMapSwizzle swz) {
  cuuint32_t es[5] = {1, 1, 1, 1, 1};
  enc(tm, CU_TENSOR_MAP_DATA_TYPE_BFLOAT16, rank, const_cast<void*>(base), dims, strides, box, es,
      CU_TENSOR_MAP_INTERLEAVE_NONE, swz, CU_TENSOR_MAP_L2_PROMOTION_L2_256B, CU_TENSOR_MAP_FLOAT_OOB_FILL_NONE);
}

}

extern "C" void kernel_launch(void* const* d_in, const int* in_sizes, int n_in, void* d_out, int out_size) {
  static EncodeFn enc = nullptr;
  static bool coresident = true;
  if (!enc) {
    void* fn = nullptr;
    cudaDriverEntryPointQueryResult qr;
    cudaGetDriverEntryPoint("cuTensorMapEncodeTiled", &fn, cudaEnableDefault, &qr);
    enc = (EncodeFn)fn;
    cudaFuncSetAttribute(fused_kernel<0>, cudaFuncAttributeMaxDynamicSharedMemorySize, SMEM_BYTES);
    cudaFuncSetAttribute(fused_kernel<1>, cudaFuncAttributeMaxDynamicSharedMemorySize, SMEM_BYTES);
    cudaFuncSetAttribute(fused_kernel<2>, cudaFuncAttributeMaxDynamicSharedMemorySize, SMEM_BYTES);
    cudaLaunchConfig_t cfg = {};
    cfg.gridDim = dim3(NCTA);
    cfg.blockDim = dim3(NTHREADS);
    cfg.dynamicSmemBytes = SMEM_BYTES;
    cudaLaunchAttribute at;
    at.id = cudaLaunchAttributeClusterDimension;
    at.val.clusterDim.x = 2;
    at.val.clusterDim.y = 1;
    at.val.clusterDim.z = 1;
    cfg.attrs = &at;
    cfg.numAttrs = 1;
    int nclusters = 0;
    if (cudaOccupancyMaxActiveClusters(&nclusters, fused_kernel<0>, &cfg) == cudaSuccess) coresident = nclusters >= NCTA / 2;
    (void)cudaGetLastError();
  }
  CUtensorMap tmX, tmW, tmWo, tmWp, tmQ, tmOb, tmXh, tmWh;
  {
    cuuint64_t dims[3] = {1024, 2, 1024};
    cuuint64_t str[2] = {2048, 4096};
    cuuint32_t box[3] = {64, 1, 128};
    make_map(enc, &tmX, d_in[6], 3, dims, str, box, CU_TENSOR_MAP_SWIZZLE_128B);
  }
  {
    cuuint64_t dims[3] = {1024, 1024, 3};
    cuuint64_t str[2] = {6144, 2048};
    cuuint32_t box[3] = {64, 32, 3};
    make_map(enc, &tmW, d_in[7], 3, dims, str, box, CU_TENSOR_MAP_SWIZZLE_128B);
  }
  {
    cuuint64_t dims[3] = {64, 1024, 16};
    cuuint64_t str[2] = {2048, 128};
    cuuint32_t box[3] = {64, 64, 2};
    cuuint32_t piece[3] = {64, 32, 1};
    make_map(enc, &tmWo, d_in[8], 3, dims, str, box, CU_TENSOR_MAP_SWIZZLE_128B);
    make_map(enc, &tmWp, d_in[8], 3, dims, str, piece, CU_TENSOR_MAP_SWIZZLE_128B);
  }
  {
    cuuint64_t dims[5] = {1024, 2, 2, 4, 128};
    cuuint64_t str[4] = {2048, 8 * 2048, 2 * 2048, 16 * 2048};
    cuuint32_t box[5] = {16, 2, 2, 4, 32};
    make_map(enc, &tmQ, d_in[0], 5, dims, str, box, CU_TENSOR_MAP_SWIZZLE_NONE);
  }
  {
    cuuint64_t dims[3] = {2048, 2, 1024};
    cuuint64_t str[2] = {4096, 8192};
    cuuint32_t box[3] = {64, 1, 16};
    make_map(enc, &tmOb, d_out, 3, dims, str, box, CU_TENSOR_MAP_SWIZZLE_128B);
  }
  {
    cuuint64_t dims[4] = {1024, 256, 2, 4};
    cuuint64_t str[3] = {4096, 2048, 256 * 4096};
    cuuint32_t box[4] = {64, 8, 2, 3};
    make_map(enc, &tmXh, d_in[6], 4, dims, str, box, CU_TENSOR_MAP_SWIZZLE_128B);
  }
  {
    cuuint64_t dims[3] = {64, 1024, 48};
    cuuint64_t str[2] = {6144, 128};
    cuuint32_t box[3] = {64, 64, 4};
    make_map(enc, &tmWh, d_in[7], 3, dims, str, box, CU_TENSOR_MAP_SWIZZLE_128B);
  }
  Params p;
  p.q = (const __nv_bfloat16*)d_in[0];
  p.k = (const __nv_bfloat16*)d_in[1];
  p.v = (const __nv_bfloat16*)d_in[2];
  p.shift_k = (const __nv_bfloat16*)d_in[3];
  p.ssm_k = (const __nv_bfloat16*)d_in[4];
  p.ssm_D = (const __nv_bfloat16*)d_in[5];
  p.x = (const __nv_bfloat16*)d_in[6];
  p.w = (const __nv_bfloat16*)d_in[7];
  p.wo = (const __nv_bfloat16*)d_in[8];
  p.out = (__nv_bfloat16*)d_out;
  p.zero = 0;
  for (int cl = 0; cl < 72; cl++) {
    const int t = cl - 4, u = t - 32;
    const bool lo = t >= 0 && t < 32, mid = u >= 0 && u < 28;
    const int grp = lo ? t & 7 : mid ? 1 + u % 7 : 0, mem = lo ? t >> 3 : mid ? 4 + u / 7 : t < 0 ? t + 6 : t - 54;
    p.tile[cl] = (uint8_t)((((grp >> 2) * 4 + (mem >> 1)) * 8 + (grp & 3) * 2 + (mem & 1)) & 63);
  }
  if (coresident) {
    fused_kernel<0><<<NCTA, NTHREADS, SMEM_BYTES>>>(p, tmX, tmW, tmWo, tmWp, tmQ, tmOb, tmXh, tmWh);
  } else {
    fused_kernel<0><<<4, NTHREADS, SMEM_BYTES>>>(p, tmX, tmW, tmWo, tmWp, tmQ, tmOb, tmXh, tmWh);
    fused_kernel<1><<<NCTA, NTHREADS, SMEM_BYTES>>>(p, tmX, tmW, tmWo, tmWp, tmQ, tmOb, tmXh, tmWh);
    fused_kernel<2><<<NCTA, NTHREADS, SMEM_BYTES>>>(p, tmX, tmW, tmWo, tmWp, tmQ, tmOb, tmXh, tmWh);
  }
}
```

```cpp
#include <cuda_runtime.h>
#include <cuda.h>
#include <cuda_bf16.h>
#include <stdint.h>

namespace {

constexpr int SEQ = 2048;
constexpr int DM = 1024;
constexpr int NCTA = 132;
constexpr int NTHREADS = 384;

constexpr int STG1A = 32768;
constexpr int NS1A = 3;
constexpr int STG1B = 12288;
constexpr int NS1B = 5;
constexpr int OFF_1B = NS1A * STG1A;
constexpr int STG2 = 32768;
constexpr int NS2 = 5;
#define PSTEP 1250
#define FPACE 260
#define FPACE2 240
#define FPACE3 180
constexpr int LEADWG = 1;
__device__ __forceinline__ uint32_t g2_a(int s, int hsel) { return (((0x97524 >> (4 * s)) & 15) ^ (s & 5 ? 0 : hsel)) << 14; }
constexpr int OFF_Q0 = 3 << 14, OFF_Q1 = 8 << 14;
constexpr int STGH = 40960;
constexpr int OFF_KH = 1 * STG2;
constexpr int OFF_OP = 2 * STG2;
constexpr int OFF_T32 = 5 * STG2 - 4096;
constexpr int OFF_X = 5 * STG2;
constexpr int XT = 8192;
__device__ __forceinline__ uint32_t g2_b(int s, int rank) {
  return s < 3 ? (s == 2 ? 6 : s) << 14 : OFF_X + (s - 3) * 2 * XT + (rank ^ 1) * 4096;
}
__device__ __forceinline__ uint32_t g2_bk(int s) { return s < 3 ? 4096 : 4 * XT; }
constexpr int OFF_BAR = OFF_X + 8 * XT;
constexpr int OFF_EX = OFF_BAR + 960;
constexpr int OFF_T16 = 230400;
constexpr int SMEM_BYTES = OFF_T16 + 2048;
static_assert(OFF_1B + NS1B * STG1B <= OFF_T32 && OFF_X % 1024 == 0, "layout");
static_assert(NS1B == NS2 && NS1B * STGH <= OFF_BAR && OFF_EX + 64 <= OFF_T16 && SMEM_BYTES <= 232448, "smem");

constexpr int BAR_FULLA = 0;
constexpr int BAR_EMPTYA = 3;
constexpr int BAR_FULLB = 6;
constexpr int BAR_EMPTYB = 11;
constexpr int BAR_FULL2 = 16;
constexpr int BAR_EMPTY2 = 21;
constexpr int BAR_EMPTY2B = 44;
constexpr int BAR_X = 26;
constexpr int BAR_LAND = 42;
constexpr int BAR_TAB = 28;
constexpr int BAR_U = 29;
constexpr int BAR_H = 30;
constexpr int BAR_Y = 32;
constexpr int BAR_XFREE = 38;
constexpr int BAR_KH = 49;
constexpr int BAR_Q = 41;

constexpr int NB_LEAD = 2;
constexpr int NB_G1END = 3;
constexpr int NB_OREADY = 4;
constexpr int NB_CONV = 5;
constexpr int NB_HELP3 = 11;
constexpr int NB_FIRST = 13;

#define REG_MATH 224
#define REG_HELP 56
constexpr int SPIN_LIMIT = 1 << 20;

__device__ __align__(1024) __nv_bfloat16 g_o[SEQ * DM];
constexpr int FS = 2;
__device__ __align__(128) uint32_t g_flag_o[128 * FS];
__device__ uint4 g_halo[128 * 192];
__device__ __align__(128) const uint32_t g_tab[2048] = {
  0x2fd93000,0x2ea72f64,0x2c722da8,0x263e2a1f,0x2ea73000,0xa63e2a1f,0xafd9ada8,0xac72af64,0x2c723000,0xafd9aa1f,0x263eada8,0x2ea72f64,
  0x263e3000,0xac72af64,0x2ea72da8,0xafd9aa1f,0xa63e3000,0x2c72af64,0xaea72da8,0x2fd9aa1f,0xac723000,0x2fd9aa1f,0xa63eada8,0xaea72f64,
  0xaea73000,0x263e2a1f,0x2fd9ada8,0x2c72af64,0xafd93000,0xaea72f64,0xac722da8,0xa63e2a1f,0x263e0000,0x2c722a1f,0x2ea72da8,0x2fd92f64,
  0x2c720000,0x2fd92f64,0x263e2da8,0xaea7aa1f,0x2ea70000,0x263e2f64,0xafd9ada8,0x2c72aa1f,0x2fd90000,0xaea72a1f,0x2c72ada8,0xa63e2f64,
  0x2fd90000,0xaea7aa1f,0x2c722da8,0xa63eaf64,0x2ea70000,0x263eaf64,0xafd92da8,0x2c722a1f,0x2c720000,0x2fd9af64,0x263eada8,0xaea72a1f,
  0x263e0000,0x2c72aa1f,0x2ea7ada8,0x2fd9af64,0xafd93000,0xaea72f64,0xac722da8,0xa63e2a1f,0xaea73000,0x263e2a1f,0x2fd9ada8,0x2c72af64,
  0xac723000,0x2fd9aa1f,0xa63eada8,0xaea72f64,0xa63e3000,0x2c72af64,0xaea72da8,0x2fd9aa1f,0x263e3000,0xac72af64,0x2ea72da8,0xafd9aa1f,
  0x2c723000,0xafd9aa1f,0x263eada8,0x2ea72f64,0x2ea73000,0xa63e2a1f,0xafd9ada8,0xac72af64,0x2fd93000,0x2ea72f64,0x2c722da8,0x263e2a1f,
  0xa63e0000,0xac722a1f,0xaea72da8,0xafd92f64,0xac720000,0xafd92f64,0xa63e2da8,0x2ea7aa1f,0xaea70000,0xa63e2f64,0x2fd9ada8,0xac72aa1f,
  0xafd90000,0x2ea72a1f,0xac72ada8,0x263e2f64,0xafd90000,0x2ea7aa1f,0xac722da8,0x263eaf64,0xaea70000,0xa63eaf64,0x2fd92da8,0xac722a1f,
  0xac720000,0xafd9af64,0xa63eada8,0x2ea72a1f,0xa63e0000,0xac72aa1f,0xaea7ada8,0xafd9af64,0xa63e0000,0xac72aa1f,0xaea7ada8,0xafd9af64,
  0xac720000,0xafd9af64,0xa63eada8,0x2ea72a1f,0xaea70000,0xa63eaf64,0x2fd92da8,0xac722a1f,0xafd90000,0x2ea7aa1f,0xac722da8,0x263eaf64,
  0xafd90000,0x2ea72a1f,0xac72ada8,0x263e2f64,0xaea70000,0xa63e2f64,0x2fd9ada8,0xac72aa1f,0xac720000,0xafd92f64,0xa63e2da8,0x2ea7aa1f,
  0xa63e0000,0xac722a1f,0xaea72da8,0xafd92f64,0x2fd93000,0x2ea72f64,0x2c722da8,0x263e2a1f,0x2ea73000,0xa63e2a1f,0xafd9ada8,0xac72af64,
  0x2c723000,0xafd9aa1f,0x263eada8,0x2ea72f64,0x263e3000,0xac72af64,0x2ea72da8,0xafd9aa1f,0xa63e3000,0x2c72af64,0xaea72da8,0x2fd9aa1f,
  0xac723000,0x2fd9aa1f,0xa63eada8,0xaea72f64,0xaea73000,0x263e2a1f,0x2fd9ada8,0x2c72af64,0xafd93000,0xaea72f64,0xac722da8,0xa63e2a1f,
  0x263e0000,0x2c72aa1f,0x2ea7ada8,0x2fd9af64,0x2c720000,0x2fd9af64,0x263eada8,0xaea72a1f,0x2ea70000,0x263eaf64,0xafd92da8,0x2c722a1f,
  0x2fd90000,0xaea7aa1f,0x2c722da8,0xa63eaf64,0x2fd90000,0xaea72a1f,0x2c72ada8,0xa63e2f64,0x2ea70000,0x263e2f64,0xafd9ada8,0x2c72aa1f,
  0x2c720000,0x2fd92f64,0x263e2da8,0xaea7aa1f,0x263e0000,0x2c722a1f,0x2ea72da8,0x2fd92f64,0xafd93000,0xaea72f64,0xac722da8,0xa63e2a1f,
  0xaea73000,0x263e2a1f,0x2fd9ada8,0x2c72af64,0xac723000,0x2fd9aa1f,0xa63eada8,0xaea72f64,0xa63e3000,0x2c72af64,0xaea72da8,0x2fd9aa1f,
  0x263e3000,0xac72af64,0x2ea72da8,0xafd9aa1f,0x2c723000,0xafd9aa1f,0x263eada8,0x2ea72f64,0x2ea73000,0xa63e2a1f,0xafd9ada8,0xac72af64,
  0x2fd93000,0x2ea72f64,0x2c722da8,0x263e2a1f,0xa63e0000,0xac72aa1f,0xaea7ada8,0xafd9af64,0x2c720000,0x2fd92f64,0x263e2da8,0xaea7aa1f,
  0xaea70000,0xa63eaf64,0x2fd92da8,0xac722a1f,0x2fd90000,0xaea72a1f,0x2c72ada8,0xa63e2f64,0xafd90000,0x2ea72a1f,0xac72ada8,0x263e2f64,
  0x2ea70000,0x263eaf64,0xafd92da8,0x2c722a1f,0xac720000,0xafd92f64,0xa63e2da8,0x2ea7aa1f,0x263e0000,0x2c72aa1f,0x2ea7ada8,0x2fd9af64,
  0x2fd93000,0x2ea72f64,0x2c722da8,0x263e2a1f,0xaea7b000,0x263eaa1f,0x2fd92da8,0x2c722f64,0x2c723000,0xafd9aa1f,0x263eada8,0x2ea72f64,
  0xa63eb000,0x2c722f64,0xaea7ada8,0x2fd92a1f,0xa63e3000,0x2c72af64,0xaea72da8,0x2fd9aa1f,0x2c72b000,0xafd92a1f,0x263e2da8,0x2ea7af64,
  0xaea73000,0x263e2a1f,0x2fd9ada8,0x2c72af64,0x2fd9b000,0x2ea7af64,0x2c72ada8,0x263eaa1f,0x263e0000,0x2c72aa1f,0x2ea7ada8,0x2fd9af64,
  0xac720000,0xafd92f64,0xa63e2da8,0x2ea7aa1f,0x2ea70000,0x263eaf64,0xafd92da8,0x2c722a1f,0xafd90000,0x2ea72a1f,0xac72ada8,0x263e2f64,
  0x2fd90000,0xaea72a1f,0x2c72ada8,0xa63e2f64,0xaea70000,0xa63eaf64,0x2fd92da8,0xac722a1f,0x2c720000,0x2fd92f64,0x263e2da8,0xaea7aa1f,
  0xa63e0000,0xac72aa1f,0xaea7ada8,0xafd9af64,0xafd93000,0xaea72f64,0xac722da8,0xa63e2a1f,0x2ea7b000,0xa63eaa1f,0xafd92da8,0xac722f64,
  0xac723000,0x2fd9aa1f,0xa63eada8,0xaea72f64,0x263eb000,0xac722f64,0x2ea7ada8,0xafd92a1f,0x263e3000,0xac72af64,0x2ea72da8,0xafd9aa1f,
  0xac72b000,0x2fd92a1f,0xa63e2da8,0xaea7af64,0x2ea73000,0xa63e2a1f,0xafd9ada8,0xac72af64,0xafd9b000,0xaea7af64,0xac72ada8,0xa63eaa1f,
  0xafd9b000,0xaea7af64,0xac72ada8,0xa63eaa1f,0x2ea73000,0xa63e2a1f,0xafd9ada8,0xac72af64,0xac72b000,0x2fd92a1f,0xa63e2da8,0xaea7af64,
  0x263e3000,0xac72af64,0x2ea72da8,0xafd9aa1f,0x263eb000,0xac722f64,0x2ea7ada8,0xafd92a1f,0xac723000,0x2fd9aa1f,0xa63eada8,0xaea72f64,
  0x2ea7b000,0xa63eaa1f,0xafd92da8,0xac722f64,0xafd93000,0xaea72f64,0xac722da8,0xa63e2a1f,0xa63e0000,0xac72aa1f,0xaea7ada8,0xafd9af64,
  0x2c720000,0x2fd92f64,0x263e2da8,0xaea7aa1f,0xaea70000,0xa63eaf64,0x2fd92da8,0xac722a1f,0x2fd90000,0xaea72a1f,0x2c72ada8,0xa63e2f64,
  0xafd90000,0x2ea72a1f,0xac72ada8,0x263e2f64,0x2ea70000,0x263eaf64,0xafd92da8,0x2c722a1f,0xac720000,0xafd92f64,0xa63e2da8,0x2ea7aa1f,
  0x263e0000,0x2c72aa1f,0x2ea7ada8,0x2fd9af64,0x2fd9b000,0x2ea7af64,0x2c72ada8,0x263eaa1f,0xaea73000,0x263e2a1f,0x2fd9ada8,0x2c72af64,
  0x2c72b000,0xafd92a1f,0x263e2da8,0x2ea7af64,0xa63e3000,0x2c72af64,0xaea72da8,0x2fd9aa1f,0xa63eb000,0x2c722f64,0xaea7ada8,0x2fd92a1f,
  0x2c723000,0xafd9aa1f,0x263eada8,0x2ea72f64,0xaea7b000,0x263eaa1f,0x2fd92da8,0x2c722f64,0x2fd93000,0x2ea72f64,0x2c722da8,0x263e2a1f,
  0x263e0000,0x2c72aa1f,0x2ea7ada8,0x2fd9af64,0xac720000,0xafd92f64,0xa63e2da8,0x2ea7aa1f,0x2ea70000,0x263eaf64,0xafd92da8,0x2c722a1f,
  0xafd90000,0x2ea72a1f,0xac72ada8,0x263e2f64,0x2fd90000,0xaea72a1f,0x2c72ada8,0xa63e2f64,0xaea70000,0xa63eaf64,0x2fd92da8,0xac722a1f,
  0x2c720000,0x2fd92f64,0x263e2da8,0xaea7aa1f,0xa63e0000,0xac72aa1f,0xaea7ada8,0xafd9af64,0x316c2fbd,0x343e32f7,0x35bc34ff,0x372c3676,
  0x371532c6,0x3a81392e,0x3bef3b71,0x3b7c3bf2,0x397034cf,0x3bfc3b6c,0x38b23b04,0xb40e31e8,0x3ae13631,0x39e73bf5,0xb6e83219,0xbbe8bb13,
  0x3bc23785,0x30be3aa9,0xbbfdb911,0x2a16b9aa,0x3bfe3865,0xb80f37a6,0xb82abc00,0x3bfd376f,0x3b9238fd,0xbb7f2311,0x3805b929,0x31223bde,
  0x3a85398b,0xbb96b742,0x3bff319e,0xbbb82f8b,0xbbe2bbf1,0xbbb7bbcf,0xbb78bb9a,0xbb27bb52,0xbb2cbbd2,0xb8a8ba19,0xb029b5df,0x35a52f59,
  0xb9dfbba1,0x2ba7b5f7,0x3a7a37b2,0x3bbd3bdd,0xb815bb60,0x39662e91,0x3b373bda,0xb0d7377a,0xb3d3bb10,0x3be9386f,0x2a7a3a31,0xbbfeb9a6,
  0x294dbab0,0x3ae53b07,0xbad51fdb,0xab43bb16,0x352fba41,0x35993c00,0xbaebba1d,0x3be531cf,0x38a3b9c5,0xb5173b21,0x2776bbe0,0x34323bf2,
  0x384537dd,0x38ea3899,0x39823937,0x3a0d39c9,0x39463a93,0x3340374e,0xb426a452,0xb979b7c8,0xbb45b924,0xbb32bc00,0xb371b902,0x38d63294,
  0xb08db9a1,0x3b3f379b,0x39583bd7,0xb8252dfb,0x3bea3a2d,0xb3ba3874,0xbb89bb0d,0x36d2b625,0xb6bb387f,0xb8d1bbf5,0x3be73602,0xb546391f,
  0xba00bb01,0x3bff35eb,0xba5c34db,0x3359bab6,0x3ac7b66b,0xb9413933,0x368dbabd,0xb0103bb3,0xbac4baf7,0xba50ba8c,0xb9cdba11,0xb93cb986,
  0x3a04388e,0x3bcb3b1e,0x3bba3c00,0x39d63afe,0x36af3a21,0xb6ffa17f,0xbbc8ba3d,0xba60bbd4,0xbbebb9af,0xb6c6bb0a,0x39f43263,0x3ad83bf7,
  0x30a6b916,0x3bc33aa5,0xb55e3790,0xbb3dbb63,0x3b423a9e,0xba642ec3,0xb0f0bb6a,0x3b8e3a25,0xb94a37bd,0x2884bb6f,0x38db3b9f,0xbbc9b85a,
  0xb840bb54,0x3a093a15,0xbb4cb850,0x3bef3457,0x3a893a4d,0x3af43ac1,0x3b4f3b24,0x3b983b76,0xbb94baba,0xbbe4bbf9,0xba58bb57,0xb699b8f8,
  0x3bfe3b18,0x394f3b5c,0xb109347b,0xbae8b884,0xbbc0bb68,0xa9b1b90c,0x3b8b387a,0x38bc3ba5,0x3ade3ba7,0xb8c1324b,0xb9f0bbf6,0x39eb9648,
  0xb96bbbd6,0x3bbf3487,0xb38939b3,0xb9f8bba3,0x370a3bf3,0xbb47b994,0x3bbc2d65,0xb8ad3889,0xb153bc00,0x37213b9c,0xb97dba90,0x3af138f3,
  0xb89eb8ee,0xb7e8b84a,0xb682b737,0xb50bb5c8,0x35233855,0xb13b2d33,0xb8e0b65f,0xbb4aba45,0xa8e8b764,0x39fc3648,0x3be63bae,0x380a3a9b,
  0xb3eb360e,0xbbfeba35,0xb552baa2,0x3a7334b7,0x381ab4ab,0x3a6f3bd8,0xb95d2e5f,0xb962bc00,0xb9e3327c,0xb402bbac,0x3bc6399d,0xb95434c3,
  0x3b2faf27,0xb6a439bc,0xb41abbf9,0x3a7e3a97,0xbbe3251b,0x3b2ab4f3,0xb9d23894,0x37f3ba49,0x3bce3bb5,0x3bf03be1,0x3bff3bfa,0x3bfb3bff,
  0x2c38b1b6,0x383a34e7,0x3aee39c0,0x3bff3bb2,0xbb81bbf8,0xb53ab999,0x38302ef5,0x3bed3ab3,0xb8cc9cb6,0xbb85bbab,0x2adeb86a,0x3bc5391b,
  0x38c73bf6,0xbadbb232,0xb6ddbba9,0x3b87361a,0x3b833201,0xb0743a39,0xba76bb5e,0x3b352dc9,0xac06bbb0,0x39743b59,0xbbeeb759,0x3aceb2ad,
  0xbbccb5d4,0x3bfb2d00,0xbb7a32de,0x3a54b7d2,0xb30fb44b,0xafefb185,0xa6adacce,0x2c9c25e4,0xbbfcbbdf,0xbacbbb9e,0xb7feb990,0xa81fb463,
  0xb58d2d97,0xbb90b9b8,0xbad1bbf4,0xb05bb85f,0x3a673c00,0xb5763493,0xbbfdbaac,0xb3a2ba29,0x3a6b2e2d,0x38203bd9,0xbb3ab49f,0xb56abb65,
  0xb581bbdc,0x3bec3907,0xb8b7363c,0xb6f4bbf8,0xbbfcb46f,0x39dab654,0xb0423b1b,0xb835bbd3,0xb3283b73,0xac6abbfa,0x35b13bd0,0xb8e5bafb,
  0x38ee3a0d,0xb84aba89,0x37373af4,0xb5c8bb4f,0x35df3a81,0x2f59bbef,0xb88e3b7c,0x3b1eb946,0x2d973ae8,0x39b8bb81,0xbbf4353a,0x385f3830,
  0xb2633b3f,0x3bf7b958,0xb60eb825,0xba353bc0,0xb7853b87,0x3aa9b3d3,0x3911bbe9,0xb9aa2a7a,0xb99d3bbf,0x34c33389,0x3bdcb9f8,0x3907bb83,
  0xbb013be5,0xb5eb394a,0x34db2884,0x3ab6b8db,0xbbd03bfb,0xbafb3b7a,0xb98b3a54,0xb74238a3,0x3a4db93c,0xbac1389e,0x3b24b7e8,0xbb763682,
  0x3b71b8a8,0xbbf23029,0x3a9335a5,0xb74eba04,0x3bf8b80a,0xb999b58d,0xaef53b90,0x3ab3bad1,0x3bd7b6c6,0xadfbb9f4,0xbb683ad8,0x390c33eb,
  0x3b10b56a,0x386fbbc2,0xba3130be,0xb9a63bfd,0x39b3b402,0x3ba3bbc6,0x3201b954,0xba393581,0x37bdb122,0x3b6fba00,0x3b9fbbff,0x385aba5c,
  0x32deac6a,0x37d2b5b1,0x39c5b8e5,0x3b21ba85,0x344b3b98,0xb185bbce,0x2cce3bf0,0x25e4bbff,0xbc003340,0x3afe3426,0xb855b979,0x2d333b94,
  0x34cfbbed,0xbb6c39df,0x3b042ba7,0xb1e8ba7a,0x3aa2a9b1,0x34b7bb8b,0xbc0038bc,0x349338cc,0xba2d3bfe,0x387430a6,0x3b0dbbc3,0xb625b55e,
  0xb63cb074,0xbbf83a76,0xb8653b35,0x37a6294d,0x3bf3bbc9,0x3994bb2f,0x2d65b6a4,0xb889341a,0xb19e3517,0x2f8b2776,0x366bb432,0x3933b840,
  0x3bb5b50b,0xbbe1330f,0x3bfaafef,0xbbff26ad,0xa4523bcb,0x37c8bbba,0xbaba39d6,0x3bf9b523,0xbba1305b,0x35f73970,0x37b2bbfc,0xbbdd38b2,
  0x387abbfe,0xbba53552,0x9cb63a73,0x3babba67,0x39162a16,0x3aa5bbea,0xb790b3ba,0xbb633b89,0xbb5e3bec,0xadc938b7,0x3ab0b6f4,0x3b07bbfe,
  0xaf27b359,0xb9bc370a,0xbbf93b47,0xba973bbc,0x3be0bb96,0x3bf2bbff,0x3b54bbb8,0x3a15bac7,0xafbd3bfb,0x32f7bbe2,0xb4ff3bb7,0x3676bb78,
  0x365fbbe4,0xba453a58,0x3bdfb699,0xbb9eac38,0xb9243bbd,0x3c00b6af,0xb902b6ff,0xb2943bc8,0x3aacbb85,0xba29aade,0xb6313bc5,0x3bf5b815,
  0xbba73b3d,0x324b381a,0x3bf6ba6f,0x9648b95d,0x3c00bae5,0x376fbad5,0xb87f2b43,0xbbf53b42,0xbbb03a7e,0xbb593bfc,0xb75939da,0x32ad3042,
  0x3abdba09,0x3bb3bb4c,0x3c00bbef,0x3b9cbbe3,0x3bf12c9c,0xbbcfb16c,0x3b9a343e,0xbb52b5bc,0xbb57b13b,0x38f838e0,0xb1b6bb4a,0xb4e73bfc,
  0x3a21340e,0x217fbb45,0xba3d3b32,0x3bd4b371,0xb86ab576,0xb91b3bfd,0x3b60b3a2,0x2e91bae1,0x34ab36d2,0x3bd8bade,0xae5fb8c1,0xbc0039f0,
  0x9fdbb80f,0xbb16382a,0xba9e3bfd,0x2ec336bb,0xb46f38ad,0x3654ac06,0x3b1bb974,0x3bd3bbee,0x3850b941,0x3457b68d,0xa51bb010,0xb4f33153,
  0xb7dd3b27,0x3899bac4,0xb9373a50,0x39c9b9cd,0x3990383a,0xb463baee,0xb2c63bff,0x392ebb2c,0x3b18ba60,0xbb5c28e8,0x347b39fc,0x3884bbe6,
  0xb219b966,0xbb133b37,0x39a130d7,0x379bbbeb,0xbbf63962,0xb2323a6b,0x3ba9b820,0x361abb3a,0xb6023a64,0x391fb0f0,0x3bd6bb8e,0x3487b9e3,
  0x3a41b835,0x3c00bb92,0x3a1dbb7f,0x31cfb805,0x3a90bb2a,0x38f3b9d2,0x35d4b7f3,0x2d00b328,0x3af7372c,0xba8cb845,0x3a1138ea,0xb986b982,
  0x39c0bacb,0xbbb237fe,0x3bd2a81f,0xba19b715,0xb764b8d6,0xb6483bfe,0x3baeb94f,0xba9bb109,0xbbda39e7,0x377a36e8,0x39afbbe8,0xbb0a308d,
  0xae2d39eb,0x3bd9b8c7,0x349fbadb,0xbb6536dd,0x3b6ab8d1,0x3a25bbe7,0xb27cb546,0xbbac396b,0x38fdbace,0xa311b52f,0xb9293599,0xbbde3aeb,
  0xb8943721,0xba49397d,0xbb733af1,0xbbfa3bcc,0xbbfb3bff,0xbbe23bf1,0xbbb73bcf,0xbb783b9a,0xbb7c3bf2,0xb9463a93,0xb340374e,0x3426a452,
  0xba603bd4,0xa8e83764,0x39fcb648,0x3be6bbae,0xb8bc3ba5,0x38cc9cb6,0x3b85bbab,0xaadeb86a,0xb56a3b65,0x3bc2b785,0x30bebaa9,0xbbfd3911,
  0xab433b16,0x3b42ba9e,0xba64aec3,0xb0f03b6a,0x33593ab6,0x370abbf3,0xbb473994,0x3bbcad65,0x37f33a49,0xb328bb73,0xac6a3bfa,0x35b1bbd0,
  0xac9c25e4,0xb16c2fbd,0xb43e32f7,0xb5bc34ff,0xb5a52f59,0xba04388e,0xbbcb3b1e,0xbbba3c00,0xb8d63294,0xbbfe3b18,0xb94f3b5c,0x3109347b,
  0xba7334b7,0xba673c00,0x35763493,0x3bfdbaac,0xbb87361a,0xb3d33b10,0x3be9b86f,0x2a7aba31,0xbbfd376f,0x36bb387f,0x38d1bbf5,0xbbe73602,
  0xbbc9385a,0x3b2f2f27,0xb6a4b9bc,0xb41a3bf9,0xbaf138f3,0x3bccb5d4,0xbbfb2d00,0x3b7a32de,0xbb273b52,0xbac43af7,0xba503a8c,0xb9cd3a11,
  0x3979b7c8,0x3b94baba,0x3be4bbf9,0x3a58bb57,0x380aba9b,0xb58dad97,0xbb9039b8,0xbad13bf4,0xbbc5391b,0xb8153b60,0x3966ae91,0x3b37bbda,
  0x2a1639aa,0x3beaba2d,0xb3bab874,0xbb893b0d,0x3b8eba25,0xb9e3b27c,0xb4023bac,0x3bc6b99d,0xb8adb889,0xac063bb0,0x3974bb59,0xbbee3759,
  0xb8e53afb,0x3a85b98b,0xbb963742,0x3bffb19e,0xb72c3676,0xb84537dd,0xb8ea3899,0xb9823937,0xb9d63afe,0xb5233855,0x313b2d33,0x38e0b65f,
  0x3ae8b884,0x3b81bbf8,0x353ab999,0xb8302ef5,0x33a2ba29,0xbae13631,0xb9e73bf5,0x36e83219,0xbbfe39a6,0x30a63916,0x3bc3baa5,0xb55eb790,
  0x3546391f,0x396bbbd6,0xbbbf3487,0x338939b3,0x3a7eba97,0xbbfc346f,0x39da3654,0xb042bb1b,0xba54b7d2,0x38a339c5,0xb517bb21,0x27763be0,
  0xb93c3986,0xb89e38ee,0xb7e8384a,0xb6823737,0x3699b8f8,0xac38b1b6,0xb83a34e7,0xbaee39c0,0xb05b385f,0x3970b4cf,0x3bfcbb6c,0x38b2bb04,
  0xb0d7b77a,0xbbeb39af,0xb6c63b0a,0x39f4b263,0x36d23625,0x3adebba7,0xb8c1b24b,0xb9f03bf6,0xb954b4c3,0xb5813bdc,0x3becb907,0xb8b7b63c,
  0x3ace32ad,0xb52fba41,0xb5993c00,0x3aebba1d,0xbbb8af8b,0x3ac7366b,0xb941b933,0x368d3abd,0xba0d39c9,0xba893a4d,0xbaf43ac1,0xbb4f3b24,
  0x3b4aba45,0x3bfcbbdf,0x3acbbb9e,0x37feb990,0xbbed3ab3,0xb9df3ba1,0x2ba735f7,0x3a7ab7b2,0x3be8bb13,0x308db9a1,0xbb3f379b,0xb9583bd7,
  0xbb3d3b63,0x381a34ab,0x3a6fbbd8,0xb95dae5f,0x39f8bba3,0xbb833201,0x30743a39,0x3a76bb5e,0xb8353bd3,0x3b92b8fd,0xbb7fa311,0x38053929,
  0x3432bbf2,0xb8403b54,0x3a09ba15,0xbb4c3850,0xb50b35c8,0xb30f344b,0xafef3185,0xa6ad2cce,0xbbff3bb2,0xbb2c3bd2,0xb8a83a19,0xb02935df,
  0xb40eb1e8,0xbb453924,0xbb323c00,0xb3713902,0x3ad8bbf7,0xb3ebb60e,0xbbfe3a35,0xb5523aa2,0x39eb1648,0x38c7bbf6,0xbadb3232,0xb6dd3ba9,
  0xb6f43bf8,0x3bfeb865,0xb80fb7a6,0xb82a3c00,0xbbe531cf,0x394a37bd,0xa884bb6f,0xb8db3b9f,0xb010bbb3,0xb1533c00,0x3721bb9c,0xb97d3a90,
  0xbb983b76,0xbbce3bb5,0xbbf03be1,0xbbff3bfa,0x281fb463,0xb71532c6,0xba81392e,0xbbef3b71,0x3bbdbbdd,0x36afba21,0xb6ff217f,0xbbc83a3d,
  0x38252dfb,0x3bc0bb68,0x29b1b90c,0xbb8b387a,0xb9623c00,0x3a6bae2d,0x3820bbd9,0xbb3a349f,0xbb352dc9,0x294d3ab0,0x3ae5bb07,0xbad59fdb,
  0x3122bbde,0xba003b01,0x3bffb5eb,0xba5cb4db,0x3befb457,0xbbe3a51b,0x3b2a34f3,0xb9d2b894,0x39c939cd,0xba4db93c,0x3ac1389e,0xbb24b7e8,
  0x3b1e3946,0xbc00b340,0x3afeb426,0xb8553979,0x3bdd38b2,0xba21340e,0xa17fbb45,0x3a3d3b32,0x3bf53815,0xb2193966,0xbb13bb37,0x39a1b0d7,
  0x3b6536dd,0x37853b87,0xbaa9b3d3,0xb911bbe9,0x3a393581,0x3b5e3bec,0x2dc938b7,0xbab0b6f4,0x3889341a,0x3bb03a7e,0x3b593bfc,0x375939da,
  0x34f33153,0x38943721,0x3a49397d,0x3b733af1,0xb9863982,0x38eeba0d,0xb84a3a89,0x3737baf4,0xb74e3a04,0xa452bbcb,0x37c83bba,0xbabab9d6,
  0xb1e83a7a,0xb924bbbd,0x3c0036af,0xb90236ff,0x2e913ae1,0xbbdab9e7,0x377ab6e8,0x39af3be8,0x361a3b3a,0xbb10b56a,0xb86fbbc2,0x3a3130be,
  0x39073b83,0xb63c3074,0xbbf8ba76,0xb865bb35,0x3a973bbc,0x346f38ad,0xb654ac06,0xbb1bb974,0x3b9c3be3,0x3a903b2a,0x38f339d2,0x35d437f3,
  0x3b763682,0xbbb5b50b,0x3be1330f,0xbbfaafef,0x2d33bb94,0x365f3be4,0xba45ba58,0x3bdf3699,0xbbd4b371,0x3764b8d6,0x36483bfe,0xbbaeb94f,
  0x379b3beb,0xbbd7b6c6,0x2dfbb9f4,0x3b683ad8,0x39aa2a7a,0x3a2d3bfe,0xb87430a6,0xbb0dbbc3,0xbb07bbfe,0x1fdbb80f,0x3b16382a,0x3a9e3bfd,
  0xb2ad3042,0xba41b835,0xbc00bb92,0xba1dbb7f,0x3bfa3bcc,0x3bd03bfb,0x3afb3b7a,0x398b3a54,0xb5c83b4f,0x344bbb98,0xb1853bce,0x2ccebbf0,
  0x3bf93523,0xbb57313b,0x38f8b8e0,0xb1b63b4a,0xb294bbc8,0x3b183a60,0xbb5ca8e8,0x347bb9fc,0xbb0ab08d,0xb263bb3f,0x3bf73958,0xb60e3825,
  0x39a63bfd,0xb9162a16,0xbaa5bbea,0x3790b3ba,0x37a6a94d,0x3c003ae5,0x376f3ad5,0xb87fab43,0xbbd3bbee,0xb8fdbace,0x2311b52f,0x39293599,
  0x2d003328,0xb2deac6a,0xb7d2b5b1,0xb9c5b8e5,0x3bff26ad,0xbbf12c9c,0x3bcfb16c,0xbb9a343e,0xbb9e2c38,0x3990b83a,0xb4633aee,0xb2c6bbff,
  0x3a9bb109,0xad973ae8,0xb9b8bb81,0x3bf4353a,0xb90c33eb,0xb87abbfe,0x3ba53552,0x1cb63a73,0x3625b55e,0x3ba73b3d,0xb24b381a,0xbbf6ba6f,
  0xaec336bb,0xbb6ab8d1,0xba25bbe7,0x327cb546,0xb1cfb805,0x37bd3122,0x3b6f3a00,0x3b9f3bff,0x374238a3,0x319e3517,0xaf8b2776,0xb66bb432,
  0x25e43bff,0xafbdbbfb,0x32f73be2,0xb4ffbbb7,0xb4e7bbfc,0x39c03acb,0xbbb2b7fe,0x3bd2281f,0x38843be6,0xbbf8b80a,0x3999b58d,0x2ef53b90,
  0xba35bbc0,0x3aa229b1,0x34b73b8b,0xbc00b8bc,0x3b633b89,0xb4ab36d2,0xbbd8bade,0x2e5fb8c1,0xbbf5bb42,0xb602ba64,0x391f30f0,0x3bd63b8e,
  0x3bde3aeb,0x3b013be5,0x35eb394a,0xb4db2884,0xbb21ba85,0xbbe0bb96,0xbbf2bbff,0xbb54bbb8,0x3b52b5bc,0xbaf7372c,0x3a8cb845,0xba1138ea,
  0x392e3b2c,0xbb71b8a8,0x3bf23029,0xba9335a5,0xb85f3830,0xb4cfbbed,0x3b6c39df,0xbb042ba7,0xbbabba67,0x386ab576,0x391b3bfd,0xbb60b3a2,
  0x1648b95d,0x3bf63962,0x32323a6b,0xbba9b820,0x3bac396b,0x399d3bbf,0xb4c33389,0xbbdcb9f8,0x385a3a5c,0xaf273359,0xb9bcb70a,0xbbf9bb47,
  0xb933b840,0xbabdba09,0xbbb3bb4c,0xbc00bbef,0x36763b78,0xb7ddbb27,0x38993ac4,0xb937ba50,0xba193715,0x35dfba81,0x2f593bef,0xb88ebb7c,
  0xbab3bad1,0x3ba1305b,0xb5f73970,0xb7b2bbfc,0x3493b8cc,0x3aac3b85,0xba292ade,0xb631bbc5,0x3c0039f0,0x2e2d39eb,0xbbd9b8c7,0xb49fbadb,
  0x348739e3,0xb9b3b402,0xbba3bbc6,0xb201b954,0xbab6b8db,0xbbf3bbc9,0xb994bb2f,0xad65b6a4,0xba15bac7,0xb850b941,0xb457b68d,0x251bb010,
  0xb9cfbb16,0x30ac2a31,0x3b9c3bf1,0xb493ae2d,0xb76fb8b4,0x35a133e3,0x3a1d3afe,0xb902b76f,0xb3e3b5a1,0x38b4376f,0x376f3902,0xbafeba1d,
  0xaa31b0ac,0x3b1639cf,0x2e2d3493,0xbbf1bb9c,0xb956ba74,0x305f29cc,0x3b633bd2,0xb44badc9,0xb6e7b859,0x353f335e,0x39d23ab6,0xb8bcb6ff,
  0xb35eb53f,0x385936e7,0x36ff38bc,0xbab6b9d2,0xa9ccb05f,0x3a743956,0x2dc9344b,0xbbd2bb63,0xb8e3b9de,0x30122967,0x3b1e3ba1,0xb402ad65,
  0xb662b801,0x34de32da,0x39823a67,0xb874b68d,0xb2dab4de,0x38013662,0x368d3874,0xba67b982,0xa967b012,0x39de38e3,0x2d653402,0xbba1bb1e,
  0xb876b952,0x2f8c2902,0x3ace3b60,0xb371ad00,0xb5e1b758,0x347e3257,0x392e3a11,0xb82ab61a,0xb257b47e,0x375835e1,0x361a382a,0xba11b92e,
  0xa902af8c,0x39523876,0x2d003371,0xbb60bace,0xb80db8ce,0x2ef3289e,0x3a733b10,0xb2deac9c,0xb562b6b3,0x342031d5,0x38d639b3,0xb7bdb5a5,
  0xb1d5b420,0x36b33562,0x35a537bd,0xb9b3b8d6,0xa89eaef3,0x38ce380d,0x2c9c32de,0xbb10ba73,0xb750b851,0x2e5a2839,0x3a0d3ab0,0xb24bac38,
  0xb4e5b613,0x33863153,0x387a394f,0xb721b52f,0xb153b386,0x361334e5,0x352f3721,0xb94fb87a,0xa839ae5a,0x38513750,0x2c38324b,0xbab0ba0d,
  0xb68eb7b4,0x2dc227a9,0x399d3a41,0xb1b6aba7,0xb46ab577,0x32cd30d2,0x381a38e5,0xb682b4b7,0xb0d2b2cd,0x3577346a,0x34b73682,0xb8e5b81a,
  0xa7a9adc2,0x37b4368e,0x2ba731b6,0xba41b99d,0xb5d2b6d1,0x2d2a26e0,0x392439c5,0xb122aade,0xb3e3b4de,0x32163052,0x376f3874,0xb5dfb43e,
  0xb052b216,0x34de33e3,0x343e35df,0xb874b76f,0xa6e0ad2a,0x36d135d2,0x2ade3122,0xb9c5b924,0xb51cb5f6,0x2c932617,0x38a3393c,0xb08daa16,
  0xb2f4b448,0x31602fa5,0x36a437fe,0xb53ab389,0xafa5b160,0x344832f4,0x3389353a,0xb7feb6a4,0xa617ac93,0x35f6351c,0x2a16308d,0xb93cb8a3,
  0xb46ab523,0x2bf6254d,0x381a38a8,0xafefa94d,0xb209b36b,0x30ac2ea7,0x35d4370a,0xb493b294,0xaea7b0ac,0x336b3209,0x32943493,0xb70ab5d4,
  0xa54dabf6,0x3523346a,0x294d2fef,0xb8a8b81a,0xb378b456,0x2ac82484,0x3715380a,0xaec3a884,0xb120b24a,0x2ff22da9,0x34ff360e,0xb3d3b19e,
  0xada9aff2,0x324a3120,0x319e33d3,0xb60eb4ff,0xa484aac8,0x34563378,0x28842ec3,0xb80ab715,0xb223b31c,0x29992376,0x35eb36c6,0xad97a776,
  0xb039b12d,0x2e8d2cac,0x3426350b,0xb27cb0a6,0xacacae8d,0x312d3039,0x30a6327c,0xb50bb426,0xa376a999,0x331c3223,0x27762d97,0xb6c6b5eb,
  0xb0d2b194,0x286b21e4,0x34b7356a,0xac6aa5e4,0xaea7b012,0x2d2a2b5f,0x32943402,0xb122af59,0xab5fad2a,0x30122ea7,0x2f593122,0xb402b294,
  0xa1e4a86b,0x319430d2,0x25e42c6a,0xb56ab4b7,0xaf0cb012,0x267b2052,0x32f73402,0xaa7aa452,0xacdeadf5,0x2b912967,0x30d731e8,0xaf8bad65,
  0xa967ab91,0x2df52cde,0x2d652f8b,0xb1e8b0d7,0xa052a67b,0x30122f0c,0x24522a7a,0xb402b2f7,0xac79ad2a,0x24201d7f,0x30743122,0xa81fa17f,
  0xaa31ab91,0x28d026e0,0x2e2d2f8b,0xacceaade,0xa6e0a8d0,0x2b912a31,0x2ade2cce,0xaf8bae2d,0x9d7fa420,0x2d2a2c79,0x217f281f,0xb122b074,
  0xa7a9a86b,0x1f1218b6,0x2ba72c6a,0xa3119cb6,0xa54da67b,0x242021e4,0x294d2a7a,0xa81fa5e4,0xa1e4a420,0x267b254d,0x25e4281f,0xaa7aa94d,
  0x98b69f12,0x286b27a9,0x1cb62311,0xac6aaba7,0x211b21e4,0x98b69248,0xa51ba5e4,0x1cb61648,0x1f122052,0x9d7f9bdb,0xa311a452,0x217f1fdb,
  0x1bdb1d7f,0xa0529f12,0x9fdba17f,0x24522311,0x124818b6,0xa1e4a11b,0x96489cb6,0x25e4251b,0x2a632b5f,0xa1e49bdb,0xae5faf59,0x25e41fdb,
  0x286b2967,0xa6e0a4e9,0xac6aad65,0x2ade28e8,0x24e926e0,0xa967a86b,0xa8e8aade,0x2d652c6a,0x1bdb21e4,0xab5faa63,0x9fdba5e4,0x2f592e5f,
  0x2dc22ea7,0xa54d9f12,0xb1b6b294,0x294d2311,0x2bf62cde,0xaa31a86b,0xafefb0d7,0x2e2d2c6a,0x286b2a31,0xacdeabf6,0xac6aae2d,0x30d72fef,
  0x1f12254d,0xaea7adc2,0xa311a94d,0x329431b6,0x302c30d2,0xa7a9a11b,0xb41ab4b7,0x2ba7251b,0x2dc22f0c,0xac79aa63,0xb1b6b2f7,0x30742e5f,
  0x2a632c79,0xaf0cadc2,0xae5fb074,0x32f731b6,0x211b27a9,0xb0d2b02c,0xa51baba7,0x34b7341a,0x317a3257,0xa902a2ad,0xb552b61a,0x2d0026ad,
  0x2f8c309f,0xaddcac2e,0xb371b487,0x31cf3029,0x2c2e2ddc,0xb09faf8c,0xb029b1cf,0x34873371,0x22ad2902,0xb257b17a,0xa6adad00,0x361a3552,
  0x32cd33e3,0xaa31a420,0xb682b76f,0x2e2d281f,0x30ac31bb,0xaf3fad2a,0xb493b58d,0x33283122,0x2d2a2f3f,0xb1bbb0ac,0xb122b328,0x358d3493,
  0x24202a31,0xb3e3b2cd,0xa81fae2d,0x376f3682,0x341334bc,0xab5fa4e9,0xb7a6b85a,0x2f5928e8,0x319432da,0xb052ae28,0xb56ab68d,0x343e3219,
  0x2e283052,0xb2dab194,0xb219b43e,0x368d356a,0x24e92b5f,0xb4bcb413,0xa8e8af59,0x385a37a6,0x34c3358c,0xac47a5b2,0xb85fb8f3,0x304229b1,
  0x327e33fd,0xb106af26,0xb63cb785,0x34e7330f,0x2f263106,0xb3fdb27e,0xb30fb4e7,0x3785363c,0x25b22c47,0xb58cb4c3,0xa9b1b042,0x38f3385f,
  0x35773662,0xacdea67b,0xb8e5b982,0x30d72a7a,0x336b3493,0xb1bbb012,0xb70ab83a,0x358d3402,0x301231bb,0xb493b36b,0xb402b58d,0x383a370a,
  0x267b2cde,0xb662b577,0xaa7ab0d7,0x398238e5,0x36303741,0xad76a744,0xb962ba04,0x316c2b43,0x342e352a,0xb271b092,0xb7d2b8ad,0x3631347b,
  0x30923271,0xb52ab42e,0xb47bb631,0x38ad37d2,0x27442d76,0xb741b630,0xab43b16c,0x3a043962,0x36ee3815,0xae0ea807,0xb9d6ba7a,0x32012c06,
  0x34a735c4,0xb329b113,0xb84ab91b,0x36d234f3,0x31133329,0xb5c4b4a7,0xb4f3b6d2,0x391b384a,0x28072e0e,0xb815b6ee,0xac06b201,0x3a7a39d6,
  0x37b4388e,0xaea7a86b,0xba41bae1,0x32942c6a,0x35233662,0xb3e3b194,0xb8a8b982,0x376f356a,0x319433e3,0xb662b523,0xb56ab76f,0x398238a8,
  0x286b2ea7,0xb88eb7b4,0xac6ab294,0x3ae13a41,0x3841390f,0xaf3fa8d0,0xbaa2bb3a,0x33282cce,0x35a13705,0xb44fb216,0xb902b9e3,0x380535df,
  0x3216344f,0xb705b5a1,0xb5dfb805,0x39e33902,0x28d02f3f,0xb90fb841,0xacceb328,0x3b3a3aa2,0x38ac3997,0xafd8a935,0xbaf7bb83,0x33ba2d33,
  0x362137ac,0xb4aeb298,0xb958ba3d,0x38503654,0x329834ae,0xb7acb621,0xb654b850,0x3a3d3958,0x29352fd8,0xb997b8ac,0xad33b3ba,0x3b833af7,
  0x391c3a28,0xb039a999,0xbb42bbbc,0x34262d97,0x36a4382d,0xb50eb31c,0xb9aaba90,0x389936c6,0x331c350e,0xb82db6a4,0xb6c6b899,0x3a9039aa,
  0x29993039,0xba28b91c,0xad97b426,0x3bbc3b42,0x39923ac3,0xb085a9fe,0xbb81bbe3,0x346f2dfb,0x372a3886,0xb570b3a0,0xb9f8badb,0x38e03737,
  0x33a03570,0xb886b72a,0xb737b8e0,0x3adb39f8,0x29fe3085,0xbac3b992,0xadfbb46f,0x3be33b81,
};

#define PROF(slot) do {} while (0)
#define PROF_DUMP() do {} while (0)
#define PROFA(slot, dep) do {} while (0)
#define PROF3(slot) do {} while (0)
#define PROF2(slot) do {} while (0)

__device__ __forceinline__ uint32_t smem_u32(const void* p) { return (uint32_t)__cvta_generic_to_shared(p); }

__device__ __forceinline__ void mbar_init(uint32_t a, uint32_t c) {
  asm volatile("mbarrier.init.shared::cta.b64 [%0], %1;\n" ::"r"(a), "r"(c) : "memory");
}
__device__ __forceinline__ void mbar_expect_tx(uint32_t a, uint32_t bytes) {
  asm volatile("mbarrier.arrive.expect_tx.shared::cta.b64 _, [%0], %1;\n" ::"r"(a), "r"(bytes) : "memory");
}
__device__ __forceinline__ void mbar_arrive_cluster(uint32_t cluster_addr) {
  asm volatile("mbarrier.arrive.shared::cluster.b64 _, [%0];\n" ::"r"(cluster_addr) : "memory");
}
__device__ __forceinline__ void mbar_arrive_cluster_n(uint32_t cluster_addr, uint32_t n) {
  asm volatile("mbarrier.arrive.shared::cluster.b64 _, [%0], %1;\n" ::"r"(cluster_addr), "r"(n) : "memory");
}
__device__ __forceinline__ bool mbar_try(uint32_t a, uint32_t parity) {
  uint32_t ok;
  asm volatile("{\n.reg .pred p;\nmbarrier.try_wait.parity.shared::cta.b64 p, [%1], %2;\nselp.u32 %0, 1, 0, p;\n}\n"
               : "=r"(ok) : "r"(a), "r"(parity) : "memory");
  return ok;
}
__device__ __forceinline__ void mbar_wait(uint32_t a, uint32_t parity) {
  if (mbar_try(a, parity)) return;
#pragma unroll 1
  for (int n = 0; n < SPIN_LIMIT; n++)
    if (mbar_try(a, parity)) break;
}
__device__ __forceinline__ bool elect_one() {
  uint32_t p;
  asm volatile("{\n.reg .pred P;\nelect.sync _|P, 0xffffffff;\nselp.u32 %0, 1, 0, P;\n}\n" : "=r"(p));
  return p;
}
__device__ __forceinline__ uint32_t mapa(uint32_t a, uint32_t rank) {
  uint32_t r;
  asm volatile("mapa.shared::cluster.u32 %0, %1, %2;\n" : "=r"(r) : "r"(a), "r"(rank));
  return r;
}
__device__ __forceinline__ void nb_sync(int id, int n) { asm volatile("bar.sync %0, %1;\n" ::"r"(id), "r"(n) : "memory"); }
__device__ __forceinline__ void nb_arrive(int id, int n) { asm volatile("bar.arrive %0, %1;\n" ::"r"(id), "r"(n) : "memory"); }
__device__ __forceinline__ void cluster_sync_all() {
  asm volatile("barrier.cluster.arrive.relaxed.aligned;\nbarrier.cluster.wait.aligned;\n" ::: "memory");
}
__device__ __forceinline__ void fence_async_smem() { asm volatile("fence.proxy.async.shared::cta;\n" ::: "memory"); }
__device__ __forceinline__ void fence_async_all() { asm volatile("fence.proxy.async.global;\n" ::: "memory"); }

__device__ __forceinline__ void tma_load_3d(uint32_t dst, const CUtensorMap* tm, uint32_t bar, int c0, int c1, int c2) {
  asm volatile(
      "cp.async.bulk.tensor.3d.shared::cluster.global.mbarrier::complete_tx::bytes [%0], [%1, {%3, %4, %5}], [%2];\n"
      ::"r"(dst), "l"(tm), "r"(bar), "r"(c0), "r"(c1), "r"(c2) : "memory");
}
__device__ __forceinline__ void tma_load_4d(uint32_t dst, const CUtensorMap* tm, uint32_t bar, int c0, int c1, int c2, int c3) {
  asm volatile(
      "cp.async.bulk.tensor.4d.shared::cluster.global.mbarrier::complete_tx::bytes [%0], [%1, {%3, %4, %5, %6}], [%2];\n"
      ::"r"(dst), "l"(tm), "r"(bar), "r"(c0), "r"(c1), "r"(c2), "r"(c3) : "memory");
}
__device__ __forceinline__ void tma_load_3d_mc(uint32_t dst, const CUtensorMap* tm, uint32_t bar, int c0, int c1, int c2) {
  asm volatile(
      "cp.async.bulk.tensor.3d.shared::cluster.global.mbarrier::complete_tx::bytes.multicast::cluster [%0], [%1, {%3, %4, %5}], [%2], %6;\n"
      ::"r"(dst), "l"(tm), "r"(bar), "r"(c0), "r"(c1), "r"(c2), "h"((uint16_t)3) : "memory");
}
__device__ __forceinline__ void bulk_load(uint32_t dst, const void* src, uint32_t bytes, uint32_t bar) {
  asm volatile("cp.async.bulk.shared::cluster.global.mbarrier::complete_tx::bytes [%0], [%1], %2, [%3];\n"
               ::"r"(dst), "l"(src), "r"(bytes), "r"(bar) : "memory");
}
__device__ __forceinline__ void tma_store_3d(const CUtensorMap* tm, uint32_t src, int c0, int c1, int c2) {
  asm volatile("cp.async.bulk.tensor.3d.global.shared::cta.bulk_group [%0, {%2, %3, %4}], [%1];\n"
               ::"l"(tm), "r"(src), "r"(c0), "r"(c1), "r"(c2) : "memory");
}
__device__ __forceinline__ void bulk_commit() { asm volatile("cp.async.bulk.commit_group;\n" ::: "memory"); }
__device__ __forceinline__ void bulk_wait0() { asm volatile("cp.async.bulk.wait_group 0;\n" ::: "memory"); }
__device__ __forceinline__ void prefetch_tmap(const CUtensorMap* tm) {
  asm volatile("prefetch.tensormap [%0];\n" ::"l"(tm) : "memory");
}

__device__ __forceinline__ void wg_fence() { asm volatile("wgmma.fence.sync.aligned;\n" ::: "memory"); }
__device__ __forceinline__ void wg_commit() { asm volatile("wgmma.commit_group.sync.aligned;\n" ::: "memory"); }
template <int N> __device__ __forceinline__ void wg_wait() {
  asm volatile("wgmma.wait_group.sync.aligned %0;\n" ::"n"(N) : "memory");
}
__device__ __forceinline__ uint64_t mkdesc(uint32_t addr, uint32_t lbo, uint32_t sbo, uint32_t swz) {
  return (uint64_t)((addr & 0x3FFFF) >> 4) | ((uint64_t)(lbo >> 4) << 16) | ((uint64_t)(sbo >> 4) << 32) |
         ((uint64_t)swz << 62);
}

#define R4(d, o) "+f"(d[o + 0]), "+f"(d[o + 1]), "+f"(d[o + 2]), "+f"(d[o + 3])
#define R8(d, o) R4(d, o), R4(d, o + 4)
#define R16(d, o) R8(d, o), R8(d, o + 8)
#define R32(d, o) R16(d, o), R16(d, o + 16)
#define R64(d, o) R32(d, o), R32(d, o + 32)

__device__ __forceinline__ void wgmma_n192(float (&d)[96], uint64_t da, uint64_t db, uint32_t acc) {
  asm volatile(
      "{\n.reg .pred p;\nsetp.ne.u32 p, %98, 0;\n"
      "wgmma.mma_async.sync.aligned.m64n192k16.f32.bf16.bf16 "
      "{%0,%1,%2,%3,%4,%5,%6,%7,%8,%9,%10,%11,%12,%13,%14,%15,%16,%17,%18,%19,%20,%21,%22,%23,%24,%25,%26,%27,%28,%29,%30,%31,"
      "%32,%33,%34,%35,%36,%37,%38,%39,%40,%41,%42,%43,%44,%45,%46,%47,%48,%49,%50,%51,%52,%53,%54,%55,%56,%57,%58,%59,%60,%61,%62,%63,"
      "%64,%65,%66,%67,%68,%69,%70,%71,%72,%73,%74,%75,%76,%77,%78,%79,%80,%81,%82,%83,%84,%85,%86,%87,%88,%89,%90,%91,%92,%93,%94,%95}, "
      "%96, %97, p, 1, 1, 0, 1;\n}\n"
      : R64(d, 0), R32(d, 64)
      : "l"(da), "l"(db), "r"(acc));
}
__device__ __forceinline__ void wgmma_n128(float (&d)[64], uint64_t da, uint64_t db, uint32_t acc) {
  asm volatile(
      "{\n.reg .pred p;\nsetp.ne.u32 p, %66, 0;\n"
      "wgmma.mma_async.sync.aligned.m64n128k16.f32.bf16.bf16 "
      "{%0,%1,%2,%3,%4,%5,%6,%7,%8,%9,%10,%11,%12,%13,%14,%15,%16,%17,%18,%19,%20,%21,%22,%23,%24,%25,%26,%27,%28,%29,%30,%31,"
      "%32,%33,%34,%35,%36,%37,%38,%39,%40,%41,%42,%43,%44,%45,%46,%47,%48,%49,%50,%51,%52,%53,%54,%55,%56,%57,%58,%59,%60,%61,%62,%63}, "
      "%64, %65, p, 1, 1, 0, 1;\n}\n"
      : R64(d, 0)
      : "l"(da), "l"(db), "r"(acc));
}
#define WG128(C, ACC)                                                                                                      \
  asm volatile(                                                                                                            \
      "{\n.reg .b64 a, b;\nmov.b64 a, {%64, %66};\nmov.b64 b, {%65, %66};\n"                                               \
      "wgmma.mma_async.sync.aligned.m64n128k16.f32.bf16.bf16 "                                                             \
      "{%0,%1,%2,%3,%4,%5,%6,%7,%8,%9,%10,%11,%12,%13,%14,%15,%16,%17,%18,%19,%20,%21,%22,%23,%24,%25,%26,%27,%28,%29,%30,%31," \
      "%32,%33,%34,%35,%36,%37,%38,%39,%40,%41,%42,%43,%44,%45,%46,%47,%48,%49,%50,%51,%52,%53,%54,%55,%56,%57,%58,%59,%60,%61," \
      "%62,%63}, a, b, " ACC ", 1, 1, 0, 1;\n}\n"                                                                          \
      : Z16(C, d, 0), Z16(C, d, 16), Z16(C, d, 32), Z16(C, d, 48)                                                          \
      : "r"(da), "r"(db), "r"(0x40000040))
#define Z4(C, d, o) C(d[o + 0]), C(d[o + 1]), C(d[o + 2]), C(d[o + 3])
#define Z16(C, d, o) Z4(C, d, o), Z4(C, d, o + 4), Z4(C, d, o + 8), Z4(C, d, o + 12)
__device__ __forceinline__ void wgmma_n128z(float (&d)[64], uint32_t da, uint32_t db) { WG128("=f", "0"); }
__device__ __forceinline__ void wgmma_n128a(float (&d)[64], uint32_t da, uint32_t db) { WG128("+f", "1"); }
template <int N> __device__ __forceinline__ void fence_regs(float (&d)[N]) {
#pragma unroll
  for (int i = 0; i < N; i++) asm volatile("" : "+f"(d[i])::"memory");
}

__device__ __forceinline__ void mma16816(float (&d)[4], uint32_t a0, uint32_t a1, uint32_t a2, uint32_t a3, uint32_t b0,
                                         uint32_t b1) {
  asm("mma.sync.aligned.m16n8k16.row.col.f32.bf16.bf16.f32 {%0,%1,%2,%3}, {%4,%5,%6,%7}, {%8,%9}, {%0,%1,%2,%3};\n"
      : "+f"(d[0]), "+f"(d[1]), "+f"(d[2]), "+f"(d[3])
      : "r"(a0), "r"(a1), "r"(a2), "r"(a3), "r"(b0), "r"(b1));
}
__device__ __forceinline__ void mma16816_z(float (&d)[4], uint32_t a0, uint32_t a1, uint32_t a2, uint32_t a3, uint32_t b0,
                                           uint32_t b1) {
  asm("mma.sync.aligned.m16n8k16.row.col.f32.bf16.bf16.f32 {%0,%1,%2,%3}, {%4,%5,%6,%7}, {%8,%9}, {%10,%10,%10,%10};\n"
      : "=f"(d[0]), "=f"(d[1]), "=f"(d[2]), "=f"(d[3])
      : "r"(a0), "r"(a1), "r"(a2), "r"(a3), "r"(b0), "r"(b1), "f"(0.f));
}
__device__ __forceinline__ void ldsm4t(uint32_t (&r)[4], uint32_t a) {
  asm volatile("ldmatrix.sync.aligned.m8n8.x4.trans.shared.b16 {%0,%1,%2,%3}, [%4];\n"
               : "=r"(r[0]), "=r"(r[1]), "=r"(r[2]), "=r"(r[3]) : "r"(a) : "memory");
}
__device__ __forceinline__ void ldsm2t(uint32_t& r0, uint32_t& r1, uint32_t a) {
  asm volatile("ldmatrix.sync.aligned.m8n8.x2.trans.shared.b16 {%0,%1}, [%2];\n" : "=r"(r0), "=r"(r1) : "r"(a) : "memory");
}
__device__ __forceinline__ void st_async128(uint32_t a, uint32_t bar, uint32_t x, uint32_t y, uint32_t z, uint32_t w) {
  asm volatile("st.async.weak.shared::cluster.mbarrier::complete_tx::bytes.v4.b32 [%0], {%2,%3,%4,%5}, [%1];\n"
               ::"r"(a), "r"(bar), "r"(x), "r"(y), "r"(z), "r"(w) : "memory");
}
__device__ __forceinline__ void mbar_arrive(uint32_t a) {
  asm volatile("mbarrier.arrive.shared::cta.b64 _, [%0];\n" ::"r"(a) : "memory");
}
__device__ __forceinline__ void stsm4(uint32_t a, uint32_t r0, uint32_t r1, uint32_t r2, uint32_t r3) {
  asm volatile("stmatrix.sync.aligned.m8n8.x4.shared.b16 [%0], {%1,%2,%3,%4};\n"
               ::"r"(a), "r"(r0), "r"(r1), "r"(r2), "r"(r3) : "memory");
}
__device__ __forceinline__ void stsm4t(uint32_t a, uint32_t r0, uint32_t r1, uint32_t r2, uint32_t r3) {
  asm volatile("stmatrix.sync.aligned.m8n8.x4.trans.shared.b16 [%0], {%1,%2,%3,%4};\n"
               ::"r"(a), "r"(r0), "r"(r1), "r"(r2), "r"(r3) : "memory");
}
__device__ __forceinline__ uint2 lds64(uint32_t a) {
  uint2 v;
  asm volatile("ld.shared.v2.u32 {%0,%1}, [%2];\n" : "=r"(v.x), "=r"(v.y) : "r"(a) : "memory");
  return v;
}
__device__ __forceinline__ uint4 lds128(uint32_t a) {
  uint4 v;
  asm volatile("ld.shared.v4.u32 {%0,%1,%2,%3}, [%4];\n" : "=r"(v.x), "=r"(v.y), "=r"(v.z), "=r"(v.w) : "r"(a) : "memory");
  return v;
}
__device__ __forceinline__ void sts128(uint32_t a, uint32_t x, uint32_t y, uint32_t z, uint32_t w) {
  asm volatile("st.shared.v4.u32 [%0], {%1,%2,%3,%4};\n" ::"r"(a), "r"(x), "r"(y), "r"(z), "r"(w) : "memory");
}
__device__ __forceinline__ void sts64(uint32_t a, uint32_t x, uint32_t y) {
  asm volatile("st.shared.v2.u32 [%0], {%1,%2};\n" ::"r"(a), "r"(x), "r"(y) : "memory");
}
__device__ __forceinline__ uint32_t pack_bf16(float lo, float hi) {
  uint32_t r;
  asm("cvt.rn.bf16x2.f32 %0, %1, %2;\n" : "=r"(r) : "f"(hi), "f"(lo));
  return r;
}
__device__ __forceinline__ uint32_t bmul2(uint32_t a, uint32_t b) {
  uint32_t r;
  asm("mul.rn.bf16x2 %0, %1, %2;\n" : "=r"(r) : "r"(a), "r"(b));
  return r;
}
__device__ __forceinline__ uint32_t bmax2(uint32_t a, uint32_t b) {
  uint32_t r;
  asm("max.bf16x2 %0, %1, %2;\n" : "=r"(r) : "r"(a), "r"(b));
  return r;
}
__device__ __forceinline__ uint32_t bfma2(uint32_t a, uint32_t b, uint32_t c) {
  uint32_t r;
  asm("fma.rn.bf16x2 %0, %1, %2, %3;\n" : "=r"(r) : "r"(a), "r"(b), "r"(c));
  return r;
}
__device__ __forceinline__ uint32_t clock32() {
  uint32_t t;
  asm volatile("mov.u32 %0, %%clock;\n" : "=r"(t));
  return t;
}
__device__ __forceinline__ void prefetch_l2(const void* p) { asm volatile("prefetch.global.L2 [%0];\n" ::"l"(p)); }
__device__ __forceinline__ void cp_async16(uint32_t dst, const void* src, uint32_t srcbytes) {
  asm volatile("cp.async.cg.shared.global.L2::256B [%0], [%1], 16, %2;\n" ::"r"(dst), "l"(src), "r"(srcbytes) : "memory");
}
__device__ __forceinline__ uint32_t ld_acquire(const uint32_t* p) {
  uint32_t v;
  asm volatile("ld.acquire.gpu.global.u32 %0, [%1];\n" : "=r"(v) : "l"(p) : "memory");
  return v;
}
__device__ __forceinline__ uint32_t ld_relaxed(const uint32_t* p) {
  uint32_t v;
  asm volatile("ld.relaxed.gpu.global.u32 %0, [%1];\n" : "=r"(v) : "l"(p) : "memory");
  return v;
}
__device__ __forceinline__ uint4 ld_b128(const uint4* p) {
  unsigned long long a, b;
  asm volatile("{\n.reg .b128 v;\nld.relaxed.gpu.global.b128 v, [%2];\nmov.b128 {%0, %1}, v;\n}\n" : "=l"(a), "=l"(b) : "l"(p) : "memory");
  return make_uint4((uint32_t)a, (uint32_t)(a >> 32), (uint32_t)b, (uint32_t)(b >> 32));
}
__device__ __forceinline__ void st_b128(uint4* p, uint32_t x, uint32_t y, uint32_t z, uint32_t w) {
  asm volatile("{\n.reg .b128 v;\nmov.b128 v, {%1, %2};\nst.relaxed.gpu.global.b128 [%0], v;\n}\n"
               ::"l"(p), "l"(x | (unsigned long long)y << 32), "l"(z | (unsigned long long)w << 32) : "memory");
}

struct Params {
  const __nv_bfloat16* x;
  const __nv_bfloat16* w;
  uint8_t tile[72];
  const __nv_bfloat16* q;
  const __nv_bfloat16* k;
  const __nv_bfloat16* v;
  const __nv_bfloat16* shift_k;
  const __nv_bfloat16* ssm_k;
  const __nv_bfloat16* ssm_D;
  const __nv_bfloat16* wo;
  __nv_bfloat16* out;
  uint32_t zero;
};

__device__ __forceinline__ uint32_t lds32(uint32_t a) {
  uint32_t v;
  asm volatile("ld.shared.u32 %0, [%1];\n" : "=r"(v) : "r"(a) : "memory");
  return v;
}
__device__ __forceinline__ float bf_lo(uint32_t v) {
  uint32_t r;
  asm("prmt.b32 %0, %1, 0, 0x1044;\n" : "=r"(r) : "r"(v));
  return __uint_as_float(r);
}
__device__ __forceinline__ float bf_hi(uint32_t v) { return __uint_as_float(v & 0xffff0000u); }
__device__ __forceinline__ float ex2(float x) {
  float r;
  asm("ex2.approx.ftz.f32 %0, %1;\n" : "=f"(r) : "f"(x));
  return r;
}
__device__ __forceinline__ float rcp(float x) {
  float r;
  asm("rcp.approx.ftz.f32 %0, %1;\n" : "=f"(r) : "f"(x));
  return r;
}

#define Q4(c, d, o) c(d[o + 0]), c(d[o + 1]), c(d[o + 2]), c(d[o + 3])
#define Q8(c, d, o) Q4(c, d, o), Q4(c, d, o + 4)
#define Q16(c, d, o) Q8(c, d, o), Q8(c, d, o + 8)
#define Q32(c, d) Q16(c, d, 0), Q16(c, d, 16)
#define L8 "{%0,%1,%2,%3,%4,%5,%6,%7}"
#define L16 "{%0,%1,%2,%3,%4,%5,%6,%7,%8,%9,%10,%11,%12,%13,%14,%15}"
#define L32 "{%0,%1,%2,%3,%4,%5,%6,%7,%8,%9,%10,%11,%12,%13,%14,%15,%16,%17,%18,%19,%20,%21,%22,%23,%24,%25,%26,%27,%28,%29,%30,%31}"
__device__ __forceinline__ void fft_rows(uint32_t (&d)[32], const uint32_t (&a)[2][4], uint64_t db) {
  asm volatile("wgmma.mma_async.sync.aligned.m64n128k16.f16.f16.f16 " L32 ", {%32,%33,%34,%35}, %36, 0, 1, 1, 1;\n"
               : Q32("=r", d) : "r"(a[0][0]), "r"(a[0][1]), "r"(a[0][2]), "r"(a[0][3]), "l"(db));
  asm volatile("wgmma.mma_async.sync.aligned.m64n128k16.f16.f16.f16 " L32 ", {%32,%33,%34,%35}, %36, 1, 1, 1, 1;\n"
               : Q32("+r", d) : "r"(a[1][0]), "r"(a[1][1]), "r"(a[1][2]), "r"(a[1][3]), "l"(db + 64));
}
template <int INV> __device__ __forceinline__ void fft_cols(uint32_t (&d)[8], const uint32_t (&a)[2][4], uint64_t db) {
  asm volatile("wgmma.mma_async.sync.aligned.m64n32k16.f16.f16.f16 " L8 ", {%8,%9,%10,%11}, %12, 0, 1, 1, %13;\n"
               : Q8("=r", d, 0) : "r"(a[0][0]), "r"(a[0][1]), "r"(a[0][2]), "r"(a[0][3]), "l"(db), "n"(INV));
  asm volatile("wgmma.mma_async.sync.aligned.m64n32k16.f16.f16.f16 " L8 ", {%8,%9,%10,%11}, %12, 1, 1, 1, %13;\n"
               : Q8("+r", d, 0) : "r"(a[1][0]), "r"(a[1][1]), "r"(a[1][2]), "r"(a[1][3]), "l"(db + (INV ? 16 : 64)), "n"(INV));
}
__device__ __forceinline__ void fft_back(float (&d)[16], uint64_t da, uint64_t db) {
  asm volatile("wgmma.mma_async.sync.aligned.m64n32k16.f32.f16.f16 " L16 ", %16, %17, 0, 1, 1, 1, 1;\n"
               : Q16("=f", d, 0) : "l"(da), "l"(db));
#pragma unroll
  for (int i = 1; i < 4; i++)
    asm volatile("wgmma.mma_async.sync.aligned.m64n32k16.f32.f16.f16 " L16 ", %16, %17, 1, 1, 1, 1, 1;\n"
                 : Q16("+f", d, 0) : "l"(da + 32 * i), "l"(db + 64 * i));
}
__device__ __forceinline__ uint32_t hmul2(uint32_t a, uint32_t b) {
  uint32_t r;
  asm("mul.rn.f16x2 %0, %1, %2;\n" : "=r"(r) : "r"(a), "r"(b));
  return r;
}
__device__ __forceinline__ uint32_t hadd2(uint32_t a, uint32_t b) {
  uint32_t r;
  asm("add.rn.f16x2 %0, %1, %2;\n" : "=r"(r) : "r"(a), "r"(b));
  return r;
}
__device__ __forceinline__ uint32_t hneg2(uint32_t a) {
  uint32_t r;
  asm("neg.f16x2 %0, %1;\n" : "=r"(r) : "r"(a));
  return r;
}
__device__ __forceinline__ uint32_t hfma2(uint32_t a, uint32_t b, uint32_t c) {
  uint32_t r;
  asm("fma.rn.f16x2 %0, %1, %2, %3;\n" : "=r"(r) : "r"(a), "r"(b), "r"(c));
  return r;
}
__device__ __forceinline__ uint32_t pack_f16(float lo, float hi) {
  uint32_t r;
  asm("cvt.rn.f16x2.f32 %0, %1, %2;\n" : "=r"(r) : "f"(hi), "f"(lo));
  return r;
}
__device__ __forceinline__ uint32_t bmaxabs2(uint32_t a, uint32_t b) {
  uint32_t r;
  asm("max.xorsign.abs.bf16x2 %0, %1, %2;\n" : "=r"(r) : "r"(a), "r"(b));
  return r;
}
struct C2 { uint32_t r, i; };
__device__ __forceinline__ C2 cmul(C2 a, C2 b) {
  return C2{hfma2(a.r, b.r, hneg2(hmul2(a.i, b.i))), hfma2(a.r, b.i, hmul2(a.i, b.r))};
}
__device__ __forceinline__ C2 cfma(C2 a, C2 b, C2 c) {
  return C2{hfma2(a.r, b.r, hfma2(hneg2(a.i), b.i, c.r)), hfma2(a.r, b.i, hfma2(a.i, b.r, c.i))};
}
__device__ __forceinline__ C2 crot(C2 z, C2 t) {
  const uint32_t r = hfma2(t.r, z.i, z.r), i = hfma2(t.i, r, z.i);
  return C2{hfma2(t.r, i, r), i};
}
__device__ __forceinline__ C2 cget(const uint32_t (&e)[8], int j, int b) { return C2{e[4 * j + b], e[4 * j + 2 + b]}; }
template <int N> __device__ __forceinline__ void fence_regs(uint32_t (&d)[N]) {
#pragma unroll
  for (int i = 0; i < N; i++) asm volatile("" : "+r"(d[i])::"memory");
}
__device__ __forceinline__ void ldsm4(uint32_t (&r)[4], uint32_t a) {
  asm volatile("ldmatrix.sync.aligned.m8n8.x4.shared.b16 {%0,%1,%2,%3}, [%4];\n"
               : "=r"(r[0]), "=r"(r[1]), "=r"(r[2]), "=r"(r[3]) : "r"(a) : "memory");
}

__device__ __forceinline__ uint32_t movm(uint32_t a) {
  uint32_t r;
  asm volatile("movmatrix.sync.aligned.m8n8.trans.b16 %0, %1;\n" : "=r"(r) : "r"(a));
  return r;
}
template <int C0, int H, bool T> __device__ __forceinline__ void attn_pack(const float (&acc)[96], uint32_t (&d)[8]) {
#pragma unroll
  for (int c = 0; c < 8; c++) {
    asm volatile("cvt.rn.bf16x2.f32 %0, %1, %2;\n" : "=r"(d[c]) : "f"(acc[4 * (C0 + c) + 2 * H + 1]), "f"(acc[4 * (C0 + c) + 2 * H]));
    if (T) d[c] = movm(d[c]);
  }
}
__device__ __forceinline__ void attn_qk(float (&s)[4], const uint32_t (&qlo)[8], const uint32_t (&qhi)[8],
                                        const uint32_t (&k)[8], int c) {
  mma16816_z(s, qlo[c], qhi[c], qlo[c + 1], qhi[c + 1], k[c], k[c + 1]);
  mma16816(s, qlo[c + 2], qhi[c + 2], qlo[c + 3], qhi[c + 3], k[c + 2], k[c + 3]);
}
template <int N> __device__ __forceinline__ void quad_softmax(float (&x)[N][2], uint32_t (&pp)[N]) {
  const float c2 = 1.4426950408889634f;
  uint32_t q[N], mx[N / 2];
#pragma unroll
  for (int n = 0; n < N; n++) {
    const uint32_t r = pack_bf16(x[n][0], x[n][1]);
    q[n] = bfma2(r, 0x3e353e35u, bmul2(r, 0x379e379eu));
    x[n][0] = bf_lo(q[n]);
    x[n][1] = bf_hi(q[n]);
  }
#pragma unroll
  for (int n = 0; n < N / 2; n++)
    mx[n] = bmax2(__byte_perm(q[2 * n], q[2 * n + 1], 0x5410), __byte_perm(q[2 * n], q[2 * n + 1], 0x7632));
#pragma unroll
  for (int o = 1; o <= 2; o++) {
#pragma unroll
    for (int n = 0; n < N / 2; n++) mx[n] = bmax2(mx[n], __shfl_xor_sync(0xffffffffu, mx[n], o));
  }
  float m[N], t[N];
#pragma unroll
  for (int n = 0; n < N / 2; n++) {
    m[2 * n] = bf_lo(mx[n]);
    m[2 * n + 1] = bf_hi(mx[n]);
  }
#pragma unroll
  for (int n = 0; n < N; n++) {
    const float nm = -m[n] * c2;
    x[n][0] = ex2(fmaf(x[n][0], c2, nm));
    x[n][1] = ex2(fmaf(x[n][1], c2, nm));
  }
#pragma unroll
  for (int n = 0; n < N; n += 2) {
    float u0, u1;
    asm("mma.sync.aligned.m16n8k8.row.col.f32.tf32.tf32.f32 {%0,%1,%2,%3}, {%4,%5,%6,%7}, {%8,%8}, {%9,%9,%9,%9};\n"
        : "=f"(t[n]), "=f"(u0), "=f"(t[n + 1]), "=f"(u1)
        : "r"(__float_as_uint(x[n][0])), "r"(__float_as_uint(x[n + 1][0])), "r"(__float_as_uint(x[n][1])),
          "r"(__float_as_uint(x[n + 1][1])), "r"(0x3f800000u), "f"(0.f));
  }
#pragma unroll
  for (int n = 0; n < N; n++) {
    const float inv = rcp(t[n]);
    pp[n] = pack_bf16(x[n][0] * inv, x[n][1] * inv);
  }
}
template <bool SPLIT>
__device__ __forceinline__ void attn_pv(uint32_t dst, const uint32_t (&vp)[8], const uint32_t (&vo)[8], int c, uint32_t pp,
                                        uint32_t maskLE) {
  const uint32_t b0 = pp & ~maskLE, b1 = pp & maskLE;
  float o[2][4];
#pragma unroll
  for (int i = 0; i < 2; i++) {
    if (SPLIT) {
      asm("mma.sync.aligned.m16n8k8.row.col.f32.bf16.bf16.f32 {%0,%1,%2,%3}, {%4,%5}, {%6}, {%7,%7,%7,%7};\n"
          : "=f"(o[i][0]), "=f"(o[i][1]), "=f"(o[i][2]), "=f"(o[i][3])
          : "r"(vp[c + 2 * i]), "r"(vp[c + 2 * i + 1]), "r"(b0), "f"(0.f));
      asm("mma.sync.aligned.m16n8k8.row.col.f32.bf16.bf16.f32 {%0,%1,%2,%3}, {%4,%5}, {%6}, {%0,%1,%2,%3};\n"
          : "+f"(o[i][0]), "+f"(o[i][1]), "+f"(o[i][2]), "+f"(o[i][3])
          : "r"(vo[c + 2 * i]), "r"(vo[c + 2 * i + 1]), "r"(b1));
    } else {
      mma16816_z(o[i], vp[c + 2 * i], vp[c + 2 * i + 1], vo[c + 2 * i], vo[c + 2 * i + 1], b0, b1);
    }
  }
  stsm4t(dst, pack_bf16(o[0][0], o[0][1]), pack_bf16(o[0][2], o[0][3]), pack_bf16(o[1][0], o[1][1]),
         pack_bf16(o[1][2], o[1][3]));
}

template <int MODE>
__global__ void __cluster_dims__(2, 1, 1) __launch_bounds__(NTHREADS, 1)
fused_kernel(const Params p, const __grid_constant__ CUtensorMap tmX, const __grid_constant__ CUtensorMap tmW,
             const __grid_constant__ CUtensorMap tmWo, const __grid_constant__ CUtensorMap tmWp,
             const __grid_constant__ CUtensorMap tmQ,
             const __grid_constant__ CUtensorMap tmOb,
             const __grid_constant__ CUtensorMap tmXh, const __grid_constant__ CUtensorMap tmWh) {
  extern __shared__ __align__(1024) uint8_t smem[];
  const int tid = threadIdx.x;
  if (tid >= 352) {
    const uint32_t i = (blockIdx.x & 127) * 16 + (tid & 15);
    prefetch_l2(tid & 16 ? (const char*)p.w + i * 128 : (const char*)p.x + i * 2048);
  }
  const uint32_t sb = smem_u32(smem);
  const int rank = blockIdx.x & 1;
  const bool halo_cta = blockIdx.x < 4;
  if (halo_cta && MODE != 0) return;
  const int tile = p.tile[blockIdx.x >> 1];
  const int rg = tile >> 3, hp = (tile & 7) * 2 + rank;
  const int par = rg >> 2, gidx = rg & 3;
  if (tid < 256 && !halo_cta && MODE != 2) {
    const uint32_t r = tid >> 3, c = tid & 7;
    asm volatile(
        "cp.async.cg.shared.global [%0 + 98304], [%1], 16;\ncp.async.cg.shared.global [%0 + 102400], [%1 + 2048], 16;\n"
        "cp.async.cg.shared.global [%0 + 106496], [%1 + 4096], 16;\ncp.async.cg.shared.global [%0], [%2], 16;\n"
        "cp.async.cg.shared.global [%0 + 4096], [%2 + 131072], 16;\ncp.async.cg.shared.global [%0 + 8192], [%2 + 262144], 16;\n"
        "cp.async.cg.shared.global [%0 + 12288], [%2 + 393216], 16;\ncp.async.cg.shared.global [%0 + 16384], [%2 + 524288], 16;\n"
        "cp.async.cg.shared.global [%0 + 20480], [%2 + 655360], 16;\ncp.async.cg.shared.global [%0 + 24576], [%2 + 786432], 16;\n"
        "cp.async.cg.shared.global [%0 + 28672], [%2 + 917504], 16;\ncp.async.commit_group;\n"
        ::"r"(sb + r * 128 + ((c ^ (r & 7)) << 4)), "l"((const char*)p.w + (r * 6144 + c * 16 + hp * 128)),
        "l"((const char*)p.x + (r * 4096 + c * 16 + gidx * 1048576 + par * 2048)) : "memory");
    static_assert(OFF_1B == 98304, "offsets above");
  }
  const uint32_t bars = sb + OFF_BAR;
  const int lane = tid & 31, warp = __shfl_sync(0xffffffffu, tid >> 5, 0);
  const int grp = par * 4 + (hp >> 2), mem = gidx * 2 + ((hp >> 1) & 1);
  const int rb2 = par * 8 + mem, cb2 = (grp & 3) * 2 + rank;
  const int chb = grp * 16 + mem * 2 + rank;
  const int cta = rg * 16 + hp;
  const int hsel = rb2 & 1;

  if (warp >= 8) {
    asm volatile("setmaxnreg.dec.sync.aligned.u32 %0;\n" :: "n"(REG_HELP));
    auto halo_issue = [&](int n, int s) {
      const uint32_t fb = bars + 8 * ((n & 1 ? BAR_FULL2 : BAR_FULLB) + s), st = sb + s * STGH;
      tma_load_3d(st + 8192, &tmWh, fb, 0, (n >> 1) * 64, 16 + (n & 1) * 16 + blockIdx.x * 4);
      tma_load_4d(st, &tmXh, fb, (n >> 1) * 64, 248, 0, 0);
      mbar_expect_tx(fb, STGH - 2048);
    };
    if (tid == 256) {
      prefetch_tmap(halo_cta ? &tmXh : &tmX);
#pragma unroll
      for (int i = 0; i < NS1B; i++) mbar_init(bars + 8 * (BAR_FULLB + i), 1);
#pragma unroll
      for (int i = 0; i < NS1A; i++) mbar_init(bars + 8 * (BAR_FULLA + i), 1);
      asm volatile("fence.mbarrier_init.release.cluster;\n" ::: "memory");
      if (!halo_cta && MODE != 2) {
        mbar_expect_tx(bars + 8 * (BAR_FULLB + 1), STG1B);
        tma_load_3d(sb + OFF_1B + 1 * STG1B, &tmW, bars + 8 * (BAR_FULLB + 1), hp * 64, 32, 0);
        mbar_expect_tx(bars + 8 * (BAR_FULLA + 1), STG1A);
        tma_load_3d(sb + STG1A, &tmX, bars + 8 * (BAR_FULLA + 1), 64, par, gidx * 256);
        tma_load_3d(sb + STG1A + 16384, &tmX, bars + 8 * (BAR_FULLA + 1), 64, par, gidx * 256 + 128);
        mbar_expect_tx(bars + 8 * (BAR_FULLB + 2), STG1B);
        tma_load_3d(sb + OFF_1B + 2 * STG1B, &tmW, bars + 8 * (BAR_FULLB + 2), hp * 64, 64, 0);
        mbar_arrive(bars + 8 * BAR_FULLA);
        mbar_arrive(bars + 8 * BAR_FULLB);
      } else if (halo_cta) {
        halo_issue(0, 0);
      }
    } else if (tid >= 289 && tid < 289 + 48 && tid != 320) {
      const uint32_t i = tid - 289 - (tid > 320), b = blockIdx.x & 127;
      if (MODE != 2) prefetch_l2(i < 16 ? (const char*)p.x + (b * 16 + i) * 2048 + 128 : (const char*)p.w + (2048 + b * 31 + i - 16) * 128);
    } else if (tid == 288) {
#pragma unroll
      for (int i = 0; i < NS1A; i++) mbar_init(bars + 8 * (BAR_EMPTYA + i), 4);
#pragma unroll
      for (int i = 0; i < NS1B; i++) mbar_init(bars + 8 * (BAR_EMPTYB + i), 2);
      mbar_init(bars + 8 * BAR_X, 3);
      mbar_init(bars + 8 * BAR_TAB, 16);
      mbar_init(bars + 8 * BAR_U, 1);
      mbar_init(bars + 8 * BAR_H, 1);
      mbar_init(bars + 8 * BAR_Q, 1);
      mbar_init(bars + 8 * BAR_LAND, 5);
      mbar_init(bars + 8 * (BAR_LAND + 1), 5);
      asm volatile("fence.mbarrier_init.release.cluster;\n" ::: "memory");
    } else if (tid == 320) {
#pragma unroll
      for (int i = 0; i < NS2; i++) {
        mbar_init(bars + 8 * (BAR_FULL2 + i), 1);
        mbar_init(bars + 8 * (BAR_EMPTY2 + i), 2);
        mbar_init(bars + 8 * (BAR_EMPTY2B + i), 2);
      }
      asm volatile("fence.mbarrier_init.release.cluster;\n" ::: "memory");
    } else if (tid == 352) {
#pragma unroll
      for (int i = 0; i < 4; i++) mbar_init(bars + 8 * (BAR_Y + i), i < 2 ? 4 : i == 2 ? 10 : 8);
      mbar_init(bars + 8 * BAR_XFREE, 1);
#pragma unroll
      for (int i = 0; i < 9; i++) mbar_init(bars + 8 * (BAR_KH + i), 1);
      asm volatile("fence.mbarrier_init.release.cluster;\n" ::: "memory");
    }
    __syncwarp();
    cluster_sync_all();
    if (warp == 8) PROF2(24);
    const int hw = warp - 8;
    const int lr = lane & 7, lm = lane >> 3;
    auto g1_issue_a = [&](int j, int s) {
      const uint32_t fb = bars + 8 * (BAR_FULLA + s);
      mbar_expect_tx(fb, STG1A);
      tma_load_3d_mc(sb + s * STG1A + rank * 16384, &tmX, fb, j * 64, par, gidx * 256 + rank * 128);
    };
    auto g1_issue_b = [&](int kb, int s) {
      const uint32_t fb = bars + 8 * (BAR_FULLB + s);
      mbar_expect_tx(fb, STG1B);
      tma_load_3d(sb + OFF_1B + s * STG1B, &tmW, fb, hp * 64, kb * 32, 0);
    };
    auto g2_k = [&](int kb) { return (kb < 2 ? hp : kb < 4 ? hp & 14 : hp & 12) ^ kb; };
    auto g2_issue_b = [&](uint32_t fb, uint32_t bytes, uint32_t dst, int k0, bool whole) {
      if (whole) {
        tma_load_3d(dst, &tmWo, fb, 0, k0, cb2 * 2);
      } else {
#pragma unroll
        for (int i = 0; i < 4; i++)
          tma_load_3d(dst + (i & 1) * XT + (i >> 1) * 4 * XT, &tmWp, fb, 0, k0 + (i >> 1) * 32, cb2 * 2 + (i & 1));
      }
      mbar_expect_tx(fb, bytes);
    };
    auto send_y = [&](uint32_t o, uint32_t step, int half, auto read) {
      const uint32_t peer = mapa(sb, rank ^ 1);
      o += OFF_X + (rank ^ 1) * 4096 + half * 2048 + lane * 16;
      uint4 a[8];
      uint32_t z = p.zero;
#pragma unroll
      for (int i = 0; i < 8; i++) {
        a[i] = lds128(sb + o + (i >> 2) * step + (i & 2) * (XT / 2) + (i & 1) * 512);
        z &= a[i].x;
      }
      read(z);
#pragma unroll
      for (int i = 0; i < 8; i++)
        st_async128(peer + o + 1024 + (i >> 2) * step + (i & 2) * (XT / 2) + (i & 1) * 512,
                    peer + OFF_BAR + 8 * (BAR_LAND + half), a[i].x, a[i].y, a[i].z, a[i].w);
    };

    if (halo_cta) {
      if (hw == 0) {
        int s = 1, ph = 1;
#pragma unroll 1
        for (int n = 1; n < 32; n++) {
          mbar_wait(bars + 8 * (BAR_EMPTYB + s), ph);
          if (elect_one()) halo_issue(n, s);
          if (++s == NS1B) { s = 0; ph ^= 1; }
        }
      }
      __syncwarp();
    } else if (hw == 0) {
      uint32_t epoch = 0;
      if (MODE == 2) {
        if (lane < NS2) mbar_arrive_cluster_n(mapa(bars, rank) + 8 * (BAR_EMPTY2 + lane), 2);
      } else {
      if (lane == 0) {
        mbar_expect_tx(bars + 8 * BAR_U, 32768);
        mbar_expect_tx(bars + 8 * BAR_LAND, 8192);
        mbar_expect_tx(bars + 8 * (BAR_LAND + 1), 8192);
        mbar_expect_tx(bars + 8 * BAR_Q, 32768);
        prefetch_tmap(&tmQ);
      }
      {
        int sa = 2, pha = 1, sbb = 3, phb = 1;
#pragma unroll 1
        for (int kb = 3; kb < 32; kb++) {
          if (!(kb & 1)) {
            mbar_wait(bars + 8 * (BAR_EMPTYA + sa), pha);
            if (elect_one()) g1_issue_a(kb >> 1, sa);
            if (++sa == NS1A) { sa = 0; pha ^= 1; }
          }
          mbar_wait(bars + 8 * (BAR_EMPTYB + sbb), phb);
          if (elect_one()) g1_issue_b(kb, sbb);
          __syncwarp();
          if (kb == 4) epoch = ld_relaxed(g_flag_o + FS * cta);
          if (kb == 4) PROF2(27);
          if (++sbb == NS1B) { sbb = 0; phb ^= 1; }
        }
      }
      auto q_issue = [&](int i) {
        mbar_wait(bars + 8 * (i ? BAR_EMPTYB + 3 : BAR_EMPTYA + 1), i);
        if (elect_one())
          asm volatile(
              "cp.async.bulk.tensor.5d.shared::cluster.global.mbarrier::complete_tx::bytes [%0], [%1, {%3, %4, %4, %4, %5}], [%2];\n"
              ::"r"(sb + (i ? OFF_Q1 : OFF_Q0)), "l"(&tmQ), "r"(bars + 8 * BAR_Q), "r"((chb & ~1) * 8), "r"(0), "r"(rank * 32 + i * 64)
              : "memory");
        __syncwarp();
      };
      epoch++;
      if (lane == 0) {
        asm volatile("st.shared.u32 [%0], %1;\n" ::"r"(sb + OFF_EX - 4), "r"(epoch) : "memory");
        prefetch_tmap(&tmWo);
        prefetch_tmap(&tmWp);
        prefetch_tmap(&tmOb);
      }
      __syncwarp();
      {
        uint4 h[6] = {};
        if (gidx != 0) {
#pragma unroll 1
          for (int n = 0; n < SPIN_LIMIT; n++) {
            bool ok = true;
#pragma unroll
            for (int i = 0; i < 6; i++) h[i] = ld_b128(g_halo + cta * 192 + i * 32 + lane);
#pragma unroll
            for (int i = 0; i < 6; i++) ok = ok && h[i].w == epoch;
            if (__all_sync(0xffffffffu, ok)) break;
          }
          PROF(18);
        }
        q_issue(0);
        sts128(sb + OFF_KH + lane * 16, h[0].x, h[0].y, h[0].z, h[1].x);
        sts128(sb + OFF_KH + 512 + lane * 16, h[1].y, h[1].z, h[2].x, h[2].y);
        sts64(sb + OFF_KH + 1024 + lane * 8, h[3].x, h[3].y);
        sts64(sb + OFF_KH + 1280 + lane * 8, h[3].z, h[4].x);
        sts64(sb + OFF_KH + 1536 + lane * 8, h[4].y, h[4].z);
        sts64(sb + OFF_KH + 1792 + lane * 8, h[5].x, h[5].y);
        __syncwarp();
        if (lane == 0) mbar_arrive(bars + 8 * BAR_KH);
      }
      q_issue(1);
      const uint32_t rb = mapa(bars, lane & 1);
      nb_sync(NB_OREADY, 288);
      if (lane == 0) {
        asm volatile("cp.async.bulk.global.shared::cta.bulk_group [%0], [%1], %2;\n" ::"l"(g_o + (size_t)cta * 16384),
                     "r"(sb + OFF_OP), "r"(32768) : "memory");
        bulk_commit();
      }
      if (lane < 2) {
#pragma unroll
        for (int i = 0; i < 4; i++) mbar_arrive_cluster(rb + 8 * (BAR_EMPTY2 + i + i / 2));
      }
      if (lane == 0) {
        bulk_wait0();
        asm volatile("fence.acq_rel.gpu;\nst.relaxed.gpu.global.u32 [%0], %1;\n"
                     "mbarrier.arrive.relaxed.cluster.shared::cluster.b64 _, [%2];\n"
                     "mbarrier.arrive.relaxed.cluster.shared::cluster.b64 _, [%3];\n"
                     ::"l"(g_flag_o + FS * cta), "r"(epoch), "r"(mapa(bars, rank ^ 1) + 8 * (BAR_EMPTY2 + 2)),
                     "r"(mapa(bars, rank) + 8 * (BAR_EMPTY2 + 2)) : "memory");
      }
      __syncwarp();
      PROF2(17);
      }
      if (MODE != 1) {
        const __nv_bfloat16* osrc = g_o + (size_t)(rb2 >> 1) * 16 * 16384 + hsel * 8192;
        if (elect_one()) {
          if (MODE != 0) bulk_load(sb + g2_a(0, hsel), osrc + hp * 16384, 16384, bars + 8 * BAR_FULL2);
#pragma unroll
          for (int kb = 1; kb < 3; kb++)
            g2_issue_b(bars + 8 * (BAR_FULL2 + kb), STG2, sb + g2_b(kb, 0), g2_k(kb) * 64, true);
        }
        mbar_wait(bars + 8 * (BAR_EMPTY2 + 2), 0);
        asm volatile("{\n.reg .pred p;\nmbarrier.test_wait.parity.acquire.cluster.shared::cta.b64 p, [%0], 0;\n}\n"
                     ::"r"(bars + 8 * (BAR_EMPTY2 + 2)) : "memory");
        fence_async_all();
        if (elect_one()) bulk_load(sb + g2_a(1, hsel), osrc + (hp ^ 1) * 16384, 16384, bars + 8 * (BAR_FULL2 + 1));
        __syncwarp();
      }
      if (MODE != 2) {
        mbar_wait(bars + 8 * (BAR_Y + 2), 0);
        send_y(0, 4 * XT, 1, [&](uint32_t) {
          fence_async_smem();
          __syncwarp();
          if (MODE == 0 && elect_one()) g2_issue_b(bars + 8 * (BAR_FULL2 + 3), STG2, sb + g2_b(3, rank), g2_k(3) * 64, false);
          __syncwarp();
        });
      }
      if (MODE != 1) {
        constexpr int K0 = MODE ? 3 : 4;
        int s = K0, k0 = g2_k(K0) * 64;
        uint32_t wbar = bars + 8 * BAR_XFREE, fb = bars + 8 * (BAR_FULL2 + K0), dst = sb + g2_b(K0, rank), ph = MODE ? 1 : 0;
        int whole = 0;
#pragma unroll 1
        for (int kb = K0; kb < 16;) {
          mbar_wait(wbar, ph);
          if (kb == 4) fence_async_smem();
          if (elect_one()) g2_issue_b(fb, STG2, dst, k0, whole);
          __syncwarp();
          kb++;
          if (++s == NS2) { s = 0; ph = kb == 2 * NS2; }
          wbar = bars + 8 * (BAR_EMPTY2B + s);
          fb = bars + 8 * (BAR_FULL2 + s);
          dst = sb + g2_b(s, rank);
          k0 = ((hp & 12) ^ kb) * 64;
          whole = s < 3;
          asm volatile("" : "+r"(fb), "+r"(k0), "+r"(whole));
        }
      }
      __syncwarp();
    } else {
      if (MODE != 2) {
      const float dall = __bfloat162float(p.ssm_D[chb * 8 + lr]);
      {
        const int g = lane >> 2, t = lane & 3;
        uint32_t w[2][4];
#pragma unroll
        for (int h = 0; h < 2; h++) {
          const uint2 x = __ldg(reinterpret_cast<const uint2*>(p.shift_k + ((chb & ~1) * 8 + h * 8 + g) * 4));
          w[h][0] = __byte_perm(x.x, x.x, 0x1010);
          w[h][1] = __byte_perm(x.x, x.x, 0x3232);
          w[h][2] = __byte_perm(x.y, x.y, 0x1010);
          w[h][3] = __byte_perm(x.y, x.y, 0x3232);
        }
        auto swz = [](int r) { return (((r & 29) | ((r ^ (r >> 2)) & 2)) << 5) | (r & 16); };
        const uint32_t kring = sb + OFF_X + 4096 + (hw - 1) * 2 * XT, vring = kring + XT;
        const int s0 = rank * 32 + (hw - 1) * 11, s1 = hw == 3 ? rank * 32 + 32 : s0 + 11;
        const size_t goff = (size_t)(s0 * 32 + (lane >> 1)) * DM + (chb & ~1) * 8 + (lane & 1) * 8;
        const __nv_bfloat16* kg = p.k + goff;
        const __nv_bfloat16* vg = p.v + goff;
        const uint32_t d0 = swz(lane >> 1) ^ ((lane & 1) << 4), d1 = swz(16 + (lane >> 1)) ^ ((lane & 1) << 4);
        auto issue = [&](int st) {
          const uint32_t a = kring + ((st & 3) << 10);
          asm volatile("cp.async.cg.shared.global.L2::256B [%0], [%2], 16;\n"
                       "cp.async.cg.shared.global.L2::256B [%1], [%2 + 32768], 16;\n"
                       "cp.async.cg.shared.global.L2::256B [%0 + 8192], [%3], 16;\n"
                       "cp.async.cg.shared.global.L2::256B [%1 + 8192], [%3 + 32768], 16;\n"
                       ::"r"(a + d0), "r"(a + d1), "l"(kg), "l"(vg) : "memory");
          kg += 32 * DM;
          vg += 32 * DM;
          asm volatile("" : "+l"(kg), "+l"(vg));
        };
        const int xa = 8 * (lr >> 1) + 2 * lm + (lr & 1), xb = 8 * (lr >> 1) - 4 + 2 * (lm & 1) + (lr & 1);
        const uint32_t la = swz(xa), lb = swz(xb & 31);
        const int backb = xb < 0 ? 1 : 0;
        const uint32_t ud[2] = {mapa(sb + OFF_X + g * XT + t * 16, 0), mapa(sb + OFF_X + g * XT + t * 16, 1)};
        const uint32_t ub[2] = {mapa(bars + 8 * BAR_U, 0), mapa(bars + 8 * BAR_U, 1)};
        if (tid == 320) prefetch_l2(g_tab + (chb & 63) * 32);
        if (lane == 0) mbar_wait(bars + 8 * (BAR_FULLB + NS1B - 1), 0);
        __syncwarp();
        if (lane >= 24) cp_async16(kring + (((s0 - 1) & 3) << 10) + d1, s0 > 0 ? kg - 16 * DM : kg, s0 > 0 ? 16 : 0);
        issue(s0);
        asm volatile("cp.async.commit_group;\n" ::: "memory");
        issue(s0 + 1);
        asm volatile("cp.async.commit_group;\n" ::: "memory");
        const __nv_bfloat16* hg = p.ssm_k + (size_t)chb * 8 * SEQ + lane * 64;
        uint32_t tn = clock32();
#pragma unroll 1
        for (int st = s0; st < s1; st++) {
          tn += PSTEP;
          while ((int)(clock32() - tn) < 0) __nanosleep(100);
          if (st + 2 < s1) issue(st + 2);
          if (hw == 1 && st - s0 < 8) prefetch_l2(hg);
          hg += SEQ;
          asm volatile("" : "+l"(hg));
          asm volatile("cp.async.commit_group;\n" ::: "memory");
          asm volatile("cp.async.wait_group 2;\n" ::: "memory");
          __syncwarp();
#pragma unroll
          for (int h = 0; h < 2; h++) {
            uint32_t e[6], vv[4], e4[4];
            ldsm4t(e4, kring + ((st & 3) << 10) + (la ^ (h << 4)));
            ldsm2t(e[0], e[1], kring + (((st - backb) & 3) << 10) + (lb ^ (h << 4)));
            ldsm4t(vv, vring + ((st & 3) << 10) + (la ^ (h << 4)));
            e[2] = e4[0]; e[3] = e4[1]; e[4] = e4[2]; e[5] = e4[3];
            uint32_t o[5];
#pragma unroll
            for (int i = 0; i < 5; i++) o[i] = __byte_perm(e[i], e[i + 1], 0x5432);
#pragma unroll
            for (int i = 0; i < 4; i++) {
              uint32_t a = bmul2(o[i], w[h][3]);
              a = bfma2(e[i + 1], w[h][2], a);
              a = bfma2(o[i + 1], w[h][1], a);
              a = bfma2(e[i + 2], w[h][0], a);
              vv[i] = bmul2(a, vv[i]);
            }
            st_async128(ud[h] + (st ^ (g & 1)) * 64, ub[h], vv[0], vv[1], vv[2], vv[3]);
          }
          __syncwarp();
        }
        fence_async_smem();
        PROF(16);
      }
      nb_sync(NB_HELP3, 96);
      if (hw == 1 && elect_one()) {
        mbar_expect_tx(bars + 8 * BAR_H, 8 * 4096 + 6144);
#pragma unroll 1
        for (int c = 0; c < 8; c++)
          bulk_load(sb + OFF_X + c * XT + 4096, p.ssm_k + (size_t)(chb * 8 + c) * SEQ, 4096, bars + 8 * BAR_H);
        bulk_load(sb + OFF_T16, g_tab, 2048, bars + 8 * BAR_H);
        bulk_load(sb + OFF_T32, g_tab + 512, 4096, bars + 8 * BAR_H);
      }
      __syncwarp();
      {
        if (hw == 3) {
          const char* wo = (const char*)p.wo + chb * 16384 + lane * 128;
#pragma unroll
          for (int i = 0; i < 4; i++) prefetch_l2(wo + i * 4096);
        }
        const int ck = 16 * (lane >> 4) + 2 * lr + (((lane >> 3) ^ (lane >> 2)) & 1);
        const uint32_t xo = (ck >> 1) * 64, xs = ((ck & 1) ^ (lr >> 1)) << 4;
#pragma unroll 1
        for (int job = hw - 1; job < 16; job += 3) {
          const int c = job & 7;
          uint4 a[8];
          float dv = __shfl_sync(0xffffffffu, dall, c);
          if (job < 8 || lane) dv = 0.f;
          const uint32_t xt = sb + OFF_X + c * XT + (job >> 3) * 4096;
          mbar_wait(bars + 8 * (job < 8 ? BAR_U : BAR_H), 0);
#pragma unroll
          for (int i = 0; i < 8; i++) a[i] = lds128(xt + i * 512 + ((ck ^ (job < 8 ? (c & 1) << 2 : 0)) << 4));
          dv += bf_lo(a[0].x);
          uint32_t m[2] = {bmaxabs2(pack_bf16(dv, 0.f), bmaxabs2(a[0].x, a[0].y)), bmaxabs2(a[0].z, a[0].w)};
#pragma unroll
          for (int i = 1; i < 8; i++) {
            m[0] = bmaxabs2(bmaxabs2(m[0], a[i].x), a[i].y);
            m[1] = bmaxabs2(bmaxabs2(m[1], a[i].z), a[i].w);
          }
          m[0] = bmaxabs2(m[0], m[1]);
          const int f = max(252 - (int)(__reduce_max_sync(0xffffffffu, max(m[0] & 0x7fffu, (m[0] >> 16) & 0x7fffu)) >> 7), 1);
          if (lane == 0) asm volatile("st.shared.u32 [%0], %1;\n" ::"r"(sb + OFF_EX + job * 4), "r"(f) : "memory");
          if (f < 113) {
#pragma unroll
            for (int i = 0; i < 8; i++)
              a[i] = make_uint4(bmul2(a[i].x, f * 0x00800080u), bmul2(a[i].y, f * 0x00800080u), bmul2(a[i].z, f * 0x00800080u),
                                bmul2(a[i].w, f * 0x00800080u));
          }
          const uint32_t mul = (f < 113 ? 15 : f - 112) * 0x00800080u;
          auto cv = [&](uint32_t x) {
            x = bmul2(x, mul);
            return (x & 0x0fff0fffu) * 7 + x;
          };
          const uint32_t dst = xt + xo;
#pragma unroll
          for (int i = 0; i < 8; i++)
            sts128(dst + (i >> 2) * 2048 + (i & 1) * 1024 + (xs ^ ((i & 2) << 4)),
                   i ? cv(a[i].x) : __byte_perm(pack_f16(dv * __uint_as_float(f << 23), 0.f), cv(a[i].x), 0x7610), cv(a[i].y),
                   cv(a[i].z), cv(a[i].w));
        }
        fence_async_smem();
        __syncwarp();
        if (lane == 0) mbar_arrive(bars + 8 * BAR_X);
        PROF(19);
      }
      if (hw < 3) {
        int lane, lr, lm;
        asm volatile("mov.u32 %0, %%laneid;\n" : "=r"(lane));
        lr = lane & 7;
        lm = lane >> 3;
#pragma unroll 1
        for (int n = 0; n < SPIN_LIMIT && !mbar_try(bars + 8 * (BAR_Y + hw - 1), 0); n++) __nanosleep(100);
        send_y((hw - 1) * 4 * XT, 2 * XT, 0, [](uint32_t) {});
        __syncwarp();
        if (lane == 0) mbar_arrive(bars + 8 * (BAR_Y + 2));
        PROF(32);
        const int c8 = 2 * lm + (lr & 1), src = (lr >> 1) & 1;
        uint32_t fa = sb + OFF_X + c8 * XT + rank * 4096 + (src == rank ? 0 : 1024) + (hw - 1) * 512;
        const uint32_t fx = ((lr >> 2) ^ ((lr & 3) << 1)) << 4;
        uint32_t qa = sb + OFF_Q0 + (hw - 1) * 8192 + (lane >> 3) * 128 + (lane & 2) * 32 + (lane & 4) * 8 + (lane & 1) * 16;
        uint4* og = reinterpret_cast<uint4*>(p.out + (size_t)(rank * 512 + (hw - 1) * 256 + (lane & 2) * 4 + (lane >> 2)) * (2 * DM) +
                                             (chb & ~1) * 8 + (lane & 1) * 8);
        mbar_wait(bars + 8 * BAR_Q, 0);
        uint32_t tn = 0;
        const uint32_t pace = hw == 2 ? FPACE2 : FPACE;
#pragma unroll 1
        for (int j = 0; j < 4; j++) {
          if (!(j & 1)) {
            mbar_wait(bars + 8 * (BAR_LAND + (j >> 1)), 0);
            tn = clock32() + (j ? 0 : (hw - 1) * (FPACE / 2));
            PROF2(33 + j * 2);
          }
#pragma unroll
          for (int i = 0; i < 8; i++) {
            if (i == 3 && j == 0 && hw == 2) {
              mbar_wait(bars + 8 * (BAR_Y + 3), 0);
              send_y(2 * XT, 4 * XT, 1, [&](uint32_t z) {
                __syncwarp();
                if (lane == 0) mbar_arrive(bars + 8 * BAR_XFREE + z);
              });
              tn = clock32();
            }
            uint32_t y[4];
            const uint4 q = lds128(qa + i * 512);
            ldsm4t(y, fa + (i >> 2) * 128 + (fx ^ ((i & 3) << 5) ^ ((i >> 2) << 4)));
            while ((int)(clock32() - tn) < 0) __nanosleep(50);
            tn += j == 3 ? FPACE3 : pace;
            og[i * 16 * (2 * DM / 8)] = make_uint4(bmul2(q.x, y[0]), bmul2(q.y, y[1]), bmul2(q.z, y[2]), bmul2(q.w, y[3]));
          }
          qa += j & 1 ? OFF_Q1 - OFF_Q0 - 4096 : 4096;
          fa += j & 1 ? 2048 - 256 : 256;
          og += (j & 1 ? 1024 - 128 : 128) * (2 * DM / 8);
        }
        PROF(22);
      }
      }
      if (MODE != 1 && hw == 3) {
        if (MODE == 0) nb_sync(NB_G1END, 288);
        if (elect_one()) g2_issue_b(bars + 8 * BAR_FULL2, MODE ? STG2 : STG2 / 2, sb + g2_b(0, 0), hp * 64, true);
        __syncwarp();
        const __nv_bfloat16* osrc = g_o + (size_t)(rb2 >> 1) * 16 * 16384 + hsel * 8192;
        if (MODE == 0) __nanosleep(1500);
        mbar_wait(bars + 8 * (BAR_EMPTY2 + 2), 0);
        const uint32_t epoch = lds32(sb + OFF_EX - 4);
        const uint32_t* flag = g_flag_o + FS * ((rb2 >> 1) * 16 + g2_k(lane & 15));
        uint32_t ready = MODE == 0 ? 0u : ~0u;
        int s = 1, ph = 0;
#pragma unroll 1
        for (int kb = 2; kb < 16; kb++) {
          if (++s == NS2) { s = 0; ph ^= 1; }
          uint32_t fb = bars + 8 * (BAR_FULL2 + s), dst = sb + g2_a(s, hsel) + rank * 8192;
          const __nv_bfloat16* src = osrc + rank * 4096 + (uint32_t)g2_k(kb) * 16384;
          asm volatile("" : "+r"(fb), "+r"(dst), "+l"(src));
          if (!(ready >> kb & 1)) {
#pragma unroll 1
            for (int n = 0; n < SPIN_LIMIT && !(ready >> kb & 1); n++)
              ready = __ballot_sync(0xffffffffu, ld_acquire(flag) == epoch);
            fence_async_all();
          }
          if (kb == 2) PROF(21);
          if (MODE == 0 && kb == 4 && rank == 1) mbar_wait(bars + 8 * BAR_TAB, 0);
          mbar_wait(fb + 8 * (BAR_EMPTY2 - BAR_FULL2), ph);
          if (elect_one()) {
            asm volatile(
                "cp.async.bulk.shared::cluster.global.mbarrier::complete_tx::bytes.multicast::cluster [%0], [%1], %2, [%3], %4;\n"
                ::"r"(dst), "l"(src), "r"(8192), "r"(fb), "h"((uint16_t)3) : "memory");
          }
          __syncwarp();
        }
      }
    }
    cluster_sync_all();
    PROF_DUMP();
  } else {
    asm volatile("barrier.cluster.arrive.relaxed.aligned;\n" ::: "memory");
    asm volatile("setmaxnreg.inc.sync.aligned.u32 %0;\n" :: "n"(REG_MATH));
    if (halo_cta || MODE == 2) asm volatile("barrier.cluster.wait.aligned;\n" ::: "memory");
    if (warp == 0) PROF2(26);
    const int wg = warp >> 2;
    const int wtid = tid & 127;
    const bool signaller = (wtid == 0) || (wtid == 32);
    const uint32_t rbars = mapa(bars, wtid >> 5 & 1);

    if (halo_cta) {
      const uint32_t epoch = ld_relaxed(g_flag_o + FS * (16 + blockIdx.x * 4)) + 1;
      float acc0[64], acc1[64];
      int s = wg, ph = 0;
#pragma unroll 1
      for (int kb = 0; kb < 16; kb++) {
        mbar_wait(bars + 8 * ((wg ? BAR_FULL2 : BAR_FULLB) + s), ph);
        const uint32_t st = sb + s * STGH;
        const uint64_t da = mkdesc(st, 16, 1024, 1);
        const uint64_t db = mkdesc(st + 8192, 8192, 1024, 1);
        wg_fence();
#pragma unroll
        for (int kk = 0; kk < 4; kk++) {
          wgmma_n128(acc0, da + 2 * kk, db + 128 * kk, kb + kk);
          wgmma_n128(acc1, da + 2 * kk, db + 1024 + 128 * kk, kb + kk);
        }
        wg_commit();
        wg_wait<0>();
        if (kb == 15) PROF(37);
        if (wtid < 2) mbar_arrive(bars + 8 * (BAR_EMPTYB + s));
        if ((s += 2) >= NS1B) s -= NS1B;
        if (s == wg) ph ^= 1;
      }
      fence_regs(acc0);
      fence_regs(acc1);
      if ((warp & 3) != 3) {
        auto put = [&](const float (&acc)[64], int hp0) {
#pragma unroll
          for (int n = 0; n < 4; n++) {
            uint32_t x[8];
#pragma unroll
            for (int c = 0; c < 8; c++) {
              x[c] = pack_bf16(acc[32 * (n >> 1) + 4 * c + 2 * (n & 1)], acc[32 * (n >> 1) + 4 * c + 2 * (n & 1) + 1]);
              if (wg) x[c] = movm(x[c]);
            }
            uint4* dst = g_halo + (((n & 1) * 4 + (warp & 3) + 1) * 16 + blockIdx.x * 4 + hp0 + (n >> 1)) * 192 + wg * 96 + lane;
            st_b128(dst, x[0], x[1], x[2], epoch);
            st_b128(dst + 32, x[3], x[4], x[5], epoch);
            st_b128(dst + 64, x[6], x[7], 0, epoch);
          }
        };
        put(acc0, 0);
        put(acc1, 2);
      }
      PROF(36);
      cluster_sync_all();
      return;
    }

    float acc[64];
    const uint32_t g2rel = wtid ? mapa(bars, rank) + 8 * BAR_EMPTY2B : mapa(bars, wg) + 8 * BAR_EMPTY2;
    uint32_t g2a = (uint32_t)mkdesc(sb + wg * 8192, 16, 0, 0), g2b = (uint32_t)mkdesc(sb, 8192, 0, 0);
    auto g2_block = [&](bool first, int s, int ph) {
      mbar_wait(bars + 8 * (BAR_FULL2 + s), ph);
      const uint32_t da = g2a + (g2_a(s, hsel) >> 4), db = g2b + (g2_b(s, rank) >> 4), dc = db + (g2_bk(s) >> 4);
      wg_fence();
      if (first) wgmma_n128z(acc, da, db);
      else wgmma_n128a(acc, da, db);
      wgmma_n128a(acc, da + 2, db + 128);
      wgmma_n128a(acc, da + 4, dc);
      wgmma_n128a(acc, da + 6, dc + 128);
      wg_commit();
    };
    if (MODE != 2) {
    uint32_t a1[2][4], sc[2];
    C2 t[2];
    {
      float acc0[96], acc1[96];
      int sa = 0, pha = 0;
      uint64_t db0 = mkdesc(sb + OFF_1B, 4096, 1024, 1);
      const uint64_t da0 = mkdesc(sb + wg * 16384, 16, 2048, 1);
      const bool sigb = wtid == 64;
      uint32_t rela = 0;
#pragma unroll 1
      for (int r = 0; r < 3; r++) {
#pragma unroll
        for (int i = 0; i < 2 * NS1B; i++) {
          if (i == 2 * NS1B - 1 && r == 2) break;
          const uint64_t da = da0 + sa * (STG1A >> 4) + (i & 1) * 4, db = db0 + (i % NS1B) * (STG1B >> 4);
          if (i || r) {
            if (!(i & 1)) mbar_wait(bars + 8 * (BAR_FULLA + sa), pha);
            mbar_wait(bars + 8 * (BAR_FULLB + i % NS1B), i / NS1B);
          } else {
            asm volatile("cp.async.wait_group 0;\n" ::: "memory");
            fence_async_smem();
            nb_sync(NB_FIRST, 256);
            PROF(0 + wg);
          }
          wg_fence();
          wgmma_n192(acc0, da + 64, db, i ? 1 : r);
          wgmma_n192(acc1, da, db, i ? 1 : r);
          wgmma_n192(acc0, da + 66, db + 128, 1);
          wgmma_n192(acc1, da + 2, db + 128, 1);
          wg_commit();
          wg_wait<1>();
          if (i || r) {
            if (sigb) mbar_arrive(bars + 8 * (BAR_EMPTYB + (i + NS1B - 1) % NS1B));
            if (!(i & 1) && signaller) mbar_arrive_cluster(rela);
          } else {
            asm volatile("barrier.cluster.wait.aligned;\n" ::: "memory");
          }
          if (i & 1) {
            rela = rbars + 8 * (BAR_EMPTYA + sa);
            if (++sa == NS1A) { sa = 0; pha ^= 1; }
          }
        }
        db0 += p.zero;
      }
      const int lr = lane & 7, lm = lane >> 3;
      const bool le0 = 2 * (lane & 3) <= (lane >> 2), le1 = 2 * (lane & 3) + 1 <= (lane >> 2);
      const uint32_t maskLE = (le0 ? 0x0000FFFFu : 0u) | (le1 ? 0xFFFF0000u : 0u);
      uint32_t q[4][8], k[5][8], vt[5][8];
      {
        static_assert(15 % NS1A == 0 && 30 % NS1B == 0, "slots of the last k blocks");
        const uint64_t da = mkdesc(sb + wg * 16384, 16, 2048, 1);
        const uint64_t db = mkdesc(sb + OFF_1B, 4096, 1024, 1);
        auto last = [&](float (&acc)[96], int ro, int i0, int i1) {
#pragma unroll
          for (int i = i0; i < i1; i++)
            wgmma_n192(acc, da + ro + (i < 2 ? 2 * (STG1A >> 4) + 4 + 2 * i : 2 * i - 4),
                       db + (i < 2 ? 4 : (i >> 1) - 1) * (STG1B >> 4) + (i & 1) * 128, 1);
          wg_commit();
        };
        mbar_wait(bars + 8 * (BAR_FULLB + 4), 1);
        wg_fence();
        last(acc0, 64, 0, 2);
        asm volatile("ld.volatile.global.v4.u32 {%0,%1,%2,%3}, [%4];\n"
                     : "=r"(t[0].r), "=r"(t[1].r), "=r"(t[0].i), "=r"(t[1].i) : "l"(g_tab + 1536 + wtid * 4) : "memory");
        mbar_wait(bars + 8 * BAR_FULLA, 1);
        mbar_wait(bars + 8 * BAR_FULLB, 0);
        mbar_wait(bars + 8 * (BAR_FULLB + 1), 0);
        wg_fence();
        last(acc0, 64, 2, 6);
        wg_wait<2>();
        if (sigb) mbar_arrive(bars + 8 * (BAR_EMPTYB + 3));
        mbar_wait(bars + 8 * (BAR_EMPTYA + 1), 0);
        mbar_wait(bars + 8 * BAR_H, 0);
        wg_fence();
        last(acc1, 0, 0, 4);
        wg_wait<1>();
        fence_regs(acc0);
        PROFA(45, 0);
        attn_pack<8, 1, false>(acc0, k[4]);
        attn_pack<16, 1, true>(acc0, vt[4]);
        const uint32_t kh = sb + (warp == 7 ? OFF_1B + 2 * STG1B : OFF_KH + (warp + 1) * 2048) + lane * 16;
        sts128(kh, k[4][0], k[4][1], k[4][2], k[4][3]);
        sts128(kh + 512, k[4][4], k[4][5], k[4][6], k[4][7]);
#pragma unroll
        for (int i = 0; i < 4; i++) sts64(kh - lane * 8 + 1024 + 256 * i, vt[4][2 * i], vt[4][2 * i + 1]);
        __syncwarp();
        if (lane == 0) mbar_arrive(bars + 8 * (BAR_KH + 1 + warp));
        last(acc1, 0, 4, 6);
        attn_pack<0, 0, false>(acc0, q[1]);
        attn_pack<0, 1, false>(acc0, q[3]);
        attn_pack<8, 0, false>(acc0, k[2]);
        attn_pack<16, 0, true>(acc0, vt[2]);
        uint32_t z = p.zero;
#pragma unroll
        for (int i = 0; i < 8; i++) z &= q[1][i] & q[3][i];
#pragma unroll
        for (int i = 0; i < 8; i += 2) z &= k[2][i] & k[2][i + 1];
        mbar_wait(bars + 8 * (BAR_KH + warp) + z, 0);
        {
          const uint32_t kh = sb + OFF_KH + warp * 2048 + lane * 16;
#pragma unroll
          for (int i = 0; i < 2; i++) {
            const uint4 t = lds128(kh + 512 * i);
            k[0][4 * i] = t.x; k[0][4 * i + 1] = t.y; k[0][4 * i + 2] = t.z; k[0][4 * i + 3] = t.w;
          }
#pragma unroll
          for (int i = 0; i < 4; i++) {
            const uint2 t = lds64(kh - lane * 8 + 1024 + 256 * i);
            vt[0][2 * i] = t.x; vt[0][2 * i + 1] = t.y;
          }
        }
        wg_wait<0>();
        fence_regs(acc1);
        if (MODE == 0) nb_arrive(NB_G1END, 288);
      }
      PROF(2 + wg);
      attn_pack<0, 0, false>(acc1, q[0]);
      attn_pack<0, 1, false>(acc1, q[2]);
      attn_pack<8, 0, false>(acc1, k[1]);
      attn_pack<8, 1, false>(acc1, k[3]);
      {
        float x[8][2];
        uint32_t pp[8];
        const bool first = warp == 0 && gidx == 0;
#pragma unroll
        for (int hd = 0; hd < 2; hd++) {
#pragma unroll
          for (int j = 0; j < 4; j += 2) {
            float s0[4], s1[4], s2[4];
            attn_qk(s2, q[j], q[j + 1], k[j + 2], 4 * hd);
            attn_qk(s1, q[j], q[j + 1], k[j + 1], 4 * hd);
            attn_qk(s0, q[j], q[j + 1], k[j], 4 * hd);
            if (j == 0 && first) s0[0] = s0[1] = -1e9f / 0.17677669529663687f;
            x[2 * j + hd][0] = le0 ? s1[0] : s0[0];
            x[2 * j + hd][1] = le1 ? s1[1] : s0[1];
            x[2 * j + 2 + hd][0] = le0 ? s2[2] : s1[2];
            x[2 * j + 2 + hd][1] = le1 ? s2[3] : s1[3];
          }
        }
        PROFA(40, __float_as_uint(x[1][0] + x[7][1]));
        attn_pack<16, 0, true>(acc1, vt[1]);
        attn_pack<16, 1, true>(acc1, vt[3]);
        quad_softmax<8>(x, pp);
        PROFA(41, pp[1] + pp[7]);
        ldsm4(a1[0], sb + OFF_T32 + (warp & 3) * 1024 + lane * 16);
        ldsm4(a1[1], sb + OFF_T32 + 512 + (warp & 3) * 1024 + lane * 16);
        const uint32_t obase = sb + OFF_OP + (warp * 32 + lr) * 128;
#pragma unroll
        for (int n = 0; n < 8; n++) {
          const uint32_t dst = obase + (n >> 1) * 1024 + (((4 * (n & 1) + lm) ^ lr) << 4);
          if (n & 2) attn_pv<true>(dst, vt[n >> 1], vt[(n >> 1) + 1], 4 * (n & 1), pp[n], maskLE);
          else attn_pv<false>(dst, vt[n >> 1], vt[(n >> 1) + 1], 4 * (n & 1), pp[n], maskLE);
        }
      }
      PROFA(42, 0);
    }

    {
      const int w = warp & 3;
      const int lr = lane & 7, lm = lane >> 3;
      const uint32_t xb = sb + OFF_X + wg * 4 * XT;
      auto uo = [](int c) { return (c & 1) * 2 * XT + (c >> 1) * 2048; };
      const uint64_t dc2 = mkdesc(sb + OFF_T16, 512, 128, 0), dc3 = mkdesc(sb + OFF_T16, 128, 512, 0);
      const uint64_t dc4 = mkdesc(sb + OFF_T32, 128, 256, 0);
      const uint64_t dx = mkdesc(xb, 4096, 512, 2), dz = mkdesc(xb, 4096, 256, 3);
      const uint32_t zs = xb + (w * 16 + (lm & 1) * 8 + lr) * 32 + (((lm >> 1) ^ (lr >> 2)) << 4);
      const uint32_t ys = xb + w * 4096 + (lm >> 1) * 256 + ((lr * 32 + (((lm & 1) ^ (lr >> 2)) << 4)) ^ (rank << 6) ^ ((w & 2) << 4));
      const bool own = (w & 1) == rank;
      const uint32_t ybar = mapa(bars, own ? rank ^ 1 : rank) + 8 * BAR_Y;
      uint32_t d[2][32], pa[2][4][2][4], e[4][4][8], ya[2][2][2][4], v[2][2][8];
      C2 s1[2][2][2];
      float o[2][16];
      auto rows = [&](int c) {
        fft_rows(d[c & 1], a1, dx + (uo(c) >> 4));
        wg_commit();
      };
      auto cols = [&](int c) {
        const int s = c & 1;
        fence_regs(d[s]);
#pragma unroll
        for (int i = 0; i < 16; i++) {
          const C2 z = crot(C2{d[s][2 * i], d[s][2 * i + 1]}, t[i & 1]);
          pa[s][i >> 2][i & 1][(i >> 1) & 1] = z.r;
          pa[s][i >> 2][i & 1][2 + ((i >> 1) & 1)] = z.i;
        }
        wg_fence();
#pragma unroll
        for (int i = 0; i < 4; i++) fft_cols<0>(e[c][i], pa[s][i], dc2);
        wg_commit();
      };
      auto prod = [&](int c, int n) {
        const int s = c & 1;
        fence_regs(e[c][2 * n]);
        fence_regs(e[c][2 * n + 1]);
#pragma unroll
        for (int j = 0; j < 2; j++) {
          const C2 u0 = cget(e[s][2 * n], j, 0), u1 = cget(e[s][2 * n], j, 1);
          const C2 h0 = cget(e[s][2 * n + 1], j, 0), h1 = cget(e[s][2 * n + 1], j, 1);
          C2 y0, y1;
          if (c < 2) {
            y0 = cmul(h0, u0);
            s1[s][n][j] = cfma(h0, u1, cmul(h1, u0));
            y1 = C2{hadd2(s1[s][n][j].r, y0.i), hadd2(s1[s][n][j].i, hneg2(y0.r))};
          } else {
            const C2 u2 = cget(e[c][2 * n], j, 0), u3 = cget(e[c][2 * n], j, 1);
            const C2 h2 = cget(e[c][2 * n + 1], j, 0), h3 = cget(e[c][2 * n + 1], j, 1);
            const C2 s2 = cfma(h0, u2, cfma(h2, u0, cmul(h1, u1)));
            y0 = C2{hadd2(s2.r, s1[s][n][j].i), hadd2(s2.i, hneg2(s1[s][n][j].r))};
            y1 = cfma(h0, u3, cfma(h1, u2, cfma(h2, u1, cfma(h3, u0, C2{s2.i, hneg2(s2.r)}))));
          }
          ya[s][n][j][0] = y0.r;
          ya[s][n][j][1] = y1.r;
          ya[s][n][j][2] = y0.i;
          ya[s][n][j][3] = y1.i;
        }
      };
      auto icols = [&](int c) {
        wg_fence();
        fft_cols<1>(v[c & 1][0], ya[c & 1][0], dc3);
        fft_cols<1>(v[c & 1][1], ya[c & 1][1], dc3);
        wg_commit();
      };
      auto stage = [&](int c) {
        const int s = c & 1;
        fence_regs(v[s][0]);
        fence_regs(v[s][1]);
#pragma unroll
        for (int b = 0; b < 4; b++) {
          const C2 x0 = cget(v[s][b >> 1], 0, b & 1), x1 = cget(v[s][b >> 1], 1, b & 1);
          const C2 z0 = crot(C2{x0.i, x0.r}, t[0]), z1 = crot(C2{x1.i, x1.r}, t[1]);
          stsm4(zs + uo(c) + b * 4096, z0.i, z0.r, z1.i, z1.r);
        }
      };
      auto back = [&](int c) {
        fft_back(o[c & 1], dz + (uo(c) >> 4), dc4);
        wg_commit();
      };
      auto out = [&](int c) {
        float (&r)[16] = o[c & 1];
        fence_regs(r);
#pragma unroll
        for (int i = 0; i < 16; i += 8)
          stsm4t(ys + uo(c) + 64 * i, bmul2(pack_bf16(r[i], r[i + 1]), sc[c & 1]), bmul2(pack_bf16(r[i + 2], r[i + 3]), sc[c & 1]),
                 bmul2(pack_bf16(r[i + 4], r[i + 5]), sc[c & 1]), bmul2(pack_bf16(r[i + 6], r[i + 7]), sc[c & 1]));
      };
      auto signal = [&](int yb, int land) {
        __syncwarp();
        if (lane == 0) {
          mbar_arrive_cluster(ybar + 8 * yb);
          if (own && land >= 0) mbar_arrive(bars + 8 * (BAR_LAND + land));
        }
      };
      mbar_wait(bars + 8 * BAR_X, 0);
      wg_fence();
      rows(0);
      rows(1);
      fence_async_smem();
      nb_arrive(NB_OREADY, 288);
#pragma unroll
      for (int i = 0; i < 2; i++) {
        const uint32_t ex = sb + OFF_EX + wg * 16 + (w & 2) * 2 + 8 * i;
        sc[i] = min(max(381 - (int)lds32(ex) - (int)lds32(ex + 32), 1), 254) * 0x00800080u;
      }
      PROF(34 + wg);
      wg_wait<1>();
      cols(0);
      wg_wait<1>();
      cols(1);
      rows(2);
      nb_sync(NB_CONV + wg, 128);
      wg_wait<2>();
      prod(0, 0);
      prod(0, 1);
      icols(0);
      wg_wait<2>();
      prod(1, 0);
      prod(1, 1);
      icols(1);
      PROF3(40 + 10 * wg);
      wg_wait<1>();
      stage(0);
      wg_wait<0>();
      stage(1);
      fence_async_smem();
      cols(2);
      PROF3(41 + 10 * wg);
      nb_sync(NB_CONV + wg, 128);
      back(0);
      back(1);
      wg_wait<2>();
      prod(2, 0);
      wg_fence();
      rows(3);
      wg_wait<1>();
      out(0);
      out(1);
      signal(wg, 0);
      PROF3(42 + 10 * wg);
      prod(2, 1);
      icols(2);
      wg_wait<1>();
      cols(3);
      PROF3(43 + 10 * wg);
      wg_wait<1>();
      stage(2);
      fence_async_smem();
      wg_wait<0>();
      prod(3, 0);
      nb_sync(NB_CONV + wg, 128);
      wg_fence();
      back(2);
      prod(3, 1);
      icols(3);
      PROF3(44 + 10 * wg);
      wg_wait<1>();
      out(2);
      signal(2, -1);
      wg_wait<0>();
      stage(3);
      PROF3(45 + 10 * wg);
      fence_async_smem();
      nb_sync(NB_FIRST, 256);
      wg_fence();
      back(3);
      constexpr int G = MODE == 0;
      if (G) {
        mbar_wait(bars + 8 * (BAR_EMPTY2 + 4), 0);
        g2_block(true, 0, 0);
      }
      wg_wait<G>();
      if (lane == 0) mbar_arrive_cluster(mapa(bars, 1) + 8 * BAR_TAB);
      out(3);
      signal(3, 1);
      PROF(6 + wg);
    }
    }

    if (MODE != 1) {
      if (MODE == 2) g2_block(true, 0, 0);
      const int lr = lane & 7, lm = lane >> 3;
      const uint32_t wb = sb + g2_a(1, 0) + warp * 2048;
      const int orow = (rb2 & 7) * 128 + warp * 16;
      uint4* og = reinterpret_cast<uint4*>(p.out + (size_t)(2 * (orow + lm) + (rb2 >> 3)) * (2 * DM) + DM + cb2 * 128 + lr * 8);
      uint32_t wst = wb + (lr + 8 * (lm & 1)) * 128, wsx = ((lm >> 1) ^ lr) << 4, wld = wb + lm * 128, wlx = (lr ^ lm) << 4;
      asm volatile("" : "+l"(og), "+r"(wst), "+r"(wsx), "+r"(wld), "+r"(wlx));
#pragma unroll 1
      for (int r = 0; r < 3; r++) {
        const bool hold = r == 2 && wg != LEADWG;
        if (hold) {
          wg_wait<0>();
          if (signaller) mbar_arrive_cluster(g2rel);
          nb_sync(NB_LEAD, 256);
        }
#pragma unroll
        for (int i = 1; i <= NS2; i++) {
          g2_block(false, i % NS2, (r & 1) ^ (i == NS2));
          if (warp == LEADWG * 4) PROF2(40 + 5 * r + i);
          if (i == 1 ? !hold : r < 2) {
            wg_wait<1>();
            if (signaller) mbar_arrive_cluster(g2rel + 8 * (i - 1));
          }
        }
        if (r == 0) PROF(8 + wg);
        g2a += p.zero;
        g2b += p.zero;
      }
      if (wg == LEADWG) nb_arrive(NB_LEAD, 256);
      asm volatile("barrier.cluster.arrive.relaxed.aligned;\n" ::: "memory");
      wg_wait<0>();
      fence_regs(acc);
      PROF(10 + wg);
#pragma unroll
      for (int h = 0; h < 2; h++) {
        const uint32_t b = h * (g2_a(3, 0) - g2_a(1, 0));
#pragma unroll
        for (int j = 8 * h; j < 8 * h + 8; j += 2)
          stsm4(wst + b + (wsx ^ ((j & 7) << 4)), pack_bf16(acc[4 * j], acc[4 * j + 1]),
                pack_bf16(acc[4 * j + 2], acc[4 * j + 3]), pack_bf16(acc[4 * j + 4], acc[4 * j + 5]),
                pack_bf16(acc[4 * j + 6], acc[4 * j + 7]));
        if (wg == LEADWG) {
          fence_async_smem();
          __syncwarp();
          if (elect_one()) {
            tma_store_3d(&tmOb, wb + b, DM + cb2 * 128 + h * 64, rb2 >> 3, orow);
            bulk_commit();
          }
        } else {
          __syncwarp();
          uint4 v[4];
#pragma unroll
          for (int i = 0; i < 4; i++) v[i] = lds128(wld + b + i * 512 + (wlx ^ ((i & 1) << 6)));
#pragma unroll
          for (int i = 0; i < 4; i++)
            asm volatile("st.global.v4.u32 [%0], {%1,%2,%3,%4};\n" ::"l"(og + i * 8 * (2 * DM / 8) + h * 8), "r"(v[i].x),
                         "r"(v[i].y), "r"(v[i].z), "r"(v[i].w) : "memory");
        }
      }
      PROF(12 + wg);
      bulk_wait0();
    } else {
      asm volatile("barrier.cluster.arrive.relaxed.aligned;\n" ::: "memory");
    }
    asm volatile("barrier.cluster.wait.aligned;\n" ::: "memory");
  }
}

typedef CUresult (*EncodeFn)(CUtensorMap*, CUtensorMapDataType, cuuint32_t, void*, const cuuint64_t*, const cuuint64_t*,
                             const cuuint32_t*, const cuuint32_t*, CUtensorMapInterleave, CUtensorMapSwizzle,
                             CUtensorMapL2promotion, CUtensorMapFloatOOBfill);

void make_map(EncodeFn enc, CUtensorMap* tm, const void* base, int rank, const cuuint64_t* dims, const cuuint64_t* strides,
              const cuuint32_t* box, CUtensorMapSwizzle swz) {
  cuuint32_t es[5] = {1, 1, 1, 1, 1};
  enc(tm, CU_TENSOR_MAP_DATA_TYPE_BFLOAT16, rank, const_cast<void*>(base), dims, strides, box, es,
      CU_TENSOR_MAP_INTERLEAVE_NONE, swz, CU_TENSOR_MAP_L2_PROMOTION_L2_256B, CU_TENSOR_MAP_FLOAT_OOB_FILL_NONE);
}

}

extern "C" void kernel_launch(void* const* d_in, const int* in_sizes, int n_in, void* d_out, int out_size) {
  static EncodeFn enc = nullptr;
  static bool coresident = true;
  if (!enc) {
    void* fn = nullptr;
    cudaDriverEntryPointQueryResult qr;
    cudaGetDriverEntryPoint("cuTensorMapEncodeTiled", &fn, cudaEnableDefault, &qr);
    enc = (EncodeFn)fn;
    cudaFuncSetAttribute(fused_kernel<0>, cudaFuncAttributeMaxDynamicSharedMemorySize, SMEM_BYTES);
    cudaFuncSetAttribute(fused_kernel<1>, cudaFuncAttributeMaxDynamicSharedMemorySize, SMEM_BYTES);
    cudaFuncSetAttribute(fused_kernel<2>, cudaFuncAttributeMaxDynamicSharedMemorySize, SMEM_BYTES);
    cudaLaunchConfig_t cfg = {};
    cfg.gridDim = dim3(NCTA);
    cfg.blockDim = dim3(NTHREADS);
    cfg.dynamicSmemBytes = SMEM_BYTES;
    cudaLaunchAttribute at;
    at.id = cudaLaunchAttributeClusterDimension;
    at.val.clusterDim.x = 2;
    at.val.clusterDim.y = 1;
    at.val.clusterDim.z = 1;
    cfg.attrs = &at;
    cfg.numAttrs = 1;
    int nclusters = 0;
    if (cudaOccupancyMaxActiveClusters(&nclusters, fused_kernel<0>, &cfg) == cudaSuccess) coresident = nclusters >= NCTA / 2;
    (void)cudaGetLastError();
  }
  CUtensorMap tmX, tmW, tmWo, tmWp, tmQ, tmOb, tmXh, tmWh;
  {
    cuuint64_t dims[3] = {1024, 2, 1024};
    cuuint64_t str[2] = {2048, 4096};
    cuuint32_t box[3] = {64, 1, 128};
    make_map(enc, &tmX, d_in[6], 3, dims, str, box, CU_TENSOR_MAP_SWIZZLE_128B);
  }
  {
    cuuint64_t dims[3] = {1024, 1024, 3};
    cuuint64_t str[2] = {6144, 2048};
    cuuint32_t box[3] = {64, 32, 3};
    make_map(enc, &tmW, d_in[7], 3, dims, str, box, CU_TENSOR_MAP_SWIZZLE_128B);
  }
  {
    cuuint64_t dims[3] = {64, 1024, 16};
    cuuint64_t str[2] = {2048, 128};
    cuuint32_t box[3] = {64, 64, 2};
    cuuint32_t piece[3] = {64, 32, 1};
    make_map(enc, &tmWo, d_in[8], 3, dims, str, box, CU_TENSOR_MAP_SWIZZLE_128B);
    make_map(enc, &tmWp, d_in[8], 3, dims, str, piece, CU_TENSOR_MAP_SWIZZLE_128B);
  }
  {
    cuuint64_t dims[5] = {1024, 2, 2, 4, 128};
    cuuint64_t str[4] = {2048, 8 * 2048, 2 * 2048, 16 * 2048};
    cuuint32_t box[5] = {16, 2, 2, 4, 32};
    make_map(enc, &tmQ, d_in[0], 5, dims, str, box, CU_TENSOR_MAP_SWIZZLE_NONE);
  }
  {
    cuuint64_t dims[3] = {2048, 2, 1024};
    cuuint64_t str[2] = {4096, 8192};
    cuuint32_t box[3] = {64, 1, 16};
    make_map(enc, &tmOb, d_out, 3, dims, str, box, CU_TENSOR_MAP_SWIZZLE_128B);
  }
  {
    cuuint64_t dims[4] = {1024, 256, 2, 4};
    cuuint64_t str[3] = {4096, 2048, 256 * 4096};
    cuuint32_t box[4] = {64, 8, 2, 3};
    make_map(enc, &tmXh, d_in[6], 4, dims, str, box, CU_TENSOR_MAP_SWIZZLE_128B);
  }
  {
    cuuint64_t dims[3] = {64, 1024, 48};
    cuuint64_t str[2] = {6144, 128};
    cuuint32_t box[3] = {64, 64, 4};
    make_map(enc, &tmWh, d_in[7], 3, dims, str, box, CU_TENSOR_MAP_SWIZZLE_128B);
  }
  Params p;
  p.q = (const __nv_bfloat16*)d_in[0];
  p.k = (const __nv_bfloat16*)d_in[1];
  p.v = (const __nv_bfloat16*)d_in[2];
  p.shift_k = (const __nv_bfloat16*)d_in[3];
  p.ssm_k = (const __nv_bfloat16*)d_in[4];
  p.ssm_D = (const __nv_bfloat16*)d_in[5];
  p.x = (const __nv_bfloat16*)d_in[6];
  p.w = (const __nv_bfloat16*)d_in[7];
  p.wo = (const __nv_bfloat16*)d_in[8];
  p.out = (__nv_bfloat16*)d_out;
  p.zero = 0;
  for (int cl = 0; cl < 72; cl++) {
    const int t = cl - 4, u = t - 32;
    const bool lo = t >= 0 && t < 32, mid = u >= 0 && u < 28;
    const int grp = lo ? t & 7 : mid ? 1 + u % 7 : 0, mem = lo ? t >> 3 : mid ? 4 + u / 7 : t < 0 ? t + 6 : t - 54;
    p.tile[cl] = (uint8_t)((((grp >> 2) * 4 + (mem >> 1)) * 8 + (grp & 3) * 2 + (mem & 1)) & 63);
  }
  if (coresident) {
    fused_kernel<0><<<NCTA, NTHREADS, SMEM_BYTES>>>(p, tmX, tmW, tmWo, tmWp, tmQ, tmOb, tmXh, tmWh);
  } else {
    fused_kernel<0><<<4, NTHREADS, SMEM_BYTES>>>(p, tmX, tmW, tmWo, tmWp, tmQ, tmOb, tmXh, tmWh);
    fused_kernel<1><<<NCTA, NTHREADS, SMEM_BYTES>>>(p, tmX, tmW, tmWo, tmWp, tmQ, tmOb, tmXh, tmWh);
    fused_kernel<2><<<NCTA, NTHREADS, SMEM_BYTES>>>(p, tmX, tmW, tmWo, tmWp, tmQ, tmOb, tmXh, tmWh);
  }
}
```

```cpp
#include <cuda_runtime.h>
#include <cuda.h>
#include <cuda_bf16.h>
#include <stdint.h>

namespace {

constexpr int SEQ = 2048;
constexpr int DM = 1024;
constexpr int NCTA = 132;
constexpr int NTHREADS = 384;

constexpr int STG1A = 32768;
constexpr int NS1A = 3;
constexpr int STG1B = 12288;
constexpr int NS1B = 5;
constexpr int OFF_1B = NS1A * STG1A;
constexpr int STG2 = 32768;
constexpr int NS2 = 5;
#define PSTEP 1250
#define FPACE 260
#define FPACE2 240
#define FPACE3 180
constexpr int LEADWG = 1;
__device__ __forceinline__ uint32_t g2_a(int s, int hsel) { return (((0x97524 >> (4 * s)) & 15) ^ (s & 5 ? 0 : hsel)) << 14; }
constexpr int OFF_Q0 = 3 << 14, OFF_Q1 = 8 << 14;
constexpr int STGH = 40960;
constexpr int OFF_KH = 1 * STG2;
constexpr int OFF_OP = 2 * STG2;
constexpr int OFF_T32 = 5 * STG2 - 4096;
constexpr int OFF_X = 5 * STG2;
constexpr int XT = 8192;
__device__ __forceinline__ uint32_t g2_b(int s, int rank) {
  return s < 3 ? (s == 2 ? 6 : s) << 14 : OFF_X + (s - 3) * 2 * XT + (rank ^ 1) * 4096;
}
__device__ __forceinline__ uint32_t g2_bk(int s) { return s < 3 ? 4096 : 4 * XT; }
constexpr int OFF_BAR = OFF_X + 8 * XT;
constexpr int OFF_EX = OFF_BAR + 960;
constexpr int OFF_T16 = 230400;
constexpr int SMEM_BYTES = OFF_T16 + 2048;
static_assert(OFF_1B + NS1B * STG1B <= OFF_T32 && OFF_X % 1024 == 0, "layout");
static_assert(NS1B == NS2 && NS1B * STGH <= OFF_BAR && OFF_EX + 64 <= OFF_T16 && SMEM_BYTES <= 232448, "smem");

constexpr int BAR_FULLA = 0;
constexpr int BAR_EMPTYA = 3;
constexpr int BAR_FULLB = 6;
constexpr int BAR_EMPTYB = 11;
constexpr int BAR_FULL2 = 16;
constexpr int BAR_EMPTY2 = 21;
constexpr int BAR_EMPTY2B = 44;
constexpr int BAR_X = 26;
constexpr int BAR_LAND = 42;
constexpr int BAR_TAB = 28;
constexpr int BAR_U = 29;
constexpr int BAR_H = 30;
constexpr int BAR_Y = 32;
constexpr int BAR_XFREE = 38;
constexpr int BAR_KH = 49;
constexpr int BAR_Q = 41;

constexpr int NB_LEAD = 2;
constexpr int NB_G1END = 3;
constexpr int NB_OREADY = 4;
constexpr int NB_CONV = 5;
constexpr int NB_HELP3 = 11;
constexpr int NB_FIRST = 13;

#define REG_MATH 224
#define REG_HELP 56
constexpr int SPIN_LIMIT = 1 << 20;

__device__ __align__(1024) __nv_bfloat16 g_o[SEQ * DM];
constexpr int FS = 2;
__device__ __align__(128) uint32_t g_flag_o[128 * FS];
__device__ uint4 g_halo[128 * 192];
__device__ __align__(128) const uint32_t g_tab[2048] = {
  0x2fd93000,0x2ea72f64,0x2c722da8,0x263e2a1f,0x2ea73000,0xa63e2a1f,0xafd9ada8,0xac72af64,0x2c723000,0xafd9aa1f,0x263eada8,0x2ea72f64,
  0x263e3000,0xac72af64,0x2ea72da8,0xafd9aa1f,0xa63e3000,0x2c72af64,0xaea72da8,0x2fd9aa1f,0xac723000,0x2fd9aa1f,0xa63eada8,0xaea72f64,
  0xaea73000,0x263e2a1f,0x2fd9ada8,0x2c72af64,0xafd93000,0xaea72f64,0xac722da8,0xa63e2a1f,0x263e0000,0x2c722a1f,0x2ea72da8,0x2fd92f64,
  0x2c720000,0x2fd92f64,0x263e2da8,0xaea7aa1f,0x2ea70000,0x263e2f64,0xafd9ada8,0x2c72aa1f,0x2fd90000,0xaea72a1f,0x2c72ada8,0xa63e2f64,
  0x2fd90000,0xaea7aa1f,0x2c722da8,0xa63eaf64,0x2ea70000,0x263eaf64,0xafd92da8,0x2c722a1f,0x2c720000,0x2fd9af64,0x263eada8,0xaea72a1f,
  0x263e0000,0x2c72aa1f,0x2ea7ada8,0x2fd9af64,0xafd93000,0xaea72f64,0xac722da8,0xa63e2a1f,0xaea73000,0x263e2a1f,0x2fd9ada8,0x2c72af64,
  0xac723000,0x2fd9aa1f,0xa63eada8,0xaea72f64,0xa63e3000,0x2c72af64,0xaea72da8,0x2fd9aa1f,0x263e3000,0xac72af64,0x2ea72da8,0xafd9aa1f,
  0x2c723000,0xafd9aa1f,0x263eada8,0x2ea72f64,0x2ea73000,0xa63e2a1f,0xafd9ada8,0xac72af64,0x2fd93000,0x2ea72f64,0x2c722da8,0x263e2a1f,
  0xa63e0000,0xac722a1f,0xaea72da8,0xafd92f64,0xac720000,0xafd92f64,0xa63e2da8,0x2ea7aa1f,0xaea70000,0xa63e2f64,0x2fd9ada8,0xac72aa1f,
  0xafd90000,0x2ea72a1f,0xac72ada8,0x263e2f64,0xafd90000,0x2ea7aa1f,0xac722da8,0x263eaf64,0xaea70000,0xa63eaf64,0x2fd92da8,0xac722a1f,
  0xac720000,0xafd9af64,0xa63eada8,0x2ea72a1f,0xa63e0000,0xac72aa1f,0xaea7ada8,0xafd9af64,0xa63e0000,0xac72aa1f,0xaea7ada8,0xafd9af64,
  0xac720000,0xafd9af64,0xa63eada8,0x2ea72a1f,0xaea70000,0xa63eaf64,0x2fd92da8,0xac722a1f,0xafd90000,0x2ea7aa1f,0xac722da8,0x263eaf64,
  0xafd90000,0x2ea72a1f,0xac72ada8,0x263e2f64,0xaea70000,0xa63e2f64,0x2fd9ada8,0xac72aa1f,0xac720000,0xafd92f64,0xa63e2da8,0x2ea7aa1f,
  0xa63e0000,0xac722a1f,0xaea72da8,0xafd92f64,0x2fd93000,0x2ea72f64,0x2c722da8,0x263e2a1f,0x2ea73000,0xa63e2a1f,0xafd9ada8,0xac72af64,
  0x2c723000,0xafd9aa1f,0x263eada8,0x2ea72f64,0x263e3000,0xac72af64,0x2ea72da8,0xafd9aa1f,0xa63e3000,0x2c72af64,0xaea72da8,0x2fd9aa1f,
  0xac723000,0x2fd9aa1f,0xa63eada8,0xaea72f64,0xaea73000,0x263e2a1f,0x2fd9ada8,0x2c72af64,0xafd93000,0xaea72f64,0xac722da8,0xa63e2a1f,
  0x263e0000,0x2c72aa1f,0x2ea7ada8,0x2fd9af64,0x2c720000,0x2fd9af64,0x263eada8,0xaea72a1f,0x2ea70000,0x263eaf64,0xafd92da8,0x2c722a1f,
  0x2fd90000,0xaea7aa1f,0x2c722da8,0xa63eaf64,0x2fd90000,0xaea72a1f,0x2c72ada8,0xa63e2f64,0x2ea70000,0x263e2f64,0xafd9ada8,0x2c72aa1f,
  0x2c720000,0x2fd92f64,0x263e2da8,0xaea7aa1f,0x263e0000,0x2c722a1f,0x2ea72da8,0x2fd92f64,0xafd93000,0xaea72f64,0xac722da8,0xa63e2a1f,
  0xaea73000,0x263e2a1f,0x2fd9ada8,0x2c72af64,0xac723000,0x2fd9aa1f,0xa63eada8,0xaea72f64,0xa63e3000,0x2c72af64,0xaea72da8,0x2fd9aa1f,
  0x263e3000,0xac72af64,0x2ea72da8,0xafd9aa1f,0x2c723000,0xafd9aa1f,0x263eada8,0x2ea72f64,0x2ea73000,0xa63e2a1f,0xafd9ada8,0xac72af64,
  0x2fd93000,0x2ea72f64,0x2c722da8,0x263e2a1f,0xa63e0000,0xac72aa1f,0xaea7ada8,0xafd9af64,0x2c720000,0x2fd92f64,0x263e2da8,0xaea7aa1f,
  0xaea70000,0xa63eaf64,0x2fd92da8,0xac722a1f,0x2fd90000,0xaea72a1f,0x2c72ada8,0xa63e2f64,0xafd90000,0x2ea72a1f,0xac72ada8,0x263e2f64,
  0x2ea70000,0x263eaf64,0xafd92da8,0x2c722a1f,0xac720000,0xafd92f64,0xa63e2da8,0x2ea7aa1f,0x263e0000,0x2c72aa1f,0x2ea7ada8,0x2fd9af64,
  0x2fd93000,0x2ea72f64,0x2c722da8,0x263e2a1f,0xaea7b000,0x263eaa1f,0x2fd92da8,0x2c722f64,0x2c723000,0xafd9aa1f,0x263eada8,0x2ea72f64,
  0xa63eb000,0x2c722f64,0xaea7ada8,0x2fd92a1f,0xa63e3000,0x2c72af64,0xaea72da8,0x2fd9aa1f,0x2c72b000,0xafd92a1f,0x263e2da8,0x2ea7af64,
  0xaea73000,0x263e2a1f,0x2fd9ada8,0x2c72af64,0x2fd9b000,0x2ea7af64,0x2c72ada8,0x263eaa1f,0x263e0000,0x2c72aa1f,0x2ea7ada8,0x2fd9af64,
  0xac720000,0xafd92f64,0xa63e2da8,0x2ea7aa1f,0x2ea70000,0x263eaf64,0xafd92da8,0x2c722a1f,0xafd90000,0x2ea72a1f,0xac72ada8,0x263e2f64,
  0x2fd90000,0xaea72a1f,0x2c72ada8,0xa63e2f64,0xaea70000,0xa63eaf64,0x2fd92da8,0xac722a1f,0x2c720000,0x2fd92f64,0x263e2da8,0xaea7aa1f,
  0xa63e0000,0xac72aa1f,0xaea7ada8,0xafd9af64,0xafd93000,0xaea72f64,0xac722da8,0xa63e2a1f,0x2ea7b000,0xa63eaa1f,0xafd92da8,0xac722f64,
  0xac723000,0x2fd9aa1f,0xa63eada8,0xaea72f64,0x263eb000,0xac722f64,0x2ea7ada8,0xafd92a1f,0x263e3000,0xac72af64,0x2ea72da8,0xafd9aa1f,
  0xac72b000,0x2fd92a1f,0xa63e2da8,0xaea7af64,0x2ea73000,0xa63e2a1f,0xafd9ada8,0xac72af64,0xafd9b000,0xaea7af64,0xac72ada8,0xa63eaa1f,
  0xafd9b000,0xaea7af64,0xac72ada8,0xa63eaa1f,0x2ea73000,0xa63e2a1f,0xafd9ada8,0xac72af64,0xac72b000,0x2fd92a1f,0xa63e2da8,0xaea7af64,
  0x263e3000,0xac72af64,0x2ea72da8,0xafd9aa1f,0x263eb000,0xac722f64,0x2ea7ada8,0xafd92a1f,0xac723000,0x2fd9aa1f,0xa63eada8,0xaea72f64,
  0x2ea7b000,0xa63eaa1f,0xafd92da8,0xac722f64,0xafd93000,0xaea72f64,0xac722da8,0xa63e2a1f,0xa63e0000,0xac72aa1f,0xaea7ada8,0xafd9af64,
  0x2c720000,0x2fd92f64,0x263e2da8,0xaea7aa1f,0xaea70000,0xa63eaf64,0x2fd92da8,0xac722a1f,0x2fd90000,0xaea72a1f,0x2c72ada8,0xa63e2f64,
  0xafd90000,0x2ea72a1f,0xac72ada8,0x263e2f64,0x2ea70000,0x263eaf64,0xafd92da8,0x2c722a1f,0xac720000,0xafd92f64,0xa63e2da8,0x2ea7aa1f,
  0x263e0000,0x2c72aa1f,0x2ea7ada8,0x2fd9af64,0x2fd9b000,0x2ea7af64,0x2c72ada8,0x263eaa1f,0xaea73000,0x263e2a1f,0x2fd9ada8,0x2c72af64,
  0x2c72b000,0xafd92a1f,0x263e2da8,0x2ea7af64,0xa63e3000,0x2c72af64,0xaea72da8,0x2fd9aa1f,0xa63eb000,0x2c722f64,0xaea7ada8,0x2fd92a1f,
  0x2c723000,0xafd9aa1f,0x263eada8,0x2ea72f64,0xaea7b000,0x263eaa1f,0x2fd92da8,0x2c722f64,0x2fd93000,0x2ea72f64,0x2c722da8,0x263e2a1f,
  0x263e0000,0x2c72aa1f,0x2ea7ada8,0x2fd9af64,0xac720000,0xafd92f64,0xa63e2da8,0x2ea7aa1f,0x2ea70000,0x263eaf64,0xafd92da8,0x2c722a1f,
  0xafd90000,0x2ea72a1f,0xac72ada8,0x263e2f64,0x2fd90000,0xaea72a1f,0x2c72ada8,0xa63e2f64,0xaea70000,0xa63eaf64,0x2fd92da8,0xac722a1f,
  0x2c720000,0x2fd92f64,0x263e2da8,0xaea7aa1f,0xa63e0000,0xac72aa1f,0xaea7ada8,0xafd9af64,0x316c2fbd,0x343e32f7,0x35bc34ff,0x372c3676,
  0x371532c6,0x3a81392e,0x3bef3b71,0x3b7c3bf2,0x397034cf,0x3bfc3b6c,0x38b23b04,0xb40e31e8,0x3ae13631,0x39e73bf5,0xb6e83219,0xbbe8bb13,
  0x3bc23785,0x30be3aa9,0xbbfdb911,0x2a16b9aa,0x3bfe3865,0xb80f37a6,0xb82abc00,0x3bfd376f,0x3b9238fd,0xbb7f2311,0x3805b929,0x31223bde,
  0x3a85398b,0xbb96b742,0x3bff319e,0xbbb82f8b,0xbbe2bbf1,0xbbb7bbcf,0xbb78bb9a,0xbb27bb52,0xbb2cbbd2,0xb8a8ba19,0xb029b5df,0x35a52f59,
  0xb9dfbba1,0x2ba7b5f7,0x3a7a37b2,0x3bbd3bdd,0xb815bb60,0x39662e91,0x3b373bda,0xb0d7377a,0xb3d3bb10,0x3be9386f,0x2a7a3a31,0xbbfeb9a6,
  0x294dbab0,0x3ae53b07,0xbad51fdb,0xab43bb16,0x352fba41,0x35993c00,0xbaebba1d,0x3be531cf,0x38a3b9c5,0xb5173b21,0x2776bbe0,0x34323bf2,
  0x384537dd,0x38ea3899,0x39823937,0x3a0d39c9,0x39463a93,0x3340374e,0xb426a452,0xb979b7c8,0xbb45b924,0xbb32bc00,0xb371b902,0x38d63294,
  0xb08db9a1,0x3b3f379b,0x39583bd7,0xb8252dfb,0x3bea3a2d,0xb3ba3874,0xbb89bb0d,0x36d2b625,0xb6bb387f,0xb8d1bbf5,0x3be73602,0xb546391f,
  0xba00bb01,0x3bff35eb,0xba5c34db,0x3359bab6,0x3ac7b66b,0xb9413933,0x368dbabd,0xb0103bb3,0xbac4baf7,0xba50ba8c,0xb9cdba11,0xb93cb986,
  0x3a04388e,0x3bcb3b1e,0x3bba3c00,0x39d63afe,0x36af3a21,0xb6ffa17f,0xbbc8ba3d,0xba60bbd4,0xbbebb9af,0xb6c6bb0a,0x39f43263,0x3ad83bf7,
  0x30a6b916,0x3bc33aa5,0xb55e3790,0xbb3dbb63,0x3b423a9e,0xba642ec3,0xb0f0bb6a,0x3b8e3a25,0xb94a37bd,0x2884bb6f,0x38db3b9f,0xbbc9b85a,
  0xb840bb54,0x3a093a15,0xbb4cb850,0x3bef3457,0x3a893a4d,0x3af43ac1,0x3b4f3b24,0x3b983b76,0xbb94baba,0xbbe4bbf9,0xba58bb57,0xb699b8f8,
  0x3bfe3b18,0x394f3b5c,0xb109347b,0xbae8b884,0xbbc0bb68,0xa9b1b90c,0x3b8b387a,0x38bc3ba5,0x3ade3ba7,0xb8c1324b,0xb9f0bbf6,0x39eb9648,
  0xb96bbbd6,0x3bbf3487,0xb38939b3,0xb9f8bba3,0x370a3bf3,0xbb47b994,0x3bbc2d65,0xb8ad3889,0xb153bc00,0x37213b9c,0xb97dba90,0x3af138f3,
  0xb89eb8ee,0xb7e8b84a,0xb682b737,0xb50bb5c8,0x35233855,0xb13b2d33,0xb8e0b65f,0xbb4aba45,0xa8e8b764,0x39fc3648,0x3be63bae,0x380a3a9b,
  0xb3eb360e,0xbbfeba35,0xb552baa2,0x3a7334b7,0x381ab4ab,0x3a6f3bd8,0xb95d2e5f,0xb962bc00,0xb9e3327c,0xb402bbac,0x3bc6399d,0xb95434c3,
  0x3b2faf27,0xb6a439bc,0xb41abbf9,0x3a7e3a97,0xbbe3251b,0x3b2ab4f3,0xb9d23894,0x37f3ba49,0x3bce3bb5,0x3bf03be1,0x3bff3bfa,0x3bfb3bff,
  0x2c38b1b6,0x383a34e7,0x3aee39c0,0x3bff3bb2,0xbb81bbf8,0xb53ab999,0x38302ef5,0x3bed3ab3,0xb8cc9cb6,0xbb85bbab,0x2adeb86a,0x3bc5391b,
  0x38c73bf6,0xbadbb232,0xb6ddbba9,0x3b87361a,0x3b833201,0xb0743a39,0xba76bb5e,0x3b352dc9,0xac06bbb0,0x39743b59,0xbbeeb759,0x3aceb2ad,
  0xbbccb5d4,0x3bfb2d00,0xbb7a32de,0x3a54b7d2,0xb30fb44b,0xafefb185,0xa6adacce,0x2c9c25e4,0xbbfcbbdf,0xbacbbb9e,0xb7feb990,0xa81fb463,
  0xb58d2d97,0xbb90b9b8,0xbad1bbf4,0xb05bb85f,0x3a673c00,0xb5763493,0xbbfdbaac,0xb3a2ba29,0x3a6b2e2d,0x38203bd9,0xbb3ab49f,0xb56abb65,
  0xb581bbdc,0x3bec3907,0xb8b7363c,0xb6f4bbf8,0xbbfcb46f,0x39dab654,0xb0423b1b,0xb835bbd3,0xb3283b73,0xac6abbfa,0x35b13bd0,0xb8e5bafb,
  0x38ee3a0d,0xb84aba89,0x37373af4,0xb5c8bb4f,0x35df3a81,0x2f59bbef,0xb88e3b7c,0x3b1eb946,0x2d973ae8,0x39b8bb81,0xbbf4353a,0x385f3830,
  0xb2633b3f,0x3bf7b958,0xb60eb825,0xba353bc0,0xb7853b87,0x3aa9b3d3,0x3911bbe9,0xb9aa2a7a,0xb99d3bbf,0x34c33389,0x3bdcb9f8,0x3907bb83,
  0xbb013be5,0xb5eb394a,0x34db2884,0x3ab6b8db,0xbbd03bfb,0xbafb3b7a,0xb98b3a54,0xb74238a3,0x3a4db93c,0xbac1389e,0x3b24b7e8,0xbb763682,
  0x3b71b8a8,0xbbf23029,0x3a9335a5,0xb74eba04,0x3bf8b80a,0xb999b58d,0xaef53b90,0x3ab3bad1,0x3bd7b6c6,0xadfbb9f4,0xbb683ad8,0x390c33eb,
  0x3b10b56a,0x386fbbc2,0xba3130be,0xb9a63bfd,0x39b3b402,0x3ba3bbc6,0x3201b954,0xba393581,0x37bdb122,0x3b6fba00,0x3b9fbbff,0x385aba5c,
  0x32deac6a,0x37d2b5b1,0x39c5b8e5,0x3b21ba85,0x344b3b98,0xb185bbce,0x2cce3bf0,0x25e4bbff,0xbc003340,0x3afe3426,0xb855b979,0x2d333b94,
  0x34cfbbed,0xbb6c39df,0x3b042ba7,0xb1e8ba7a,0x3aa2a9b1,0x34b7bb8b,0xbc0038bc,0x349338cc,0xba2d3bfe,0x387430a6,0x3b0dbbc3,0xb625b55e,
  0xb63cb074,0xbbf83a76,0xb8653b35,0x37a6294d,0x3bf3bbc9,0x3994bb2f,0x2d65b6a4,0xb889341a,0xb19e3517,0x2f8b2776,0x366bb432,0x3933b840,
  0x3bb5b50b,0xbbe1330f,0x3bfaafef,0xbbff26ad,0xa4523bcb,0x37c8bbba,0xbaba39d6,0x3bf9b523,0xbba1305b,0x35f73970,0x37b2bbfc,0xbbdd38b2,
  0x387abbfe,0xbba53552,0x9cb63a73,0x3babba67,0x39162a16,0x3aa5bbea,0xb790b3ba,0xbb633b89,0xbb5e3bec,0xadc938b7,0x3ab0b6f4,0x3b07bbfe,
  0xaf27b359,0xb9bc370a,0xbbf93b47,0xba973bbc,0x3be0bb96,0x3bf2bbff,0x3b54bbb8,0x3a15bac7,0xafbd3bfb,0x32f7bbe2,0xb4ff3bb7,0x3676bb78,
  0x365fbbe4,0xba453a58,0x3bdfb699,0xbb9eac38,0xb9243bbd,0x3c00b6af,0xb902b6ff,0xb2943bc8,0x3aacbb85,0xba29aade,0xb6313bc5,0x3bf5b815,
  0xbba73b3d,0x324b381a,0x3bf6ba6f,0x9648b95d,0x3c00bae5,0x376fbad5,0xb87f2b43,0xbbf53b42,0xbbb03a7e,0xbb593bfc,0xb75939da,0x32ad3042,
  0x3abdba09,0x3bb3bb4c,0x3c00bbef,0x3b9cbbe3,0x3bf12c9c,0xbbcfb16c,0x3b9a343e,0xbb52b5bc,0xbb57b13b,0x38f838e0,0xb1b6bb4a,0xb4e73bfc,
  0x3a21340e,0x217fbb45,0xba3d3b32,0x3bd4b371,0xb86ab576,0xb91b3bfd,0x3b60b3a2,0x2e91bae1,0x34ab36d2,0x3bd8bade,0xae5fb8c1,0xbc0039f0,
  0x9fdbb80f,0xbb16382a,0xba9e3bfd,0x2ec336bb,0xb46f38ad,0x3654ac06,0x3b1bb974,0x3bd3bbee,0x3850b941,0x3457b68d,0xa51bb010,0xb4f33153,
  0xb7dd3b27,0x3899bac4,0xb9373a50,0x39c9b9cd,0x3990383a,0xb463baee,0xb2c63bff,0x392ebb2c,0x3b18ba60,0xbb5c28e8,0x347b39fc,0x3884bbe6,
  0xb219b966,0xbb133b37,0x39a130d7,0x379bbbeb,0xbbf63962,0xb2323a6b,0x3ba9b820,0x361abb3a,0xb6023a64,0x391fb0f0,0x3bd6bb8e,0x3487b9e3,
  0x3a41b835,0x3c00bb92,0x3a1dbb7f,0x31cfb805,0x3a90bb2a,0x38f3b9d2,0x35d4b7f3,0x2d00b328,0x3af7372c,0xba8cb845,0x3a1138ea,0xb986b982,
  0x39c0bacb,0xbbb237fe,0x3bd2a81f,0xba19b715,0xb764b8d6,0xb6483bfe,0x3baeb94f,0xba9bb109,0xbbda39e7,0x377a36e8,0x39afbbe8,0xbb0a308d,
  0xae2d39eb,0x3bd9b8c7,0x349fbadb,0xbb6536dd,0x3b6ab8d1,0x3a25bbe7,0xb27cb546,0xbbac396b,0x38fdbace,0xa311b52f,0xb9293599,0xbbde3aeb,
  0xb8943721,0xba49397d,0xbb733af1,0xbbfa3bcc,0xbbfb3bff,0xbbe23bf1,0xbbb73bcf,0xbb783b9a,0xbb7c3bf2,0xb9463a93,0xb340374e,0x3426a452,
  0xba603bd4,0xa8e83764,0x39fcb648,0x3be6bbae,0xb8bc3ba5,0x38cc9cb6,0x3b85bbab,0xaadeb86a,0xb56a3b65,0x3bc2b785,0x30bebaa9,0xbbfd3911,
  0xab433b16,0x3b42ba9e,0xba64aec3,0xb0f03b6a,0x33593ab6,0x370abbf3,0xbb473994,0x3bbcad65,0x37f33a49,0xb328bb73,0xac6a3bfa,0x35b1bbd0,
  0xac9c25e4,0xb16c2fbd,0xb43e32f7,0xb5bc34ff,0xb5a52f59,0xba04388e,0xbbcb3b1e,0xbbba3c00,0xb8d63294,0xbbfe3b18,0xb94f3b5c,0x3109347b,
  0xba7334b7,0xba673c00,0x35763493,0x3bfdbaac,0xbb87361a,0xb3d33b10,0x3be9b86f,0x2a7aba31,0xbbfd376f,0x36bb387f,0x38d1bbf5,0xbbe73602,
  0xbbc9385a,0x3b2f2f27,0xb6a4b9bc,0xb41a3bf9,0xbaf138f3,0x3bccb5d4,0xbbfb2d00,0x3b7a32de,0xbb273b52,0xbac43af7,0xba503a8c,0xb9cd3a11,
  0x3979b7c8,0x3b94baba,0x3be4bbf9,0x3a58bb57,0x380aba9b,0xb58dad97,0xbb9039b8,0xbad13bf4,0xbbc5391b,0xb8153b60,0x3966ae91,0x3b37bbda,
  0x2a1639aa,0x3beaba2d,0xb3bab874,0xbb893b0d,0x3b8eba25,0xb9e3b27c,0xb4023bac,0x3bc6b99d,0xb8adb889,0xac063bb0,0x3974bb59,0xbbee3759,
  0xb8e53afb,0x3a85b98b,0xbb963742,0x3bffb19e,0xb72c3676,0xb84537dd,0xb8ea3899,0xb9823937,0xb9d63afe,0xb5233855,0x313b2d33,0x38e0b65f,
  0x3ae8b884,0x3b81bbf8,0x353ab999,0xb8302ef5,0x33a2ba29,0xbae13631,0xb9e73bf5,0x36e83219,0xbbfe39a6,0x30a63916,0x3bc3baa5,0xb55eb790,
  0x3546391f,0x396bbbd6,0xbbbf3487,0x338939b3,0x3a7eba97,0xbbfc346f,0x39da3654,0xb042bb1b,0xba54b7d2,0x38a339c5,0xb517bb21,0x27763be0,
  0xb93c3986,0xb89e38ee,0xb7e8384a,0xb6823737,0x3699b8f8,0xac38b1b6,0xb83a34e7,0xbaee39c0,0xb05b385f,0x3970b4cf,0x3bfcbb6c,0x38b2bb04,
  0xb0d7b77a,0xbbeb39af,0xb6c63b0a,0x39f4b263,0x36d23625,0x3adebba7,0xb8c1b24b,0xb9f03bf6,0xb954b4c3,0xb5813bdc,0x3becb907,0xb8b7b63c,
  0x3ace32ad,0xb52fba41,0xb5993c00,0x3aebba1d,0xbbb8af8b,0x3ac7366b,0xb941b933,0x368d3abd,0xba0d39c9,0xba893a4d,0xbaf43ac1,0xbb4f3b24,
  0x3b4aba45,0x3bfcbbdf,0x3acbbb9e,0x37feb990,0xbbed3ab3,0xb9df3ba1,0x2ba735f7,0x3a7ab7b2,0x3be8bb13,0x308db9a1,0xbb3f379b,0xb9583bd7,
  0xbb3d3b63,0x381a34ab,0x3a6fbbd8,0xb95dae5f,0x39f8bba3,0xbb833201,0x30743a39,0x3a76bb5e,0xb8353bd3,0x3b92b8fd,0xbb7fa311,0x38053929,
  0x3432bbf2,0xb8403b54,0x3a09ba15,0xbb4c3850,0xb50b35c8,0xb30f344b,0xafef3185,0xa6ad2cce,0xbbff3bb2,0xbb2c3bd2,0xb8a83a19,0xb02935df,
  0xb40eb1e8,0xbb453924,0xbb323c00,0xb3713902,0x3ad8bbf7,0xb3ebb60e,0xbbfe3a35,0xb5523aa2,0x39eb1648,0x38c7bbf6,0xbadb3232,0xb6dd3ba9,
  0xb6f43bf8,0x3bfeb865,0xb80fb7a6,0xb82a3c00,0xbbe531cf,0x394a37bd,0xa884bb6f,0xb8db3b9f,0xb010bbb3,0xb1533c00,0x3721bb9c,0xb97d3a90,
  0xbb983b76,0xbbce3bb5,0xbbf03be1,0xbbff3bfa,0x281fb463,0xb71532c6,0xba81392e,0xbbef3b71,0x3bbdbbdd,0x36afba21,0xb6ff217f,0xbbc83a3d,
  0x38252dfb,0x3bc0bb68,0x29b1b90c,0xbb8b387a,0xb9623c00,0x3a6bae2d,0x3820bbd9,0xbb3a349f,0xbb352dc9,0x294d3ab0,0x3ae5bb07,0xbad59fdb,
  0x3122bbde,0xba003b01,0x3bffb5eb,0xba5cb4db,0x3befb457,0xbbe3a51b,0x3b2a34f3,0xb9d2b894,0x39c939cd,0xba4db93c,0x3ac1389e,0xbb24b7e8,
  0x3b1e3946,0xbc00b340,0x3afeb426,0xb8553979,0x3bdd38b2,0xba21340e,0xa17fbb45,0x3a3d3b32,0x3bf53815,0xb2193966,0xbb13bb37,0x39a1b0d7,
  0x3b6536dd,0x37853b87,0xbaa9b3d3,0xb911bbe9,0x3a393581,0x3b5e3bec,0x2dc938b7,0xbab0b6f4,0x3889341a,0x3bb03a7e,0x3b593bfc,0x375939da,
  0x34f33153,0x38943721,0x3a49397d,0x3b733af1,0xb9863982,0x38eeba0d,0xb84a3a89,0x3737baf4,0xb74e3a04,0xa452bbcb,0x37c83bba,0xbabab9d6,
  0xb1e83a7a,0xb924bbbd,0x3c0036af,0xb90236ff,0x2e913ae1,0xbbdab9e7,0x377ab6e8,0x39af3be8,0x361a3b3a,0xbb10b56a,0xb86fbbc2,0x3a3130be,
  0x39073b83,0xb63c3074,0xbbf8ba76,0xb865bb35,0x3a973bbc,0x346f38ad,0xb654ac06,0xbb1bb974,0x3b9c3be3,0x3a903b2a,0x38f339d2,0x35d437f3,
  0x3b763682,0xbbb5b50b,0x3be1330f,0xbbfaafef,0x2d33bb94,0x365f3be4,0xba45ba58,0x3bdf3699,0xbbd4b371,0x3764b8d6,0x36483bfe,0xbbaeb94f,
  0x379b3beb,0xbbd7b6c6,0x2dfbb9f4,0x3b683ad8,0x39aa2a7a,0x3a2d3bfe,0xb87430a6,0xbb0dbbc3,0xbb07bbfe,0x1fdbb80f,0x3b16382a,0x3a9e3bfd,
  0xb2ad3042,0xba41b835,0xbc00bb92,0xba1dbb7f,0x3bfa3bcc,0x3bd03bfb,0x3afb3b7a,0x398b3a54,0xb5c83b4f,0x344bbb98,0xb1853bce,0x2ccebbf0,
  0x3bf93523,0xbb57313b,0x38f8b8e0,0xb1b63b4a,0xb294bbc8,0x3b183a60,0xbb5ca8e8,0x347bb9fc,0xbb0ab08d,0xb263bb3f,0x3bf73958,0xb60e3825,
  0x39a63bfd,0xb9162a16,0xbaa5bbea,0x3790b3ba,0x37a6a94d,0x3c003ae5,0x376f3ad5,0xb87fab43,0xbbd3bbee,0xb8fdbace,0x2311b52f,0x39293599,
  0x2d003328,0xb2deac6a,0xb7d2b5b1,0xb9c5b8e5,0x3bff26ad,0xbbf12c9c,0x3bcfb16c,0xbb9a343e,0xbb9e2c38,0x3990b83a,0xb4633aee,0xb2c6bbff,
  0x3a9bb109,0xad973ae8,0xb9b8bb81,0x3bf4353a,0xb90c33eb,0xb87abbfe,0x3ba53552,0x1cb63a73,0x3625b55e,0x3ba73b3d,0xb24b381a,0xbbf6ba6f,
  0xaec336bb,0xbb6ab8d1,0xba25bbe7,0x327cb546,0xb1cfb805,0x37bd3122,0x3b6f3a00,0x3b9f3bff,0x374238a3,0x319e3517,0xaf8b2776,0xb66bb432,
  0x25e43bff,0xafbdbbfb,0x32f73be2,0xb4ffbbb7,0xb4e7bbfc,0x39c03acb,0xbbb2b7fe,0x3bd2281f,0x38843be6,0xbbf8b80a,0x3999b58d,0x2ef53b90,
  0xba35bbc0,0x3aa229b1,0x34b73b8b,0xbc00b8bc,0x3b633b89,0xb4ab36d2,0xbbd8bade,0x2e5fb8c1,0xbbf5bb42,0xb602ba64,0x391f30f0,0x3bd63b8e,
  0x3bde3aeb,0x3b013be5,0x35eb394a,0xb4db2884,0xbb21ba85,0xbbe0bb96,0xbbf2bbff,0xbb54bbb8,0x3b52b5bc,0xbaf7372c,0x3a8cb845,0xba1138ea,
  0x392e3b2c,0xbb71b8a8,0x3bf23029,0xba9335a5,0xb85f3830,0xb4cfbbed,0x3b6c39df,0xbb042ba7,0xbbabba67,0x386ab576,0x391b3bfd,0xbb60b3a2,
  0x1648b95d,0x3bf63962,0x32323a6b,0xbba9b820,0x3bac396b,0x399d3bbf,0xb4c33389,0xbbdcb9f8,0x385a3a5c,0xaf273359,0xb9bcb70a,0xbbf9bb47,
  0xb933b840,0xbabdba09,0xbbb3bb4c,0xbc00bbef,0x36763b78,0xb7ddbb27,0x38993ac4,0xb937ba50,0xba193715,0x35dfba81,0x2f593bef,0xb88ebb7c,
  0xbab3bad1,0x3ba1305b,0xb5f73970,0xb7b2bbfc,0x3493b8cc,0x3aac3b85,0xba292ade,0xb631bbc5,0x3c0039f0,0x2e2d39eb,0xbbd9b8c7,0xb49fbadb,
  0x348739e3,0xb9b3b402,0xbba3bbc6,0xb201b954,0xbab6b8db,0xbbf3bbc9,0xb994bb2f,0xad65b6a4,0xba15bac7,0xb850b941,0xb457b68d,0x251bb010,
  0xb9cfbb16,0x30ac2a31,0x3b9c3bf1,0xb493ae2d,0xb76fb8b4,0x35a133e3,0x3a1d3afe,0xb902b76f,0xb3e3b5a1,0x38b4376f,0x376f3902,0xbafeba1d,
  0xaa31b0ac,0x3b1639cf,0x2e2d3493,0xbbf1bb9c,0xb956ba74,0x305f29cc,0x3b633bd2,0xb44badc9,0xb6e7b859,0x353f335e,0x39d23ab6,0xb8bcb6ff,
  0xb35eb53f,0x385936e7,0x36ff38bc,0xbab6b9d2,0xa9ccb05f,0x3a743956,0x2dc9344b,0xbbd2bb63,0xb8e3b9de,0x30122967,0x3b1e3ba1,0xb402ad65,
  0xb662b801,0x34de32da,0x39823a67,0xb874b68d,0xb2dab4de,0x38013662,0x368d3874,0xba67b982,0xa967b012,0x39de38e3,0x2d653402,0xbba1bb1e,
  0xb876b952,0x2f8c2902,0x3ace3b60,0xb371ad00,0xb5e1b758,0x347e3257,0x392e3a11,0xb82ab61a,0xb257b47e,0x375835e1,0x361a382a,0xba11b92e,
  0xa902af8c,0x39523876,0x2d003371,0xbb60bace,0xb80db8ce,0x2ef3289e,0x3a733b10,0xb2deac9c,0xb562b6b3,0x342031d5,0x38d639b3,0xb7bdb5a5,
  0xb1d5b420,0x36b33562,0x35a537bd,0xb9b3b8d6,0xa89eaef3,0x38ce380d,0x2c9c32de,0xbb10ba73,0xb750b851,0x2e5a2839,0x3a0d3ab0,0xb24bac38,
  0xb4e5b613,0x33863153,0x387a394f,0xb721b52f,0xb153b386,0x361334e5,0x352f3721,0xb94fb87a,0xa839ae5a,0x38513750,0x2c38324b,0xbab0ba0d,
  0xb68eb7b4,0x2dc227a9,0x399d3a41,0xb1b6aba7,0xb46ab577,0x32cd30d2,0x381a38e5,0xb682b4b7,0xb0d2b2cd,0x3577346a,0x34b73682,0xb8e5b81a,
  0xa7a9adc2,0x37b4368e,0x2ba731b6,0xba41b99d,0xb5d2b6d1,0x2d2a26e0,0x392439c5,0xb122aade,0xb3e3b4de,0x32163052,0x376f3874,0xb5dfb43e,
  0xb052b216,0x34de33e3,0x343e35df,0xb874b76f,0xa6e0ad2a,0x36d135d2,0x2ade3122,0xb9c5b924,0xb51cb5f6,0x2c932617,0x38a3393c,0xb08daa16,
  0xb2f4b448,0x31602fa5,0x36a437fe,0xb53ab389,0xafa5b160,0x344832f4,0x3389353a,0xb7feb6a4,0xa617ac93,0x35f6351c,0x2a16308d,0xb93cb8a3,
  0xb46ab523,0x2bf6254d,0x381a38a8,0xafefa94d,0xb209b36b,0x30ac2ea7,0x35d4370a,0xb493b294,0xaea7b0ac,0x336b3209,0x32943493,0xb70ab5d4,
  0xa54dabf6,0x3523346a,0x294d2fef,0xb8a8b81a,0xb378b456,0x2ac82484,0x3715380a,0xaec3a884,0xb120b24a,0x2ff22da9,0x34ff360e,0xb3d3b19e,
  0xada9aff2,0x324a3120,0x319e33d3,0xb60eb4ff,0xa484aac8,0x34563378,0x28842ec3,0xb80ab715,0xb223b31c,0x29992376,0x35eb36c6,0xad97a776,
  0xb039b12d,0x2e8d2cac,0x3426350b,0xb27cb0a6,0xacacae8d,0x312d3039,0x30a6327c,0xb50bb426,0xa376a999,0x331c3223,0x27762d97,0xb6c6b5eb,
  0xb0d2b194,0x286b21e4,0x34b7356a,0xac6aa5e4,0xaea7b012,0x2d2a2b5f,0x32943402,0xb122af59,0xab5fad2a,0x30122ea7,0x2f593122,0xb402b294,
  0xa1e4a86b,0x319430d2,0x25e42c6a,0xb56ab4b7,0xaf0cb012,0x267b2052,0x32f73402,0xaa7aa452,0xacdeadf5,0x2b912967,0x30d731e8,0xaf8bad65,
  0xa967ab91,0x2df52cde,0x2d652f8b,0xb1e8b0d7,0xa052a67b,0x30122f0c,0x24522a7a,0xb402b2f7,0xac79ad2a,0x24201d7f,0x30743122,0xa81fa17f,
  0xaa31ab91,0x28d026e0,0x2e2d2f8b,0xacceaade,0xa6e0a8d0,0x2b912a31,0x2ade2cce,0xaf8bae2d,0x9d7fa420,0x2d2a2c79,0x217f281f,0xb122b074,
  0xa7a9a86b,0x1f1218b6,0x2ba72c6a,0xa3119cb6,0xa54da67b,0x242021e4,0x294d2a7a,0xa81fa5e4,0xa1e4a420,0x267b254d,0x25e4281f,0xaa7aa94d,
  0x98b69f12,0x286b27a9,0x1cb62311,0xac6aaba7,0x211b21e4,0x98b69248,0xa51ba5e4,0x1cb61648,0x1f122052,0x9d7f9bdb,0xa311a452,0x217f1fdb,
  0x1bdb1d7f,0xa0529f12,0x9fdba17f,0x24522311,0x124818b6,0xa1e4a11b,0x96489cb6,0x25e4251b,0x2a632b5f,0xa1e49bdb,0xae5faf59,0x25e41fdb,
  0x286b2967,0xa6e0a4e9,0xac6aad65,0x2ade28e8,0x24e926e0,0xa967a86b,0xa8e8aade,0x2d652c6a,0x1bdb21e4,0xab5faa63,0x9fdba5e4,0x2f592e5f,
  0x2dc22ea7,0xa54d9f12,0xb1b6b294,0x294d2311,0x2bf62cde,0xaa31a86b,0xafefb0d7,0x2e2d2c6a,0x286b2a31,0xacdeabf6,0xac6aae2d,0x30d72fef,
  0x1f12254d,0xaea7adc2,0xa311a94d,0x329431b6,0x302c30d2,0xa7a9a11b,0xb41ab4b7,0x2ba7251b,0x2dc22f0c,0xac79aa63,0xb1b6b2f7,0x30742e5f,
  0x2a632c79,0xaf0cadc2,0xae5fb074,0x32f731b6,0x211b27a9,0xb0d2b02c,0xa51baba7,0x34b7341a,0x317a3257,0xa902a2ad,0xb552b61a,0x2d0026ad,
  0x2f8c309f,0xaddcac2e,0xb371b487,0x31cf3029,0x2c2e2ddc,0xb09faf8c,0xb029b1cf,0x34873371,0x22ad2902,0xb257b17a,0xa6adad00,0x361a3552,
  0x32cd33e3,0xaa31a420,0xb682b76f,0x2e2d281f,0x30ac31bb,0xaf3fad2a,0xb493b58d,0x33283122,0x2d2a2f3f,0xb1bbb0ac,0xb122b328,0x358d3493,
  0x24202a31,0xb3e3b2cd,0xa81fae2d,0x376f3682,0x341334bc,0xab5fa4e9,0xb7a6b85a,0x2f5928e8,0x319432da,0xb052ae28,0xb56ab68d,0x343e3219,
  0x2e283052,0xb2dab194,0xb219b43e,0x368d356a,0x24e92b5f,0xb4bcb413,0xa8e8af59,0x385a37a6,0x34c3358c,0xac47a5b2,0xb85fb8f3,0x304229b1,
  0x327e33fd,0xb106af26,0xb63cb785,0x34e7330f,0x2f263106,0xb3fdb27e,0xb30fb4e7,0x3785363c,0x25b22c47,0xb58cb4c3,0xa9b1b042,0x38f3385f,
  0x35773662,0xacdea67b,0xb8e5b982,0x30d72a7a,0x336b3493,0xb1bbb012,0xb70ab83a,0x358d3402,0x301231bb,0xb493b36b,0xb402b58d,0x383a370a,
  0x267b2cde,0xb662b577,0xaa7ab0d7,0x398238e5,0x36303741,0xad76a744,0xb962ba04,0x316c2b43,0x342e352a,0xb271b092,0xb7d2b8ad,0x3631347b,
  0x30923271,0xb52ab42e,0xb47bb631,0x38ad37d2,0x27442d76,0xb741b630,0xab43b16c,0x3a043962,0x36ee3815,0xae0ea807,0xb9d6ba7a,0x32012c06,
  0x34a735c4,0xb329b113,0xb84ab91b,0x36d234f3,0x31133329,0xb5c4b4a7,0xb4f3b6d2,0x391b384a,0x28072e0e,0xb815b6ee,0xac06b201,0x3a7a39d6,
  0x37b4388e,0xaea7a86b,0xba41bae1,0x32942c6a,0x35233662,0xb3e3b194,0xb8a8b982,0x376f356a,0x319433e3,0xb662b523,0xb56ab76f,0x398238a8,
  0x286b2ea7,0xb88eb7b4,0xac6ab294,0x3ae13a41,0x3841390f,0xaf3fa8d0,0xbaa2bb3a,0x33282cce,0x35a13705,0xb44fb216,0xb902b9e3,0x380535df,
  0x3216344f,0xb705b5a1,0xb5dfb805,0x39e33902,0x28d02f3f,0xb90fb841,0xacceb328,0x3b3a3aa2,0x38ac3997,0xafd8a935,0xbaf7bb83,0x33ba2d33,
  0x362137ac,0xb4aeb298,0xb958ba3d,0x38503654,0x329834ae,0xb7acb621,0xb654b850,0x3a3d3958,0x29352fd8,0xb997b8ac,0xad33b3ba,0x3b833af7,
  0x391c3a28,0xb039a999,0xbb42bbbc,0x34262d97,0x36a4382d,0xb50eb31c,0xb9aaba90,0x389936c6,0x331c350e,0xb82db6a4,0xb6c6b899,0x3a9039aa,
  0x29993039,0xba28b91c,0xad97b426,0x3bbc3b42,0x39923ac3,0xb085a9fe,0xbb81bbe3,0x346f2dfb,0x372a3886,0xb570b3a0,0xb9f8badb,0x38e03737,
  0x33a03570,0xb886b72a,0xb737b8e0,0x3adb39f8,0x29fe3085,0xbac3b992,0xadfbb46f,0x3be33b81,
};

#define PROF(slot) do {} while (0)
#define PROF_DUMP() do {} while (0)
#define PROFA(slot, dep) do {} while (0)
#define PROF3(slot) do {} while (0)
#define PROF2(slot) do {} while (0)

__device__ __forceinline__ uint32_t smem_u32(const void* p) { return (uint32_t)__cvta_generic_to_shared(p); }

__device__ __forceinline__ void mbar_init(uint32_t a, uint32_t c) {
  asm volatile("mbarrier.init.shared::cta.b64 [%0], %1;\n" ::"r"(a), "r"(c) : "memory");
}
__device__ __forceinline__ void mbar_expect_tx(uint32_t a, uint32_t bytes) {
  asm volatile("mbarrier.arrive.expect_tx.shared::cta.b64 _, [%0], %1;\n" ::"r"(a), "r"(bytes) : "memory");
}
__device__ __forceinline__ void mbar_arrive_cluster(uint32_t cluster_addr) {
  asm volatile("mbarrier.arrive.shared::cluster.b64 _, [%0];\n" ::"r"(cluster_addr) : "memory");
}
__device__ __forceinline__ void mbar_arrive_cluster_n(uint32_t cluster_addr, uint32_t n) {
  asm volatile("mbarrier.arrive.shared::cluster.b64 _, [%0], %1;\n" ::"r"(cluster_addr), "r"(n) : "memory");
}
__device__ __forceinline__ bool mbar_try(uint32_t a, uint32_t parity) {
  uint32_t ok;
  asm volatile("{\n.reg .pred p;\nmbarrier.try_wait.parity.shared::cta.b64 p, [%1], %2;\nselp.u32 %0, 1, 0, p;\n}\n"
               : "=r"(ok) : "r"(a), "r"(parity) : "memory");
  return ok;
}
__device__ __forceinline__ void mbar_wait(uint32_t a, uint32_t parity) {
  if (mbar_try(a, parity)) return;
#pragma unroll 1
  for (int n = 0; n < SPIN_LIMIT; n++)
    if (mbar_try(a, parity)) break;
}
__device__ __forceinline__ bool elect_one() {
  uint32_t p;
  asm volatile("{\n.reg .pred P;\nelect.sync _|P, 0xffffffff;\nselp.u32 %0, 1, 0, P;\n}\n" : "=r"(p));
  return p;
}
__device__ __forceinline__ uint32_t mapa(uint32_t a, uint32_t rank) {
  uint32_t r;
  asm volatile("mapa.shared::cluster.u32 %0, %1, %2;\n" : "=r"(r) : "r"(a), "r"(rank));
  return r;
}
__device__ __forceinline__ void nb_sync(int id, int n) { asm volatile("bar.sync %0, %1;\n" ::"r"(id), "r"(n) : "memory"); }
__device__ __forceinline__ void nb_arrive(int id, int n) { asm volatile("bar.arrive %0, %1;\n" ::"r"(id), "r"(n) : "memory"); }
__device__ __forceinline__ void cluster_sync_all() {
  asm volatile("barrier.cluster.arrive.relaxed.aligned;\nbarrier.cluster.wait.aligned;\n" ::: "memory");
}
__device__ __forceinline__ void fence_async_smem() { asm volatile("fence.proxy.async.shared::cta;\n" ::: "memory"); }
__device__ __forceinline__ void fence_async_all() { asm volatile("fence.proxy.async.global;\n" ::: "memory"); }

__device__ __forceinline__ void tma_load_3d(uint32_t dst, const CUtensorMap* tm, uint32_t bar, int c0, int c1, int c2) {
  asm volatile(
      "cp.async.bulk.tensor.3d.shared::cluster.global.mbarrier::complete_tx::bytes [%0], [%1, {%3, %4, %5}], [%2];\n"
      ::"r"(dst), "l"(tm), "r"(bar), "r"(c0), "r"(c1), "r"(c2) : "memory");
}
__device__ __forceinline__ void tma_load_4d(uint32_t dst, const CUtensorMap* tm, uint32_t bar, int c0, int c1, int c2, int c3) {
  asm volatile(
      "cp.async.bulk.tensor.4d.shared::cluster.global.mbarrier::complete_tx::bytes [%0], [%1, {%3, %4, %5, %6}], [%2];\n"
      ::"r"(dst), "l"(tm), "r"(bar), "r"(c0), "r"(c1), "r"(c2), "r"(c3) : "memory");
}
__device__ __forceinline__ void tma_load_3d_mc(uint32_t dst, const CUtensorMap* tm, uint32_t bar, int c0, int c1, int c2) {
  asm volatile(
      "cp.async.bulk.tensor.3d.shared::cluster.global.mbarrier::complete_tx::bytes.multicast::cluster [%0], [%1, {%3, %4, %5}], [%2], %6;\n"
      ::"r"(dst), "l"(tm), "r"(bar), "r"(c0), "r"(c1), "r"(c2), "h"((uint16_t)3) : "memory");
}
__device__ __forceinline__ void bulk_load(uint32_t dst, const void* src, uint32_t bytes, uint32_t bar) {
  asm volatile("cp.async.bulk.shared::cluster.global.mbarrier::complete_tx::bytes [%0], [%1], %2, [%3];\n"
               ::"r"(dst), "l"(src), "r"(bytes), "r"(bar) : "memory");
}
__device__ __forceinline__ void tma_store_3d(const CUtensorMap* tm, uint32_t src, int c0, int c1, int c2) {
  asm volatile("cp.async.bulk.tensor.3d.global.shared::cta.bulk_group [%0, {%2, %3, %4}], [%1];\n"
               ::"l"(tm), "r"(src), "r"(c0), "r"(c1), "r"(c2) : "memory");
}
__device__ __forceinline__ void bulk_commit() { asm volatile("cp.async.bulk.commit_group;\n" ::: "memory"); }
__device__ __forceinline__ void bulk_wait0() { asm volatile("cp.async.bulk.wait_group 0;\n" ::: "memory"); }
__device__ __forceinline__ void prefetch_tmap(const CUtensorMap* tm) {
  asm volatile("prefetch.tensormap [%0];\n" ::"l"(tm) : "memory");
}

__device__ __forceinline__ void wg_fence() { asm volatile("wgmma.fence.sync.aligned;\n" ::: "memory"); }
__device__ __forceinline__ void wg_commit() { asm volatile("wgmma.commit_group.sync.aligned;\n" ::: "memory"); }
template <int N> __device__ __forceinline__ void wg_wait() {
  asm volatile("wgmma.wait_group.sync.aligned %0;\n" ::"n"(N) : "memory");
}
__device__ __forceinline__ uint64_t mkdesc(uint32_t addr, uint32_t lbo, uint32_t sbo, uint32_t swz) {
  return (uint64_t)((addr & 0x3FFFF) >> 4) | ((uint64_t)(lbo >> 4) << 16) | ((uint64_t)(sbo >> 4) << 32) |
         ((uint64_t)swz << 62);
}

#define R4(d, o) "+f"(d[o + 0]), "+f"(d[o + 1]), "+f"(d[o + 2]), "+f"(d[o + 3])
#define R8(d, o) R4(d, o), R4(d, o + 4)
#define R16(d, o) R8(d, o), R8(d, o + 8)
#define R32(d, o) R16(d, o), R16(d, o + 16)
#define R64(d, o) R32(d, o), R32(d, o + 32)

__device__ __forceinline__ void wgmma_n192(float (&d)[96], uint64_t da, uint64_t db, uint32_t acc) {
  asm volatile(
      "{\n.reg .pred p;\nsetp.ne.u32 p, %98, 0;\n"
      "wgmma.mma_async.sync.aligned.m64n192k16.f32.bf16.bf16 "
      "{%0,%1,%2,%3,%4,%5,%6,%7,%8,%9,%10,%11,%12,%13,%14,%15,%16,%17,%18,%19,%20,%21,%22,%23,%24,%25,%26,%27,%28,%29,%30,%31,"
      "%32,%33,%34,%35,%36,%37,%38,%39,%40,%41,%42,%43,%44,%45,%46,%47,%48,%49,%50,%51,%52,%53,%54,%55,%56,%57,%58,%59,%60,%61,%62,%63,"
      "%64,%65,%66,%67,%68,%69,%70,%71,%72,%73,%74,%75,%76,%77,%78,%79,%80,%81,%82,%83,%84,%85,%86,%87,%88,%89,%90,%91,%92,%93,%94,%95}, "
      "%96, %97, p, 1, 1, 0, 1;\n}\n"
      : R64(d, 0), R32(d, 64)
      : "l"(da), "l"(db), "r"(acc));
}
__device__ __forceinline__ void wgmma_n128(float (&d)[64], uint64_t da, uint64_t db, uint32_t acc) {
  asm volatile(
      "{\n.reg .pred p;\nsetp.ne.u32 p, %66, 0;\n"
      "wgmma.mma_async.sync.aligned.m64n128k16.f32.bf16.bf16 "
      "{%0,%1,%2,%3,%4,%5,%6,%7,%8,%9,%10,%11,%12,%13,%14,%15,%16,%17,%18,%19,%20,%21,%22,%23,%24,%25,%26,%27,%28,%29,%30,%31,"
      "%32,%33,%34,%35,%36,%37,%38,%39,%40,%41,%42,%43,%44,%45,%46,%47,%48,%49,%50,%51,%52,%53,%54,%55,%56,%57,%58,%59,%60,%61,%62,%63}, "
      "%64, %65, p, 1, 1, 0, 1;\n}\n"
      : R64(d, 0)
      : "l"(da), "l"(db), "r"(acc));
}
#define WG128(C, ACC)                                                                                                      \
  asm volatile(                                                                                                            \
      "{\n.reg .b64 a, b;\nmov.b64 a, {%64, %66};\nmov.b64 b, {%65, %66};\n"                                               \
      "wgmma.mma_async.sync.aligned.m64n128k16.f32.bf16.bf16 "                                                             \
      "{%0,%1,%2,%3,%4,%5,%6,%7,%8,%9,%10,%11,%12,%13,%14,%15,%16,%17,%18,%19,%20,%21,%22,%23,%24,%25,%26,%27,%28,%29,%30,%31," \
      "%32,%33,%34,%35,%36,%37,%38,%39,%40,%41,%42,%43,%44,%45,%46,%47,%48,%49,%50,%51,%52,%53,%54,%55,%56,%57,%58,%59,%60,%61," \
      "%62,%63}, a, b, " ACC ", 1, 1, 0, 1;\n}\n"                                                                          \
      : Z16(C, d, 0), Z16(C, d, 16), Z16(C, d, 32), Z16(C, d, 48)                                                          \
      : "r"(da), "r"(db), "r"(0x40000040))
#define Z4(C, d, o) C(d[o + 0]), C(d[o + 1]), C(d[o + 2]), C(d[o + 3])
#define Z16(C, d, o) Z4(C, d, o), Z4(C, d, o + 4), Z4(C, d, o + 8), Z4(C, d, o + 12)
__device__ __forceinline__ void wgmma_n128z(float (&d)[64], uint32_t da, uint32_t db) { WG128("=f", "0"); }
__device__ __forceinline__ void wgmma_n128a(float (&d)[64], uint32_t da, uint32_t db) { WG128("+f", "1"); }
template <int N> __device__ __forceinline__ void fence_regs(float (&d)[N]) {
#pragma unroll
  for (int i = 0; i < N; i++) asm volatile("" : "+f"(d[i])::"memory");
}

__device__ __forceinline__ void mma16816(float (&d)[4], uint32_t a0, uint32_t a1, uint32_t a2, uint32_t a3, uint32_t b0,
                                         uint32_t b1) {
  asm("mma.sync.aligned.m16n8k16.row.col.f32.bf16.bf16.f32 {%0,%1,%2,%3}, {%4,%5,%6,%7}, {%8,%9}, {%0,%1,%2,%3};\n"
      : "+f"(d[0]), "+f"(d[1]), "+f"(d[2]), "+f"(d[3])
      : "r"(a0), "r"(a1), "r"(a2), "r"(a3), "r"(b0), "r"(b1));
}
__device__ __forceinline__ void mma16816_z(float (&d)[4], uint32_t a0, uint32_t a1, uint32_t a2, uint32_t a3, uint32_t b0,
                                           uint32_t b1) {
  asm("mma.sync.aligned.m16n8k16.row.col.f32.bf16.bf16.f32 {%0,%1,%2,%3}, {%4,%5,%6,%7}, {%8,%9}, {%10,%10,%10,%10};\n"
      : "=f"(d[0]), "=f"(d[1]), "=f"(d[2]), "=f"(d[3])
      : "r"(a0), "r"(a1), "r"(a2), "r"(a3), "r"(b0), "r"(b1), "f"(0.f));
}
__device__ __forceinline__ void ldsm4t(uint32_t (&r)[4], uint32_t a) {
  asm volatile("ldmatrix.sync.aligned.m8n8.x4.trans.shared.b16 {%0,%1,%2,%3}, [%4];\n"
               : "=r"(r[0]), "=r"(r[1]), "=r"(r[2]), "=r"(r[3]) : "r"(a) : "memory");
}
__device__ __forceinline__ void ldsm2t(uint32_t& r0, uint32_t& r1, uint32_t a) {
  asm volatile("ldmatrix.sync.aligned.m8n8.x2.trans.shared.b16 {%0,%1}, [%2];\n" : "=r"(r0), "=r"(r1) : "r"(a) : "memory");
}
__device__ __forceinline__ void st_async128(uint32_t a, uint32_t bar, uint32_t x, uint32_t y, uint32_t z, uint32_t w) {
  asm volatile("st.async.weak.shared::cluster.mbarrier::complete_tx::bytes.v4.b32 [%0], {%2,%3,%4,%5}, [%1];\n"
               ::"r"(a), "r"(bar), "r"(x), "r"(y), "r"(z), "r"(w) : "memory");
}
__device__ __forceinline__ void mbar_arrive(uint32_t a) {
  asm volatile("mbarrier.arrive.shared::cta.b64 _, [%0];\n" ::"r"(a) : "memory");
}
__device__ __forceinline__ void stsm4(uint32_t a, uint32_t r0, uint32_t r1, uint32_t r2, uint32_t r3) {
  asm volatile("stmatrix.sync.aligned.m8n8.x4.shared.b16 [%0], {%1,%2,%3,%4};\n"
               ::"r"(a), "r"(r0), "r"(r1), "r"(r2), "r"(r3) : "memory");
}
__device__ __forceinline__ void stsm4t(uint32_t a, uint32_t r0, uint32_t r1, uint32_t r2, uint32_t r3) {
  asm volatile("stmatrix.sync.aligned.m8n8.x4.trans.shared.b16 [%0], {%1,%2,%3,%4};\n"
               ::"r"(a), "r"(r0), "r"(r1), "r"(r2), "r"(r3) : "memory");
}
__device__ __forceinline__ uint2 lds64(uint32_t a) {
  uint2 v;
  asm volatile("ld.shared.v2.u32 {%0,%1}, [%2];\n" : "=r"(v.x), "=r"(v.y) : "r"(a) : "memory");
  return v;
}
__device__ __forceinline__ uint4 lds128(uint32_t a) {
  uint4 v;
  asm volatile("ld.shared.v4.u32 {%0,%1,%2,%3}, [%4];\n" : "=r"(v.x), "=r"(v.y), "=r"(v.z), "=r"(v.w) : "r"(a) : "memory");
  return v;
}
__device__ __forceinline__ void sts128(uint32_t a, uint32_t x, uint32_t y, uint32_t z, uint32_t w) {
  asm volatile("st.shared.v4.u32 [%0], {%1,%2,%3,%4};\n" ::"r"(a), "r"(x), "r"(y), "r"(z), "r"(w) : "memory");
}
__device__ __forceinline__ void sts64(uint32_t a, uint32_t x, uint32_t y) {
  asm volatile("st.shared.v2.u32 [%0], {%1,%2};\n" ::"r"(a), "r"(x), "r"(y) : "memory");
}
__device__ __forceinline__ uint32_t pack_bf16(float lo, float hi) {
  uint32_t r;
  asm("cvt.rn.bf16x2.f32 %0, %1, %2;\n" : "=r"(r) : "f"(hi), "f"(lo));
  return r;
}
__device__ __forceinline__ uint32_t bmul2(uint32_t a, uint32_t b) {
  uint32_t r;
  asm("mul.rn.bf16x2 %0, %1, %2;\n" : "=r"(r) : "r"(a), "r"(b));
  return r;
}
__device__ __forceinline__ uint32_t bmax2(uint32_t a, uint32_t b) {
  uint32_t r;
  asm("max.bf16x2 %0, %1, %2;\n" : "=r"(r) : "r"(a), "r"(b));
  return r;
}
__device__ __forceinline__ uint32_t bfma2(uint32_t a, uint32_t b, uint32_t c) {
  uint32_t r;
  asm("fma.rn.bf16x2 %0, %1, %2, %3;\n" : "=r"(r) : "r"(a), "r"(b), "r"(c));
  return r;
}
__device__ __forceinline__ uint32_t clock32() {
  uint32_t t;
  asm volatile("mov.u32 %0, %%clock;\n" : "=r"(t));
  return t;
}
__device__ __forceinline__ void prefetch_l2(const void* p) { asm volatile("prefetch.global.L2 [%0];\n" ::"l"(p)); }
__device__ __forceinline__ void cp_async16(uint32_t dst, const void* src, uint32_t srcbytes) {
  asm volatile("cp.async.cg.shared.global.L2::256B [%0], [%1], 16, %2;\n" ::"r"(dst), "l"(src), "r"(srcbytes) : "memory");
}
__device__ __forceinline__ uint32_t ld_acquire(const uint32_t* p) {
  uint32_t v;
  asm volatile("ld.acquire.gpu.global.u32 %0, [%1];\n" : "=r"(v) : "l"(p) : "memory");
  return v;
}
__device__ __forceinline__ uint32_t ld_relaxed(const uint32_t* p) {
  uint32_t v;
  asm volatile("ld.relaxed.gpu.global.u32 %0, [%1];\n" : "=r"(v) : "l"(p) : "memory");
  return v;
}
__device__ __forceinline__ uint4 ld_b128(const uint4* p) {
  unsigned long long a, b;
  asm volatile("{\n.reg .b128 v;\nld.relaxed.gpu.global.b128 v, [%2];\nmov.b128 {%0, %1}, v;\n}\n" : "=l"(a), "=l"(b) : "l"(p) : "memory");
  return make_uint4((uint32_t)a, (uint32_t)(a >> 32), (uint32_t)b, (uint32_t)(b >> 32));
}
__device__ __forceinline__ void st_b128(uint4* p, uint32_t x, uint32_t y, uint32_t z, uint32_t w) {
  asm volatile("{\n.reg .b128 v;\nmov.b128 v, {%1, %2};\nst.relaxed.gpu.global.b128 [%0], v;\n}\n"
               ::"l"(p), "l"(x | (unsigned long long)y << 32), "l"(z | (unsigned long long)w << 32) : "memory");
}

struct Params {
  const __nv_bfloat16* x;
  const __nv_bfloat16* w;
  uint8_t tile[72];
  const __nv_bfloat16* q;
  const __nv_bfloat16* k;
  const __nv_bfloat16* v;
  const __nv_bfloat16* shift_k;
  const __nv_bfloat16* ssm_k;
  const __nv_bfloat16* ssm_D;
  const __nv_bfloat16* wo;
  __nv_bfloat16* out;
  uint32_t zero;
};

__device__ __forceinline__ uint32_t lds32(uint32_t a) {
  uint32_t v;
  asm volatile("ld.shared.u32 %0, [%1];\n" : "=r"(v) : "r"(a) : "memory");
  return v;
}
__device__ __forceinline__ float bf_lo(uint32_t v) {
  uint32_t r;
  asm("prmt.b32 %0, %1, 0, 0x1044;\n" : "=r"(r) : "r"(v));
  return __uint_as_float(r);
}
__device__ __forceinline__ float bf_hi(uint32_t v) { return __uint_as_float(v & 0xffff0000u); }
__device__ __forceinline__ float ex2(float x) {
  float r;
  asm("ex2.approx.ftz.f32 %0, %1;\n" : "=f"(r) : "f"(x));
  return r;
}
__device__ __forceinline__ float rcp(float x) {
  float r;
  asm("rcp.approx.ftz.f32 %0, %1;\n" : "=f"(r) : "f"(x));
  return r;
}

#define Q4(c, d, o) c(d[o + 0]), c(d[o + 1]), c(d[o + 2]), c(d[o + 3])
#define Q8(c, d, o) Q4(c, d, o), Q4(c, d, o + 4)
#define Q16(c, d, o) Q8(c, d, o), Q8(c, d, o + 8)
#define Q32(c, d) Q16(c, d, 0), Q16(c, d, 16)
#define L8 "{%0,%1,%2,%3,%4,%5,%6,%7}"
#define L16 "{%0,%1,%2,%3,%4,%5,%6,%7,%8,%9,%10,%11,%12,%13,%14,%15}"
#define L32 "{%0,%1,%2,%3,%4,%5,%6,%7,%8,%9,%10,%11,%12,%13,%14,%15,%16,%17,%18,%19,%20,%21,%22,%23,%24,%25,%26,%27,%28,%29,%30,%31}"
__device__ __forceinline__ void fft_rows(uint32_t (&d)[32], const uint32_t (&a)[2][4], uint64_t db) {
  asm volatile("wgmma.mma_async.sync.aligned.m64n128k16.f16.f16.f16 " L32 ", {%32,%33,%34,%35}, %36, 0, 1, 1, 1;\n"
               : Q32("=r", d) : "r"(a[0][0]), "r"(a[0][1]), "r"(a[0][2]), "r"(a[0][3]), "l"(db));
  asm volatile("wgmma.mma_async.sync.aligned.m64n128k16.f16.f16.f16 " L32 ", {%32,%33,%34,%35}, %36, 1, 1, 1, 1;\n"
               : Q32("+r", d) : "r"(a[1][0]), "r"(a[1][1]), "r"(a[1][2]), "r"(a[1][3]), "l"(db + 64));
}
template <int INV> __device__ __forceinline__ void fft_cols(uint32_t (&d)[8], const uint32_t (&a)[2][4], uint64_t db) {
  asm volatile("wgmma.mma_async.sync.aligned.m64n32k16.f16.f16.f16 " L8 ", {%8,%9,%10,%11}, %12, 0, 1, 1, %13;\n"
               : Q8("=r", d, 0) : "r"(a[0][0]), "r"(a[0][1]), "r"(a[0][2]), "r"(a[0][3]), "l"(db), "n"(INV));
  asm volatile("wgmma.mma_async.sync.aligned.m64n32k16.f16.f16.f16 " L8 ", {%8,%9,%10,%11}, %12, 1, 1, 1, %13;\n"
               : Q8("+r", d, 0) : "r"(a[1][0]), "r"(a[1][1]), "r"(a[1][2]), "r"(a[1][3]), "l"(db + (INV ? 16 : 64)), "n"(INV));
}
__device__ __forceinline__ void fft_back(float (&d)[16], uint64_t da, uint64_t db) {
  asm volatile("wgmma.mma_async.sync.aligned.m64n32k16.f32.f16.f16 " L16 ", %16, %17, 0, 1, 1, 1, 1;\n"
               : Q16("=f", d, 0) : "l"(da), "l"(db));
#pragma unroll
  for (int i = 1; i < 4; i++)
    asm volatile("wgmma.mma_async.sync.aligned.m64n32k16.f32.f16.f16 " L16 ", %16, %17, 1, 1, 1, 1, 1;\n"
                 : Q16("+f", d, 0) : "l"(da + 32 * i), "l"(db + 64 * i));
}
__device__ __forceinline__ uint32_t hmul2(uint32_t a, uint32_t b) {
  uint32_t r;
  asm("mul.rn.f16x2 %0, %1, %2;\n" : "=r"(r) : "r"(a), "r"(b));
  return r;
}
__device__ __forceinline__ uint32_t hadd2(uint32_t a, uint32_t b) {
  uint32_t r;
  asm("add.rn.f16x2 %0, %1, %2;\n" : "=r"(r) : "r"(a), "r"(b));
  return r;
}
__device__ __forceinline__ uint32_t hneg2(uint32_t a) {
  uint32_t r;
  asm("neg.f16x2 %0, %1;\n" : "=r"(r) : "r"(a));
  return r;
}
__device__ __forceinline__ uint32_t hfma2(uint32_t a, uint32_t b, uint32_t c) {
  uint32_t r;
  asm("fma.rn.f16x2 %0, %1, %2, %3;\n" : "=r"(r) : "r"(a), "r"(b), "r"(c));
  return r;
}
__device__ __forceinline__ uint32_t pack_f16(float lo, float hi) {
  uint32_t r;
  asm("cvt.rn.f16x2.f32 %0, %1, %2;\n" : "=r"(r) : "f"(hi), "f"(lo));
  return r;
}
__device__ __forceinline__ uint32_t bmaxabs2(uint32_t a, uint32_t b) {
  uint32_t r;
  asm("max.xorsign.abs.bf16x2 %0, %1, %2;\n" : "=r"(r) : "r"(a), "r"(b));
  return r;
}
struct C2 { uint32_t r, i; };
__device__ __forceinline__ C2 cmul(C2 a, C2 b) {
  return C2{hfma2(a.r, b.r, hneg2(hmul2(a.i, b.i))), hfma2(a.r, b.i, hmul2(a.i, b.r))};
}
__device__ __forceinline__ C2 cfma(C2 a, C2 b, C2 c) {
  return C2{hfma2(a.r, b.r, hfma2(hneg2(a.i), b.i, c.r)), hfma2(a.r, b.i, hfma2(a.i, b.r, c.i))};
}
__device__ __forceinline__ C2 crot(C2 z, C2 t) {
  const uint32_t r = hfma2(t.r, z.i, z.r), i = hfma2(t.i, r, z.i);
  return C2{hfma2(t.r, i, r), i};
}
__device__ __forceinline__ C2 cget(const uint32_t (&e)[8], int j, int b) { return C2{e[4 * j + b], e[4 * j + 2 + b]}; }
template <int N> __device__ __forceinline__ void fence_regs(uint32_t (&d)[N]) {
#pragma unroll
  for (int i = 0; i < N; i++) asm volatile("" : "+r"(d[i])::"memory");
}
__device__ __forceinline__ void ldsm4(uint32_t (&r)[4], uint32_t a) {
  asm volatile("ldmatrix.sync.aligned.m8n8.x4.shared.b16 {%0,%1,%2,%3}, [%4];\n"
               : "=r"(r[0]), "=r"(r[1]), "=r"(r[2]), "=r"(r[3]) : "r"(a) : "memory");
}

__device__ __forceinline__ uint32_t movm(uint32_t a) {
  uint32_t r;
  asm volatile("movmatrix.sync.aligned.m8n8.trans.b16 %0, %1;\n" : "=r"(r) : "r"(a));
  return r;
}
template <int C0, int H, bool T> __device__ __forceinline__ void attn_pack(const float (&acc)[96], uint32_t (&d)[8]) {
#pragma unroll
  for (int c = 0; c < 8; c++) {
    asm volatile("cvt.rn.bf16x2.f32 %0, %1, %2;\n" : "=r"(d[c]) : "f"(acc[4 * (C0 + c) + 2 * H + 1]), "f"(acc[4 * (C0 + c) + 2 * H]));
    if (T) d[c] = movm(d[c]);
  }
}
__device__ __forceinline__ void attn_qk(float (&s)[4], const uint32_t (&qlo)[8], const uint32_t (&qhi)[8],
                                        const uint32_t (&k)[8], int c) {
  mma16816_z(s, qlo[c], qhi[c], qlo[c + 1], qhi[c + 1], k[c], k[c + 1]);
  mma16816(s, qlo[c + 2], qhi[c + 2], qlo[c + 3], qhi[c + 3], k[c + 2], k[c + 3]);
}
template <int N> __device__ __forceinline__ void quad_softmax(float (&x)[N][2], uint32_t (&pp)[N]) {
  const float c2 = 1.4426950408889634f;
  uint32_t q[N], mx[N / 2];
#pragma unroll
  for (int n = 0; n < N; n++) {
    const uint32_t r = pack_bf16(x[n][0], x[n][1]);
    q[n] = bfma2(r, 0x3e353e35u, bmul2(r, 0x379e379eu));
    x[n][0] = bf_lo(q[n]);
    x[n][1] = bf_hi(q[n]);
  }
#pragma unroll
  for (int n = 0; n < N / 2; n++)
    mx[n] = bmax2(__byte_perm(q[2 * n], q[2 * n + 1], 0x5410), __byte_perm(q[2 * n], q[2 * n + 1], 0x7632));
#pragma unroll
  for (int o = 1; o <= 2; o++) {
#pragma unroll
    for (int n = 0; n < N / 2; n++) mx[n] = bmax2(mx[n], __shfl_xor_sync(0xffffffffu, mx[n], o));
  }
  float m[N], t[N];
#pragma unroll
  for (int n = 0; n < N / 2; n++) {
    m[2 * n] = bf_lo(mx[n]);
    m[2 * n + 1] = bf_hi(mx[n]);
  }
#pragma unroll
  for (int n = 0; n < N; n++) {
    const float nm = -m[n] * c2;
    x[n][0] = ex2(fmaf(x[n][0], c2, nm));
    x[n][1] = ex2(fmaf(x[n][1], c2, nm));
  }
#pragma unroll
  for (int n = 0; n < N; n += 2) {
    float u0, u1;
    asm("mma.sync.aligned.m16n8k8.row.col.f32.tf32.tf32.f32 {%0,%1,%2,%3}, {%4,%5,%6,%7}, {%8,%8}, {%9,%9,%9,%9};\n"
        : "=f"(t[n]), "=f"(u0), "=f"(t[n + 1]), "=f"(u1)
        : "r"(__float_as_uint(x[n][0])), "r"(__float_as_uint(x[n + 1][0])), "r"(__float_as_uint(x[n][1])),
          "r"(__float_as_uint(x[n + 1][1])), "r"(0x3f800000u), "f"(0.f));
  }
#pragma unroll
  for (int n = 0; n < N; n++) {
    const float inv = rcp(t[n]);
    pp[n] = pack_bf16(x[n][0] * inv, x[n][1] * inv);
  }
}
template <bool SPLIT>
__device__ __forceinline__ void attn_pv(uint32_t dst, const uint32_t (&vp)[8], const uint32_t (&vo)[8], int c, uint32_t pp,
                                        uint32_t maskLE) {
  const uint32_t b0 = pp & ~maskLE, b1 = pp & maskLE;
  float o[2][4];
#pragma unroll
  for (int i = 0; i < 2; i++) {
    if (SPLIT) {
      asm("mma.sync.aligned.m16n8k8.row.col.f32.bf16.bf16.f32 {%0,%1,%2,%3}, {%4,%5}, {%6}, {%7,%7,%7,%7};\n"
          : "=f"(o[i][0]), "=f"(o[i][1]), "=f"(o[i][2]), "=f"(o[i][3])
          : "r"(vp[c + 2 * i]), "r"(vp[c + 2 * i + 1]), "r"(b0), "f"(0.f));
      asm("mma.sync.aligned.m16n8k8.row.col.f32.bf16.bf16.f32 {%0,%1,%2,%3}, {%4,%5}, {%6}, {%0,%1,%2,%3};\n"
          : "+f"(o[i][0]), "+f"(o[i][1]), "+f"(o[i][2]), "+f"(o[i][3])
          : "r"(vo[c + 2 * i]), "r"(vo[c + 2 * i + 1]), "r"(b1));
    } else {
      mma16816_z(o[i], vp[c + 2 * i], vp[c + 2 * i + 1], vo[c + 2 * i], vo[c + 2 * i + 1], b0, b1);
    }
  }
  stsm4t(dst, pack_bf16(o[0][0], o[0][1]), pack_bf16(o[0][2], o[0][3]), pack_bf16(o[1][0], o[1][1]),
         pack_bf16(o[1][2], o[1][3]));
}

template <int MODE>
__global__ void __cluster_dims__(2, 1, 1) __launch_bounds__(NTHREADS, 1)
fused_kernel(const Params p, const __grid_constant__ CUtensorMap tmX, const __grid_constant__ CUtensorMap tmW,
             const __grid_constant__ CUtensorMap tmWo, const __grid_constant__ CUtensorMap tmWp,
             const __grid_constant__ CUtensorMap tmQ,
             const __grid_constant__ CUtensorMap tmOb,
             const __grid_constant__ CUtensorMap tmXh, const __grid_constant__ CUtensorMap tmWh) {
  extern __shared__ __align__(1024) uint8_t smem[];
  const int tid = threadIdx.x;
  if (tid >= 352) {
    const uint32_t i = (blockIdx.x & 127) * 16 + (tid & 15);
    prefetch_l2(tid & 16 ? (const char*)p.w + i * 128 : (const char*)p.x + i * 2048);
  }
  const uint32_t sb = smem_u32(smem);
  const int rank = blockIdx.x & 1;
  const bool halo_cta = blockIdx.x < 4;
  if (halo_cta && MODE != 0) return;
  const int tile = p.tile[blockIdx.x >> 1];
  const int rg = tile >> 3, hp = (tile & 7) * 2 + rank;
  const int par = rg >> 2, gidx = rg & 3;
  if (tid < 256 && !halo_cta && MODE != 2) {
    const uint32_t r = (tid >> 3) & 15, c = tid & 7, h = tid >> 7, dst = sb + r * 128 + ((c ^ (r & 7)) << 4);
    if (!h) {
      asm volatile(
          "cp.async.cg.shared.global [%0 + 98304], [%1], 16;\ncp.async.cg.shared.global [%0 + 102400], [%1 + 2048], 16;\n"
          "cp.async.cg.shared.global [%0 + 106496], [%1 + 4096], 16;\ncp.async.cg.shared.global [%0 + 100352], [%1 + 98304], 16;\n"
          "cp.async.cg.shared.global [%0 + 104448], [%1 + 100352], 16;\ncp.async.cg.shared.global [%0 + 108544], [%1 + 102400], 16;\n"
          ::"r"(dst), "l"((const char*)p.w + (r * 6144 + c * 16 + hp * 128)) : "memory");
    }
    asm volatile(
        "cp.async.cg.shared.global [%0], [%1], 16;\ncp.async.cg.shared.global [%0 + 2048], [%1 + 65536], 16;\n"
        "cp.async.cg.shared.global [%0 + 4096], [%1 + 131072], 16;\ncp.async.cg.shared.global [%0 + 6144], [%1 + 196608], 16;\n"
        "cp.async.cg.shared.global [%0 + 8192], [%1 + 262144], 16;\ncp.async.cg.shared.global [%0 + 10240], [%1 + 327680], 16;\n"
        "cp.async.cg.shared.global [%0 + 12288], [%1 + 393216], 16;\ncp.async.cg.shared.global [%0 + 14336], [%1 + 458752], 16;\n"
        "cp.async.commit_group;\n"
        ::"r"(dst + h * 16384), "l"((const char*)p.x + (r * 4096 + c * 16 + h * 524288 + gidx * 1048576 + par * 2048)) : "memory");
    static_assert(OFF_1B == 98304, "offsets above");
  }
  const uint32_t bars = sb + OFF_BAR;
  const int lane = tid & 31, warp = __shfl_sync(0xffffffffu, tid >> 5, 0);
  const int grp = par * 4 + (hp >> 2), mem = gidx * 2 + ((hp >> 1) & 1);
  const int rb2 = par * 8 + mem, cb2 = (grp & 3) * 2 + rank;
  const int chb = grp * 16 + mem * 2 + rank;
  const int cta = rg * 16 + hp;
  const int hsel = rb2 & 1;

  if (warp >= 8) {
    asm volatile("setmaxnreg.dec.sync.aligned.u32 %0;\n" :: "n"(REG_HELP));
    auto halo_issue = [&](int n, int s) {
      const uint32_t fb = bars + 8 * ((n & 1 ? BAR_FULL2 : BAR_FULLB) + s), st = sb + s * STGH;
      tma_load_3d(st + 8192, &tmWh, fb, 0, (n >> 1) * 64, 16 + (n & 1) * 16 + blockIdx.x * 4);
      tma_load_4d(st, &tmXh, fb, (n >> 1) * 64, 248, 0, 0);
      mbar_expect_tx(fb, STGH - 2048);
    };
    if (tid == 256) {
      prefetch_tmap(halo_cta ? &tmXh : &tmX);
#pragma unroll
      for (int i = 0; i < NS1B; i++) mbar_init(bars + 8 * (BAR_FULLB + i), 1);
#pragma unroll
      for (int i = 0; i < NS1A; i++) mbar_init(bars + 8 * (BAR_FULLA + i), 1);
      asm volatile("fence.mbarrier_init.release.cluster;\n" ::: "memory");
      if (!halo_cta && MODE != 2) {
        mbar_expect_tx(bars + 8 * (BAR_FULLB + 1), STG1B);
        tma_load_3d(sb + OFF_1B + 1 * STG1B, &tmW, bars + 8 * (BAR_FULLB + 1), hp * 64, 32, 0);
        mbar_expect_tx(bars + 8 * (BAR_FULLA + 1), STG1A);
        tma_load_3d(sb + STG1A, &tmX, bars + 8 * (BAR_FULLA + 1), 64, par, gidx * 256);
        tma_load_3d(sb + STG1A + 16384, &tmX, bars + 8 * (BAR_FULLA + 1), 64, par, gidx * 256 + 128);
        mbar_expect_tx(bars + 8 * (BAR_FULLB + 2), STG1B);
        tma_load_3d(sb + OFF_1B + 2 * STG1B, &tmW, bars + 8 * (BAR_FULLB + 2), hp * 64, 64, 0);
        mbar_arrive(bars + 8 * BAR_FULLA);
        mbar_arrive(bars + 8 * BAR_FULLB);
      } else if (halo_cta) {
        halo_issue(0, 0);
      }
    } else if (tid >= 289 && tid < 289 + 48 && tid != 320) {
      const uint32_t i = tid - 289 - (tid > 320), b = blockIdx.x & 127;
      if (MODE != 2) prefetch_l2(i < 16 ? (const char*)p.x + (b * 16 + i) * 2048 + 128 : (const char*)p.w + (2048 + b * 31 + i - 16) * 128);
    } else if (tid == 288) {
#pragma unroll
      for (int i = 0; i < NS1A; i++) mbar_init(bars + 8 * (BAR_EMPTYA + i), 4);
#pragma unroll
      for (int i = 0; i < NS1B; i++) mbar_init(bars + 8 * (BAR_EMPTYB + i), 2);
      mbar_init(bars + 8 * BAR_X, 3);
      mbar_init(bars + 8 * BAR_TAB, 16);
      mbar_init(bars + 8 * BAR_U, 1);
      mbar_init(bars + 8 * BAR_H, 1);
      mbar_init(bars + 8 * BAR_Q, 1);
      mbar_init(bars + 8 * BAR_LAND, 5);
      mbar_init(bars + 8 * (BAR_LAND + 1), 5);
      asm volatile("fence.mbarrier_init.release.cluster;\n" ::: "memory");
    } else if (tid == 320) {
#pragma unroll
      for (int i = 0; i < NS2; i++) {
        mbar_init(bars + 8 * (BAR_FULL2 + i), 1);
        mbar_init(bars + 8 * (BAR_EMPTY2 + i), 2);
        mbar_init(bars + 8 * (BAR_EMPTY2B + i), 2);
      }
      asm volatile("fence.mbarrier_init.release.cluster;\n" ::: "memory");
    } else if (tid == 352) {
#pragma unroll
      for (int i = 0; i < 4; i++) mbar_init(bars + 8 * (BAR_Y + i), i < 2 ? 4 : i == 2 ? 10 : 8);
      mbar_init(bars + 8 * BAR_XFREE, 1);
#pragma unroll
      for (int i = 0; i < 9; i++) mbar_init(bars + 8 * (BAR_KH + i), 1);
      asm volatile("fence.mbarrier_init.release.cluster;\n" ::: "memory");
    }
    __syncwarp();
    cluster_sync_all();
    if (warp == 8) PROF2(24);
    const int hw = warp - 8;
    const int lr = lane & 7, lm = lane >> 3;
    auto g1_issue_a = [&](int j, int s) {
      const uint32_t fb = bars + 8 * (BAR_FULLA + s);
      mbar_expect_tx(fb, STG1A);
      tma_load_3d_mc(sb + s * STG1A + rank * 16384, &tmX, fb, j * 64, par, gidx * 256 + rank * 128);
    };
    auto g1_issue_b = [&](int kb, int s) {
      const uint32_t fb = bars + 8 * (BAR_FULLB + s);
      mbar_expect_tx(fb, STG1B);
      tma_load_3d(sb + OFF_1B + s * STG1B, &tmW, fb, hp * 64, kb * 32, 0);
    };
    auto g2_k = [&](int kb) { return (kb < 2 ? hp : kb < 4 ? hp & 14 : hp & 12) ^ kb; };
    auto g2_issue_b = [&](uint32_t fb, uint32_t bytes, uint32_t dst, int k0, bool whole) {
      if (whole) {
        tma_load_3d(dst, &tmWo, fb, 0, k0, cb2 * 2);
      } else {
#pragma unroll
        for (int i = 0; i < 4; i++)
          tma_load_3d(dst + (i & 1) * XT + (i >> 1) * 4 * XT, &tmWp, fb, 0, k0 + (i >> 1) * 32, cb2 * 2 + (i & 1));
      }
      mbar_expect_tx(fb, bytes);
    };
    auto send_y = [&](uint32_t o, uint32_t step, int half, auto read) {
      const uint32_t peer = mapa(sb, rank ^ 1);
      o += OFF_X + (rank ^ 1) * 4096 + half * 2048 + lane * 16;
      uint4 a[8];
      uint32_t z = p.zero;
#pragma unroll
      for (int i = 0; i < 8; i++) {
        a[i] = lds128(sb + o + (i >> 2) * step + (i & 2) * (XT / 2) + (i & 1) * 512);
        z &= a[i].x;
      }
      read(z);
#pragma unroll
      for (int i = 0; i < 8; i++)
        st_async128(peer + o + 1024 + (i >> 2) * step + (i & 2) * (XT / 2) + (i & 1) * 512,
                    peer + OFF_BAR + 8 * (BAR_LAND + half), a[i].x, a[i].y, a[i].z, a[i].w);
    };

    if (halo_cta) {
      if (hw == 0) {
        int s = 1, ph = 1;
#pragma unroll 1
        for (int n = 1; n < 32; n++) {
          mbar_wait(bars + 8 * (BAR_EMPTYB + s), ph);
          if (elect_one()) halo_issue(n, s);
          if (++s == NS1B) { s = 0; ph ^= 1; }
        }
      }
      __syncwarp();
    } else if (hw == 0) {
      uint32_t epoch = 0;
      if (MODE == 2) {
        if (lane < NS2) mbar_arrive_cluster_n(mapa(bars, rank) + 8 * (BAR_EMPTY2 + lane), 2);
      } else {
      if (lane == 0) {
        mbar_expect_tx(bars + 8 * BAR_U, 32768);
        mbar_expect_tx(bars + 8 * BAR_LAND, 8192);
        mbar_expect_tx(bars + 8 * (BAR_LAND + 1), 8192);
        mbar_expect_tx(bars + 8 * BAR_Q, 32768);
        prefetch_tmap(&tmQ);
      }
      {
        int sa = 2, pha = 1, sbb = 3, phb = 1;
#pragma unroll 1
        for (int kb = 3; kb < 32; kb++) {
          if (!(kb & 1)) {
            mbar_wait(bars + 8 * (BAR_EMPTYA + sa), pha);
            if (elect_one()) g1_issue_a(kb >> 1, sa);
            if (++sa == NS1A) { sa = 0; pha ^= 1; }
          }
          mbar_wait(bars + 8 * (BAR_EMPTYB + sbb), phb);
          if (elect_one()) g1_issue_b(kb, sbb);
          __syncwarp();
          if (kb == 4) epoch = ld_relaxed(g_flag_o + FS * cta);
          if (kb == 4) PROF2(27);
          if (++sbb == NS1B) { sbb = 0; phb ^= 1; }
        }
      }
      auto q_issue = [&](int i) {
        mbar_wait(bars + 8 * (i ? BAR_EMPTYB + 3 : BAR_EMPTYA + 1), i);
        if (elect_one())
          asm volatile(
              "cp.async.bulk.tensor.5d.shared::cluster.global.mbarrier::complete_tx::bytes [%0], [%1, {%3, %4, %4, %4, %5}], [%2];\n"
              ::"r"(sb + (i ? OFF_Q1 : OFF_Q0)), "l"(&tmQ), "r"(bars + 8 * BAR_Q), "r"((chb & ~1) * 8), "r"(0), "r"(rank * 32 + i * 64)
              : "memory");
        __syncwarp();
      };
      epoch++;
      if (lane == 0) {
        asm volatile("st.shared.u32 [%0], %1;\n" ::"r"(sb + OFF_EX - 4), "r"(epoch) : "memory");
        prefetch_tmap(&tmWo);
        prefetch_tmap(&tmWp);
        prefetch_tmap(&tmOb);
      }
      __syncwarp();
      {
        uint4 h[6] = {};
        if (gidx != 0) {
#pragma unroll 1
          for (int n = 0; n < SPIN_LIMIT; n++) {
            bool ok = true;
#pragma unroll
            for (int i = 0; i < 6; i++) h[i] = ld_b128(g_halo + cta * 192 + i * 32 + lane);
#pragma unroll
            for (int i = 0; i < 6; i++) ok = ok && h[i].w == epoch;
            if (__all_sync(0xffffffffu, ok)) break;
          }
          PROF(18);
        }
        q_issue(0);
        sts128(sb + OFF_KH + lane * 16, h[0].x, h[0].y, h[0].z, h[1].x);
        sts128(sb + OFF_KH + 512 + lane * 16, h[1].y, h[1].z, h[2].x, h[2].y);
        sts64(sb + OFF_KH + 1024 + lane * 8, h[3].x, h[3].y);
        sts64(sb + OFF_KH + 1280 + lane * 8, h[3].z, h[4].x);
        sts64(sb + OFF_KH + 1536 + lane * 8, h[4].y, h[4].z);
        sts64(sb + OFF_KH + 1792 + lane * 8, h[5].x, h[5].y);
        __syncwarp();
        if (lane == 0) mbar_arrive(bars + 8 * BAR_KH);
      }
      q_issue(1);
      const uint32_t rb = mapa(bars, lane & 1);
      nb_sync(NB_OREADY, 288);
      if (lane == 0) {
        asm volatile("cp.async.bulk.global.shared::cta.bulk_group [%0], [%1], %2;\n" ::"l"(g_o + (size_t)cta * 16384),
                     "r"(sb + OFF_OP), "r"(32768) : "memory");
        bulk_commit();
      }
      if (lane < 2) {
#pragma unroll
        for (int i = 0; i < 4; i++) mbar_arrive_cluster(rb + 8 * (BAR_EMPTY2 + i + i / 2));
      }
      if (lane == 0) {
        bulk_wait0();
        asm volatile("fence.acq_rel.gpu;\nst.relaxed.gpu.global.u32 [%0], %1;\n"
                     "mbarrier.arrive.relaxed.cluster.shared::cluster.b64 _, [%2];\n"
                     "mbarrier.arrive.relaxed.cluster.shared::cluster.b64 _, [%3];\n"
                     ::"l"(g_flag_o + FS * cta), "r"(epoch), "r"(mapa(bars, rank ^ 1) + 8 * (BAR_EMPTY2 + 2)),
                     "r"(mapa(bars, rank) + 8 * (BAR_EMPTY2 + 2)) : "memory");
      }
      __syncwarp();
      PROF2(17);
      }
      if (MODE != 1) {
        const __nv_bfloat16* osrc = g_o + (size_t)(rb2 >> 1) * 16 * 16384 + hsel * 8192;
        if (elect_one()) {
          if (MODE != 0) bulk_load(sb + g2_a(0, hsel), osrc + hp * 16384, 16384, bars + 8 * BAR_FULL2);
#pragma unroll
          for (int kb = 1; kb < 3; kb++)
            g2_issue_b(bars + 8 * (BAR_FULL2 + kb), STG2, sb + g2_b(kb, 0), g2_k(kb) * 64, true);
        }
        mbar_wait(bars + 8 * (BAR_EMPTY2 + 2), 0);
        asm volatile("{\n.reg .pred p;\nmbarrier.test_wait.parity.acquire.cluster.shared::cta.b64 p, [%0], 0;\n}\n"
                     ::"r"(bars + 8 * (BAR_EMPTY2 + 2)) : "memory");
        fence_async_all();
        if (elect_one()) bulk_load(sb + g2_a(1, hsel), osrc + (hp ^ 1) * 16384, 16384, bars + 8 * (BAR_FULL2 + 1));
        __syncwarp();
      }
      if (MODE != 2) {
        mbar_wait(bars + 8 * (BAR_Y + 2), 0);
        send_y(0, 4 * XT, 1, [&](uint32_t) {
          fence_async_smem();
          __syncwarp();
          if (MODE == 0 && elect_one()) g2_issue_b(bars + 8 * (BAR_FULL2 + 3), STG2, sb + g2_b(3, rank), g2_k(3) * 64, false);
          __syncwarp();
        });
      }
      if (MODE != 1) {
        constexpr int K0 = MODE ? 3 : 4;
        int s = K0, k0 = g2_k(K0) * 64;
        uint32_t wbar = bars + 8 * BAR_XFREE, fb = bars + 8 * (BAR_FULL2 + K0), dst = sb + g2_b(K0, rank), ph = MODE ? 1 : 0;
        int whole = 0;
#pragma unroll 1
        for (int kb = K0; kb < 16;) {
          mbar_wait(wbar, ph);
          if (kb == 4) fence_async_smem();
          if (elect_one()) g2_issue_b(fb, STG2, dst, k0, whole);
          __syncwarp();
          kb++;
          if (++s == NS2) { s = 0; ph = kb == 2 * NS2; }
          wbar = bars + 8 * (BAR_EMPTY2B + s);
          fb = bars + 8 * (BAR_FULL2 + s);
          dst = sb + g2_b(s, rank);
          k0 = ((hp & 12) ^ kb) * 64;
          whole = s < 3;
          asm volatile("" : "+r"(fb), "+r"(k0), "+r"(whole));
        }
      }
      __syncwarp();
    } else {
      if (MODE != 2) {
      const float dall = __bfloat162float(p.ssm_D[chb * 8 + lr]);
      {
        const int g = lane >> 2, t = lane & 3;
        uint32_t w[2][4];
#pragma unroll
        for (int h = 0; h < 2; h++) {
          const uint2 x = __ldg(reinterpret_cast<const uint2*>(p.shift_k + ((chb & ~1) * 8 + h * 8 + g) * 4));
          w[h][0] = __byte_perm(x.x, x.x, 0x1010);
          w[h][1] = __byte_perm(x.x, x.x, 0x3232);
          w[h][2] = __byte_perm(x.y, x.y, 0x1010);
          w[h][3] = __byte_perm(x.y, x.y, 0x3232);
        }
        auto swz = [](int r) { return (((r & 29) | ((r ^ (r >> 2)) & 2)) << 5) | (r & 16); };
        const uint32_t kring = sb + OFF_X + 4096 + (hw - 1) * 2 * XT, vring = kring + XT;
        const int s0 = rank * 32 + (hw - 1) * 11, s1 = hw == 3 ? rank * 32 + 32 : s0 + 11;
        const size_t goff = (size_t)(s0 * 32 + (lane >> 1)) * DM + (chb & ~1) * 8 + (lane & 1) * 8;
        const __nv_bfloat16* kg = p.k + goff;
        const __nv_bfloat16* vg = p.v + goff;
        const uint32_t d0 = swz(lane >> 1) ^ ((lane & 1) << 4), d1 = swz(16 + (lane >> 1)) ^ ((lane & 1) << 4);
        auto issue = [&](int st) {
          const uint32_t a = kring + ((st & 3) << 10);
          asm volatile("cp.async.cg.shared.global.L2::256B [%0], [%2], 16;\n"
                       "cp.async.cg.shared.global.L2::256B [%1], [%2 + 32768], 16;\n"
                       "cp.async.cg.shared.global.L2::256B [%0 + 8192], [%3], 16;\n"
                       "cp.async.cg.shared.global.L2::256B [%1 + 8192], [%3 + 32768], 16;\n"
                       ::"r"(a + d0), "r"(a + d1), "l"(kg), "l"(vg) : "memory");
          kg += 32 * DM;
          vg += 32 * DM;
          asm volatile("" : "+l"(kg), "+l"(vg));
        };
        const int xa = 8 * (lr >> 1) + 2 * lm + (lr & 1), xb = 8 * (lr >> 1) - 4 + 2 * (lm & 1) + (lr & 1);
        const uint32_t la = swz(xa), lb = swz(xb & 31);
        const int backb = xb < 0 ? 1 : 0;
        const uint32_t ud[2] = {mapa(sb + OFF_X + g * XT + t * 16, 0), mapa(sb + OFF_X + g * XT + t * 16, 1)};
        const uint32_t ub[2] = {mapa(bars + 8 * BAR_U, 0), mapa(bars + 8 * BAR_U, 1)};
        if (tid == 320) prefetch_l2(g_tab + (chb & 63) * 32);
        if (lane == 0) mbar_wait(bars + 8 * (BAR_FULLB + NS1B - 1), 0);
        __syncwarp();
        if (lane >= 24) cp_async16(kring + (((s0 - 1) & 3) << 10) + d1, s0 > 0 ? kg - 16 * DM : kg, s0 > 0 ? 16 : 0);
        issue(s0);
        asm volatile("cp.async.commit_group;\n" ::: "memory");
        issue(s0 + 1);
        asm volatile("cp.async.commit_group;\n" ::: "memory");
        const __nv_bfloat16* hg = p.ssm_k + (size_t)chb * 8 * SEQ + lane * 64;
        uint32_t tn = clock32();
#pragma unroll 1
        for (int st = s0; st < s1; st++) {
          tn += PSTEP;
          while ((int)(clock32() - tn) < 0) __nanosleep(100);
          if (st + 2 < s1) issue(st + 2);
          if (hw == 1 && st - s0 < 8) prefetch_l2(hg);
          hg += SEQ;
          asm volatile("" : "+l"(hg));
          asm volatile("cp.async.commit_group;\n" ::: "memory");
          asm volatile("cp.async.wait_group 2;\n" ::: "memory");
          __syncwarp();
#pragma unroll
          for (int h = 0; h < 2; h++) {
            uint32_t e[6], vv[4], e4[4];
            ldsm4t(e4, kring + ((st & 3) << 10) + (la ^ (h << 4)));
            ldsm2t(e[0], e[1], kring + (((st - backb) & 3) << 10) + (lb ^ (h << 4)));
            ldsm4t(vv, vring + ((st & 3) << 10) + (la ^ (h << 4)));
            e[2] = e4[0]; e[3] = e4[1]; e[4] = e4[2]; e[5] = e4[3];
            uint32_t o[5];
#pragma unroll
            for (int i = 0; i < 5; i++) o[i] = __byte_perm(e[i], e[i + 1], 0x5432);
#pragma unroll
            for (int i = 0; i < 4; i++) {
              uint32_t a = bmul2(o[i], w[h][3]);
              a = bfma2(e[i + 1], w[h][2], a);
              a = bfma2(o[i + 1], w[h][1], a);
              a = bfma2(e[i + 2], w[h][0], a);
              vv[i] = bmul2(a, vv[i]);
            }
            st_async128(ud[h] + (st ^ (g & 1)) * 64, ub[h], vv[0], vv[1], vv[2], vv[3]);
          }
          __syncwarp();
        }
        fence_async_smem();
        PROF(16);
      }
      nb_sync(NB_HELP3, 96);
      if (hw == 1 && elect_one()) {
        mbar_expect_tx(bars + 8 * BAR_H, 8 * 4096 + 6144);
#pragma unroll 1
        for (int c = 0; c < 8; c++)
          bulk_load(sb + OFF_X + c * XT + 4096, p.ssm_k + (size_t)(chb * 8 + c) * SEQ, 4096, bars + 8 * BAR_H);
        bulk_load(sb + OFF_T16, g_tab, 2048, bars + 8 * BAR_H);
        bulk_load(sb + OFF_T32, g_tab + 512, 4096, bars + 8 * BAR_H);
      }
      __syncwarp();
      {
        if (hw == 3) {
          const char* wo = (const char*)p.wo + chb * 16384 + lane * 128;
#pragma unroll
          for (int i = 0; i < 4; i++) prefetch_l2(wo + i * 4096);
        }
        const int ck = 16 * (lane >> 4) + 2 * lr + (((lane >> 3) ^ (lane >> 2)) & 1);
        const uint32_t xo = (ck >> 1) * 64, xs = ((ck & 1) ^ (lr >> 1)) << 4;
#pragma unroll 1
        for (int job = hw - 1; job < 16; job += 3) {
          const int c = job & 7;
          uint4 a[8];
          float dv = __shfl_sync(0xffffffffu, dall, c);
          if (job < 8 || lane) dv = 0.f;
          const uint32_t xt = sb + OFF_X + c * XT + (job >> 3) * 4096;
          mbar_wait(bars + 8 * (job < 8 ? BAR_U : BAR_H), 0);
#pragma unroll
          for (int i = 0; i < 8; i++) a[i] = lds128(xt + i * 512 + ((ck ^ (job < 8 ? (c & 1) << 2 : 0)) << 4));
          dv += bf_lo(a[0].x);
          uint32_t m[2] = {bmaxabs2(pack_bf16(dv, 0.f), bmaxabs2(a[0].x, a[0].y)), bmaxabs2(a[0].z, a[0].w)};
#pragma unroll
          for (int i = 1; i < 8; i++) {
            m[0] = bmaxabs2(bmaxabs2(m[0], a[i].x), a[i].y);
            m[1] = bmaxabs2(bmaxabs2(m[1], a[i].z), a[i].w);
          }
          m[0] = bmaxabs2(m[0], m[1]);
          const int f = max(252 - (int)(__reduce_max_sync(0xffffffffu, max(m[0] & 0x7fffu, (m[0] >> 16) & 0x7fffu)) >> 7), 1);
          if (lane == 0) asm volatile("st.shared.u32 [%0], %1;\n" ::"r"(sb + OFF_EX + job * 4), "r"(f) : "memory");
          if (f < 113) {
#pragma unroll
            for (int i = 0; i < 8; i++)
              a[i] = make_uint4(bmul2(a[i].x, f * 0x00800080u), bmul2(a[i].y, f * 0x00800080u), bmul2(a[i].z, f * 0x00800080u),
                                bmul2(a[i].w, f * 0x00800080u));
          }
          const uint32_t mul = (f < 113 ? 15 : f - 112) * 0x00800080u;
          auto cv = [&](uint32_t x) {
            x = bmul2(x, mul);
            return (x & 0x0fff0fffu) * 7 + x;
          };
          const uint32_t dst = xt + xo;
#pragma unroll
          for (int i = 0; i < 8; i++)
            sts128(dst + (i >> 2) * 2048 + (i & 1) * 1024 + (xs ^ ((i & 2) << 4)),
                   i ? cv(a[i].x) : __byte_perm(pack_f16(dv * __uint_as_float(f << 23), 0.f), cv(a[i].x), 0x7610), cv(a[i].y),
                   cv(a[i].z), cv(a[i].w));
        }
        fence_async_smem();
        __syncwarp();
        if (lane == 0) mbar_arrive(bars + 8 * BAR_X);
        PROF(19);
      }
      if (hw < 3) {
        int lane, lr, lm;
        asm volatile("mov.u32 %0, %%laneid;\n" : "=r"(lane));
        lr = lane & 7;
        lm = lane >> 3;
#pragma unroll 1
        for (int n = 0; n < SPIN_LIMIT && !mbar_try(bars + 8 * (BAR_Y + hw - 1), 0); n++) __nanosleep(100);
        send_y((hw - 1) * 4 * XT, 2 * XT, 0, [](uint32_t) {});
        __syncwarp();
        if (lane == 0) mbar_arrive(bars + 8 * (BAR_Y + 2));
        PROF(32);
        const int c8 = 2 * lm + (lr & 1), src = (lr >> 1) & 1;
        uint32_t fa = sb + OFF_X + c8 * XT + rank * 4096 + (src == rank ? 0 : 1024) + (hw - 1) * 512;
        const uint32_t fx = ((lr >> 2) ^ ((lr & 3) << 1)) << 4;
        uint32_t qa = sb + OFF_Q0 + (hw - 1) * 8192 + (lane >> 3) * 128 + (lane & 2) * 32 + (lane & 4) * 8 + (lane & 1) * 16;
        uint4* og = reinterpret_cast<uint4*>(p.out + (size_t)(rank * 512 + (hw - 1) * 256 + (lane & 2) * 4 + (lane >> 2)) * (2 * DM) +
                                             (chb & ~1) * 8 + (lane & 1) * 8);
        mbar_wait(bars + 8 * BAR_Q, 0);
        uint32_t tn = 0;
        const uint32_t pace = hw == 2 ? FPACE2 : FPACE;
#pragma unroll 1
        for (int j = 0; j < 4; j++) {
          if (!(j & 1)) {
            mbar_wait(bars + 8 * (BAR_LAND + (j >> 1)), 0);
            tn = clock32() + (j ? 0 : (hw - 1) * (FPACE / 2));
            PROF2(33 + j * 2);
          }
#pragma unroll
          for (int i = 0; i < 8; i++) {
            if (i == 3 && j == 0 && hw == 2) {
              mbar_wait(bars + 8 * (BAR_Y + 3), 0);
              send_y(2 * XT, 4 * XT, 1, [&](uint32_t z) {
                __syncwarp();
                if (lane == 0) mbar_arrive(bars + 8 * BAR_XFREE + z);
              });
              tn = clock32();
            }
            uint32_t y[4];
            const uint4 q = lds128(qa + i * 512);
            ldsm4t(y, fa + (i >> 2) * 128 + (fx ^ ((i & 3) << 5) ^ ((i >> 2) << 4)));
            while ((int)(clock32() - tn) < 0) __nanosleep(50);
            tn += j == 3 ? FPACE3 : pace;
            og[i * 16 * (2 * DM / 8)] = make_uint4(bmul2(q.x, y[0]), bmul2(q.y, y[1]), bmul2(q.z, y[2]), bmul2(q.w, y[3]));
          }
          qa += j & 1 ? OFF_Q1 - OFF_Q0 - 4096 : 4096;
          fa += j & 1 ? 2048 - 256 : 256;
          og += (j & 1 ? 1024 - 128 : 128) * (2 * DM / 8);
        }
        PROF(22);
      }
      }
      if (MODE != 1 && hw == 3) {
        if (MODE == 0) nb_sync(NB_G1END, 288);
        if (elect_one()) g2_issue_b(bars + 8 * BAR_FULL2, MODE ? STG2 : STG2 / 2, sb + g2_b(0, 0), hp * 64, true);
        __syncwarp();
        const __nv_bfloat16* osrc = g_o + (size_t)(rb2 >> 1) * 16 * 16384 + hsel * 8192;
        if (MODE == 0) __nanosleep(1500);
        mbar_wait(bars + 8 * (BAR_EMPTY2 + 2), 0);
        const uint32_t epoch = lds32(sb + OFF_EX - 4);
        const uint32_t* flag = g_flag_o + FS * ((rb2 >> 1) * 16 + g2_k(lane & 15));
        uint32_t ready = MODE == 0 ? 0u : ~0u;
        int s = 1, ph = 0;
#pragma unroll 1
        for (int kb = 2; kb < 16; kb++) {
          if (++s == NS2) { s = 0; ph ^= 1; }
          uint32_t fb = bars + 8 * (BAR_FULL2 + s), dst = sb + g2_a(s, hsel) + rank * 8192;
          const __nv_bfloat16* src = osrc + rank * 4096 + (uint32_t)g2_k(kb) * 16384;
          asm volatile("" : "+r"(fb), "+r"(dst), "+l"(src));
          if (!(ready >> kb & 1)) {
#pragma unroll 1
            for (int n = 0; n < SPIN_LIMIT && !(ready >> kb & 1); n++)
              ready = __ballot_sync(0xffffffffu, ld_acquire(flag) == epoch);
            fence_async_all();
          }
          if (kb == 2) PROF(21);
          if (MODE == 0 && kb == 4 && rank == 1) mbar_wait(bars + 8 * BAR_TAB, 0);
          mbar_wait(fb + 8 * (BAR_EMPTY2 - BAR_FULL2), ph);
          if (elect_one()) {
            asm volatile(
                "cp.async.bulk.shared::cluster.global.mbarrier::complete_tx::bytes.multicast::cluster [%0], [%1], %2, [%3], %4;\n"
                ::"r"(dst), "l"(src), "r"(8192), "r"(fb), "h"((uint16_t)3) : "memory");
          }
          __syncwarp();
        }
      }
    }
    cluster_sync_all();
    PROF_DUMP();
  } else {
    asm volatile("barrier.cluster.arrive.relaxed.aligned;\n" ::: "memory");
    asm volatile("setmaxnreg.inc.sync.aligned.u32 %0;\n" :: "n"(REG_MATH));
    if (halo_cta || MODE == 2) asm volatile("barrier.cluster.wait.aligned;\n" ::: "memory");
    if (warp == 0) PROF2(26);
    const int wg = warp >> 2;
    const int wtid = tid & 127;
    const bool signaller = (wtid == 0) || (wtid == 32);
    const uint32_t rbars = mapa(bars, wtid >> 5 & 1);

    if (halo_cta) {
      const uint32_t epoch = ld_relaxed(g_flag_o + FS * (16 + blockIdx.x * 4)) + 1;
      float acc0[64], acc1[64];
      int s = wg, ph = 0;
#pragma unroll 1
      for (int kb = 0; kb < 16; kb++) {
        mbar_wait(bars + 8 * ((wg ? BAR_FULL2 : BAR_FULLB) + s), ph);
        const uint32_t st = sb + s * STGH;
        const uint64_t da = mkdesc(st, 16, 1024, 1);
        const uint64_t db = mkdesc(st + 8192, 8192, 1024, 1);
        wg_fence();
#pragma unroll
        for (int kk = 0; kk < 4; kk++) {
          wgmma_n128(acc0, da + 2 * kk, db + 128 * kk, kb + kk);
          wgmma_n128(acc1, da + 2 * kk, db + 1024 + 128 * kk, kb + kk);
        }
        wg_commit();
        wg_wait<0>();
        if (kb == 15) PROF(37);
        if (wtid < 2) mbar_arrive(bars + 8 * (BAR_EMPTYB + s));
        if ((s += 2) >= NS1B) s -= NS1B;
        if (s == wg) ph ^= 1;
      }
      fence_regs(acc0);
      fence_regs(acc1);
      if ((warp & 3) != 3) {
        auto put = [&](const float (&acc)[64], int hp0) {
#pragma unroll
          for (int n = 0; n < 4; n++) {
            uint32_t x[8];
#pragma unroll
            for (int c = 0; c < 8; c++) {
              x[c] = pack_bf16(acc[32 * (n >> 1) + 4 * c + 2 * (n & 1)], acc[32 * (n >> 1) + 4 * c + 2 * (n & 1) + 1]);
              if (wg) x[c] = movm(x[c]);
            }
            uint4* dst = g_halo + (((n & 1) * 4 + (warp & 3) + 1) * 16 + blockIdx.x * 4 + hp0 + (n >> 1)) * 192 + wg * 96 + lane;
            st_b128(dst, x[0], x[1], x[2], epoch);
            st_b128(dst + 32, x[3], x[4], x[5], epoch);
            st_b128(dst + 64, x[6], x[7], 0, epoch);
          }
        };
        put(acc0, 0);
        put(acc1, 2);
      }
      PROF(36);
      cluster_sync_all();
      return;
    }

    float acc[64];
    const uint32_t g2rel = wtid ? mapa(bars, rank) + 8 * BAR_EMPTY2B : mapa(bars, wg) + 8 * BAR_EMPTY2;
    uint32_t g2a = (uint32_t)mkdesc(sb + wg * 8192, 16, 0, 0), g2b = (uint32_t)mkdesc(sb, 8192, 0, 0);
    auto g2_block = [&](bool first, int s, int ph) {
      mbar_wait(bars + 8 * (BAR_FULL2 + s), ph);
      const uint32_t da = g2a + (g2_a(s, hsel) >> 4), db = g2b + (g2_b(s, rank) >> 4), dc = db + (g2_bk(s) >> 4);
      wg_fence();
      if (first) wgmma_n128z(acc, da, db);
      else wgmma_n128a(acc, da, db);
      wgmma_n128a(acc, da + 2, db + 128);
      wgmma_n128a(acc, da + 4, dc);
      wgmma_n128a(acc, da + 6, dc + 128);
      wg_commit();
    };
    if (MODE != 2) {
    uint32_t a1[2][4], sc[2];
    C2 t[2];
    {
      float acc0[96], acc1[96];
      int sa = 0, pha = 0;
      uint64_t db0 = mkdesc(sb + OFF_1B, 4096, 1024, 1);
      const uint64_t da0 = mkdesc(sb + wg * 16384, 16, 2048, 1);
      const bool sigb = wtid == 64;
      uint32_t rela = 0;
#pragma unroll 1
      for (int r = 0; r < 3; r++) {
#pragma unroll
        for (int i = 0; i < 2 * NS1B; i++) {
          if (i == 2 * NS1B - 1 && r == 2) break;
          const uint64_t da = da0 + sa * (STG1A >> 4) + (i & 1) * 4, db = db0 + (i % NS1B) * (STG1B >> 4);
          if (i || r) {
            if (!(i & 1)) mbar_wait(bars + 8 * (BAR_FULLA + sa), pha);
            mbar_wait(bars + 8 * (BAR_FULLB + i % NS1B), i / NS1B);
          } else {
            asm volatile("cp.async.wait_group 0;\n" ::: "memory");
            fence_async_smem();
            if (wg == 0) {
              nb_arrive(NB_FIRST, 256);
              nb_sync(NB_CONV, 128);
            } else {
              nb_sync(NB_FIRST, 256);
            }
            PROF(0 + wg);
          }
          wg_fence();
          wgmma_n192(acc0, da + 64, db, i ? 1 : r);
          wgmma_n192(acc1, da, db, i ? 1 : r);
          wgmma_n192(acc0, da + 66, db + 128, 1);
          wgmma_n192(acc1, da + 2, db + 128, 1);
          wg_commit();
          wg_wait<1>();
          if (i || r) {
            if (sigb) mbar_arrive(bars + 8 * (BAR_EMPTYB + (i + NS1B - 1) % NS1B));
            if (!(i & 1) && signaller) mbar_arrive_cluster(rela);
          } else {
            asm volatile("barrier.cluster.wait.aligned;\n" ::: "memory");
          }
          if (i & 1) {
            rela = rbars + 8 * (BAR_EMPTYA + sa);
            if (++sa == NS1A) { sa = 0; pha ^= 1; }
          }
        }
        db0 += p.zero;
      }
      const int lr = lane & 7, lm = lane >> 3;
      const bool le0 = 2 * (lane & 3) <= (lane >> 2), le1 = 2 * (lane & 3) + 1 <= (lane >> 2);
      const uint32_t maskLE = (le0 ? 0x0000FFFFu : 0u) | (le1 ? 0xFFFF0000u : 0u);
      uint32_t q[4][8], k[5][8], vt[5][8];
      {
        static_assert(15 % NS1A == 0 && 30 % NS1B == 0, "slots of the last k blocks");
        const uint64_t da = mkdesc(sb + wg * 16384, 16, 2048, 1);
        const uint64_t db = mkdesc(sb + OFF_1B, 4096, 1024, 1);
        auto last = [&](float (&acc)[96], int ro, int i0, int i1) {
#pragma unroll
          for (int i = i0; i < i1; i++)
            wgmma_n192(acc, da + ro + (i < 2 ? 2 * (STG1A >> 4) + 4 + 2 * i : 2 * i - 4),
                       db + (i < 2 ? 4 : (i >> 1) - 1) * (STG1B >> 4) + (i & 1) * 128, 1);
          wg_commit();
        };
        mbar_wait(bars + 8 * (BAR_FULLB + 4), 1);
        wg_fence();
        last(acc0, 64, 0, 2);
        asm volatile("ld.volatile.global.v4.u32 {%0,%1,%2,%3}, [%4];\n"
                     : "=r"(t[0].r), "=r"(t[1].r), "=r"(t[0].i), "=r"(t[1].i) : "l"(g_tab + 1536 + wtid * 4) : "memory");
        mbar_wait(bars + 8 * BAR_FULLA, 1);
        mbar_wait(bars + 8 * BAR_FULLB, 0);
        mbar_wait(bars + 8 * (BAR_FULLB + 1), 0);
        wg_fence();
        last(acc0, 64, 2, 6);
        wg_wait<2>();
        if (sigb) mbar_arrive(bars + 8 * (BAR_EMPTYB + 3));
        mbar_wait(bars + 8 * (BAR_EMPTYA + 1), 0);
        mbar_wait(bars + 8 * BAR_H, 0);
        wg_fence();
        last(acc1, 0, 0, 4);
        wg_wait<1>();
        fence_regs(acc0);
        PROFA(45, 0);
        attn_pack<8, 1, false>(acc0, k[4]);
        attn_pack<16, 1, true>(acc0, vt[4]);
        const uint32_t kh = sb + (warp == 7 ? OFF_1B + 2 * STG1B : OFF_KH + (warp + 1) * 2048) + lane * 16;
        sts128(kh, k[4][0], k[4][1], k[4][2], k[4][3]);
        sts128(kh + 512, k[4][4], k[4][5], k[4][6], k[4][7]);
#pragma unroll
        for (int i = 0; i < 4; i++) sts64(kh - lane * 8 + 1024 + 256 * i, vt[4][2 * i], vt[4][2 * i + 1]);
        __syncwarp();
        if (lane == 0) mbar_arrive(bars + 8 * (BAR_KH + 1 + warp));
        last(acc1, 0, 4, 6);
        attn_pack<0, 0, false>(acc0, q[1]);
        attn_pack<0, 1, false>(acc0, q[3]);
        attn_pack<8, 0, false>(acc0, k[2]);
        attn_pack<16, 0, true>(acc0, vt[2]);
        uint32_t z = p.zero;
#pragma unroll
        for (int i = 0; i < 8; i++) z &= q[1][i] & q[3][i];
#pragma unroll
        for (int i = 0; i < 8; i += 2) z &= k[2][i] & k[2][i + 1];
        mbar_wait(bars + 8 * (BAR_KH + warp) + z, 0);
        {
          const uint32_t kh = sb + OFF_KH + warp * 2048 + lane * 16;
#pragma unroll
          for (int i = 0; i < 2; i++) {
            const uint4 t = lds128(kh + 512 * i);
            k[0][4 * i] = t.x; k[0][4 * i + 1] = t.y; k[0][4 * i + 2] = t.z; k[0][4 * i + 3] = t.w;
          }
#pragma unroll
          for (int i = 0; i < 4; i++) {
            const uint2 t = lds64(kh - lane * 8 + 1024 + 256 * i);
            vt[0][2 * i] = t.x; vt[0][2 * i + 1] = t.y;
          }
        }
        wg_wait<0>();
        fence_regs(acc1);
        if (MODE == 0) nb_arrive(NB_G1END, 288);
      }
      PROF(2 + wg);
      attn_pack<0, 0, false>(acc1, q[0]);
      attn_pack<0, 1, false>(acc1, q[2]);
      attn_pack<8, 0, false>(acc1, k[1]);
      attn_pack<8, 1, false>(acc1, k[3]);
      {
        float x[8][2];
        uint32_t pp[8];
        const bool first = warp == 0 && gidx == 0;
#pragma unroll
        for (int hd = 0; hd < 2; hd++) {
#pragma unroll
          for (int j = 0; j < 4; j += 2) {
            float s0[4], s1[4], s2[4];
            attn_qk(s2, q[j], q[j + 1], k[j + 2], 4 * hd);
            attn_qk(s1, q[j], q[j + 1], k[j + 1], 4 * hd);
            attn_qk(s0, q[j], q[j + 1], k[j], 4 * hd);
            if (j == 0 && first) s0[0] = s0[1] = -1e9f / 0.17677669529663687f;
            x[2 * j + hd][0] = le0 ? s1[0] : s0[0];
            x[2 * j + hd][1] = le1 ? s1[1] : s0[1];
            x[2 * j + 2 + hd][0] = le0 ? s2[2] : s1[2];
            x[2 * j + 2 + hd][1] = le1 ? s2[3] : s1[3];
          }
        }
        PROFA(40, __float_as_uint(x[1][0] + x[7][1]));
        attn_pack<16, 0, true>(acc1, vt[1]);
        attn_pack<16, 1, true>(acc1, vt[3]);
        quad_softmax<8>(x, pp);
        PROFA(41, pp[1] + pp[7]);
        ldsm4(a1[0], sb + OFF_T32 + (warp & 3) * 1024 + lane * 16);
        ldsm4(a1[1], sb + OFF_T32 + 512 + (warp & 3) * 1024 + lane * 16);
        const uint32_t obase = sb + OFF_OP + (warp * 32 + lr) * 128;
#pragma unroll
        for (int n = 0; n < 8; n++) {
          const uint32_t dst = obase + (n >> 1) * 1024 + (((4 * (n & 1) + lm) ^ lr) << 4);
          if (n & 2) attn_pv<true>(dst, vt[n >> 1], vt[(n >> 1) + 1], 4 * (n & 1), pp[n], maskLE);
          else attn_pv<false>(dst, vt[n >> 1], vt[(n >> 1) + 1], 4 * (n & 1), pp[n], maskLE);
        }
      }
      PROFA(42, 0);
    }

    {
      const int w = warp & 3;
      const int lr = lane & 7, lm = lane >> 3;
      const uint32_t xb = sb + OFF_X + wg * 4 * XT;
      auto uo = [](int c) { return (c & 1) * 2 * XT + (c >> 1) * 2048; };
      const uint64_t dc2 = mkdesc(sb + OFF_T16, 512, 128, 0), dc3 = mkdesc(sb + OFF_T16, 128, 512, 0);
      const uint64_t dc4 = mkdesc(sb + OFF_T32, 128, 256, 0);
      const uint64_t dx = mkdesc(xb, 4096, 512, 2), dz = mkdesc(xb, 4096, 256, 3);
      const uint32_t zs = xb + (w * 16 + (lm & 1) * 8 + lr) * 32 + (((lm >> 1) ^ (lr >> 2)) << 4);
      const uint32_t ys = xb + w * 4096 + (lm >> 1) * 256 + ((lr * 32 + (((lm & 1) ^ (lr >> 2)) << 4)) ^ (rank << 6) ^ ((w & 2) << 4));
      const bool own = (w & 1) == rank;
      const uint32_t ybar = mapa(bars, own ? rank ^ 1 : rank) + 8 * BAR_Y;
      uint32_t d[2][32], pa[2][4][2][4], e[4][4][8], ya[2][2][2][4], v[2][2][8];
      C2 s1[2][2][2];
      float o[2][16];
      auto rows = [&](int c) {
        fft_rows(d[c & 1], a1, dx + (uo(c) >> 4));
        wg_commit();
      };
      auto cols = [&](int c) {
        const int s = c & 1;
        fence_regs(d[s]);
#pragma unroll
        for (int i = 0; i < 16; i++) {
          const C2 z = crot(C2{d[s][2 * i], d[s][2 * i + 1]}, t[i & 1]);
          pa[s][i >> 2][i & 1][(i >> 1) & 1] = z.r;
          pa[s][i >> 2][i & 1][2 + ((i >> 1) & 1)] = z.i;
        }
        wg_fence();
#pragma unroll
        for (int i = 0; i < 4; i++) fft_cols<0>(e[c][i], pa[s][i], dc2);
        wg_commit();
      };
      auto prod = [&](int c, int n) {
        const int s = c & 1;
        fence_regs(e[c][2 * n]);
        fence_regs(e[c][2 * n + 1]);
#pragma unroll
        for (int j = 0; j < 2; j++) {
          const C2 u0 = cget(e[s][2 * n], j, 0), u1 = cget(e[s][2 * n], j, 1);
          const C2 h0 = cget(e[s][2 * n + 1], j, 0), h1 = cget(e[s][2 * n + 1], j, 1);
          C2 y0, y1;
          if (c < 2) {
            y0 = cmul(h0, u0);
            s1[s][n][j] = cfma(h0, u1, cmul(h1, u0));
            y1 = C2{hadd2(s1[s][n][j].r, y0.i), hadd2(s1[s][n][j].i, hneg2(y0.r))};
          } else {
            const C2 u2 = cget(e[c][2 * n], j, 0), u3 = cget(e[c][2 * n], j, 1);
            const C2 h2 = cget(e[c][2 * n + 1], j, 0), h3 = cget(e[c][2 * n + 1], j, 1);
            const C2 s2 = cfma(h0, u2, cfma(h2, u0, cmul(h1, u1)));
            y0 = C2{hadd2(s2.r, s1[s][n][j].i), hadd2(s2.i, hneg2(s1[s][n][j].r))};
            y1 = cfma(h0, u3, cfma(h1, u2, cfma(h2, u1, cfma(h3, u0, C2{s2.i, hneg2(s2.r)}))));
          }
          ya[s][n][j][0] = y0.r;
          ya[s][n][j][1] = y1.r;
          ya[s][n][j][2] = y0.i;
          ya[s][n][j][3] = y1.i;
        }
      };
      auto icols = [&](int c) {
        wg_fence();
        fft_cols<1>(v[c & 1][0], ya[c & 1][0], dc3);
        fft_cols<1>(v[c & 1][1], ya[c & 1][1], dc3);
        wg_commit();
      };
      auto stage = [&](int c) {
        const int s = c & 1;
        fence_regs(v[s][0]);
        fence_regs(v[s][1]);
#pragma unroll
        for (int b = 0; b < 4; b++) {
          const C2 x0 = cget(v[s][b >> 1], 0, b & 1), x1 = cget(v[s][b >> 1], 1, b & 1);
          const C2 z0 = crot(C2{x0.i, x0.r}, t[0]), z1 = crot(C2{x1.i, x1.r}, t[1]);
          stsm4(zs + uo(c) + b * 4096, z0.i, z0.r, z1.i, z1.r);
        }
      };
      auto back = [&](int c) {
        fft_back(o[c & 1], dz + (uo(c) >> 4), dc4);
        wg_commit();
      };
      auto out = [&](int c) {
        float (&r)[16] = o[c & 1];
        fence_regs(r);
#pragma unroll
        for (int i = 0; i < 16; i += 8)
          stsm4t(ys + uo(c) + 64 * i, bmul2(pack_bf16(r[i], r[i + 1]), sc[c & 1]), bmul2(pack_bf16(r[i + 2], r[i + 3]), sc[c & 1]),
                 bmul2(pack_bf16(r[i + 4], r[i + 5]), sc[c & 1]), bmul2(pack_bf16(r[i + 6], r[i + 7]), sc[c & 1]));
      };
      auto signal = [&](int yb, int land) {
        __syncwarp();
        if (lane == 0) {
          mbar_arrive_cluster(ybar + 8 * yb);
          if (own && land >= 0) mbar_arrive(bars + 8 * (BAR_LAND + land));
        }
      };
      mbar_wait(bars + 8 * BAR_X, 0);
      wg_fence();
      rows(0);
      rows(1);
      fence_async_smem();
      nb_arrive(NB_OREADY, 288);
#pragma unroll
      for (int i = 0; i < 2; i++) {
        const uint32_t ex = sb + OFF_EX + wg * 16 + (w & 2) * 2 + 8 * i;
        sc[i] = min(max(381 - (int)lds32(ex) - (int)lds32(ex + 32), 1), 254) * 0x00800080u;
      }
      PROF(34 + wg);
      wg_wait<1>();
      cols(0);
      wg_wait<1>();
      cols(1);
      rows(2);
      nb_sync(NB_CONV + wg, 128);
      wg_wait<2>();
      prod(0, 0);
      prod(0, 1);
      icols(0);
      wg_wait<2>();
      prod(1, 0);
      prod(1, 1);
      icols(1);
      PROF3(40 + 10 * wg);
      wg_wait<1>();
      stage(0);
      wg_wait<0>();
      stage(1);
      fence_async_smem();
      cols(2);
      PROF3(41 + 10 * wg);
      nb_sync(NB_CONV + wg, 128);
      back(0);
      back(1);
      wg_wait<2>();
      prod(2, 0);
      wg_fence();
      rows(3);
      wg_wait<1>();
      out(0);
      out(1);
      signal(wg, 0);
      PROF3(42 + 10 * wg);
      prod(2, 1);
      icols(2);
      wg_wait<1>();
      cols(3);
      PROF3(43 + 10 * wg);
      wg_wait<1>();
      stage(2);
      fence_async_smem();
      wg_wait<0>();
      prod(3, 0);
      nb_sync(NB_CONV + wg, 128);
      wg_fence();
      back(2);
      prod(3, 1);
      icols(3);
      PROF3(44 + 10 * wg);
      wg_wait<1>();
      out(2);
      signal(2, -1);
      wg_wait<0>();
      stage(3);
      PROF3(45 + 10 * wg);
      fence_async_smem();
      nb_sync(NB_FIRST, 256);
      wg_fence();
      back(3);
      constexpr int G = MODE == 0;
      if (G) {
        mbar_wait(bars + 8 * (BAR_EMPTY2 + 4), 0);
        g2_block(true, 0, 0);
      }
      wg_wait<G>();
      if (lane == 0) mbar_arrive_cluster(mapa(bars, 1) + 8 * BAR_TAB);
      out(3);
      signal(3, 1);
      PROF(6 + wg);
    }
    }

    if (MODE != 1) {
      if (MODE == 2) g2_block(true, 0, 0);
      const int lr = lane & 7, lm = lane >> 3;
      const uint32_t wb = sb + g2_a(1, 0) + warp * 2048;
      const int orow = (rb2 & 7) * 128 + warp * 16;
      uint4* og = reinterpret_cast<uint4*>(p.out + (size_t)(2 * (orow + lm) + (rb2 >> 3)) * (2 * DM) + DM + cb2 * 128 + lr * 8);
      uint32_t wst = wb + (lr + 8 * (lm & 1)) * 128, wsx = ((lm >> 1) ^ lr) << 4, wld = wb + lm * 128, wlx = (lr ^ lm) << 4;
      asm volatile("" : "+l"(og), "+r"(wst), "+r"(wsx), "+r"(wld), "+r"(wlx));
#pragma unroll 1
      for (int r = 0; r < 3; r++) {
        const bool hold = r == 2 && wg != LEADWG;
        if (hold) {
          wg_wait<0>();
          if (signaller) mbar_arrive_cluster(g2rel);
          nb_sync(NB_LEAD, 256);
        }
#pragma unroll
        for (int i = 1; i <= NS2; i++) {
          g2_block(false, i % NS2, (r & 1) ^ (i == NS2));
          if (warp == LEADWG * 4) PROF2(40 + 5 * r + i);
          if (i == 1 ? !hold : r < 2) {
            wg_wait<1>();
            if (signaller) mbar_arrive_cluster(g2rel + 8 * (i - 1));
          }
        }
        if (r == 0) PROF(8 + wg);
        g2a += p.zero;
        g2b += p.zero;
      }
      if (wg == LEADWG) nb_arrive(NB_LEAD, 256);
      asm volatile("barrier.cluster.arrive.relaxed.aligned;\n" ::: "memory");
      wg_wait<0>();
      fence_regs(acc);
      PROF(10 + wg);
#pragma unroll
      for (int h = 0; h < 2; h++) {
        const uint32_t b = h * (g2_a(3, 0) - g2_a(1, 0));
#pragma unroll
        for (int j = 8 * h; j < 8 * h + 8; j += 2)
          stsm4(wst + b + (wsx ^ ((j & 7) << 4)), pack_bf16(acc[4 * j], acc[4 * j + 1]),
                pack_bf16(acc[4 * j + 2], acc[4 * j + 3]), pack_bf16(acc[4 * j + 4], acc[4 * j + 5]),
                pack_bf16(acc[4 * j + 6], acc[4 * j + 7]));
        if (wg == LEADWG) {
          fence_async_smem();
          __syncwarp();
          if (elect_one()) {
            tma_store_3d(&tmOb, wb + b, DM + cb2 * 128 + h * 64, rb2 >> 3, orow);
            bulk_commit();
          }
        } else {
          __syncwarp();
          uint4 v[4];
#pragma unroll
          for (int i = 0; i < 4; i++) v[i] = lds128(wld + b + i * 512 + (wlx ^ ((i & 1) << 6)));
#pragma unroll
          for (int i = 0; i < 4; i++)
            asm volatile("st.global.v4.u32 [%0], {%1,%2,%3,%4};\n" ::"l"(og + i * 8 * (2 * DM / 8) + h * 8), "r"(v[i].x),
                         "r"(v[i].y), "r"(v[i].z), "r"(v[i].w) : "memory");
        }
      }
      PROF(12 + wg);
      bulk_wait0();
    } else {
      asm volatile("barrier.cluster.arrive.relaxed.aligned;\n" ::: "memory");
    }
    asm volatile("barrier.cluster.wait.aligned;\n" ::: "memory");
  }
}

typedef CUresult (*EncodeFn)(CUtensorMap*, CUtensorMapDataType, cuuint32_t, void*, const cuuint64_t*, const cuuint64_t*,
                             const cuuint32_t*, const cuuint32_t*, CUtensorMapInterleave, CUtensorMapSwizzle,
                             CUtensorMapL2promotion, CUtensorMapFloatOOBfill);

void make_map(EncodeFn enc, CUtensorMap* tm, const void* base, int rank, const cuuint64_t* dims, const cuuint64_t* strides,
              const cuuint32_t* box, CUtensorMapSwizzle swz) {
  cuuint32_t es[5] = {1, 1, 1, 1, 1};
  enc(tm, CU_TENSOR_MAP_DATA_TYPE_BFLOAT16, rank, const_cast<void*>(base), dims, strides, box, es,
      CU_TENSOR_MAP_INTERLEAVE_NONE, swz, CU_TENSOR_MAP_L2_PROMOTION_L2_256B, CU_TENSOR_MAP_FLOAT_OOB_FILL_NONE);
}

}

extern "C" void kernel_launch(void* const* d_in, const int* in_sizes, int n_in, void* d_out, int out_size) {
  static EncodeFn enc = nullptr;
  static bool coresident = true;
  if (!enc) {
    void* fn = nullptr;
    cudaDriverEntryPointQueryResult qr;
    cudaGetDriverEntryPoint("cuTensorMapEncodeTiled", &fn, cudaEnableDefault, &qr);
    enc = (EncodeFn)fn;
    cudaFuncSetAttribute(fused_kernel<0>, cudaFuncAttributeMaxDynamicSharedMemorySize, SMEM_BYTES);
    cudaFuncSetAttribute(fused_kernel<1>, cudaFuncAttributeMaxDynamicSharedMemorySize, SMEM_BYTES);
    cudaFuncSetAttribute(fused_kernel<2>, cudaFuncAttributeMaxDynamicSharedMemorySize, SMEM_BYTES);
    cudaLaunchConfig_t cfg = {};
    cfg.gridDim = dim3(NCTA);
    cfg.blockDim = dim3(NTHREADS);
    cfg.dynamicSmemBytes = SMEM_BYTES;
    cudaLaunchAttribute at;
    at.id = cudaLaunchAttributeClusterDimension;
    at.val.clusterDim.x = 2;
    at.val.clusterDim.y = 1;
    at.val.clusterDim.z = 1;
    cfg.attrs = &at;
    cfg.numAttrs = 1;
    int nclusters = 0;
    if (cudaOccupancyMaxActiveClusters(&nclusters, fused_kernel<0>, &cfg) == cudaSuccess) coresident = nclusters >= NCTA / 2;
    (void)cudaGetLastError();
  }
  CUtensorMap tmX, tmW, tmWo, tmWp, tmQ, tmOb, tmXh, tmWh;
  {
    cuuint64_t dims[3] = {1024, 2, 1024};
    cuuint64_t str[2] = {2048, 4096};
    cuuint32_t box[3] = {64, 1, 128};
    make_map(enc, &tmX, d_in[6], 3, dims, str, box, CU_TENSOR_MAP_SWIZZLE_128B);
  }
  {
    cuuint64_t dims[3] = {1024, 1024, 3};
    cuuint64_t str[2] = {6144, 2048};
    cuuint32_t box[3] = {64, 32, 3};
    make_map(enc, &tmW, d_in[7], 3, dims, str, box, CU_TENSOR_MAP_SWIZZLE_128B);
  }
  {
    cuuint64_t dims[3] = {64, 1024, 16};
    cuuint64_t str[2] = {2048, 128};
    cuuint32_t box[3] = {64, 64, 2};
    cuuint32_t piece[3] = {64, 32, 1};
    make_map(enc, &tmWo, d_in[8], 3, dims, str, box, CU_TENSOR_MAP_SWIZZLE_128B);
    make_map(enc, &tmWp, d_in[8], 3, dims, str, piece, CU_TENSOR_MAP_SWIZZLE_128B);
  }
  {
    cuuint64_t dims[5] = {1024, 2, 2, 4, 128};
    cuuint64_t str[4] = {2048, 8 * 2048, 2 * 2048, 16 * 2048};
    cuuint32_t box[5] = {16, 2, 2, 4, 32};
    make_map(enc, &tmQ, d_in[0], 5, dims, str, box, CU_TENSOR_MAP_SWIZZLE_NONE);
  }
  {
    cuuint64_t dims[3] = {2048, 2, 1024};
    cuuint64_t str[2] = {4096, 8192};
    cuuint32_t box[3] = {64, 1, 16};
    make_map(enc, &tmOb, d_out, 3, dims, str, box, CU_TENSOR_MAP_SWIZZLE_128B);
  }
  {
    cuuint64_t dims[4] = {1024, 256, 2, 4};
    cuuint64_t str[3] = {4096, 2048, 256 * 4096};
    cuuint32_t box[4] = {64, 8, 2, 3};
    make_map(enc, &tmXh, d_in[6], 4, dims, str, box, CU_TENSOR_MAP_SWIZZLE_128B);
  }
  {
    cuuint64_t dims[3] = {64, 1024, 48};
    cuuint64_t str[2] = {6144, 128};
    cuuint32_t box[3] = {64, 64, 4};
    make_map(enc, &tmWh, d_in[7], 3, dims, str, box, CU_TENSOR_MAP_SWIZZLE_128B);
  }
  Params p;
  p.q = (const __nv_bfloat16*)d_in[0];
  p.k = (const __nv_bfloat16*)d_in[1];
  p.v = (const __nv_bfloat16*)d_in[2];
  p.shift_k = (const __nv_bfloat16*)d_in[3];
  p.ssm_k = (const __nv_bfloat16*)d_in[4];
  p.ssm_D = (const __nv_bfloat16*)d_in[5];
  p.x = (const __nv_bfloat16*)d_in[6];
  p.w = (const __nv_bfloat16*)d_in[7];
  p.wo = (const __nv_bfloat16*)d_in[8];
  p.out = (__nv_bfloat16*)d_out;
  p.zero = 0;
  for (int cl = 0; cl < 72; cl++) {
    const int t = cl - 4, u = t - 32;
    const bool lo = t >= 0 && t < 32, mid = u >= 0 && u < 28;
    const int grp = lo ? t & 7 : mid ? 1 + u % 7 : 0, mem = lo ? t >> 3 : mid ? 4 + u / 7 : t < 0 ? t + 6 : t - 54;
    p.tile[cl] = (uint8_t)((((grp >> 2) * 4 + (mem >> 1)) * 8 + (grp & 3) * 2 + (mem & 1)) & 63);
  }
  if (coresident) {
    fused_kernel<0><<<NCTA, NTHREADS, SMEM_BYTES>>>(p, tmX, tmW, tmWo, tmWp, tmQ, tmOb, tmXh, tmWh);
  } else {
    fused_kernel<0><<<4, NTHREADS, SMEM_BYTES>>>(p, tmX, tmW, tmWo, tmWp, tmQ, tmOb, tmXh, tmWh);
    fused_kernel<1><<<NCTA, NTHREADS, SMEM_BYTES>>>(p, tmX, tmW, tmWo, tmWp, tmQ, tmOb, tmXh, tmWh);
    fused_kernel<2><<<NCTA, NTHREADS, SMEM_BYTES>>>(p, tmX, tmW, tmWo, tmWp, tmQ, tmOb, tmXh, tmWh);
  }
}
```
